```python
import torch

def _softmax(x, axis=-1):
    return torch.softmax(x, dim=axis)
def _gelu(x):
    return torch.nn.functional.gelu(x, approximate="tanh")
def _silu(x):
    return torch.nn.functional.silu(x)
def _sigmoid(x):
    return torch.sigmoid(x)
def _layernorm(x, axis=-1, eps=1e-5):
    m = x.mean(dim=axis, keepdim=True)
    v = x.var(dim=axis, keepdim=True, unbiased=False)
    return (x - m) / torch.sqrt(v + eps)
def _scatter_add(tgt, idx, src, axis=0):
    return tgt.clone().index_add_(axis, idx, src)
def _segment_sum(src, seg, n):
    out = torch.zeros((n,) + src.shape[1:], dtype=src.dtype)
    return out.index_add_(0, seg, src)
def _pad(x, pw):
    flat = tuple(v for pair in reversed(pw) for v in pair)
    return torch.nn.functional.pad(x, flat)

kernel_name = 'sequential_preLN__ssm_conv_s4d__moe_arch_mod__prompt'

def setup_inputs():

    _w = (lambda a: (lambda t: t.to(torch.bfloat16) if t.is_floating_point() else t)(torch.as_tensor(a)))
    def _A_setup():
        Bsz, L, D, N = 1, 2048, 576, 128
        return {
            "u": _w((lambda *s: torch.randn(*s, dtype=torch.bfloat16) * 0.2)(Bsz, L, D)),
            "log_A_real": _w((lambda *s: torch.randn(*s, dtype=torch.bfloat16) * 6.4)(D, N) * 0.5),
            "A_imag": _w((lambda *s: torch.randn(*s, dtype=torch.bfloat16) * 0.2)(D, N) * 3.14),
            "C_real": _w((lambda *s: torch.randn(*s, dtype=torch.bfloat16) * 0.2)(D, N) / N ** 0.5),
            "C_imag": _w((lambda *s: torch.randn(*s, dtype=torch.bfloat16) * 0.2)(D, N) / N ** 0.5),
            "log_dt": _w((lambda *s: torch.randn(*s, dtype=torch.bfloat16) * 0.2)(D) * 0.5 - 4.0),
            "D_skip": _w((lambda *s: torch.randn(*s, dtype=torch.bfloat16) * 0.2)(D)),
        }
    _A_in = _A_setup()

    def _B_setup():
        B, S, D, F, C = 1, 2048, 576, 4608, 8
        return {
            "x": _w((lambda *s: torch.randn(*s, dtype=torch.bfloat16) * 0.2)(B, S, D)),
            "w_r": _w((lambda *s: torch.randn(*s, dtype=torch.bfloat16) * 0.2)(D)),
            "w_gate": _w((lambda *s: torch.randn(*s, dtype=torch.bfloat16) * 0.2)(D, F)),
            "w_up": _w((lambda *s: torch.randn(*s, dtype=torch.bfloat16) * 0.2)(D, F)),
            "w_down": _w((lambda *s: torch.randn(*s, dtype=torch.bfloat16) * 0.2)(F, D)),
        }
    _B_in = _B_setup()

    return {
        "A_u": _A_in["u"],
        "A_log_A_real": _A_in["log_A_real"],
        "A_A_imag": _A_in["A_imag"],
        "A_C_real": _A_in["C_real"],
        "A_C_imag": _A_in["C_imag"],
        "A_log_dt": _A_in["log_dt"],
        "A_D_skip": _A_in["D_skip"],
        "B_x": _B_in["x"],
        "B_w_r": _B_in["w_r"],
        "B_w_gate": _B_in["w_gate"],
        "B_w_up": _B_in["w_up"],
        "B_w_down": _B_in["w_down"],
    }

def reference(A_u, A_log_A_real, A_A_imag, A_C_real, A_C_imag, A_log_dt, A_D_skip, B_x, B_w_r, B_w_gate, B_w_up, B_w_down):
    def _A_ref(u, log_A_real, A_imag, C_real, C_imag, log_dt, D_skip):
        L = u.shape[1]
        dt = torch.exp(log_dt)
        A = -torch.exp(log_A_real) + 1j * A_imag
        C = (C_real + 1j * C_imag) * dt[:, None]
        pos = (lambda x, dt: x.to(dt))(torch.arange(L), log_dt.dtype)
        P = torch.exp((A * dt[:, None])[:, :, None] * pos[None, None, :])
        K = 2.0 * torch.einsum("dn,dnl->dl", C, P).real
        L2 = 2 * L
        u_t = (lambda x, *d: x.permute(*d))(u, 0, 2, 1)
        Kf = (lambda x, *a, **k: torch.fft.rfft(x.float(), *a, **k))(K, L2)
        Uf = (lambda x, *a, **k: torch.fft.rfft(x.float(), *a, **k))(u_t, L2)
        y = (lambda x, *a, **k: torch.fft.irfft(x, *a, **k).to(torch.bfloat16))(Uf * Kf[None, :, :], L2)[:, :, :L]
        y = (lambda x, *d: x.permute(*d))(y, 0, 2, 1)
        return y + u * D_skip[None, None, :]

    def _B_ref(x, w_r, w_gate, w_up, w_down):
        B, S, D = x.shape
        C = 8
        r = x @ w_r
        idx = torch.argsort(-r, axis=-1)[:, :C]
        idx_e = (lambda x, n, axis: torch.repeat_interleave(x, n, dim=axis))(idx.reshape(B, C, 1), D, axis=2)
        x_sel = (lambda x, i, axis: torch.take_along_dim(x, i, dim=axis))(x, idx_e, axis=1)
        g = _silu(x_sel @ w_gate)
        u = x_sel @ w_up
        y = (g * u) @ w_down
        r_sel = _sigmoid((lambda x, i, axis: torch.take_along_dim(x, i, dim=axis))(r, idx, axis=1))
        y = y * r_sel.reshape(B, C, 1)
        b_off = (torch.arange(B) * S).reshape(B, 1)
        flat_idx = (idx + b_off).reshape(B * C)
        zero = (x * 0.0).reshape(B * S, D)
        upd = _scatter_add(zero, flat_idx, y.reshape(B * C, D), axis=0)
        return x + upd.reshape(B, S, D)

    x = A_u
    h = x + _A_ref(_layernorm(x, axis=-1), A_log_A_real, A_A_imag, A_C_real, A_C_imag, A_log_dt, A_D_skip)
    h2 = h + _B_ref(_layernorm(h, axis=-1), B_w_r, B_w_gate, B_w_up, B_w_down)
    return h2
```

```cpp
#include <cuda_runtime.h>
#include <cuda.h>
#include <cuda_fp16.h>
#include <cuda_bf16.h>
#include <stdint.h>

#define LSEQ 2048
#define DM 576
#define NST 128
#define FF 4608
#define NSEL 8
#define NCTA 128
#define NTHR 640
#define NWRK 640

typedef __nv_bfloat16 bf16;

#define SM_WG 0
#define SM_WU 41472
#define SM_XC (82944 - 32768)
#define SM_WD 82944
#define W_PITCH 144
#define WD_PITCH 592
#define SM_XT (SM_PL - 18 * 1152)
#define SM_PL (SM_WD + 46080)
#define PL_HALF 1344
#define PLW_B 2624
#define PL_B (4 * PLW_B)
#define SM_U (SM_PL + 5 * PL_B)
#define UPAD 20
#define ULO_B ((UPAD + 128) * 16)
#define USLOT_B (2 * ULO_B)
#define SM_ZERO (SM_U + 4 * USLOT_B + 128)
#define SM_KW (SM_U + 5 * USLOT_B)
#define KW_B 3712
#define KW_PL 1216
#define KW_P 2400
#define KW_H 3440
#define SM_MISC (SM_KW + 5 * KW_B)
#define SM_LC (SM_MISC + 384)
#define SM_LNP (SM_LC + 768)
#define SM_RX (SM_LNP + 3840)
#define SMEM_TOTAL (SM_RX + 3088)
#define YKEY 0xffc1ffc1u
#define TBP 112
#define TBW (32 * TBP)
#define SM_OUT SM_PL
#define SM_XS (SM_PL + 18432)
#define XS_PITCH 592
#define SM_GU (SM_PL + 23296)
#define SM_EX (SM_PL + 24576)
#define SM_FS (SM_PL + 43008)
#define SM_CAND SM_KW

struct __align__(128) Scratch {
    unsigned hint[8 * 32];
    unsigned flag[32];
    unsigned short sc[LSEQ];
    uint32_t stat[LSEQ];
    uint32_t uT[64 * (LSEQ / 2)];
    uint32_t y[NCTA * DM * 8];
    uint32_t part[72 * 64 * 64];
    uint32_t rows[(2 * NCTA + NSEL) * DM];
};
__device__ Scratch g_scratch;
#define STAMP(i)
#define STAMPX(i)

__device__ __forceinline__ float rbf(float x) {
    uint32_t r;
    asm("cvt.rn.bf16x2.f32 %0, %1, %2;\n" : "=r"(r) : "f"(x), "f"(0.f));
    return __uint_as_float(r & 0xffff0000u);
}
__device__ __forceinline__ uint32_t pack_bf16(float lo, float hi) {
    uint32_t r;
    asm("cvt.rn.bf16x2.f32 %0, %1, %2;\n" : "=r"(r) : "f"(hi), "f"(lo));
    return r;
}
__device__ __forceinline__ uint32_t pack_f16(float lo, float hi) {
    uint32_t r;
    asm("cvt.rn.f16x2.f32 %0, %1, %2;\n" : "=r"(r) : "f"(hi), "f"(lo));
    return r;
}
__device__ __forceinline__ uint32_t pack_f16_rz(float lo, float hi) {
    uint32_t r;
    asm("cvt.rz.f16x2.f32 %0, %1, %2;\n" : "=r"(r) : "f"(hi), "f"(lo));
    return r;
}
__device__ __forceinline__ float bf_lo(uint32_t w) { return __uint_as_float(w << 16); }
__device__ __forceinline__ float bf_hi(uint32_t w) { return __uint_as_float(w & 0xffff0000u); }
__device__ __forceinline__ uint32_t hadd2_bf(uint32_t a, uint32_t b) {
    __nv_bfloat162 r = __hadd2_rn(*reinterpret_cast<__nv_bfloat162*>(&a), *reinterpret_cast<__nv_bfloat162*>(&b));
    return *reinterpret_cast<uint32_t*>(&r);
}
__device__ __forceinline__ uint32_t hsub2_bf(uint32_t a, uint32_t b) {
    __nv_bfloat162 r = __hsub2_rn(*reinterpret_cast<__nv_bfloat162*>(&a), *reinterpret_cast<__nv_bfloat162*>(&b));
    return *reinterpret_cast<uint32_t*>(&r);
}
__device__ __forceinline__ uint32_t hmul2_bf(uint32_t a, uint32_t b) {
    __nv_bfloat162 r = __hmul2_rn(*reinterpret_cast<__nv_bfloat162*>(&a), *reinterpret_cast<__nv_bfloat162*>(&b));
    return *reinterpret_cast<uint32_t*>(&r);
}
__device__ __forceinline__ uint32_t hfma2_bf(uint32_t a, uint32_t b, uint32_t c) { uint32_t r; asm("fma.rn.bf16x2 %0, %1, %2, %3;\n" : "=r"(r) : "r"(a), "r"(b), "r"(c)); return r; }
__device__ __forceinline__ uint32_t hmul2(uint32_t a, uint32_t b) { uint32_t r; asm("mul.rn.f16x2 %0, %1, %2;\n" : "=r"(r) : "r"(a), "r"(b)); return r; }
__device__ __forceinline__ uint32_t hadd2(uint32_t a, uint32_t b) { uint32_t r; asm("add.rn.f16x2 %0, %1, %2;\n" : "=r"(r) : "r"(a), "r"(b)); return r; }
__device__ __forceinline__ uint32_t hfma2(uint32_t a, uint32_t b, uint32_t c) { uint32_t r; asm("fma.rn.f16x2 %0, %1, %2, %3;\n" : "=r"(r) : "r"(a), "r"(b), "r"(c)); return r; }
__device__ __forceinline__ uint32_t hfms2(uint32_t a, uint32_t b, uint32_t c) {
    uint32_t r;
    asm("{\n.reg .b32 n;\nneg.f16x2 n, %2;\nfma.rn.f16x2 %0, %1, n, %3;\n}\n" : "=r"(r) : "r"(a), "r"(b), "r"(c));
    return r;
}
__device__ __forceinline__ uint32_t nzw(uint32_t w) { return w ? w : 0x8000u; }
__device__ __forceinline__ uint32_t nzf(float f) { const uint32_t w = __float_as_uint(f); return w ? w : 0x80000000u; }
__device__ __forceinline__ uint32_t smem_u32(const void* p) { return (uint32_t)__cvta_generic_to_shared(p); }
__device__ __forceinline__ uint32_t lds32(uint32_t addr) {
    uint32_t v;
    asm volatile("ld.shared.u32 %0, [%1];\n" : "=r"(v) : "r"(addr) : "memory");
    return v;
}
__device__ __forceinline__ uint32_t lds16(uint32_t addr) {
    unsigned short v;
    asm volatile("ld.shared.u16 %0, [%1];\n" : "=h"(v) : "r"(addr) : "memory");
    return v;
}
__device__ __forceinline__ uint2 lds64(uint32_t addr) {
    uint2 v;
    asm volatile("ld.shared.v2.u32 {%0,%1}, [%2];\n" : "=r"(v.x), "=r"(v.y) : "r"(addr) : "memory");
    return v;
}
__device__ __forceinline__ uint4 lds128(uint32_t addr) {
    uint4 v;
    asm volatile("ld.shared.v4.u32 {%0,%1,%2,%3}, [%4];\n" : "=r"(v.x), "=r"(v.y), "=r"(v.z), "=r"(v.w) : "r"(addr) : "memory");
    return v;
}
__device__ __forceinline__ float ldsf(uint32_t addr) { return __uint_as_float(lds32(addr)); }
__device__ __forceinline__ void sts32(uint32_t addr, uint32_t v) { asm volatile("st.shared.u32 [%0], %1;\n" ::"r"(addr), "r"(v) : "memory"); }
__device__ __forceinline__ void sts16(uint32_t addr, uint32_t v) { asm volatile("st.shared.u16 [%0], %1;\n" ::"r"(addr), "h"((unsigned short)v) : "memory"); }
__device__ __forceinline__ void stsf(uint32_t addr, float v) { sts32(addr, __float_as_uint(v)); }
__device__ __forceinline__ void sts64(uint32_t addr, uint32_t a, uint32_t b) { asm volatile("st.shared.v2.u32 [%0], {%1,%2};\n" ::"r"(addr), "r"(a), "r"(b) : "memory"); }
__device__ __forceinline__ void sts64f(uint32_t addr, float a, float b) { sts64(addr, __float_as_uint(a), __float_as_uint(b)); }
__device__ __forceinline__ void sts128(uint32_t addr, uint32_t a, uint32_t b, uint32_t c, uint32_t d) {
    asm volatile("st.shared.v4.u32 [%0], {%1,%2,%3,%4};\n" ::"r"(addr), "r"(a), "r"(b), "r"(c), "r"(d) : "memory");
}
__device__ __forceinline__ void sts128f(uint32_t addr, const float (&v)[4]) {
    sts128(addr, __float_as_uint(v[0]), __float_as_uint(v[1]), __float_as_uint(v[2]), __float_as_uint(v[3]));
}
__device__ __forceinline__ void ldsm_x4(uint32_t& r0, uint32_t& r1, uint32_t& r2, uint32_t& r3, uint32_t addr) {
    asm volatile("ldmatrix.sync.aligned.m8n8.x4.shared.b16 {%0,%1,%2,%3}, [%4];\n"
                 : "=r"(r0), "=r"(r1), "=r"(r2), "=r"(r3) : "r"(addr) : "memory");
}
__device__ __forceinline__ void ldsm_x4_t(uint32_t& r0, uint32_t& r1, uint32_t& r2, uint32_t& r3, uint32_t addr) {
    asm volatile("ldmatrix.sync.aligned.m8n8.x4.trans.shared.b16 {%0,%1,%2,%3}, [%4];\n"
                 : "=r"(r0), "=r"(r1), "=r"(r2), "=r"(r3) : "r"(addr) : "memory");
}
__device__ __forceinline__ void ldsm_x2_t(uint32_t& r0, uint32_t& r1, uint32_t addr) {
    asm volatile("ldmatrix.sync.aligned.m8n8.x2.trans.shared.b16 {%0,%1}, [%2];\n" : "=r"(r0), "=r"(r1) : "r"(addr) : "memory");
}
__device__ __forceinline__ void ldsm_x1_t(uint32_t& r0, uint32_t addr) {
    asm volatile("ldmatrix.sync.aligned.m8n8.x1.trans.shared.b16 {%0}, [%1];\n" : "=r"(r0) : "r"(addr) : "memory");
}
__device__ __forceinline__ void stsm_x4(uint32_t addr, uint32_t r0, uint32_t r1, uint32_t r2, uint32_t r3) {
    asm volatile("stmatrix.sync.aligned.m8n8.x4.shared.b16 [%0], {%1,%2,%3,%4};\n" ::"r"(addr), "r"(r0), "r"(r1), "r"(r2), "r"(r3) : "memory");
}
__device__ __forceinline__ void stsm_x4_t(uint32_t addr, uint32_t r0, uint32_t r1, uint32_t r2, uint32_t r3) {
    asm volatile("stmatrix.sync.aligned.m8n8.x4.trans.shared.b16 [%0], {%1,%2,%3,%4};\n" ::"r"(addr), "r"(r0), "r"(r1), "r"(r2), "r"(r3) : "memory");
}
__device__ __forceinline__ uint32_t movm(uint32_t a) {
    uint32_t d;
    asm volatile("movmatrix.sync.aligned.m8n8.trans.b16 %0, %1;\n" : "=r"(d) : "r"(a));
    return d;
}
__device__ __forceinline__ void mma_f16(float (&c)[4], uint32_t a0, uint32_t a1, uint32_t a2, uint32_t a3, uint32_t b0, uint32_t b1) {
    asm volatile(
        "mma.sync.aligned.m16n8k16.row.col.f32.f16.f16.f32 {%0,%1,%2,%3}, {%4,%5,%6,%7}, {%8,%9}, {%0,%1,%2,%3};\n"
        : "+f"(c[0]), "+f"(c[1]), "+f"(c[2]), "+f"(c[3])
        : "r"(a0), "r"(a1), "r"(a2), "r"(a3), "r"(b0), "r"(b1));
}
__device__ __forceinline__ void mma_bf16(float (&c)[4], uint32_t a0, uint32_t a1, uint32_t a2, uint32_t a3, uint32_t b0, uint32_t b1) {
    asm volatile(
        "mma.sync.aligned.m16n8k16.row.col.f32.bf16.bf16.f32 {%0,%1,%2,%3}, {%4,%5,%6,%7}, {%8,%9}, {%0,%1,%2,%3};\n"
        : "+f"(c[0]), "+f"(c[1]), "+f"(c[2]), "+f"(c[3])
        : "r"(a0), "r"(a1), "r"(a2), "r"(a3), "r"(b0), "r"(b1));
}
__device__ __forceinline__ void mma_bf16_k8(float (&c)[4], uint32_t a0, uint32_t a1, uint32_t b0) {
    asm volatile("mma.sync.aligned.m16n8k8.row.col.f32.bf16.bf16.f32 {%0,%1,%2,%3}, {%4,%5}, {%6}, {%0,%1,%2,%3};\n"
                 : "+f"(c[0]), "+f"(c[1]), "+f"(c[2]), "+f"(c[3]) : "r"(a0), "r"(a1), "r"(b0));
}
__device__ __forceinline__ void bar_sync(int id, int n) { asm volatile("bar.sync %0, %1;\n" ::"r"(id), "r"(n) : "memory"); }
__device__ __forceinline__ void bar_arrive(int id, int n) { asm volatile("bar.arrive %0, %1;\n" ::"r"(id), "r"(n) : "memory"); }
__device__ __forceinline__ uint4 ld_poll(const void* p) {
    uint4 v;
    asm volatile("ld.relaxed.gpu.global.v4.u32 {%0,%1,%2,%3}, [%4];\n" : "=r"(v.x), "=r"(v.y), "=r"(v.z), "=r"(v.w) : "l"(p) : "memory");
    return v;
}
__device__ __forceinline__ uint2 ld_poll64(const void* p) {
    uint2 v;
    asm volatile("ld.relaxed.gpu.global.v2.u32 {%0,%1}, [%2];\n" : "=r"(v.x), "=r"(v.y) : "l"(p) : "memory");
    return v;
}
__device__ __forceinline__ uint32_t ld_poll32(const void* p) {
    uint32_t v;
    asm volatile("ld.relaxed.gpu.global.u32 %0, [%1];\n" : "=r"(v) : "l"(p) : "memory");
    return v;
}
__device__ __forceinline__ uint4 ldg128(const void* p) {
    uint4 v;
    asm volatile("ld.global.nc.v4.u32 {%0,%1,%2,%3}, [%4];\n" : "=r"(v.x), "=r"(v.y), "=r"(v.z), "=r"(v.w) : "l"(p));
    return v;
}
__device__ __forceinline__ uint2 ldg64(const void* p) {
    uint2 v;
    asm volatile("ld.global.nc.v2.u32 {%0,%1}, [%2];\n" : "=r"(v.x), "=r"(v.y) : "l"(p));
    return v;
}
__device__ __forceinline__ uint32_t ldg16(const void* p) {
    uint32_t v;
    asm volatile("ld.global.nc.u16 %0, [%1];\n" : "=r"(v) : "l"(p));
    return v;
}
__device__ __forceinline__ uint4 ldo128(const void* p) {
    uint4 v;
    asm volatile("ld.relaxed.cta.global.v4.u32 {%0,%1,%2,%3}, [%4];\n" : "=r"(v.x), "=r"(v.y), "=r"(v.z), "=r"(v.w) : "l"(p) : "memory");
    return v;
}
__device__ __forceinline__ uint2 ldo64(const void* p) {
    uint2 v;
    asm volatile("ld.relaxed.cta.global.v2.u32 {%0,%1}, [%2];\n" : "=r"(v.x), "=r"(v.y) : "l"(p) : "memory");
    return v;
}
__device__ __forceinline__ uint32_t ldo16(const void* p) {
    uint32_t v;
    asm volatile("ld.relaxed.cta.global.u16 %0, [%1];\n" : "=r"(v) : "l"(p) : "memory");
    return v;
}
__device__ __forceinline__ void stg128(void* p, uint32_t a, uint32_t b, uint32_t c, uint32_t d) {
    asm volatile("st.global.v4.u32 [%0], {%1,%2,%3,%4};\n" ::"l"(p), "r"(a), "r"(b), "r"(c), "r"(d) : "memory");
}
__device__ __forceinline__ void stg64(void* p, uint32_t a, uint32_t b) { asm volatile("st.global.v2.u32 [%0], {%1,%2};\n" ::"l"(p), "r"(a), "r"(b) : "memory"); }
__device__ __forceinline__ bool all_nz(const uint4& v) { return v.x && v.y && v.z && v.w; }
#define SPIN_LIMIT (1 << 21)
#define TRAP() __trap()
__device__ __forceinline__ void mbar_init(uint32_t bar, uint32_t cnt) { asm volatile("mbarrier.init.shared::cta.b64 [%0], %1;\n" ::"r"(bar), "r"(cnt) : "memory"); }
__device__ __forceinline__ void mbar_expect(uint32_t bar, uint32_t bytes) {
    asm volatile("mbarrier.arrive.expect_tx.shared::cta.b64 _, [%0], %1;\n" ::"r"(bar), "r"(bytes) : "memory");
}
__device__ __forceinline__ void mbar_arrive(uint32_t bar) { asm volatile("mbarrier.arrive.shared::cta.b64 _, [%0];\n" ::"r"(bar) : "memory"); }
__device__ __forceinline__ void mbar_wait_cluster(uint32_t bar) {
    asm volatile(
        "{\n.reg .pred p;\n"
        "W_%=:\n"
        "mbarrier.try_wait.parity.acquire.cluster.shared::cta.b64 p, [%0], 0;\n"
        "@!p bra W_%=;\n}\n" ::"r"(bar) : "memory");
}
__device__ __forceinline__ void mbar_wait(uint32_t bar) {
    asm volatile(
        "{\n.reg .pred p;\n"
        "W_%=:\n"
        "mbarrier.try_wait.parity.shared::cta.b64 p, [%0], 0;\n"
        "@!p bra W_%=;\n}\n" ::"r"(bar) : "memory");
}
__device__ __forceinline__ bool mbar_test(uint32_t bar) {
    uint32_t r;
    asm volatile("{\n.reg .pred p;\nmbarrier.test_wait.parity.shared::cta.b64 p, [%1], 0;\nselp.u32 %0, 1, 0, p;\n}\n" : "=r"(r) : "r"(bar) : "memory");
    return __any_sync(0xffffffffu, r);
}
__device__ __forceinline__ void bulk_g2s(uint32_t dst, const void* src, uint32_t bytes, uint32_t bar) {
    asm volatile("cp.async.bulk.shared::cluster.global.mbarrier::complete_tx::bytes [%0], [%1], %2, [%3];\n" ::"r"(dst), "l"(src), "r"(bytes), "r"(bar) : "memory");
}
__device__ __forceinline__ void bulk_s2g(void* dst, uint32_t src, uint32_t bytes) {
    asm volatile("cp.async.bulk.global.shared::cta.bulk_group [%0], [%1], %2;\ncp.async.bulk.commit_group;\n" ::"l"(dst), "r"(src), "r"(bytes) : "memory");
}
__device__ __forceinline__ void tma_2d(uint32_t dst, const CUtensorMap* tm, int c0, int c1, uint32_t bar) {
    asm volatile("cp.async.bulk.tensor.2d.shared::cluster.global.mbarrier::complete_tx::bytes [%0], [%1, {%3, %4}], [%2];\n"
                 ::"r"(dst), "l"(tm), "r"(bar), "r"(c0), "r"(c1) : "memory");
}
__device__ __forceinline__ void tma_4d(uint32_t dst, const CUtensorMap* tm, int c0, int c3, uint32_t bar) {
    asm volatile("cp.async.bulk.tensor.4d.shared::cluster.global.mbarrier::complete_tx::bytes [%0], [%1, {%3, %4, %4, %5}], [%2];\n"
                 ::"r"(dst), "l"(tm), "r"(bar), "r"(c0), "r"(0), "r"(c3) : "memory");
}
__device__ __forceinline__ void tma_4d_mc(uint32_t dst, const CUtensorMap* tm, int c0, int c3, uint32_t bar) {
    asm volatile("cp.async.bulk.tensor.4d.shared::cluster.global.mbarrier::complete_tx::bytes.multicast::cluster [%0], [%1, {%3, %4, %4, %5}], [%2], %6;\n"
                 ::"r"(dst), "l"(tm), "r"(bar), "r"(c0), "r"(0), "r"(c3), "h"((unsigned short)3) : "memory");
}
__device__ __forceinline__ void l2_prefetch(const void* src, uint32_t bytes) {
    asm volatile("cp.async.bulk.prefetch.L2.global [%0], %1;\n" ::"l"(src), "r"(bytes) : "memory");
}
__device__ __forceinline__ bool elect_one() {
    uint32_t r;
    asm volatile("{\n.reg .pred p;\nelect.sync _|p, 0xffffffff;\nselp.u32 %0, 1, 0, p;\n}\n" : "=r"(r));
    return r;
}
__device__ __forceinline__ void fence_async() { asm volatile("fence.proxy.async.shared::cta;\n" ::: "memory"); }

__device__ __forceinline__ float2 cmul(float2 a, float2 b) {
    return make_float2(fmaf(a.x, b.x, -a.y * b.y), fmaf(a.x, b.y, a.y * b.x));
}
__device__ __forceinline__ float2 csq(float2 a) {
    float p = a.x * a.y;
    return make_float2(fmaf(a.x, a.x, -a.y * a.y), p + p);
}
__device__ __forceinline__ float ex2_approx(float x) { float r; asm("ex2.approx.ftz.f32 %0, %1;\n" : "=f"(r) : "f"(x)); return r; }
__device__ __forceinline__ float exp_bf(float x) { return rbf(ex2_approx(__fmul_ru(x, 1.4426950408889634f))); }
__device__ __forceinline__ float2 cexp_e(float lr2, float li, float e) {
    const float m = ex2_approx(lr2 * e);
    return make_float2(m * __cosf(li * e), m * __sinf(li * e));
}
__device__ __forceinline__ float rcp_approx(float x) { float r; asm("rcp.approx.ftz.f32 %0, %1;\n" : "=f"(r) : "f"(x)); return r; }
__device__ __forceinline__ float sqrt_approx(float x) { float r; asm("sqrt.approx.f32 %0, %1;\n" : "=f"(r) : "f"(x)); return r; }

__device__ __forceinline__ void wg_fence() { asm volatile("wgmma.fence.sync.aligned;\n" ::: "memory"); }
__device__ __forceinline__ void wg_commit() { asm volatile("wgmma.commit_group.sync.aligned;\n" ::: "memory"); }
__device__ __forceinline__ void wg_wait0() { asm volatile("wgmma.wait_group.sync.aligned 0;\n" ::: "memory"); }
template <int T> __device__ __forceinline__ void wg_mma(float (&acc)[16][4], const uint32_t* a, uint64_t desc);
template <int T> __device__ __forceinline__ void wg_first(float (&acc)[16][4], const uint32_t* a, uint64_t desc);
template <> __device__ __forceinline__ void wg_mma<0>(float (&acc)[16][4], const uint32_t* a, uint64_t desc) {
    asm volatile("wgmma.mma_async.sync.aligned.m64n128k16.f32.f16.f16 {%0,%1,%2,%3,%4,%5,%6,%7,%8,%9,%10,%11,%12,%13,%14,%15,%16,%17,%18,%19,%20,%21,%22,%23,%24,%25,%26,%27,%28,%29,%30,%31,%32,%33,%34,%35,%36,%37,%38,%39,%40,%41,%42,%43,%44,%45,%46,%47,%48,%49,%50,%51,%52,%53,%54,%55,%56,%57,%58,%59,%60,%61,%62,%63}, {%64,%65,%66,%67}, %68, 1, 1, 1, 0;\n"
                 : "+f"(acc[0][0]), "+f"(acc[0][1]), "+f"(acc[0][2]), "+f"(acc[0][3]), "+f"(acc[1][0]), "+f"(acc[1][1]), "+f"(acc[1][2]), "+f"(acc[1][3]), "+f"(acc[2][0]), "+f"(acc[2][1]), "+f"(acc[2][2]), "+f"(acc[2][3]), "+f"(acc[3][0]), "+f"(acc[3][1]), "+f"(acc[3][2]), "+f"(acc[3][3]), "+f"(acc[4][0]), "+f"(acc[4][1]), "+f"(acc[4][2]), "+f"(acc[4][3]), "+f"(acc[5][0]), "+f"(acc[5][1]), "+f"(acc[5][2]), "+f"(acc[5][3]), "+f"(acc[6][0]), "+f"(acc[6][1]), "+f"(acc[6][2]), "+f"(acc[6][3]), "+f"(acc[7][0]), "+f"(acc[7][1]), "+f"(acc[7][2]), "+f"(acc[7][3]), "+f"(acc[8][0]), "+f"(acc[8][1]), "+f"(acc[8][2]), "+f"(acc[8][3]), "+f"(acc[9][0]), "+f"(acc[9][1]), "+f"(acc[9][2]), "+f"(acc[9][3]), "+f"(acc[10][0]), "+f"(acc[10][1]), "+f"(acc[10][2]), "+f"(acc[10][3]), "+f"(acc[11][0]), "+f"(acc[11][1]), "+f"(acc[11][2]), "+f"(acc[11][3]), "+f"(acc[12][0]), "+f"(acc[12][1]), "+f"(acc[12][2]), "+f"(acc[12][3]), "+f"(acc[13][0]), "+f"(acc[13][1]), "+f"(acc[13][2]), "+f"(acc[13][3]), "+f"(acc[14][0]), "+f"(acc[14][1]), "+f"(acc[14][2]), "+f"(acc[14][3]), "+f"(acc[15][0]), "+f"(acc[15][1]), "+f"(acc[15][2]), "+f"(acc[15][3])
                 : "r"(a[0]), "r"(a[1]), "r"(a[2]), "r"(a[3]), "l"(desc));
}
template <> __device__ __forceinline__ void wg_mma<2>(float (&acc)[16][4], const uint32_t* a, uint64_t desc) {
    asm volatile("wgmma.mma_async.sync.aligned.m64n112k16.f32.f16.f16 {%0,%1,%2,%3,%4,%5,%6,%7,%8,%9,%10,%11,%12,%13,%14,%15,%16,%17,%18,%19,%20,%21,%22,%23,%24,%25,%26,%27,%28,%29,%30,%31,%32,%33,%34,%35,%36,%37,%38,%39,%40,%41,%42,%43,%44,%45,%46,%47,%48,%49,%50,%51,%52,%53,%54,%55}, {%56,%57,%58,%59}, %60, 1, 1, 1, 0;\n"
                 : "+f"(acc[2][0]), "+f"(acc[2][1]), "+f"(acc[2][2]), "+f"(acc[2][3]), "+f"(acc[3][0]), "+f"(acc[3][1]), "+f"(acc[3][2]), "+f"(acc[3][3]), "+f"(acc[4][0]), "+f"(acc[4][1]), "+f"(acc[4][2]), "+f"(acc[4][3]), "+f"(acc[5][0]), "+f"(acc[5][1]), "+f"(acc[5][2]), "+f"(acc[5][3]), "+f"(acc[6][0]), "+f"(acc[6][1]), "+f"(acc[6][2]), "+f"(acc[6][3]), "+f"(acc[7][0]), "+f"(acc[7][1]), "+f"(acc[7][2]), "+f"(acc[7][3]), "+f"(acc[8][0]), "+f"(acc[8][1]), "+f"(acc[8][2]), "+f"(acc[8][3]), "+f"(acc[9][0]), "+f"(acc[9][1]), "+f"(acc[9][2]), "+f"(acc[9][3]), "+f"(acc[10][0]), "+f"(acc[10][1]), "+f"(acc[10][2]), "+f"(acc[10][3]), "+f"(acc[11][0]), "+f"(acc[11][1]), "+f"(acc[11][2]), "+f"(acc[11][3]), "+f"(acc[12][0]), "+f"(acc[12][1]), "+f"(acc[12][2]), "+f"(acc[12][3]), "+f"(acc[13][0]), "+f"(acc[13][1]), "+f"(acc[13][2]), "+f"(acc[13][3]), "+f"(acc[14][0]), "+f"(acc[14][1]), "+f"(acc[14][2]), "+f"(acc[14][3]), "+f"(acc[15][0]), "+f"(acc[15][1]), "+f"(acc[15][2]), "+f"(acc[15][3])
                 : "r"(a[0]), "r"(a[1]), "r"(a[2]), "r"(a[3]), "l"(desc));
}
template <> __device__ __forceinline__ void wg_mma<4>(float (&acc)[16][4], const uint32_t* a, uint64_t desc) {
    asm volatile("wgmma.mma_async.sync.aligned.m64n96k16.f32.f16.f16 {%0,%1,%2,%3,%4,%5,%6,%7,%8,%9,%10,%11,%12,%13,%14,%15,%16,%17,%18,%19,%20,%21,%22,%23,%24,%25,%26,%27,%28,%29,%30,%31,%32,%33,%34,%35,%36,%37,%38,%39,%40,%41,%42,%43,%44,%45,%46,%47}, {%48,%49,%50,%51}, %52, 1, 1, 1, 0;\n"
                 : "+f"(acc[4][0]), "+f"(acc[4][1]), "+f"(acc[4][2]), "+f"(acc[4][3]), "+f"(acc[5][0]), "+f"(acc[5][1]), "+f"(acc[5][2]), "+f"(acc[5][3]), "+f"(acc[6][0]), "+f"(acc[6][1]), "+f"(acc[6][2]), "+f"(acc[6][3]), "+f"(acc[7][0]), "+f"(acc[7][1]), "+f"(acc[7][2]), "+f"(acc[7][3]), "+f"(acc[8][0]), "+f"(acc[8][1]), "+f"(acc[8][2]), "+f"(acc[8][3]), "+f"(acc[9][0]), "+f"(acc[9][1]), "+f"(acc[9][2]), "+f"(acc[9][3]), "+f"(acc[10][0]), "+f"(acc[10][1]), "+f"(acc[10][2]), "+f"(acc[10][3]), "+f"(acc[11][0]), "+f"(acc[11][1]), "+f"(acc[11][2]), "+f"(acc[11][3]), "+f"(acc[12][0]), "+f"(acc[12][1]), "+f"(acc[12][2]), "+f"(acc[12][3]), "+f"(acc[13][0]), "+f"(acc[13][1]), "+f"(acc[13][2]), "+f"(acc[13][3]), "+f"(acc[14][0]), "+f"(acc[14][1]), "+f"(acc[14][2]), "+f"(acc[14][3]), "+f"(acc[15][0]), "+f"(acc[15][1]), "+f"(acc[15][2]), "+f"(acc[15][3])
                 : "r"(a[0]), "r"(a[1]), "r"(a[2]), "r"(a[3]), "l"(desc));
}
template <> __device__ __forceinline__ void wg_mma<6>(float (&acc)[16][4], const uint32_t* a, uint64_t desc) {
    asm volatile("wgmma.mma_async.sync.aligned.m64n80k16.f32.f16.f16 {%0,%1,%2,%3,%4,%5,%6,%7,%8,%9,%10,%11,%12,%13,%14,%15,%16,%17,%18,%19,%20,%21,%22,%23,%24,%25,%26,%27,%28,%29,%30,%31,%32,%33,%34,%35,%36,%37,%38,%39}, {%40,%41,%42,%43}, %44, 1, 1, 1, 0;\n"
                 : "+f"(acc[6][0]), "+f"(acc[6][1]), "+f"(acc[6][2]), "+f"(acc[6][3]), "+f"(acc[7][0]), "+f"(acc[7][1]), "+f"(acc[7][2]), "+f"(acc[7][3]), "+f"(acc[8][0]), "+f"(acc[8][1]), "+f"(acc[8][2]), "+f"(acc[8][3]), "+f"(acc[9][0]), "+f"(acc[9][1]), "+f"(acc[9][2]), "+f"(acc[9][3]), "+f"(acc[10][0]), "+f"(acc[10][1]), "+f"(acc[10][2]), "+f"(acc[10][3]), "+f"(acc[11][0]), "+f"(acc[11][1]), "+f"(acc[11][2]), "+f"(acc[11][3]), "+f"(acc[12][0]), "+f"(acc[12][1]), "+f"(acc[12][2]), "+f"(acc[12][3]), "+f"(acc[13][0]), "+f"(acc[13][1]), "+f"(acc[13][2]), "+f"(acc[13][3]), "+f"(acc[14][0]), "+f"(acc[14][1]), "+f"(acc[14][2]), "+f"(acc[14][3]), "+f"(acc[15][0]), "+f"(acc[15][1]), "+f"(acc[15][2]), "+f"(acc[15][3])
                 : "r"(a[0]), "r"(a[1]), "r"(a[2]), "r"(a[3]), "l"(desc));
}
template <> __device__ __forceinline__ void wg_mma<8>(float (&acc)[16][4], const uint32_t* a, uint64_t desc) {
    asm volatile("wgmma.mma_async.sync.aligned.m64n64k16.f32.f16.f16 {%0,%1,%2,%3,%4,%5,%6,%7,%8,%9,%10,%11,%12,%13,%14,%15,%16,%17,%18,%19,%20,%21,%22,%23,%24,%25,%26,%27,%28,%29,%30,%31}, {%32,%33,%34,%35}, %36, 1, 1, 1, 0;\n"
                 : "+f"(acc[8][0]), "+f"(acc[8][1]), "+f"(acc[8][2]), "+f"(acc[8][3]), "+f"(acc[9][0]), "+f"(acc[9][1]), "+f"(acc[9][2]), "+f"(acc[9][3]), "+f"(acc[10][0]), "+f"(acc[10][1]), "+f"(acc[10][2]), "+f"(acc[10][3]), "+f"(acc[11][0]), "+f"(acc[11][1]), "+f"(acc[11][2]), "+f"(acc[11][3]), "+f"(acc[12][0]), "+f"(acc[12][1]), "+f"(acc[12][2]), "+f"(acc[12][3]), "+f"(acc[13][0]), "+f"(acc[13][1]), "+f"(acc[13][2]), "+f"(acc[13][3]), "+f"(acc[14][0]), "+f"(acc[14][1]), "+f"(acc[14][2]), "+f"(acc[14][3]), "+f"(acc[15][0]), "+f"(acc[15][1]), "+f"(acc[15][2]), "+f"(acc[15][3])
                 : "r"(a[0]), "r"(a[1]), "r"(a[2]), "r"(a[3]), "l"(desc));
}
template <> __device__ __forceinline__ void wg_mma<10>(float (&acc)[16][4], const uint32_t* a, uint64_t desc) {
    asm volatile("wgmma.mma_async.sync.aligned.m64n48k16.f32.f16.f16 {%0,%1,%2,%3,%4,%5,%6,%7,%8,%9,%10,%11,%12,%13,%14,%15,%16,%17,%18,%19,%20,%21,%22,%23}, {%24,%25,%26,%27}, %28, 1, 1, 1, 0;\n"
                 : "+f"(acc[10][0]), "+f"(acc[10][1]), "+f"(acc[10][2]), "+f"(acc[10][3]), "+f"(acc[11][0]), "+f"(acc[11][1]), "+f"(acc[11][2]), "+f"(acc[11][3]), "+f"(acc[12][0]), "+f"(acc[12][1]), "+f"(acc[12][2]), "+f"(acc[12][3]), "+f"(acc[13][0]), "+f"(acc[13][1]), "+f"(acc[13][2]), "+f"(acc[13][3]), "+f"(acc[14][0]), "+f"(acc[14][1]), "+f"(acc[14][2]), "+f"(acc[14][3]), "+f"(acc[15][0]), "+f"(acc[15][1]), "+f"(acc[15][2]), "+f"(acc[15][3])
                 : "r"(a[0]), "r"(a[1]), "r"(a[2]), "r"(a[3]), "l"(desc));
}
template <> __device__ __forceinline__ void wg_mma<12>(float (&acc)[16][4], const uint32_t* a, uint64_t desc) {
    asm volatile("wgmma.mma_async.sync.aligned.m64n32k16.f32.f16.f16 {%0,%1,%2,%3,%4,%5,%6,%7,%8,%9,%10,%11,%12,%13,%14,%15}, {%16,%17,%18,%19}, %20, 1, 1, 1, 0;\n"
                 : "+f"(acc[12][0]), "+f"(acc[12][1]), "+f"(acc[12][2]), "+f"(acc[12][3]), "+f"(acc[13][0]), "+f"(acc[13][1]), "+f"(acc[13][2]), "+f"(acc[13][3]), "+f"(acc[14][0]), "+f"(acc[14][1]), "+f"(acc[14][2]), "+f"(acc[14][3]), "+f"(acc[15][0]), "+f"(acc[15][1]), "+f"(acc[15][2]), "+f"(acc[15][3])
                 : "r"(a[0]), "r"(a[1]), "r"(a[2]), "r"(a[3]), "l"(desc));
}
template <> __device__ __forceinline__ void wg_mma<14>(float (&acc)[16][4], const uint32_t* a, uint64_t desc) {
    asm volatile("wgmma.mma_async.sync.aligned.m64n16k16.f32.f16.f16 {%0,%1,%2,%3,%4,%5,%6,%7}, {%8,%9,%10,%11}, %12, 1, 1, 1, 0;\n"
                 : "+f"(acc[14][0]), "+f"(acc[14][1]), "+f"(acc[14][2]), "+f"(acc[14][3]), "+f"(acc[15][0]), "+f"(acc[15][1]), "+f"(acc[15][2]), "+f"(acc[15][3])
                 : "r"(a[0]), "r"(a[1]), "r"(a[2]), "r"(a[3]), "l"(desc));
}
template <> __device__ __forceinline__ void wg_first<0>(float (&acc)[16][4], const uint32_t* a, uint64_t desc) {
    asm volatile("wgmma.mma_async.sync.aligned.m64n128k16.f32.f16.f16 {%0,%1,%2,%3,%4,%5,%6,%7,%8,%9,%10,%11,%12,%13,%14,%15,%16,%17,%18,%19,%20,%21,%22,%23,%24,%25,%26,%27,%28,%29,%30,%31,%32,%33,%34,%35,%36,%37,%38,%39,%40,%41,%42,%43,%44,%45,%46,%47,%48,%49,%50,%51,%52,%53,%54,%55,%56,%57,%58,%59,%60,%61,%62,%63}, {%64,%65,%66,%67}, %68, 0, 1, 1, 0;\n"
                 : "=f"(acc[0][0]), "=f"(acc[0][1]), "=f"(acc[0][2]), "=f"(acc[0][3]), "=f"(acc[1][0]), "=f"(acc[1][1]), "=f"(acc[1][2]), "=f"(acc[1][3]), "=f"(acc[2][0]), "=f"(acc[2][1]), "=f"(acc[2][2]), "=f"(acc[2][3]), "=f"(acc[3][0]), "=f"(acc[3][1]), "=f"(acc[3][2]), "=f"(acc[3][3]), "=f"(acc[4][0]), "=f"(acc[4][1]), "=f"(acc[4][2]), "=f"(acc[4][3]), "=f"(acc[5][0]), "=f"(acc[5][1]), "=f"(acc[5][2]), "=f"(acc[5][3]), "=f"(acc[6][0]), "=f"(acc[6][1]), "=f"(acc[6][2]), "=f"(acc[6][3]), "=f"(acc[7][0]), "=f"(acc[7][1]), "=f"(acc[7][2]), "=f"(acc[7][3]), "=f"(acc[8][0]), "=f"(acc[8][1]), "=f"(acc[8][2]), "=f"(acc[8][3]), "=f"(acc[9][0]), "=f"(acc[9][1]), "=f"(acc[9][2]), "=f"(acc[9][3]), "=f"(acc[10][0]), "=f"(acc[10][1]), "=f"(acc[10][2]), "=f"(acc[10][3]), "=f"(acc[11][0]), "=f"(acc[11][1]), "=f"(acc[11][2]), "=f"(acc[11][3]), "=f"(acc[12][0]), "=f"(acc[12][1]), "=f"(acc[12][2]), "=f"(acc[12][3]), "=f"(acc[13][0]), "=f"(acc[13][1]), "=f"(acc[13][2]), "=f"(acc[13][3]), "=f"(acc[14][0]), "=f"(acc[14][1]), "=f"(acc[14][2]), "=f"(acc[14][3]), "=f"(acc[15][0]), "=f"(acc[15][1]), "=f"(acc[15][2]), "=f"(acc[15][3])
                 : "r"(a[0]), "r"(a[1]), "r"(a[2]), "r"(a[3]), "l"(desc));
}
template <> __device__ __forceinline__ void wg_first<4>(float (&acc)[16][4], const uint32_t* a, uint64_t desc) {
    asm volatile("wgmma.mma_async.sync.aligned.m64n96k16.f32.f16.f16 {%0,%1,%2,%3,%4,%5,%6,%7,%8,%9,%10,%11,%12,%13,%14,%15,%16,%17,%18,%19,%20,%21,%22,%23,%24,%25,%26,%27,%28,%29,%30,%31,%32,%33,%34,%35,%36,%37,%38,%39,%40,%41,%42,%43,%44,%45,%46,%47}, {%48,%49,%50,%51}, %52, 0, 1, 1, 0;\n"
                 : "=f"(acc[4][0]), "=f"(acc[4][1]), "=f"(acc[4][2]), "=f"(acc[4][3]), "=f"(acc[5][0]), "=f"(acc[5][1]), "=f"(acc[5][2]), "=f"(acc[5][3]), "=f"(acc[6][0]), "=f"(acc[6][1]), "=f"(acc[6][2]), "=f"(acc[6][3]), "=f"(acc[7][0]), "=f"(acc[7][1]), "=f"(acc[7][2]), "=f"(acc[7][3]), "=f"(acc[8][0]), "=f"(acc[8][1]), "=f"(acc[8][2]), "=f"(acc[8][3]), "=f"(acc[9][0]), "=f"(acc[9][1]), "=f"(acc[9][2]), "=f"(acc[9][3]), "=f"(acc[10][0]), "=f"(acc[10][1]), "=f"(acc[10][2]), "=f"(acc[10][3]), "=f"(acc[11][0]), "=f"(acc[11][1]), "=f"(acc[11][2]), "=f"(acc[11][3]), "=f"(acc[12][0]), "=f"(acc[12][1]), "=f"(acc[12][2]), "=f"(acc[12][3]), "=f"(acc[13][0]), "=f"(acc[13][1]), "=f"(acc[13][2]), "=f"(acc[13][3]), "=f"(acc[14][0]), "=f"(acc[14][1]), "=f"(acc[14][2]), "=f"(acc[14][3]), "=f"(acc[15][0]), "=f"(acc[15][1]), "=f"(acc[15][2]), "=f"(acc[15][3])
                 : "r"(a[0]), "r"(a[1]), "r"(a[2]), "r"(a[3]), "l"(desc));
}

#define EARLYN 2
#define K8 0
#define HOLD 1
#define MC 1
#define STAMP2(i) STAMP(i)
#undef STAMPX
#define STAMPX(i)
#define PBAR 1
#define WDLY 300
#define EXP 0
#define XWHEN 0
#define RWHEN 0
#define HW 15
#define PEARLY 0
#define XG 5
struct Params {
    const bf16 *x, *lar, *aim, *cre, *cim, *ldt, *dsk;
    Scratch* s;
    const bf16 *wr, *wg, *wu, *wd;
    bf16* out;
};

#define TOK(g) (2 * (g) - ((g) & 1))
#define ROWTOK(r) (TOK((r) & 7) + (((r) >> 2) & 2))
__device__ __forceinline__ void ln_partial(const uint32_t (&H)[2][4], const uint32_t (&bw)[4], uint32_t lp, int warp, int g, int t) {
    float cs[4] = {0.f, 0.f, 0.f, 0.f}, cl[4] = {0.f, 0.f, 0.f, 0.f}, ch[4] = {0.f, 0.f, 0.f, 0.f};
#pragma unroll
    for (int k = 0; k < 4; k += 2) {
        mma_bf16(cs, H[0][k], H[1][k], H[0][k + 1], H[1][k + 1], bw[k], bw[k + 1]);
        mma_bf16(cl, H[0][k], H[1][k], H[0][k + 1], H[1][k + 1], H[0][k], H[0][k + 1]);
        mma_bf16(ch, H[0][k], H[1][k], H[0][k + 1], H[1][k + 1], H[1][k], H[1][k + 1]);
    }
    const uint32_t a = lp + (g * 20 + warp) * 4;
    if (t == 0) {
        stsf(a, cs[0]); stsf(a + 8 * 80, cs[2]);
    }
    if (t == (g >> 1)) { stsf(a + 16 * 80, (g & 1) ? cl[1] : cl[0]); stsf(a + 24 * 80, (g & 1) ? ch[3] : ch[2]); }
}
__device__ __forceinline__ float sum18(uint32_t a) {
    const uint4 p = lds128(a), q = lds128(a + 16), r = lds128(a + 32), s = lds128(a + 48);
    const uint2 u = lds64(a + 64);
#define F(x) __uint_as_float(x)
    return (((F(p.x) + F(p.y)) + (F(p.z) + F(p.w))) + ((F(q.x) + F(q.y)) + (F(q.z) + F(q.w)))) +
           (((F(r.x) + F(r.y)) + (F(r.z) + F(r.w))) + ((F(s.x) + F(s.y)) + (F(s.z) + F(s.w))) + (F(u.x) + F(u.y)));
#undef F
}
__device__ __forceinline__ void ln_stats(float sm, float sq, float& mb, float& sd) {
    const float m0 = sm * (1.0f / 576.0f);
    const float mean = fmaf(fmaf(-m0, 576.0f, sm), 1.0f / 576.0f, m0);
    const float var = fmaxf(fmaf(-mean, mean, sq * (1.0f / 576.0f)), 0.f);
    mb = rbf(mean);
    sd = rbf(sqrt_approx(rbf(rbf(var) + 1e-5f)));
}
__device__ __forceinline__ void ln_finish(float v, int lane, float& mb, float& rc) {
    const float o = __shfl_xor_sync(0xffffffffu, v, 16);
    float sd;
    ln_stats(lane < 16 ? v : o, lane < 16 ? o : v, mb, sd);
    rc = rcp_approx(sd);
}
__device__ __forceinline__ uint32_t ln_apply(uint32_t w, uint32_t m2, uint32_t rh, uint32_t rl) {
    const uint32_t d = hsub2_bf(w, m2);
    return hfma2_bf(d, rh, hmul2_bf(d, rl));
}
__device__ __forceinline__ void stat_store(uint32_t a, float mb, float rc, uint32_t extra) {
    const float rh = rbf(rc);
    sts64(a, (__float_as_uint(mb) >> 16) | (extra << 16), pack_bf16(rh, rc - rh));
}
#define STAT_M(s) __byte_perm((s).x, (s).x, 0x1010)
#define STAT_H(s) __byte_perm((s).y, (s).y, 0x1010)
#define STAT_L(s) __byte_perm((s).y, (s).y, 0x3232)

__device__ __forceinline__ void hcmul(uint32_t re, uint32_t im, uint32_t zx, uint32_t zy, uint32_t& ore, uint32_t& oim) {
    ore = hfms2(im, zy, hmul2(re, zx));
    oim = hfma2(re, zy, hmul2(im, zx));
}

struct KGen {
    uint32_t A[2][4][4];
    float2 z1, z8, z64, z128, T[9];
};
__device__ __forceinline__ void kgen_setup(KGen& k, float lar, float aim, float dt) {
    const float lr2 = -(exp_bf(lar) * dt) * 1.4426950408889634f, li = aim * dt;
    k.z1 = cexp_e(lr2, li, 1.0f);
    k.z8 = cexp_e(lr2, li, 8.0f);
    k.z64 = cexp_e(lr2, li, 64.0f);
}
__device__ __forceinline__ void kgen_rows(KGen& k, uint32_t tb, int lane) {
    const float2 z8 = k.z8, z64 = k.z64;
    const uint32_t row = tb + lane * TBP;
    k.z128 = csq(z64);
    const float2 z16 = csq(z8), z24 = cmul(z16, z8), z32 = csq(z16), z40 = cmul(z32, z8), z48 = csq(z24), z56 = cmul(z32, z24);
    uint32_t re[4], im[4], a[4], b[4];
    re[0] = pack_f16(1.0f, z8.x); im[0] = pack_f16(0.0f, z8.y);
    re[1] = pack_f16(z16.x, z24.x); im[1] = pack_f16(z16.y, z24.y);
    re[2] = pack_f16(z32.x, z40.x); im[2] = pack_f16(z32.y, z40.y);
    re[3] = pack_f16(z48.x, z56.x); im[3] = pack_f16(z48.y, z56.y);
    sts128(row, re[0], re[1], re[2], re[3]);
    sts128(row + 32, im[0], im[1], im[2], im[3]);
    const uint32_t zx = pack_f16(z64.x, z64.x), zy = pack_f16(z64.y, z64.y), zw = pack_f16(k.z128.x, k.z128.y);
#pragma unroll
    for (int j = 0; j < 4; j++) hcmul(re[j], im[j], zx, zy, a[j], b[j]);
    sts128(row + 16, a[0], a[1], a[2], a[3]);
    sts128(row + 48, b[0], b[1], b[2], b[3]);
    const int mi = lane >> 3;
    const uint32_t zd = tb + mi * TBP + 96;
    sts16(zd + (lane & 7) * 2, zw); sts16(zd + (lane & 7) * 2 + 4 * TBP, zw >> 16);
    __syncwarp();
    const uint32_t ad = tb + (lane & 7) * TBP + mi * 16;
    ldsm_x4(a[0], a[1], a[2], a[3], zd);
    ldsm_x4(b[0], b[1], b[2], b[3], zd + 4 * TBP);
#pragma unroll
    for (int ks = 0; ks < 4; ks++) {
        ldsm_x4_t(k.A[0][ks][0], k.A[0][ks][1], k.A[0][ks][2], k.A[0][ks][3], ad + ks * 8 * TBP);
        hcmul(k.A[0][ks][0], k.A[0][ks][2], a[ks], b[ks], k.A[1][ks][0], k.A[1][ks][2]);
        hcmul(k.A[0][ks][1], k.A[0][ks][3], a[ks], b[ks], k.A[1][ks][1], k.A[1][ks][3]);
    }
}
__device__ __forceinline__ void kgen_chain(KGen& k, uint32_t cr, uint32_t ci, float cs) {
    k.T[0] = make_float2(bf_lo(cr) * cs, -bf_lo(ci) * cs);
    const float2 y1 = make_float2(k.z1.x, -k.z1.y);
#pragma unroll
    for (int c = 1; c < 8; c++) k.T[c] = cmul(k.T[c - 1], y1);
    k.T[8] = cmul(k.T[0], make_float2(k.z8.x, -k.z8.y));
}
__device__ __forceinline__ void kgen_cols(KGen& k, uint32_t tb, int lane) {
    const uint32_t row = tb + lane * TBP;
    const float2 (&T)[9] = k.T;
    const float2 y128 = make_float2(k.z128.x, -k.z128.y);
    const float2 y256 = csq(y128), y512 = csq(y256), y768 = cmul(y512, y256), y1024 = csq(y512);
    const float2 c1032 = cmul(T[8], y1024);
    __syncwarp();
    sts128(row, pack_f16(T[0].x, T[1].x), pack_f16(T[2].x, T[3].x), pack_f16(T[4].x, T[5].x), pack_f16(T[6].x, T[7].x));
    sts128(row + 16, pack_f16(T[0].y, T[1].y), pack_f16(T[2].y, T[3].y), pack_f16(T[4].y, T[5].y), pack_f16(T[6].y, T[7].y));
    uint32_t a[4], b[4];
    {
        const uint32_t zx = pack_f16(y256.x, y256.x), zy = pack_f16(y256.y, y256.y);
        hcmul(pack_f16(T[0].x, T[2].x), pack_f16(T[0].y, T[2].y), zx, zy, a[0], b[0]);
        hcmul(pack_f16(T[4].x, T[6].x), pack_f16(T[4].y, T[6].y), zx, zy, a[1], b[1]);
        const uint32_t r04 = pack_f16(T[0].x, T[4].x), i04 = pack_f16(T[0].y, T[4].y);
        hcmul(r04, i04, pack_f16(y512.x, y512.x), pack_f16(y512.y, y512.y), a[2], b[2]);
        hcmul(r04, i04, pack_f16(y768.x, y768.x), pack_f16(y768.y, y768.y), a[3], b[3]);
    }
    sts128(row + 32, a[0], a[1], a[2], a[3]);
    sts128(row + 48, b[0], b[1], b[2], b[3]);
    {
        const uint32_t r0 = pack_f16(1.0f, y256.x), i0 = pack_f16(0.0f, y256.y), r1 = pack_f16(y512.x, y768.x), i1 = pack_f16(y512.y, y768.y);
        const uint32_t zx = pack_f16(T[8].x, T[8].x), zy = pack_f16(T[8].y, T[8].y), wx = pack_f16(c1032.x, c1032.x), wy = pack_f16(c1032.y, c1032.y);
        hcmul(r0, i0, zx, zy, a[0], b[0]); hcmul(r1, i1, zx, zy, a[1], b[1]);
        hcmul(r0, i0, wx, wy, a[2], b[2]); hcmul(r1, i1, wx, wy, a[3], b[3]);
    }
    sts128(row + 64, a[0], a[1], a[2], a[3]);
    sts128(row + 80, b[0], b[1], b[2], b[3]);
}
__device__ __forceinline__ void kgen_mma(const KGen& k, uint32_t tb, int lane) {
    __syncwarp();
    float acc[2][3][4];
#pragma unroll
    for (int i = 0; i < 6; i++)
#pragma unroll
        for (int j = 0; j < 4; j++) acc[i / 3][i % 3][j] = 0.f;
    const int mi = lane >> 3;
    const uint32_t bd = tb + ((lane & 7) + 8 * (mi >> 1)) * TBP + (mi & 1) * 16;
#pragma unroll
    for (int kp = 0; kp < 2; kp++)
#pragma unroll
        for (int j = 0; j < 3; j++) {
            uint32_t b[4];
            ldsm_x4_t(b[0], b[1], b[2], b[3], bd + kp * 16 * TBP + j * 32);
#pragma unroll
            for (int h = 0; h < 2; h++)
#pragma unroll
                for (int m = 0; m < 2; m++) {
                    const uint32_t (&A)[4] = k.A[m][2 * kp + h];
                    mma_f16(acc[m][j], A[0], A[1], A[2], A[3], b[2 * h], b[2 * h + 1]);
                }
        }
    __syncwarp();
#define PK(j) pack_f16(acc[0][j][0], acc[0][j][1]), pack_f16(acc[0][j][2], acc[0][j][3]), pack_f16(acc[1][j][0], acc[1][j][1]), pack_f16(acc[1][j][2], acc[1][j][3])
    stsm_x4(tb + lane * 16, PK(0));
    stsm_x4(tb + 512 + lane * 16, PK(1));
    stsm_x4_t(tb + 1024 + (lane & 7) * 80 + mi * 16, PK(2));
#undef PK
}
__device__ __forceinline__ uint32_t table_buf(uint32_t sb, int warp) { return sb + SM_WD + (warp < 16 ? warp + 4 : warp - 16) * TBW; }

__device__ __forceinline__ uint4 lds16x4(uint32_t a) { return make_uint4(lds16(a), lds16(a + TBW), lds16(a + 2 * TBW), lds16(a + 3 * TBW)); }
__device__ __forceinline__ void combine_setup(uint32_t sb, int warp, int lane, uint32_t kw, uint32_t& o, uint32_t& n, uint32_t& d) {
    const int wq = warp & 3;
    const uint32_t a = table_buf(sb, warp & ~3);
    o = wq == 3 ? a + 1024 + 320 + (lane >> 3) * 80 + (lane & 7) * 8 : a + (wq ? 504 + wq * 8 : 0) + lane * 16;
    n = a + 1024 + wq * 80 + lane * 2;
    d = wq < 3 ? kw + (wq == 2 ? KW_P : 32 + wq * 512) + lane * 16 : kw + KW_H + 8 + lane * 8;
}
__device__ __forceinline__ void kgen_combine(int wq, int lane, uint32_t o, uint32_t na, uint32_t d) {
#define S4(f) hadd2(hadd2(u.f, v.f), hadd2(w.f, x.f))
#define H4(v) hadd2(hadd2(v.x, v.y), hadd2(v.z, v.w))
#define BP __byte_perm
    if (wq == 0) {
        const uint4 u = lds128(o), v = lds128(o + TBW), w = lds128(o + 2 * TBW), x = lds128(o + 3 * TBW), nn = lds16x4(na);
        const uint32_t n = H4(nn), k0 = S4(x), k2 = S4(y), k4 = S4(z), k6 = S4(w);
        sts128(d, BP(k0, k0, 0x1032), BP(k0, k2, 0x3254), BP(k2, k2, 0x1032), BP(k2, k4, 0x3254));
        sts128(d + KW_PL, BP(k4, k4, 0x1032), BP(k4, k6, 0x3254), BP(k6, k6, 0x1032), BP(k6, n, 0x3254));
        if (lane == 0) sts32(d + KW_PL - 4, k0 & 0xffffu);
    } else {
        const uint2 u = lds64(o), v = lds64(o + TBW), w = lds64(o + 2 * TBW), x = lds64(o + 3 * TBW);
        uint4 nn = make_uint4(0u, 0u, 0u, 0u), mm = nn;
        if (wq < 3) nn = lds16x4(na);
        if (wq == 2) mm = lds16x4(na + 80);
        const uint32_t k0 = S4(x), k2 = S4(y), n = H4(nn), m = H4(mm);
        if (wq == 3) {
            sts64(d, k0, k2);
        } else if (wq == 1) {
            const uint32_t cc = BP(k2, k2, 0x1010);
            sts128(d, BP(k0, k0, 0x1010), BP(k0, k0, 0x1032), BP(k0, k2, 0x3254), cc);
            sts128(d + KW_PL, cc, BP(k2, k2, 0x1032), BP(k2, n, 0x3254), BP(n, n, 0x1010));
        } else {
            const uint32_t w40 = BP(k0, k0, 0x1032), w84 = BP(k0, n, 0x3254), w0 = BP(k0, k0, 0x1010), w4 = BP(k0, k0, 0x3232), w8 = BP(n, n, 0x1010);
            sts64(d, w40, w84);
            sts64(d + 512, BP(k2, k2, 0x1032), BP(k2, m, 0x3254));
            if (lane < 8) { sts128(d - (KW_P - 1056), w0, w0, w40, w4); sts128(d - (KW_P - 1056 - KW_PL), w4, w84, w8, w8); }
            if (lane == 31) sts16(d + (KW_H + 6 - KW_P - 496), m);
        }
    }
#undef S4
#undef H4
#undef BP
}

__device__ __forceinline__ int c_exponent(const uint2& r, const uint2& i, float dt) {
    const uint32_t mx = __vmaxu2(__vmaxu2(r.x & 0x7fff7fffu, r.y & 0x7fff7fffu), __vmaxu2(i.x & 0x7fff7fffu, i.y & 0x7fff7fffu));
    return __reduce_max_sync(0xffffffffu, max(mx, mx << 16) + (__float_as_uint(dt) & 0x7f800000u)) >> 23;
}

__device__ __forceinline__ int warp_v() { int l; asm volatile("mov.u32 %0, %%tid.x;" : "=r"(l)); return __shfl_sync(0xffffffffu, l >> 5, 0); }
__device__ __forceinline__ int lane_v() { int l; asm volatile("mov.u32 %0, %%laneid;" : "=r"(l)); return l; }
__device__ __forceinline__ uint32_t prmt_v(uint32_t a, uint32_t b, uint32_t s) { uint32_t d; asm volatile("prmt.b32 %0, %1, %2, %3;\n" : "=r"(d) : "r"(a), "r"(b), "r"(s)); return d; }
__device__ __forceinline__ uint32_t mov_v(uint32_t a) { uint32_t d; asm volatile("mov.b32 %0, %1;\n" : "=r"(d) : "r"(a)); return d; }
template <int G>
__device__ __forceinline__ void conv_rename(float (&acc)[16][4]) {
#pragma unroll
    for (int i = G; i < 16; i++)
#pragma unroll
        for (int j = 0; j < 4; j++) { float v; asm volatile("mov.b32 %0, %1;\n" : "=f"(v) : "f"(acc[i][j])); acc[i][j] = v; }
}
struct Conv {
    uint32_t kw;
    uint32_t wa;
    uint32_t pa, s2;
    uint32_t s8;
    uint32_t id;
    uint32_t lc;
    uint32_t fs;
    uint32_t fl, yo;
    size_t ycopy;
    uint32_t ps;
    uint64_t d0;
    int warp;
};
struct Pk { uint32_t w[4]; };
__device__ __forceinline__ Pk pk2(const float (&u)[4], const float (&v)[4]) {
    Pk r;
    r.w[0] = pack_f16(u[0], u[1]); r.w[1] = pack_f16(u[2], u[3]); r.w[2] = pack_f16(v[0], v[1]); r.w[3] = pack_f16(v[2], v[3]);
    return r;
}
__device__ __forceinline__ void park(uint32_t a, const Pk& v) {
    asm volatile("stmatrix.sync.aligned.m8n8.x4.trans.shared.b16 [%0], {%1,%2,%3,%4};\n" ::"r"(a), "r"(v.w[0]), "r"(v.w[1]), "r"(v.w[2]), "r"(v.w[3]) : "memory");
}
__device__ __forceinline__ void conv_constants(uint32_t lc, int l) {
    const int d = (l >> 2) - 2 * (l & 3);
    const int e = d + 8, r4 = (e + 1 + ((e >> 2) & 1)) >> 2, p4 = (e + (((e - 1) >> 2) & 1)) >> 2;
    const uint32_t s2 = r4 == p4 ? 0x1010u : 0x3210u;
    sts64(lc + l * 8, KW_P + ((r4 - 5) >> 1) * 16 + ((r4 - 5) & 1) * 4, s2 | ((d < 0 ? s2 : 0x7654u) << 16));
    const int lo = (d >= 4) - (d < -3), ho = (d >= 5) - (d < -2), le = (d > 4) - (d < -4), he = (d > 5) - (d < -3);
    sts32(lc + 512 + l * 8, (0x5454u + lo * 0x22 + ho * 0x2200) | ((0x3232u + le * 0x22 + he * 0x2200) << 16));
    const int cc = l >> 2, j = l & 3;
    sts64(lc + 256 + l * 8, (j >> 1) * PL_HALF + (16 + cc) * 16 + (j & 1) * 8, (cc >> 1) * (DM * 64) + (cc & 1) * 32 + j * 8);
}
__device__ __forceinline__ void conv_selectors4(Conv& c) {
    const uint2 v = lds64(c.lc + lane_v() * 8);
    c.pa = v.x; c.s2 = v.y;
}
__device__ __forceinline__ void conv_selectors8(Conv& c) { c.s8 = lds32(c.lc + 512 + lane_v() * 8); }
template <int G, int I0, int I1>
__device__ __forceinline__ void conv_load(const Conv& c, uint32_t (&q)[9]) {
    const int wq = c.warp & 3;
    if (G < 2) {
#pragma unroll
        for (int i = I0; i < I1; i++) q[i] = lds32(c.wa + G * 512 + i * 16);
    } else if (G < 4) {
        const uint32_t a = (G == 2 && wq == 0) ? c.wa + 1024 : c.pa + c.kw + wq * 128 + (G < 2 ? 0 : G - 2) * 512;
#pragma unroll
        for (int i = I0; i < I1; i++) q[i] = lds32(a + i * 16);
    } else {
        const uint4 u = lds128(c.kw + KW_H + (G < 4 ? 0 : G - 4) * 64 + wq * 16);
        const uint2 v = lds64(c.kw + KW_H + (G < 4 ? 0 : G - 4) * 64 + wq * 16 + 16);
        q[0] = u.x; q[1] = u.y; q[2] = u.z; q[3] = u.w; q[4] = v.x; q[5] = v.y;
        if (G == 4 && wq == 0) { q[6] = lds32(c.pa + c.kw + 1024); q[7] = lds32(c.pa + c.kw + 1040); }
    }
}
template <int G, int J0, int J1>
__device__ __forceinline__ void conv_frag(const Conv& c, const uint32_t (&q)[9], uint32_t* a, const Pk& dp) {
    const uint32_t dep = dp.w[0];
    if (G < 4) {
        const uint32_t s = (G < 2 || (G == 2 && (c.warp & 3) == 0)) ? c.id : c.s2;
#pragma unroll
        for (int j = J0; j < J1; j++) {
            uint32_t* o = a + 4 * (j - J0);
            o[0] = prmt_v(q[2 * j + 1], dp.w[0], s); o[1] = prmt_v(q[2 * j + 2], dp.w[1], s); o[2] = prmt_v(q[2 * j], dp.w[2], s); o[3] = prmt_v(q[2 * j + 1], dp.w[3], s);
        }
    } else {
        const uint32_t so = prmt_v(c.s8, dep, c.id), se = prmt_v(c.s8, dep, c.id + 0x22);
#pragma unroll
        for (int j = J0; j < J1; j++) {
            uint32_t* o = a + 4 * (j - J0);
            o[0] = prmt_v(q[j + 1], q[j + 2], se); o[1] = prmt_v(q[j + 1], q[j + 2], so); o[2] = prmt_v(q[j], q[j + 1], so);
            if (G == 4 && j == 0 && (c.warp & 3) == 0) {
                o[2] = prmt_v(q[6], dep, c.s2);
                o[0] = prmt_v(q[7], o[0], c.s2 >> 16);
            }
            o[3] = mov_v(o[0]);
        }
    }
}
template <int G, int J0, int J1>
__device__ __forceinline__ void conv_frag(const Conv& c, const uint32_t (&q)[9], uint32_t* a, float depf) {
    const uint32_t d = __float_as_uint(depf);
    conv_frag<G, J0, J1>(c, q, a, Pk{{d, d, d, d}});
}
template <int G, int T, int J0, int J1>
__device__ __forceinline__ void conv_mma(float (&acc)[16][4], const Conv& c, const uint32_t* a) {
#pragma unroll
    for (int j = J0; j < J1; j++) wg_mma<T>(acc, a + 4 * (j - J0), c.d0 - 8 * (2 * G - T) - j);
}
__device__ __forceinline__ float h_lo(uint32_t w) { return __half2float(__ushort_as_half((unsigned short)(w & 0xffffu))); }
__device__ __forceinline__ float h_hi(uint32_t w) { return __half2float(__ushort_as_half((unsigned short)(w >> 16))); }
__device__ __forceinline__ void flush_setup(Conv& c) {
    const uint2 v = lds64(c.lc + 256 + lane_v() * 8);
    c.fl = v.x; c.yo = v.y;
}
template <int Q>
__device__ __forceinline__ void flush_load(const Conv& c, uint32_t pl, uint2 (&f)[4]) {
#pragma unroll
    for (int w = 0; w < 4; w++) f[w] = lds64(c.fl + pl + (Q & 1) * 512 + w * (PLW_B - 64));
}
template <int Q>
__device__ __forceinline__ void flush_load_first(const Conv& c, uint32_t pl, uint2 (&f)[4], float depf) {
    const uint32_t p = prmt_v(c.fl, __float_as_uint(depf), c.id) + pl + (Q & 1) * 512;
#define LDV64(d, a) asm volatile("ld.volatile.shared.v2.u32 {%0,%1}, [%2];\n" : "=r"(d.x), "=r"(d.y) : "r"(a) : "memory")
    LDV64(f[0], p); LDV64(f[1], p + (PLW_B - 64)); LDV64(f[2], p + 2 * (PLW_B - 64)); LDV64(f[3], p + 3 * (PLW_B - 64));
}
#define FDEP __uint_as_float(f[3].y)
template <int Q, int mode>
__device__ __forceinline__ void conv_flush(const Conv& c, const uint2 (&f)[4], unsigned char* gy, uint32_t rx) {
    const uint32_t a0 = hadd2(f[0].x, f[1].x), a1 = hadd2(f[2].x, f[3].x), b0 = hadd2(f[0].y, f[1].y), b1 = hadd2(f[2].y, f[3].y);
    if (Q > 0 && mode == 1) {
        const uint32_t ra = rx + 16 + (Q > 0 ? Q - 1 : 0) * 1024 + (c.warp & 3) * 256 + lane_v() * 8;
        asm volatile("st.async.shared::cluster.mbarrier::complete_tx::bytes.v2.b32 [%0], {%1,%2}, [%3];\n"
                     ::"r"(ra ^ 0x1000000u), "r"(hadd2(a0, a1)), "r"(hadd2(b0, b1)), "r"((rx + (Q > 1 ? 8 : 0)) ^ 0x1000000u) : "memory");
        return;
    }
    float v0 = h_lo(a0) + h_lo(a1), v1 = h_hi(a0) + h_hi(a1), v2 = h_lo(b0) + h_lo(b1), v3 = h_hi(b0) + h_hi(b1);
    if (Q > 0 && mode == 2) {
        const uint2 o = lds64(rx + 16 + (Q > 0 ? Q - 1 : 0) * 1024 + (c.warp & 3) * 256 + lane_v() * 8);
        v0 += h_lo(o.x); v1 += h_hi(o.x); v2 += h_lo(o.y); v3 += h_hi(o.y);
    }
    const uint32_t lo = hmul2_bf(pack_bf16(v0, v1), c.fs), hi = hmul2_bf(pack_bf16(v2, v3), c.fs);
    stg64(gy + Q * 32 * DM * 32 + c.yo, lo ^ YKEY, hi ^ YKEY);
}
template <int I, bool S = false> struct IC { static constexpr int value = I; static constexpr bool shared = S; };
template <class T> __device__ constexpr bool wg_is4() { return T::shared; }
#define SLOT(n) (c.ps + (2 + ((n) & 7)) * 128)
#define GO() do { wg_commit(); __syncwarp(); } while (0)
#define DEP acc[15][3]
template <class FG, class FP, class FN>
__device__ __forceinline__ void conv_head(Conv& c, float (&acc)[16][4], uint32_t (&q)[9], uint32_t (&r)[9], uint32_t* a, FG fg, FP pre, FN next) {
    c.id = 0x3210u + (c.warp >> 8);
    conv_load<0, 0, 9>(c, q);
    conv_frag<0, 0, 1>(c, q, a, 0.f);
    pre();
    wg_fence(); wg_first<0>(acc, a, c.d0); GO();
    park(c.ps, Pk{{0u, 0u, 0u, 0u}});
    wg_wait0();
    conv_frag<0, 1, 2>(c, q, a, DEP);
    wg_fence(); conv_mma<0, 0, 1, 2>(acc, c, a); GO();
    fg(IC<0>());
    wg_wait0();
    conv_frag<0, 2, 3>(c, q, a, DEP);
    wg_fence(); conv_mma<0, 0, 2, 3>(acc, c, a); GO();
    conv_load<1, 0, 5>(c, r);
    wg_wait0();
    conv_frag<0, 3, 4>(c, q, a, DEP);
    wg_fence(); conv_mma<0, 0, 3, 4>(acc, c, a); GO();
    conv_load<1, 5, 9>(c, r);
    fg(IC<1>());
    wg_wait0();
    const Pk k = pk2(acc[0], acc[1]);
    conv_rename<2>(acc);
    conv_frag<1, 0, 2>(c, r, a, k);
    wg_fence(); conv_mma<1, 2, 0, 2>(acc, c, a); GO();
    park(SLOT(0), k);
    next(IC<0>());
    fg(IC<2>());
    wg_wait0();
    conv_frag<1, 2, 4>(c, r, a, DEP);
    wg_fence(); conv_mma<1, 2, 2, 4>(acc, c, a); GO();
    next(IC<1>());
    fg(IC<3>());
    wg_wait0();
}
template <class FG, class FP>
__device__ __forceinline__ void conv_run(Conv& c, uint32_t pl, unsigned char* gy, FG fg, FP pre) {
    float acc[16][4];
    uint32_t q[9], r[9], a[32];
    uint2 f[4];
    const int bid = 1 + (c.warp >> 2);
    conv_head(c, acc, q, r, a, fg, pre, [&](auto i) { if (decltype(i)::value == 0) conv_selectors4(c); else conv_load<2, 0, 9>(c, q); });
    Pk k = pk2(acc[2], acc[3]);
    conv_rename<4>(acc);
    conv_frag<2, 0, 4>(c, q, a, k);
    wg_fence(); conv_mma<2, 4, 0, 4>(acc, c, a); GO();
    park(SLOT(2), k);
    conv_load<3, 0, 9>(c, q);
    flush_setup(c);
    bar_sync(bid, 128);
    fg(IC<4>());
    wg_wait0();
    conv_rename<6>(acc);
    flush_load_first<0>(c, pl, f, DEP);
    conv_frag<3, 0, 4>(c, q, a, FDEP);
    wg_fence(); conv_mma<3, 6, 0, 4>(acc, c, a); GO();
    park(SLOT(4), pk2(acc[4], acc[5]));
    conv_load<4, 0, 9>(c, q);
    conv_selectors8(c);
    conv_flush<0, 0>(c, f, gy, 0u);
    fg(IC<5>());
    wg_wait0();
    conv_rename<8>(acc);
    conv_frag<4, 0, 4>(c, q, a, DEP);
    wg_fence(); conv_mma<4, 8, 0, 4>(acc, c, a); GO();
    k = pk2(acc[6], acc[7]);
    park(SLOT(6), k); park(c.ps, k);
    conv_load<5, 0, 9>(c, q);
    bar_sync(bid, 128);
    fg(IC<6>());
    wg_wait0();
    conv_rename<10>(acc);
    flush_load_first<1>(c, pl, f, DEP);
    conv_frag<5, 0, 4>(c, q, a, FDEP);
    wg_fence(); conv_mma<5, 10, 0, 4>(acc, c, a); GO();
    park(SLOT(8), pk2(acc[8], acc[9]));
    conv_load<6, 0, 9>(c, q); conv_load<7, 0, 9>(c, r);
    conv_flush<1, 0>(c, f, gy, 0u);
    fg(IC<7>());
    wg_wait0();
    conv_rename<12>(acc);
    conv_frag<6, 0, 4>(c, q, a, DEP); conv_frag<7, 0, 4>(c, r, a + 16, DEP);
    wg_fence(); conv_mma<6, 12, 0, 4>(acc, c, a); conv_mma<7, 12, 0, 4>(acc, c, a + 16); GO();
    park(SLOT(10), pk2(acc[10], acc[11]));
    bar_sync(bid, 128);
    flush_load<2>(c, pl, f);
    conv_flush<2, 0>(c, f, gy, 0u);
    fg(IC<8>());
    wg_wait0();
    park(SLOT(12), pk2(acc[12], acc[13])); park(SLOT(14), pk2(acc[14], acc[15]));
    bar_sync(bid, 128);
    flush_load<3>(c, pl, f);
    conv_flush<3, 0>(c, f, gy, 0u);
}
template <class FG>
__device__ __forceinline__ void conv_outer(Conv& c, uint32_t pl, unsigned char* gy, uint32_t rx, FG fg) {
    float acc[16][4];
    uint32_t q[9], r[9], a[32];
    uint2 f[4], f2[4];
    const int bid = 1 + (c.warp >> 2);
    conv_head(c, acc, q, r, a, [&](auto gi) { if (decltype(gi)::value == 2) fg(IC<2, true>()); }, [&]() {}, [&](auto i) { if (decltype(i)::value == 0) conv_selectors8(c); else conv_load<6, 0, 9>(c, q); });
    park(SLOT(2), pk2(acc[2], acc[3])); park(SLOT(4), pk2(acc[4], acc[5]));
    const Pk k = pk2(acc[6], acc[7]);
    park(SLOT(6), k);
    conv_load<7, 0, 9>(c, r);
    conv_rename<12>(acc);
    conv_frag<6, 0, 4>(c, q, a, __uint_as_float(k.w[3])); conv_frag<7, 0, 4>(c, r, a + 16, __uint_as_float(k.w[3]));
    wg_fence(); conv_mma<6, 12, 0, 4>(acc, c, a); conv_mma<7, 12, 0, 4>(acc, c, a + 16); GO();
    flush_setup(c);
    bar_sync(bid, 128);
    flush_load<0>(c, pl, f); flush_load<1>(c, pl, f2);
    conv_flush<1, 1>(c, f2, gy, rx);
    conv_flush<0, 1>(c, f, gy, rx);
    wg_wait0();
    bar_sync(bid, 128);
    park(c.ps, k); park(SLOT(8), pk2(acc[8], acc[9])); park(SLOT(10), pk2(acc[10], acc[11]));
    park(SLOT(12), pk2(acc[12], acc[13])); park(SLOT(14), pk2(acc[14], acc[15]));
    bar_sync(bid, 128);
    flush_load<2>(c, pl, f); flush_load<3>(c, pl, f2);
    conv_flush<2, 1>(c, f, gy, rx);
    conv_flush<3, 1>(c, f2, gy, rx);
}
template <class FG>
__device__ __forceinline__ void conv_inner(Conv& c, uint32_t pl, unsigned char* gy, uint32_t rx, FG fg) {
    float acc[16][4];
    uint32_t q[9], a[16];
    uint2 f[4], f2[4];
    const int bid = 1 + (c.warp >> 2);
    c.id = 0x3210u + (c.warp >> 8);
    conv_selectors4(c);
    conv_load<2, 0, 9>(c, q);
    conv_frag<2, 0, 4>(c, q, a, 0.f);
    wg_fence(); wg_first<4>(acc, a, c.d0); conv_mma<2, 4, 1, 4>(acc, c, a + 4); GO();
    conv_load<3, 0, 9>(c, q);
    park(SLOT(2), Pk{{0u, 0u, 0u, 0u}});
    fg(IC<2, true>());
    wg_wait0();
    conv_rename<6>(acc);
    conv_frag<3, 0, 4>(c, q, a, DEP);
    wg_fence(); conv_mma<3, 6, 0, 4>(acc, c, a); GO();
    park(SLOT(4), pk2(acc[4], acc[5]));
    conv_load<4, 0, 9>(c, q);
    conv_selectors8(c);
    wg_wait0();
    conv_rename<8>(acc);
    conv_frag<4, 0, 4>(c, q, a, DEP);
    wg_fence(); conv_mma<4, 8, 0, 4>(acc, c, a); GO();
    const Pk k = pk2(acc[6], acc[7]);
    park(SLOT(6), k); park(c.ps, k);
    conv_load<5, 0, 9>(c, q);
    flush_setup(c);
    wg_wait0();
    conv_rename<10>(acc);
    conv_frag<5, 0, 4>(c, q, a, DEP);
    wg_fence(); conv_mma<5, 10, 0, 4>(acc, c, a); GO();
    park(SLOT(8), pk2(acc[8], acc[9]));
    bar_sync(bid, 128);
    flush_load<1>(c, pl, f);
    mbar_wait(rx);
    conv_flush<1, 2>(c, f, gy, rx);
    wg_wait0();
    bar_sync(bid, 128);
    park(SLOT(10), pk2(acc[10], acc[11])); park(SLOT(12), pk2(acc[12], acc[13])); park(SLOT(14), pk2(acc[14], acc[15]));
    bar_sync(bid, 128);
    flush_load<3>(c, pl, f); flush_load<2>(c, pl, f2);
    mbar_wait(rx + 8);
    conv_flush<3, 2>(c, f, gy, rx);
    conv_flush<2, 2>(c, f2, gy, rx);
}
#undef SLOT
#undef GO
#undef DEP
template <int U0, int U1>
__device__ __forceinline__ void weight_units(uint32_t sb, const CUtensorMap* tg, const CUtensorMap* tu, const CUtensorMap* td, bool w) {
    if (U1 > U0 && w && elect_one()) {
#pragma unroll
        for (int n = U0; n < U1; n++) {
            const int i = n;
            if (i < 12) tma_2d(sb + SM_WG + i * 6912, i < 6 ? tg : tu, 72 * (blockIdx.x >> 1), 288 * (blockIdx.x & 1) + (i % 6) * 48, sb + SM_MISC + 328);
            else tma_2d(sb + SM_WD + (i - 12) * 4736, td, 144 * (blockIdx.x & 1), 72 * (blockIdx.x >> 1) + 8 * (i - 12), sb + SM_MISC + 336);
        }
    }
}
#define WS 1111121111122103100
__device__ constexpr int wsched(int i) {
    unsigned long long v = WS;
    int n = 0;
    for (int k = 19; k >= 1; k--) { if (k < i) n += (int)(v % 10); v /= 10; }
    return n;
}
static_assert(wsched(20) == 21 && wsched(6) <= 7 && wsched(11) <= 12 && wsched(16) <= 17, "");
__device__ __forceinline__ void weight_prefetch(const Params& p, int u, int lane) {
    const int b = blockIdx.x;
    const char* a = u < 12 ? reinterpret_cast<const char*>(u < 6 ? p.wg : p.wu) + ((b >> 6) * 288 + (u % 6) * 48) * (FF * 2) + (b & 63) * 6912
                           : reinterpret_cast<const char*>(p.wd) + (72 * (b >> 1) + 8 * (u - 12)) * 1152 + (b & 1) * 4608;
    asm volatile("prefetch.global.L2 [%0];\n" ::"l"(a + lane * 128));
    if (lane < (u < 12 ? 22 : 4)) asm volatile("prefetch.global.L2 [%0];\n" ::"l"(a + 4096 + lane * 128));
}
#define PF0 0
#define PF1 0
#define WPOINT(i, w) do { weight_units<wsched(i), wsched(i + 1)>(sb, &tm_g, &tm_u, &tm_d, w); } while (0)

__global__ void __launch_bounds__(NTHR, 1) __cluster_dims__(2, 1, 1)
fused_kernel(const Params p, const __grid_constant__ CUtensorMap tm_g, const __grid_constant__ CUtensorMap tm_u, const __grid_constant__ CUtensorMap tm_d, const __grid_constant__ CUtensorMap tm_x) {
    extern __shared__ __align__(1024) unsigned char smem[];
    const uint32_t sb = smem_u32(smem);
    const int tid = threadIdx.x, warp = __shfl_sync(0xffffffffu, tid >> 5, 0), lane = tid & 31;
    const int b = blockIdx.x, P = b >> 1, odd = b & 1;
    const int g = lane >> 2, t = lane & 3;
    const int wg = warp >> 2, t128 = tid & 127;
    const uint32_t s_stat = sb + SM_MISC;
    const uint32_t s_key = sb + SM_MISC + 128;
    const uint32_t s_wm = sb + SM_MISC + 160;
    const uint32_t s_k16 = sb + SM_MISC + 192;
    const uint32_t s_cnt = sb + SM_MISC + 320;
    const uint32_t bar_w = sb + SM_MISC + 328, bar_d = bar_w + 8, bar_g = bar_w + 16, bar_x = bar_w + 24, bar_t = bar_w + 32;
    STAMP(0);

    if (warp == 19) {
        if (lane == 0) {
            mbar_init(bar_w, 1); mbar_init(bar_d, 1); mbar_init(bar_g, 1); mbar_init(sb + SM_RX, 1); mbar_init(sb + SM_RX + 8, 1);
            mbar_init(bar_x, 1); mbar_init(bar_t, 1); mbar_expect(bar_x, 32768);
            asm volatile("fence.mbarrier_init.release.cluster;\n" ::: "memory");
            mbar_expect(bar_w, 82944); mbar_expect(bar_d, 72 * WD_PITCH); mbar_expect(bar_g, 9216); mbar_expect(bar_t, 18 * 1152); mbar_expect(sb + SM_RX, 1024); mbar_expect(sb + SM_RX + 8, 2048); sts32(s_cnt, 0);
        }
        __syncwarp();
    } else if (warp == 18) {
#pragma unroll
        for (int i = 0; i < 9; i++) sts128(sb + SM_ZERO + (i * 32 + lane) * 16, 0u, 0u, 0u, 0u);
        fence_async();
        __syncwarp();
    }
    const int ch = wg < 4 ? 4 * b + wg : 512 + P;
    const bf16 *q0 = p.lar + ch * NST, *q1 = p.aim + ch * NST, *q2 = p.cre + ch * NST, *q3 = p.cim + ch * NST;
    asm volatile("" : "+l"(q0), "+l"(q1), "+l"(q2), "+l"(q3));
    const uint32_t ldt = ldo16(p.ldt + ch), pl = ldo16(q0 + t128), pa2 = ldo16(q1 + t128);
    const uint32_t pc = ldo16(q2 + t128), pi = ldo16(q3 + t128);
    const uint2 call_re = ldo64(q2 + 4 * lane), call_im = ldo64(q3 + 4 * lane);
    if (PBAR) { if (wg == 4) bar_sync(0, NWRK); else bar_arrive(0, NWRK); }
    uint4 xv[9], xu[2];
    if (wg == 4) {
        const bf16* xp = p.x + (size_t)(16 * b + 4 * (warp & 3) + (g & 3)) * DM + 288 * (g >> 2) + 8 * t;
#pragma unroll
        for (int c = 0; c < 9; c++) xv[c] = ldo128(xp + c * 32);
        if (warp < 18) {
            const bf16* xq = p.x + (size_t)(16 * b + TOK(g)) * DM + 32 * warp + 8 * t;
            xu[0] = ldo128(xq); xu[1] = ldo128(xq + 2 * DM);
        }
    }
    auto resets = [&](int z) {
        if (lane < 2) bulk_s2g(lane ? reinterpret_cast<unsigned char*>(p.s->sc) + b * 32 : reinterpret_cast<unsigned char*>(p.s->y) + 96 * 18432 + b * 4608 + z, sb + SM_ZERO, lane ? 32 : 4608);
        __syncwarp();
    };
    auto xcols = [&](int z) {
        if (MC) {
            asm volatile("barrier.cluster.wait.aligned;\n" ::: "memory");
            if (elect_one()) tma_4d_mc(sb + SM_XC + odd * 16384, &tm_x, 8 * P + z, 2 * odd, bar_x);
        } else if (elect_one()) tma_4d(sb + SM_XC, &tm_x, 8 * P + z, 0, bar_x);
        __syncwarp();
    };
    if (MC) asm volatile("barrier.cluster.arrive.relaxed.aligned;\n" ::: "memory");
    if (warp == 18) { resets(0); bar_arrive(12, 64); }
    if (warp == 19) { bar_sync(12, 64); xcols(0); }
    const uint32_t kw = sb + SM_KW + wg * KW_B;
    const uint32_t tb = table_buf(sb, warp);
    if (wg == 4) {
        const int wq = warp & 3;
        const uint32_t epl = ld_poll32(p.s->hint + (b & 7) * 32 + 1);
        unsigned char* const ud = reinterpret_cast<unsigned char*>(p.s->uT) + (size_t)(8 * wq + 2 * (g >> 1)) * 16384 + b * 128 + (g & 1) * 32 + t * 8;
        uint32_t* const sd_ = p.s->stat + 16 * b + 4 * wq + g;
        const bool own = g < 4 && t == (g >> 1);
        if (own) *reinterpret_cast<volatile uint32_t*>(sd_) = 0u;
        if (wq < 2) {
#pragma unroll
            for (int k = 0; k < 4; k++) *reinterpret_cast<volatile unsigned long long*>(ud + (k >> 1) * 16384 + (k & 1) * 64) = 0ull;
        }
        if (wq == 1) conv_constants(sb + SM_LC, lane);
        uint32_t one;
        asm volatile("st.volatile.shared.u32 [%1], 0x3f803f80;\nld.volatile.shared.u32 %0, [%1];\n" : "=r"(one) : "r"(tb + lane * 4) : "memory");
        float cs[2][4] = {}, d1[2][4] = {}, d2[2][4] = {};
#pragma unroll
        for (int c = 0; c < 9; c++) {
            const uint4 v = xv[c];
            mma_bf16(cs[c & 1], v.x, v.y, v.z, v.w, one, one);
            mma_bf16(d1[c & 1], v.x, v.y, v.z, v.w, v.x, v.z); mma_bf16(d2[c & 1], v.x, v.y, v.z, v.w, v.y, v.w);
        }
        STAMP(27);
        float sm = (cs[0][0] + cs[0][2]) + (cs[1][0] + cs[1][2]);
        float sq = (g & 1) ? (d1[0][1] + d2[0][3]) + (d1[1][1] + d2[1][3]) : (d1[0][0] + d2[0][2]) + (d1[1][0] + d2[1][2]);
        sm += __shfl_xor_sync(0xffffffffu, sm, 18); sq += __shfl_xor_sync(0xffffffffu, sq, 18);
        if (HOLD == 1) bar_arrive(6 + wq, 160);
        float mb, sd;
        ln_stats(sm, sq, mb, sd);
        if (own) *sd_ = (__float_as_uint(mb) >> 16) | (__float_as_uint(sd) & 0x7fff0000u) | (epl << 31);
        STAMPX(22);
        if (wq < PF0) weight_prefetch(p, wq, lane);
        if (HOLD == 2) bar_arrive(6 + wq, 160);
        if (own) stat_store(s_stat + (2 * wq + (g & 1) + 8 * (g >> 1)) * 8, mb, rcp_approx(sd), 0u);
        if (lane == 1) sts32(s_cnt + 4, epl);
        if (wq == 2) asm volatile("cp.async.bulk.wait_group 0;\n" ::: "memory");
        bar_sync(5, 128);
        STAMP(28);
        if (wq >= 2) { bar_arrive(2 * wq - 3, 160); bar_arrive(2 * wq - 2, 160); }
        WPOINT(1, wq == 3);
        if (wq < 2) {
            const uint32_t utag = (epl % 7u + 1u) * 0x10001u;
            uint32_t U[2][4];
#pragma unroll
            for (int hf = 0; hf < 2; hf++) {
                const uint2 st = lds64(s_stat + (g + 8 * hf) * 8);
                const uint32_t X[4] = {xu[hf].x, xu[hf].y, xu[hf].z, xu[hf].w};
#pragma unroll
                for (int k = 0; k < 4; k++) {
                    const uint32_t u = ln_apply(X[k], STAT_M(st), STAT_H(st), STAT_L(st));
                    U[hf][k] = movm((pack_f16(bf_lo(u), bf_hi(u)) & 0xfff8fff8u) | utag);
                }
            }
#pragma unroll
            for (int k = 0; k < 4; k++) stg64(ud + (k >> 1) * 16384 + (k & 1) * 64, U[0][k], U[1][k]);
        }
    } else if (warp == 0) {
#pragma unroll
        for (int i = 0; i < 7; i++) sts128(sb + SM_LNP + (i * 32 + lane) * 16, 0u, 0u, 0u, 0u);
    }
    if (t128 < 2 * UPAD) sts128(sb + SM_U + wg * USLOT_B + (t128 & 1) * ULO_B + (t128 >> 1) * 16, 0u, 0u, 0u, 0u);
    if (t128 >= 124) sts128(kw + (t128 & 1) * 16 + (t128 & 2) * (KW_PL / 2), 0u, 0u, 0u, 0u);
    uint32_t co, cn, cd;
    combine_setup(sb, warp, lane, kw, co, cn, cd);
    const uint4* usrc = wg < 4 ? reinterpret_cast<const uint4*>(p.s->stat) + tid
                               : reinterpret_cast<const uint4*>(p.s->uT) + (P >> 2) * 1024 + (t128 >> 1) * 8 + (P & 3) * 2 + (t128 & 1);
    uint32_t zero;
    {
        uint32_t uo = (uint32_t)(reinterpret_cast<const char*>(usrc) - reinterpret_cast<const char*>(p.s)), pk = (cn - co + 1024) | ((cd - kw) << 16);
        asm volatile("st.volatile.shared.v4.u32 [%4], {0, %1, %2, %3};\nld.volatile.shared.v4.u32 {%0, %1, %2, %3}, [%4];\n" : "=r"(zero), "+r"(co), "+r"(pk), "+r"(uo) : "r"(tb + lane * 16) : "memory");
        cn = co + (pk & 0xffffu) - 1024; cd = kw + (pk >> 16);
        usrc = reinterpret_cast<const uint4*>(reinterpret_cast<const char*>(p.s) + uo);
    }
    const float dt = exp_bf(__uint_as_float(__byte_perm(ldt, zero, 0x1044)));
    STAMP(1);
    if (wg < 4) { STAMPX(16); }
    KGen kg;
    kgen_setup(kg, __uint_as_float(__byte_perm(pl, zero, 0x1044)), __uint_as_float(__byte_perm(pa2, zero, 0x1044)), dt);
    kgen_rows(kg, tb, lane);
    STAMP(2);
    const int E = min(max(c_exponent(call_re, call_im, dt) - 243, -120), 120);
    kgen_chain(kg, pc, pi, dt * __uint_as_float((uint32_t)(128 - E) << 23));
    STAMP(3);
    WPOINT(2, warp == 19);
    kgen_cols(kg, tb, lane);
    STAMP(4);
    WPOINT(3, warp == 19);
    if (wg < 4) { STAMPX(17); }
    if (HOLD && wg < 4) bar_sync(6 + (warp & 3), 160);
    if (wg < 4) { STAMPX(19); }
    kgen_mma(kg, tb, lane);
    if (wg < 4) { STAMPX(20); }
    STAMP(5);
    WPOINT(4, warp == 19);
    if (wg < 4) bar_sync(1 + wg, 160); else bar_sync(5, 128);
    if (wg < 4) { STAMPX(21); }
    uint4 uv0, uv1;
    if (PEARLY) { uv0 = ld_poll(usrc); if (wg == 4) uv1 = ld_poll(usrc + 512); }
    kgen_combine(warp & 3, lane, co, cn, cd);
    const uint32_t ep = lds32(s_cnt + 4);
    if (!PEARLY) { uv0 = ld_poll(usrc); if (wg == 4) uv1 = ld_poll(usrc + 512); }
    STAMP(6);
    if (wg < 4) { STAMPX(18); }
    WPOINT(5, warp == 19);
    if (MC && warp != 19) asm volatile("barrier.cluster.wait.aligned;\n" ::: "memory");
    {
        const int wq = warp & 3;
        Conv c;
        const uint32_t pln = sb + SM_PL + wg * PL_B;
        const int e = g - 2 * t + 7;
        c.kw = kw; c.wa = kw + ((e >> 2) & 1) * KW_PL + (8 * wq + (e >> 3)) * 16 + (e & 3) * 4;
        c.ps = mov_v(pln + wq * PLW_B + ((lane >> 3) & 1) * PL_HALF + ((lane >> 4) * 8 + (lane & 7)) * 16); c.warp = warp;
        c.lc = sb + SM_LC; c.fs = (uint32_t)(127 + E) * 0x800080u;
        c.d0 = ((uint64_t)(ULO_B >> 4) << 16) | ((uint64_t)(128 >> 4) << 32) | (uint64_t)(((sb + SM_U + wg * USLOT_B + UPAD * 16) & 0x3FFFF) >> 4);
        unsigned char* gy = reinterpret_cast<unsigned char*>(p.s->y) + ((size_t)(4 * wq) * DM + ch) * 64;
        auto hook = [&](auto gi) {
                     constexpr int G = decltype(gi)::value;
                     if (G == (wg_is4<decltype(gi)>() ? 2 : 5)) asm volatile("barrier.cluster.wait.aligned;\n" ::: "memory");
                     if (G == 0 && warp == HW) {
                         const int l2 = lane_v();
                         if (l2 < (b < 72 ? 7 : 2))
                             bulk_s2g(l2 < 2 ? reinterpret_cast<unsigned char*>(p.s->rows) + b * 4608 + l2 * 2304 : reinterpret_cast<unsigned char*>(p.s->part) + b * 16384 + (l2 - 2) * 3200,
                                      sb + SM_LNP, l2 < 2 ? 2304 : 3584);
                         __syncwarp();
                     }
                     if (!wg_is4<decltype(gi)>() && PF1 && G >= PF1 && G < PF1 + 2 && (warp >> 1) == 2) weight_prefetch(p, 17 + 2 * (G - PF1) + (warp & 1), lane_v());
                     if (!wg_is4<decltype(gi)>()) WPOINT(6 + G, warp == 12 + (G & 3));
                     if (!wg_is4<decltype(gi)>() && G == XG && warp == 11 && elect_one()) {
                         bulk_g2s(sb + SM_XT, p.x + (size_t)16 * b * DM, 16 * 1152, bar_t);
                         bulk_g2s(sb + SM_XT + 16 * 1152, p.dsk, 1152, bar_t);
                         bulk_g2s(sb + SM_XT + 17 * 1152, p.wr, 1152, bar_t);
                     }
                 };
        bar_sync(1 + wg, 128);
        if (wg < 4) {
            asm volatile("barrier.cluster.arrive.relaxed.aligned;\n" ::: "memory");
            conv_run(c, pln + wq * 128, gy, hook, [&]() {
                STAMPX(23);
                mbar_wait(bar_x);
                STAMP(9);
                STAMPX(24);
                uint2 xc[4];
                uint32_t xw[4][2];
#pragma unroll
                for (int j = 0; j < 4; j++) xc[j] = lds64(sb + SM_XC + wg * 8192 + j * 2048 + t128 * 16 + odd * 8);
#pragma unroll
                for (int i = 0; i < 8; i++) {
                    const int k = i >> 1, h = i & 1;
                    xw[k][h] = prmt_v(k < 2 ? xc[2 * h].x : xc[2 * h].y, k < 2 ? xc[2 * h + 1].x : xc[2 * h + 1].y, (k & 1) ? 0x7632 : 0x5410);
                }
                const uint32_t ub = mov_v(sb + SM_U + UPAD * 16 + ((tid >> 1) & 1) * ULO_B + (tid >> 2) * 16 + (tid & 1) * 8), tag = ep << 31;
                int it = 0;
                while (min(min((int)(uv0.x ^ tag), (int)(uv0.y ^ tag)), min((int)(uv0.z ^ tag), (int)(uv0.w ^ tag))) < 0x10000) {
                    if (++it > SPIN_LIMIT) TRAP();
                    uv0 = ld_poll(usrc);
                }
                STAMP(8);
                STAMPX(26);
                const float r0 = rcp_approx(fabsf(bf_hi(uv0.x))), r1 = rcp_approx(fabsf(bf_hi(uv0.y))), r2 = rcp_approx(fabsf(bf_hi(uv0.z))), r3 = rcp_approx(fabsf(bf_hi(uv0.w)));
                const uint32_t m[2] = {__byte_perm(uv0.x, uv0.y, 0x5410), __byte_perm(uv0.z, uv0.w, 0x5410)};
                const uint32_t rh[2] = {pack_bf16(r0, r1), pack_bf16(r2, r3)};
                const uint32_t rl[2] = {pack_bf16(r0 - bf_lo(rh[0]), r1 - bf_hi(rh[0])), pack_bf16(r2 - bf_lo(rh[1]), r3 - bf_hi(rh[1]))};
#pragma unroll
                for (int k = 0; k < 4; k++) {
                    const uint32_t u0 = ln_apply(xw[k][0], m[0], rh[0], rl[0]), u1 = ln_apply(xw[k][1], m[1], rh[1], rl[1]);
                    sts64(ub + k * USLOT_B, pack_f16(bf_lo(u0), bf_hi(u0)), pack_f16(bf_lo(u1), bf_hi(u1)));
                }
                STAMPX(29);
                fence_async();
                bar_sync(14, 512);
                STAMP(7);
            });
        } else {
            auto stage = [&]() {
                const uint32_t tag = (ep % 7u + 1u) * 0x10001u;
                int it = 0;
                while (true) {
                    uv0.x ^= tag; uv0.y ^= tag; uv0.z ^= tag; uv0.w ^= tag; uv1.x ^= tag; uv1.y ^= tag; uv1.z ^= tag; uv1.w ^= tag;
                    if ((((uv0.x | uv0.y | uv0.z) | (uv0.w | uv1.x | uv1.y) | (uv1.z | uv1.w)) & 0x70007u) == 0) break;
                    if (++it > SPIN_LIMIT) TRAP();
                    uv0 = ld_poll(usrc); uv1 = ld_poll(usrc + 512);
                }
                STAMP(8);
                const uint32_t ub = sb + SM_U + UPAD * 16 + 4 * USLOT_B + (t128 & 1) * ULO_B + (t128 >> 1) * 16;
                sts128(ub, uv0.x, uv0.y, uv0.z, uv0.w);
                sts128(ub + 1024, uv1.x, uv1.y, uv1.z, uv1.w);
                fence_async();
                asm volatile("barrier.cluster.arrive.relaxed.aligned;\n" ::: "memory");
                bar_sync(5, 128);
                STAMP(7);
            };
            stage();
            if (odd) conv_inner(c, pln + wq * 128, gy, sb + SM_RX, hook);
            else conv_outer(c, pln + wq * 128, gy, sb + SM_RX, hook);
        }
        STAMP(10);
    }
    {
    const int warp = warp_v(), lane = lane_v(), tid = 32 * warp + lane, g = lane >> 2, t = lane & 3;
    uint4 wr = make_uint4(0u, 0u, 0u, 0u);
    if (warp == HW) asm volatile("cp.async.bulk.wait_group 0;\n" ::: "memory");
    bar_sync(0, NWRK);
    STAMP(11);
    WPOINT(15, warp == 18);
    uint32_t H[2][4], U2[2][4] = {};
    uint32_t WA[9][4];
    auto load_wa = [&]() {
        mbar_wait(bar_w);
        const int mi = lane >> 3, rr = lane & 7;
        const uint32_t aad = sb + SM_WG + (mi & 1) * SM_WU + ((warp & 1) * 144 + rr + 8 * (mi >> 1)) * W_PITCH + (warp >> 1) * 16;
#pragma unroll
        for (int k = 0; k < 9; k++) ldsm_x4_t(WA[k][0], WA[k][1], WA[k][2], WA[k][3], aad + k * 16 * W_PITCH);
    };
    if (warp < 18) {
        const unsigned char* ys = reinterpret_cast<const unsigned char*>(p.s->y) + ((size_t)P * DM + 32 * warp + 8 * (g >> 1) + (g & 1)) * 64 + odd * 32 + t * 8;
        uint2 yv[4];
#pragma unroll
        for (int k = 0; k < 4; k++) yv[k] = ld_poll64(ys + k * 128);
        mbar_wait(bar_t);
        const uint32_t xa = sb + SM_XT + warp * 64 + t * 16;
        const uint4 x0 = lds128(xa + TOK(g) * 1152), x1 = lds128(xa + (TOK(g) + 2) * 1152), dk = lds128(xa + 16 * 1152);
        if (g == 0) wr = lds128(xa + 17 * 1152);
        const uint32_t Z[2][4] = {{x0.x, x0.y, x0.z, x0.w}, {x1.x, x1.y, x1.z, x1.w}}, D4[4] = {dk.x, dk.y, dk.z, dk.w};
#pragma unroll
        for (int hf = 0; hf < 2; hf++) {
            const uint2 st = lds64(s_stat + (g + 8 * hf) * 8);
#pragma unroll
            for (int k = 0; k < 4; k++) H[hf][k] = hmul2_bf(ln_apply(Z[hf][k], STAT_M(st), STAT_H(st), STAT_L(st)), D4[k]);
        }
        int it = 0;
        while (!__all_sync(0xffffffffu, yv[0].x && yv[0].y && yv[1].x && yv[1].y && yv[2].x && yv[2].y && yv[3].x && yv[3].y)) {
#pragma unroll
            for (int k = 0; k < 4; k++) yv[k] = ld_poll64(ys + k * 128);
            if (++it > SPIN_LIMIT) TRAP();
        }
        STAMP(12);
        const uint32_t one = g == 0 ? 0x3f803f80u : 0u;
        const uint32_t WR[4] = {one, one, one, one};
#pragma unroll
        for (int k = 0; k < 4; k++) {
            H[0][k] = hadd2_bf(Z[0][k], hadd2_bf(movm(yv[k].x ^ YKEY), H[0][k]));
            H[1][k] = hadd2_bf(Z[1][k], hadd2_bf(movm(yv[k].y ^ YKEY), H[1][k]));
        }
        ln_partial(H, WR, sb + SM_LNP, warp, g, t);
    } else if (warp == 19) {
#pragma unroll 1
        for (int i = lane; i < 520; i += 32) sts128(sb + SM_CAND + i * 16, 0u, 0u, 0u, 0u);
#pragma unroll 1
        for (int i = lane; i < 288; i += 32) sts128(sb + SM_ZERO + i * 16, 0u, 0u, 0u, 0u);
        fence_async();
    }
    bar_sync(0, NWRK);
    STAMP(13);
    WPOINT(16, warp == 19);
    if (warp == 18) {
        float mb, rc;
        ln_finish(sum18(sb + SM_LNP + lane * 80), lane, mb, rc);
        if (lane < 16) stat_store(s_stat + lane * 8, mb, rc, 0u);
    }
    bar_sync(0, NWRK);
    STAMP(14);
    WPOINT(17, warp == 19);
    auto publish = [&](bool hi, int slot) {
        uint4* rowp = reinterpret_cast<uint4*>(p.s->rows) + slot * 144 + warp * 4 + t;
        stg128(rowp, nzw(hi ? U2[1][0] : U2[0][0]), nzw(hi ? U2[1][1] : U2[0][1]), nzw(hi ? U2[1][2] : U2[0][2]), nzw(hi ? U2[1][3] : U2[0][3]));
        stg128(rowp + 72, nzw(hi ? H[1][0] : H[0][0]), nzw(hi ? H[1][1] : H[0][1]), nzw(hi ? H[1][2] : H[0][2]), nzw(hi ? H[1][3] : H[0][3]));
    };
    uint4 kv = make_uint4(1, 1, 1, 1);
    const uint4* ksrc = reinterpret_cast<const uint4*>(p.s->sc) + tid;
    if (warp < 18) {
#pragma unroll
        for (int hf = 0; hf < 2; hf++) {
            const uint2 st = lds64(s_stat + (g + 8 * hf) * 8);
#pragma unroll
            for (int k = 0; k < 4; k++) U2[hf][k] = ln_apply(H[hf][k], STAT_M(st), STAT_H(st), STAT_L(st));
        }
        {
            float cs[4] = {0.f, 0.f, 0.f, 0.f};
            mma_bf16(cs, U2[0][0], U2[1][0], U2[0][1], U2[1][1], wr.x, wr.y);
            mma_bf16(cs, U2[0][2], U2[1][2], U2[0][3], U2[1][3], wr.z, wr.w);
            if (t == 0) { stsf(sb + SM_LNP + ((32 + g) * 20 + warp) * 4, cs[0]); stsf(sb + SM_LNP + ((40 + g) * 20 + warp) * 4, cs[2]); }
            bar_arrive(10, 608);
        }
        bar_sync(11, 608);
#pragma unroll
        for (int hf = 0; hf < 2; hf++)
            sts128(sb + SM_OUT + (TOK(g) + 2 * hf) * (DM * 2) + warp * 64 + t * 16,
                   hadd2_bf(H[hf][0], U2[hf][0]), hadd2_bf(H[hf][1], U2[hf][1]), hadd2_bf(H[hf][2], U2[hf][2]), hadd2_bf(H[hf][3], U2[hf][3]));
        fence_async();
        bar_arrive(9, 608);
        if (tid < 256) kv = ld_poll(ksrc);
        const uint32_t rk[2] = {lds32(s_wm + 32 + 64 + g * 4), lds32(s_wm + 32 + 64 + 32 + g * 4)};
        uint32_t lo = min(rk[0], rk[1]), hi = max(rk[0], rk[1]);
#pragma unroll 1
        while (lo < EARLYN) { publish(lo == rk[1], 2 * b + lo); lo = hi; hi = 16; }
        if (warp >= 8) load_wa();
    } else if (warp == 18) {
        bar_sync(10, 608);
        const float r = sum18(sb + SM_LNP + (32 + (lane & 15)) * 80);
        const uint32_t bits = pack_bf16(r, 0.f) & 0xffffu;
        const uint32_t k = max((bits & 0x8000u) ? (~bits & 0xffffu) : (bits | 0x8000u), 1u);
        const uint32_t me = (k << 16) | (uint32_t)(15 - ROWTOK(lane & 15));
        if (lane < 16) {
            p.s->sc[16 * b + ROWTOK(lane)] = (unsigned short)k;
            sts32(s_k16 + lane * 4, me);
        }
        __syncwarp();
        int rank = 0;
#pragma unroll
        for (int q = 0; q < 4; q++) {
            const uint4 v = lds128(s_k16 + q * 16);
            rank += (v.x > me) + (v.y > me) + (v.z > me) + (v.w > me);
        }
        if (lane < 16) sts32(s_wm + 32 + 64 + lane * 4, rank);
        bar_arrive(11, 608);
    } else if (warp == 19) {
        bar_sync(9, 608);
        if (lane == 0) bulk_s2g(p.out + (size_t)16 * b * DM, sb + SM_OUT, 16 * DM * 2);
        __syncwarp();
        WPOINT(18, true);
        __nanosleep(WDLY);
        WPOINT(19, true);
    }
    STAMP(15);
    uint32_t kmax = 0;
    if (tid < 256) {
        int it = 0;
        while (true) {
            const uint32_t mn = __vminu2(__vminu2(kv.x, kv.y), __vminu2(kv.z, kv.w));
            if ((mn & 0xffffu) && (mn >> 16)) break;
            if (++it > SPIN_LIMIT) TRAP();
            kv = ld_poll(ksrc);
        }
        const uint32_t mx = __vmaxu2(__vmaxu2(kv.x, kv.y), __vmaxu2(kv.z, kv.w));
        kmax = max(mx & 0xffffu, mx >> 16);
        const uint32_t m = __reduce_max_sync(0xffffffffu, kmax);
        if (lane == 0) sts32(s_wm + warp * 4, m);
    }
    if (warp < 8) bar_sync(8, 256);
    STAMP2(16);
    if (tid < 256) {
        const uint4 m0 = lds128(s_wm), m1 = lds128(s_wm + 16);
        const uint32_t T = min(min(min(m0.x, m0.y), min(m0.z, m0.w)), min(min(m1.x, m1.y), min(m1.z, m1.w)));
        if (kmax >= T) {
            const uint32_t kk[4] = {kv.x, kv.y, kv.z, kv.w};
            uint32_t m = 0;
#pragma unroll
            for (int i = 0; i < 8; i++) m |= (((i & 1) ? kk[i >> 1] >> 16 : kk[i >> 1] & 0xffffu) >= T ? 1u : 0u) << i;
            uint32_t pos;
            asm volatile("atom.shared.add.u32 %0, [%1], %2;\n" : "=r"(pos) : "r"(s_cnt), "r"(__popc(m)) : "memory");
            pos = sb + SM_CAND + pos * 4;
#pragma unroll 1
            while (m) {
                const int i = __ffs(m) - 1;
                m &= m - 1;
                const uint32_t w = (i & 4) ? ((i & 2) ? kv.w : kv.z) : ((i & 2) ? kv.y : kv.x);
                sts32(pos, __byte_perm(w, 2047 - 8 * tid - i, (i & 1) ? 0x3254 : 0x1054));
                pos += 4;
            }
        }
    }
    if (warp < 8) bar_sync(8, 256);
    STAMP2(17);
    if (warp < 8) {
        const int n = (int)lds32(s_cnt);
#pragma unroll 1
        for (int i = tid; i < n; i += 256) {
            const uint32_t k = lds32(sb + SM_CAND + i * 4);
            int r0 = 0, r1 = 0;
            int j = 0;
#pragma unroll 1
            do {
#pragma unroll
                for (int q = 0; q < 4; q++) {
                    const uint4 v = lds128(sb + SM_CAND + (j + 4 * q) * 4);
                    r0 += (v.x > k) + (v.y > k); r1 += (v.z > k) + (v.w > k);
                }
                j += 16;
            } while (j < n && r0 + r1 < NSEL);
            if (r0 + r1 < NSEL) sts32(s_key + (r0 + r1) * 4, k);
        }
    }
    bar_sync(0, NWRK);
    STAMP2(18);
    const int gs = tid / 36;
    int slot, tok;
    {
        const uint4 ka = lds128(s_key), kb = lds128(s_key + 16);
        const uint32_t k = lds32(s_key + (lane & 7) * 4);
        tok = 2047 - (int)(k & 0x7ffu);
#define SAME(v) ((v) > k && (((v) ^ k) & 0x7f0u) == 0)
        const int lr = (SAME(ka.x) + SAME(ka.y)) + (SAME(ka.z) + SAME(ka.w)) + (SAME(kb.x) + SAME(kb.y)) + SAME(kb.z);
#undef SAME
        slot = lr < EARLYN ? 2 * (tok >> 4) + lr : 2 * NCTA + (lane & 7);
        const uint32_t late = __ballot_sync(0xffffffffu, lr >= EARLYN) & 0xffu;
        if (late) {
            const uint32_t ep = lds32(s_cnt + 4);
            const bool mine = lr >= EARLYN && (tok >> 4) == b;
            uint32_t todo = __ballot_sync(0xffffffffu, mine) & 0xffu;
            if (todo) {
#pragma unroll 1
                while (todo) {
                    const int s = __ffs(todo) - 1, tk = __shfl_sync(0xffffffffu, tok, s);
                    todo &= todo - 1;
                    if (warp < 18 && (tk & 13) == TOK(g)) publish(tk & 2, 2 * NCTA + s);
                }
                __threadfence();
                bar_sync(0, NWRK);
                if (tid < NSEL && mine) *reinterpret_cast<volatile unsigned*>(p.s->flag + tid) = ep + 1u;
            }
            int it = 0;
            while (__any_sync(0xffffffffu, lr >= EARLYN && ld_poll32(p.s->flag + (lane & 7)) != ep + 1u)) { if (++it > SPIN_LIMIT) TRAP(); }
            __threadfence();
        }
    }
    const uint4* src0 = reinterpret_cast<const uint4*>(p.s->rows) + __shfl_sync(0xffffffffu, slot, gs & 7) * 144 + 36 * odd + (tid - gs * 36);
    uint4 v0 = make_uint4(1, 1, 1, 1);
    if (tid < 288) v0 = ld_poll(src0);
    uint32_t WD[18];
    if (warp < 18) {
        if (warp < 8) load_wa();
        mbar_wait(bar_d);
        const int mi = lane >> 3, rr = lane & 7;
        const uint32_t base = sb + SM_WD + (2 * warp + (mi & 1)) * 16 + rr * WD_PITCH;
#pragma unroll
        for (int k = 0; k < 4; k++) ldsm_x4_t(WD[4 * k], WD[4 * k + 1], WD[4 * k + 2], WD[4 * k + 3], base + (k * 16 + 8 * (mi >> 1)) * WD_PITCH);
        ldsm_x2_t(WD[16], WD[17], base + 64 * WD_PITCH);
    }
    float hv = 0.f, u2 = 0.f, rs = 0.f;
    const int fl = 16 * (b & 1) + ((tid >> 2) & 15), fc = 16 * (b >> 1) + (fl >> 2) + 8 * ((tid >> 1) & 1), fsl = 2 * (fl & 3) + (tid & 1);
    int ftok = 0;
    if (warp >= 18) {
        const int fslot = __shfl_sync(0xffffffffu, slot, fsl);
        if (b < 72) {
            const uint32_t kk = lds32(s_key + fsl * 4);
            ftok = 2047 - (int)(kk & 0x7ffu);
            uint32_t hw, uw;
            int it = 0;
            do {
                hw = ld_poll32(p.s->rows + fslot * DM + 288 + (fc >> 1)); uw = ld_poll32(p.s->rows + fslot * DM + (fc >> 1));
                if (++it > SPIN_LIMIT) TRAP();
            } while (!hw || !uw);
            const unsigned k16 = kk >> 16;
            const unsigned bits = (k16 & 0x8000u) ? (k16 & 0x7fffu) : (~k16 & 0xffffu);
            rs = rbf(__fdividef(1.0f, 1.0f + __expf(-__uint_as_float(bits << 16))));
            hv = (fc & 1) ? bf_hi(hw) : bf_lo(hw);
            u2 = (fc & 1) ? bf_hi(uw) : bf_lo(uw);
        }
    } else if (warp < 9) {
        int it = 0;
        while (!all_nz(v0)) {
            if (++it > SPIN_LIMIT) TRAP();
            v0 = ld_poll(src0);
        }
        sts128(sb + SM_XS + gs * XS_PITCH + (tid - gs * 36) * 16, v0.x, v0.y, v0.z, v0.w);
    }
    bar_sync(0, NWRK);
    STAMP2(19);
    if (warp < 18) {
        float c4[3][4];
#pragma unroll
        for (int i = 0; i < 3; i++)
#pragma unroll
            for (int j = 0; j < 4; j++) c4[i][j] = 0.f;
        const uint32_t bad = sb + SM_XS + (lane & 7) * XS_PITCH + ((warp & 1) * 144 + 8 * (lane >> 3)) * 2;
#pragma unroll
        for (int k = 0; k < 9; k += 2) {
            uint32_t b0, b1, b2, b3;
            ldsm_x4(b0, b1, b2, b3, bad + k * 32);
            mma_bf16(c4[k % 3], WA[k][0], WA[k][1], WA[k][2], WA[k][3], b0, b1);
            if (k < 8) mma_bf16(c4[(k + 1) % 3], WA[k + 1][0], WA[k + 1][1], WA[k + 1][2], WA[k + 1][3], b2, b3);
        }
        const uint32_t ex = sb + SM_EX + (2 * odd + (warp & 1)) * 4608 + (warp >> 1) * 512 + lane * 16;
        const float e4[4] = {c4[0][0] + c4[1][0] + c4[2][0], c4[0][1] + c4[1][1] + c4[2][1], c4[0][2] + c4[1][2] + c4[2][2], c4[0][3] + c4[1][3] + c4[2][3]};
        asm volatile("st.async.shared::cluster.mbarrier::complete_tx::bytes.v4.f32 [%0], {%1,%2,%3,%4}, [%5];\n"
                     ::"r"(ex ^ 0x1000000u), "f"(e4[0]), "f"(e4[1]), "f"(e4[2]), "f"(e4[3]), "r"(bar_g ^ 0x1000000u) : "memory");
        sts128f(ex, e4);
        if (warp < 9) bar_sync(6, 576); else bar_arrive(6, 576);
    }
    STAMP2(20);
    if (warp < 9) {
        mbar_wait_cluster(bar_g);
        const uint32_t ex = sb + SM_EX + tid * 16;
        const uint4 a = lds128(ex), c = lds128(ex + 4608), d = lds128(ex + 9216), e = lds128(ex + 13824);
#define S4(f) rbf((__uint_as_float(a.f) + __uint_as_float(c.f)) + (__uint_as_float(d.f) + __uint_as_float(e.f)))
        const float G0 = S4(x), G1 = S4(y), U0 = S4(z), U1 = S4(w);
#undef S4
        sts32(sb + SM_GU + tid * 4, pack_bf16(rbf(__fdividef(G0, 1.0f + __expf(-G0))) * U0, rbf(__fdividef(G1, 1.0f + __expf(-G1))) * U1));
    }
    if (warp == 19 && lane >= 28 && b < 96)
        bulk_s2g(reinterpret_cast<unsigned char*>(p.s->y) + b * 18432 + (lane - 28) * 4608, sb + SM_ZERO, 4608);
    if (warp == 19 && __any_sync(0xffffffffu, (tok >> 4) == b)) asm volatile("cp.async.bulk.wait_group 0;\n" ::: "memory");
    if (warp != 18) bar_sync(7, 608);
    STAMP2(21);
    if (warp < 18) {
        uint32_t gb[9];
        ldsm_x4_t(gb[0], gb[1], gb[2], gb[3], sb + SM_GU + lane * 16);
        ldsm_x4_t(gb[4], gb[5], gb[6], gb[7], sb + SM_GU + 512 + lane * 16);
        ldsm_x1_t(gb[8], sb + SM_GU + 1024 + (lane & 7) * 16);
        float c4[4] = {0.f, 0.f, 0.f, 0.f}, d4[4] = {0.f, 0.f, 0.f, 0.f};
        mma_bf16(c4, WD[0], WD[1], WD[2], WD[3], gb[0], gb[1]);
        mma_bf16(d4, WD[4], WD[5], WD[6], WD[7], gb[2], gb[3]);
        mma_bf16(c4, WD[8], WD[9], WD[10], WD[11], gb[4], gb[5]);
        mma_bf16(d4, WD[12], WD[13], WD[14], WD[15], gb[6], gb[7]);
        mma_bf16(c4, WD[16], WD[17], 0u, 0u, gb[8], 0u);
        stg128(p.s->part + ((size_t)(2 * (18 * odd + warp) + (lane >> 4)) * 64 + P) * 64 + (lane & 15) * 4,
               nzf(c4[0] + d4[0]), nzf(c4[1] + d4[1]), nzf(c4[2] + d4[2]), nzf(c4[3] + d4[3]));
    }
    STAMP2(22);
    if (b < 72) {
        if (tid < 512) {
            const uint4* src = reinterpret_cast<const uint4*>(p.s->part) + (size_t)b * 1024 + tid;
            uint4 a, c;
            int it = 0;
            while (true) {
                a = ld_poll(src); c = ld_poll(src + 512);
                if (all_nz(a) && all_nz(c)) break;
                if (++it > SPIN_LIMIT) TRAP();
            }
            STAMP2(24);
            const float s0 = __uint_as_float(a.x) + __uint_as_float(c.x), s1 = __uint_as_float(a.y) + __uint_as_float(c.y);
            const float s2 = __uint_as_float(a.z) + __uint_as_float(c.z), s3 = __uint_as_float(a.w) + __uint_as_float(c.w);
            const bool up = lane & 16;
            const float r0 = __shfl_xor_sync(0xffffffffu, up ? s0 : s2, 16), r1 = __shfl_xor_sync(0xffffffffu, up ? s1 : s3, 16);
            sts64f(sb + SM_FS + warp * 256 + (lane & 15) * 16 + (up ? 8 : 0), (up ? s2 : s0) + r0, (up ? s3 : s1) + r1);
        }
        bar_sync(0, NWRK);
        if (warp >= 18) {
            float v0 = 0.f, v1 = 0.f, v2 = 0.f, v3 = 0.f;
            const uint32_t a = sb + SM_FS + (tid - 576) * 4;
#pragma unroll
            for (int i = 0; i < 16; i += 4) { v0 += ldsf(a + i * 256); v1 += ldsf(a + i * 256 + 256); v2 += ldsf(a + i * 256 + 512); v3 += ldsf(a + i * 256 + 768); }
            const float y3 = rbf(rbf((v0 + v1) + (v2 + v3)) * rs);
            p.out[(size_t)ftok * DM + fc] = __float2bfloat16_rn(hv + rbf(u2 + y3));
        }
    }
    if (warp == 19) asm volatile("cp.async.bulk.wait_group.read 0;\n" ::: "memory");
    if (b == 0 && tid < 8) *reinterpret_cast<volatile unsigned*>(p.s->hint + tid * 32 + 1) = lds32(s_cnt + 4) + 1u;
    STAMP(25);
    }
}

typedef CUresult (*PFN_tmEncode)(CUtensorMap*, CUtensorMapDataType, cuuint32_t, void*, const cuuint64_t*, const cuuint64_t*, const cuuint32_t*,
                                 const cuuint32_t*, CUtensorMapInterleave, CUtensorMapSwizzle, CUtensorMapL2promotion, CUtensorMapFloatOOBfill);

extern "C" void kernel_launch(void* const* d_in, const int* in_sizes, int n_in, void* d_out, int out_size) {
    Params p;
    p.x = (const bf16*)d_in[0];
    p.lar = (const bf16*)d_in[1];
    p.aim = (const bf16*)d_in[2];
    p.cre = (const bf16*)d_in[3];
    p.cim = (const bf16*)d_in[4];
    p.ldt = (const bf16*)d_in[5];
    p.dsk = (const bf16*)d_in[6];
    p.wr = (const bf16*)d_in[8];
    p.wg = (const bf16*)d_in[9];
    p.wu = (const bf16*)d_in[10];
    p.wd = (const bf16*)d_in[11];
    p.out = (bf16*)d_out;
    static PFN_tmEncode enc = nullptr;
    static void* scratch = nullptr;
    if (!enc) {
        cudaFuncSetAttribute(fused_kernel, cudaFuncAttributeMaxDynamicSharedMemorySize, SMEM_TOTAL);
        void* fn = nullptr;
        cudaDriverEntryPointQueryResult qr;
        cudaGetDriverEntryPoint("cuTensorMapEncodeTiled", &fn, cudaEnableDefault, &qr);
        enc = (PFN_tmEncode)fn;
        cudaGetSymbolAddress(&scratch, g_scratch);
    }
    p.s = (Scratch*)scratch;
    CUtensorMap tm_g, tm_u, tm_d, tm_x;
    const cuuint64_t dims[2] = {FF, DM}, strides[1] = {FF * 2};
    const cuuint32_t box[2] = {72, 48}, es[2] = {1, 1};
    enc(&tm_g, CU_TENSOR_MAP_DATA_TYPE_BFLOAT16, 2, d_in[9], dims, strides, box, es, CU_TENSOR_MAP_INTERLEAVE_NONE, CU_TENSOR_MAP_SWIZZLE_NONE,
        CU_TENSOR_MAP_L2_PROMOTION_NONE, CU_TENSOR_MAP_FLOAT_OOB_FILL_NONE);
    enc(&tm_u, CU_TENSOR_MAP_DATA_TYPE_BFLOAT16, 2, d_in[10], dims, strides, box, es, CU_TENSOR_MAP_INTERLEAVE_NONE, CU_TENSOR_MAP_SWIZZLE_NONE,
        CU_TENSOR_MAP_L2_PROMOTION_NONE, CU_TENSOR_MAP_FLOAT_OOB_FILL_NONE);
    const cuuint64_t ddims[2] = {DM / 2, FF}, dstrides[1] = {DM * 2};
    const cuuint32_t dbox[2] = {WD_PITCH / 4, 8};
    enc(&tm_d, CU_TENSOR_MAP_DATA_TYPE_UINT32, 2, d_in[11], ddims, dstrides, dbox, es, CU_TENSOR_MAP_INTERLEAVE_NONE, CU_TENSOR_MAP_SWIZZLE_NONE,
        CU_TENSOR_MAP_L2_PROMOTION_NONE, CU_TENSOR_MAP_FLOAT_OOB_FILL_NONE);
    const cuuint64_t xdims[4] = {DM, 128, 4, 4}, xstrides[3] = {DM * 8, DM * 2, DM * 1024};
    const cuuint32_t xbox[4] = {8, 128, 4, MC ? 2 : 4}, xes[4] = {1, 1, 1, 1};
    enc(&tm_x, CU_TENSOR_MAP_DATA_TYPE_BFLOAT16, 4, d_in[0], xdims, xstrides, xbox, xes, CU_TENSOR_MAP_INTERLEAVE_NONE, CU_TENSOR_MAP_SWIZZLE_NONE,
        CU_TENSOR_MAP_L2_PROMOTION_NONE, CU_TENSOR_MAP_FLOAT_OOB_FILL_NONE);
    fused_kernel<<<NCTA, NTHR, SMEM_TOTAL>>>(p, tm_g, tm_u, tm_d, tm_x);
}
```

```cpp
#include <cuda_runtime.h>
#include <cuda.h>
#include <cuda_fp16.h>
#include <cuda_bf16.h>
#include <stdint.h>

#define LSEQ 2048
#define DM 576
#define NST 128
#define FF 4608
#define NSEL 8
#define NCTA 128
#define NTHR 640
#define NWRK 640

typedef __nv_bfloat16 bf16;

#define SM_WG 0
#define SM_WU 41472
#define SM_XC (82944 - 32768)
#define SM_WD 82944
#define W_PITCH 144
#define WD_PITCH 592
#define SM_XT (SM_PL - 18 * 1152)
#define SM_PL (SM_WD + 46080)
#define PL_HALF 1344
#define PLW_B 2624
#define PL_B (4 * PLW_B)
#define SM_U (SM_PL + 5 * PL_B)
#define UPAD 20
#define ULO_B ((UPAD + 128) * 16)
#define USLOT_B (2 * ULO_B)
#define SM_ZERO (SM_U + 4 * USLOT_B + 128)
#define SM_KW (SM_U + 5 * USLOT_B)
#define KW_B 3712
#define KW_PL 1216
#define KW_P 2400
#define KW_H 3440
#define SM_MISC (SM_KW + 5 * KW_B)
#define SM_LC (SM_MISC + 384)
#define SM_LNP (SM_LC + 768)
#define SM_RX (SM_LNP + 3840)
#define SMEM_TOTAL (SM_RX + 3088)
#define YKEY 0xffc1ffc1u
#define TBP 112
#define TBW (32 * TBP)
#define SM_OUT SM_PL
#define SM_XS (SM_PL + 18432)
#define XS_PITCH 592
#define SM_GU (SM_PL + 23296)
#define SM_EX (SM_PL + 24576)
#define SM_KEYS SM_KW

struct __align__(128) Scratch {
    unsigned hint[8 * 32];
    unsigned flag[32];
    uint32_t key[NCTA * 8];
    uint32_t stat[LSEQ];
    uint32_t uT[64 * (LSEQ / 2)];
    uint32_t y[(NCTA + 96) * DM * 8];
    uint32_t part[288 * 64 * 16];
    uint32_t rows[(2 * NCTA + NSEL) * DM];
};
__device__ Scratch g_scratch;
#define STAMP(i)
#define STAMPX(i)
#define STAMPY(i)

__device__ __forceinline__ float rbf(float x) {
    uint32_t r;
    asm("cvt.rn.bf16x2.f32 %0, %1, %2;\n" : "=r"(r) : "f"(x), "f"(0.f));
    return __uint_as_float(r & 0xffff0000u);
}
__device__ __forceinline__ uint32_t pack_bf16(float lo, float hi) {
    uint32_t r;
    asm("cvt.rn.bf16x2.f32 %0, %1, %2;\n" : "=r"(r) : "f"(hi), "f"(lo));
    return r;
}
__device__ __forceinline__ uint32_t pack_f16(float lo, float hi) {
    uint32_t r;
    asm("cvt.rn.f16x2.f32 %0, %1, %2;\n" : "=r"(r) : "f"(hi), "f"(lo));
    return r;
}
__device__ __forceinline__ uint32_t pack_f16_rz(float lo, float hi) {
    uint32_t r;
    asm("cvt.rz.f16x2.f32 %0, %1, %2;\n" : "=r"(r) : "f"(hi), "f"(lo));
    return r;
}
__device__ __forceinline__ float bf_lo(uint32_t w) { return __uint_as_float(w << 16); }
__device__ __forceinline__ float bf_hi(uint32_t w) { return __uint_as_float(w & 0xffff0000u); }
__device__ __forceinline__ uint32_t hadd2_bf(uint32_t a, uint32_t b) {
    __nv_bfloat162 r = __hadd2_rn(*reinterpret_cast<__nv_bfloat162*>(&a), *reinterpret_cast<__nv_bfloat162*>(&b));
    return *reinterpret_cast<uint32_t*>(&r);
}
__device__ __forceinline__ uint32_t hsub2_bf(uint32_t a, uint32_t b) {
    __nv_bfloat162 r = __hsub2_rn(*reinterpret_cast<__nv_bfloat162*>(&a), *reinterpret_cast<__nv_bfloat162*>(&b));
    return *reinterpret_cast<uint32_t*>(&r);
}
__device__ __forceinline__ uint32_t hmul2_bf(uint32_t a, uint32_t b) {
    __nv_bfloat162 r = __hmul2_rn(*reinterpret_cast<__nv_bfloat162*>(&a), *reinterpret_cast<__nv_bfloat162*>(&b));
    return *reinterpret_cast<uint32_t*>(&r);
}
__device__ __forceinline__ uint32_t hfma2_bf(uint32_t a, uint32_t b, uint32_t c) { uint32_t r; asm("fma.rn.bf16x2 %0, %1, %2, %3;\n" : "=r"(r) : "r"(a), "r"(b), "r"(c)); return r; }
__device__ __forceinline__ uint32_t hmul2(uint32_t a, uint32_t b) { uint32_t r; asm("mul.rn.f16x2 %0, %1, %2;\n" : "=r"(r) : "r"(a), "r"(b)); return r; }
__device__ __forceinline__ uint32_t hadd2(uint32_t a, uint32_t b) { uint32_t r; asm("add.rn.f16x2 %0, %1, %2;\n" : "=r"(r) : "r"(a), "r"(b)); return r; }
__device__ __forceinline__ uint32_t hfma2(uint32_t a, uint32_t b, uint32_t c) { uint32_t r; asm("fma.rn.f16x2 %0, %1, %2, %3;\n" : "=r"(r) : "r"(a), "r"(b), "r"(c)); return r; }
__device__ __forceinline__ uint32_t hfms2(uint32_t a, uint32_t b, uint32_t c) {
    uint32_t r;
    asm("{\n.reg .b32 n;\nneg.f16x2 n, %2;\nfma.rn.f16x2 %0, %1, n, %3;\n}\n" : "=r"(r) : "r"(a), "r"(b), "r"(c));
    return r;
}
__device__ __forceinline__ uint32_t nzw(uint32_t w) { return w ? w : 0x8000u; }
__device__ __forceinline__ uint32_t nzf(float f) { const uint32_t w = __float_as_uint(f); return w ? w : 0x80000000u; }
__device__ __forceinline__ uint32_t smem_u32(const void* p) { return (uint32_t)__cvta_generic_to_shared(p); }
__device__ __forceinline__ uint32_t lds32(uint32_t addr) {
    uint32_t v;
    asm volatile("ld.shared.u32 %0, [%1];\n" : "=r"(v) : "r"(addr) : "memory");
    return v;
}
__device__ __forceinline__ uint32_t lds16(uint32_t addr) {
    unsigned short v;
    asm volatile("ld.shared.u16 %0, [%1];\n" : "=h"(v) : "r"(addr) : "memory");
    return v;
}
__device__ __forceinline__ uint2 lds64(uint32_t addr) {
    uint2 v;
    asm volatile("ld.shared.v2.u32 {%0,%1}, [%2];\n" : "=r"(v.x), "=r"(v.y) : "r"(addr) : "memory");
    return v;
}
__device__ __forceinline__ uint4 lds128(uint32_t addr) {
    uint4 v;
    asm volatile("ld.shared.v4.u32 {%0,%1,%2,%3}, [%4];\n" : "=r"(v.x), "=r"(v.y), "=r"(v.z), "=r"(v.w) : "r"(addr) : "memory");
    return v;
}
__device__ __forceinline__ float ldsf(uint32_t addr) { return __uint_as_float(lds32(addr)); }
__device__ __forceinline__ void sts32(uint32_t addr, uint32_t v) { asm volatile("st.shared.u32 [%0], %1;\n" ::"r"(addr), "r"(v) : "memory"); }
__device__ __forceinline__ void sts16(uint32_t addr, uint32_t v) { asm volatile("st.shared.u16 [%0], %1;\n" ::"r"(addr), "h"((unsigned short)v) : "memory"); }
__device__ __forceinline__ void stsf(uint32_t addr, float v) { sts32(addr, __float_as_uint(v)); }
__device__ __forceinline__ void sts64(uint32_t addr, uint32_t a, uint32_t b) { asm volatile("st.shared.v2.u32 [%0], {%1,%2};\n" ::"r"(addr), "r"(a), "r"(b) : "memory"); }
__device__ __forceinline__ void sts64f(uint32_t addr, float a, float b) { sts64(addr, __float_as_uint(a), __float_as_uint(b)); }
__device__ __forceinline__ void sts128(uint32_t addr, uint32_t a, uint32_t b, uint32_t c, uint32_t d) {
    asm volatile("st.shared.v4.u32 [%0], {%1,%2,%3,%4};\n" ::"r"(addr), "r"(a), "r"(b), "r"(c), "r"(d) : "memory");
}
__device__ __forceinline__ void sts128f(uint32_t addr, const float (&v)[4]) {
    sts128(addr, __float_as_uint(v[0]), __float_as_uint(v[1]), __float_as_uint(v[2]), __float_as_uint(v[3]));
}
__device__ __forceinline__ void ldsm_x4(uint32_t& r0, uint32_t& r1, uint32_t& r2, uint32_t& r3, uint32_t addr) {
    asm volatile("ldmatrix.sync.aligned.m8n8.x4.shared.b16 {%0,%1,%2,%3}, [%4];\n"
                 : "=r"(r0), "=r"(r1), "=r"(r2), "=r"(r3) : "r"(addr) : "memory");
}
__device__ __forceinline__ void ldsm_x4_t(uint32_t& r0, uint32_t& r1, uint32_t& r2, uint32_t& r3, uint32_t addr) {
    asm volatile("ldmatrix.sync.aligned.m8n8.x4.trans.shared.b16 {%0,%1,%2,%3}, [%4];\n"
                 : "=r"(r0), "=r"(r1), "=r"(r2), "=r"(r3) : "r"(addr) : "memory");
}
__device__ __forceinline__ void ldsm_x2_t(uint32_t& r0, uint32_t& r1, uint32_t addr) {
    asm volatile("ldmatrix.sync.aligned.m8n8.x2.trans.shared.b16 {%0,%1}, [%2];\n" : "=r"(r0), "=r"(r1) : "r"(addr) : "memory");
}
__device__ __forceinline__ void ldsm_x1_t(uint32_t& r0, uint32_t addr) {
    asm volatile("ldmatrix.sync.aligned.m8n8.x1.trans.shared.b16 {%0}, [%1];\n" : "=r"(r0) : "r"(addr) : "memory");
}
__device__ __forceinline__ void stsm_x4(uint32_t addr, uint32_t r0, uint32_t r1, uint32_t r2, uint32_t r3) {
    asm volatile("stmatrix.sync.aligned.m8n8.x4.shared.b16 [%0], {%1,%2,%3,%4};\n" ::"r"(addr), "r"(r0), "r"(r1), "r"(r2), "r"(r3) : "memory");
}
__device__ __forceinline__ void stsm_x4_t(uint32_t addr, uint32_t r0, uint32_t r1, uint32_t r2, uint32_t r3) {
    asm volatile("stmatrix.sync.aligned.m8n8.x4.trans.shared.b16 [%0], {%1,%2,%3,%4};\n" ::"r"(addr), "r"(r0), "r"(r1), "r"(r2), "r"(r3) : "memory");
}
__device__ __forceinline__ uint32_t movm(uint32_t a) {
    uint32_t d;
    asm volatile("movmatrix.sync.aligned.m8n8.trans.b16 %0, %1;\n" : "=r"(d) : "r"(a));
    return d;
}
__device__ __forceinline__ void mma_f16(float (&c)[4], uint32_t a0, uint32_t a1, uint32_t a2, uint32_t a3, uint32_t b0, uint32_t b1) {
    asm volatile(
        "mma.sync.aligned.m16n8k16.row.col.f32.f16.f16.f32 {%0,%1,%2,%3}, {%4,%5,%6,%7}, {%8,%9}, {%0,%1,%2,%3};\n"
        : "+f"(c[0]), "+f"(c[1]), "+f"(c[2]), "+f"(c[3])
        : "r"(a0), "r"(a1), "r"(a2), "r"(a3), "r"(b0), "r"(b1));
}
__device__ __forceinline__ void mma_bf16(float (&c)[4], uint32_t a0, uint32_t a1, uint32_t a2, uint32_t a3, uint32_t b0, uint32_t b1) {
    asm volatile(
        "mma.sync.aligned.m16n8k16.row.col.f32.bf16.bf16.f32 {%0,%1,%2,%3}, {%4,%5,%6,%7}, {%8,%9}, {%0,%1,%2,%3};\n"
        : "+f"(c[0]), "+f"(c[1]), "+f"(c[2]), "+f"(c[3])
        : "r"(a0), "r"(a1), "r"(a2), "r"(a3), "r"(b0), "r"(b1));
}
__device__ __forceinline__ void mma_bf16_k8(float (&c)[4], uint32_t a0, uint32_t a1, uint32_t b0) {
    asm volatile("mma.sync.aligned.m16n8k8.row.col.f32.bf16.bf16.f32 {%0,%1,%2,%3}, {%4,%5}, {%6}, {%0,%1,%2,%3};\n"
                 : "+f"(c[0]), "+f"(c[1]), "+f"(c[2]), "+f"(c[3]) : "r"(a0), "r"(a1), "r"(b0));
}
__device__ __forceinline__ void bar_sync(int id, int n) { asm volatile("bar.sync %0, %1;\n" ::"r"(id), "r"(n) : "memory"); }
__device__ __forceinline__ void bar_arrive(int id, int n) { asm volatile("bar.arrive %0, %1;\n" ::"r"(id), "r"(n) : "memory"); }
__device__ __forceinline__ uint4 ld_poll(const void* p) {
    uint4 v;
    asm volatile("ld.relaxed.gpu.global.v4.u32 {%0,%1,%2,%3}, [%4];\n" : "=r"(v.x), "=r"(v.y), "=r"(v.z), "=r"(v.w) : "l"(p) : "memory");
    return v;
}
__device__ __forceinline__ uint2 ld_poll64(const void* p) {
    uint2 v;
    asm volatile("ld.relaxed.gpu.global.v2.u32 {%0,%1}, [%2];\n" : "=r"(v.x), "=r"(v.y) : "l"(p) : "memory");
    return v;
}
__device__ __forceinline__ uint32_t ld_poll32(const void* p) {
    uint32_t v;
    asm volatile("ld.relaxed.gpu.global.u32 %0, [%1];\n" : "=r"(v) : "l"(p) : "memory");
    return v;
}
__device__ __forceinline__ uint4 ldg128(const void* p) {
    uint4 v;
    asm volatile("ld.global.nc.v4.u32 {%0,%1,%2,%3}, [%4];\n" : "=r"(v.x), "=r"(v.y), "=r"(v.z), "=r"(v.w) : "l"(p));
    return v;
}
__device__ __forceinline__ uint2 ldg64(const void* p) {
    uint2 v;
    asm volatile("ld.global.nc.v2.u32 {%0,%1}, [%2];\n" : "=r"(v.x), "=r"(v.y) : "l"(p));
    return v;
}
__device__ __forceinline__ uint32_t ldg16(const void* p) {
    uint32_t v;
    asm volatile("ld.global.nc.u16 %0, [%1];\n" : "=r"(v) : "l"(p));
    return v;
}
__device__ __forceinline__ uint4 ldo128(const void* p) {
    uint4 v;
    asm volatile("ld.relaxed.cta.global.v4.u32 {%0,%1,%2,%3}, [%4];\n" : "=r"(v.x), "=r"(v.y), "=r"(v.z), "=r"(v.w) : "l"(p) : "memory");
    return v;
}
__device__ __forceinline__ uint2 ldo64(const void* p) {
    uint2 v;
    asm volatile("ld.relaxed.cta.global.v2.u32 {%0,%1}, [%2];\n" : "=r"(v.x), "=r"(v.y) : "l"(p) : "memory");
    return v;
}
__device__ __forceinline__ uint32_t ldo16(const void* p) {
    uint32_t v;
    asm volatile("ld.relaxed.cta.global.u16 %0, [%1];\n" : "=r"(v) : "l"(p) : "memory");
    return v;
}
__device__ __forceinline__ void stg128(void* p, uint32_t a, uint32_t b, uint32_t c, uint32_t d) {
    asm volatile("st.global.v4.u32 [%0], {%1,%2,%3,%4};\n" ::"l"(p), "r"(a), "r"(b), "r"(c), "r"(d) : "memory");
}
__device__ __forceinline__ void stg64(void* p, uint32_t a, uint32_t b) { asm volatile("st.global.v2.u32 [%0], {%1,%2};\n" ::"l"(p), "r"(a), "r"(b) : "memory"); }
__device__ __forceinline__ uint32_t min4(const uint4& v) { return min(min(v.x, v.y), min(v.z, v.w)); }
#define SPIN_LIMIT (1 << 21)
#define TRAP() __trap()
__device__ __forceinline__ void mbar_init(uint32_t bar, uint32_t cnt) { asm volatile("mbarrier.init.shared::cta.b64 [%0], %1;\n" ::"r"(bar), "r"(cnt) : "memory"); }
__device__ __forceinline__ void mbar_expect(uint32_t bar, uint32_t bytes) {
    asm volatile("mbarrier.arrive.expect_tx.shared::cta.b64 _, [%0], %1;\n" ::"r"(bar), "r"(bytes) : "memory");
}
__device__ __forceinline__ void mbar_arrive(uint32_t bar) { asm volatile("mbarrier.arrive.shared::cta.b64 _, [%0];\n" ::"r"(bar) : "memory"); }
__device__ __forceinline__ void mbar_wait_cluster(uint32_t bar) {
    asm volatile(
        "{\n.reg .pred p;\n"
        "W_%=:\n"
        "mbarrier.try_wait.parity.acquire.cluster.shared::cta.b64 p, [%0], 0;\n"
        "@!p bra W_%=;\n}\n" ::"r"(bar) : "memory");
}
__device__ __forceinline__ void mbar_wait(uint32_t bar) {
    asm volatile(
        "{\n.reg .pred p;\n"
        "W_%=:\n"
        "mbarrier.try_wait.parity.shared::cta.b64 p, [%0], 0;\n"
        "@!p bra W_%=;\n}\n" ::"r"(bar) : "memory");
}
__device__ __forceinline__ bool mbar_test(uint32_t bar) {
    uint32_t r;
    asm volatile("{\n.reg .pred p;\nmbarrier.test_wait.parity.shared::cta.b64 p, [%1], 0;\nselp.u32 %0, 1, 0, p;\n}\n" : "=r"(r) : "r"(bar) : "memory");
    return __any_sync(0xffffffffu, r);
}
__device__ __forceinline__ void bulk_g2s(uint32_t dst, const void* src, uint32_t bytes, uint32_t bar) {
    asm volatile("cp.async.bulk.shared::cluster.global.mbarrier::complete_tx::bytes [%0], [%1], %2, [%3];\n" ::"r"(dst), "l"(src), "r"(bytes), "r"(bar) : "memory");
}
__device__ __forceinline__ void bulk_s2g(void* dst, uint32_t src, uint32_t bytes) {
    asm volatile("cp.async.bulk.global.shared::cta.bulk_group [%0], [%1], %2;\ncp.async.bulk.commit_group;\n" ::"l"(dst), "r"(src), "r"(bytes) : "memory");
}
__device__ __forceinline__ void tma_2d(uint32_t dst, const CUtensorMap* tm, int c0, int c1, uint32_t bar) {
    asm volatile("cp.async.bulk.tensor.2d.shared::cluster.global.mbarrier::complete_tx::bytes [%0], [%1, {%3, %4}], [%2];\n"
                 ::"r"(dst), "l"(tm), "r"(bar), "r"(c0), "r"(c1) : "memory");
}
__device__ __forceinline__ void tma_4d(uint32_t dst, const CUtensorMap* tm, int c0, int c3, uint32_t bar) {
    asm volatile("cp.async.bulk.tensor.4d.shared::cluster.global.mbarrier::complete_tx::bytes [%0], [%1, {%3, %4, %4, %5}], [%2];\n"
                 ::"r"(dst), "l"(tm), "r"(bar), "r"(c0), "r"(0), "r"(c3) : "memory");
}
__device__ __forceinline__ void tma_4d_mc(uint32_t dst, const CUtensorMap* tm, int c0, int c3, uint32_t bar) {
    asm volatile("cp.async.bulk.tensor.4d.shared::cluster.global.mbarrier::complete_tx::bytes.multicast::cluster [%0], [%1, {%3, %4, %4, %5}], [%2], %6;\n"
                 ::"r"(dst), "l"(tm), "r"(bar), "r"(c0), "r"(0), "r"(c3), "h"((unsigned short)3) : "memory");
}
__device__ __forceinline__ void l2_prefetch(const void* src, uint32_t bytes) {
    asm volatile("cp.async.bulk.prefetch.L2.global [%0], %1;\n" ::"l"(src), "r"(bytes) : "memory");
}
__device__ __forceinline__ bool elect_one() {
    uint32_t r;
    asm volatile("{\n.reg .pred p;\nelect.sync _|p, 0xffffffff;\nselp.u32 %0, 1, 0, p;\n}\n" : "=r"(r));
    return r;
}
__device__ __forceinline__ void delay(uint32_t clks) {
    uint32_t t0, t1;
    asm volatile("mov.u32 %0, %%clock;" : "=r"(t0) :: "memory");
    do { asm volatile("mov.u32 %0, %%clock;" : "=r"(t1) :: "memory"); } while (t1 - t0 < clks);
}
__device__ __forceinline__ void fence_async() { asm volatile("fence.proxy.async.shared::cta;\n" ::: "memory"); }

__device__ __forceinline__ float2 cmul(float2 a, float2 b) {
    return make_float2(fmaf(a.x, b.x, -a.y * b.y), fmaf(a.x, b.y, a.y * b.x));
}
__device__ __forceinline__ float2 csq(float2 a) {
    float p = a.x * a.y;
    return make_float2(fmaf(a.x, a.x, -a.y * a.y), p + p);
}
__device__ __forceinline__ float ex2_approx(float x) { float r; asm("ex2.approx.ftz.f32 %0, %1;\n" : "=f"(r) : "f"(x)); return r; }
__device__ __forceinline__ float exp_bf(float x) { return rbf(ex2_approx(__fmul_ru(x, 1.4426950408889634f))); }
__device__ __forceinline__ float2 cexp_e(float lr2, float li, float e) {
    const float m = ex2_approx(lr2 * e);
    return make_float2(m * __cosf(li * e), m * __sinf(li * e));
}
__device__ __forceinline__ float rcp_approx(float x) { float r; asm("rcp.approx.ftz.f32 %0, %1;\n" : "=f"(r) : "f"(x)); return r; }
__device__ __forceinline__ float sqrt_approx(float x) { float r; asm("sqrt.approx.ftz.f32 %0, %1;\n" : "=f"(r) : "f"(x)); return r; }

__device__ __forceinline__ void wg_fence() { asm volatile("wgmma.fence.sync.aligned;\n" ::: "memory"); }
__device__ __forceinline__ void wg_commit() { asm volatile("wgmma.commit_group.sync.aligned;\n" ::: "memory"); }
__device__ __forceinline__ void wg_wait0() { asm volatile("wgmma.wait_group.sync.aligned 0;\n" ::: "memory"); }
template <int T> __device__ __forceinline__ void wg_mma(float (&acc)[16][4], const uint32_t* a, uint64_t desc);
template <int T> __device__ __forceinline__ void wg_first(float (&acc)[16][4], const uint32_t* a, uint64_t desc);
template <> __device__ __forceinline__ void wg_mma<0>(float (&acc)[16][4], const uint32_t* a, uint64_t desc) {
    asm volatile("wgmma.mma_async.sync.aligned.m64n128k16.f32.f16.f16 {%0,%1,%2,%3,%4,%5,%6,%7,%8,%9,%10,%11,%12,%13,%14,%15,%16,%17,%18,%19,%20,%21,%22,%23,%24,%25,%26,%27,%28,%29,%30,%31,%32,%33,%34,%35,%36,%37,%38,%39,%40,%41,%42,%43,%44,%45,%46,%47,%48,%49,%50,%51,%52,%53,%54,%55,%56,%57,%58,%59,%60,%61,%62,%63}, {%64,%65,%66,%67}, %68, 1, 1, 1, 0;\n"
                 : "+f"(acc[0][0]), "+f"(acc[0][1]), "+f"(acc[0][2]), "+f"(acc[0][3]), "+f"(acc[1][0]), "+f"(acc[1][1]), "+f"(acc[1][2]), "+f"(acc[1][3]), "+f"(acc[2][0]), "+f"(acc[2][1]), "+f"(acc[2][2]), "+f"(acc[2][3]), "+f"(acc[3][0]), "+f"(acc[3][1]), "+f"(acc[3][2]), "+f"(acc[3][3]), "+f"(acc[4][0]), "+f"(acc[4][1]), "+f"(acc[4][2]), "+f"(acc[4][3]), "+f"(acc[5][0]), "+f"(acc[5][1]), "+f"(acc[5][2]), "+f"(acc[5][3]), "+f"(acc[6][0]), "+f"(acc[6][1]), "+f"(acc[6][2]), "+f"(acc[6][3]), "+f"(acc[7][0]), "+f"(acc[7][1]), "+f"(acc[7][2]), "+f"(acc[7][3]), "+f"(acc[8][0]), "+f"(acc[8][1]), "+f"(acc[8][2]), "+f"(acc[8][3]), "+f"(acc[9][0]), "+f"(acc[9][1]), "+f"(acc[9][2]), "+f"(acc[9][3]), "+f"(acc[10][0]), "+f"(acc[10][1]), "+f"(acc[10][2]), "+f"(acc[10][3]), "+f"(acc[11][0]), "+f"(acc[11][1]), "+f"(acc[11][2]), "+f"(acc[11][3]), "+f"(acc[12][0]), "+f"(acc[12][1]), "+f"(acc[12][2]), "+f"(acc[12][3]), "+f"(acc[13][0]), "+f"(acc[13][1]), "+f"(acc[13][2]), "+f"(acc[13][3]), "+f"(acc[14][0]), "+f"(acc[14][1]), "+f"(acc[14][2]), "+f"(acc[14][3]), "+f"(acc[15][0]), "+f"(acc[15][1]), "+f"(acc[15][2]), "+f"(acc[15][3])
                 : "r"(a[0]), "r"(a[1]), "r"(a[2]), "r"(a[3]), "l"(desc));
}
template <> __device__ __forceinline__ void wg_mma<2>(float (&acc)[16][4], const uint32_t* a, uint64_t desc) {
    asm volatile("wgmma.mma_async.sync.aligned.m64n112k16.f32.f16.f16 {%0,%1,%2,%3,%4,%5,%6,%7,%8,%9,%10,%11,%12,%13,%14,%15,%16,%17,%18,%19,%20,%21,%22,%23,%24,%25,%26,%27,%28,%29,%30,%31,%32,%33,%34,%35,%36,%37,%38,%39,%40,%41,%42,%43,%44,%45,%46,%47,%48,%49,%50,%51,%52,%53,%54,%55}, {%56,%57,%58,%59}, %60, 1, 1, 1, 0;\n"
                 : "+f"(acc[2][0]), "+f"(acc[2][1]), "+f"(acc[2][2]), "+f"(acc[2][3]), "+f"(acc[3][0]), "+f"(acc[3][1]), "+f"(acc[3][2]), "+f"(acc[3][3]), "+f"(acc[4][0]), "+f"(acc[4][1]), "+f"(acc[4][2]), "+f"(acc[4][3]), "+f"(acc[5][0]), "+f"(acc[5][1]), "+f"(acc[5][2]), "+f"(acc[5][3]), "+f"(acc[6][0]), "+f"(acc[6][1]), "+f"(acc[6][2]), "+f"(acc[6][3]), "+f"(acc[7][0]), "+f"(acc[7][1]), "+f"(acc[7][2]), "+f"(acc[7][3]), "+f"(acc[8][0]), "+f"(acc[8][1]), "+f"(acc[8][2]), "+f"(acc[8][3]), "+f"(acc[9][0]), "+f"(acc[9][1]), "+f"(acc[9][2]), "+f"(acc[9][3]), "+f"(acc[10][0]), "+f"(acc[10][1]), "+f"(acc[10][2]), "+f"(acc[10][3]), "+f"(acc[11][0]), "+f"(acc[11][1]), "+f"(acc[11][2]), "+f"(acc[11][3]), "+f"(acc[12][0]), "+f"(acc[12][1]), "+f"(acc[12][2]), "+f"(acc[12][3]), "+f"(acc[13][0]), "+f"(acc[13][1]), "+f"(acc[13][2]), "+f"(acc[13][3]), "+f"(acc[14][0]), "+f"(acc[14][1]), "+f"(acc[14][2]), "+f"(acc[14][3]), "+f"(acc[15][0]), "+f"(acc[15][1]), "+f"(acc[15][2]), "+f"(acc[15][3])
                 : "r"(a[0]), "r"(a[1]), "r"(a[2]), "r"(a[3]), "l"(desc));
}
template <> __device__ __forceinline__ void wg_mma<4>(float (&acc)[16][4], const uint32_t* a, uint64_t desc) {
    asm volatile("wgmma.mma_async.sync.aligned.m64n96k16.f32.f16.f16 {%0,%1,%2,%3,%4,%5,%6,%7,%8,%9,%10,%11,%12,%13,%14,%15,%16,%17,%18,%19,%20,%21,%22,%23,%24,%25,%26,%27,%28,%29,%30,%31,%32,%33,%34,%35,%36,%37,%38,%39,%40,%41,%42,%43,%44,%45,%46,%47}, {%48,%49,%50,%51}, %52, 1, 1, 1, 0;\n"
                 : "+f"(acc[4][0]), "+f"(acc[4][1]), "+f"(acc[4][2]), "+f"(acc[4][3]), "+f"(acc[5][0]), "+f"(acc[5][1]), "+f"(acc[5][2]), "+f"(acc[5][3]), "+f"(acc[6][0]), "+f"(acc[6][1]), "+f"(acc[6][2]), "+f"(acc[6][3]), "+f"(acc[7][0]), "+f"(acc[7][1]), "+f"(acc[7][2]), "+f"(acc[7][3]), "+f"(acc[8][0]), "+f"(acc[8][1]), "+f"(acc[8][2]), "+f"(acc[8][3]), "+f"(acc[9][0]), "+f"(acc[9][1]), "+f"(acc[9][2]), "+f"(acc[9][3]), "+f"(acc[10][0]), "+f"(acc[10][1]), "+f"(acc[10][2]), "+f"(acc[10][3]), "+f"(acc[11][0]), "+f"(acc[11][1]), "+f"(acc[11][2]), "+f"(acc[11][3]), "+f"(acc[12][0]), "+f"(acc[12][1]), "+f"(acc[12][2]), "+f"(acc[12][3]), "+f"(acc[13][0]), "+f"(acc[13][1]), "+f"(acc[13][2]), "+f"(acc[13][3]), "+f"(acc[14][0]), "+f"(acc[14][1]), "+f"(acc[14][2]), "+f"(acc[14][3]), "+f"(acc[15][0]), "+f"(acc[15][1]), "+f"(acc[15][2]), "+f"(acc[15][3])
                 : "r"(a[0]), "r"(a[1]), "r"(a[2]), "r"(a[3]), "l"(desc));
}
template <> __device__ __forceinline__ void wg_mma<6>(float (&acc)[16][4], const uint32_t* a, uint64_t desc) {
    asm volatile("wgmma.mma_async.sync.aligned.m64n80k16.f32.f16.f16 {%0,%1,%2,%3,%4,%5,%6,%7,%8,%9,%10,%11,%12,%13,%14,%15,%16,%17,%18,%19,%20,%21,%22,%23,%24,%25,%26,%27,%28,%29,%30,%31,%32,%33,%34,%35,%36,%37,%38,%39}, {%40,%41,%42,%43}, %44, 1, 1, 1, 0;\n"
                 : "+f"(acc[6][0]), "+f"(acc[6][1]), "+f"(acc[6][2]), "+f"(acc[6][3]), "+f"(acc[7][0]), "+f"(acc[7][1]), "+f"(acc[7][2]), "+f"(acc[7][3]), "+f"(acc[8][0]), "+f"(acc[8][1]), "+f"(acc[8][2]), "+f"(acc[8][3]), "+f"(acc[9][0]), "+f"(acc[9][1]), "+f"(acc[9][2]), "+f"(acc[9][3]), "+f"(acc[10][0]), "+f"(acc[10][1]), "+f"(acc[10][2]), "+f"(acc[10][3]), "+f"(acc[11][0]), "+f"(acc[11][1]), "+f"(acc[11][2]), "+f"(acc[11][3]), "+f"(acc[12][0]), "+f"(acc[12][1]), "+f"(acc[12][2]), "+f"(acc[12][3]), "+f"(acc[13][0]), "+f"(acc[13][1]), "+f"(acc[13][2]), "+f"(acc[13][3]), "+f"(acc[14][0]), "+f"(acc[14][1]), "+f"(acc[14][2]), "+f"(acc[14][3]), "+f"(acc[15][0]), "+f"(acc[15][1]), "+f"(acc[15][2]), "+f"(acc[15][3])
                 : "r"(a[0]), "r"(a[1]), "r"(a[2]), "r"(a[3]), "l"(desc));
}
template <> __device__ __forceinline__ void wg_mma<8>(float (&acc)[16][4], const uint32_t* a, uint64_t desc) {
    asm volatile("wgmma.mma_async.sync.aligned.m64n64k16.f32.f16.f16 {%0,%1,%2,%3,%4,%5,%6,%7,%8,%9,%10,%11,%12,%13,%14,%15,%16,%17,%18,%19,%20,%21,%22,%23,%24,%25,%26,%27,%28,%29,%30,%31}, {%32,%33,%34,%35}, %36, 1, 1, 1, 0;\n"
                 : "+f"(acc[8][0]), "+f"(acc[8][1]), "+f"(acc[8][2]), "+f"(acc[8][3]), "+f"(acc[9][0]), "+f"(acc[9][1]), "+f"(acc[9][2]), "+f"(acc[9][3]), "+f"(acc[10][0]), "+f"(acc[10][1]), "+f"(acc[10][2]), "+f"(acc[10][3]), "+f"(acc[11][0]), "+f"(acc[11][1]), "+f"(acc[11][2]), "+f"(acc[11][3]), "+f"(acc[12][0]), "+f"(acc[12][1]), "+f"(acc[12][2]), "+f"(acc[12][3]), "+f"(acc[13][0]), "+f"(acc[13][1]), "+f"(acc[13][2]), "+f"(acc[13][3]), "+f"(acc[14][0]), "+f"(acc[14][1]), "+f"(acc[14][2]), "+f"(acc[14][3]), "+f"(acc[15][0]), "+f"(acc[15][1]), "+f"(acc[15][2]), "+f"(acc[15][3])
                 : "r"(a[0]), "r"(a[1]), "r"(a[2]), "r"(a[3]), "l"(desc));
}
template <> __device__ __forceinline__ void wg_mma<10>(float (&acc)[16][4], const uint32_t* a, uint64_t desc) {
    asm volatile("wgmma.mma_async.sync.aligned.m64n48k16.f32.f16.f16 {%0,%1,%2,%3,%4,%5,%6,%7,%8,%9,%10,%11,%12,%13,%14,%15,%16,%17,%18,%19,%20,%21,%22,%23}, {%24,%25,%26,%27}, %28, 1, 1, 1, 0;\n"
                 : "+f"(acc[10][0]), "+f"(acc[10][1]), "+f"(acc[10][2]), "+f"(acc[10][3]), "+f"(acc[11][0]), "+f"(acc[11][1]), "+f"(acc[11][2]), "+f"(acc[11][3]), "+f"(acc[12][0]), "+f"(acc[12][1]), "+f"(acc[12][2]), "+f"(acc[12][3]), "+f"(acc[13][0]), "+f"(acc[13][1]), "+f"(acc[13][2]), "+f"(acc[13][3]), "+f"(acc[14][0]), "+f"(acc[14][1]), "+f"(acc[14][2]), "+f"(acc[14][3]), "+f"(acc[15][0]), "+f"(acc[15][1]), "+f"(acc[15][2]), "+f"(acc[15][3])
                 : "r"(a[0]), "r"(a[1]), "r"(a[2]), "r"(a[3]), "l"(desc));
}
template <> __device__ __forceinline__ void wg_mma<12>(float (&acc)[16][4], const uint32_t* a, uint64_t desc) {
    asm volatile("wgmma.mma_async.sync.aligned.m64n32k16.f32.f16.f16 {%0,%1,%2,%3,%4,%5,%6,%7,%8,%9,%10,%11,%12,%13,%14,%15}, {%16,%17,%18,%19}, %20, 1, 1, 1, 0;\n"
                 : "+f"(acc[12][0]), "+f"(acc[12][1]), "+f"(acc[12][2]), "+f"(acc[12][3]), "+f"(acc[13][0]), "+f"(acc[13][1]), "+f"(acc[13][2]), "+f"(acc[13][3]), "+f"(acc[14][0]), "+f"(acc[14][1]), "+f"(acc[14][2]), "+f"(acc[14][3]), "+f"(acc[15][0]), "+f"(acc[15][1]), "+f"(acc[15][2]), "+f"(acc[15][3])
                 : "r"(a[0]), "r"(a[1]), "r"(a[2]), "r"(a[3]), "l"(desc));
}
template <> __device__ __forceinline__ void wg_mma<14>(float (&acc)[16][4], const uint32_t* a, uint64_t desc) {
    asm volatile("wgmma.mma_async.sync.aligned.m64n16k16.f32.f16.f16 {%0,%1,%2,%3,%4,%5,%6,%7}, {%8,%9,%10,%11}, %12, 1, 1, 1, 0;\n"
                 : "+f"(acc[14][0]), "+f"(acc[14][1]), "+f"(acc[14][2]), "+f"(acc[14][3]), "+f"(acc[15][0]), "+f"(acc[15][1]), "+f"(acc[15][2]), "+f"(acc[15][3])
                 : "r"(a[0]), "r"(a[1]), "r"(a[2]), "r"(a[3]), "l"(desc));
}
template <> __device__ __forceinline__ void wg_first<0>(float (&acc)[16][4], const uint32_t* a, uint64_t desc) {
    asm volatile("wgmma.mma_async.sync.aligned.m64n128k16.f32.f16.f16 {%0,%1,%2,%3,%4,%5,%6,%7,%8,%9,%10,%11,%12,%13,%14,%15,%16,%17,%18,%19,%20,%21,%22,%23,%24,%25,%26,%27,%28,%29,%30,%31,%32,%33,%34,%35,%36,%37,%38,%39,%40,%41,%42,%43,%44,%45,%46,%47,%48,%49,%50,%51,%52,%53,%54,%55,%56,%57,%58,%59,%60,%61,%62,%63}, {%64,%65,%66,%67}, %68, 0, 1, 1, 0;\n"
                 : "=f"(acc[0][0]), "=f"(acc[0][1]), "=f"(acc[0][2]), "=f"(acc[0][3]), "=f"(acc[1][0]), "=f"(acc[1][1]), "=f"(acc[1][2]), "=f"(acc[1][3]), "=f"(acc[2][0]), "=f"(acc[2][1]), "=f"(acc[2][2]), "=f"(acc[2][3]), "=f"(acc[3][0]), "=f"(acc[3][1]), "=f"(acc[3][2]), "=f"(acc[3][3]), "=f"(acc[4][0]), "=f"(acc[4][1]), "=f"(acc[4][2]), "=f"(acc[4][3]), "=f"(acc[5][0]), "=f"(acc[5][1]), "=f"(acc[5][2]), "=f"(acc[5][3]), "=f"(acc[6][0]), "=f"(acc[6][1]), "=f"(acc[6][2]), "=f"(acc[6][3]), "=f"(acc[7][0]), "=f"(acc[7][1]), "=f"(acc[7][2]), "=f"(acc[7][3]), "=f"(acc[8][0]), "=f"(acc[8][1]), "=f"(acc[8][2]), "=f"(acc[8][3]), "=f"(acc[9][0]), "=f"(acc[9][1]), "=f"(acc[9][2]), "=f"(acc[9][3]), "=f"(acc[10][0]), "=f"(acc[10][1]), "=f"(acc[10][2]), "=f"(acc[10][3]), "=f"(acc[11][0]), "=f"(acc[11][1]), "=f"(acc[11][2]), "=f"(acc[11][3]), "=f"(acc[12][0]), "=f"(acc[12][1]), "=f"(acc[12][2]), "=f"(acc[12][3]), "=f"(acc[13][0]), "=f"(acc[13][1]), "=f"(acc[13][2]), "=f"(acc[13][3]), "=f"(acc[14][0]), "=f"(acc[14][1]), "=f"(acc[14][2]), "=f"(acc[14][3]), "=f"(acc[15][0]), "=f"(acc[15][1]), "=f"(acc[15][2]), "=f"(acc[15][3])
                 : "r"(a[0]), "r"(a[1]), "r"(a[2]), "r"(a[3]), "l"(desc));
}
template <> __device__ __forceinline__ void wg_first<4>(float (&acc)[16][4], const uint32_t* a, uint64_t desc) {
    asm volatile("wgmma.mma_async.sync.aligned.m64n96k16.f32.f16.f16 {%0,%1,%2,%3,%4,%5,%6,%7,%8,%9,%10,%11,%12,%13,%14,%15,%16,%17,%18,%19,%20,%21,%22,%23,%24,%25,%26,%27,%28,%29,%30,%31,%32,%33,%34,%35,%36,%37,%38,%39,%40,%41,%42,%43,%44,%45,%46,%47}, {%48,%49,%50,%51}, %52, 0, 1, 1, 0;\n"
                 : "=f"(acc[4][0]), "=f"(acc[4][1]), "=f"(acc[4][2]), "=f"(acc[4][3]), "=f"(acc[5][0]), "=f"(acc[5][1]), "=f"(acc[5][2]), "=f"(acc[5][3]), "=f"(acc[6][0]), "=f"(acc[6][1]), "=f"(acc[6][2]), "=f"(acc[6][3]), "=f"(acc[7][0]), "=f"(acc[7][1]), "=f"(acc[7][2]), "=f"(acc[7][3]), "=f"(acc[8][0]), "=f"(acc[8][1]), "=f"(acc[8][2]), "=f"(acc[8][3]), "=f"(acc[9][0]), "=f"(acc[9][1]), "=f"(acc[9][2]), "=f"(acc[9][3]), "=f"(acc[10][0]), "=f"(acc[10][1]), "=f"(acc[10][2]), "=f"(acc[10][3]), "=f"(acc[11][0]), "=f"(acc[11][1]), "=f"(acc[11][2]), "=f"(acc[11][3]), "=f"(acc[12][0]), "=f"(acc[12][1]), "=f"(acc[12][2]), "=f"(acc[12][3]), "=f"(acc[13][0]), "=f"(acc[13][1]), "=f"(acc[13][2]), "=f"(acc[13][3]), "=f"(acc[14][0]), "=f"(acc[14][1]), "=f"(acc[14][2]), "=f"(acc[14][3]), "=f"(acc[15][0]), "=f"(acc[15][1]), "=f"(acc[15][2]), "=f"(acc[15][3])
                 : "r"(a[0]), "r"(a[1]), "r"(a[2]), "r"(a[3]), "l"(desc));
}

#define EARLYN 2
#define K8 0
#define HOLD 1
#define MC 1
#define STAMPW(i) STAMPY(i)
#define STAMP2(i) STAMP(i)
#undef STAMPX
#define STAMPX(i)
#define PBAR 1
#define WDLY 500
#define CBAR 1
#define FDLY 300
#define KDLY 500
#define OEARLY 0
#define EXP 0
#define XWHEN 0
#define RWHEN 0
#define HW 11
#define PEARLY 0
#define XG 6
struct Params {
    const bf16 *x, *lar, *aim, *cre, *cim, *ldt, *dsk;
    Scratch* s;
    const bf16 *wr, *wg, *wu, *wd;
    bf16* out;
};

#define TOK(g) (2 * (g) - ((g) & 1))
#define ROWTOK(r) (TOK((r) & 7) + (((r) >> 2) & 2))
__device__ __forceinline__ void ln_partial(const uint32_t (&H)[2][4], uint32_t lp, int warp, int g, int t) {
    float cs[4] = {0.f, 0.f, 0.f, 0.f}, cl[4] = {0.f, 0.f, 0.f, 0.f}, ch[4] = {0.f, 0.f, 0.f, 0.f};
#pragma unroll
    for (int k = 0; k < 4; k += 2) {
        mma_bf16(cs, H[0][k], H[1][k], H[0][k + 1], H[1][k + 1], 0x3f803f80u, 0x3f803f80u);
        mma_bf16(cl, H[0][k], H[1][k], H[0][k + 1], H[1][k + 1], H[0][k], H[0][k + 1]);
        mma_bf16(ch, H[0][k], H[1][k], H[0][k + 1], H[1][k + 1], H[1][k], H[1][k + 1]);
    }
    const uint32_t a = lp + (g * 20 + warp) * 4;
    if (t == (g >> 1)) { stsf(a, cs[0]); stsf(a + 8 * 80, cs[2]); stsf(a + 16 * 80, (g & 1) ? cl[1] : cl[0]); stsf(a + 24 * 80, (g & 1) ? ch[3] : ch[2]); }
}
__device__ __forceinline__ float sum18(uint32_t a) {
    const uint4 p = lds128(a), q = lds128(a + 16), r = lds128(a + 32), s = lds128(a + 48);
    const uint2 u = lds64(a + 64);
#define F(x) __uint_as_float(x)
    return (((F(p.x) + F(p.y)) + (F(p.z) + F(p.w))) + ((F(q.x) + F(q.y)) + (F(q.z) + F(q.w)))) +
           (((F(r.x) + F(r.y)) + (F(r.z) + F(r.w))) + ((F(s.x) + F(s.y)) + (F(s.z) + F(s.w))) + (F(u.x) + F(u.y)));
#undef F
}
__device__ __forceinline__ void ln_stats(float sm, float sq, float& mb, float& sd) {
    const float m0 = sm * (1.0f / 576.0f);
    const float mean = fmaf(fmaf(-m0, 576.0f, sm), 1.0f / 576.0f, m0);
    const float var = fmaxf(fmaf(-mean, mean, sq * (1.0f / 576.0f)), 0.f);
    mb = rbf(mean);
    sd = rbf(sqrt_approx(rbf(rbf(var) + 1e-5f)));
}
__device__ __forceinline__ void ln_finish(float v, int lane, float& mb, float& rc) {
    const float o = __shfl_xor_sync(0xffffffffu, v, 16);
    float sd;
    ln_stats(lane < 16 ? v : o, lane < 16 ? o : v, mb, sd);
    rc = rcp_approx(sd);
}
__device__ __forceinline__ uint32_t ln_apply(uint32_t w, uint32_t m2, uint32_t rh, uint32_t rl) {
    const uint32_t d = hsub2_bf(w, m2);
    return hfma2_bf(d, rh, hmul2_bf(d, rl));
}
__device__ __forceinline__ void stat_store(uint32_t a, float mb, float rc, uint32_t extra) {
    const float rh = rbf(rc);
    sts64(a, (__float_as_uint(mb) >> 16) | (extra << 16), pack_bf16(rh, rc - rh));
}
#define STAT_M(s) __byte_perm((s).x, (s).x, 0x1010)
#define STAT_H(s) __byte_perm((s).y, (s).y, 0x1010)
#define STAT_L(s) __byte_perm((s).y, (s).y, 0x3232)

__device__ __forceinline__ void hcmul(uint32_t re, uint32_t im, uint32_t zx, uint32_t zy, uint32_t& ore, uint32_t& oim) {
    ore = hfms2(im, zy, hmul2(re, zx));
    oim = hfma2(re, zy, hmul2(im, zx));
}

struct KGen {
    uint32_t A[2][4][4];
    float2 z1, z8, z64, z128, T[9];
};
__device__ __forceinline__ void kgen_setup(KGen& k, float lar, float aim, float dt) {
    const float lr2 = -(exp_bf(lar) * dt) * 1.4426950408889634f, li = aim * dt;
    k.z1 = cexp_e(lr2, li, 1.0f);
    k.z8 = cexp_e(lr2, li, 8.0f);
    k.z64 = cexp_e(lr2, li, 64.0f);
}
__device__ __forceinline__ void kgen_rows(KGen& k, uint32_t tb, int lane) {
    const float2 z8 = k.z8, z64 = k.z64;
    const uint32_t row = tb + lane * TBP;
    k.z128 = csq(z64);
    const float2 z16 = csq(z8), z24 = cmul(z16, z8), z32 = csq(z16), z40 = cmul(z32, z8), z48 = csq(z24), z56 = cmul(z32, z24);
    uint32_t re[4], im[4], a[4], b[4];
    re[0] = pack_f16(1.0f, z8.x); im[0] = pack_f16(0.0f, z8.y);
    re[1] = pack_f16(z16.x, z24.x); im[1] = pack_f16(z16.y, z24.y);
    re[2] = pack_f16(z32.x, z40.x); im[2] = pack_f16(z32.y, z40.y);
    re[3] = pack_f16(z48.x, z56.x); im[3] = pack_f16(z48.y, z56.y);
    sts128(row, re[0], re[1], re[2], re[3]);
    sts128(row + 32, im[0], im[1], im[2], im[3]);
    const uint32_t zx = pack_f16(z64.x, z64.x), zy = pack_f16(z64.y, z64.y), zw = pack_f16(k.z128.x, k.z128.y);
#pragma unroll
    for (int j = 0; j < 4; j++) hcmul(re[j], im[j], zx, zy, a[j], b[j]);
    sts128(row + 16, a[0], a[1], a[2], a[3]);
    sts128(row + 48, b[0], b[1], b[2], b[3]);
    const int mi = lane >> 3;
    const uint32_t zd = tb + mi * TBP + 96;
    sts16(zd + (lane & 7) * 2, zw); sts16(zd + (lane & 7) * 2 + 4 * TBP, zw >> 16);
    __syncwarp();
    const uint32_t ad = tb + (lane & 7) * TBP + mi * 16;
    ldsm_x4(a[0], a[1], a[2], a[3], zd);
    ldsm_x4(b[0], b[1], b[2], b[3], zd + 4 * TBP);
#pragma unroll
    for (int ks = 0; ks < 4; ks++) {
        ldsm_x4_t(k.A[0][ks][0], k.A[0][ks][1], k.A[0][ks][2], k.A[0][ks][3], ad + ks * 8 * TBP);
        hcmul(k.A[0][ks][0], k.A[0][ks][2], a[ks], b[ks], k.A[1][ks][0], k.A[1][ks][2]);
        hcmul(k.A[0][ks][1], k.A[0][ks][3], a[ks], b[ks], k.A[1][ks][1], k.A[1][ks][3]);
    }
}
__device__ __forceinline__ void kgen_chain(KGen& k, uint32_t cr, uint32_t ci, float cs) {
    k.T[0] = make_float2(bf_lo(cr) * cs, -bf_lo(ci) * cs);
    const float2 y1 = make_float2(k.z1.x, -k.z1.y);
#pragma unroll
    for (int c = 1; c < 8; c++) k.T[c] = cmul(k.T[c - 1], y1);
    k.T[8] = cmul(k.T[0], make_float2(k.z8.x, -k.z8.y));
}
__device__ __forceinline__ void kgen_cols(KGen& k, uint32_t tb, int lane) {
    const uint32_t row = tb + lane * TBP;
    const float2 (&T)[9] = k.T;
    const float2 y128 = make_float2(k.z128.x, -k.z128.y);
    const float2 y256 = csq(y128), y512 = csq(y256), y768 = cmul(y512, y256), y1024 = csq(y512);
    const float2 c1032 = cmul(T[8], y1024);
    __syncwarp();
    sts128(row, pack_f16(T[0].x, T[1].x), pack_f16(T[2].x, T[3].x), pack_f16(T[4].x, T[5].x), pack_f16(T[6].x, T[7].x));
    sts128(row + 16, pack_f16(T[0].y, T[1].y), pack_f16(T[2].y, T[3].y), pack_f16(T[4].y, T[5].y), pack_f16(T[6].y, T[7].y));
    uint32_t a[4], b[4];
    {
        const uint32_t zx = pack_f16(y256.x, y256.x), zy = pack_f16(y256.y, y256.y);
        hcmul(pack_f16(T[0].x, T[2].x), pack_f16(T[0].y, T[2].y), zx, zy, a[0], b[0]);
        hcmul(pack_f16(T[4].x, T[6].x), pack_f16(T[4].y, T[6].y), zx, zy, a[1], b[1]);
        const uint32_t r04 = pack_f16(T[0].x, T[4].x), i04 = pack_f16(T[0].y, T[4].y);
        hcmul(r04, i04, pack_f16(y512.x, y512.x), pack_f16(y512.y, y512.y), a[2], b[2]);
        hcmul(r04, i04, pack_f16(y768.x, y768.x), pack_f16(y768.y, y768.y), a[3], b[3]);
    }
    sts128(row + 32, a[0], a[1], a[2], a[3]);
    sts128(row + 48, b[0], b[1], b[2], b[3]);
    {
        const uint32_t r0 = pack_f16(1.0f, y256.x), i0 = pack_f16(0.0f, y256.y), r1 = pack_f16(y512.x, y768.x), i1 = pack_f16(y512.y, y768.y);
        const uint32_t zx = pack_f16(T[8].x, T[8].x), zy = pack_f16(T[8].y, T[8].y), wx = pack_f16(c1032.x, c1032.x), wy = pack_f16(c1032.y, c1032.y);
        hcmul(r0, i0, zx, zy, a[0], b[0]); hcmul(r1, i1, zx, zy, a[1], b[1]);
        hcmul(r0, i0, wx, wy, a[2], b[2]); hcmul(r1, i1, wx, wy, a[3], b[3]);
    }
    sts128(row + 64, a[0], a[1], a[2], a[3]);
    sts128(row + 80, b[0], b[1], b[2], b[3]);
}
__device__ __forceinline__ void kgen_mma(const KGen& k, uint32_t tb, int lane) {
    __syncwarp();
    float acc[2][3][4];
#pragma unroll
    for (int i = 0; i < 6; i++)
#pragma unroll
        for (int j = 0; j < 4; j++) acc[i / 3][i % 3][j] = 0.f;
    const int mi = lane >> 3;
    const uint32_t bd = tb + ((lane & 7) + 8 * (mi >> 1)) * TBP + (mi & 1) * 16;
#pragma unroll
    for (int kp = 0; kp < 2; kp++)
#pragma unroll
        for (int j = 0; j < 3; j++) {
            uint32_t b[4];
            ldsm_x4_t(b[0], b[1], b[2], b[3], bd + kp * 16 * TBP + j * 32);
#pragma unroll
            for (int h = 0; h < 2; h++)
#pragma unroll
                for (int m = 0; m < 2; m++) {
                    const uint32_t (&A)[4] = k.A[m][2 * kp + h];
                    mma_f16(acc[m][j], A[0], A[1], A[2], A[3], b[2 * h], b[2 * h + 1]);
                }
        }
    __syncwarp();
#define PK(j) pack_f16(acc[0][j][0], acc[0][j][1]), pack_f16(acc[0][j][2], acc[0][j][3]), pack_f16(acc[1][j][0], acc[1][j][1]), pack_f16(acc[1][j][2], acc[1][j][3])
    stsm_x4(tb + lane * 16, PK(0));
    stsm_x4(tb + 512 + lane * 16, PK(1));
    stsm_x4_t(tb + 1024 + (lane & 7) * 80 + mi * 16, PK(2));
#undef PK
}
__device__ __forceinline__ uint32_t table_buf(uint32_t sb, int warp) { return sb + SM_WD + (warp < 16 ? warp + 4 : warp - 16) * TBW; }

__device__ __forceinline__ uint4 lds16x4(uint32_t a) { return make_uint4(lds16(a), lds16(a + TBW), lds16(a + 2 * TBW), lds16(a + 3 * TBW)); }
__device__ __forceinline__ void combine_setup(uint32_t sb, int warp, int lane, uint32_t kw, uint32_t& o, uint32_t& n, uint32_t& d) {
    const int wq = warp & 3;
    const uint32_t a = table_buf(sb, warp & ~3);
    o = wq == 3 ? a + 1024 + 320 + (lane >> 3) * 80 + (lane & 7) * 8 : a + (wq ? 504 + wq * 8 : 0) + lane * 16;
    n = a + 1024 + wq * 80 + lane * 2;
    d = wq < 3 ? kw + (wq == 2 ? KW_P : 32 + wq * 512) + lane * 16 : kw + KW_H + 8 + lane * 8;
}
__device__ __forceinline__ void kgen_combine(int wq, int lane, uint32_t o, uint32_t na, uint32_t d) {
#define S4(f) hadd2(hadd2(u.f, v.f), hadd2(w.f, x.f))
#define H4(v) hadd2(hadd2(v.x, v.y), hadd2(v.z, v.w))
#define BP __byte_perm
    if (wq == 0) {
        const uint4 u = lds128(o), v = lds128(o + TBW), w = lds128(o + 2 * TBW), x = lds128(o + 3 * TBW), nn = lds16x4(na);
        const uint32_t n = H4(nn), k0 = S4(x), k2 = S4(y), k4 = S4(z), k6 = S4(w);
        sts128(d, BP(k0, k0, 0x1032), BP(k0, k2, 0x3254), BP(k2, k2, 0x1032), BP(k2, k4, 0x3254));
        sts128(d + KW_PL, BP(k4, k4, 0x1032), BP(k4, k6, 0x3254), BP(k6, k6, 0x1032), BP(k6, n, 0x3254));
        if (lane == 0) sts32(d + KW_PL - 4, k0 & 0xffffu);
    } else {
        const uint2 u = lds64(o), v = lds64(o + TBW), w = lds64(o + 2 * TBW), x = lds64(o + 3 * TBW);
        uint4 nn = make_uint4(0u, 0u, 0u, 0u), mm = nn;
        if (wq < 3) nn = lds16x4(na);
        if (wq == 2) mm = lds16x4(na + 80);
        const uint32_t k0 = S4(x), k2 = S4(y), n = H4(nn), m = H4(mm);
        if (wq == 3) {
            sts64(d, k0, k2);
        } else if (wq == 1) {
            const uint32_t cc = BP(k2, k2, 0x1010);
            sts128(d, BP(k0, k0, 0x1010), BP(k0, k0, 0x1032), BP(k0, k2, 0x3254), cc);
            sts128(d + KW_PL, cc, BP(k2, k2, 0x1032), BP(k2, n, 0x3254), BP(n, n, 0x1010));
        } else {
            const uint32_t w40 = BP(k0, k0, 0x1032), w84 = BP(k0, n, 0x3254), w0 = BP(k0, k0, 0x1010), w4 = BP(k0, k0, 0x3232), w8 = BP(n, n, 0x1010);
            sts64(d, w40, w84);
            sts64(d + 512, BP(k2, k2, 0x1032), BP(k2, m, 0x3254));
            if (lane < 8) { sts128(d - (KW_P - 1056), w0, w0, w40, w4); sts128(d - (KW_P - 1056 - KW_PL), w4, w84, w8, w8); }
            if (lane == 31) sts16(d + (KW_H + 6 - KW_P - 496), m);
        }
    }
#undef S4
#undef H4
#undef BP
}

__device__ __forceinline__ int c_exponent(const uint2& r, const uint2& i, float dt) {
    const uint32_t mx = __vmaxu2(__vmaxu2(r.x & 0x7fff7fffu, r.y & 0x7fff7fffu), __vmaxu2(i.x & 0x7fff7fffu, i.y & 0x7fff7fffu));
    return __reduce_max_sync(0xffffffffu, max(mx, mx << 16) + (__float_as_uint(dt) & 0x7f800000u)) >> 23;
}

__device__ __forceinline__ int warp_v() { int l; asm volatile("mov.u32 %0, %%tid.x;" : "=r"(l)); return __shfl_sync(0xffffffffu, l >> 5, 0); }
__device__ __forceinline__ int lane_v() { int l; asm volatile("mov.u32 %0, %%laneid;" : "=r"(l)); return l; }
__device__ __forceinline__ uint32_t prmt_v(uint32_t a, uint32_t b, uint32_t s) { uint32_t d; asm volatile("prmt.b32 %0, %1, %2, %3;\n" : "=r"(d) : "r"(a), "r"(b), "r"(s)); return d; }
__device__ __forceinline__ uint32_t mov_v(uint32_t a) { uint32_t d; asm volatile("mov.b32 %0, %1;\n" : "=r"(d) : "r"(a)); return d; }
template <int G>
__device__ __forceinline__ void conv_rename(float (&acc)[16][4]) {
#pragma unroll
    for (int i = G; i < 16; i++)
#pragma unroll
        for (int j = 0; j < 4; j++) { float v; asm volatile("mov.b32 %0, %1;\n" : "=f"(v) : "f"(acc[i][j])); acc[i][j] = v; }
}
struct Conv {
    uint32_t kw;
    uint32_t wa;
    uint32_t pa, s2;
    uint32_t s8;
    uint32_t id;
    uint32_t lc;
    uint32_t fs;
    uint32_t fl, yo;
    uint32_t yp;
    size_t ycopy;
    uint32_t ps;
    uint64_t d0;
    int warp;
};
struct Pk { uint32_t w[4]; };
__device__ __forceinline__ Pk pk2(const float (&u)[4], const float (&v)[4]) {
    Pk r;
    r.w[0] = pack_f16(u[0], u[1]); r.w[1] = pack_f16(u[2], u[3]); r.w[2] = pack_f16(v[0], v[1]); r.w[3] = pack_f16(v[2], v[3]);
    return r;
}
__device__ __forceinline__ void park(uint32_t a, const Pk& v) {
    asm volatile("stmatrix.sync.aligned.m8n8.x4.trans.shared.b16 [%0], {%1,%2,%3,%4};\n" ::"r"(a), "r"(v.w[0]), "r"(v.w[1]), "r"(v.w[2]), "r"(v.w[3]) : "memory");
}
__device__ __forceinline__ void conv_constants(uint32_t lc, int l) {
    const int d = (l >> 2) - 2 * (l & 3);
    const int e = d + 8, r4 = (e + 1 + ((e >> 2) & 1)) >> 2, p4 = (e + (((e - 1) >> 2) & 1)) >> 2;
    const uint32_t s2 = r4 == p4 ? 0x1010u : 0x3210u;
    sts64(lc + l * 8, KW_P + ((r4 - 5) >> 1) * 16 + ((r4 - 5) & 1) * 4, s2 | ((d < 0 ? s2 : 0x7654u) << 16));
    const int lo = (d >= 4) - (d < -3), ho = (d >= 5) - (d < -2), le = (d > 4) - (d < -4), he = (d > 5) - (d < -3);
    sts32(lc + 512 + l * 8, (0x5454u + lo * 0x22 + ho * 0x2200) | ((0x3232u + le * 0x22 + he * 0x2200) << 16));
    const int cc = l >> 2, j = l & 3;
    sts64(lc + 256 + l * 8, (j >> 1) * PL_HALF + (16 + cc) * 16 + (j & 1) * 8, (cc >> 1) * (DM * 64) + (cc & 1) * 32 + j * 8);
}
__device__ __forceinline__ void conv_selectors4(Conv& c) {
    const uint2 v = lds64(c.lc + lane_v() * 8);
    c.pa = v.x; c.s2 = v.y;
}
__device__ __forceinline__ void conv_selectors8(Conv& c) { c.s8 = lds32(c.lc + 512 + lane_v() * 8); }
template <int G, int I0, int I1>
__device__ __forceinline__ void conv_load(const Conv& c, uint32_t (&q)[9]) {
    const int wq = c.warp & 3;
    if (G < 2) {
#pragma unroll
        for (int i = I0; i < I1; i++) q[i] = lds32(c.wa + G * 512 + i * 16);
    } else if (G < 4) {
        const uint32_t a = (G == 2 && wq == 0) ? c.wa + 1024 : c.pa + c.kw + wq * 128 + (G < 2 ? 0 : G - 2) * 512;
#pragma unroll
        for (int i = I0; i < I1; i++) q[i] = lds32(a + i * 16);
    } else {
        const uint4 u = lds128(c.kw + KW_H + (G < 4 ? 0 : G - 4) * 64 + wq * 16);
        const uint2 v = lds64(c.kw + KW_H + (G < 4 ? 0 : G - 4) * 64 + wq * 16 + 16);
        q[0] = u.x; q[1] = u.y; q[2] = u.z; q[3] = u.w; q[4] = v.x; q[5] = v.y;
        if (G == 4 && wq == 0) { q[6] = lds32(c.pa + c.kw + 1024); q[7] = lds32(c.pa + c.kw + 1040); }
    }
}
template <int G, int J0, int J1>
__device__ __forceinline__ void conv_frag(const Conv& c, const uint32_t (&q)[9], uint32_t* a, const Pk& dp) {
    const uint32_t dep = dp.w[0];
    if (G < 4) {
        const uint32_t s = (G < 2 || (G == 2 && (c.warp & 3) == 0)) ? c.id : c.s2;
#pragma unroll
        for (int j = J0; j < J1; j++) {
            uint32_t* o = a + 4 * (j - J0);
            o[0] = prmt_v(q[2 * j + 1], dp.w[0], s); o[1] = prmt_v(q[2 * j + 2], dp.w[1], s); o[2] = prmt_v(q[2 * j], dp.w[2], s); o[3] = prmt_v(q[2 * j + 1], dp.w[3], s);
        }
    } else {
        const uint32_t so = prmt_v(c.s8, dep, c.id), se = prmt_v(c.s8, dep, c.id + 0x22);
#pragma unroll
        for (int j = J0; j < J1; j++) {
            uint32_t* o = a + 4 * (j - J0);
            o[0] = prmt_v(q[j + 1], q[j + 2], se); o[1] = prmt_v(q[j + 1], q[j + 2], so); o[2] = prmt_v(q[j], q[j + 1], so);
            if (G == 4 && j == 0 && (c.warp & 3) == 0) {
                o[2] = prmt_v(q[6], dep, c.s2);
                o[0] = prmt_v(q[7], o[0], c.s2 >> 16);
            }
            o[3] = mov_v(o[0]);
        }
    }
}
template <int G, int J0, int J1>
__device__ __forceinline__ void conv_frag(const Conv& c, const uint32_t (&q)[9], uint32_t* a, float depf) {
    const uint32_t d = __float_as_uint(depf);
    conv_frag<G, J0, J1>(c, q, a, Pk{{d, d, d, d}});
}
template <int G, int T, int J0, int J1>
__device__ __forceinline__ void conv_mma(float (&acc)[16][4], const Conv& c, const uint32_t* a) {
#pragma unroll
    for (int j = J0; j < J1; j++) wg_mma<T>(acc, a + 4 * (j - J0), c.d0 - 8 * (2 * G - T) - j);
}
__device__ __forceinline__ float h_lo(uint32_t w) { return __half2float(__ushort_as_half((unsigned short)(w & 0xffffu))); }
__device__ __forceinline__ float h_hi(uint32_t w) { return __half2float(__ushort_as_half((unsigned short)(w >> 16))); }
__device__ __forceinline__ void flush_setup(Conv& c) {
    const uint2 v = lds64(c.lc + 256 + lane_v() * 8);
    c.fl = v.x; c.yo = v.y;
}
template <int Q>
__device__ __forceinline__ void flush_load(const Conv& c, uint32_t pl, uint2 (&f)[4]) {
#pragma unroll
    for (int w = 0; w < 4; w++) f[w] = lds64(c.fl + pl + (Q & 1) * 512 + w * (PLW_B - 64));
}
template <int Q>
__device__ __forceinline__ void flush_load_first(const Conv& c, uint32_t pl, uint2 (&f)[4], float depf) {
    const uint32_t p = prmt_v(c.fl, __float_as_uint(depf), c.id) + pl + (Q & 1) * 512;
#define LDV64(d, a) asm volatile("ld.volatile.shared.v2.u32 {%0,%1}, [%2];\n" : "=r"(d.x), "=r"(d.y) : "r"(a) : "memory")
    LDV64(f[0], p); LDV64(f[1], p + (PLW_B - 64)); LDV64(f[2], p + 2 * (PLW_B - 64)); LDV64(f[3], p + 3 * (PLW_B - 64));
}
#define FDEP __uint_as_float(f[3].y)
template <int Q, int mode>
__device__ __forceinline__ void conv_flush(const Conv& c, const uint2 (&f)[4], unsigned char* gy, uint32_t rx) {
    const uint32_t a0 = hadd2(f[0].x, f[1].x), a1 = hadd2(f[2].x, f[3].x), b0 = hadd2(f[0].y, f[1].y), b1 = hadd2(f[2].y, f[3].y);
    if (Q > 0 && mode == 1) {
        const uint32_t ra = rx + 16 + (Q > 0 ? Q - 1 : 0) * 1024 + (c.warp & 3) * 256 + lane_v() * 8;
        asm volatile("st.async.shared::cluster.mbarrier::complete_tx::bytes.v2.b32 [%0], {%1,%2}, [%3];\n"
                     ::"r"(ra ^ 0x1000000u), "r"(hadd2(a0, a1)), "r"(hadd2(b0, b1)), "r"((rx + (Q > 1 ? 8 : 0)) ^ 0x1000000u) : "memory");
        return;
    }
    float v0 = h_lo(a0) + h_lo(a1), v1 = h_hi(a0) + h_hi(a1), v2 = h_lo(b0) + h_lo(b1), v3 = h_hi(b0) + h_hi(b1);
    if (Q > 0 && mode == 2) {
        const uint2 o = lds64(rx + 16 + (Q > 0 ? Q - 1 : 0) * 1024 + (c.warp & 3) * 256 + lane_v() * 8);
        v0 += h_lo(o.x); v1 += h_hi(o.x); v2 += h_lo(o.y); v3 += h_hi(o.y);
    }
    const uint32_t lo = hmul2_bf(pack_bf16(v0, v1), c.fs), hi = hmul2_bf(pack_bf16(v2, v3), c.fs);
    stg64(gy + Q * 32 * DM * 32 + (c.yo + (Q < 3 ? c.yp : 0u)), lo ^ YKEY, hi ^ YKEY);
}
template <int I, bool S = false> struct IC { static constexpr int value = I; static constexpr bool shared = S; };
template <class T> __device__ constexpr bool wg_is4() { return T::shared; }
#define SLOT(n) (c.ps + (2 + ((n) & 7)) * 128)
#define GO() do { wg_commit(); __syncwarp(); } while (0)
#define DEP acc[15][3]
template <class FG, class FP, class FN>
__device__ __forceinline__ void conv_head(Conv& c, float (&acc)[16][4], uint32_t (&q)[9], uint32_t (&r)[9], uint32_t* a, FG fg, FP pre, FN next) {
    c.id = 0x3210u + (c.warp >> 8);
    conv_load<0, 0, 9>(c, q);
    conv_frag<0, 0, 1>(c, q, a, 0.f);
    pre();
    wg_fence(); wg_first<0>(acc, a, c.d0); GO();
    park(c.ps, Pk{{0u, 0u, 0u, 0u}});
    wg_wait0();
    conv_frag<0, 1, 2>(c, q, a, DEP);
    wg_fence(); conv_mma<0, 0, 1, 2>(acc, c, a); GO();
    fg(IC<0>());
    wg_wait0();
    conv_frag<0, 2, 3>(c, q, a, DEP);
    wg_fence(); conv_mma<0, 0, 2, 3>(acc, c, a); GO();
    conv_load<1, 0, 5>(c, r);
    wg_wait0();
    conv_frag<0, 3, 4>(c, q, a, DEP);
    wg_fence(); conv_mma<0, 0, 3, 4>(acc, c, a); GO();
    conv_load<1, 5, 9>(c, r);
    fg(IC<1>());
    wg_wait0();
    const Pk k = pk2(acc[0], acc[1]);
    conv_rename<2>(acc);
    conv_frag<1, 0, 2>(c, r, a, k);
    wg_fence(); conv_mma<1, 2, 0, 2>(acc, c, a); GO();
    park(SLOT(0), k);
    next(IC<0>());
    fg(IC<2>());
    wg_wait0();
    conv_frag<1, 2, 4>(c, r, a, DEP);
    wg_fence(); conv_mma<1, 2, 2, 4>(acc, c, a); GO();
    next(IC<1>());
    fg(IC<3>());
    wg_wait0();
}
template <class FG, class FP>
__device__ __forceinline__ void conv_run(Conv& c, uint32_t pl, unsigned char* gy, FG fg, FP pre) {
    float acc[16][4];
    uint32_t q[9], r[9], a[32];
    uint2 f[4];
    const int bid = 1 + (c.warp >> 2);
    conv_head(c, acc, q, r, a, fg, pre, [&](auto i) { if (decltype(i)::value == 0) conv_selectors4(c); else conv_load<2, 0, 9>(c, q); });
    Pk k = pk2(acc[2], acc[3]);
    conv_rename<4>(acc);
    conv_frag<2, 0, 4>(c, q, a, k);
    wg_fence(); conv_mma<2, 4, 0, 4>(acc, c, a); GO();
    park(SLOT(2), k);
    conv_load<3, 0, 9>(c, q);
    flush_setup(c);
    bar_sync(bid, 128);
    fg(IC<4>());
    wg_wait0();
    conv_rename<6>(acc);
    flush_load_first<0>(c, pl, f, DEP);
    conv_frag<3, 0, 4>(c, q, a, FDEP);
    wg_fence(); conv_mma<3, 6, 0, 4>(acc, c, a); GO();
    park(SLOT(4), pk2(acc[4], acc[5]));
    conv_load<4, 0, 9>(c, q);
    conv_selectors8(c);
    conv_flush<0, 0>(c, f, gy, 0u);
    fg(IC<5>());
    wg_wait0();
    conv_rename<8>(acc);
    conv_frag<4, 0, 4>(c, q, a, DEP);
    wg_fence(); conv_mma<4, 8, 0, 4>(acc, c, a); GO();
    k = pk2(acc[6], acc[7]);
    park(SLOT(6), k); park(c.ps, k);
    conv_load<5, 0, 9>(c, q);
    bar_sync(bid, 128);
    fg(IC<6>());
    wg_wait0();
    conv_rename<10>(acc);
    flush_load_first<1>(c, pl, f, DEP);
    conv_frag<5, 0, 4>(c, q, a, FDEP);
    wg_fence(); conv_mma<5, 10, 0, 4>(acc, c, a); GO();
    park(SLOT(8), pk2(acc[8], acc[9]));
    conv_load<6, 0, 9>(c, q); conv_load<7, 0, 9>(c, r);
    conv_flush<1, 0>(c, f, gy, 0u);
    fg(IC<7>());
    wg_wait0();
    conv_rename<12>(acc);
    conv_frag<6, 0, 4>(c, q, a, DEP); conv_frag<7, 0, 4>(c, r, a + 16, DEP);
    wg_fence(); conv_mma<6, 12, 0, 4>(acc, c, a); conv_mma<7, 12, 0, 4>(acc, c, a + 16); GO();
    park(SLOT(10), pk2(acc[10], acc[11]));
    bar_sync(bid, 128);
    flush_load<2>(c, pl, f);
    conv_flush<2, 0>(c, f, gy, 0u);
    fg(IC<8>());
    wg_wait0();
    park(SLOT(12), pk2(acc[12], acc[13])); park(SLOT(14), pk2(acc[14], acc[15]));
    bar_sync(bid, 128);
    flush_load<3>(c, pl, f);
    conv_flush<3, 0>(c, f, gy, 0u);
}
template <class FG>
__device__ __forceinline__ void conv_outer(Conv& c, uint32_t pl, unsigned char* gy, uint32_t rx, FG fg) {
    float acc[16][4];
    uint32_t q[9], r[9], a[32];
    uint2 f[4], f2[4];
    const int bid = 1 + (c.warp >> 2);
    conv_head(c, acc, q, r, a, [&](auto gi) { if (decltype(gi)::value == 2) fg(IC<2, true>()); }, [&]() {}, [&](auto i) { if (decltype(i)::value == 0) conv_selectors8(c); else conv_load<6, 0, 9>(c, q); });
    park(SLOT(2), pk2(acc[2], acc[3])); park(SLOT(4), pk2(acc[4], acc[5]));
    const Pk k = pk2(acc[6], acc[7]);
    park(SLOT(6), k);
    conv_load<7, 0, 9>(c, r);
    conv_rename<12>(acc);
    conv_frag<6, 0, 4>(c, q, a, __uint_as_float(k.w[3])); conv_frag<7, 0, 4>(c, r, a + 16, __uint_as_float(k.w[3]));
    wg_fence(); conv_mma<6, 12, 0, 4>(acc, c, a); conv_mma<7, 12, 0, 4>(acc, c, a + 16); GO();
    flush_setup(c);
    bar_sync(bid, 128);
    flush_load<0>(c, pl, f); flush_load<1>(c, pl, f2);
    conv_flush<1, 1>(c, f2, gy, rx);
    conv_flush<0, 1>(c, f, gy, rx);
    wg_wait0();
    bar_sync(bid, 128);
    park(c.ps, k); park(SLOT(8), pk2(acc[8], acc[9])); park(SLOT(10), pk2(acc[10], acc[11]));
    park(SLOT(12), pk2(acc[12], acc[13])); park(SLOT(14), pk2(acc[14], acc[15]));
    bar_sync(bid, 128);
    flush_load<2>(c, pl, f); flush_load<3>(c, pl, f2);
    conv_flush<2, 1>(c, f, gy, rx);
    conv_flush<3, 1>(c, f2, gy, rx);
}
template <class FG>
__device__ __forceinline__ void conv_inner(Conv& c, uint32_t pl, unsigned char* gy, uint32_t rx, FG fg) {
    float acc[16][4];
    uint32_t q[9], a[16];
    uint2 f[4], f2[4];
    const int bid = 1 + (c.warp >> 2);
    c.id = 0x3210u + (c.warp >> 8);
    conv_selectors4(c);
    conv_load<2, 0, 9>(c, q);
    conv_frag<2, 0, 4>(c, q, a, 0.f);
    wg_fence(); wg_first<4>(acc, a, c.d0); conv_mma<2, 4, 1, 4>(acc, c, a + 4); GO();
    conv_load<3, 0, 9>(c, q);
    park(SLOT(2), Pk{{0u, 0u, 0u, 0u}});
    fg(IC<2, true>());
    wg_wait0();
    conv_rename<6>(acc);
    conv_frag<3, 0, 4>(c, q, a, DEP);
    wg_fence(); conv_mma<3, 6, 0, 4>(acc, c, a); GO();
    park(SLOT(4), pk2(acc[4], acc[5]));
    conv_load<4, 0, 9>(c, q);
    conv_selectors8(c);
    wg_wait0();
    conv_rename<8>(acc);
    conv_frag<4, 0, 4>(c, q, a, DEP);
    wg_fence(); conv_mma<4, 8, 0, 4>(acc, c, a); GO();
    const Pk k = pk2(acc[6], acc[7]);
    park(SLOT(6), k); park(c.ps, k);
    conv_load<5, 0, 9>(c, q);
    flush_setup(c);
    wg_wait0();
    conv_rename<10>(acc);
    conv_frag<5, 0, 4>(c, q, a, DEP);
    wg_fence(); conv_mma<5, 10, 0, 4>(acc, c, a); GO();
    park(SLOT(8), pk2(acc[8], acc[9]));
    bar_sync(bid, 128);
    flush_load<1>(c, pl, f);
    mbar_wait(rx);
    conv_flush<1, 2>(c, f, gy, rx);
    wg_wait0();
    bar_sync(bid, 128);
    park(SLOT(10), pk2(acc[10], acc[11])); park(SLOT(12), pk2(acc[12], acc[13])); park(SLOT(14), pk2(acc[14], acc[15]));
    bar_sync(bid, 128);
    flush_load<3>(c, pl, f); flush_load<2>(c, pl, f2);
    mbar_wait(rx + 8);
    conv_flush<3, 2>(c, f, gy, rx);
    conv_flush<2, 2>(c, f2, gy, rx);
}
#undef SLOT
#undef GO
#undef DEP
template <int U0, int U1>
__device__ __forceinline__ void weight_units(uint32_t sb, const CUtensorMap* tg, const CUtensorMap* tu, const CUtensorMap* td, bool w) {
    if (U1 > U0 && w && elect_one()) {
#pragma unroll
        for (int n = U0; n < U1; n++) {
            const int i = n;
            if (i < 12) tma_2d(sb + SM_WG + i * 6912, i < 6 ? tg : tu, 72 * (blockIdx.x >> 1), 288 * (blockIdx.x & 1) + (i % 6) * 48, sb + SM_MISC + 328);
            else tma_2d(sb + SM_WD + (i - 12) * 4736, td, 144 * (blockIdx.x & 1), 72 * (blockIdx.x >> 1) + 8 * (i - 12), sb + SM_MISC + 336);
        }
    }
}
#define WS 1111121111122103100
__device__ constexpr int wsched(int i) {
    unsigned long long v = WS;
    int n = 0;
    for (int k = 19; k >= 1; k--) { if (k < i) n += (int)(v % 10); v /= 10; }
    return n;
}
static_assert(wsched(20) == 21 && wsched(6) <= 7 && wsched(11) <= 12 && wsched(16) <= 17 && wsched(16) == wsched(15), "");
__device__ __forceinline__ void weight_prefetch(const Params& p, int u, int lane) {
    const int b = blockIdx.x;
    const char* a = u < 12 ? reinterpret_cast<const char*>(u < 6 ? p.wg : p.wu) + ((b >> 6) * 288 + (u % 6) * 48) * (FF * 2) + (b & 63) * 6912
                           : reinterpret_cast<const char*>(p.wd) + (72 * (b >> 1) + 8 * (u - 12)) * 1152 + (b & 1) * 4608;
    asm volatile("prefetch.global.L2 [%0];\n" ::"l"(a + lane * 128));
    if (lane < (u < 12 ? 22 : 4)) asm volatile("prefetch.global.L2 [%0];\n" ::"l"(a + 4096 + lane * 128));
}
#define PF0 0
#define PF1 0
#define WPOINT(i, w) do { weight_units<wsched(i), wsched(i + 1)>(sb, &tm_g, &tm_u, &tm_d, w); } while (0)

__global__ void __launch_bounds__(NTHR, 1) __cluster_dims__(2, 1, 1)
fused_kernel(const Params p, const __grid_constant__ CUtensorMap tm_g, const __grid_constant__ CUtensorMap tm_u, const __grid_constant__ CUtensorMap tm_d, const __grid_constant__ CUtensorMap tm_x) {
    extern __shared__ __align__(1024) unsigned char smem[];
    const uint32_t sb = smem_u32(smem);
    const int tid = threadIdx.x, warp = __shfl_sync(0xffffffffu, tid >> 5, 0), lane = tid & 31;
    const int b = blockIdx.x, P = b >> 1, odd = b & 1;
    const int g = lane >> 2, t = lane & 3;
    const int wg = warp >> 2, t128 = tid & 127;
    const uint32_t s_stat = sb + SM_MISC;
    const uint32_t s_key = sb + SM_MISC + 128;
    const uint32_t s_rank = sb + SM_MISC + 256;
    const uint32_t s_k16 = sb + SM_MISC + 192;
    const uint32_t s_cnt = sb + SM_MISC + 320;
    const uint32_t bar_w = sb + SM_MISC + 328, bar_d = bar_w + 8, bar_g = bar_w + 16, bar_x = bar_w + 24, bar_t = bar_w + 32;
    STAMP(0);

    if (warp == 19) {
        if (lane == 0) {
            mbar_init(bar_w, 1); mbar_init(bar_d, 1); mbar_init(bar_g, 1 + OEARLY); mbar_init(sb + SM_RX, 1); mbar_init(sb + SM_RX + 8, 1);
            mbar_init(bar_x, 1); mbar_init(bar_t, 1); mbar_expect(bar_x, 32768);
            asm volatile("fence.mbarrier_init.release.cluster;\n" ::: "memory");
            mbar_expect(bar_w, 82944); mbar_expect(bar_d, 72 * WD_PITCH); mbar_expect(bar_g, 9216); mbar_expect(bar_t, 18 * 1152); mbar_expect(sb + SM_RX, 1024); mbar_expect(sb + SM_RX + 8, 2048);
        }
        __syncwarp();
    } else if (warp == 18) {
#pragma unroll
        for (int i = 0; i < 9; i++) sts128(sb + SM_ZERO + (i * 32 + lane) * 16, 0u, 0u, 0u, 0u);
        fence_async();
        __syncwarp();
    }
    const int ch = wg < 4 ? 4 * b + wg : 512 + P;
    const bf16 *q0 = p.lar + ch * NST, *q1 = p.aim + ch * NST, *q2 = p.cre + ch * NST, *q3 = p.cim + ch * NST;
    asm volatile("" : "+l"(q0), "+l"(q1), "+l"(q2), "+l"(q3));
    const uint32_t ldt = ldo16(p.ldt + ch), pl = ldo16(q0 + t128), pa2 = ldo16(q1 + t128);
    const uint32_t pc = ldo16(q2 + t128), pi = ldo16(q3 + t128);
    const uint2 call_re = ldo64(q2 + 4 * lane), call_im = ldo64(q3 + 4 * lane);
    if (PBAR) { if (wg == 4) bar_sync(0, NWRK); else bar_arrive(0, NWRK); }
    uint4 xv[9], xu[2];
    if (wg == 4) {
        const bf16* xp = p.x + (size_t)(16 * b + 4 * (warp & 3) + (g & 3)) * DM + 288 * (g >> 2) + 8 * t;
#pragma unroll
        for (int c = 0; c < 9; c++) xv[c] = ldo128(xp + c * 32);
        if (warp < 18) {
            const bf16* xq = p.x + (size_t)(16 * b + TOK(g)) * DM + 32 * warp + 8 * t;
            xu[0] = ldo128(xq); xu[1] = ldo128(xq + 2 * DM);
        }
    }
    auto xcols = [&](int z) {
        if (MC) {
            asm volatile("barrier.cluster.wait.aligned;\n" ::: "memory");
            if (elect_one()) tma_4d_mc(sb + SM_XC + odd * 16384, &tm_x, 8 * P + z, 2 * odd, bar_x);
        } else if (elect_one()) tma_4d(sb + SM_XC, &tm_x, 8 * P + z, 0, bar_x);
        __syncwarp();
    };
    if (MC) asm volatile("barrier.cluster.arrive.relaxed.aligned;\n" ::: "memory");
    if (warp == 18) {
        if (lane == 0) bulk_s2g(reinterpret_cast<unsigned char*>(p.s->y) + 96 * 18432 + b * 4608, sb + SM_ZERO, 4608);
        bar_arrive(12, 64);
    }
    if (warp == 19) { bar_sync(12, 64); xcols(0); }
    const uint32_t kw = sb + SM_KW + wg * KW_B;
    const uint32_t tb = table_buf(sb, warp);
    if (wg == 4) {
        const int wq = warp & 3;
        const uint32_t epl = ld_poll32(p.s->hint + (b & 7) * 32 + 1);
        unsigned char* const ud = reinterpret_cast<unsigned char*>(p.s->uT) + (size_t)(8 * wq + 2 * (g >> 1)) * 16384 + b * 128 + (g & 1) * 32 + t * 8;
        uint32_t* const sd_ = p.s->stat + 16 * b + 4 * wq + g;
        const bool own = g < 4 && t == (g >> 1);
        if (own) *reinterpret_cast<volatile uint32_t*>(sd_) = 0u;
        if (wq < 2) {
#pragma unroll
            for (int k = 0; k < 4; k++) *reinterpret_cast<volatile unsigned long long*>(ud + (k >> 1) * 16384 + (k & 1) * 64) = 0ull;
        }
        if (wq == 1) conv_constants(sb + SM_LC, lane);
        uint32_t one;
        asm volatile("st.volatile.shared.u32 [%1], 0x3f803f80;\nld.volatile.shared.u32 %0, [%1];\n" : "=r"(one) : "r"(tb + lane * 4) : "memory");
        float cs[2][4] = {}, d1[2][4] = {}, d2[2][4] = {};
#pragma unroll
        for (int c = 0; c < 9; c++) {
            const uint4 v = xv[c];
            mma_bf16(cs[c & 1], v.x, v.y, v.z, v.w, one, one);
            mma_bf16(d1[c & 1], v.x, v.y, v.z, v.w, v.x, v.z); mma_bf16(d2[c & 1], v.x, v.y, v.z, v.w, v.y, v.w);
        }
        STAMP(27);
        float sm = (cs[0][0] + cs[0][2]) + (cs[1][0] + cs[1][2]);
        float sq = (g & 1) ? (d1[0][1] + d2[0][3]) + (d1[1][1] + d2[1][3]) : (d1[0][0] + d2[0][2]) + (d1[1][0] + d2[1][2]);
        sm += __shfl_xor_sync(0xffffffffu, sm, 18); sq += __shfl_xor_sync(0xffffffffu, sq, 18);
        if (HOLD == 1) bar_arrive(6 + wq, 160);
        float mb, sd;
        ln_stats(sm, sq, mb, sd);
        if (own) *sd_ = (__float_as_uint(mb) >> 16) | (__float_as_uint(sd) & 0x7fff0000u) | (epl << 31);
        STAMPX(22);
        if (wq < PF0) weight_prefetch(p, wq, lane);
        if (HOLD == 2) bar_arrive(6 + wq, 160);
        if (own) stat_store(s_stat + (2 * wq + (g & 1) + 8 * (g >> 1)) * 8, mb, rcp_approx(sd), 0u);
        if (lane == 1) sts32(s_cnt + 4, epl);
        if (wq == 2) asm volatile("cp.async.bulk.wait_group 0;\n" ::: "memory");
        bar_sync(5, 128);
        STAMP(28);
        if (wq >= 2) { bar_arrive(2 * wq - 3, 160); bar_arrive(2 * wq - 2, 160); }
        WPOINT(1, wq == 3);
        if (wq == 2 && lane < 8) p.s->key[8 * b + lane] = epl & 1u;
        if (wq < 2) {
            const uint32_t utag = (epl % 7u + 1u) * 0x10001u;
            uint32_t U[2][4];
#pragma unroll
            for (int hf = 0; hf < 2; hf++) {
                const uint2 st = lds64(s_stat + (g + 8 * hf) * 8);
                const uint32_t X[4] = {xu[hf].x, xu[hf].y, xu[hf].z, xu[hf].w};
#pragma unroll
                for (int k = 0; k < 4; k++) {
                    const uint32_t u = ln_apply(X[k], STAT_M(st), STAT_H(st), STAT_L(st));
                    U[hf][k] = movm((pack_f16(bf_lo(u), bf_hi(u)) & 0xfff8fff8u) | utag);
                }
            }
#pragma unroll
            for (int k = 0; k < 4; k++) stg64(ud + (k >> 1) * 16384 + (k & 1) * 64, U[0][k], U[1][k]);
        }
    } else if (warp == 0) {
#pragma unroll
        for (int i = 0; i < 7; i++) sts128(sb + SM_LNP + (i * 32 + lane) * 16, 0u, 0u, 0u, 0u);
    }
    if (t128 < 2 * UPAD) sts128(sb + SM_U + wg * USLOT_B + (t128 & 1) * ULO_B + (t128 >> 1) * 16, 0u, 0u, 0u, 0u);
    if (t128 >= 124) sts128(kw + (t128 & 1) * 16 + (t128 & 2) * (KW_PL / 2), 0u, 0u, 0u, 0u);
    uint32_t co, cn, cd;
    combine_setup(sb, warp, lane, kw, co, cn, cd);
    const uint4* usrc = wg < 4 ? reinterpret_cast<const uint4*>(p.s->stat) + tid
                               : reinterpret_cast<const uint4*>(p.s->uT) + (P >> 2) * 1024 + (t128 >> 1) * 8 + (P & 3) * 2 + (t128 & 1);
    uint32_t zero;
    {
        uint32_t uo = (uint32_t)(reinterpret_cast<const char*>(usrc) - reinterpret_cast<const char*>(p.s)), pk = (cn - co + 1024) | ((cd - kw) << 16);
        asm volatile("st.volatile.shared.v4.u32 [%4], {0, %1, %2, %3};\nld.volatile.shared.v4.u32 {%0, %1, %2, %3}, [%4];\n" : "=r"(zero), "+r"(co), "+r"(pk), "+r"(uo) : "r"(tb + lane * 16) : "memory");
        cn = co + (pk & 0xffffu) - 1024; cd = kw + (pk >> 16);
        usrc = reinterpret_cast<const uint4*>(reinterpret_cast<const char*>(p.s) + uo);
    }
    const float dt = exp_bf(__uint_as_float(__byte_perm(ldt, zero, 0x1044)));
    STAMP(1);
    if (wg < 4) { STAMPX(16); }
    KGen kg;
    kgen_setup(kg, __uint_as_float(__byte_perm(pl, zero, 0x1044)), __uint_as_float(__byte_perm(pa2, zero, 0x1044)), dt);
    kgen_rows(kg, tb, lane);
    STAMP(2);
    const int E = min(max(c_exponent(call_re, call_im, dt) - 243, -120), 120);
    kgen_chain(kg, pc, pi, dt * __uint_as_float((uint32_t)(128 - E) << 23));
    STAMP(3);
    WPOINT(2, warp == 19);
    kgen_cols(kg, tb, lane);
    STAMP(4);
    WPOINT(3, warp == 19);
    if (wg < 4) { STAMPX(17); }
    if (HOLD && wg < 4) bar_sync(6 + (warp & 3), 160);
    if (wg < 4) { STAMPX(19); }
    kgen_mma(kg, tb, lane);
    if (wg < 4) { STAMPX(20); }
    STAMP(5);
    WPOINT(4, warp == 19);
    if (wg < 4) bar_sync(1 + wg, 160); else bar_sync(5, 128);
    if (wg < 4) { STAMPX(21); }
    uint4 uv0, uv1;
    if (PEARLY) { uv0 = ld_poll(usrc); if (wg == 4) uv1 = ld_poll(usrc + 512); }
    kgen_combine(warp & 3, lane, co, cn, cd);
    const uint32_t ep = lds32(s_cnt + 4);
    if (!PEARLY) { uv0 = ld_poll(usrc); if (wg == 4) uv1 = ld_poll(usrc + 512); }
    STAMP(6);
    if (wg < 4) { STAMPX(18); }
    WPOINT(5, warp == 19);
    if (MC && warp != 19) asm volatile("barrier.cluster.wait.aligned;\n" ::: "memory");
    {
        const int wq = warp & 3;
        Conv c;
        const uint32_t pln = sb + SM_PL + wg * PL_B;
        const int e = g - 2 * t + 7;
        c.kw = kw; c.wa = kw + ((e >> 2) & 1) * KW_PL + (8 * wq + (e >> 3)) * 16 + (e & 3) * 4;
        c.ps = mov_v(pln + wq * PLW_B + ((lane >> 3) & 1) * PL_HALF + ((lane >> 4) * 8 + (lane & 7)) * 16); c.warp = warp;
        c.lc = sb + SM_LC; c.fs = (uint32_t)(127 + E) * 0x800080u; c.yp = (__shfl_sync(0xffffffffu, ep, 0) & 1u) * (NCTA * 18432u);
        c.d0 = ((uint64_t)(ULO_B >> 4) << 16) | ((uint64_t)(128 >> 4) << 32) | (uint64_t)(((sb + SM_U + wg * USLOT_B + UPAD * 16) & 0x3FFFF) >> 4);
        unsigned char* gy = reinterpret_cast<unsigned char*>(p.s->y) + ((size_t)(4 * wq) * DM + ch) * 64;
        auto hook = [&](auto gi) {
                     constexpr int G = decltype(gi)::value;
                     if (G == (wg_is4<decltype(gi)>() ? 2 : 5)) asm volatile("barrier.cluster.wait.aligned;\n" ::: "memory");
                     if (!wg_is4<decltype(gi)>() && G < 4 && warp == HW) {
                         const int l2 = lane_v();
                         unsigned char* const sc = reinterpret_cast<unsigned char*>(p.s);
                         if (G == 0 && l2 < 2) bulk_s2g(sc + offsetof(Scratch, rows) + b * 4608 + l2 * 2304, sb + SM_LNP, 2304);
                         if (b < 96 && l2 < (G ? 3 : 1))
                             bulk_s2g(l2 ? sc + offsetof(Scratch, y) + (NCTA * 18432u - c.yp) + b * 18432 + (2 * G + l2 - 3) * 3072 : sc + offsetof(Scratch, part) + b * 12288 + G * 3072,
                                      sb + SM_LNP, 3072);
                         __syncwarp();
                     }
                     if (!wg_is4<decltype(gi)>() && PF1 && G >= PF1 && G < PF1 + 2 && (warp >> 1) == 2) weight_prefetch(p, 17 + 2 * (G - PF1) + (warp & 1), lane_v());
                     if (!wg_is4<decltype(gi)>()) WPOINT(6 + G, warp == 12 + (G & 3));
                     if (!wg_is4<decltype(gi)>() && G == XG && warp == HW) { asm volatile("cp.async.bulk.wait_group 0;\n" ::: "memory"); __syncwarp(); }
                     if (!wg_is4<decltype(gi)>() && G == XG && warp == HW && elect_one()) {
                         bulk_g2s(sb + SM_XT, p.x + (size_t)16 * b * DM, 16 * 1152, bar_t);
                         bulk_g2s(sb + SM_XT + 16 * 1152, p.dsk, 1152, bar_t);
                         bulk_g2s(sb + SM_XT + 17 * 1152, p.wr, 1152, bar_t);
                     }
                 };
        bar_sync(1 + wg, 128);
        if (wg < 4) {
            asm volatile("barrier.cluster.arrive.relaxed.aligned;\n" ::: "memory");
            conv_run(c, pln + wq * 128, gy, hook, [&]() {
                STAMPX(23);
                mbar_wait(bar_x);
                STAMP(9);
                STAMPX(24);
                uint2 xc[4];
                uint32_t xw[4][2];
#pragma unroll
                for (int j = 0; j < 4; j++) xc[j] = lds64(sb + SM_XC + wg * 8192 + j * 2048 + t128 * 16 + odd * 8);
#pragma unroll
                for (int i = 0; i < 8; i++) {
                    const int k = i >> 1, h = i & 1;
                    xw[k][h] = prmt_v(k < 2 ? xc[2 * h].x : xc[2 * h].y, k < 2 ? xc[2 * h + 1].x : xc[2 * h + 1].y, (k & 1) ? 0x7632 : 0x5410);
                }
                const uint32_t ub = mov_v(sb + SM_U + UPAD * 16 + ((tid >> 1) & 1) * ULO_B + (tid >> 2) * 16 + (tid & 1) * 8), tag = ep << 31;
                int it = 0;
                while (min(min((int)(uv0.x ^ tag), (int)(uv0.y ^ tag)), min((int)(uv0.z ^ tag), (int)(uv0.w ^ tag))) < 0x10000) {
                    if (++it > SPIN_LIMIT) TRAP();
                    uv0 = ld_poll(usrc);
                }
                STAMP(8);
                STAMPX(26);
                const float r0 = rcp_approx(fabsf(bf_hi(uv0.x))), r1 = rcp_approx(fabsf(bf_hi(uv0.y))), r2 = rcp_approx(fabsf(bf_hi(uv0.z))), r3 = rcp_approx(fabsf(bf_hi(uv0.w)));
                const uint32_t m[2] = {__byte_perm(uv0.x, uv0.y, 0x5410), __byte_perm(uv0.z, uv0.w, 0x5410)};
                const uint32_t rh[2] = {pack_bf16(r0, r1), pack_bf16(r2, r3)};
                const uint32_t rl[2] = {pack_bf16(r0 - bf_lo(rh[0]), r1 - bf_hi(rh[0])), pack_bf16(r2 - bf_lo(rh[1]), r3 - bf_hi(rh[1]))};
#pragma unroll
                for (int k = 0; k < 4; k++) {
                    const uint32_t u0 = ln_apply(xw[k][0], m[0], rh[0], rl[0]), u1 = ln_apply(xw[k][1], m[1], rh[1], rl[1]);
                    sts64(ub + k * USLOT_B, pack_f16(bf_lo(u0), bf_hi(u0)), pack_f16(bf_lo(u1), bf_hi(u1)));
                }
                STAMPX(29);
                fence_async();
                bar_sync(14, 512);
                STAMP(7);
            });
        } else {
            auto stage = [&]() {
                const uint32_t tag = (ep % 7u + 1u) * 0x10001u;
                int it = 0;
                while (true) {
                    uv0.x ^= tag; uv0.y ^= tag; uv0.z ^= tag; uv0.w ^= tag; uv1.x ^= tag; uv1.y ^= tag; uv1.z ^= tag; uv1.w ^= tag;
                    if ((((uv0.x | uv0.y | uv0.z) | (uv0.w | uv1.x | uv1.y) | (uv1.z | uv1.w)) & 0x70007u) == 0) break;
                    if (++it > SPIN_LIMIT) TRAP();
                    uv0 = ld_poll(usrc); uv1 = ld_poll(usrc + 512);
                }
                STAMP(8);
                const uint32_t ub = sb + SM_U + UPAD * 16 + 4 * USLOT_B + (t128 & 1) * ULO_B + (t128 >> 1) * 16;
                sts128(ub, uv0.x, uv0.y, uv0.z, uv0.w);
                sts128(ub + 1024, uv1.x, uv1.y, uv1.z, uv1.w);
                fence_async();
                asm volatile("barrier.cluster.arrive.relaxed.aligned;\n" ::: "memory");
                bar_sync(5, 128);
                STAMP(7);
            };
            stage();
            if (odd) conv_inner(c, pln + wq * 128, gy, sb + SM_RX, hook);
            else conv_outer(c, pln + wq * 128, gy, sb + SM_RX, hook);
        }
        STAMP(10);
    }
    {
    const int lane = lane_v(), tid = 32 * warp + lane, g = lane >> 2, t = lane & 3;
    const uint32_t par = ~lds32(s_cnt + 4) & 1u;
    if (CBAR) bar_sync(0, NWRK);
    STAMP(11);
    uint32_t H[2][4] = {}, U2[2][4] = {};
    uint32_t WA[9][4], WD[18];
    auto publish = [&](bool hi, int slot) {
        uint4* rowp = reinterpret_cast<uint4*>(p.s->rows) + slot * 144 + warp * 4 + t;
        stg128(rowp, nzw(hi ? U2[1][0] : U2[0][0]), nzw(hi ? U2[1][1] : U2[0][1]), nzw(hi ? U2[1][2] : U2[0][2]), nzw(hi ? U2[1][3] : U2[0][3]));
        stg128(rowp + 72, nzw(hi ? H[1][0] : H[0][0]), nzw(hi ? H[1][1] : H[0][1]), nzw(hi ? H[1][2] : H[0][2]), nzw(hi ? H[1][3] : H[0][3]));
    };
#define KTOK(k) (2047 - (int)(((k) >> 5) & 0x7ffu))
#define KLATE(k) (((k) & 0x1cu) != 0)
#define KSLOT(k, s) (KLATE(k) ? 2 * NCTA + (s) : 2 * (KTOK(k) >> 4) + (int)(((k) >> 1) & 1u))
    const uint4* const rsrc = reinterpret_cast<const uint4*>(p.s->rows) + 36 * odd;
    auto gather = [&](uint32_t mine) {
        int it = 0;
#pragma unroll 1
        for (int r = 0; r < 9; r++) {
            const uint32_t k = r < 8 ? __shfl_sync(0xffffffffu, mine, 4 * r) : mine;
            const int row = r < 8 ? r : g, c = r < 8 ? lane : 32 + t;
            uint4 v;
            do { v = ld_poll(rsrc + KSLOT(k, row) * 144 + c); if (++it > SPIN_LIMIT) TRAP(); } while (!min4(v));
            sts128(sb + SM_XS + row * XS_PITCH + c * 16, v.x, v.y, v.z, v.w);
        }
    };
    if (warp < 18) {
        const unsigned char* ys = reinterpret_cast<const unsigned char*>(p.s->y) + (b < 96 ? (par ^ 1u) * (NCTA * 18432u) : 0u) +
                                  ((P * DM + 32 * warp + 8 * (g >> 1) + (g & 1)) * 64 + odd * 32 + t * 8);
        uint2 yv[4];
#pragma unroll
        for (int k = 0; k < 4; k++) yv[k] = ld_poll64(ys + k * 128);
        mbar_wait(bar_t);
        const uint32_t xa = sb + SM_XT + warp * 64 + t * 16;
        const uint4 x0 = lds128(xa + TOK(g) * 1152), x1 = lds128(xa + (TOK(g) + 2) * 1152), dk = lds128(xa + 16 * 1152);
        uint4 wr = make_uint4(0u, 0u, 0u, 0u);
        if (g == 0) wr = lds128(xa + 17 * 1152);
        const uint32_t Z[2][4] = {{x0.x, x0.y, x0.z, x0.w}, {x1.x, x1.y, x1.z, x1.w}}, D4[4] = {dk.x, dk.y, dk.z, dk.w};
#pragma unroll
        for (int hf = 0; hf < 2; hf++) {
            const uint2 st = lds64(s_stat + (g + 8 * hf) * 8);
#pragma unroll
            for (int k = 0; k < 4; k++) H[hf][k] = hmul2_bf(ln_apply(Z[hf][k], STAT_M(st), STAT_H(st), STAT_L(st)), D4[k]);
        }
        int it = 0;
        while (__any_sync(0xffffffffu, min(min(min(yv[0].x, yv[0].y), min(yv[1].x, yv[1].y)), min(min(yv[2].x, yv[2].y), min(yv[3].x, yv[3].y))) == 0)) {
#pragma unroll
            for (int k = 0; k < 4; k++) yv[k] = ld_poll64(ys + k * 128);
            if (++it > SPIN_LIMIT) TRAP();
        }
        STAMP(12);
#pragma unroll
        for (int k = 0; k < 4; k++) {
            H[0][k] = hadd2_bf(Z[0][k], hadd2_bf(movm(yv[k].x ^ YKEY), H[0][k]));
            H[1][k] = hadd2_bf(Z[1][k], hadd2_bf(movm(yv[k].y ^ YKEY), H[1][k]));
        }
        ln_partial(H, sb + SM_LNP, warp, g, t);
        bar_arrive(6, NWRK);
        STAMP(13);
        bar_sync(7, 608);
        STAMP(14);
#pragma unroll
        for (int hf = 0; hf < 2; hf++) {
            const uint2 st = lds64(s_stat + (g + 8 * hf) * 8);
#pragma unroll
            for (int k = 0; k < 4; k++) U2[hf][k] = ln_apply(H[hf][k], STAT_M(st), STAT_H(st), STAT_L(st));
        }
        {
            float cs[4] = {0.f, 0.f, 0.f, 0.f};
            mma_bf16(cs, U2[0][0], U2[1][0], U2[0][1], U2[1][1], wr.x, wr.y);
            mma_bf16(cs, U2[0][2], U2[1][2], U2[0][3], U2[1][3], wr.z, wr.w);
            if (t == 0) { stsf(sb + SM_LNP + ((32 + g) * 20 + warp) * 4, cs[0]); stsf(sb + SM_LNP + ((40 + g) * 20 + warp) * 4, cs[2]); }
            bar_arrive(8, 608);
        }
        bar_sync(9, 608);
        const uint32_t rk[2] = {lds32(s_rank + g * 4), lds32(s_rank + 32 + g * 4)};
#pragma unroll
        for (int hf = 0; hf < 2; hf++)
            sts128(sb + SM_OUT + (TOK(g) + 2 * hf) * (DM * 2) + warp * 64 + t * 16,
                   hadd2_bf(H[hf][0], U2[hf][0]), hadd2_bf(H[hf][1], U2[hf][1]), hadd2_bf(H[hf][2], U2[hf][2]), hadd2_bf(H[hf][3], U2[hf][3]));
        fence_async();
        if (OEARLY) bar_arrive(10, 608);
        uint32_t lo = min(rk[0], rk[1]), hi = max(rk[0], rk[1]);
#pragma unroll 1
        while (lo < 2) { publish(lo == rk[1], 2 * b + lo); lo = hi; hi = 16; }
        STAMP(15);
        {
            const int mi = lane >> 3, rr = lane & 7;
            mbar_wait(bar_w);
            const uint32_t aad = sb + SM_WG + (mi & 1) * SM_WU + ((warp & 1) * 144 + rr + 8 * (mi >> 1)) * W_PITCH + (warp >> 1) * 16;
#pragma unroll
            for (int k = 0; k < 9; k++) ldsm_x4_t(WA[k][0], WA[k][1], WA[k][2], WA[k][3], aad + k * 16 * W_PITCH);
        }
        STAMP2(17);
        bar_sync(11, NWRK);
    } else if (warp == 18) {
        bar_sync(6, NWRK);
        {
            float mb, rc;
            ln_finish(sum18(sb + SM_LNP + lane * 80), lane, mb, rc);
            if (lane < 16) stat_store(s_stat + lane * 8, mb, rc, 0u);
        }
        bar_arrive(7, 608);
        const uint4* ksrc = reinterpret_cast<const uint4*>(p.s->key) + lane;
        const uint32_t klo = (uint32_t)(2047 - 16 * b - ROWTOK(lane & 15)) << 5 | par;
        bar_sync(8, 608);
        {
            const float r = sum18(sb + SM_LNP + (32 + (lane & 15)) * 80);
            const uint32_t bits = pack_bf16(0.f, r);
            const uint32_t me = ((bits ^ ((uint32_t)((int)bits >> 31) | 0x80000000u)) & 0xffff0000u) | klo;
            sts32(s_k16 + (lane & 15) * 4, me);
            __syncwarp();
            const uint4 v = lds128(s_k16 + (lane & 16) * 2), w = lds128(s_k16 + (lane & 16) * 2 + 16);
            int rank = ((v.x > me) + (v.y > me)) + ((v.z > me) + (v.w > me)) + (((w.x > me) + (w.y > me)) + ((w.z > me) + (w.w > me)));
            rank += __shfl_xor_sync(0xffffffffu, rank, 16);
            if (lane < 16 && rank < 8) p.s->key[8 * b + rank] = me | (rank << 1);
            if (lane >= 16) sts32(s_rank + (lane & 15) * 4, rank);
        }
        bar_arrive(9, 608);
        uint4 kq[4];
        int it = 0;
        if (KDLY) delay(KDLY);
        do {
#pragma unroll
            for (int i = 0; i < 4; i++) kq[i] = ld_poll(ksrc + lane + 64 * i);
            if (++it > SPIN_LIMIT) TRAP();
        } while (__any_sync(0xffffffffu, ((((kq[0].x ^ par) | (kq[0].y ^ par) | (kq[0].z ^ par)) | ((kq[1].x ^ par) | (kq[1].y ^ par) | (kq[1].z ^ par)) |
                                           ((kq[2].x ^ par) | (kq[2].y ^ par) | (kq[2].z ^ par)) | ((kq[3].x ^ par) | (kq[3].y ^ par) | (kq[3].z ^ par))) & 1u) != 0));
        STAMPW(16);
        uint32_t u[4], mine = 0, m;
        {
            uint32_t S[2][4];
#pragma unroll
            for (int i = 0; i < 2; i++) {
                const uint4 &c = kq[2 * i], &d = kq[2 * i + 1];
                const uint32_t m1 = min(c.x, d.x), m2 = max(c.y, d.y);
                S[i][0] = max(c.x, d.x); S[i][1] = max(m1, m2); S[i][2] = min(m1, m2); S[i][3] = min(c.y, d.y);
            }
            const uint32_t a0 = max(S[0][0], S[1][3]), a1 = max(S[0][1], S[1][2]), a2 = max(S[0][2], S[1][1]), a3 = max(S[0][3], S[1][0]);
            const uint32_t b0 = max(a0, a2), b2 = min(a0, a2), b1 = max(a1, a3), b3 = min(a1, a3);
            u[0] = max(b0, b1); u[1] = min(b0, b1); u[2] = max(b2, b3); u[3] = min(b2, b3);
        }
        uint4 v[9];
#pragma unroll
        for (int r = 0; r < 8; r++) {
            m = __reduce_max_sync(0xffffffffu, u[0]);
            if (u[0] == m) { u[0] = u[1]; u[1] = u[2]; u[2] = u[3]; u[3] = 0; }
            if (g == r) mine = m;
            v[r] = ld_poll(rsrc + (2 * (KTOK(m) >> 4) + ((m >> 1) & 1u)) * 144 + lane);
        }
        v[8] = ld_poll(rsrc + (2 * (KTOK(mine) >> 4) + ((mine >> 1) & 1u)) * 144 + 32 + t);
        bool again = __any_sync(0xffffffffu, u[0] == 0 || max(max(kq[0].z, kq[1].z), max(kq[2].z, kq[3].z)) > m);
        if (again) {
#pragma unroll 1
            for (int i = 0; i < 8; i++) {
                uint4 k;
                do { k = ld_poll(ksrc + 32 * i); if (++it > SPIN_LIMIT) TRAP(); } while (((k.x ^ par) | (k.y ^ par) | (k.z ^ par) | (k.w ^ par)) & 1u);
                sts128(sb + SM_KEYS + (32 * i + lane) * 16, k.x, k.y, k.z, k.w);
            }
            m = 0xffffffffu;
#pragma unroll 1
            for (int r = 0; r < 8; r++) {
                uint32_t c = 0;
#pragma unroll 2
                for (int i = 0; i < 8; i++) {
                    const uint4 k = lds128(sb + SM_KEYS + (32 * i + lane) * 16);
                    c = max(max(c, k.x < m ? k.x : 0u), max(k.y < m ? k.y : 0u, max(k.z < m ? k.z : 0u, k.w < m ? k.w : 0u)));
                }
                m = __reduce_max_sync(0xffffffffu, c);
                if (g == r) mine = m;
            }
        }
        if (t == 0) sts32(s_key + g * 4, mine);
        uint32_t mn = 1;
#pragma unroll
        for (int r = 0; r < 9; r++) {
            sts128(sb + SM_XS + (r < 8 ? r * XS_PITCH + lane * 16 : g * XS_PITCH + (32 + t) * 16), v[r].x, v[r].y, v[r].z, v[r].w);
            mn = min(mn, min4(v[r]));
        }
        if ((again || __any_sync(0xffffffffu, mn == 0)) && !__any_sync(0xffffffffu, KLATE(mine))) gather(mine);
        STAMPW(18);
        bar_sync(11, NWRK);
    } else {
        bar_sync(6, NWRK);
        WPOINT(16, true);
        if (wsched(18) > wsched(17)) delay(WDLY);
        WPOINT(17, true);
        if (OEARLY) {
            bar_sync(10, 608);
            if (lane == 0) bulk_s2g(p.out + (size_t)16 * b * DM, sb + SM_OUT, 16 * DM * 2);
            __syncwarp();
        } else if (wsched(19) > wsched(18)) delay(WDLY);
        WPOINT(18, true);
        if (wsched(20) > wsched(19)) delay(WDLY);
        WPOINT(19, true);
        bar_sync(11, NWRK);
    }
    STAMP2(19);
    const uint32_t kk = lds32(s_key + (lane & 7) * 4);
    float e4[4];
    auto gate_up = [&]() {
        float c4[3][4];
#pragma unroll
        for (int i = 0; i < 3; i++)
#pragma unroll
            for (int j = 0; j < 4; j++) c4[i][j] = 0.f;
        const uint32_t bad = sb + SM_XS + (lane & 7) * XS_PITCH + ((warp & 1) * 144 + 8 * (lane >> 3)) * 2;
#pragma unroll
        for (int k = 0; k < 9; k += 2) {
            uint32_t b0, b1, b2, b3;
            ldsm_x4(b0, b1, b2, b3, bad + k * 32);
            mma_bf16(c4[k % 3], WA[k][0], WA[k][1], WA[k][2], WA[k][3], b0, b1);
            if (k < 8) mma_bf16(c4[(k + 1) % 3], WA[k + 1][0], WA[k + 1][1], WA[k + 1][2], WA[k + 1][3], b2, b3);
        }
#pragma unroll
        for (int j = 0; j < 4; j++) e4[j] = c4[0][j] + c4[1][j] + c4[2][j];
    };
    if (warp < 18) gate_up();
    if (!OEARLY && warp == 19) {
        const uint32_t sel = __reduce_or_sync(0xffffffffu, (KTOK(kk) >> 4) == b ? 1u << (KTOK(kk) & 15) : 0u);
        if (sel ? lane < 16 && !((sel >> lane) & 1u) : lane == 0) bulk_s2g(p.out + (size_t)(16 * b + lane) * DM, sb + SM_OUT + lane * (DM * 2), sel ? DM * 2 : 16 * DM * 2);
        __syncwarp();
    }
    if (OEARLY && tid == 608) {
        asm volatile("cp.async.bulk.wait_group 0;\n" ::: "memory");
        asm volatile("mbarrier.arrive.relaxed.cluster.shared::cluster.b64 _, [%0];\n" ::"r"(bar_g ^ 0x1000000u) : "memory");
    }
    if (__any_sync(0xffffffffu, KLATE(kk))) {
        const uint32_t ep = lds32(s_cnt + 4);
        const bool own = KLATE(kk) && (KTOK(kk) >> 4) == b;
        uint32_t todo = __ballot_sync(0xffffffffu, own) & 0xffu;
        if (todo) {
#pragma unroll 1
            while (todo) {
                const int s = __ffs(todo) - 1, tk = KTOK(__shfl_sync(0xffffffffu, kk, s));
                todo &= todo - 1;
                if (warp < 18 && (tk & 13) == TOK(g)) publish(tk & 2, 2 * NCTA + s);
            }
            __threadfence();
        }
        bar_sync(0, NWRK);
        if (tid < NSEL && own) *reinterpret_cast<volatile unsigned*>(p.s->flag + tid) = ep + 1u;
        int it = 0;
        while (__any_sync(0xffffffffu, KLATE(kk) && ld_poll32(p.s->flag + (lane & 7)) != ep + 1u)) { if (++it > SPIN_LIMIT) TRAP(); }
        __threadfence();
        if (warp == 18) gather(__shfl_sync(0xffffffffu, kk, g));
        bar_sync(0, NWRK);
        if (warp < 18) gate_up();
    }
    if (warp < 18) {
        const uint32_t ex = sb + SM_EX + (2 * odd + (warp & 1)) * 4608 + (warp >> 1) * 512 + lane * 16;
        asm volatile("st.async.shared::cluster.mbarrier::complete_tx::bytes.v4.f32 [%0], {%1,%2,%3,%4}, [%5];\n"
                     ::"r"(ex ^ 0x1000000u), "f"(e4[0]), "f"(e4[1]), "f"(e4[2]), "f"(e4[3]), "r"(bar_g ^ 0x1000000u) : "memory");
        sts128f(ex, e4);
        if (warp < 9) bar_sync(12, 576); else bar_arrive(12, 576);
        const int mi = lane >> 3, rr = lane & 7;
        mbar_wait(bar_d);
        const uint32_t base = sb + SM_WD + (2 * warp + (mi & 1)) * 16 + rr * WD_PITCH;
#pragma unroll
        for (int k = 0; k < 4; k++) ldsm_x4_t(WD[4 * k], WD[4 * k + 1], WD[4 * k + 2], WD[4 * k + 3], base + (k * 16 + 8 * (mi >> 1)) * WD_PITCH);
        ldsm_x2_t(WD[16], WD[17], base + 64 * WD_PITCH);
    }
    STAMP2(20);
    const int grp = 3 * b + warp - 17, fsl = 2 * t + ((lane >> 3) & 1), fc = 16 * (grp >> 3) + (grp & 7) + 8 * (lane >> 4);
    const uint32_t fk = __shfl_sync(0xffffffffu, kk, fsl);
    uint32_t hw = 0, uw = 0;
    const uint32_t* const fsrc = p.s->rows + KSLOT(fk, fsl) * DM + (fc >> 1);
    if (warp < 9) {
        mbar_wait(bar_g);
        const uint32_t ex = sb + SM_EX + tid * 16;
        const uint4 a = lds128(ex), c = lds128(ex + 4608), d = lds128(ex + 9216), e = lds128(ex + 13824);
#define S4(f) rbf((__uint_as_float(a.f) + __uint_as_float(c.f)) + (__uint_as_float(d.f) + __uint_as_float(e.f)))
        const float G0 = S4(x), G1 = S4(y), U0 = S4(z), U1 = S4(w);
#undef S4
        sts32(sb + SM_GU + tid * 4, pack_bf16(rbf(__fdividef(G0, 1.0f + __expf(-G0))) * U0, rbf(__fdividef(G1, 1.0f + __expf(-G1))) * U1));
    } else if (warp >= 17) {
        if (b < 96) { hw = ld_poll32(fsrc + 288); uw = ld_poll32(fsrc); }
    }
    bar_sync(13, NWRK);
    STAMP2(21);
    if (warp < 18) {
        uint32_t gb[9];
        ldsm_x4_t(gb[0], gb[1], gb[2], gb[3], sb + SM_GU + lane * 16);
        ldsm_x4_t(gb[4], gb[5], gb[6], gb[7], sb + SM_GU + 512 + lane * 16);
        ldsm_x1_t(gb[8], sb + SM_GU + 1024 + (lane & 7) * 16);
        float c4[4] = {0.f, 0.f, 0.f, 0.f}, d4[4] = {0.f, 0.f, 0.f, 0.f};
        mma_bf16(c4, WD[0], WD[1], WD[2], WD[3], gb[0], gb[1]);
        mma_bf16(d4, WD[4], WD[5], WD[6], WD[7], gb[2], gb[3]);
        mma_bf16(c4, WD[8], WD[9], WD[10], WD[11], gb[4], gb[5]);
        mma_bf16(d4, WD[12], WD[13], WD[14], WD[15], gb[6], gb[7]);
        mma_bf16(c4, WD[16], WD[17], 0u, 0u, gb[8], 0u);
        stg128(p.s->part + ((8 * (18 * odd + warp) + g) * 64 + P) * 16 + t * 4,
               __float_as_uint(c4[0] + d4[0]) | 1u, __float_as_uint(c4[1] + d4[1]) | 1u, __float_as_uint(c4[2] + d4[2]) | 1u, __float_as_uint(c4[3] + d4[3]) | 1u);
    }
    STAMP2(22);
    if (warp >= 17 && b < 96) {
        int it = 0;
        while (!hw || !uw) { hw = ld_poll32(fsrc + 288); uw = ld_poll32(fsrc); if (++it > SPIN_LIMIT) TRAP(); }
        const uint32_t bits = (fk ^ ((uint32_t)((int)~fk >> 31) | 0x80000000u)) & 0xffff0000u;
        const float rs = rbf(__fdividef(1.0f, 1.0f + __expf(-__uint_as_float(bits))));
        const float hv = (fc & 1) ? bf_hi(hw) : bf_lo(hw), u2 = (fc & 1) ? bf_hi(uw) : bf_lo(uw);
        bf16* const dst = p.out + KTOK(fk) * DM + fc;
        delay(warp > 17 ? FDLY + 250 : FDLY);
        const uint4* src = reinterpret_cast<const uint4*>(p.s->part) + grp * 256 + lane;
        uint4 a[8];
        do {
#pragma unroll
            for (int i = 0; i < 8; i++) a[i] = ld_poll(src + 32 * i);
            if (++it > SPIN_LIMIT) TRAP();
#define A4(v) (v.x & v.y & v.z & v.w)
        } while (!(((A4(a[0]) & A4(a[1])) & (A4(a[2]) & A4(a[3])) & (A4(a[4]) & A4(a[5])) & (A4(a[6]) & A4(a[7]))) & 1u));
#undef A4
        STAMP2(24);
#define S8(f) (((__uint_as_float(a[0].f) + __uint_as_float(a[1].f)) + (__uint_as_float(a[2].f) + __uint_as_float(a[3].f))) + \
               ((__uint_as_float(a[4].f) + __uint_as_float(a[5].f)) + (__uint_as_float(a[6].f) + __uint_as_float(a[7].f))))
        const float s0 = S8(x), s1 = S8(y), s2 = S8(z), s3 = S8(w);
#undef S8
        const bool up = lane & 16, od = lane & 8;
        const float r0 = (up ? s2 : s0) + __shfl_xor_sync(0xffffffffu, up ? s0 : s2, 16), r1 = (up ? s3 : s1) + __shfl_xor_sync(0xffffffffu, up ? s1 : s3, 16);
        float y = (od ? r1 : r0) + __shfl_xor_sync(0xffffffffu, od ? r0 : r1, 8);
        y += __shfl_xor_sync(0xffffffffu, y, 4);
        if (!(lane & 4)) *dst = __float2bfloat16_rn(hv + rbf(u2 + rbf(rbf(y) * rs)));
    }
    if (warp == 19) asm volatile("cp.async.bulk.wait_group.read 0;\n" ::: "memory");
    if (b == 0 && tid < 8) *reinterpret_cast<volatile unsigned*>(p.s->hint + tid * 32 + 1) = lds32(s_cnt + 4) + 1u;
    STAMP(25);
    }
}

typedef CUresult (*PFN_tmEncode)(CUtensorMap*, CUtensorMapDataType, cuuint32_t, void*, const cuuint64_t*, const cuuint64_t*, const cuuint32_t*,
                                 const cuuint32_t*, CUtensorMapInterleave, CUtensorMapSwizzle, CUtensorMapL2promotion, CUtensorMapFloatOOBfill);

extern "C" void kernel_launch(void* const* d_in, const int* in_sizes, int n_in, void* d_out, int out_size) {
    Params p;
    p.x = (const bf16*)d_in[0];
    p.lar = (const bf16*)d_in[1];
    p.aim = (const bf16*)d_in[2];
    p.cre = (const bf16*)d_in[3];
    p.cim = (const bf16*)d_in[4];
    p.ldt = (const bf16*)d_in[5];
    p.dsk = (const bf16*)d_in[6];
    p.wr = (const bf16*)d_in[8];
    p.wg = (const bf16*)d_in[9];
    p.wu = (const bf16*)d_in[10];
    p.wd = (const bf16*)d_in[11];
    p.out = (bf16*)d_out;
    static PFN_tmEncode enc = nullptr;
    static void* scratch = nullptr;
    if (!enc) {
        cudaFuncSetAttribute(fused_kernel, cudaFuncAttributeMaxDynamicSharedMemorySize, SMEM_TOTAL);
        void* fn = nullptr;
        cudaDriverEntryPointQueryResult qr;
        cudaGetDriverEntryPoint("cuTensorMapEncodeTiled", &fn, cudaEnableDefault, &qr);
        enc = (PFN_tmEncode)fn;
        cudaGetSymbolAddress(&scratch, g_scratch);
    }
    p.s = (Scratch*)scratch;
    CUtensorMap tm_g, tm_u, tm_d, tm_x;
    const cuuint64_t dims[2] = {FF, DM}, strides[1] = {FF * 2};
    const cuuint32_t box[2] = {72, 48}, es[2] = {1, 1};
    enc(&tm_g, CU_TENSOR_MAP_DATA_TYPE_BFLOAT16, 2, d_in[9], dims, strides, box, es, CU_TENSOR_MAP_INTERLEAVE_NONE, CU_TENSOR_MAP_SWIZZLE_NONE,
        CU_TENSOR_MAP_L2_PROMOTION_NONE, CU_TENSOR_MAP_FLOAT_OOB_FILL_NONE);
    enc(&tm_u, CU_TENSOR_MAP_DATA_TYPE_BFLOAT16, 2, d_in[10], dims, strides, box, es, CU_TENSOR_MAP_INTERLEAVE_NONE, CU_TENSOR_MAP_SWIZZLE_NONE,
        CU_TENSOR_MAP_L2_PROMOTION_NONE, CU_TENSOR_MAP_FLOAT_OOB_FILL_NONE);
    const cuuint64_t ddims[2] = {DM / 2, FF}, dstrides[1] = {DM * 2};
    const cuuint32_t dbox[2] = {WD_PITCH / 4, 8};
    enc(&tm_d, CU_TENSOR_MAP_DATA_TYPE_UINT32, 2, d_in[11], ddims, dstrides, dbox, es, CU_TENSOR_MAP_INTERLEAVE_NONE, CU_TENSOR_MAP_SWIZZLE_NONE,
        CU_TENSOR_MAP_L2_PROMOTION_NONE, CU_TENSOR_MAP_FLOAT_OOB_FILL_NONE);
    const cuuint64_t xdims[4] = {DM, 128, 4, 4}, xstrides[3] = {DM * 8, DM * 2, DM * 1024};
    const cuuint32_t xbox[4] = {8, 128, 4, MC ? 2 : 4}, xes[4] = {1, 1, 1, 1};
    enc(&tm_x, CU_TENSOR_MAP_DATA_TYPE_BFLOAT16, 4, d_in[0], xdims, xstrides, xbox, xes, CU_TENSOR_MAP_INTERLEAVE_NONE, CU_TENSOR_MAP_SWIZZLE_NONE,
        CU_TENSOR_MAP_L2_PROMOTION_NONE, CU_TENSOR_MAP_FLOAT_OOB_FILL_NONE);
    fused_kernel<<<NCTA, NTHR, SMEM_TOTAL>>>(p, tm_g, tm_u, tm_d, tm_x);
}
```

```cpp
#include <cuda_runtime.h>
#include <cuda.h>
#include <cuda_fp16.h>
#include <cuda_bf16.h>
#include <stdint.h>

#define LSEQ 2048
#define DM 576
#define NST 128
#define FF 4608
#define NSEL 8
#define NCTA 128
#define NTHR 640
#define NWRK 640

typedef __nv_bfloat16 bf16;

#define SM_WG 0
#define SM_WU 41472
#define SM_XC (82944 - 32768)
#define SM_WD 82944
#define W_PITCH 144
#define WD_PITCH 592
#define SM_XT (SM_PL - 18 * 1152)
#define SM_PL (SM_WD + 46080)
#define PL_HALF 1344
#define PLW_B 2624
#define PL_B (4 * PLW_B)
#define SM_U (SM_PL + 5 * PL_B)
#define UPAD 20
#define ULO_B ((UPAD + 128) * 16)
#define USLOT_B (2 * ULO_B)
#define SM_ZERO (SM_U + 4 * USLOT_B + 128)
#define SM_KW (SM_U + 5 * USLOT_B)
#define KW_B 3712
#define KW_PL 1216
#define KW_P 2400
#define KW_H 3440
#define SM_MISC (SM_KW + 5 * KW_B)
#define SM_LC (SM_MISC + 384)
#define SM_LNP (SM_LC + 768)
#define SM_RX (SM_LNP + 3840)
#define SMEM_TOTAL (SM_RX + 3088)
#define YKEY 0xffc1ffc1u
#define TBP 112
#define TBW (32 * TBP)
#define SM_OUT SM_PL
#define SM_XS (SM_PL + 18432)
#define XS_PITCH 592
#define SM_GU (SM_PL + 23296)
#define SM_EX (SM_PL + 24576)
#define SM_KEYS SM_KW

struct __align__(128) Scratch {
    unsigned hint[8 * 32];
    unsigned flag[32];
    uint32_t key[NCTA * 8];
    uint32_t stat[LSEQ];
    uint32_t uT[64 * (LSEQ / 2)];
    uint32_t y[(NCTA + 96) * DM * 8];
    uint32_t part[288 * 64 * 16];
    uint32_t rows[(2 * NCTA + NSEL) * DM];
};
__device__ Scratch g_scratch;
#define STAMP(i)
#define STAMPX(i)
#define STAMPY(i)

__device__ __forceinline__ float rbf(float x) {
    uint32_t r;
    asm("cvt.rn.bf16x2.f32 %0, %1, %2;\n" : "=r"(r) : "f"(x), "f"(0.f));
    return __uint_as_float(r & 0xffff0000u);
}
__device__ __forceinline__ uint32_t pack_bf16(float lo, float hi) {
    uint32_t r;
    asm("cvt.rn.bf16x2.f32 %0, %1, %2;\n" : "=r"(r) : "f"(hi), "f"(lo));
    return r;
}
__device__ __forceinline__ uint32_t pack_f16(float lo, float hi) {
    uint32_t r;
    asm("cvt.rn.f16x2.f32 %0, %1, %2;\n" : "=r"(r) : "f"(hi), "f"(lo));
    return r;
}
__device__ __forceinline__ uint32_t pack_f16_rz(float lo, float hi) {
    uint32_t r;
    asm("cvt.rz.f16x2.f32 %0, %1, %2;\n" : "=r"(r) : "f"(hi), "f"(lo));
    return r;
}
__device__ __forceinline__ float bf_lo(uint32_t w) { return __uint_as_float(w << 16); }
__device__ __forceinline__ float bf_hi(uint32_t w) { return __uint_as_float(w & 0xffff0000u); }
__device__ __forceinline__ uint32_t hadd2_bf(uint32_t a, uint32_t b) {
    __nv_bfloat162 r = __hadd2_rn(*reinterpret_cast<__nv_bfloat162*>(&a), *reinterpret_cast<__nv_bfloat162*>(&b));
    return *reinterpret_cast<uint32_t*>(&r);
}
__device__ __forceinline__ uint32_t hsub2_bf(uint32_t a, uint32_t b) {
    __nv_bfloat162 r = __hsub2_rn(*reinterpret_cast<__nv_bfloat162*>(&a), *reinterpret_cast<__nv_bfloat162*>(&b));
    return *reinterpret_cast<uint32_t*>(&r);
}
__device__ __forceinline__ uint32_t hmul2_bf(uint32_t a, uint32_t b) {
    __nv_bfloat162 r = __hmul2_rn(*reinterpret_cast<__nv_bfloat162*>(&a), *reinterpret_cast<__nv_bfloat162*>(&b));
    return *reinterpret_cast<uint32_t*>(&r);
}
__device__ __forceinline__ uint32_t hfma2_bf(uint32_t a, uint32_t b, uint32_t c) { uint32_t r; asm("fma.rn.bf16x2 %0, %1, %2, %3;\n" : "=r"(r) : "r"(a), "r"(b), "r"(c)); return r; }
__device__ __forceinline__ uint32_t hmul2(uint32_t a, uint32_t b) { uint32_t r; asm("mul.rn.f16x2 %0, %1, %2;\n" : "=r"(r) : "r"(a), "r"(b)); return r; }
__device__ __forceinline__ uint32_t hadd2(uint32_t a, uint32_t b) { uint32_t r; asm("add.rn.f16x2 %0, %1, %2;\n" : "=r"(r) : "r"(a), "r"(b)); return r; }
__device__ __forceinline__ uint32_t hfma2(uint32_t a, uint32_t b, uint32_t c) { uint32_t r; asm("fma.rn.f16x2 %0, %1, %2, %3;\n" : "=r"(r) : "r"(a), "r"(b), "r"(c)); return r; }
__device__ __forceinline__ uint32_t hfms2(uint32_t a, uint32_t b, uint32_t c) {
    uint32_t r;
    asm("{\n.reg .b32 n;\nneg.f16x2 n, %2;\nfma.rn.f16x2 %0, %1, n, %3;\n}\n" : "=r"(r) : "r"(a), "r"(b), "r"(c));
    return r;
}
__device__ __forceinline__ uint32_t nzw(uint32_t w) { return w ? w : 0x8000u; }
__device__ __forceinline__ uint32_t nzf(float f) { const uint32_t w = __float_as_uint(f); return w ? w : 0x80000000u; }
__device__ __forceinline__ uint32_t smem_u32(const void* p) { return (uint32_t)__cvta_generic_to_shared(p); }
__device__ __forceinline__ uint32_t lds32(uint32_t addr) {
    uint32_t v;
    asm volatile("ld.shared.u32 %0, [%1];\n" : "=r"(v) : "r"(addr) : "memory");
    return v;
}
__device__ __forceinline__ uint32_t lds16(uint32_t addr) {
    unsigned short v;
    asm volatile("ld.shared.u16 %0, [%1];\n" : "=h"(v) : "r"(addr) : "memory");
    return v;
}
__device__ __forceinline__ uint2 lds64(uint32_t addr) {
    uint2 v;
    asm volatile("ld.shared.v2.u32 {%0,%1}, [%2];\n" : "=r"(v.x), "=r"(v.y) : "r"(addr) : "memory");
    return v;
}
__device__ __forceinline__ uint4 lds128(uint32_t addr) {
    uint4 v;
    asm volatile("ld.shared.v4.u32 {%0,%1,%2,%3}, [%4];\n" : "=r"(v.x), "=r"(v.y), "=r"(v.z), "=r"(v.w) : "r"(addr) : "memory");
    return v;
}
__device__ __forceinline__ float ldsf(uint32_t addr) { return __uint_as_float(lds32(addr)); }
__device__ __forceinline__ void sts32(uint32_t addr, uint32_t v) { asm volatile("st.shared.u32 [%0], %1;\n" ::"r"(addr), "r"(v) : "memory"); }
__device__ __forceinline__ void sts16(uint32_t addr, uint32_t v) { asm volatile("st.shared.u16 [%0], %1;\n" ::"r"(addr), "h"((unsigned short)v) : "memory"); }
__device__ __forceinline__ void stsf(uint32_t addr, float v) { sts32(addr, __float_as_uint(v)); }
__device__ __forceinline__ void sts64(uint32_t addr, uint32_t a, uint32_t b) { asm volatile("st.shared.v2.u32 [%0], {%1,%2};\n" ::"r"(addr), "r"(a), "r"(b) : "memory"); }
__device__ __forceinline__ void sts64f(uint32_t addr, float a, float b) { sts64(addr, __float_as_uint(a), __float_as_uint(b)); }
__device__ __forceinline__ void sts128(uint32_t addr, uint32_t a, uint32_t b, uint32_t c, uint32_t d) {
    asm volatile("st.shared.v4.u32 [%0], {%1,%2,%3,%4};\n" ::"r"(addr), "r"(a), "r"(b), "r"(c), "r"(d) : "memory");
}
__device__ __forceinline__ void sts128f(uint32_t addr, const float (&v)[4]) {
    sts128(addr, __float_as_uint(v[0]), __float_as_uint(v[1]), __float_as_uint(v[2]), __float_as_uint(v[3]));
}
__device__ __forceinline__ void ldsm_x4(uint32_t& r0, uint32_t& r1, uint32_t& r2, uint32_t& r3, uint32_t addr) {
    asm volatile("ldmatrix.sync.aligned.m8n8.x4.shared.b16 {%0,%1,%2,%3}, [%4];\n"
                 : "=r"(r0), "=r"(r1), "=r"(r2), "=r"(r3) : "r"(addr) : "memory");
}
__device__ __forceinline__ void ldsm_x4_t(uint32_t& r0, uint32_t& r1, uint32_t& r2, uint32_t& r3, uint32_t addr) {
    asm volatile("ldmatrix.sync.aligned.m8n8.x4.trans.shared.b16 {%0,%1,%2,%3}, [%4];\n"
                 : "=r"(r0), "=r"(r1), "=r"(r2), "=r"(r3) : "r"(addr) : "memory");
}
__device__ __forceinline__ void ldsm_x2_t(uint32_t& r0, uint32_t& r1, uint32_t addr) {
    asm volatile("ldmatrix.sync.aligned.m8n8.x2.trans.shared.b16 {%0,%1}, [%2];\n" : "=r"(r0), "=r"(r1) : "r"(addr) : "memory");
}
__device__ __forceinline__ void ldsm_x1_t(uint32_t& r0, uint32_t addr) {
    asm volatile("ldmatrix.sync.aligned.m8n8.x1.trans.shared.b16 {%0}, [%1];\n" : "=r"(r0) : "r"(addr) : "memory");
}
__device__ __forceinline__ void stsm_x4(uint32_t addr, uint32_t r0, uint32_t r1, uint32_t r2, uint32_t r3) {
    asm volatile("stmatrix.sync.aligned.m8n8.x4.shared.b16 [%0], {%1,%2,%3,%4};\n" ::"r"(addr), "r"(r0), "r"(r1), "r"(r2), "r"(r3) : "memory");
}
__device__ __forceinline__ void stsm_x4_t(uint32_t addr, uint32_t r0, uint32_t r1, uint32_t r2, uint32_t r3) {
    asm volatile("stmatrix.sync.aligned.m8n8.x4.trans.shared.b16 [%0], {%1,%2,%3,%4};\n" ::"r"(addr), "r"(r0), "r"(r1), "r"(r2), "r"(r3) : "memory");
}
__device__ __forceinline__ uint32_t movm(uint32_t a) {
    uint32_t d;
    asm volatile("movmatrix.sync.aligned.m8n8.trans.b16 %0, %1;\n" : "=r"(d) : "r"(a));
    return d;
}
__device__ __forceinline__ void mma_f16(float (&c)[4], uint32_t a0, uint32_t a1, uint32_t a2, uint32_t a3, uint32_t b0, uint32_t b1) {
    asm volatile(
        "mma.sync.aligned.m16n8k16.row.col.f32.f16.f16.f32 {%0,%1,%2,%3}, {%4,%5,%6,%7}, {%8,%9}, {%0,%1,%2,%3};\n"
        : "+f"(c[0]), "+f"(c[1]), "+f"(c[2]), "+f"(c[3])
        : "r"(a0), "r"(a1), "r"(a2), "r"(a3), "r"(b0), "r"(b1));
}
__device__ __forceinline__ void mma_bf16(float (&c)[4], uint32_t a0, uint32_t a1, uint32_t a2, uint32_t a3, uint32_t b0, uint32_t b1) {
    asm volatile(
        "mma.sync.aligned.m16n8k16.row.col.f32.bf16.bf16.f32 {%0,%1,%2,%3}, {%4,%5,%6,%7}, {%8,%9}, {%0,%1,%2,%3};\n"
        : "+f"(c[0]), "+f"(c[1]), "+f"(c[2]), "+f"(c[3])
        : "r"(a0), "r"(a1), "r"(a2), "r"(a3), "r"(b0), "r"(b1));
}
__device__ __forceinline__ void mma_bf16_k8(float (&c)[4], uint32_t a0, uint32_t a1, uint32_t b0) {
    asm volatile("mma.sync.aligned.m16n8k8.row.col.f32.bf16.bf16.f32 {%0,%1,%2,%3}, {%4,%5}, {%6}, {%0,%1,%2,%3};\n"
                 : "+f"(c[0]), "+f"(c[1]), "+f"(c[2]), "+f"(c[3]) : "r"(a0), "r"(a1), "r"(b0));
}
__device__ __forceinline__ void bar_sync(int id, int n) { asm volatile("bar.sync %0, %1;\n" ::"r"(id), "r"(n) : "memory"); }
__device__ __forceinline__ void bar_arrive(int id, int n) { asm volatile("bar.arrive %0, %1;\n" ::"r"(id), "r"(n) : "memory"); }
__device__ __forceinline__ uint4 ld_poll(const void* p) {
    uint4 v;
    asm volatile("ld.relaxed.gpu.global.v4.u32 {%0,%1,%2,%3}, [%4];\n" : "=r"(v.x), "=r"(v.y), "=r"(v.z), "=r"(v.w) : "l"(p) : "memory");
    return v;
}
__device__ __forceinline__ uint2 ld_poll64(const void* p) {
    uint2 v;
    asm volatile("ld.relaxed.gpu.global.v2.u32 {%0,%1}, [%2];\n" : "=r"(v.x), "=r"(v.y) : "l"(p) : "memory");
    return v;
}
__device__ __forceinline__ uint32_t ld_poll32(const void* p) {
    uint32_t v;
    asm volatile("ld.relaxed.gpu.global.u32 %0, [%1];\n" : "=r"(v) : "l"(p) : "memory");
    return v;
}
__device__ __forceinline__ uint4 ldg128(const void* p) {
    uint4 v;
    asm volatile("ld.global.nc.v4.u32 {%0,%1,%2,%3}, [%4];\n" : "=r"(v.x), "=r"(v.y), "=r"(v.z), "=r"(v.w) : "l"(p));
    return v;
}
__device__ __forceinline__ uint2 ldg64(const void* p) {
    uint2 v;
    asm volatile("ld.global.nc.v2.u32 {%0,%1}, [%2];\n" : "=r"(v.x), "=r"(v.y) : "l"(p));
    return v;
}
__device__ __forceinline__ uint32_t ldg16(const void* p) {
    uint32_t v;
    asm volatile("ld.global.nc.u16 %0, [%1];\n" : "=r"(v) : "l"(p));
    return v;
}
__device__ __forceinline__ uint4 ldo128(const void* p) {
    uint4 v;
    asm volatile("ld.relaxed.cta.global.v4.u32 {%0,%1,%2,%3}, [%4];\n" : "=r"(v.x), "=r"(v.y), "=r"(v.z), "=r"(v.w) : "l"(p) : "memory");
    return v;
}
__device__ __forceinline__ uint2 ldo64(const void* p) {
    uint2 v;
    asm volatile("ld.relaxed.cta.global.v2.u32 {%0,%1}, [%2];\n" : "=r"(v.x), "=r"(v.y) : "l"(p) : "memory");
    return v;
}
__device__ __forceinline__ uint32_t ldo16(const void* p) {
    uint32_t v;
    asm volatile("ld.relaxed.cta.global.u16 %0, [%1];\n" : "=r"(v) : "l"(p) : "memory");
    return v;
}
__device__ __forceinline__ void stg128(void* p, uint32_t a, uint32_t b, uint32_t c, uint32_t d) {
    asm volatile("st.global.v4.u32 [%0], {%1,%2,%3,%4};\n" ::"l"(p), "r"(a), "r"(b), "r"(c), "r"(d) : "memory");
}
__device__ __forceinline__ void stg64(void* p, uint32_t a, uint32_t b) { asm volatile("st.global.v2.u32 [%0], {%1,%2};\n" ::"l"(p), "r"(a), "r"(b) : "memory"); }
__device__ __forceinline__ uint32_t min4(const uint4& v) { return min(min(v.x, v.y), min(v.z, v.w)); }
#define SPIN_LIMIT (1 << 21)
#define TRAP() __trap()
__device__ __forceinline__ void mbar_init(uint32_t bar, uint32_t cnt) { asm volatile("mbarrier.init.shared::cta.b64 [%0], %1;\n" ::"r"(bar), "r"(cnt) : "memory"); }
__device__ __forceinline__ void mbar_expect(uint32_t bar, uint32_t bytes) {
    asm volatile("mbarrier.arrive.expect_tx.shared::cta.b64 _, [%0], %1;\n" ::"r"(bar), "r"(bytes) : "memory");
}
__device__ __forceinline__ void mbar_arrive(uint32_t bar) { asm volatile("mbarrier.arrive.shared::cta.b64 _, [%0];\n" ::"r"(bar) : "memory"); }
__device__ __forceinline__ void mbar_wait_cluster(uint32_t bar) {
    asm volatile(
        "{\n.reg .pred p;\n"
        "W_%=:\n"
        "mbarrier.try_wait.parity.acquire.cluster.shared::cta.b64 p, [%0], 0;\n"
        "@!p bra W_%=;\n}\n" ::"r"(bar) : "memory");
}
__device__ __forceinline__ void mbar_wait(uint32_t bar) {
    asm volatile(
        "{\n.reg .pred p;\n"
        "W_%=:\n"
        "mbarrier.try_wait.parity.shared::cta.b64 p, [%0], 0;\n"
        "@!p bra W_%=;\n}\n" ::"r"(bar) : "memory");
}
__device__ __forceinline__ bool mbar_test(uint32_t bar) {
    uint32_t r;
    asm volatile("{\n.reg .pred p;\nmbarrier.test_wait.parity.shared::cta.b64 p, [%1], 0;\nselp.u32 %0, 1, 0, p;\n}\n" : "=r"(r) : "r"(bar) : "memory");
    return __any_sync(0xffffffffu, r);
}
__device__ __forceinline__ void bulk_g2s(uint32_t dst, const void* src, uint32_t bytes, uint32_t bar) {
    asm volatile("cp.async.bulk.shared::cluster.global.mbarrier::complete_tx::bytes [%0], [%1], %2, [%3];\n" ::"r"(dst), "l"(src), "r"(bytes), "r"(bar) : "memory");
}
__device__ __forceinline__ void bulk_s2g(void* dst, uint32_t src, uint32_t bytes) {
    asm volatile("cp.async.bulk.global.shared::cta.bulk_group [%0], [%1], %2;\ncp.async.bulk.commit_group;\n" ::"l"(dst), "r"(src), "r"(bytes) : "memory");
}
__device__ __forceinline__ void tma_2d(uint32_t dst, const CUtensorMap* tm, int c0, int c1, uint32_t bar) {
    asm volatile("cp.async.bulk.tensor.2d.shared::cluster.global.mbarrier::complete_tx::bytes [%0], [%1, {%3, %4}], [%2];\n"
                 ::"r"(dst), "l"(tm), "r"(bar), "r"(c0), "r"(c1) : "memory");
}
__device__ __forceinline__ void tma_4d(uint32_t dst, const CUtensorMap* tm, int c0, int c3, uint32_t bar) {
    asm volatile("cp.async.bulk.tensor.4d.shared::cluster.global.mbarrier::complete_tx::bytes [%0], [%1, {%3, %4, %4, %5}], [%2];\n"
                 ::"r"(dst), "l"(tm), "r"(bar), "r"(c0), "r"(0), "r"(c3) : "memory");
}
__device__ __forceinline__ void tma_4d_mc(uint32_t dst, const CUtensorMap* tm, int c0, int c3, uint32_t bar) {
    asm volatile("cp.async.bulk.tensor.4d.shared::cluster.global.mbarrier::complete_tx::bytes.multicast::cluster [%0], [%1, {%3, %4, %4, %5}], [%2], %6;\n"
                 ::"r"(dst), "l"(tm), "r"(bar), "r"(c0), "r"(0), "r"(c3), "h"((unsigned short)3) : "memory");
}
__device__ __forceinline__ void l2_prefetch(const void* src, uint32_t bytes) {
    asm volatile("cp.async.bulk.prefetch.L2.global [%0], %1;\n" ::"l"(src), "r"(bytes) : "memory");
}
__device__ __forceinline__ bool elect_one() {
    uint32_t r;
    asm volatile("{\n.reg .pred p;\nelect.sync _|p, 0xffffffff;\nselp.u32 %0, 1, 0, p;\n}\n" : "=r"(r));
    return r;
}
__device__ __forceinline__ void delay(uint32_t clks) {
    uint32_t t0, t1;
    asm volatile("mov.u32 %0, %%clock;" : "=r"(t0) :: "memory");
    do { asm volatile("mov.u32 %0, %%clock;" : "=r"(t1) :: "memory"); } while (t1 - t0 < clks);
}
__device__ __forceinline__ void fence_async() { asm volatile("fence.proxy.async.shared::cta;\n" ::: "memory"); }

__device__ __forceinline__ float2 cmul(float2 a, float2 b) {
    return make_float2(fmaf(a.x, b.x, -a.y * b.y), fmaf(a.x, b.y, a.y * b.x));
}
__device__ __forceinline__ float2 csq(float2 a) {
    float p = a.x * a.y;
    return make_float2(fmaf(a.x, a.x, -a.y * a.y), p + p);
}
__device__ __forceinline__ float ex2_approx(float x) { float r; asm("ex2.approx.ftz.f32 %0, %1;\n" : "=f"(r) : "f"(x)); return r; }
__device__ __forceinline__ float exp_bf(float x) { return rbf(ex2_approx(__fmul_ru(x, 1.4426950408889634f))); }
__device__ __forceinline__ float2 cexp_e(float lr2, float li, float e) {
    const float m = ex2_approx(lr2 * e);
    return make_float2(m * __cosf(li * e), m * __sinf(li * e));
}
__device__ __forceinline__ float rcp_approx(float x) { float r; asm("rcp.approx.ftz.f32 %0, %1;\n" : "=f"(r) : "f"(x)); return r; }
__device__ __forceinline__ float sqrt_approx(float x) { float r; asm("sqrt.approx.ftz.f32 %0, %1;\n" : "=f"(r) : "f"(x)); return r; }

__device__ __forceinline__ void wg_fence() { asm volatile("wgmma.fence.sync.aligned;\n" ::: "memory"); }
__device__ __forceinline__ void wg_commit() { asm volatile("wgmma.commit_group.sync.aligned;\n" ::: "memory"); }
__device__ __forceinline__ void wg_wait0() { asm volatile("wgmma.wait_group.sync.aligned 0;\n" ::: "memory"); }
template <int T> __device__ __forceinline__ void wg_mma(float (&acc)[16][4], const uint32_t* a, uint64_t desc);
template <int T> __device__ __forceinline__ void wg_first(float (&acc)[16][4], const uint32_t* a, uint64_t desc);
template <> __device__ __forceinline__ void wg_mma<0>(float (&acc)[16][4], const uint32_t* a, uint64_t desc) {
    asm volatile("wgmma.mma_async.sync.aligned.m64n128k16.f32.f16.f16 {%0,%1,%2,%3,%4,%5,%6,%7,%8,%9,%10,%11,%12,%13,%14,%15,%16,%17,%18,%19,%20,%21,%22,%23,%24,%25,%26,%27,%28,%29,%30,%31,%32,%33,%34,%35,%36,%37,%38,%39,%40,%41,%42,%43,%44,%45,%46,%47,%48,%49,%50,%51,%52,%53,%54,%55,%56,%57,%58,%59,%60,%61,%62,%63}, {%64,%65,%66,%67}, %68, 1, 1, 1, 0;\n"
                 : "+f"(acc[0][0]), "+f"(acc[0][1]), "+f"(acc[0][2]), "+f"(acc[0][3]), "+f"(acc[1][0]), "+f"(acc[1][1]), "+f"(acc[1][2]), "+f"(acc[1][3]), "+f"(acc[2][0]), "+f"(acc[2][1]), "+f"(acc[2][2]), "+f"(acc[2][3]), "+f"(acc[3][0]), "+f"(acc[3][1]), "+f"(acc[3][2]), "+f"(acc[3][3]), "+f"(acc[4][0]), "+f"(acc[4][1]), "+f"(acc[4][2]), "+f"(acc[4][3]), "+f"(acc[5][0]), "+f"(acc[5][1]), "+f"(acc[5][2]), "+f"(acc[5][3]), "+f"(acc[6][0]), "+f"(acc[6][1]), "+f"(acc[6][2]), "+f"(acc[6][3]), "+f"(acc[7][0]), "+f"(acc[7][1]), "+f"(acc[7][2]), "+f"(acc[7][3]), "+f"(acc[8][0]), "+f"(acc[8][1]), "+f"(acc[8][2]), "+f"(acc[8][3]), "+f"(acc[9][0]), "+f"(acc[9][1]), "+f"(acc[9][2]), "+f"(acc[9][3]), "+f"(acc[10][0]), "+f"(acc[10][1]), "+f"(acc[10][2]), "+f"(acc[10][3]), "+f"(acc[11][0]), "+f"(acc[11][1]), "+f"(acc[11][2]), "+f"(acc[11][3]), "+f"(acc[12][0]), "+f"(acc[12][1]), "+f"(acc[12][2]), "+f"(acc[12][3]), "+f"(acc[13][0]), "+f"(acc[13][1]), "+f"(acc[13][2]), "+f"(acc[13][3]), "+f"(acc[14][0]), "+f"(acc[14][1]), "+f"(acc[14][2]), "+f"(acc[14][3]), "+f"(acc[15][0]), "+f"(acc[15][1]), "+f"(acc[15][2]), "+f"(acc[15][3])
                 : "r"(a[0]), "r"(a[1]), "r"(a[2]), "r"(a[3]), "l"(desc));
}
template <> __device__ __forceinline__ void wg_mma<2>(float (&acc)[16][4], const uint32_t* a, uint64_t desc) {
    asm volatile("wgmma.mma_async.sync.aligned.m64n112k16.f32.f16.f16 {%0,%1,%2,%3,%4,%5,%6,%7,%8,%9,%10,%11,%12,%13,%14,%15,%16,%17,%18,%19,%20,%21,%22,%23,%24,%25,%26,%27,%28,%29,%30,%31,%32,%33,%34,%35,%36,%37,%38,%39,%40,%41,%42,%43,%44,%45,%46,%47,%48,%49,%50,%51,%52,%53,%54,%55}, {%56,%57,%58,%59}, %60, 1, 1, 1, 0;\n"
                 : "+f"(acc[2][0]), "+f"(acc[2][1]), "+f"(acc[2][2]), "+f"(acc[2][3]), "+f"(acc[3][0]), "+f"(acc[3][1]), "+f"(acc[3][2]), "+f"(acc[3][3]), "+f"(acc[4][0]), "+f"(acc[4][1]), "+f"(acc[4][2]), "+f"(acc[4][3]), "+f"(acc[5][0]), "+f"(acc[5][1]), "+f"(acc[5][2]), "+f"(acc[5][3]), "+f"(acc[6][0]), "+f"(acc[6][1]), "+f"(acc[6][2]), "+f"(acc[6][3]), "+f"(acc[7][0]), "+f"(acc[7][1]), "+f"(acc[7][2]), "+f"(acc[7][3]), "+f"(acc[8][0]), "+f"(acc[8][1]), "+f"(acc[8][2]), "+f"(acc[8][3]), "+f"(acc[9][0]), "+f"(acc[9][1]), "+f"(acc[9][2]), "+f"(acc[9][3]), "+f"(acc[10][0]), "+f"(acc[10][1]), "+f"(acc[10][2]), "+f"(acc[10][3]), "+f"(acc[11][0]), "+f"(acc[11][1]), "+f"(acc[11][2]), "+f"(acc[11][3]), "+f"(acc[12][0]), "+f"(acc[12][1]), "+f"(acc[12][2]), "+f"(acc[12][3]), "+f"(acc[13][0]), "+f"(acc[13][1]), "+f"(acc[13][2]), "+f"(acc[13][3]), "+f"(acc[14][0]), "+f"(acc[14][1]), "+f"(acc[14][2]), "+f"(acc[14][3]), "+f"(acc[15][0]), "+f"(acc[15][1]), "+f"(acc[15][2]), "+f"(acc[15][3])
                 : "r"(a[0]), "r"(a[1]), "r"(a[2]), "r"(a[3]), "l"(desc));
}
template <> __device__ __forceinline__ void wg_mma<4>(float (&acc)[16][4], const uint32_t* a, uint64_t desc) {
    asm volatile("wgmma.mma_async.sync.aligned.m64n96k16.f32.f16.f16 {%0,%1,%2,%3,%4,%5,%6,%7,%8,%9,%10,%11,%12,%13,%14,%15,%16,%17,%18,%19,%20,%21,%22,%23,%24,%25,%26,%27,%28,%29,%30,%31,%32,%33,%34,%35,%36,%37,%38,%39,%40,%41,%42,%43,%44,%45,%46,%47}, {%48,%49,%50,%51}, %52, 1, 1, 1, 0;\n"
                 : "+f"(acc[4][0]), "+f"(acc[4][1]), "+f"(acc[4][2]), "+f"(acc[4][3]), "+f"(acc[5][0]), "+f"(acc[5][1]), "+f"(acc[5][2]), "+f"(acc[5][3]), "+f"(acc[6][0]), "+f"(acc[6][1]), "+f"(acc[6][2]), "+f"(acc[6][3]), "+f"(acc[7][0]), "+f"(acc[7][1]), "+f"(acc[7][2]), "+f"(acc[7][3]), "+f"(acc[8][0]), "+f"(acc[8][1]), "+f"(acc[8][2]), "+f"(acc[8][3]), "+f"(acc[9][0]), "+f"(acc[9][1]), "+f"(acc[9][2]), "+f"(acc[9][3]), "+f"(acc[10][0]), "+f"(acc[10][1]), "+f"(acc[10][2]), "+f"(acc[10][3]), "+f"(acc[11][0]), "+f"(acc[11][1]), "+f"(acc[11][2]), "+f"(acc[11][3]), "+f"(acc[12][0]), "+f"(acc[12][1]), "+f"(acc[12][2]), "+f"(acc[12][3]), "+f"(acc[13][0]), "+f"(acc[13][1]), "+f"(acc[13][2]), "+f"(acc[13][3]), "+f"(acc[14][0]), "+f"(acc[14][1]), "+f"(acc[14][2]), "+f"(acc[14][3]), "+f"(acc[15][0]), "+f"(acc[15][1]), "+f"(acc[15][2]), "+f"(acc[15][3])
                 : "r"(a[0]), "r"(a[1]), "r"(a[2]), "r"(a[3]), "l"(desc));
}
template <> __device__ __forceinline__ void wg_mma<6>(float (&acc)[16][4], const uint32_t* a, uint64_t desc) {
    asm volatile("wgmma.mma_async.sync.aligned.m64n80k16.f32.f16.f16 {%0,%1,%2,%3,%4,%5,%6,%7,%8,%9,%10,%11,%12,%13,%14,%15,%16,%17,%18,%19,%20,%21,%22,%23,%24,%25,%26,%27,%28,%29,%30,%31,%32,%33,%34,%35,%36,%37,%38,%39}, {%40,%41,%42,%43}, %44, 1, 1, 1, 0;\n"
                 : "+f"(acc[6][0]), "+f"(acc[6][1]), "+f"(acc[6][2]), "+f"(acc[6][3]), "+f"(acc[7][0]), "+f"(acc[7][1]), "+f"(acc[7][2]), "+f"(acc[7][3]), "+f"(acc[8][0]), "+f"(acc[8][1]), "+f"(acc[8][2]), "+f"(acc[8][3]), "+f"(acc[9][0]), "+f"(acc[9][1]), "+f"(acc[9][2]), "+f"(acc[9][3]), "+f"(acc[10][0]), "+f"(acc[10][1]), "+f"(acc[10][2]), "+f"(acc[10][3]), "+f"(acc[11][0]), "+f"(acc[11][1]), "+f"(acc[11][2]), "+f"(acc[11][3]), "+f"(acc[12][0]), "+f"(acc[12][1]), "+f"(acc[12][2]), "+f"(acc[12][3]), "+f"(acc[13][0]), "+f"(acc[13][1]), "+f"(acc[13][2]), "+f"(acc[13][3]), "+f"(acc[14][0]), "+f"(acc[14][1]), "+f"(acc[14][2]), "+f"(acc[14][3]), "+f"(acc[15][0]), "+f"(acc[15][1]), "+f"(acc[15][2]), "+f"(acc[15][3])
                 : "r"(a[0]), "r"(a[1]), "r"(a[2]), "r"(a[3]), "l"(desc));
}
template <> __device__ __forceinline__ void wg_mma<8>(float (&acc)[16][4], const uint32_t* a, uint64_t desc) {
    asm volatile("wgmma.mma_async.sync.aligned.m64n64k16.f32.f16.f16 {%0,%1,%2,%3,%4,%5,%6,%7,%8,%9,%10,%11,%12,%13,%14,%15,%16,%17,%18,%19,%20,%21,%22,%23,%24,%25,%26,%27,%28,%29,%30,%31}, {%32,%33,%34,%35}, %36, 1, 1, 1, 0;\n"
                 : "+f"(acc[8][0]), "+f"(acc[8][1]), "+f"(acc[8][2]), "+f"(acc[8][3]), "+f"(acc[9][0]), "+f"(acc[9][1]), "+f"(acc[9][2]), "+f"(acc[9][3]), "+f"(acc[10][0]), "+f"(acc[10][1]), "+f"(acc[10][2]), "+f"(acc[10][3]), "+f"(acc[11][0]), "+f"(acc[11][1]), "+f"(acc[11][2]), "+f"(acc[11][3]), "+f"(acc[12][0]), "+f"(acc[12][1]), "+f"(acc[12][2]), "+f"(acc[12][3]), "+f"(acc[13][0]), "+f"(acc[13][1]), "+f"(acc[13][2]), "+f"(acc[13][3]), "+f"(acc[14][0]), "+f"(acc[14][1]), "+f"(acc[14][2]), "+f"(acc[14][3]), "+f"(acc[15][0]), "+f"(acc[15][1]), "+f"(acc[15][2]), "+f"(acc[15][3])
                 : "r"(a[0]), "r"(a[1]), "r"(a[2]), "r"(a[3]), "l"(desc));
}
template <> __device__ __forceinline__ void wg_mma<10>(float (&acc)[16][4], const uint32_t* a, uint64_t desc) {
    asm volatile("wgmma.mma_async.sync.aligned.m64n48k16.f32.f16.f16 {%0,%1,%2,%3,%4,%5,%6,%7,%8,%9,%10,%11,%12,%13,%14,%15,%16,%17,%18,%19,%20,%21,%22,%23}, {%24,%25,%26,%27}, %28, 1, 1, 1, 0;\n"
                 : "+f"(acc[10][0]), "+f"(acc[10][1]), "+f"(acc[10][2]), "+f"(acc[10][3]), "+f"(acc[11][0]), "+f"(acc[11][1]), "+f"(acc[11][2]), "+f"(acc[11][3]), "+f"(acc[12][0]), "+f"(acc[12][1]), "+f"(acc[12][2]), "+f"(acc[12][3]), "+f"(acc[13][0]), "+f"(acc[13][1]), "+f"(acc[13][2]), "+f"(acc[13][3]), "+f"(acc[14][0]), "+f"(acc[14][1]), "+f"(acc[14][2]), "+f"(acc[14][3]), "+f"(acc[15][0]), "+f"(acc[15][1]), "+f"(acc[15][2]), "+f"(acc[15][3])
                 : "r"(a[0]), "r"(a[1]), "r"(a[2]), "r"(a[3]), "l"(desc));
}
template <> __device__ __forceinline__ void wg_mma<12>(float (&acc)[16][4], const uint32_t* a, uint64_t desc) {
    asm volatile("wgmma.mma_async.sync.aligned.m64n32k16.f32.f16.f16 {%0,%1,%2,%3,%4,%5,%6,%7,%8,%9,%10,%11,%12,%13,%14,%15}, {%16,%17,%18,%19}, %20, 1, 1, 1, 0;\n"
                 : "+f"(acc[12][0]), "+f"(acc[12][1]), "+f"(acc[12][2]), "+f"(acc[12][3]), "+f"(acc[13][0]), "+f"(acc[13][1]), "+f"(acc[13][2]), "+f"(acc[13][3]), "+f"(acc[14][0]), "+f"(acc[14][1]), "+f"(acc[14][2]), "+f"(acc[14][3]), "+f"(acc[15][0]), "+f"(acc[15][1]), "+f"(acc[15][2]), "+f"(acc[15][3])
                 : "r"(a[0]), "r"(a[1]), "r"(a[2]), "r"(a[3]), "l"(desc));
}
template <> __device__ __forceinline__ void wg_mma<14>(float (&acc)[16][4], const uint32_t* a, uint64_t desc) {
    asm volatile("wgmma.mma_async.sync.aligned.m64n16k16.f32.f16.f16 {%0,%1,%2,%3,%4,%5,%6,%7}, {%8,%9,%10,%11}, %12, 1, 1, 1, 0;\n"
                 : "+f"(acc[14][0]), "+f"(acc[14][1]), "+f"(acc[14][2]), "+f"(acc[14][3]), "+f"(acc[15][0]), "+f"(acc[15][1]), "+f"(acc[15][2]), "+f"(acc[15][3])
                 : "r"(a[0]), "r"(a[1]), "r"(a[2]), "r"(a[3]), "l"(desc));
}
template <> __device__ __forceinline__ void wg_first<0>(float (&acc)[16][4], const uint32_t* a, uint64_t desc) {
    asm volatile("wgmma.mma_async.sync.aligned.m64n128k16.f32.f16.f16 {%0,%1,%2,%3,%4,%5,%6,%7,%8,%9,%10,%11,%12,%13,%14,%15,%16,%17,%18,%19,%20,%21,%22,%23,%24,%25,%26,%27,%28,%29,%30,%31,%32,%33,%34,%35,%36,%37,%38,%39,%40,%41,%42,%43,%44,%45,%46,%47,%48,%49,%50,%51,%52,%53,%54,%55,%56,%57,%58,%59,%60,%61,%62,%63}, {%64,%65,%66,%67}, %68, 0, 1, 1, 0;\n"
                 : "=f"(acc[0][0]), "=f"(acc[0][1]), "=f"(acc[0][2]), "=f"(acc[0][3]), "=f"(acc[1][0]), "=f"(acc[1][1]), "=f"(acc[1][2]), "=f"(acc[1][3]), "=f"(acc[2][0]), "=f"(acc[2][1]), "=f"(acc[2][2]), "=f"(acc[2][3]), "=f"(acc[3][0]), "=f"(acc[3][1]), "=f"(acc[3][2]), "=f"(acc[3][3]), "=f"(acc[4][0]), "=f"(acc[4][1]), "=f"(acc[4][2]), "=f"(acc[4][3]), "=f"(acc[5][0]), "=f"(acc[5][1]), "=f"(acc[5][2]), "=f"(acc[5][3]), "=f"(acc[6][0]), "=f"(acc[6][1]), "=f"(acc[6][2]), "=f"(acc[6][3]), "=f"(acc[7][0]), "=f"(acc[7][1]), "=f"(acc[7][2]), "=f"(acc[7][3]), "=f"(acc[8][0]), "=f"(acc[8][1]), "=f"(acc[8][2]), "=f"(acc[8][3]), "=f"(acc[9][0]), "=f"(acc[9][1]), "=f"(acc[9][2]), "=f"(acc[9][3]), "=f"(acc[10][0]), "=f"(acc[10][1]), "=f"(acc[10][2]), "=f"(acc[10][3]), "=f"(acc[11][0]), "=f"(acc[11][1]), "=f"(acc[11][2]), "=f"(acc[11][3]), "=f"(acc[12][0]), "=f"(acc[12][1]), "=f"(acc[12][2]), "=f"(acc[12][3]), "=f"(acc[13][0]), "=f"(acc[13][1]), "=f"(acc[13][2]), "=f"(acc[13][3]), "=f"(acc[14][0]), "=f"(acc[14][1]), "=f"(acc[14][2]), "=f"(acc[14][3]), "=f"(acc[15][0]), "=f"(acc[15][1]), "=f"(acc[15][2]), "=f"(acc[15][3])
                 : "r"(a[0]), "r"(a[1]), "r"(a[2]), "r"(a[3]), "l"(desc));
}
template <> __device__ __forceinline__ void wg_first<4>(float (&acc)[16][4], const uint32_t* a, uint64_t desc) {
    asm volatile("wgmma.mma_async.sync.aligned.m64n96k16.f32.f16.f16 {%0,%1,%2,%3,%4,%5,%6,%7,%8,%9,%10,%11,%12,%13,%14,%15,%16,%17,%18,%19,%20,%21,%22,%23,%24,%25,%26,%27,%28,%29,%30,%31,%32,%33,%34,%35,%36,%37,%38,%39,%40,%41,%42,%43,%44,%45,%46,%47}, {%48,%49,%50,%51}, %52, 0, 1, 1, 0;\n"
                 : "=f"(acc[4][0]), "=f"(acc[4][1]), "=f"(acc[4][2]), "=f"(acc[4][3]), "=f"(acc[5][0]), "=f"(acc[5][1]), "=f"(acc[5][2]), "=f"(acc[5][3]), "=f"(acc[6][0]), "=f"(acc[6][1]), "=f"(acc[6][2]), "=f"(acc[6][3]), "=f"(acc[7][0]), "=f"(acc[7][1]), "=f"(acc[7][2]), "=f"(acc[7][3]), "=f"(acc[8][0]), "=f"(acc[8][1]), "=f"(acc[8][2]), "=f"(acc[8][3]), "=f"(acc[9][0]), "=f"(acc[9][1]), "=f"(acc[9][2]), "=f"(acc[9][3]), "=f"(acc[10][0]), "=f"(acc[10][1]), "=f"(acc[10][2]), "=f"(acc[10][3]), "=f"(acc[11][0]), "=f"(acc[11][1]), "=f"(acc[11][2]), "=f"(acc[11][3]), "=f"(acc[12][0]), "=f"(acc[12][1]), "=f"(acc[12][2]), "=f"(acc[12][3]), "=f"(acc[13][0]), "=f"(acc[13][1]), "=f"(acc[13][2]), "=f"(acc[13][3]), "=f"(acc[14][0]), "=f"(acc[14][1]), "=f"(acc[14][2]), "=f"(acc[14][3]), "=f"(acc[15][0]), "=f"(acc[15][1]), "=f"(acc[15][2]), "=f"(acc[15][3])
                 : "r"(a[0]), "r"(a[1]), "r"(a[2]), "r"(a[3]), "l"(desc));
}

#define EARLYN 2
#define K8 0
#define HOLD 1
#define MC 1
#define STAMPW(i) STAMPY(i)
#define STAMP2(i) STAMP(i)
#undef STAMPX
#define STAMPX(i)
#define PBAR 1
#define WDLY 500
#define CBAR 1
#define FDLY 800
#define YDLY 1
#define YFROM 0
#define YPRE 0
#define KDLY 700
#define OEARLY 0
#define EXP 0
#define XWHEN 0
#define RWHEN 0
#define HW 11
#define PEARLY 0
#define XG 6
struct Params {
    const bf16 *x, *lar, *aim, *cre, *cim, *ldt, *dsk;
    Scratch* s;
    const bf16 *wr, *wg, *wu, *wd;
    bf16* out;
};

#define TOK(g) (2 * (g) - ((g) & 1))
#define ROWTOK(r) (TOK((r) & 7) + (((r) >> 2) & 2))
__device__ __forceinline__ void ln_partial(const uint32_t (&H)[2][4], uint32_t lp, int warp, int g, int t) {
    float cs[4] = {0.f, 0.f, 0.f, 0.f}, cl[4] = {0.f, 0.f, 0.f, 0.f}, ch[4] = {0.f, 0.f, 0.f, 0.f};
#pragma unroll
    for (int k = 0; k < 4; k += 2) {
        mma_bf16(cs, H[0][k], H[1][k], H[0][k + 1], H[1][k + 1], 0x3f803f80u, 0x3f803f80u);
        mma_bf16(cl, H[0][k], H[1][k], H[0][k + 1], H[1][k + 1], H[0][k], H[0][k + 1]);
        mma_bf16(ch, H[0][k], H[1][k], H[0][k + 1], H[1][k + 1], H[1][k], H[1][k + 1]);
    }
    const uint32_t a = lp + (g * 20 + warp) * 4;
    if (t == (g >> 1)) { stsf(a, cs[0]); stsf(a + 8 * 80, cs[2]); stsf(a + 16 * 80, (g & 1) ? cl[1] : cl[0]); stsf(a + 24 * 80, (g & 1) ? ch[3] : ch[2]); }
}
__device__ __forceinline__ float sum18(uint32_t a) {
    const uint4 p = lds128(a), q = lds128(a + 16), r = lds128(a + 32), s = lds128(a + 48);
    const uint2 u = lds64(a + 64);
#define F(x) __uint_as_float(x)
    return (((F(p.x) + F(p.y)) + (F(p.z) + F(p.w))) + ((F(q.x) + F(q.y)) + (F(q.z) + F(q.w)))) +
           (((F(r.x) + F(r.y)) + (F(r.z) + F(r.w))) + ((F(s.x) + F(s.y)) + (F(s.z) + F(s.w))) + (F(u.x) + F(u.y)));
#undef F
}
__device__ __forceinline__ void ln_stats(float sm, float sq, float& mb, float& sd) {
    const float m0 = sm * (1.0f / 576.0f);
    const float mean = fmaf(fmaf(-m0, 576.0f, sm), 1.0f / 576.0f, m0);
    const float var = fmaxf(fmaf(-mean, mean, sq * (1.0f / 576.0f)), 0.f);
    mb = rbf(mean);
    sd = rbf(sqrt_approx(rbf(rbf(var) + 1e-5f)));
}
__device__ __forceinline__ void ln_finish(float v, int lane, float& mb, float& rc) {
    const float o = __shfl_xor_sync(0xffffffffu, v, 16);
    float sd;
    ln_stats(lane < 16 ? v : o, lane < 16 ? o : v, mb, sd);
    rc = rcp_approx(sd);
}
__device__ __forceinline__ uint32_t ln_apply(uint32_t w, uint32_t m2, uint32_t rh, uint32_t rl) {
    const uint32_t d = hsub2_bf(w, m2);
    return hfma2_bf(d, rh, hmul2_bf(d, rl));
}
__device__ __forceinline__ void stat_store(uint32_t a, float mb, float rc, uint32_t extra) {
    const float rh = rbf(rc);
    sts64(a, (__float_as_uint(mb) >> 16) | (extra << 16), pack_bf16(rh, rc - rh));
}
#define STAT_M(s) __byte_perm((s).x, (s).x, 0x1010)
#define STAT_H(s) __byte_perm((s).y, (s).y, 0x1010)
#define STAT_L(s) __byte_perm((s).y, (s).y, 0x3232)

__device__ __forceinline__ void hcmul(uint32_t re, uint32_t im, uint32_t zx, uint32_t zy, uint32_t& ore, uint32_t& oim) {
    ore = hfms2(im, zy, hmul2(re, zx));
    oim = hfma2(re, zy, hmul2(im, zx));
}

struct KGen {
    uint32_t A[2][4][4];
    float2 z1, z8, z64, z128, T[9];
};
__device__ __forceinline__ void kgen_setup(KGen& k, float lar, float aim, float dt) {
    const float lr2 = -(exp_bf(lar) * dt) * 1.4426950408889634f, li = aim * dt;
    k.z1 = cexp_e(lr2, li, 1.0f);
    k.z8 = cexp_e(lr2, li, 8.0f);
    k.z64 = cexp_e(lr2, li, 64.0f);
}
__device__ __forceinline__ void kgen_rows(KGen& k, uint32_t tb, int lane) {
    const float2 z8 = k.z8, z64 = k.z64;
    const uint32_t row = tb + lane * TBP;
    k.z128 = csq(z64);
    const float2 z16 = csq(z8), z24 = cmul(z16, z8), z32 = csq(z16), z40 = cmul(z32, z8), z48 = csq(z24), z56 = cmul(z32, z24);
    uint32_t re[4], im[4], a[4], b[4];
    re[0] = pack_f16(1.0f, z8.x); im[0] = pack_f16(0.0f, z8.y);
    re[1] = pack_f16(z16.x, z24.x); im[1] = pack_f16(z16.y, z24.y);
    re[2] = pack_f16(z32.x, z40.x); im[2] = pack_f16(z32.y, z40.y);
    re[3] = pack_f16(z48.x, z56.x); im[3] = pack_f16(z48.y, z56.y);
    sts128(row, re[0], re[1], re[2], re[3]);
    sts128(row + 32, im[0], im[1], im[2], im[3]);
    const uint32_t zx = pack_f16(z64.x, z64.x), zy = pack_f16(z64.y, z64.y), zw = pack_f16(k.z128.x, k.z128.y);
#pragma unroll
    for (int j = 0; j < 4; j++) hcmul(re[j], im[j], zx, zy, a[j], b[j]);
    sts128(row + 16, a[0], a[1], a[2], a[3]);
    sts128(row + 48, b[0], b[1], b[2], b[3]);
    const int mi = lane >> 3;
    const uint32_t zd = tb + mi * TBP + 96;
    sts16(zd + (lane & 7) * 2, zw); sts16(zd + (lane & 7) * 2 + 4 * TBP, zw >> 16);
    __syncwarp();
    const uint32_t ad = tb + (lane & 7) * TBP + mi * 16;
    ldsm_x4(a[0], a[1], a[2], a[3], zd);
    ldsm_x4(b[0], b[1], b[2], b[3], zd + 4 * TBP);
#pragma unroll
    for (int ks = 0; ks < 4; ks++) {
        ldsm_x4_t(k.A[0][ks][0], k.A[0][ks][1], k.A[0][ks][2], k.A[0][ks][3], ad + ks * 8 * TBP);
        hcmul(k.A[0][ks][0], k.A[0][ks][2], a[ks], b[ks], k.A[1][ks][0], k.A[1][ks][2]);
        hcmul(k.A[0][ks][1], k.A[0][ks][3], a[ks], b[ks], k.A[1][ks][1], k.A[1][ks][3]);
    }
}
__device__ __forceinline__ void kgen_chain(KGen& k, uint32_t cr, uint32_t ci, float cs) {
    k.T[0] = make_float2(bf_lo(cr) * cs, -bf_lo(ci) * cs);
    const float2 y1 = make_float2(k.z1.x, -k.z1.y);
#pragma unroll
    for (int c = 1; c < 8; c++) k.T[c] = cmul(k.T[c - 1], y1);
    k.T[8] = cmul(k.T[0], make_float2(k.z8.x, -k.z8.y));
}
__device__ __forceinline__ void kgen_cols(KGen& k, uint32_t tb, int lane) {
    const uint32_t row = tb + lane * TBP;
    const float2 (&T)[9] = k.T;
    const float2 y128 = make_float2(k.z128.x, -k.z128.y);
    const float2 y256 = csq(y128), y512 = csq(y256), y768 = cmul(y512, y256), y1024 = csq(y512);
    const float2 c1032 = cmul(T[8], y1024);
    __syncwarp();
    sts128(row, pack_f16(T[0].x, T[1].x), pack_f16(T[2].x, T[3].x), pack_f16(T[4].x, T[5].x), pack_f16(T[6].x, T[7].x));
    sts128(row + 16, pack_f16(T[0].y, T[1].y), pack_f16(T[2].y, T[3].y), pack_f16(T[4].y, T[5].y), pack_f16(T[6].y, T[7].y));
    uint32_t a[4], b[4];
    {
        const uint32_t zx = pack_f16(y256.x, y256.x), zy = pack_f16(y256.y, y256.y);
        hcmul(pack_f16(T[0].x, T[2].x), pack_f16(T[0].y, T[2].y), zx, zy, a[0], b[0]);
        hcmul(pack_f16(T[4].x, T[6].x), pack_f16(T[4].y, T[6].y), zx, zy, a[1], b[1]);
        const uint32_t r04 = pack_f16(T[0].x, T[4].x), i04 = pack_f16(T[0].y, T[4].y);
        hcmul(r04, i04, pack_f16(y512.x, y512.x), pack_f16(y512.y, y512.y), a[2], b[2]);
        hcmul(r04, i04, pack_f16(y768.x, y768.x), pack_f16(y768.y, y768.y), a[3], b[3]);
    }
    sts128(row + 32, a[0], a[1], a[2], a[3]);
    sts128(row + 48, b[0], b[1], b[2], b[3]);
    {
        const uint32_t r0 = pack_f16(1.0f, y256.x), i0 = pack_f16(0.0f, y256.y), r1 = pack_f16(y512.x, y768.x), i1 = pack_f16(y512.y, y768.y);
        const uint32_t zx = pack_f16(T[8].x, T[8].x), zy = pack_f16(T[8].y, T[8].y), wx = pack_f16(c1032.x, c1032.x), wy = pack_f16(c1032.y, c1032.y);
        hcmul(r0, i0, zx, zy, a[0], b[0]); hcmul(r1, i1, zx, zy, a[1], b[1]);
        hcmul(r0, i0, wx, wy, a[2], b[2]); hcmul(r1, i1, wx, wy, a[3], b[3]);
    }
    sts128(row + 64, a[0], a[1], a[2], a[3]);
    sts128(row + 80, b[0], b[1], b[2], b[3]);
}
__device__ __forceinline__ void kgen_mma(const KGen& k, uint32_t tb, int lane) {
    __syncwarp();
    float acc[2][3][4];
#pragma unroll
    for (int i = 0; i < 6; i++)
#pragma unroll
        for (int j = 0; j < 4; j++) acc[i / 3][i % 3][j] = 0.f;
    const int mi = lane >> 3;
    const uint32_t bd = tb + ((lane & 7) + 8 * (mi >> 1)) * TBP + (mi & 1) * 16;
#pragma unroll
    for (int kp = 0; kp < 2; kp++)
#pragma unroll
        for (int j = 0; j < 3; j++) {
            uint32_t b[4];
            ldsm_x4_t(b[0], b[1], b[2], b[3], bd + kp * 16 * TBP + j * 32);
#pragma unroll
            for (int h = 0; h < 2; h++)
#pragma unroll
                for (int m = 0; m < 2; m++) {
                    const uint32_t (&A)[4] = k.A[m][2 * kp + h];
                    mma_f16(acc[m][j], A[0], A[1], A[2], A[3], b[2 * h], b[2 * h + 1]);
                }
        }
    __syncwarp();
#define PK(j) pack_f16(acc[0][j][0], acc[0][j][1]), pack_f16(acc[0][j][2], acc[0][j][3]), pack_f16(acc[1][j][0], acc[1][j][1]), pack_f16(acc[1][j][2], acc[1][j][3])
    stsm_x4(tb + lane * 16, PK(0));
    stsm_x4(tb + 512 + lane * 16, PK(1));
    stsm_x4_t(tb + 1024 + (lane & 7) * 80 + mi * 16, PK(2));
#undef PK
}
__device__ __forceinline__ uint32_t table_buf(uint32_t sb, int warp) { return sb + SM_WD + (warp < 16 ? warp + 4 : warp - 16) * TBW; }

__device__ __forceinline__ uint4 lds16x4(uint32_t a) { return make_uint4(lds16(a), lds16(a + TBW), lds16(a + 2 * TBW), lds16(a + 3 * TBW)); }
__device__ __forceinline__ void combine_setup(uint32_t sb, int warp, int lane, uint32_t kw, uint32_t& o, uint32_t& n, uint32_t& d) {
    const int wq = warp & 3;
    const uint32_t a = table_buf(sb, warp & ~3);
    o = wq == 3 ? a + 1024 + 320 + (lane >> 3) * 80 + (lane & 7) * 8 : a + (wq ? 504 + wq * 8 : 0) + lane * 16;
    n = a + 1024 + wq * 80 + lane * 2;
    d = wq < 3 ? kw + (wq == 2 ? KW_P : 32 + wq * 512) + lane * 16 : kw + KW_H + 8 + lane * 8;
}
__device__ __forceinline__ void kgen_combine(int wq, int lane, uint32_t o, uint32_t na, uint32_t d) {
#define S4(f) hadd2(hadd2(u.f, v.f), hadd2(w.f, x.f))
#define H4(v) hadd2(hadd2(v.x, v.y), hadd2(v.z, v.w))
#define BP __byte_perm
    if (wq == 0) {
        const uint4 u = lds128(o), v = lds128(o + TBW), w = lds128(o + 2 * TBW), x = lds128(o + 3 * TBW), nn = lds16x4(na);
        const uint32_t n = H4(nn), k0 = S4(x), k2 = S4(y), k4 = S4(z), k6 = S4(w);
        sts128(d, BP(k0, k0, 0x1032), BP(k0, k2, 0x3254), BP(k2, k2, 0x1032), BP(k2, k4, 0x3254));
        sts128(d + KW_PL, BP(k4, k4, 0x1032), BP(k4, k6, 0x3254), BP(k6, k6, 0x1032), BP(k6, n, 0x3254));
        if (lane == 0) sts32(d + KW_PL - 4, k0 & 0xffffu);
    } else {
        const uint2 u = lds64(o), v = lds64(o + TBW), w = lds64(o + 2 * TBW), x = lds64(o + 3 * TBW);
        uint4 nn = make_uint4(0u, 0u, 0u, 0u), mm = nn;
        if (wq < 3) nn = lds16x4(na);
        if (wq == 2) mm = lds16x4(na + 80);
        const uint32_t k0 = S4(x), k2 = S4(y), n = H4(nn), m = H4(mm);
        if (wq == 3) {
            sts64(d, k0, k2);
        } else if (wq == 1) {
            const uint32_t cc = BP(k2, k2, 0x1010);
            sts128(d, BP(k0, k0, 0x1010), BP(k0, k0, 0x1032), BP(k0, k2, 0x3254), cc);
            sts128(d + KW_PL, cc, BP(k2, k2, 0x1032), BP(k2, n, 0x3254), BP(n, n, 0x1010));
        } else {
            const uint32_t w40 = BP(k0, k0, 0x1032), w84 = BP(k0, n, 0x3254), w0 = BP(k0, k0, 0x1010), w4 = BP(k0, k0, 0x3232), w8 = BP(n, n, 0x1010);
            sts64(d, w40, w84);
            sts64(d + 512, BP(k2, k2, 0x1032), BP(k2, m, 0x3254));
            if (lane < 8) { sts128(d - (KW_P - 1056), w0, w0, w40, w4); sts128(d - (KW_P - 1056 - KW_PL), w4, w84, w8, w8); }
            if (lane == 31) sts16(d + (KW_H + 6 - KW_P - 496), m);
        }
    }
#undef S4
#undef H4
#undef BP
}

__device__ __forceinline__ int c_exponent(const uint2& r, const uint2& i, float dt) {
    const uint32_t mx = __vmaxu2(__vmaxu2(r.x & 0x7fff7fffu, r.y & 0x7fff7fffu), __vmaxu2(i.x & 0x7fff7fffu, i.y & 0x7fff7fffu));
    return __reduce_max_sync(0xffffffffu, max(mx, mx << 16) + (__float_as_uint(dt) & 0x7f800000u)) >> 23;
}

__device__ __forceinline__ int warp_v() { int l; asm volatile("mov.u32 %0, %%tid.x;" : "=r"(l)); return __shfl_sync(0xffffffffu, l >> 5, 0); }
__device__ __forceinline__ int lane_v() { int l; asm volatile("mov.u32 %0, %%laneid;" : "=r"(l)); return l; }
__device__ __forceinline__ uint32_t prmt_v(uint32_t a, uint32_t b, uint32_t s) { uint32_t d; asm volatile("prmt.b32 %0, %1, %2, %3;\n" : "=r"(d) : "r"(a), "r"(b), "r"(s)); return d; }
__device__ __forceinline__ uint32_t mov_v(uint32_t a) { uint32_t d; asm volatile("mov.b32 %0, %1;\n" : "=r"(d) : "r"(a)); return d; }
template <int G>
__device__ __forceinline__ void conv_rename(float (&acc)[16][4]) {
#pragma unroll
    for (int i = G; i < 16; i++)
#pragma unroll
        for (int j = 0; j < 4; j++) { float v; asm volatile("mov.b32 %0, %1;\n" : "=f"(v) : "f"(acc[i][j])); acc[i][j] = v; }
}
struct Conv {
    uint32_t kw;
    uint32_t wa;
    uint32_t pa, s2;
    uint32_t s8;
    uint32_t id;
    uint32_t lc;
    uint32_t fs;
    uint32_t fl, yo;
    uint32_t yp;
    size_t ycopy;
    uint32_t ps;
    uint64_t d0;
    int warp;
};
struct Pk { uint32_t w[4]; };
__device__ __forceinline__ Pk pk2(const float (&u)[4], const float (&v)[4]) {
    Pk r;
    r.w[0] = pack_f16(u[0], u[1]); r.w[1] = pack_f16(u[2], u[3]); r.w[2] = pack_f16(v[0], v[1]); r.w[3] = pack_f16(v[2], v[3]);
    return r;
}
__device__ __forceinline__ void park(uint32_t a, const Pk& v) {
    asm volatile("stmatrix.sync.aligned.m8n8.x4.trans.shared.b16 [%0], {%1,%2,%3,%4};\n" ::"r"(a), "r"(v.w[0]), "r"(v.w[1]), "r"(v.w[2]), "r"(v.w[3]) : "memory");
}
__device__ __forceinline__ void conv_constants(uint32_t lc, int l) {
    const int d = (l >> 2) - 2 * (l & 3);
    const int e = d + 8, r4 = (e + 1 + ((e >> 2) & 1)) >> 2, p4 = (e + (((e - 1) >> 2) & 1)) >> 2;
    const uint32_t s2 = r4 == p4 ? 0x1010u : 0x3210u;
    sts64(lc + l * 8, KW_P + ((r4 - 5) >> 1) * 16 + ((r4 - 5) & 1) * 4, s2 | ((d < 0 ? s2 : 0x7654u) << 16));
    const int lo = (d >= 4) - (d < -3), ho = (d >= 5) - (d < -2), le = (d > 4) - (d < -4), he = (d > 5) - (d < -3);
    sts32(lc + 512 + l * 8, (0x5454u + lo * 0x22 + ho * 0x2200) | ((0x3232u + le * 0x22 + he * 0x2200) << 16));
    const int cc = l >> 2, j = l & 3;
    sts64(lc + 256 + l * 8, (j >> 1) * PL_HALF + (16 + cc) * 16 + (j & 1) * 8, (cc >> 1) * (DM * 64) + (cc & 1) * 32 + j * 8);
}
__device__ __forceinline__ void conv_selectors4(Conv& c) {
    const uint2 v = lds64(c.lc + lane_v() * 8);
    c.pa = v.x; c.s2 = v.y;
}
__device__ __forceinline__ void conv_selectors8(Conv& c) { c.s8 = lds32(c.lc + 512 + lane_v() * 8); }
template <int G, int I0, int I1>
__device__ __forceinline__ void conv_load(const Conv& c, uint32_t (&q)[9]) {
    const int wq = c.warp & 3;
    if (G < 2) {
#pragma unroll
        for (int i = I0; i < I1; i++) q[i] = lds32(c.wa + G * 512 + i * 16);
    } else if (G < 4) {
        const uint32_t a = (G == 2 && wq == 0) ? c.wa + 1024 : c.pa + c.kw + wq * 128 + (G < 2 ? 0 : G - 2) * 512;
#pragma unroll
        for (int i = I0; i < I1; i++) q[i] = lds32(a + i * 16);
    } else {
        const uint4 u = lds128(c.kw + KW_H + (G < 4 ? 0 : G - 4) * 64 + wq * 16);
        const uint2 v = lds64(c.kw + KW_H + (G < 4 ? 0 : G - 4) * 64 + wq * 16 + 16);
        q[0] = u.x; q[1] = u.y; q[2] = u.z; q[3] = u.w; q[4] = v.x; q[5] = v.y;
        if (G == 4 && wq == 0) { q[6] = lds32(c.pa + c.kw + 1024); q[7] = lds32(c.pa + c.kw + 1040); }
    }
}
template <int G, int J0, int J1>
__device__ __forceinline__ void conv_frag(const Conv& c, const uint32_t (&q)[9], uint32_t* a, const Pk& dp) {
    const uint32_t dep = dp.w[0];
    if (G < 4) {
        const uint32_t s = (G < 2 || (G == 2 && (c.warp & 3) == 0)) ? c.id : c.s2;
#pragma unroll
        for (int j = J0; j < J1; j++) {
            uint32_t* o = a + 4 * (j - J0);
            o[0] = prmt_v(q[2 * j + 1], dp.w[0], s); o[1] = prmt_v(q[2 * j + 2], dp.w[1], s); o[2] = prmt_v(q[2 * j], dp.w[2], s); o[3] = prmt_v(q[2 * j + 1], dp.w[3], s);
        }
    } else {
        const uint32_t so = prmt_v(c.s8, dep, c.id), se = prmt_v(c.s8, dep, c.id + 0x22);
#pragma unroll
        for (int j = J0; j < J1; j++) {
            uint32_t* o = a + 4 * (j - J0);
            o[0] = prmt_v(q[j + 1], q[j + 2], se); o[1] = prmt_v(q[j + 1], q[j + 2], so); o[2] = prmt_v(q[j], q[j + 1], so);
            if (G == 4 && j == 0 && (c.warp & 3) == 0) {
                o[2] = prmt_v(q[6], dep, c.s2);
                o[0] = prmt_v(q[7], o[0], c.s2 >> 16);
            }
            o[3] = mov_v(o[0]);
        }
    }
}
template <int G, int J0, int J1>
__device__ __forceinline__ void conv_frag(const Conv& c, const uint32_t (&q)[9], uint32_t* a, float depf) {
    const uint32_t d = __float_as_uint(depf);
    conv_frag<G, J0, J1>(c, q, a, Pk{{d, d, d, d}});
}
template <int G, int T, int J0, int J1>
__device__ __forceinline__ void conv_mma(float (&acc)[16][4], const Conv& c, const uint32_t* a) {
#pragma unroll
    for (int j = J0; j < J1; j++) wg_mma<T>(acc, a + 4 * (j - J0), c.d0 - 8 * (2 * G - T) - j);
}
__device__ __forceinline__ float h_lo(uint32_t w) { return __half2float(__ushort_as_half((unsigned short)(w & 0xffffu))); }
__device__ __forceinline__ float h_hi(uint32_t w) { return __half2float(__ushort_as_half((unsigned short)(w >> 16))); }
__device__ __forceinline__ void flush_setup(Conv& c) {
    const uint2 v = lds64(c.lc + 256 + lane_v() * 8);
    c.fl = v.x; c.yo = v.y;
}
template <int Q>
__device__ __forceinline__ void flush_load(const Conv& c, uint32_t pl, uint2 (&f)[4]) {
#pragma unroll
    for (int w = 0; w < 4; w++) f[w] = lds64(c.fl + pl + (Q & 1) * 512 + w * (PLW_B - 64));
}
template <int Q>
__device__ __forceinline__ void flush_load_first(const Conv& c, uint32_t pl, uint2 (&f)[4], float depf) {
    const uint32_t p = prmt_v(c.fl, __float_as_uint(depf), c.id) + pl + (Q & 1) * 512;
#define LDV64(d, a) asm volatile("ld.volatile.shared.v2.u32 {%0,%1}, [%2];\n" : "=r"(d.x), "=r"(d.y) : "r"(a) : "memory")
    LDV64(f[0], p); LDV64(f[1], p + (PLW_B - 64)); LDV64(f[2], p + 2 * (PLW_B - 64)); LDV64(f[3], p + 3 * (PLW_B - 64));
}
#define FDEP __uint_as_float(f[3].y)
template <int Q, int mode>
__device__ __forceinline__ void conv_flush(const Conv& c, const uint2 (&f)[4], unsigned char* gy, uint32_t rx) {
    const uint32_t a0 = hadd2(f[0].x, f[1].x), a1 = hadd2(f[2].x, f[3].x), b0 = hadd2(f[0].y, f[1].y), b1 = hadd2(f[2].y, f[3].y);
    if (Q > 0 && mode == 1) {
        const uint32_t ra = rx + 16 + (Q > 0 ? Q - 1 : 0) * 1024 + (c.warp & 3) * 256 + lane_v() * 8;
        asm volatile("st.async.shared::cluster.mbarrier::complete_tx::bytes.v2.b32 [%0], {%1,%2}, [%3];\n"
                     ::"r"(ra ^ 0x1000000u), "r"(hadd2(a0, a1)), "r"(hadd2(b0, b1)), "r"((rx + (Q > 1 ? 8 : 0)) ^ 0x1000000u) : "memory");
        return;
    }
    float v0 = h_lo(a0) + h_lo(a1), v1 = h_hi(a0) + h_hi(a1), v2 = h_lo(b0) + h_lo(b1), v3 = h_hi(b0) + h_hi(b1);
    if (Q > 0 && mode == 2) {
        const uint2 o = lds64(rx + 16 + (Q > 0 ? Q - 1 : 0) * 1024 + (c.warp & 3) * 256 + lane_v() * 8);
        v0 += h_lo(o.x); v1 += h_hi(o.x); v2 += h_lo(o.y); v3 += h_hi(o.y);
    }
    const uint32_t lo = hmul2_bf(pack_bf16(v0, v1), c.fs), hi = hmul2_bf(pack_bf16(v2, v3), c.fs);
    stg64(gy + Q * 32 * DM * 32 + (c.yo + (Q < 3 ? c.yp : 0u)), lo ^ YKEY, hi ^ YKEY);
}
template <int I, bool S = false> struct IC { static constexpr int value = I; static constexpr bool shared = S; };
template <class T> __device__ constexpr bool wg_is4() { return T::shared; }
#define SLOT(n) (c.ps + (2 + ((n) & 7)) * 128)
#define GO() do { wg_commit(); __syncwarp(); } while (0)
#define DEP acc[15][3]
template <class FG, class FP, class FN>
__device__ __forceinline__ void conv_head(Conv& c, float (&acc)[16][4], uint32_t (&q)[9], uint32_t (&r)[9], uint32_t* a, FG fg, FP pre, FN next) {
    c.id = 0x3210u + (c.warp >> 8);
    conv_load<0, 0, 9>(c, q);
    conv_frag<0, 0, 1>(c, q, a, 0.f);
    pre();
    wg_fence(); wg_first<0>(acc, a, c.d0); GO();
    park(c.ps, Pk{{0u, 0u, 0u, 0u}});
    wg_wait0();
    conv_frag<0, 1, 2>(c, q, a, DEP);
    wg_fence(); conv_mma<0, 0, 1, 2>(acc, c, a); GO();
    fg(IC<0>());
    wg_wait0();
    conv_frag<0, 2, 3>(c, q, a, DEP);
    wg_fence(); conv_mma<0, 0, 2, 3>(acc, c, a); GO();
    conv_load<1, 0, 5>(c, r);
    wg_wait0();
    conv_frag<0, 3, 4>(c, q, a, DEP);
    wg_fence(); conv_mma<0, 0, 3, 4>(acc, c, a); GO();
    conv_load<1, 5, 9>(c, r);
    fg(IC<1>());
    wg_wait0();
    const Pk k = pk2(acc[0], acc[1]);
    conv_rename<2>(acc);
    conv_frag<1, 0, 2>(c, r, a, k);
    wg_fence(); conv_mma<1, 2, 0, 2>(acc, c, a); GO();
    park(SLOT(0), k);
    next(IC<0>());
    fg(IC<2>());
    wg_wait0();
    conv_frag<1, 2, 4>(c, r, a, DEP);
    wg_fence(); conv_mma<1, 2, 2, 4>(acc, c, a); GO();
    next(IC<1>());
    fg(IC<3>());
    wg_wait0();
}
template <class FG, class FP>
__device__ __forceinline__ void conv_run(Conv& c, uint32_t pl, unsigned char* gy, FG fg, FP pre) {
    float acc[16][4];
    uint32_t q[9], r[9], a[32];
    uint2 f[4];
    const int bid = 1 + (c.warp >> 2);
    conv_head(c, acc, q, r, a, fg, pre, [&](auto i) { if (decltype(i)::value == 0) conv_selectors4(c); else conv_load<2, 0, 9>(c, q); });
    Pk k = pk2(acc[2], acc[3]);
    conv_rename<4>(acc);
    conv_frag<2, 0, 4>(c, q, a, k);
    wg_fence(); conv_mma<2, 4, 0, 4>(acc, c, a); GO();
    park(SLOT(2), k);
    conv_load<3, 0, 9>(c, q);
    flush_setup(c);
    bar_sync(bid, 128);
    fg(IC<4>());
    wg_wait0();
    conv_rename<6>(acc);
    flush_load_first<0>(c, pl, f, DEP);
    conv_frag<3, 0, 4>(c, q, a, FDEP);
    wg_fence(); conv_mma<3, 6, 0, 4>(acc, c, a); GO();
    park(SLOT(4), pk2(acc[4], acc[5]));
    conv_load<4, 0, 9>(c, q);
    conv_selectors8(c);
    conv_flush<0, 0>(c, f, gy, 0u);
    fg(IC<5>());
    wg_wait0();
    conv_rename<8>(acc);
    conv_frag<4, 0, 4>(c, q, a, DEP);
    wg_fence(); conv_mma<4, 8, 0, 4>(acc, c, a); GO();
    k = pk2(acc[6], acc[7]);
    park(SLOT(6), k); park(c.ps, k);
    conv_load<5, 0, 9>(c, q);
    bar_sync(bid, 128);
    fg(IC<6>());
    wg_wait0();
    conv_rename<10>(acc);
    flush_load_first<1>(c, pl, f, DEP);
    conv_frag<5, 0, 4>(c, q, a, FDEP);
    wg_fence(); conv_mma<5, 10, 0, 4>(acc, c, a); GO();
    park(SLOT(8), pk2(acc[8], acc[9]));
    conv_load<6, 0, 9>(c, q); conv_load<7, 0, 9>(c, r);
    conv_flush<1, 0>(c, f, gy, 0u);
    fg(IC<7>());
    wg_wait0();
    conv_rename<12>(acc);
    conv_frag<6, 0, 4>(c, q, a, DEP); conv_frag<7, 0, 4>(c, r, a + 16, DEP);
    wg_fence(); conv_mma<6, 12, 0, 4>(acc, c, a); conv_mma<7, 12, 0, 4>(acc, c, a + 16); GO();
    park(SLOT(10), pk2(acc[10], acc[11]));
    bar_sync(bid, 128);
    flush_load<2>(c, pl, f);
    conv_flush<2, 0>(c, f, gy, 0u);
    fg(IC<8>());
    wg_wait0();
    park(SLOT(12), pk2(acc[12], acc[13])); park(SLOT(14), pk2(acc[14], acc[15]));
    bar_sync(bid, 128);
    flush_load<3>(c, pl, f);
    conv_flush<3, 0>(c, f, gy, 0u);
}
template <class FG>
__device__ __forceinline__ void conv_outer(Conv& c, uint32_t pl, unsigned char* gy, uint32_t rx, FG fg) {
    float acc[16][4];
    uint32_t q[9], r[9], a[32];
    uint2 f[4], f2[4];
    const int bid = 1 + (c.warp >> 2);
    conv_head(c, acc, q, r, a, [&](auto gi) { if (decltype(gi)::value == 2) fg(IC<2, true>()); }, [&]() {}, [&](auto i) { if (decltype(i)::value == 0) conv_selectors8(c); else conv_load<6, 0, 9>(c, q); });
    park(SLOT(2), pk2(acc[2], acc[3])); park(SLOT(4), pk2(acc[4], acc[5]));
    const Pk k = pk2(acc[6], acc[7]);
    park(SLOT(6), k);
    conv_load<7, 0, 9>(c, r);
    conv_rename<12>(acc);
    conv_frag<6, 0, 4>(c, q, a, __uint_as_float(k.w[3])); conv_frag<7, 0, 4>(c, r, a + 16, __uint_as_float(k.w[3]));
    wg_fence(); conv_mma<6, 12, 0, 4>(acc, c, a); conv_mma<7, 12, 0, 4>(acc, c, a + 16); GO();
    flush_setup(c);
    bar_sync(bid, 128);
    flush_load<0>(c, pl, f); flush_load<1>(c, pl, f2);
    conv_flush<1, 1>(c, f2, gy, rx);
    conv_flush<0, 1>(c, f, gy, rx);
    wg_wait0();
    bar_sync(bid, 128);
    park(c.ps, k); park(SLOT(8), pk2(acc[8], acc[9])); park(SLOT(10), pk2(acc[10], acc[11]));
    park(SLOT(12), pk2(acc[12], acc[13])); park(SLOT(14), pk2(acc[14], acc[15]));
    bar_sync(bid, 128);
    flush_load<2>(c, pl, f); flush_load<3>(c, pl, f2);
    conv_flush<2, 1>(c, f, gy, rx);
    conv_flush<3, 1>(c, f2, gy, rx);
}
template <class FG>
__device__ __forceinline__ void conv_inner(Conv& c, uint32_t pl, unsigned char* gy, uint32_t rx, FG fg) {
    float acc[16][4];
    uint32_t q[9], a[16];
    uint2 f[4], f2[4];
    const int bid = 1 + (c.warp >> 2);
    c.id = 0x3210u + (c.warp >> 8);
    conv_selectors4(c);
    conv_load<2, 0, 9>(c, q);
    conv_frag<2, 0, 4>(c, q, a, 0.f);
    wg_fence(); wg_first<4>(acc, a, c.d0); conv_mma<2, 4, 1, 4>(acc, c, a + 4); GO();
    conv_load<3, 0, 9>(c, q);
    park(SLOT(2), Pk{{0u, 0u, 0u, 0u}});
    fg(IC<2, true>());
    wg_wait0();
    conv_rename<6>(acc);
    conv_frag<3, 0, 4>(c, q, a, DEP);
    wg_fence(); conv_mma<3, 6, 0, 4>(acc, c, a); GO();
    park(SLOT(4), pk2(acc[4], acc[5]));
    conv_load<4, 0, 9>(c, q);
    conv_selectors8(c);
    wg_wait0();
    conv_rename<8>(acc);
    conv_frag<4, 0, 4>(c, q, a, DEP);
    wg_fence(); conv_mma<4, 8, 0, 4>(acc, c, a); GO();
    const Pk k = pk2(acc[6], acc[7]);
    park(SLOT(6), k); park(c.ps, k);
    conv_load<5, 0, 9>(c, q);
    flush_setup(c);
    wg_wait0();
    conv_rename<10>(acc);
    conv_frag<5, 0, 4>(c, q, a, DEP);
    wg_fence(); conv_mma<5, 10, 0, 4>(acc, c, a); GO();
    park(SLOT(8), pk2(acc[8], acc[9]));
    bar_sync(bid, 128);
    flush_load<1>(c, pl, f);
    mbar_wait(rx);
    conv_flush<1, 2>(c, f, gy, rx);
    wg_wait0();
    bar_sync(bid, 128);
    park(SLOT(10), pk2(acc[10], acc[11])); park(SLOT(12), pk2(acc[12], acc[13])); park(SLOT(14), pk2(acc[14], acc[15]));
    bar_sync(bid, 128);
    flush_load<3>(c, pl, f); flush_load<2>(c, pl, f2);
    mbar_wait(rx + 8);
    conv_flush<3, 2>(c, f, gy, rx);
    conv_flush<2, 2>(c, f2, gy, rx);
}
#undef SLOT
#undef GO
#undef DEP
template <int U0, int U1>
__device__ __forceinline__ void weight_units(uint32_t sb, const CUtensorMap* tg, const CUtensorMap* tu, const CUtensorMap* td, bool w) {
    if (U1 > U0 && w && elect_one()) {
#pragma unroll
        for (int n = U0; n < U1; n++) {
            const int i = n;
            if (i < 12) tma_2d(sb + SM_WG + i * 6912, i < 6 ? tg : tu, 72 * (blockIdx.x >> 1), 288 * (blockIdx.x & 1) + (i % 6) * 48, sb + SM_MISC + 328);
            else tma_2d(sb + SM_WD + (i - 12) * 4736, td, 144 * (blockIdx.x & 1), 72 * (blockIdx.x >> 1) + 8 * (i - 12), sb + SM_MISC + 336);
        }
    }
}
#define WS 1111121111122004100
__device__ constexpr int wsched(int i) {
    unsigned long long v = WS;
    int n = 0;
    for (int k = 19; k >= 1; k--) { if (k < i) n += (int)(v % 10); v /= 10; }
    return n;
}
static_assert(wsched(20) == 21 && wsched(6) <= 7 && wsched(11) <= 12 && wsched(16) <= 17 && wsched(16) == wsched(15), "");
__device__ __forceinline__ void weight_prefetch(const Params& p, int u, int lane) {
    const int b = blockIdx.x;
    const char* a = u < 12 ? reinterpret_cast<const char*>(u < 6 ? p.wg : p.wu) + ((b >> 6) * 288 + (u % 6) * 48) * (FF * 2) + (b & 63) * 6912
                           : reinterpret_cast<const char*>(p.wd) + (72 * (b >> 1) + 8 * (u - 12)) * 1152 + (b & 1) * 4608;
    asm volatile("prefetch.global.L2 [%0];\n" ::"l"(a + lane * 128));
    if (lane < (u < 12 ? 22 : 4)) asm volatile("prefetch.global.L2 [%0];\n" ::"l"(a + 4096 + lane * 128));
}
#define PF0 0
#define PF1 0
#define WPOINT(i, w) do { weight_units<wsched(i), wsched(i + 1)>(sb, &tm_g, &tm_u, &tm_d, w); } while (0)

__global__ void __launch_bounds__(NTHR, 1) __cluster_dims__(2, 1, 1)
fused_kernel(const Params p, const __grid_constant__ CUtensorMap tm_g, const __grid_constant__ CUtensorMap tm_u, const __grid_constant__ CUtensorMap tm_d, const __grid_constant__ CUtensorMap tm_x) {
    extern __shared__ __align__(1024) unsigned char smem[];
    const uint32_t sb = smem_u32(smem);
    const int tid = threadIdx.x, warp = __shfl_sync(0xffffffffu, tid >> 5, 0), lane = tid & 31;
    const int b = blockIdx.x, P = b >> 1, odd = b & 1;
    const int g = lane >> 2, t = lane & 3;
    const int wg = warp >> 2, t128 = tid & 127;
    const uint32_t s_stat = sb + SM_MISC;
    const uint32_t s_key = sb + SM_MISC + 128;
    const uint32_t s_rank = sb + SM_MISC + 256;
    const uint32_t s_k16 = sb + SM_MISC + 192;
    const uint32_t s_cnt = sb + SM_MISC + 320;
    const uint32_t bar_w = sb + SM_MISC + 328, bar_d = bar_w + 8, bar_g = bar_w + 16, bar_x = bar_w + 24, bar_t = bar_w + 32;
    STAMP(0);

    if (warp == 19) {
        if (lane == 0) {
            mbar_init(bar_w, 1); mbar_init(bar_d, 1); mbar_init(bar_g, 1 + OEARLY); mbar_init(sb + SM_RX, 1); mbar_init(sb + SM_RX + 8, 1);
            mbar_init(bar_x, 1); mbar_init(bar_t, 1); mbar_expect(bar_x, 32768);
            asm volatile("fence.mbarrier_init.release.cluster;\n" ::: "memory");
            mbar_expect(bar_w, 82944); mbar_expect(bar_d, 72 * WD_PITCH); mbar_expect(bar_g, 9216); mbar_expect(bar_t, 18 * 1152); mbar_expect(sb + SM_RX, 1024); mbar_expect(sb + SM_RX + 8, 2048);
        }
        __syncwarp();
    } else if (warp == 18) {
#pragma unroll
        for (int i = 0; i < 9; i++) sts128(sb + SM_ZERO + (i * 32 + lane) * 16, 0u, 0u, 0u, 0u);
        fence_async();
        __syncwarp();
    }
    const int ch = wg < 4 ? 4 * b + wg : 512 + P;
    const bf16 *q0 = p.lar + ch * NST, *q1 = p.aim + ch * NST, *q2 = p.cre + ch * NST, *q3 = p.cim + ch * NST;
    asm volatile("" : "+l"(q0), "+l"(q1), "+l"(q2), "+l"(q3));
    const uint32_t ldt = ldo16(p.ldt + ch), pl = ldo16(q0 + t128), pa2 = ldo16(q1 + t128);
    const uint32_t pc = ldo16(q2 + t128), pi = ldo16(q3 + t128);
    const uint2 call_re = ldo64(q2 + 4 * lane), call_im = ldo64(q3 + 4 * lane);
    if (PBAR) { if (wg == 4) bar_sync(0, NWRK); else bar_arrive(0, NWRK); }
    uint4 xv[9], xu[2];
    if (wg == 4) {
        const bf16* xp = p.x + (size_t)(16 * b + 4 * (warp & 3) + (g & 3)) * DM + 288 * (g >> 2) + 8 * t;
#pragma unroll
        for (int c = 0; c < 9; c++) xv[c] = ldo128(xp + c * 32);
        if (warp < 18) {
            const bf16* xq = p.x + (size_t)(16 * b + TOK(g)) * DM + 32 * warp + 8 * t;
            xu[0] = ldo128(xq); xu[1] = ldo128(xq + 2 * DM);
        }
    }
    auto xcols = [&](int z) {
        if (MC) {
            asm volatile("barrier.cluster.wait.aligned;\n" ::: "memory");
            if (elect_one()) tma_4d_mc(sb + SM_XC + odd * 16384, &tm_x, 8 * P + z, 2 * odd, bar_x);
        } else if (elect_one()) tma_4d(sb + SM_XC, &tm_x, 8 * P + z, 0, bar_x);
        __syncwarp();
    };
    if (MC) asm volatile("barrier.cluster.arrive.relaxed.aligned;\n" ::: "memory");
    if (warp == 18) {
        if (lane == 0) bulk_s2g(reinterpret_cast<unsigned char*>(p.s->y) + 96 * 18432 + b * 4608, sb + SM_ZERO, 4608);
        bar_arrive(12, 64);
    }
    if (warp == 19) { bar_sync(12, 64); xcols(0); }
    const uint32_t kw = sb + SM_KW + wg * KW_B;
    const uint32_t tb = table_buf(sb, warp);
    if (wg == 4) {
        const int wq = warp & 3;
        const uint32_t epl = ld_poll32(p.s->hint + (b & 7) * 32 + 1);
        unsigned char* const ud = reinterpret_cast<unsigned char*>(p.s->uT) + (size_t)(8 * wq + 2 * (g >> 1)) * 16384 + b * 128 + (g & 1) * 32 + t * 8;
        uint32_t* const sd_ = p.s->stat + 16 * b + 4 * wq + g;
        const bool own = g < 4 && t == (g >> 1);
        if (own) *reinterpret_cast<volatile uint32_t*>(sd_) = 0u;
        if (wq < 2) {
#pragma unroll
            for (int k = 0; k < 4; k++) *reinterpret_cast<volatile unsigned long long*>(ud + (k >> 1) * 16384 + (k & 1) * 64) = 0ull;
        }
        if (wq == 1) conv_constants(sb + SM_LC, lane);
        uint32_t one;
        asm volatile("st.volatile.shared.u32 [%1], 0x3f803f80;\nld.volatile.shared.u32 %0, [%1];\n" : "=r"(one) : "r"(tb + lane * 4) : "memory");
        float cs[2][4] = {}, d1[2][4] = {}, d2[2][4] = {};
#pragma unroll
        for (int c = 0; c < 9; c++) {
            const uint4 v = xv[c];
            mma_bf16(cs[c & 1], v.x, v.y, v.z, v.w, one, one);
            mma_bf16(d1[c & 1], v.x, v.y, v.z, v.w, v.x, v.z); mma_bf16(d2[c & 1], v.x, v.y, v.z, v.w, v.y, v.w);
        }
        STAMP(27);
        float sm = (cs[0][0] + cs[0][2]) + (cs[1][0] + cs[1][2]);
        float sq = (g & 1) ? (d1[0][1] + d2[0][3]) + (d1[1][1] + d2[1][3]) : (d1[0][0] + d2[0][2]) + (d1[1][0] + d2[1][2]);
        sm += __shfl_xor_sync(0xffffffffu, sm, 18); sq += __shfl_xor_sync(0xffffffffu, sq, 18);
        if (HOLD == 1) bar_arrive(6 + wq, 160);
        float mb, sd;
        ln_stats(sm, sq, mb, sd);
        if (own) *sd_ = (__float_as_uint(mb) >> 16) | (__float_as_uint(sd) & 0x7fff0000u) | (epl << 31);
        STAMPX(22);
        if (wq < PF0) weight_prefetch(p, wq, lane);
        if (HOLD == 2) bar_arrive(6 + wq, 160);
        if (own) stat_store(s_stat + (2 * wq + (g & 1) + 8 * (g >> 1)) * 8, mb, rcp_approx(sd), 0u);
        if (lane == 1) sts32(s_cnt + 4, epl);
        if (wq == 2) asm volatile("cp.async.bulk.wait_group 0;\n" ::: "memory");
        bar_sync(5, 128);
        STAMP(28);
        if (wq >= 2) { bar_arrive(2 * wq - 3, 160); bar_arrive(2 * wq - 2, 160); }
        WPOINT(1, wq == 3);
        if (wq == 2 && lane < 8) p.s->key[8 * b + lane] = epl & 1u;
        if (wq < 2) {
            const uint32_t utag = (epl % 7u + 1u) * 0x10001u;
            uint32_t U[2][4];
#pragma unroll
            for (int hf = 0; hf < 2; hf++) {
                const uint2 st = lds64(s_stat + (g + 8 * hf) * 8);
                const uint32_t X[4] = {xu[hf].x, xu[hf].y, xu[hf].z, xu[hf].w};
#pragma unroll
                for (int k = 0; k < 4; k++) {
                    const uint32_t u = ln_apply(X[k], STAT_M(st), STAT_H(st), STAT_L(st));
                    U[hf][k] = movm((pack_f16(bf_lo(u), bf_hi(u)) & 0xfff8fff8u) | utag);
                }
            }
#pragma unroll
            for (int k = 0; k < 4; k++) stg64(ud + (k >> 1) * 16384 + (k & 1) * 64, U[0][k], U[1][k]);
        }
    } else if (warp == 0) {
#pragma unroll
        for (int i = 0; i < 7; i++) sts128(sb + SM_LNP + (i * 32 + lane) * 16, 0u, 0u, 0u, 0u);
    }
    if (t128 < 2 * UPAD) sts128(sb + SM_U + wg * USLOT_B + (t128 & 1) * ULO_B + (t128 >> 1) * 16, 0u, 0u, 0u, 0u);
    if (t128 >= 124) sts128(kw + (t128 & 1) * 16 + (t128 & 2) * (KW_PL / 2), 0u, 0u, 0u, 0u);
    uint32_t co, cn, cd;
    combine_setup(sb, warp, lane, kw, co, cn, cd);
    const uint4* usrc = wg < 4 ? reinterpret_cast<const uint4*>(p.s->stat) + tid
                               : reinterpret_cast<const uint4*>(p.s->uT) + (P >> 2) * 1024 + (t128 >> 1) * 8 + (P & 3) * 2 + (t128 & 1);
    uint32_t zero;
    {
        uint32_t uo = (uint32_t)(reinterpret_cast<const char*>(usrc) - reinterpret_cast<const char*>(p.s)), pk = (cn - co + 1024) | ((cd - kw) << 16);
        asm volatile("st.volatile.shared.v4.u32 [%4], {0, %1, %2, %3};\nld.volatile.shared.v4.u32 {%0, %1, %2, %3}, [%4];\n" : "=r"(zero), "+r"(co), "+r"(pk), "+r"(uo) : "r"(tb + lane * 16) : "memory");
        cn = co + (pk & 0xffffu) - 1024; cd = kw + (pk >> 16);
        usrc = reinterpret_cast<const uint4*>(reinterpret_cast<const char*>(p.s) + uo);
    }
    const float dt = exp_bf(__uint_as_float(__byte_perm(ldt, zero, 0x1044)));
    STAMP(1);
    if (wg < 4) { STAMPX(16); }
    KGen kg;
    kgen_setup(kg, __uint_as_float(__byte_perm(pl, zero, 0x1044)), __uint_as_float(__byte_perm(pa2, zero, 0x1044)), dt);
    kgen_rows(kg, tb, lane);
    STAMP(2);
    const int E = min(max(c_exponent(call_re, call_im, dt) - 243, -120), 120);
    kgen_chain(kg, pc, pi, dt * __uint_as_float((uint32_t)(128 - E) << 23));
    STAMP(3);
    WPOINT(2, warp == 19);
    kgen_cols(kg, tb, lane);
    STAMP(4);
    WPOINT(3, warp == 19);
    if (wg < 4) { STAMPX(17); }
    if (HOLD && wg < 4) bar_sync(6 + (warp & 3), 160);
    if (wg < 4) { STAMPX(19); }
    kgen_mma(kg, tb, lane);
    if (wg < 4) { STAMPX(20); }
    STAMP(5);
    WPOINT(4, warp == 19);
    if (wg < 4) bar_sync(1 + wg, 160); else bar_sync(5, 128);
    if (wg < 4) { STAMPX(21); }
    uint4 uv0, uv1;
    if (PEARLY) { uv0 = ld_poll(usrc); if (wg == 4) uv1 = ld_poll(usrc + 512); }
    kgen_combine(warp & 3, lane, co, cn, cd);
    const uint32_t ep = lds32(s_cnt + 4);
    if (!PEARLY) { uv0 = ld_poll(usrc); if (wg == 4) uv1 = ld_poll(usrc + 512); }
    STAMP(6);
    if (wg < 4) { STAMPX(18); }
    WPOINT(5, warp == 19);
    if (MC && warp != 19) asm volatile("barrier.cluster.wait.aligned;\n" ::: "memory");
    uint2 yv[4] = {};
    {
        const int wq = warp & 3;
        Conv c;
        const uint32_t pln = sb + SM_PL + wg * PL_B;
        const int e = g - 2 * t + 7;
        c.kw = kw; c.wa = kw + ((e >> 2) & 1) * KW_PL + (8 * wq + (e >> 3)) * 16 + (e & 3) * 4;
        c.ps = mov_v(pln + wq * PLW_B + ((lane >> 3) & 1) * PL_HALF + ((lane >> 4) * 8 + (lane & 7)) * 16); c.warp = warp;
        c.lc = sb + SM_LC; c.fs = (uint32_t)(127 + E) * 0x800080u; c.yp = (__shfl_sync(0xffffffffu, ep, 0) & 1u) * (NCTA * 18432u);
        c.d0 = ((uint64_t)(ULO_B >> 4) << 16) | ((uint64_t)(128 >> 4) << 32) | (uint64_t)(((sb + SM_U + wg * USLOT_B + UPAD * 16) & 0x3FFFF) >> 4);
        unsigned char* gy = reinterpret_cast<unsigned char*>(p.s->y) + ((size_t)(4 * wq) * DM + ch) * 64;
        auto hook = [&](auto gi) {
                     constexpr int G = decltype(gi)::value;
                     if (G == (wg_is4<decltype(gi)>() ? 2 : 5)) asm volatile("barrier.cluster.wait.aligned;\n" ::: "memory");
                     if (!wg_is4<decltype(gi)>() && G < 4 && warp == HW) {
                         const int l2 = lane_v();
                         unsigned char* const sc = reinterpret_cast<unsigned char*>(p.s);
                         if (G == 0 && l2 < 2) bulk_s2g(sc + offsetof(Scratch, rows) + b * 4608 + l2 * 2304, sb + SM_LNP, 2304);
                         if (b < 96 && l2 < (G ? 3 : 1))
                             bulk_s2g(l2 ? sc + offsetof(Scratch, y) + (NCTA * 18432u - c.yp) + b * 18432 + (2 * G + l2 - 3) * 3072 : sc + offsetof(Scratch, part) + b * 12288 + G * 3072,
                                      sb + SM_LNP, 3072);
                         __syncwarp();
                     }
                     if (!wg_is4<decltype(gi)>() && PF1 && G >= PF1 && G < PF1 + 2 && (warp >> 1) == 2) weight_prefetch(p, 17 + 2 * (G - PF1) + (warp & 1), lane_v());
                     if (!wg_is4<decltype(gi)>()) WPOINT(6 + G, warp == 12 + (G & 3));
                     if (YPRE && G == 8 && b < YPRE) {
                         const int l2 = lane_v();
                         const unsigned char* ys = reinterpret_cast<const unsigned char*>(p.s->y) + c.yp + ((P * DM + 32 * warp + (l2 & 24) + ((l2 >> 2) & 1)) * 64 + odd * 32 + (l2 & 3) * 8);
#pragma unroll
                         for (int k = 0; k < 4; k++) yv[k] = ld_poll64(ys + k * 128);
                     }
                     if (!wg_is4<decltype(gi)>() && G == XG && warp == HW) { asm volatile("cp.async.bulk.wait_group 0;\n" ::: "memory"); __syncwarp(); }
                     if (!wg_is4<decltype(gi)>() && G == XG && warp == HW && elect_one()) {
                         bulk_g2s(sb + SM_XT, p.x + (size_t)16 * b * DM, 16 * 1152, bar_t);
                         bulk_g2s(sb + SM_XT + 16 * 1152, p.dsk, 1152, bar_t);
                         bulk_g2s(sb + SM_XT + 17 * 1152, p.wr, 1152, bar_t);
                     }
                 };
        bar_sync(1 + wg, 128);
        if (wg < 4) {
            asm volatile("barrier.cluster.arrive.relaxed.aligned;\n" ::: "memory");
            conv_run(c, pln + wq * 128, gy, hook, [&]() {
                STAMPX(23);
                mbar_wait(bar_x);
                STAMP(9);
                STAMPX(24);
                uint2 xc[4];
                uint32_t xw[4][2];
#pragma unroll
                for (int j = 0; j < 4; j++) xc[j] = lds64(sb + SM_XC + wg * 8192 + j * 2048 + t128 * 16 + odd * 8);
#pragma unroll
                for (int i = 0; i < 8; i++) {
                    const int k = i >> 1, h = i & 1;
                    xw[k][h] = prmt_v(k < 2 ? xc[2 * h].x : xc[2 * h].y, k < 2 ? xc[2 * h + 1].x : xc[2 * h + 1].y, (k & 1) ? 0x7632 : 0x5410);
                }
                const uint32_t ub = mov_v(sb + SM_U + UPAD * 16 + ((tid >> 1) & 1) * ULO_B + (tid >> 2) * 16 + (tid & 1) * 8), tag = ep << 31;
                int it = 0;
                while (min(min((int)(uv0.x ^ tag), (int)(uv0.y ^ tag)), min((int)(uv0.z ^ tag), (int)(uv0.w ^ tag))) < 0x10000) {
                    if (++it > SPIN_LIMIT) TRAP();
                    uv0 = ld_poll(usrc);
                }
                STAMP(8);
                STAMPX(26);
                const float r0 = rcp_approx(fabsf(bf_hi(uv0.x))), r1 = rcp_approx(fabsf(bf_hi(uv0.y))), r2 = rcp_approx(fabsf(bf_hi(uv0.z))), r3 = rcp_approx(fabsf(bf_hi(uv0.w)));
                const uint32_t m[2] = {__byte_perm(uv0.x, uv0.y, 0x5410), __byte_perm(uv0.z, uv0.w, 0x5410)};
                const uint32_t rh[2] = {pack_bf16(r0, r1), pack_bf16(r2, r3)};
                const uint32_t rl[2] = {pack_bf16(r0 - bf_lo(rh[0]), r1 - bf_hi(rh[0])), pack_bf16(r2 - bf_lo(rh[1]), r3 - bf_hi(rh[1]))};
#pragma unroll
                for (int k = 0; k < 4; k++) {
                    const uint32_t u0 = ln_apply(xw[k][0], m[0], rh[0], rl[0]), u1 = ln_apply(xw[k][1], m[1], rh[1], rl[1]);
                    sts64(ub + k * USLOT_B, pack_f16(bf_lo(u0), bf_hi(u0)), pack_f16(bf_lo(u1), bf_hi(u1)));
                }
                STAMPX(29);
                fence_async();
                bar_sync(14, 512);
                STAMP(7);
            });
        } else {
            auto stage = [&]() {
                const uint32_t tag = (ep % 7u + 1u) * 0x10001u;
                int it = 0;
                while (true) {
                    uv0.x ^= tag; uv0.y ^= tag; uv0.z ^= tag; uv0.w ^= tag; uv1.x ^= tag; uv1.y ^= tag; uv1.z ^= tag; uv1.w ^= tag;
                    if ((((uv0.x | uv0.y | uv0.z) | (uv0.w | uv1.x | uv1.y) | (uv1.z | uv1.w)) & 0x70007u) == 0) break;
                    if (++it > SPIN_LIMIT) TRAP();
                    uv0 = ld_poll(usrc); uv1 = ld_poll(usrc + 512);
                }
                STAMP(8);
                const uint32_t ub = sb + SM_U + UPAD * 16 + 4 * USLOT_B + (t128 & 1) * ULO_B + (t128 >> 1) * 16;
                sts128(ub, uv0.x, uv0.y, uv0.z, uv0.w);
                sts128(ub + 1024, uv1.x, uv1.y, uv1.z, uv1.w);
                fence_async();
                asm volatile("barrier.cluster.arrive.relaxed.aligned;\n" ::: "memory");
                bar_sync(5, 128);
                STAMP(7);
            };
            stage();
            if (odd) conv_inner(c, pln + wq * 128, gy, sb + SM_RX, hook);
            else conv_outer(c, pln + wq * 128, gy, sb + SM_RX, hook);
        }
        STAMP(10);
    }
    {
    const int lane = lane_v(), tid = 32 * warp + lane, g = lane >> 2, t = lane & 3;
    const uint32_t par = ~lds32(s_cnt + 4) & 1u;
    if (CBAR) bar_sync(0, NWRK);
    STAMP(11);
    uint32_t H[2][4] = {}, U2[2][4] = {};
    uint32_t WA[9][4], WD[18];
    auto publish = [&](bool hi, int slot) {
        uint4* rowp = reinterpret_cast<uint4*>(p.s->rows) + slot * 144 + warp * 4 + t;
        stg128(rowp, nzw(hi ? U2[1][0] : U2[0][0]), nzw(hi ? U2[1][1] : U2[0][1]), nzw(hi ? U2[1][2] : U2[0][2]), nzw(hi ? U2[1][3] : U2[0][3]));
        stg128(rowp + 72, nzw(hi ? H[1][0] : H[0][0]), nzw(hi ? H[1][1] : H[0][1]), nzw(hi ? H[1][2] : H[0][2]), nzw(hi ? H[1][3] : H[0][3]));
    };
#define KTOK(k) (2047 - (int)(((k) >> 5) & 0x7ffu))
#define KLATE(k) (((k) & 0x1cu) != 0)
#define KSLOT(k, s) (KLATE(k) ? 2 * NCTA + (s) : 2 * (KTOK(k) >> 4) + (int)(((k) >> 1) & 1u))
    const uint4* const rsrc = reinterpret_cast<const uint4*>(p.s->rows) + 36 * odd;
    auto gather = [&](uint32_t mine) {
        int it = 0;
#pragma unroll 1
        for (int r = 0; r < 9; r++) {
            const uint32_t k = r < 8 ? __shfl_sync(0xffffffffu, mine, 4 * r) : mine;
            const int row = r < 8 ? r : g, c = r < 8 ? lane : 32 + t;
            uint4 v;
            do { v = ld_poll(rsrc + KSLOT(k, row) * 144 + c); if (++it > SPIN_LIMIT) TRAP(); } while (!min4(v));
            sts128(sb + SM_XS + row * XS_PITCH + c * 16, v.x, v.y, v.z, v.w);
        }
    };
    if (warp < 18) {
        const unsigned char* ys = reinterpret_cast<const unsigned char*>(p.s->y) + (b < 96 ? (par ^ 1u) * (NCTA * 18432u) : 0u) +
                                  ((P * DM + 32 * warp + 8 * (g >> 1) + (g & 1)) * 64 + odd * 32 + t * 8);
        if (YDLY == 0 || b < YFROM) {
#pragma unroll
            for (int k = 0; k < 4; k++) yv[k] = ld_poll64(ys + k * 128);
        } else if (YDLY > 1) delay(YDLY);
        mbar_wait(bar_t);
        const uint32_t xa = sb + SM_XT + warp * 64 + t * 16;
        const uint4 x0 = lds128(xa + TOK(g) * 1152), x1 = lds128(xa + (TOK(g) + 2) * 1152), dk = lds128(xa + 16 * 1152);
        uint4 wr = make_uint4(0u, 0u, 0u, 0u);
        if (g == 0) wr = lds128(xa + 17 * 1152);
        const uint32_t Z[2][4] = {{x0.x, x0.y, x0.z, x0.w}, {x1.x, x1.y, x1.z, x1.w}}, D4[4] = {dk.x, dk.y, dk.z, dk.w};
#pragma unroll
        for (int hf = 0; hf < 2; hf++) {
            const uint2 st = lds64(s_stat + (g + 8 * hf) * 8);
#pragma unroll
            for (int k = 0; k < 4; k++) H[hf][k] = hmul2_bf(ln_apply(Z[hf][k], STAT_M(st), STAT_H(st), STAT_L(st)), D4[k]);
        }
        int it = 0;
        while (__any_sync(0xffffffffu, min(min(min(yv[0].x, yv[0].y), min(yv[1].x, yv[1].y)), min(min(yv[2].x, yv[2].y), min(yv[3].x, yv[3].y))) == 0)) {
#pragma unroll
            for (int k = 0; k < 4; k++) yv[k] = ld_poll64(ys + k * 128);
            if (++it > SPIN_LIMIT) TRAP();
        }
        STAMP(12);
#pragma unroll
        for (int k = 0; k < 4; k++) {
            H[0][k] = hadd2_bf(Z[0][k], hadd2_bf(movm(yv[k].x ^ YKEY), H[0][k]));
            H[1][k] = hadd2_bf(Z[1][k], hadd2_bf(movm(yv[k].y ^ YKEY), H[1][k]));
        }
        ln_partial(H, sb + SM_LNP, warp, g, t);
        bar_arrive(6, NWRK);
        STAMP(13);
        bar_sync(7, 608);
        STAMP(14);
#pragma unroll
        for (int hf = 0; hf < 2; hf++) {
            const uint2 st = lds64(s_stat + (g + 8 * hf) * 8);
#pragma unroll
            for (int k = 0; k < 4; k++) U2[hf][k] = ln_apply(H[hf][k], STAT_M(st), STAT_H(st), STAT_L(st));
        }
        {
            float cs[4] = {0.f, 0.f, 0.f, 0.f};
            mma_bf16(cs, U2[0][0], U2[1][0], U2[0][1], U2[1][1], wr.x, wr.y);
            mma_bf16(cs, U2[0][2], U2[1][2], U2[0][3], U2[1][3], wr.z, wr.w);
            if (t == 0) { stsf(sb + SM_LNP + ((32 + g) * 20 + warp) * 4, cs[0]); stsf(sb + SM_LNP + ((40 + g) * 20 + warp) * 4, cs[2]); }
            bar_arrive(8, 608);
        }
        bar_sync(9, 608);
        const uint32_t rk[2] = {lds32(s_rank + g * 4), lds32(s_rank + 32 + g * 4)};
#pragma unroll
        for (int hf = 0; hf < 2; hf++)
            sts128(sb + SM_OUT + (TOK(g) + 2 * hf) * (DM * 2) + warp * 64 + t * 16,
                   hadd2_bf(H[hf][0], U2[hf][0]), hadd2_bf(H[hf][1], U2[hf][1]), hadd2_bf(H[hf][2], U2[hf][2]), hadd2_bf(H[hf][3], U2[hf][3]));
        fence_async();
        if (OEARLY) bar_arrive(10, 608);
        uint32_t lo = min(rk[0], rk[1]), hi = max(rk[0], rk[1]);
#pragma unroll 1
        while (lo < 2) { publish(lo == rk[1], 2 * b + lo); lo = hi; hi = 16; }
        STAMP(15);
        {
            const int mi = lane >> 3, rr = lane & 7;
            mbar_wait(bar_w);
            const uint32_t aad = sb + SM_WG + (mi & 1) * SM_WU + ((warp & 1) * 144 + rr + 8 * (mi >> 1)) * W_PITCH + (warp >> 1) * 16;
#pragma unroll
            for (int k = 0; k < 9; k++) ldsm_x4_t(WA[k][0], WA[k][1], WA[k][2], WA[k][3], aad + k * 16 * W_PITCH);
        }
        STAMP2(17);
        bar_sync(11, NWRK);
    } else if (warp == 18) {
        bar_sync(6, NWRK);
        {
            float mb, rc;
            ln_finish(sum18(sb + SM_LNP + lane * 80), lane, mb, rc);
            if (lane < 16) stat_store(s_stat + lane * 8, mb, rc, 0u);
        }
        bar_arrive(7, 608);
        const uint4* ksrc = reinterpret_cast<const uint4*>(p.s->key) + lane;
        const uint32_t klo = (uint32_t)(2047 - 16 * b - ROWTOK(lane & 15)) << 5 | par;
        bar_sync(8, 608);
        {
            const float r = sum18(sb + SM_LNP + (32 + (lane & 15)) * 80);
            const uint32_t bits = pack_bf16(0.f, r);
            const uint32_t me = ((bits ^ ((uint32_t)((int)bits >> 31) | 0x80000000u)) & 0xffff0000u) | klo;
            sts32(s_k16 + (lane & 15) * 4, me);
            __syncwarp();
            const uint4 v = lds128(s_k16 + (lane & 16) * 2), w = lds128(s_k16 + (lane & 16) * 2 + 16);
            int rank = ((v.x > me) + (v.y > me)) + ((v.z > me) + (v.w > me)) + (((w.x > me) + (w.y > me)) + ((w.z > me) + (w.w > me)));
            rank += __shfl_xor_sync(0xffffffffu, rank, 16);
            if (lane < 16 && rank < 8) p.s->key[8 * b + rank] = me | (rank << 1);
            if (lane >= 16) sts32(s_rank + (lane & 15) * 4, rank);
        }
        bar_arrive(9, 608);
        uint4 kq[4];
        int it = 0;
        if (KDLY) delay(KDLY);
        do {
#pragma unroll
            for (int i = 0; i < 4; i++) kq[i] = ld_poll(ksrc + lane + 64 * i);
            if (++it > SPIN_LIMIT) TRAP();
        } while (__any_sync(0xffffffffu, ((((kq[0].x ^ par) | (kq[0].y ^ par) | (kq[0].z ^ par)) | ((kq[1].x ^ par) | (kq[1].y ^ par) | (kq[1].z ^ par)) |
                                           ((kq[2].x ^ par) | (kq[2].y ^ par) | (kq[2].z ^ par)) | ((kq[3].x ^ par) | (kq[3].y ^ par) | (kq[3].z ^ par))) & 1u) != 0));
        STAMPW(16);
        uint32_t u[4], mine = 0, m;
        {
            uint32_t S[2][4];
#pragma unroll
            for (int i = 0; i < 2; i++) {
                const uint4 &c = kq[2 * i], &d = kq[2 * i + 1];
                const uint32_t m1 = min(c.x, d.x), m2 = max(c.y, d.y);
                S[i][0] = max(c.x, d.x); S[i][1] = max(m1, m2); S[i][2] = min(m1, m2); S[i][3] = min(c.y, d.y);
            }
            const uint32_t a0 = max(S[0][0], S[1][3]), a1 = max(S[0][1], S[1][2]), a2 = max(S[0][2], S[1][1]), a3 = max(S[0][3], S[1][0]);
            const uint32_t b0 = max(a0, a2), b2 = min(a0, a2), b1 = max(a1, a3), b3 = min(a1, a3);
            u[0] = max(b0, b1); u[1] = min(b0, b1); u[2] = max(b2, b3); u[3] = min(b2, b3);
        }
        uint4 v[9];
#pragma unroll
        for (int r = 0; r < 8; r++) {
            m = __reduce_max_sync(0xffffffffu, u[0]);
            if (u[0] == m) { u[0] = u[1]; u[1] = u[2]; u[2] = u[3]; u[3] = 0; }
            if (g == r) mine = m;
            v[r] = ld_poll(rsrc + (2 * (KTOK(m) >> 4) + ((m >> 1) & 1u)) * 144 + lane);
        }
        v[8] = ld_poll(rsrc + (2 * (KTOK(mine) >> 4) + ((mine >> 1) & 1u)) * 144 + 32 + t);
        bool again = __any_sync(0xffffffffu, u[0] == 0 || max(max(kq[0].z, kq[1].z), max(kq[2].z, kq[3].z)) > m);
        if (again) {
#pragma unroll 1
            for (int i = 0; i < 8; i++) {
                uint4 k;
                do { k = ld_poll(ksrc + 32 * i); if (++it > SPIN_LIMIT) TRAP(); } while (((k.x ^ par) | (k.y ^ par) | (k.z ^ par) | (k.w ^ par)) & 1u);
                sts128(sb + SM_KEYS + (32 * i + lane) * 16, k.x, k.y, k.z, k.w);
            }
            m = 0xffffffffu;
#pragma unroll 1
            for (int r = 0; r < 8; r++) {
                uint32_t c = 0;
#pragma unroll 2
                for (int i = 0; i < 8; i++) {
                    const uint4 k = lds128(sb + SM_KEYS + (32 * i + lane) * 16);
                    c = max(max(c, k.x < m ? k.x : 0u), max(k.y < m ? k.y : 0u, max(k.z < m ? k.z : 0u, k.w < m ? k.w : 0u)));
                }
                m = __reduce_max_sync(0xffffffffu, c);
                if (g == r) mine = m;
            }
        }
        if (t == 0) sts32(s_key + g * 4, mine);
        uint32_t mn = 1;
#pragma unroll
        for (int r = 0; r < 9; r++) {
            sts128(sb + SM_XS + (r < 8 ? r * XS_PITCH + lane * 16 : g * XS_PITCH + (32 + t) * 16), v[r].x, v[r].y, v[r].z, v[r].w);
            mn = min(mn, min4(v[r]));
        }
        if ((again || __any_sync(0xffffffffu, mn == 0)) && !__any_sync(0xffffffffu, KLATE(mine))) gather(mine);
        STAMPW(18);
        bar_sync(11, NWRK);
    } else {
        bar_sync(6, NWRK);
        WPOINT(16, true);
        if (wsched(18) > wsched(17)) delay(WDLY);
        WPOINT(17, true);
        if (OEARLY) {
            bar_sync(10, 608);
            if (lane == 0) bulk_s2g(p.out + (size_t)16 * b * DM, sb + SM_OUT, 16 * DM * 2);
            __syncwarp();
        } else if (wsched(19) > wsched(18)) delay(WDLY);
        WPOINT(18, true);
        if (wsched(20) > wsched(19)) delay(WDLY);
        WPOINT(19, true);
        bar_sync(11, NWRK);
    }
    STAMP2(19);
    const uint32_t kk = lds32(s_key + (lane & 7) * 4);
    float e4[4];
    auto gate_up = [&]() {
        float c4[3][4];
#pragma unroll
        for (int i = 0; i < 3; i++)
#pragma unroll
            for (int j = 0; j < 4; j++) c4[i][j] = 0.f;
        const uint32_t bad = sb + SM_XS + (lane & 7) * XS_PITCH + ((warp & 1) * 144 + 8 * (lane >> 3)) * 2;
#pragma unroll
        for (int k = 0; k < 9; k += 2) {
            uint32_t b0, b1, b2, b3;
            ldsm_x4(b0, b1, b2, b3, bad + k * 32);
            mma_bf16(c4[k % 3], WA[k][0], WA[k][1], WA[k][2], WA[k][3], b0, b1);
            if (k < 8) mma_bf16(c4[(k + 1) % 3], WA[k + 1][0], WA[k + 1][1], WA[k + 1][2], WA[k + 1][3], b2, b3);
        }
#pragma unroll
        for (int j = 0; j < 4; j++) e4[j] = c4[0][j] + c4[1][j] + c4[2][j];
    };
    if (warp < 18) gate_up();
    if (!OEARLY && warp == 19) {
        const uint32_t sel = __reduce_or_sync(0xffffffffu, (KTOK(kk) >> 4) == b ? 1u << (KTOK(kk) & 15) : 0u);
        if (sel ? lane < 16 && !((sel >> lane) & 1u) : lane == 0) bulk_s2g(p.out + (size_t)(16 * b + lane) * DM, sb + SM_OUT + lane * (DM * 2), sel ? DM * 2 : 16 * DM * 2);
        __syncwarp();
    }
    if (OEARLY && tid == 608) {
        asm volatile("cp.async.bulk.wait_group 0;\n" ::: "memory");
        asm volatile("mbarrier.arrive.relaxed.cluster.shared::cluster.b64 _, [%0];\n" ::"r"(bar_g ^ 0x1000000u) : "memory");
    }
    if (__any_sync(0xffffffffu, KLATE(kk))) {
        const uint32_t ep = lds32(s_cnt + 4);
        const bool own = KLATE(kk) && (KTOK(kk) >> 4) == b;
        uint32_t todo = __ballot_sync(0xffffffffu, own) & 0xffu;
        if (todo) {
#pragma unroll 1
            while (todo) {
                const int s = __ffs(todo) - 1, tk = KTOK(__shfl_sync(0xffffffffu, kk, s));
                todo &= todo - 1;
                if (warp < 18 && (tk & 13) == TOK(g)) publish(tk & 2, 2 * NCTA + s);
            }
            __threadfence();
        }
        bar_sync(0, NWRK);
        if (tid < NSEL && own) *reinterpret_cast<volatile unsigned*>(p.s->flag + tid) = ep + 1u;
        int it = 0;
        while (__any_sync(0xffffffffu, KLATE(kk) && ld_poll32(p.s->flag + (lane & 7)) != ep + 1u)) { if (++it > SPIN_LIMIT) TRAP(); }
        __threadfence();
        if (warp == 18) gather(__shfl_sync(0xffffffffu, kk, g));
        bar_sync(0, NWRK);
        if (warp < 18) gate_up();
    }
    if (warp < 18) {
        const uint32_t ex = sb + SM_EX + (2 * odd + (warp & 1)) * 4608 + (warp >> 1) * 512 + lane * 16;
        asm volatile("st.async.shared::cluster.mbarrier::complete_tx::bytes.v4.f32 [%0], {%1,%2,%3,%4}, [%5];\n"
                     ::"r"(ex ^ 0x1000000u), "f"(e4[0]), "f"(e4[1]), "f"(e4[2]), "f"(e4[3]), "r"(bar_g ^ 0x1000000u) : "memory");
        sts128f(ex, e4);
        if (warp < 9) bar_sync(12, 576); else bar_arrive(12, 576);
        const int mi = lane >> 3, rr = lane & 7;
        mbar_wait(bar_d);
        const uint32_t base = sb + SM_WD + (2 * warp + (mi & 1)) * 16 + rr * WD_PITCH;
#pragma unroll
        for (int k = 0; k < 4; k++) ldsm_x4_t(WD[4 * k], WD[4 * k + 1], WD[4 * k + 2], WD[4 * k + 3], base + (k * 16 + 8 * (mi >> 1)) * WD_PITCH);
        ldsm_x2_t(WD[16], WD[17], base + 64 * WD_PITCH);
    }
    STAMP2(20);
    const int grp = 3 * b + warp - 17, fsl = 2 * t + ((lane >> 3) & 1), fc = 16 * (grp >> 3) + (grp & 7) + 8 * (lane >> 4);
    const uint32_t fk = __shfl_sync(0xffffffffu, kk, fsl);
    uint32_t hw = 0, uw = 0;
    const uint32_t* const fsrc = p.s->rows + KSLOT(fk, fsl) * DM + (fc >> 1);
    if (warp < 9) {
        mbar_wait(bar_g);
        const uint32_t ex = sb + SM_EX + tid * 16;
        const uint4 a = lds128(ex), c = lds128(ex + 4608), d = lds128(ex + 9216), e = lds128(ex + 13824);
#define S4(f) rbf((__uint_as_float(a.f) + __uint_as_float(c.f)) + (__uint_as_float(d.f) + __uint_as_float(e.f)))
        const float G0 = S4(x), G1 = S4(y), U0 = S4(z), U1 = S4(w);
#undef S4
        sts32(sb + SM_GU + tid * 4, pack_bf16(rbf(__fdividef(G0, 1.0f + __expf(-G0))) * U0, rbf(__fdividef(G1, 1.0f + __expf(-G1))) * U1));
    } else if (warp >= 17) {
        if (b < 96) { hw = ld_poll32(fsrc + 288); uw = ld_poll32(fsrc); }
    }
    bar_sync(13, NWRK);
    STAMP2(21);
    if (warp < 18) {
        uint32_t gb[9];
        ldsm_x4_t(gb[0], gb[1], gb[2], gb[3], sb + SM_GU + lane * 16);
        ldsm_x4_t(gb[4], gb[5], gb[6], gb[7], sb + SM_GU + 512 + lane * 16);
        ldsm_x1_t(gb[8], sb + SM_GU + 1024 + (lane & 7) * 16);
        float c4[4] = {0.f, 0.f, 0.f, 0.f}, d4[4] = {0.f, 0.f, 0.f, 0.f};
        mma_bf16(c4, WD[0], WD[1], WD[2], WD[3], gb[0], gb[1]);
        mma_bf16(d4, WD[4], WD[5], WD[6], WD[7], gb[2], gb[3]);
        mma_bf16(c4, WD[8], WD[9], WD[10], WD[11], gb[4], gb[5]);
        mma_bf16(d4, WD[12], WD[13], WD[14], WD[15], gb[6], gb[7]);
        mma_bf16(c4, WD[16], WD[17], 0u, 0u, gb[8], 0u);
        stg128(p.s->part + ((8 * (18 * odd + warp) + g) * 64 + P) * 16 + t * 4,
               __float_as_uint(c4[0] + d4[0]) | 1u, __float_as_uint(c4[1] + d4[1]) | 1u, __float_as_uint(c4[2] + d4[2]) | 1u, __float_as_uint(c4[3] + d4[3]) | 1u);
    }
    STAMP2(22);
    if (warp >= 17 && b < 96) {
        int it = 0;
        while (!hw || !uw) { hw = ld_poll32(fsrc + 288); uw = ld_poll32(fsrc); if (++it > SPIN_LIMIT) TRAP(); }
        const uint32_t bits = (fk ^ ((uint32_t)((int)~fk >> 31) | 0x80000000u)) & 0xffff0000u;
        const float rs = rbf(__fdividef(1.0f, 1.0f + __expf(-__uint_as_float(bits))));
        const float hv = (fc & 1) ? bf_hi(hw) : bf_lo(hw), u2 = (fc & 1) ? bf_hi(uw) : bf_lo(uw);
        bf16* const dst = p.out + KTOK(fk) * DM + fc;
        delay(warp > 17 ? FDLY + 250 : FDLY);
        const uint4* src = reinterpret_cast<const uint4*>(p.s->part) + grp * 256 + lane;
        uint4 a[8];
        do {
#pragma unroll
            for (int i = 0; i < 8; i++) a[i] = ld_poll(src + 32 * i);
            if (++it > SPIN_LIMIT) TRAP();
#define A4(v) (v.x & v.y & v.z & v.w)
        } while (!(((A4(a[0]) & A4(a[1])) & (A4(a[2]) & A4(a[3])) & (A4(a[4]) & A4(a[5])) & (A4(a[6]) & A4(a[7]))) & 1u));
#undef A4
        STAMP2(24);
#define S8(f) (((__uint_as_float(a[0].f) + __uint_as_float(a[1].f)) + (__uint_as_float(a[2].f) + __uint_as_float(a[3].f))) + \
               ((__uint_as_float(a[4].f) + __uint_as_float(a[5].f)) + (__uint_as_float(a[6].f) + __uint_as_float(a[7].f))))
        const float s0 = S8(x), s1 = S8(y), s2 = S8(z), s3 = S8(w);
#undef S8
        const bool up = lane & 16, od = lane & 8;
        const float r0 = (up ? s2 : s0) + __shfl_xor_sync(0xffffffffu, up ? s0 : s2, 16), r1 = (up ? s3 : s1) + __shfl_xor_sync(0xffffffffu, up ? s1 : s3, 16);
        float y = (od ? r1 : r0) + __shfl_xor_sync(0xffffffffu, od ? r0 : r1, 8);
        y += __shfl_xor_sync(0xffffffffu, y, 4);
        if (!(lane & 4)) *dst = __float2bfloat16_rn(hv + rbf(u2 + rbf(rbf(y) * rs)));
    }
    if (warp == 19) asm volatile("cp.async.bulk.wait_group.read 0;\n" ::: "memory");
    if (b == 0 && tid < 8) *reinterpret_cast<volatile unsigned*>(p.s->hint + tid * 32 + 1) = lds32(s_cnt + 4) + 1u;
    STAMP(25);
    }
}

typedef CUresult (*PFN_tmEncode)(CUtensorMap*, CUtensorMapDataType, cuuint32_t, void*, const cuuint64_t*, const cuuint64_t*, const cuuint32_t*,
                                 const cuuint32_t*, CUtensorMapInterleave, CUtensorMapSwizzle, CUtensorMapL2promotion, CUtensorMapFloatOOBfill);

extern "C" void kernel_launch(void* const* d_in, const int* in_sizes, int n_in, void* d_out, int out_size) {
    Params p;
    p.x = (const bf16*)d_in[0];
    p.lar = (const bf16*)d_in[1];
    p.aim = (const bf16*)d_in[2];
    p.cre = (const bf16*)d_in[3];
    p.cim = (const bf16*)d_in[4];
    p.ldt = (const bf16*)d_in[5];
    p.dsk = (const bf16*)d_in[6];
    p.wr = (const bf16*)d_in[8];
    p.wg = (const bf16*)d_in[9];
    p.wu = (const bf16*)d_in[10];
    p.wd = (const bf16*)d_in[11];
    p.out = (bf16*)d_out;
    static PFN_tmEncode enc = nullptr;
    static void* scratch = nullptr;
    if (!enc) {
        cudaFuncSetAttribute(fused_kernel, cudaFuncAttributeMaxDynamicSharedMemorySize, SMEM_TOTAL);
        void* fn = nullptr;
        cudaDriverEntryPointQueryResult qr;
        cudaGetDriverEntryPoint("cuTensorMapEncodeTiled", &fn, cudaEnableDefault, &qr);
        enc = (PFN_tmEncode)fn;
        cudaGetSymbolAddress(&scratch, g_scratch);
    }
    p.s = (Scratch*)scratch;
    CUtensorMap tm_g, tm_u, tm_d, tm_x;
    const cuuint64_t dims[2] = {FF, DM}, strides[1] = {FF * 2};
    const cuuint32_t box[2] = {72, 48}, es[2] = {1, 1};
    enc(&tm_g, CU_TENSOR_MAP_DATA_TYPE_BFLOAT16, 2, d_in[9], dims, strides, box, es, CU_TENSOR_MAP_INTERLEAVE_NONE, CU_TENSOR_MAP_SWIZZLE_NONE,
        CU_TENSOR_MAP_L2_PROMOTION_NONE, CU_TENSOR_MAP_FLOAT_OOB_FILL_NONE);
    enc(&tm_u, CU_TENSOR_MAP_DATA_TYPE_BFLOAT16, 2, d_in[10], dims, strides, box, es, CU_TENSOR_MAP_INTERLEAVE_NONE, CU_TENSOR_MAP_SWIZZLE_NONE,
        CU_TENSOR_MAP_L2_PROMOTION_NONE, CU_TENSOR_MAP_FLOAT_OOB_FILL_NONE);
    const cuuint64_t ddims[2] = {DM / 2, FF}, dstrides[1] = {DM * 2};
    const cuuint32_t dbox[2] = {WD_PITCH / 4, 8};
    enc(&tm_d, CU_TENSOR_MAP_DATA_TYPE_UINT32, 2, d_in[11], ddims, dstrides, dbox, es, CU_TENSOR_MAP_INTERLEAVE_NONE, CU_TENSOR_MAP_SWIZZLE_NONE,
        CU_TENSOR_MAP_L2_PROMOTION_NONE, CU_TENSOR_MAP_FLOAT_OOB_FILL_NONE);
    const cuuint64_t xdims[4] = {DM, 128, 4, 4}, xstrides[3] = {DM * 8, DM * 2, DM * 1024};
    const cuuint32_t xbox[4] = {8, 128, 4, MC ? 2 : 4}, xes[4] = {1, 1, 1, 1};
    enc(&tm_x, CU_TENSOR_MAP_DATA_TYPE_BFLOAT16, 4, d_in[0], xdims, xstrides, xbox, xes, CU_TENSOR_MAP_INTERLEAVE_NONE, CU_TENSOR_MAP_SWIZZLE_NONE,
        CU_TENSOR_MAP_L2_PROMOTION_NONE, CU_TENSOR_MAP_FLOAT_OOB_FILL_NONE);
    fused_kernel<<<NCTA, NTHR, SMEM_TOTAL>>>(p, tm_g, tm_u, tm_d, tm_x);
}
```

```cpp
#include <cuda_runtime.h>
#include <cuda.h>
#include <cuda_fp16.h>
#include <cuda_bf16.h>
#include <stdint.h>

#define LSEQ 2048
#define DM 576
#define NST 128
#define FF 4608
#define NSEL 8
#define NCTA 128
#define NTHR 640
#define NWRK 640

typedef __nv_bfloat16 bf16;

#define SM_WG 0
#define SM_WU 41472
#define SM_XC (82944 - 32768)
#define SM_WD 82944
#define W_PITCH 144
#define WD_PITCH 592
#define SM_XT (SM_PL - 18 * 1152)
#define SM_PL (SM_WD + 46080)
#define PL_HALF 1344
#define PLW_B 2624
#define PL_B (4 * PLW_B)
#define SM_U (SM_PL + 5 * PL_B)
#define UPAD 20
#define ULO_B ((UPAD + 128) * 16)
#define USLOT_B (2 * ULO_B)
#define SM_ZERO (SM_U + 4 * USLOT_B + 128)
#define SM_KW (SM_U + 5 * USLOT_B)
#define KW_B 3712
#define KW_PL 1216
#define KW_P 2400
#define KW_H 3440
#define SM_MISC (SM_KW + 5 * KW_B)
#define SM_LC (SM_MISC + 384)
#define SM_LNP (SM_LC + 768)
#define SM_RX (SM_LNP + 3840)
#define SMEM_TOTAL (SM_RX + 3088)
#define YKEY 0xffc1ffc1u
#define TBP 112
#define TBW (32 * TBP)
#define SM_OUT SM_PL
#define SM_XS (SM_PL + 18432)
#define XS_PITCH 592
#define SM_GU (SM_PL + 23296)
#define SM_EX (SM_PL + 24576)
#define SM_KEYS SM_KW

struct __align__(128) Scratch {
    unsigned hint[8 * 32];
    unsigned flag[32];
    uint32_t key[NCTA * 8];
    uint32_t stat[LSEQ];
    uint32_t uT[64 * (LSEQ / 2)];
    uint32_t y[(NCTA + 96) * DM * 8];
    uint32_t part[288 * 64 * 16];
    uint32_t rows[(2 * NCTA + NSEL) * DM];
};
__device__ Scratch g_scratch;
#define STAMP(i)
#define STAMPX(i)
#define STAMPY(i)

__device__ __forceinline__ float rbf(float x) {
    uint32_t r;
    asm("cvt.rn.bf16x2.f32 %0, %1, %2;\n" : "=r"(r) : "f"(x), "f"(0.f));
    return __uint_as_float(r & 0xffff0000u);
}
__device__ __forceinline__ uint32_t pack_bf16(float lo, float hi) {
    uint32_t r;
    asm("cvt.rn.bf16x2.f32 %0, %1, %2;\n" : "=r"(r) : "f"(hi), "f"(lo));
    return r;
}
__device__ __forceinline__ uint32_t pack_f16(float lo, float hi) {
    uint32_t r;
    asm("cvt.rn.f16x2.f32 %0, %1, %2;\n" : "=r"(r) : "f"(hi), "f"(lo));
    return r;
}
__device__ __forceinline__ uint32_t pack_f16_rz(float lo, float hi) {
    uint32_t r;
    asm("cvt.rz.f16x2.f32 %0, %1, %2;\n" : "=r"(r) : "f"(hi), "f"(lo));
    return r;
}
__device__ __forceinline__ float bf_lo(uint32_t w) { return __uint_as_float(w << 16); }
__device__ __forceinline__ float bf_hi(uint32_t w) { return __uint_as_float(w & 0xffff0000u); }
__device__ __forceinline__ uint32_t hadd2_bf(uint32_t a, uint32_t b) {
    __nv_bfloat162 r = __hadd2_rn(*reinterpret_cast<__nv_bfloat162*>(&a), *reinterpret_cast<__nv_bfloat162*>(&b));
    return *reinterpret_cast<uint32_t*>(&r);
}
__device__ __forceinline__ uint32_t hsub2_bf(uint32_t a, uint32_t b) {
    __nv_bfloat162 r = __hsub2_rn(*reinterpret_cast<__nv_bfloat162*>(&a), *reinterpret_cast<__nv_bfloat162*>(&b));
    return *reinterpret_cast<uint32_t*>(&r);
}
__device__ __forceinline__ uint32_t hmul2_bf(uint32_t a, uint32_t b) {
    __nv_bfloat162 r = __hmul2_rn(*reinterpret_cast<__nv_bfloat162*>(&a), *reinterpret_cast<__nv_bfloat162*>(&b));
    return *reinterpret_cast<uint32_t*>(&r);
}
__device__ __forceinline__ uint32_t hfma2_bf(uint32_t a, uint32_t b, uint32_t c) { uint32_t r; asm("fma.rn.bf16x2 %0, %1, %2, %3;\n" : "=r"(r) : "r"(a), "r"(b), "r"(c)); return r; }
__device__ __forceinline__ uint32_t hmul2(uint32_t a, uint32_t b) { uint32_t r; asm("mul.rn.f16x2 %0, %1, %2;\n" : "=r"(r) : "r"(a), "r"(b)); return r; }
__device__ __forceinline__ uint32_t hadd2(uint32_t a, uint32_t b) { uint32_t r; asm("add.rn.f16x2 %0, %1, %2;\n" : "=r"(r) : "r"(a), "r"(b)); return r; }
__device__ __forceinline__ uint32_t hfma2(uint32_t a, uint32_t b, uint32_t c) { uint32_t r; asm("fma.rn.f16x2 %0, %1, %2, %3;\n" : "=r"(r) : "r"(a), "r"(b), "r"(c)); return r; }
__device__ __forceinline__ uint32_t hfms2(uint32_t a, uint32_t b, uint32_t c) {
    uint32_t r;
    asm("{\n.reg .b32 n;\nneg.f16x2 n, %2;\nfma.rn.f16x2 %0, %1, n, %3;\n}\n" : "=r"(r) : "r"(a), "r"(b), "r"(c));
    return r;
}
__device__ __forceinline__ uint32_t nzw(uint32_t w) { return w ? w : 0x8000u; }
__device__ __forceinline__ uint32_t nzf(float f) { const uint32_t w = __float_as_uint(f); return w ? w : 0x80000000u; }
__device__ __forceinline__ uint32_t smem_u32(const void* p) { return (uint32_t)__cvta_generic_to_shared(p); }
__device__ __forceinline__ uint32_t lds32(uint32_t addr) {
    uint32_t v;
    asm volatile("ld.shared.u32 %0, [%1];\n" : "=r"(v) : "r"(addr) : "memory");
    return v;
}
__device__ __forceinline__ uint32_t lds16(uint32_t addr) {
    unsigned short v;
    asm volatile("ld.shared.u16 %0, [%1];\n" : "=h"(v) : "r"(addr) : "memory");
    return v;
}
__device__ __forceinline__ uint2 lds64(uint32_t addr) {
    uint2 v;
    asm volatile("ld.shared.v2.u32 {%0,%1}, [%2];\n" : "=r"(v.x), "=r"(v.y) : "r"(addr) : "memory");
    return v;
}
__device__ __forceinline__ uint4 lds128(uint32_t addr) {
    uint4 v;
    asm volatile("ld.shared.v4.u32 {%0,%1,%2,%3}, [%4];\n" : "=r"(v.x), "=r"(v.y), "=r"(v.z), "=r"(v.w) : "r"(addr) : "memory");
    return v;
}
__device__ __forceinline__ float ldsf(uint32_t addr) { return __uint_as_float(lds32(addr)); }
__device__ __forceinline__ void sts32(uint32_t addr, uint32_t v) { asm volatile("st.shared.u32 [%0], %1;\n" ::"r"(addr), "r"(v) : "memory"); }
__device__ __forceinline__ void sts16(uint32_t addr, uint32_t v) { asm volatile("st.shared.u16 [%0], %1;\n" ::"r"(addr), "h"((unsigned short)v) : "memory"); }
__device__ __forceinline__ void stsf(uint32_t addr, float v) { sts32(addr, __float_as_uint(v)); }
__device__ __forceinline__ void sts64(uint32_t addr, uint32_t a, uint32_t b) { asm volatile("st.shared.v2.u32 [%0], {%1,%2};\n" ::"r"(addr), "r"(a), "r"(b) : "memory"); }
__device__ __forceinline__ void sts64f(uint32_t addr, float a, float b) { sts64(addr, __float_as_uint(a), __float_as_uint(b)); }
__device__ __forceinline__ void sts128(uint32_t addr, uint32_t a, uint32_t b, uint32_t c, uint32_t d) {
    asm volatile("st.shared.v4.u32 [%0], {%1,%2,%3,%4};\n" ::"r"(addr), "r"(a), "r"(b), "r"(c), "r"(d) : "memory");
}
__device__ __forceinline__ void sts128f(uint32_t addr, const float (&v)[4]) {
    sts128(addr, __float_as_uint(v[0]), __float_as_uint(v[1]), __float_as_uint(v[2]), __float_as_uint(v[3]));
}
__device__ __forceinline__ void ldsm_x4(uint32_t& r0, uint32_t& r1, uint32_t& r2, uint32_t& r3, uint32_t addr) {
    asm volatile("ldmatrix.sync.aligned.m8n8.x4.shared.b16 {%0,%1,%2,%3}, [%4];\n"
                 : "=r"(r0), "=r"(r1), "=r"(r2), "=r"(r3) : "r"(addr) : "memory");
}
__device__ __forceinline__ void ldsm_x4_t(uint32_t& r0, uint32_t& r1, uint32_t& r2, uint32_t& r3, uint32_t addr) {
    asm volatile("ldmatrix.sync.aligned.m8n8.x4.trans.shared.b16 {%0,%1,%2,%3}, [%4];\n"
                 : "=r"(r0), "=r"(r1), "=r"(r2), "=r"(r3) : "r"(addr) : "memory");
}
__device__ __forceinline__ void ldsm_x2_t(uint32_t& r0, uint32_t& r1, uint32_t addr) {
    asm volatile("ldmatrix.sync.aligned.m8n8.x2.trans.shared.b16 {%0,%1}, [%2];\n" : "=r"(r0), "=r"(r1) : "r"(addr) : "memory");
}
__device__ __forceinline__ void ldsm_x1_t(uint32_t& r0, uint32_t addr) {
    asm volatile("ldmatrix.sync.aligned.m8n8.x1.trans.shared.b16 {%0}, [%1];\n" : "=r"(r0) : "r"(addr) : "memory");
}
__device__ __forceinline__ void stsm_x4(uint32_t addr, uint32_t r0, uint32_t r1, uint32_t r2, uint32_t r3) {
    asm volatile("stmatrix.sync.aligned.m8n8.x4.shared.b16 [%0], {%1,%2,%3,%4};\n" ::"r"(addr), "r"(r0), "r"(r1), "r"(r2), "r"(r3) : "memory");
}
__device__ __forceinline__ void stsm_x4_t(uint32_t addr, uint32_t r0, uint32_t r1, uint32_t r2, uint32_t r3) {
    asm volatile("stmatrix.sync.aligned.m8n8.x4.trans.shared.b16 [%0], {%1,%2,%3,%4};\n" ::"r"(addr), "r"(r0), "r"(r1), "r"(r2), "r"(r3) : "memory");
}
__device__ __forceinline__ uint32_t movm(uint32_t a) {
    uint32_t d;
    asm volatile("movmatrix.sync.aligned.m8n8.trans.b16 %0, %1;\n" : "=r"(d) : "r"(a));
    return d;
}
__device__ __forceinline__ void mma_f16(float (&c)[4], uint32_t a0, uint32_t a1, uint32_t a2, uint32_t a3, uint32_t b0, uint32_t b1) {
    asm volatile(
        "mma.sync.aligned.m16n8k16.row.col.f32.f16.f16.f32 {%0,%1,%2,%3}, {%4,%5,%6,%7}, {%8,%9}, {%0,%1,%2,%3};\n"
        : "+f"(c[0]), "+f"(c[1]), "+f"(c[2]), "+f"(c[3])
        : "r"(a0), "r"(a1), "r"(a2), "r"(a3), "r"(b0), "r"(b1));
}
__device__ __forceinline__ void mma_bf16(float (&c)[4], uint32_t a0, uint32_t a1, uint32_t a2, uint32_t a3, uint32_t b0, uint32_t b1) {
    asm volatile(
        "mma.sync.aligned.m16n8k16.row.col.f32.bf16.bf16.f32 {%0,%1,%2,%3}, {%4,%5,%6,%7}, {%8,%9}, {%0,%1,%2,%3};\n"
        : "+f"(c[0]), "+f"(c[1]), "+f"(c[2]), "+f"(c[3])
        : "r"(a0), "r"(a1), "r"(a2), "r"(a3), "r"(b0), "r"(b1));
}
__device__ __forceinline__ void mma_bf16_k8(float (&c)[4], uint32_t a0, uint32_t a1, uint32_t b0) {
    asm volatile("mma.sync.aligned.m16n8k8.row.col.f32.bf16.bf16.f32 {%0,%1,%2,%3}, {%4,%5}, {%6}, {%0,%1,%2,%3};\n"
                 : "+f"(c[0]), "+f"(c[1]), "+f"(c[2]), "+f"(c[3]) : "r"(a0), "r"(a1), "r"(b0));
}
__device__ __forceinline__ void bar_sync(int id, int n) { asm volatile("bar.sync %0, %1;\n" ::"r"(id), "r"(n) : "memory"); }
__device__ __forceinline__ void bar_arrive(int id, int n) { asm volatile("bar.arrive %0, %1;\n" ::"r"(id), "r"(n) : "memory"); }
__device__ __forceinline__ bool bar_or(int id, int n, bool v) {
    uint32_t r;
    asm volatile("{\n.reg .pred p, q;\nsetp.ne.u32 p, %3, 0;\nbar.red.or.pred q, %1, %2, p;\nselp.u32 %0, 1, 0, q;\n}\n" : "=r"(r) : "r"(id), "r"(n), "r"((uint32_t)v) : "memory");
    return r;
}
__device__ __forceinline__ uint32_t and3(uint32_t a, uint32_t b, uint32_t c) { uint32_t r; asm("lop3.b32 %0, %1, %2, %3, 0x80;\n" : "=r"(r) : "r"(a), "r"(b), "r"(c)); return r; }
__device__ __forceinline__ uint32_t or3(uint32_t a, uint32_t b, uint32_t c) { uint32_t r; asm("lop3.b32 %0, %1, %2, %3, 0xfe;\n" : "=r"(r) : "r"(a), "r"(b), "r"(c)); return r; }
__device__ __forceinline__ uint32_t pin(uint32_t v) { uint32_t r; asm volatile("shfl.sync.bfly.b32 %0, %1, 0, 0x1f, 0xffffffff;\n" : "=r"(r) : "r"(v) : "memory"); return r; }
__device__ __forceinline__ uint4 ld_poll(const void* p) {
    uint4 v;
    asm volatile("ld.relaxed.gpu.global.v4.u32 {%0,%1,%2,%3}, [%4];\n" : "=r"(v.x), "=r"(v.y), "=r"(v.z), "=r"(v.w) : "l"(p) : "memory");
    return v;
}
__device__ __forceinline__ uint2 ld_poll64(const void* p) {
    uint2 v;
    asm volatile("ld.relaxed.gpu.global.v2.u32 {%0,%1}, [%2];\n" : "=r"(v.x), "=r"(v.y) : "l"(p) : "memory");
    return v;
}
__device__ __forceinline__ uint32_t ld_poll32(const void* p) {
    uint32_t v;
    asm volatile("ld.relaxed.gpu.global.u32 %0, [%1];\n" : "=r"(v) : "l"(p) : "memory");
    return v;
}
__device__ __forceinline__ uint32_t ld_acquire32(const void* p) {
    uint32_t v;
    asm volatile("ld.acquire.gpu.global.u32 %0, [%1];\n" : "=r"(v) : "l"(p) : "memory");
    return v;
}
__device__ __forceinline__ uint4 ldg128(const void* p) {
    uint4 v;
    asm volatile("ld.global.nc.v4.u32 {%0,%1,%2,%3}, [%4];\n" : "=r"(v.x), "=r"(v.y), "=r"(v.z), "=r"(v.w) : "l"(p));
    return v;
}
__device__ __forceinline__ uint2 ldg64(const void* p) {
    uint2 v;
    asm volatile("ld.global.nc.v2.u32 {%0,%1}, [%2];\n" : "=r"(v.x), "=r"(v.y) : "l"(p));
    return v;
}
__device__ __forceinline__ uint32_t ldg16(const void* p) {
    uint32_t v;
    asm volatile("ld.global.nc.u16 %0, [%1];\n" : "=r"(v) : "l"(p));
    return v;
}
__device__ __forceinline__ uint4 ldo128(const void* p) {
    uint4 v;
    asm volatile("ld.relaxed.cta.global.v4.u32 {%0,%1,%2,%3}, [%4];\n" : "=r"(v.x), "=r"(v.y), "=r"(v.z), "=r"(v.w) : "l"(p) : "memory");
    return v;
}
__device__ __forceinline__ uint2 ldo64(const void* p) {
    uint2 v;
    asm volatile("ld.relaxed.cta.global.v2.u32 {%0,%1}, [%2];\n" : "=r"(v.x), "=r"(v.y) : "l"(p) : "memory");
    return v;
}
__device__ __forceinline__ uint32_t ldo16(const void* p) {
    uint32_t v;
    asm volatile("ld.relaxed.cta.global.u16 %0, [%1];\n" : "=r"(v) : "l"(p) : "memory");
    return v;
}
__device__ __forceinline__ void stg128(void* p, uint32_t a, uint32_t b, uint32_t c, uint32_t d) {
    asm volatile("st.global.v4.u32 [%0], {%1,%2,%3,%4};\n" ::"l"(p), "r"(a), "r"(b), "r"(c), "r"(d) : "memory");
}
__device__ __forceinline__ void stg64(void* p, uint32_t a, uint32_t b) { asm volatile("st.global.v2.u32 [%0], {%1,%2};\n" ::"l"(p), "r"(a), "r"(b) : "memory"); }
__device__ __forceinline__ uint32_t min4(const uint4& v) { return min(min(v.x, v.y), min(v.z, v.w)); }
#define SPIN_LIMIT (1 << 21)
#define TRAP() __trap()
__device__ __forceinline__ void mbar_init(uint32_t bar, uint32_t cnt) { asm volatile("mbarrier.init.shared::cta.b64 [%0], %1;\n" ::"r"(bar), "r"(cnt) : "memory"); }
__device__ __forceinline__ void mbar_expect(uint32_t bar, uint32_t bytes) {
    asm volatile("mbarrier.arrive.expect_tx.shared::cta.b64 _, [%0], %1;\n" ::"r"(bar), "r"(bytes) : "memory");
}
__device__ __forceinline__ void mbar_arrive(uint32_t bar) { asm volatile("mbarrier.arrive.shared::cta.b64 _, [%0];\n" ::"r"(bar) : "memory"); }
__device__ __forceinline__ void mbar_wait_cluster(uint32_t bar) {
    asm volatile(
        "{\n.reg .pred p;\n"
        "W_%=:\n"
        "mbarrier.try_wait.parity.acquire.cluster.shared::cta.b64 p, [%0], 0;\n"
        "@!p bra W_%=;\n}\n" ::"r"(bar) : "memory");
}
__device__ __forceinline__ void mbar_wait(uint32_t bar) {
    asm volatile(
        "{\n.reg .pred p;\n"
        "W_%=:\n"
        "mbarrier.try_wait.parity.shared::cta.b64 p, [%0], 0;\n"
        "@!p bra W_%=;\n}\n" ::"r"(bar) : "memory");
}
__device__ __forceinline__ bool mbar_test(uint32_t bar) {
    uint32_t r;
    asm volatile("{\n.reg .pred p;\nmbarrier.test_wait.parity.shared::cta.b64 p, [%1], 0;\nselp.u32 %0, 1, 0, p;\n}\n" : "=r"(r) : "r"(bar) : "memory");
    return __any_sync(0xffffffffu, r);
}
__device__ __forceinline__ void bulk_g2s(uint32_t dst, const void* src, uint32_t bytes, uint32_t bar) {
    asm volatile("cp.async.bulk.shared::cluster.global.mbarrier::complete_tx::bytes [%0], [%1], %2, [%3];\n" ::"r"(dst), "l"(src), "r"(bytes), "r"(bar) : "memory");
}
__device__ __forceinline__ void bulk_s2g(void* dst, uint32_t src, uint32_t bytes) {
    asm volatile("cp.async.bulk.global.shared::cta.bulk_group [%0], [%1], %2;\ncp.async.bulk.commit_group;\n" ::"l"(dst), "r"(src), "r"(bytes) : "memory");
}
__device__ __forceinline__ void tma_2d(uint32_t dst, const CUtensorMap* tm, int c0, int c1, uint32_t bar) {
    asm volatile("cp.async.bulk.tensor.2d.shared::cluster.global.mbarrier::complete_tx::bytes [%0], [%1, {%3, %4}], [%2];\n"
                 ::"r"(dst), "l"(tm), "r"(bar), "r"(c0), "r"(c1) : "memory");
}
__device__ __forceinline__ void tma_4d(uint32_t dst, const CUtensorMap* tm, int c0, int c3, uint32_t bar) {
    asm volatile("cp.async.bulk.tensor.4d.shared::cluster.global.mbarrier::complete_tx::bytes [%0], [%1, {%3, %4, %4, %5}], [%2];\n"
                 ::"r"(dst), "l"(tm), "r"(bar), "r"(c0), "r"(0), "r"(c3) : "memory");
}
__device__ __forceinline__ void tma_4d_mc(uint32_t dst, const CUtensorMap* tm, int c0, int c3, uint32_t bar) {
    asm volatile("cp.async.bulk.tensor.4d.shared::cluster.global.mbarrier::complete_tx::bytes.multicast::cluster [%0], [%1, {%3, %4, %4, %5}], [%2], %6;\n"
                 ::"r"(dst), "l"(tm), "r"(bar), "r"(c0), "r"(0), "r"(c3), "h"((unsigned short)3) : "memory");
}
__device__ __forceinline__ void l2_prefetch(const void* src, uint32_t bytes) {
    asm volatile("cp.async.bulk.prefetch.L2.global [%0], %1;\n" ::"l"(src), "r"(bytes) : "memory");
}
__device__ __forceinline__ bool elect_one() {
    uint32_t r;
    asm volatile("{\n.reg .pred p;\nelect.sync _|p, 0xffffffff;\nselp.u32 %0, 1, 0, p;\n}\n" : "=r"(r));
    return r;
}
__device__ __forceinline__ void delay(uint32_t clks) {
    uint32_t t0, t1;
    asm volatile("mov.u32 %0, %%clock;" : "=r"(t0) :: "memory");
    do { asm volatile("mov.u32 %0, %%clock;" : "=r"(t1) :: "memory"); } while (t1 - t0 < clks);
}
__device__ __forceinline__ void fence_async() { asm volatile("fence.proxy.async.shared::cta;\n" ::: "memory"); }

__device__ __forceinline__ float2 cmul(float2 a, float2 b) {
    return make_float2(fmaf(a.x, b.x, -a.y * b.y), fmaf(a.x, b.y, a.y * b.x));
}
__device__ __forceinline__ float2 csq(float2 a) {
    float p = a.x * a.y;
    return make_float2(fmaf(a.x, a.x, -a.y * a.y), p + p);
}
__device__ __forceinline__ float ex2_approx(float x) { float r; asm("ex2.approx.ftz.f32 %0, %1;\n" : "=f"(r) : "f"(x)); return r; }
__device__ __forceinline__ float exp_bf(float x) { return rbf(ex2_approx(__fmul_ru(x, 1.4426950408889634f))); }
__device__ __forceinline__ float2 cexp_e(float lr2, float li, float e) {
    const float m = ex2_approx(lr2 * e);
    return make_float2(m * __cosf(li * e), m * __sinf(li * e));
}
__device__ __forceinline__ float rcp_approx(float x) { float r; asm("rcp.approx.ftz.f32 %0, %1;\n" : "=f"(r) : "f"(x)); return r; }
__device__ __forceinline__ float sigmoid_f(float x) { return rcp_approx(1.0f + ex2_approx(x * -1.4426950408889634f)); }
__device__ __forceinline__ float sqrt_approx(float x) { float r; asm("sqrt.approx.ftz.f32 %0, %1;\n" : "=f"(r) : "f"(x)); return r; }

__device__ __forceinline__ void wg_fence() { asm volatile("wgmma.fence.sync.aligned;\n" ::: "memory"); }
__device__ __forceinline__ void wg_commit() { asm volatile("wgmma.commit_group.sync.aligned;\n" ::: "memory"); }
__device__ __forceinline__ void wg_wait0() { asm volatile("wgmma.wait_group.sync.aligned 0;\n" ::: "memory"); }
template <int T> __device__ __forceinline__ void wg_mma(float (&acc)[16][4], const uint32_t* a, uint64_t desc);
template <int T> __device__ __forceinline__ void wg_first(float (&acc)[16][4], const uint32_t* a, uint64_t desc);
template <> __device__ __forceinline__ void wg_mma<0>(float (&acc)[16][4], const uint32_t* a, uint64_t desc) {
    asm volatile("wgmma.mma_async.sync.aligned.m64n128k16.f32.f16.f16 {%0,%1,%2,%3,%4,%5,%6,%7,%8,%9,%10,%11,%12,%13,%14,%15,%16,%17,%18,%19,%20,%21,%22,%23,%24,%25,%26,%27,%28,%29,%30,%31,%32,%33,%34,%35,%36,%37,%38,%39,%40,%41,%42,%43,%44,%45,%46,%47,%48,%49,%50,%51,%52,%53,%54,%55,%56,%57,%58,%59,%60,%61,%62,%63}, {%64,%65,%66,%67}, %68, 1, 1, 1, 0;\n"
                 : "+f"(acc[0][0]), "+f"(acc[0][1]), "+f"(acc[0][2]), "+f"(acc[0][3]), "+f"(acc[1][0]), "+f"(acc[1][1]), "+f"(acc[1][2]), "+f"(acc[1][3]), "+f"(acc[2][0]), "+f"(acc[2][1]), "+f"(acc[2][2]), "+f"(acc[2][3]), "+f"(acc[3][0]), "+f"(acc[3][1]), "+f"(acc[3][2]), "+f"(acc[3][3]), "+f"(acc[4][0]), "+f"(acc[4][1]), "+f"(acc[4][2]), "+f"(acc[4][3]), "+f"(acc[5][0]), "+f"(acc[5][1]), "+f"(acc[5][2]), "+f"(acc[5][3]), "+f"(acc[6][0]), "+f"(acc[6][1]), "+f"(acc[6][2]), "+f"(acc[6][3]), "+f"(acc[7][0]), "+f"(acc[7][1]), "+f"(acc[7][2]), "+f"(acc[7][3]), "+f"(acc[8][0]), "+f"(acc[8][1]), "+f"(acc[8][2]), "+f"(acc[8][3]), "+f"(acc[9][0]), "+f"(acc[9][1]), "+f"(acc[9][2]), "+f"(acc[9][3]), "+f"(acc[10][0]), "+f"(acc[10][1]), "+f"(acc[10][2]), "+f"(acc[10][3]), "+f"(acc[11][0]), "+f"(acc[11][1]), "+f"(acc[11][2]), "+f"(acc[11][3]), "+f"(acc[12][0]), "+f"(acc[12][1]), "+f"(acc[12][2]), "+f"(acc[12][3]), "+f"(acc[13][0]), "+f"(acc[13][1]), "+f"(acc[13][2]), "+f"(acc[13][3]), "+f"(acc[14][0]), "+f"(acc[14][1]), "+f"(acc[14][2]), "+f"(acc[14][3]), "+f"(acc[15][0]), "+f"(acc[15][1]), "+f"(acc[15][2]), "+f"(acc[15][3])
                 : "r"(a[0]), "r"(a[1]), "r"(a[2]), "r"(a[3]), "l"(desc));
}
template <> __device__ __forceinline__ void wg_mma<2>(float (&acc)[16][4], const uint32_t* a, uint64_t desc) {
    asm volatile("wgmma.mma_async.sync.aligned.m64n112k16.f32.f16.f16 {%0,%1,%2,%3,%4,%5,%6,%7,%8,%9,%10,%11,%12,%13,%14,%15,%16,%17,%18,%19,%20,%21,%22,%23,%24,%25,%26,%27,%28,%29,%30,%31,%32,%33,%34,%35,%36,%37,%38,%39,%40,%41,%42,%43,%44,%45,%46,%47,%48,%49,%50,%51,%52,%53,%54,%55}, {%56,%57,%58,%59}, %60, 1, 1, 1, 0;\n"
                 : "+f"(acc[2][0]), "+f"(acc[2][1]), "+f"(acc[2][2]), "+f"(acc[2][3]), "+f"(acc[3][0]), "+f"(acc[3][1]), "+f"(acc[3][2]), "+f"(acc[3][3]), "+f"(acc[4][0]), "+f"(acc[4][1]), "+f"(acc[4][2]), "+f"(acc[4][3]), "+f"(acc[5][0]), "+f"(acc[5][1]), "+f"(acc[5][2]), "+f"(acc[5][3]), "+f"(acc[6][0]), "+f"(acc[6][1]), "+f"(acc[6][2]), "+f"(acc[6][3]), "+f"(acc[7][0]), "+f"(acc[7][1]), "+f"(acc[7][2]), "+f"(acc[7][3]), "+f"(acc[8][0]), "+f"(acc[8][1]), "+f"(acc[8][2]), "+f"(acc[8][3]), "+f"(acc[9][0]), "+f"(acc[9][1]), "+f"(acc[9][2]), "+f"(acc[9][3]), "+f"(acc[10][0]), "+f"(acc[10][1]), "+f"(acc[10][2]), "+f"(acc[10][3]), "+f"(acc[11][0]), "+f"(acc[11][1]), "+f"(acc[11][2]), "+f"(acc[11][3]), "+f"(acc[12][0]), "+f"(acc[12][1]), "+f"(acc[12][2]), "+f"(acc[12][3]), "+f"(acc[13][0]), "+f"(acc[13][1]), "+f"(acc[13][2]), "+f"(acc[13][3]), "+f"(acc[14][0]), "+f"(acc[14][1]), "+f"(acc[14][2]), "+f"(acc[14][3]), "+f"(acc[15][0]), "+f"(acc[15][1]), "+f"(acc[15][2]), "+f"(acc[15][3])
                 : "r"(a[0]), "r"(a[1]), "r"(a[2]), "r"(a[3]), "l"(desc));
}
template <> __device__ __forceinline__ void wg_mma<4>(float (&acc)[16][4], const uint32_t* a, uint64_t desc) {
    asm volatile("wgmma.mma_async.sync.aligned.m64n96k16.f32.f16.f16 {%0,%1,%2,%3,%4,%5,%6,%7,%8,%9,%10,%11,%12,%13,%14,%15,%16,%17,%18,%19,%20,%21,%22,%23,%24,%25,%26,%27,%28,%29,%30,%31,%32,%33,%34,%35,%36,%37,%38,%39,%40,%41,%42,%43,%44,%45,%46,%47}, {%48,%49,%50,%51}, %52, 1, 1, 1, 0;\n"
                 : "+f"(acc[4][0]), "+f"(acc[4][1]), "+f"(acc[4][2]), "+f"(acc[4][3]), "+f"(acc[5][0]), "+f"(acc[5][1]), "+f"(acc[5][2]), "+f"(acc[5][3]), "+f"(acc[6][0]), "+f"(acc[6][1]), "+f"(acc[6][2]), "+f"(acc[6][3]), "+f"(acc[7][0]), "+f"(acc[7][1]), "+f"(acc[7][2]), "+f"(acc[7][3]), "+f"(acc[8][0]), "+f"(acc[8][1]), "+f"(acc[8][2]), "+f"(acc[8][3]), "+f"(acc[9][0]), "+f"(acc[9][1]), "+f"(acc[9][2]), "+f"(acc[9][3]), "+f"(acc[10][0]), "+f"(acc[10][1]), "+f"(acc[10][2]), "+f"(acc[10][3]), "+f"(acc[11][0]), "+f"(acc[11][1]), "+f"(acc[11][2]), "+f"(acc[11][3]), "+f"(acc[12][0]), "+f"(acc[12][1]), "+f"(acc[12][2]), "+f"(acc[12][3]), "+f"(acc[13][0]), "+f"(acc[13][1]), "+f"(acc[13][2]), "+f"(acc[13][3]), "+f"(acc[14][0]), "+f"(acc[14][1]), "+f"(acc[14][2]), "+f"(acc[14][3]), "+f"(acc[15][0]), "+f"(acc[15][1]), "+f"(acc[15][2]), "+f"(acc[15][3])
                 : "r"(a[0]), "r"(a[1]), "r"(a[2]), "r"(a[3]), "l"(desc));
}
template <> __device__ __forceinline__ void wg_mma<6>(float (&acc)[16][4], const uint32_t* a, uint64_t desc) {
    asm volatile("wgmma.mma_async.sync.aligned.m64n80k16.f32.f16.f16 {%0,%1,%2,%3,%4,%5,%6,%7,%8,%9,%10,%11,%12,%13,%14,%15,%16,%17,%18,%19,%20,%21,%22,%23,%24,%25,%26,%27,%28,%29,%30,%31,%32,%33,%34,%35,%36,%37,%38,%39}, {%40,%41,%42,%43}, %44, 1, 1, 1, 0;\n"
                 : "+f"(acc[6][0]), "+f"(acc[6][1]), "+f"(acc[6][2]), "+f"(acc[6][3]), "+f"(acc[7][0]), "+f"(acc[7][1]), "+f"(acc[7][2]), "+f"(acc[7][3]), "+f"(acc[8][0]), "+f"(acc[8][1]), "+f"(acc[8][2]), "+f"(acc[8][3]), "+f"(acc[9][0]), "+f"(acc[9][1]), "+f"(acc[9][2]), "+f"(acc[9][3]), "+f"(acc[10][0]), "+f"(acc[10][1]), "+f"(acc[10][2]), "+f"(acc[10][3]), "+f"(acc[11][0]), "+f"(acc[11][1]), "+f"(acc[11][2]), "+f"(acc[11][3]), "+f"(acc[12][0]), "+f"(acc[12][1]), "+f"(acc[12][2]), "+f"(acc[12][3]), "+f"(acc[13][0]), "+f"(acc[13][1]), "+f"(acc[13][2]), "+f"(acc[13][3]), "+f"(acc[14][0]), "+f"(acc[14][1]), "+f"(acc[14][2]), "+f"(acc[14][3]), "+f"(acc[15][0]), "+f"(acc[15][1]), "+f"(acc[15][2]), "+f"(acc[15][3])
                 : "r"(a[0]), "r"(a[1]), "r"(a[2]), "r"(a[3]), "l"(desc));
}
template <> __device__ __forceinline__ void wg_mma<8>(float (&acc)[16][4], const uint32_t* a, uint64_t desc) {
    asm volatile("wgmma.mma_async.sync.aligned.m64n64k16.f32.f16.f16 {%0,%1,%2,%3,%4,%5,%6,%7,%8,%9,%10,%11,%12,%13,%14,%15,%16,%17,%18,%19,%20,%21,%22,%23,%24,%25,%26,%27,%28,%29,%30,%31}, {%32,%33,%34,%35}, %36, 1, 1, 1, 0;\n"
                 : "+f"(acc[8][0]), "+f"(acc[8][1]), "+f"(acc[8][2]), "+f"(acc[8][3]), "+f"(acc[9][0]), "+f"(acc[9][1]), "+f"(acc[9][2]), "+f"(acc[9][3]), "+f"(acc[10][0]), "+f"(acc[10][1]), "+f"(acc[10][2]), "+f"(acc[10][3]), "+f"(acc[11][0]), "+f"(acc[11][1]), "+f"(acc[11][2]), "+f"(acc[11][3]), "+f"(acc[12][0]), "+f"(acc[12][1]), "+f"(acc[12][2]), "+f"(acc[12][3]), "+f"(acc[13][0]), "+f"(acc[13][1]), "+f"(acc[13][2]), "+f"(acc[13][3]), "+f"(acc[14][0]), "+f"(acc[14][1]), "+f"(acc[14][2]), "+f"(acc[14][3]), "+f"(acc[15][0]), "+f"(acc[15][1]), "+f"(acc[15][2]), "+f"(acc[15][3])
                 : "r"(a[0]), "r"(a[1]), "r"(a[2]), "r"(a[3]), "l"(desc));
}
template <> __device__ __forceinline__ void wg_mma<10>(float (&acc)[16][4], const uint32_t* a, uint64_t desc) {
    asm volatile("wgmma.mma_async.sync.aligned.m64n48k16.f32.f16.f16 {%0,%1,%2,%3,%4,%5,%6,%7,%8,%9,%10,%11,%12,%13,%14,%15,%16,%17,%18,%19,%20,%21,%22,%23}, {%24,%25,%26,%27}, %28, 1, 1, 1, 0;\n"
                 : "+f"(acc[10][0]), "+f"(acc[10][1]), "+f"(acc[10][2]), "+f"(acc[10][3]), "+f"(acc[11][0]), "+f"(acc[11][1]), "+f"(acc[11][2]), "+f"(acc[11][3]), "+f"(acc[12][0]), "+f"(acc[12][1]), "+f"(acc[12][2]), "+f"(acc[12][3]), "+f"(acc[13][0]), "+f"(acc[13][1]), "+f"(acc[13][2]), "+f"(acc[13][3]), "+f"(acc[14][0]), "+f"(acc[14][1]), "+f"(acc[14][2]), "+f"(acc[14][3]), "+f"(acc[15][0]), "+f"(acc[15][1]), "+f"(acc[15][2]), "+f"(acc[15][3])
                 : "r"(a[0]), "r"(a[1]), "r"(a[2]), "r"(a[3]), "l"(desc));
}
template <> __device__ __forceinline__ void wg_mma<12>(float (&acc)[16][4], const uint32_t* a, uint64_t desc) {
    asm volatile("wgmma.mma_async.sync.aligned.m64n32k16.f32.f16.f16 {%0,%1,%2,%3,%4,%5,%6,%7,%8,%9,%10,%11,%12,%13,%14,%15}, {%16,%17,%18,%19}, %20, 1, 1, 1, 0;\n"
                 : "+f"(acc[12][0]), "+f"(acc[12][1]), "+f"(acc[12][2]), "+f"(acc[12][3]), "+f"(acc[13][0]), "+f"(acc[13][1]), "+f"(acc[13][2]), "+f"(acc[13][3]), "+f"(acc[14][0]), "+f"(acc[14][1]), "+f"(acc[14][2]), "+f"(acc[14][3]), "+f"(acc[15][0]), "+f"(acc[15][1]), "+f"(acc[15][2]), "+f"(acc[15][3])
                 : "r"(a[0]), "r"(a[1]), "r"(a[2]), "r"(a[3]), "l"(desc));
}
template <> __device__ __forceinline__ void wg_mma<14>(float (&acc)[16][4], const uint32_t* a, uint64_t desc) {
    asm volatile("wgmma.mma_async.sync.aligned.m64n16k16.f32.f16.f16 {%0,%1,%2,%3,%4,%5,%6,%7}, {%8,%9,%10,%11}, %12, 1, 1, 1, 0;\n"
                 : "+f"(acc[14][0]), "+f"(acc[14][1]), "+f"(acc[14][2]), "+f"(acc[14][3]), "+f"(acc[15][0]), "+f"(acc[15][1]), "+f"(acc[15][2]), "+f"(acc[15][3])
                 : "r"(a[0]), "r"(a[1]), "r"(a[2]), "r"(a[3]), "l"(desc));
}
template <> __device__ __forceinline__ void wg_first<0>(float (&acc)[16][4], const uint32_t* a, uint64_t desc) {
    asm volatile("wgmma.mma_async.sync.aligned.m64n128k16.f32.f16.f16 {%0,%1,%2,%3,%4,%5,%6,%7,%8,%9,%10,%11,%12,%13,%14,%15,%16,%17,%18,%19,%20,%21,%22,%23,%24,%25,%26,%27,%28,%29,%30,%31,%32,%33,%34,%35,%36,%37,%38,%39,%40,%41,%42,%43,%44,%45,%46,%47,%48,%49,%50,%51,%52,%53,%54,%55,%56,%57,%58,%59,%60,%61,%62,%63}, {%64,%65,%66,%67}, %68, 0, 1, 1, 0;\n"
                 : "=f"(acc[0][0]), "=f"(acc[0][1]), "=f"(acc[0][2]), "=f"(acc[0][3]), "=f"(acc[1][0]), "=f"(acc[1][1]), "=f"(acc[1][2]), "=f"(acc[1][3]), "=f"(acc[2][0]), "=f"(acc[2][1]), "=f"(acc[2][2]), "=f"(acc[2][3]), "=f"(acc[3][0]), "=f"(acc[3][1]), "=f"(acc[3][2]), "=f"(acc[3][3]), "=f"(acc[4][0]), "=f"(acc[4][1]), "=f"(acc[4][2]), "=f"(acc[4][3]), "=f"(acc[5][0]), "=f"(acc[5][1]), "=f"(acc[5][2]), "=f"(acc[5][3]), "=f"(acc[6][0]), "=f"(acc[6][1]), "=f"(acc[6][2]), "=f"(acc[6][3]), "=f"(acc[7][0]), "=f"(acc[7][1]), "=f"(acc[7][2]), "=f"(acc[7][3]), "=f"(acc[8][0]), "=f"(acc[8][1]), "=f"(acc[8][2]), "=f"(acc[8][3]), "=f"(acc[9][0]), "=f"(acc[9][1]), "=f"(acc[9][2]), "=f"(acc[9][3]), "=f"(acc[10][0]), "=f"(acc[10][1]), "=f"(acc[10][2]), "=f"(acc[10][3]), "=f"(acc[11][0]), "=f"(acc[11][1]), "=f"(acc[11][2]), "=f"(acc[11][3]), "=f"(acc[12][0]), "=f"(acc[12][1]), "=f"(acc[12][2]), "=f"(acc[12][3]), "=f"(acc[13][0]), "=f"(acc[13][1]), "=f"(acc[13][2]), "=f"(acc[13][3]), "=f"(acc[14][0]), "=f"(acc[14][1]), "=f"(acc[14][2]), "=f"(acc[14][3]), "=f"(acc[15][0]), "=f"(acc[15][1]), "=f"(acc[15][2]), "=f"(acc[15][3])
                 : "r"(a[0]), "r"(a[1]), "r"(a[2]), "r"(a[3]), "l"(desc));
}
template <> __device__ __forceinline__ void wg_first<4>(float (&acc)[16][4], const uint32_t* a, uint64_t desc) {
    asm volatile("wgmma.mma_async.sync.aligned.m64n96k16.f32.f16.f16 {%0,%1,%2,%3,%4,%5,%6,%7,%8,%9,%10,%11,%12,%13,%14,%15,%16,%17,%18,%19,%20,%21,%22,%23,%24,%25,%26,%27,%28,%29,%30,%31,%32,%33,%34,%35,%36,%37,%38,%39,%40,%41,%42,%43,%44,%45,%46,%47}, {%48,%49,%50,%51}, %52, 0, 1, 1, 0;\n"
                 : "=f"(acc[4][0]), "=f"(acc[4][1]), "=f"(acc[4][2]), "=f"(acc[4][3]), "=f"(acc[5][0]), "=f"(acc[5][1]), "=f"(acc[5][2]), "=f"(acc[5][3]), "=f"(acc[6][0]), "=f"(acc[6][1]), "=f"(acc[6][2]), "=f"(acc[6][3]), "=f"(acc[7][0]), "=f"(acc[7][1]), "=f"(acc[7][2]), "=f"(acc[7][3]), "=f"(acc[8][0]), "=f"(acc[8][1]), "=f"(acc[8][2]), "=f"(acc[8][3]), "=f"(acc[9][0]), "=f"(acc[9][1]), "=f"(acc[9][2]), "=f"(acc[9][3]), "=f"(acc[10][0]), "=f"(acc[10][1]), "=f"(acc[10][2]), "=f"(acc[10][3]), "=f"(acc[11][0]), "=f"(acc[11][1]), "=f"(acc[11][2]), "=f"(acc[11][3]), "=f"(acc[12][0]), "=f"(acc[12][1]), "=f"(acc[12][2]), "=f"(acc[12][3]), "=f"(acc[13][0]), "=f"(acc[13][1]), "=f"(acc[13][2]), "=f"(acc[13][3]), "=f"(acc[14][0]), "=f"(acc[14][1]), "=f"(acc[14][2]), "=f"(acc[14][3]), "=f"(acc[15][0]), "=f"(acc[15][1]), "=f"(acc[15][2]), "=f"(acc[15][3])
                 : "r"(a[0]), "r"(a[1]), "r"(a[2]), "r"(a[3]), "l"(desc));
}

#define EARLYN 2
#define K8 0
#define HOLD 1
#define MC 1
#define STAMPW(i) STAMPY(i)
#define STAMP2(i) STAMP(i)
#undef STAMPX
#define STAMPX(i)
#define PBAR 1
#define WDLY 500
#define CBAR 1
#define FDLY 1000
#define FDLY2 0
#define YDLY 1
#define YFROM 0
#define YPRE 0
#define KDLY 700
#define OEARLY 0
#define EXP 0
#define XWHEN 0
#define RWHEN 0
#define HW 11
#define PEARLY 0
#define XG 6
struct Params {
    const bf16 *x, *lar, *aim, *cre, *cim, *ldt, *dsk;
    Scratch* s;
    const bf16 *wr, *wg, *wu, *wd;
    bf16* out;
};

#define TOK(g) (2 * (g) - ((g) & 1))
#define ROWTOK(r) (TOK((r) & 7) + (((r) >> 2) & 2))
__device__ __forceinline__ void ln_partial(const uint32_t (&H)[2][4], uint32_t lp, int warp, int g, int t) {
    float cs[4] = {0.f, 0.f, 0.f, 0.f}, cl[4] = {0.f, 0.f, 0.f, 0.f}, ch[4] = {0.f, 0.f, 0.f, 0.f};
#pragma unroll
    for (int k = 0; k < 4; k += 2) {
        mma_bf16(cs, H[0][k], H[1][k], H[0][k + 1], H[1][k + 1], 0x3f803f80u, 0x3f803f80u);
        mma_bf16(cl, H[0][k], H[1][k], H[0][k + 1], H[1][k + 1], H[0][k], H[0][k + 1]);
        mma_bf16(ch, H[0][k], H[1][k], H[0][k + 1], H[1][k + 1], H[1][k], H[1][k + 1]);
    }
    const uint32_t a = lp + (g * 20 + warp) * 4;
    if (t == (g >> 1)) { stsf(a, cs[0]); stsf(a + 8 * 80, cs[2]); stsf(a + 16 * 80, (g & 1) ? cl[1] : cl[0]); stsf(a + 24 * 80, (g & 1) ? ch[3] : ch[2]); }
}
__device__ __forceinline__ float sum18(uint32_t a) {
    const uint4 p = lds128(a), q = lds128(a + 16), r = lds128(a + 32), s = lds128(a + 48);
    const uint2 u = lds64(a + 64);
#define F(x) __uint_as_float(x)
    return (((F(p.x) + F(p.y)) + (F(p.z) + F(p.w))) + ((F(q.x) + F(q.y)) + (F(q.z) + F(q.w)))) +
           (((F(r.x) + F(r.y)) + (F(r.z) + F(r.w))) + ((F(s.x) + F(s.y)) + (F(s.z) + F(s.w))) + (F(u.x) + F(u.y)));
#undef F
}
__device__ __forceinline__ void ln_stats(float sm, float sq, float& mb, float& sd) {
    const float m0 = sm * (1.0f / 576.0f);
    const float mean = fmaf(fmaf(-m0, 576.0f, sm), 1.0f / 576.0f, m0);
    const float var = fmaxf(fmaf(-mean, mean, sq * (1.0f / 576.0f)), 0.f);
    mb = rbf(mean);
    sd = rbf(sqrt_approx(rbf(rbf(var) + 1e-5f)));
}
__device__ __forceinline__ void ln_finish(float v, int lane, float& mb, float& rc) {
    const float o = __shfl_xor_sync(0xffffffffu, v, 16);
    float sd;
    ln_stats(lane < 16 ? v : o, lane < 16 ? o : v, mb, sd);
    rc = rcp_approx(sd);
}
__device__ __forceinline__ uint32_t ln_apply(uint32_t w, uint32_t m2, uint32_t rh, uint32_t rl) {
    const uint32_t d = hsub2_bf(w, m2);
    return hfma2_bf(d, rh, hmul2_bf(d, rl));
}
__device__ __forceinline__ void stat_store(uint32_t a, float mb, float rc, uint32_t extra) {
    const float rh = rbf(rc);
    sts64(a, (__float_as_uint(mb) >> 16) | (extra << 16), pack_bf16(rh, rc - rh));
}
#define STAT_M(s) __byte_perm((s).x, (s).x, 0x1010)
#define STAT_H(s) __byte_perm((s).y, (s).y, 0x1010)
#define STAT_L(s) __byte_perm((s).y, (s).y, 0x3232)

__device__ __forceinline__ void hcmul(uint32_t re, uint32_t im, uint32_t zx, uint32_t zy, uint32_t& ore, uint32_t& oim) {
    ore = hfms2(im, zy, hmul2(re, zx));
    oim = hfma2(re, zy, hmul2(im, zx));
}

struct KGen {
    uint32_t A[2][4][4];
    float2 z1, z8, z64, z128, T[9];
};
__device__ __forceinline__ void kgen_setup(KGen& k, float lar, float aim, float dt) {
    const float lr2 = -(exp_bf(lar) * dt) * 1.4426950408889634f, li = aim * dt;
    k.z1 = cexp_e(lr2, li, 1.0f);
    k.z8 = cexp_e(lr2, li, 8.0f);
    k.z64 = cexp_e(lr2, li, 64.0f);
}
__device__ __forceinline__ void kgen_rows(KGen& k, uint32_t tb, int lane) {
    const float2 z8 = k.z8, z64 = k.z64;
    const uint32_t row = tb + lane * TBP;
    k.z128 = csq(z64);
    const float2 z16 = csq(z8), z24 = cmul(z16, z8), z32 = csq(z16), z40 = cmul(z32, z8), z48 = csq(z24), z56 = cmul(z32, z24);
    uint32_t re[4], im[4], a[4], b[4];
    re[0] = pack_f16(1.0f, z8.x); im[0] = pack_f16(0.0f, z8.y);
    re[1] = pack_f16(z16.x, z24.x); im[1] = pack_f16(z16.y, z24.y);
    re[2] = pack_f16(z32.x, z40.x); im[2] = pack_f16(z32.y, z40.y);
    re[3] = pack_f16(z48.x, z56.x); im[3] = pack_f16(z48.y, z56.y);
    sts128(row, re[0], re[1], re[2], re[3]);
    sts128(row + 32, im[0], im[1], im[2], im[3]);
    const uint32_t zx = pack_f16(z64.x, z64.x), zy = pack_f16(z64.y, z64.y), zw = pack_f16(k.z128.x, k.z128.y);
#pragma unroll
    for (int j = 0; j < 4; j++) hcmul(re[j], im[j], zx, zy, a[j], b[j]);
    sts128(row + 16, a[0], a[1], a[2], a[3]);
    sts128(row + 48, b[0], b[1], b[2], b[3]);
    const int mi = lane >> 3;
    const uint32_t zd = tb + mi * TBP + 96;
    sts16(zd + (lane & 7) * 2, zw); sts16(zd + (lane & 7) * 2 + 4 * TBP, zw >> 16);
    __syncwarp();
    const uint32_t ad = tb + (lane & 7) * TBP + mi * 16;
    ldsm_x4(a[0], a[1], a[2], a[3], zd);
    ldsm_x4(b[0], b[1], b[2], b[3], zd + 4 * TBP);
#pragma unroll
    for (int ks = 0; ks < 4; ks++) {
        ldsm_x4_t(k.A[0][ks][0], k.A[0][ks][1], k.A[0][ks][2], k.A[0][ks][3], ad + ks * 8 * TBP);
        hcmul(k.A[0][ks][0], k.A[0][ks][2], a[ks], b[ks], k.A[1][ks][0], k.A[1][ks][2]);
        hcmul(k.A[0][ks][1], k.A[0][ks][3], a[ks], b[ks], k.A[1][ks][1], k.A[1][ks][3]);
    }
}
__device__ __forceinline__ void kgen_chain(KGen& k, uint32_t cr, uint32_t ci, float cs) {
    k.T[0] = make_float2(bf_lo(cr) * cs, -bf_lo(ci) * cs);
    const float2 y1 = make_float2(k.z1.x, -k.z1.y);
#pragma unroll
    for (int c = 1; c < 8; c++) k.T[c] = cmul(k.T[c - 1], y1);
    k.T[8] = cmul(k.T[0], make_float2(k.z8.x, -k.z8.y));
}
__device__ __forceinline__ void kgen_cols(KGen& k, uint32_t tb, int lane) {
    const uint32_t row = tb + lane * TBP;
    const float2 (&T)[9] = k.T;
    const float2 y128 = make_float2(k.z128.x, -k.z128.y);
    const float2 y256 = csq(y128), y512 = csq(y256), y768 = cmul(y512, y256), y1024 = csq(y512);
    const float2 c1032 = cmul(T[8], y1024);
    __syncwarp();
    sts128(row, pack_f16(T[0].x, T[1].x), pack_f16(T[2].x, T[3].x), pack_f16(T[4].x, T[5].x), pack_f16(T[6].x, T[7].x));
    sts128(row + 16, pack_f16(T[0].y, T[1].y), pack_f16(T[2].y, T[3].y), pack_f16(T[4].y, T[5].y), pack_f16(T[6].y, T[7].y));
    uint32_t a[4], b[4];
    {
        const uint32_t zx = pack_f16(y256.x, y256.x), zy = pack_f16(y256.y, y256.y);
        hcmul(pack_f16(T[0].x, T[2].x), pack_f16(T[0].y, T[2].y), zx, zy, a[0], b[0]);
        hcmul(pack_f16(T[4].x, T[6].x), pack_f16(T[4].y, T[6].y), zx, zy, a[1], b[1]);
        const uint32_t r04 = pack_f16(T[0].x, T[4].x), i04 = pack_f16(T[0].y, T[4].y);
        hcmul(r04, i04, pack_f16(y512.x, y512.x), pack_f16(y512.y, y512.y), a[2], b[2]);
        hcmul(r04, i04, pack_f16(y768.x, y768.x), pack_f16(y768.y, y768.y), a[3], b[3]);
    }
    sts128(row + 32, a[0], a[1], a[2], a[3]);
    sts128(row + 48, b[0], b[1], b[2], b[3]);
    {
        const uint32_t r0 = pack_f16(1.0f, y256.x), i0 = pack_f16(0.0f, y256.y), r1 = pack_f16(y512.x, y768.x), i1 = pack_f16(y512.y, y768.y);
        const uint32_t zx = pack_f16(T[8].x, T[8].x), zy = pack_f16(T[8].y, T[8].y), wx = pack_f16(c1032.x, c1032.x), wy = pack_f16(c1032.y, c1032.y);
        hcmul(r0, i0, zx, zy, a[0], b[0]); hcmul(r1, i1, zx, zy, a[1], b[1]);
        hcmul(r0, i0, wx, wy, a[2], b[2]); hcmul(r1, i1, wx, wy, a[3], b[3]);
    }
    sts128(row + 64, a[0], a[1], a[2], a[3]);
    sts128(row + 80, b[0], b[1], b[2], b[3]);
}
__device__ __forceinline__ void kgen_mma(const KGen& k, uint32_t tb, int lane) {
    __syncwarp();
    float acc[2][3][4];
#pragma unroll
    for (int i = 0; i < 6; i++)
#pragma unroll
        for (int j = 0; j < 4; j++) acc[i / 3][i % 3][j] = 0.f;
    const int mi = lane >> 3;
    const uint32_t bd = tb + ((lane & 7) + 8 * (mi >> 1)) * TBP + (mi & 1) * 16;
#pragma unroll
    for (int kp = 0; kp < 2; kp++)
#pragma unroll
        for (int j = 0; j < 3; j++) {
            uint32_t b[4];
            ldsm_x4_t(b[0], b[1], b[2], b[3], bd + kp * 16 * TBP + j * 32);
#pragma unroll
            for (int h = 0; h < 2; h++)
#pragma unroll
                for (int m = 0; m < 2; m++) {
                    const uint32_t (&A)[4] = k.A[m][2 * kp + h];
                    mma_f16(acc[m][j], A[0], A[1], A[2], A[3], b[2 * h], b[2 * h + 1]);
                }
        }
    __syncwarp();
#define PK(j) pack_f16(acc[0][j][0], acc[0][j][1]), pack_f16(acc[0][j][2], acc[0][j][3]), pack_f16(acc[1][j][0], acc[1][j][1]), pack_f16(acc[1][j][2], acc[1][j][3])
    stsm_x4(tb + lane * 16, PK(0));
    stsm_x4(tb + 512 + lane * 16, PK(1));
    stsm_x4_t(tb + 1024 + (lane & 7) * 80 + mi * 16, PK(2));
#undef PK
}
__device__ __forceinline__ uint32_t table_buf(uint32_t sb, int warp) { return sb + SM_WD + (warp < 16 ? warp + 4 : warp - 16) * TBW; }

__device__ __forceinline__ uint4 lds16x4(uint32_t a) { return make_uint4(lds16(a), lds16(a + TBW), lds16(a + 2 * TBW), lds16(a + 3 * TBW)); }
__device__ __forceinline__ void combine_setup(uint32_t sb, int warp, int lane, uint32_t kw, uint32_t& o, uint32_t& n, uint32_t& d) {
    const int wq = warp & 3;
    const uint32_t a = table_buf(sb, warp & ~3);
    o = wq == 3 ? a + 1024 + 320 + (lane >> 3) * 80 + (lane & 7) * 8 : a + (wq ? 504 + wq * 8 : 0) + lane * 16;
    n = a + 1024 + wq * 80 + lane * 2;
    d = wq < 3 ? kw + (wq == 2 ? KW_P : 32 + wq * 512) + lane * 16 : kw + KW_H + 8 + lane * 8;
}
__device__ __forceinline__ void kgen_combine(int wq, int lane, uint32_t o, uint32_t na, uint32_t d) {
#define S4(f) hadd2(hadd2(u.f, v.f), hadd2(w.f, x.f))
#define H4(v) hadd2(hadd2(v.x, v.y), hadd2(v.z, v.w))
#define BP __byte_perm
    if (wq == 0) {
        const uint4 u = lds128(o), v = lds128(o + TBW), w = lds128(o + 2 * TBW), x = lds128(o + 3 * TBW), nn = lds16x4(na);
        const uint32_t n = H4(nn), k0 = S4(x), k2 = S4(y), k4 = S4(z), k6 = S4(w);
        sts128(d, BP(k0, k0, 0x1032), BP(k0, k2, 0x3254), BP(k2, k2, 0x1032), BP(k2, k4, 0x3254));
        sts128(d + KW_PL, BP(k4, k4, 0x1032), BP(k4, k6, 0x3254), BP(k6, k6, 0x1032), BP(k6, n, 0x3254));
        if (lane == 0) sts32(d + KW_PL - 4, k0 & 0xffffu);
    } else {
        const uint2 u = lds64(o), v = lds64(o + TBW), w = lds64(o + 2 * TBW), x = lds64(o + 3 * TBW);
        uint4 nn = make_uint4(0u, 0u, 0u, 0u), mm = nn;
        if (wq < 3) nn = lds16x4(na);
        if (wq == 2) mm = lds16x4(na + 80);
        const uint32_t k0 = S4(x), k2 = S4(y), n = H4(nn), m = H4(mm);
        if (wq == 3) {
            sts64(d, k0, k2);
        } else if (wq == 1) {
            const uint32_t cc = BP(k2, k2, 0x1010);
            sts128(d, BP(k0, k0, 0x1010), BP(k0, k0, 0x1032), BP(k0, k2, 0x3254), cc);
            sts128(d + KW_PL, cc, BP(k2, k2, 0x1032), BP(k2, n, 0x3254), BP(n, n, 0x1010));
        } else {
            const uint32_t w40 = BP(k0, k0, 0x1032), w84 = BP(k0, n, 0x3254), w0 = BP(k0, k0, 0x1010), w4 = BP(k0, k0, 0x3232), w8 = BP(n, n, 0x1010);
            sts64(d, w40, w84);
            sts64(d + 512, BP(k2, k2, 0x1032), BP(k2, m, 0x3254));
            if (lane < 8) { sts128(d - (KW_P - 1056), w0, w0, w40, w4); sts128(d - (KW_P - 1056 - KW_PL), w4, w84, w8, w8); }
            if (lane == 31) sts16(d + (KW_H + 6 - KW_P - 496), m);
        }
    }
#undef S4
#undef H4
#undef BP
}

__device__ __forceinline__ int c_exponent(const uint2& r, const uint2& i, float dt) {
    const uint32_t mx = __vmaxu2(__vmaxu2(r.x & 0x7fff7fffu, r.y & 0x7fff7fffu), __vmaxu2(i.x & 0x7fff7fffu, i.y & 0x7fff7fffu));
    return __reduce_max_sync(0xffffffffu, max(mx, mx << 16) + (__float_as_uint(dt) & 0x7f800000u)) >> 23;
}

__device__ __forceinline__ int warp_v() { int l; asm volatile("mov.u32 %0, %%tid.x;" : "=r"(l)); return __shfl_sync(0xffffffffu, l >> 5, 0); }
__device__ __forceinline__ int lane_v() { int l; asm volatile("mov.u32 %0, %%laneid;" : "=r"(l)); return l; }
__device__ __forceinline__ uint32_t prmt_v(uint32_t a, uint32_t b, uint32_t s) { uint32_t d; asm volatile("prmt.b32 %0, %1, %2, %3;\n" : "=r"(d) : "r"(a), "r"(b), "r"(s)); return d; }
__device__ __forceinline__ uint32_t mov_v(uint32_t a) { uint32_t d; asm volatile("mov.b32 %0, %1;\n" : "=r"(d) : "r"(a)); return d; }
template <int G>
__device__ __forceinline__ void conv_rename(float (&acc)[16][4]) {
#pragma unroll
    for (int i = G; i < 16; i++)
#pragma unroll
        for (int j = 0; j < 4; j++) { float v; asm volatile("mov.b32 %0, %1;\n" : "=f"(v) : "f"(acc[i][j])); acc[i][j] = v; }
}
struct Conv {
    uint32_t kw;
    uint32_t wa;
    uint32_t pa, s2;
    uint32_t s8;
    uint32_t id;
    uint32_t lc;
    uint32_t fs;
    uint32_t fl, yo;
    uint32_t yp;
    size_t ycopy;
    uint32_t ps;
    uint64_t d0;
    int warp;
};
struct Pk { uint32_t w[4]; };
__device__ __forceinline__ Pk pk2(const float (&u)[4], const float (&v)[4]) {
    Pk r;
    r.w[0] = pack_f16(u[0], u[1]); r.w[1] = pack_f16(u[2], u[3]); r.w[2] = pack_f16(v[0], v[1]); r.w[3] = pack_f16(v[2], v[3]);
    return r;
}
__device__ __forceinline__ void park(uint32_t a, const Pk& v) {
    asm volatile("stmatrix.sync.aligned.m8n8.x4.trans.shared.b16 [%0], {%1,%2,%3,%4};\n" ::"r"(a), "r"(v.w[0]), "r"(v.w[1]), "r"(v.w[2]), "r"(v.w[3]) : "memory");
}
__device__ __forceinline__ void conv_constants(uint32_t lc, int l) {
    const int d = (l >> 2) - 2 * (l & 3);
    const int e = d + 8, r4 = (e + 1 + ((e >> 2) & 1)) >> 2, p4 = (e + (((e - 1) >> 2) & 1)) >> 2;
    const uint32_t s2 = r4 == p4 ? 0x1010u : 0x3210u;
    sts64(lc + l * 8, KW_P + ((r4 - 5) >> 1) * 16 + ((r4 - 5) & 1) * 4, s2 | ((d < 0 ? s2 : 0x7654u) << 16));
    const int lo = (d >= 4) - (d < -3), ho = (d >= 5) - (d < -2), le = (d > 4) - (d < -4), he = (d > 5) - (d < -3);
    sts32(lc + 512 + l * 8, (0x5454u + lo * 0x22 + ho * 0x2200) | ((0x3232u + le * 0x22 + he * 0x2200) << 16));
    const int cc = l >> 2, j = l & 3;
    sts64(lc + 256 + l * 8, (j >> 1) * PL_HALF + (16 + cc) * 16 + (j & 1) * 8, (cc >> 1) * (DM * 64) + (cc & 1) * 32 + j * 8);
}
__device__ __forceinline__ void conv_selectors4(Conv& c) {
    const uint2 v = lds64(c.lc + lane_v() * 8);
    c.pa = v.x; c.s2 = v.y;
}
__device__ __forceinline__ void conv_selectors8(Conv& c) { c.s8 = lds32(c.lc + 512 + lane_v() * 8); }
template <int G, int I0, int I1>
__device__ __forceinline__ void conv_load(const Conv& c, uint32_t (&q)[9]) {
    const int wq = c.warp & 3;
    if (G < 2) {
#pragma unroll
        for (int i = I0; i < I1; i++) q[i] = lds32(c.wa + G * 512 + i * 16);
    } else if (G < 4) {
        const uint32_t a = (G == 2 && wq == 0) ? c.wa + 1024 : c.pa + c.kw + wq * 128 + (G < 2 ? 0 : G - 2) * 512;
#pragma unroll
        for (int i = I0; i < I1; i++) q[i] = lds32(a + i * 16);
    } else {
        const uint4 u = lds128(c.kw + KW_H + (G < 4 ? 0 : G - 4) * 64 + wq * 16);
        const uint2 v = lds64(c.kw + KW_H + (G < 4 ? 0 : G - 4) * 64 + wq * 16 + 16);
        q[0] = u.x; q[1] = u.y; q[2] = u.z; q[3] = u.w; q[4] = v.x; q[5] = v.y;
        if (G == 4 && wq == 0) { q[6] = lds32(c.pa + c.kw + 1024); q[7] = lds32(c.pa + c.kw + 1040); }
    }
}
template <int G, int J0, int J1>
__device__ __forceinline__ void conv_frag(const Conv& c, const uint32_t (&q)[9], uint32_t* a, const Pk& dp) {
    const uint32_t dep = dp.w[0];
    if (G < 4) {
        const uint32_t s = (G < 2 || (G == 2 && (c.warp & 3) == 0)) ? c.id : c.s2;
#pragma unroll
        for (int j = J0; j < J1; j++) {
            uint32_t* o = a + 4 * (j - J0);
            o[0] = prmt_v(q[2 * j + 1], dp.w[0], s); o[1] = prmt_v(q[2 * j + 2], dp.w[1], s); o[2] = prmt_v(q[2 * j], dp.w[2], s); o[3] = prmt_v(q[2 * j + 1], dp.w[3], s);
        }
    } else {
        const uint32_t so = prmt_v(c.s8, dep, c.id), se = prmt_v(c.s8, dep, c.id + 0x22);
#pragma unroll
        for (int j = J0; j < J1; j++) {
            uint32_t* o = a + 4 * (j - J0);
            o[0] = prmt_v(q[j + 1], q[j + 2], se); o[1] = prmt_v(q[j + 1], q[j + 2], so); o[2] = prmt_v(q[j], q[j + 1], so);
            if (G == 4 && j == 0 && (c.warp & 3) == 0) {
                o[2] = prmt_v(q[6], dep, c.s2);
                o[0] = prmt_v(q[7], o[0], c.s2 >> 16);
            }
            o[3] = mov_v(o[0]);
        }
    }
}
template <int G, int J0, int J1>
__device__ __forceinline__ void conv_frag(const Conv& c, const uint32_t (&q)[9], uint32_t* a, float depf) {
    const uint32_t d = __float_as_uint(depf);
    conv_frag<G, J0, J1>(c, q, a, Pk{{d, d, d, d}});
}
template <int G, int T, int J0, int J1>
__device__ __forceinline__ void conv_mma(float (&acc)[16][4], const Conv& c, const uint32_t* a) {
#pragma unroll
    for (int j = J0; j < J1; j++) wg_mma<T>(acc, a + 4 * (j - J0), c.d0 - 8 * (2 * G - T) - j);
}
__device__ __forceinline__ float h_lo(uint32_t w) { return __half2float(__ushort_as_half((unsigned short)(w & 0xffffu))); }
__device__ __forceinline__ float h_hi(uint32_t w) { return __half2float(__ushort_as_half((unsigned short)(w >> 16))); }
__device__ __forceinline__ void flush_setup(Conv& c) {
    const uint2 v = lds64(c.lc + 256 + lane_v() * 8);
    c.fl = v.x; c.yo = v.y;
}
template <int Q>
__device__ __forceinline__ void flush_load(const Conv& c, uint32_t pl, uint2 (&f)[4]) {
#pragma unroll
    for (int w = 0; w < 4; w++) f[w] = lds64(c.fl + pl + (Q & 1) * 512 + w * (PLW_B - 64));
}
template <int Q>
__device__ __forceinline__ void flush_load_first(const Conv& c, uint32_t pl, uint2 (&f)[4], float depf) {
    const uint32_t p = prmt_v(c.fl, __float_as_uint(depf), c.id) + pl + (Q & 1) * 512;
#define LDV64(d, a) asm volatile("ld.volatile.shared.v2.u32 {%0,%1}, [%2];\n" : "=r"(d.x), "=r"(d.y) : "r"(a) : "memory")
    LDV64(f[0], p); LDV64(f[1], p + (PLW_B - 64)); LDV64(f[2], p + 2 * (PLW_B - 64)); LDV64(f[3], p + 3 * (PLW_B - 64));
}
#define FDEP __uint_as_float(f[3].y)
template <int Q, int mode>
__device__ __forceinline__ void conv_flush(const Conv& c, const uint2 (&f)[4], unsigned char* gy, uint32_t rx) {
    const uint32_t a0 = hadd2(f[0].x, f[1].x), a1 = hadd2(f[2].x, f[3].x), b0 = hadd2(f[0].y, f[1].y), b1 = hadd2(f[2].y, f[3].y);
    if (Q > 0 && mode == 1) {
        const uint32_t ra = rx + 16 + (Q > 0 ? Q - 1 : 0) * 1024 + (c.warp & 3) * 256 + lane_v() * 8;
        asm volatile("st.async.shared::cluster.mbarrier::complete_tx::bytes.v2.b32 [%0], {%1,%2}, [%3];\n"
                     ::"r"(ra ^ 0x1000000u), "r"(hadd2(a0, a1)), "r"(hadd2(b0, b1)), "r"((rx + (Q > 1 ? 8 : 0)) ^ 0x1000000u) : "memory");
        return;
    }
    float v0 = h_lo(a0) + h_lo(a1), v1 = h_hi(a0) + h_hi(a1), v2 = h_lo(b0) + h_lo(b1), v3 = h_hi(b0) + h_hi(b1);
    if (Q > 0 && mode == 2) {
        const uint2 o = lds64(rx + 16 + (Q > 0 ? Q - 1 : 0) * 1024 + (c.warp & 3) * 256 + lane_v() * 8);
        v0 += h_lo(o.x); v1 += h_hi(o.x); v2 += h_lo(o.y); v3 += h_hi(o.y);
    }
    const uint32_t lo = hmul2_bf(pack_bf16(v0, v1), c.fs), hi = hmul2_bf(pack_bf16(v2, v3), c.fs);
    stg64(gy + Q * 32 * DM * 32 + (c.yo + (Q < 3 ? c.yp : 0u)), lo ^ YKEY, hi ^ YKEY);
}
template <int I, bool S = false> struct IC { static constexpr int value = I; static constexpr bool shared = S; };
template <class T> __device__ constexpr bool wg_is4() { return T::shared; }
#define SLOT(n) (c.ps + (2 + ((n) & 7)) * 128)
#define GO() do { wg_commit(); __syncwarp(); } while (0)
#define DEP acc[15][3]
template <class FG, class FP, class FN>
__device__ __forceinline__ void conv_head(Conv& c, float (&acc)[16][4], uint32_t (&q)[9], uint32_t (&r)[9], uint32_t* a, FG fg, FP pre, FN next) {
    c.id = 0x3210u + (c.warp >> 8);
    conv_load<0, 0, 9>(c, q);
    conv_frag<0, 0, 1>(c, q, a, 0.f);
    pre();
    wg_fence(); wg_first<0>(acc, a, c.d0); GO();
    park(c.ps, Pk{{0u, 0u, 0u, 0u}});
    wg_wait0();
    conv_frag<0, 1, 2>(c, q, a, DEP);
    wg_fence(); conv_mma<0, 0, 1, 2>(acc, c, a); GO();
    fg(IC<0>());
    wg_wait0();
    conv_frag<0, 2, 3>(c, q, a, DEP);
    wg_fence(); conv_mma<0, 0, 2, 3>(acc, c, a); GO();
    conv_load<1, 0, 5>(c, r);
    wg_wait0();
    conv_frag<0, 3, 4>(c, q, a, DEP);
    wg_fence(); conv_mma<0, 0, 3, 4>(acc, c, a); GO();
    conv_load<1, 5, 9>(c, r);
    fg(IC<1>());
    wg_wait0();
    const Pk k = pk2(acc[0], acc[1]);
    conv_rename<2>(acc);
    conv_frag<1, 0, 2>(c, r, a, k);
    wg_fence(); conv_mma<1, 2, 0, 2>(acc, c, a); GO();
    park(SLOT(0), k);
    next(IC<0>());
    fg(IC<2>());
    wg_wait0();
    conv_frag<1, 2, 4>(c, r, a, DEP);
    wg_fence(); conv_mma<1, 2, 2, 4>(acc, c, a); GO();
    next(IC<1>());
    fg(IC<3>());
    wg_wait0();
}
template <class FG, class FP>
__device__ __forceinline__ void conv_run(Conv& c, uint32_t pl, unsigned char* gy, FG fg, FP pre) {
    float acc[16][4];
    uint32_t q[9], r[9], a[32];
    uint2 f[4];
    const int bid = 1 + (c.warp >> 2);
    conv_head(c, acc, q, r, a, fg, pre, [&](auto i) { if (decltype(i)::value == 0) conv_selectors4(c); else conv_load<2, 0, 9>(c, q); });
    Pk k = pk2(acc[2], acc[3]);
    conv_rename<4>(acc);
    conv_frag<2, 0, 4>(c, q, a, k);
    wg_fence(); conv_mma<2, 4, 0, 4>(acc, c, a); GO();
    park(SLOT(2), k);
    conv_load<3, 0, 9>(c, q);
    flush_setup(c);
    bar_sync(bid, 128);
    fg(IC<4>());
    wg_wait0();
    conv_rename<6>(acc);
    flush_load_first<0>(c, pl, f, DEP);
    conv_frag<3, 0, 4>(c, q, a, FDEP);
    wg_fence(); conv_mma<3, 6, 0, 4>(acc, c, a); GO();
    park(SLOT(4), pk2(acc[4], acc[5]));
    conv_load<4, 0, 9>(c, q);
    conv_selectors8(c);
    conv_flush<0, 0>(c, f, gy, 0u);
    fg(IC<5>());
    wg_wait0();
    conv_rename<8>(acc);
    conv_frag<4, 0, 4>(c, q, a, DEP);
    wg_fence(); conv_mma<4, 8, 0, 4>(acc, c, a); GO();
    k = pk2(acc[6], acc[7]);
    park(SLOT(6), k); park(c.ps, k);
    conv_load<5, 0, 9>(c, q);
    bar_sync(bid, 128);
    fg(IC<6>());
    wg_wait0();
    conv_rename<10>(acc);
    flush_load_first<1>(c, pl, f, DEP);
    conv_frag<5, 0, 4>(c, q, a, FDEP);
    wg_fence(); conv_mma<5, 10, 0, 4>(acc, c, a); GO();
    park(SLOT(8), pk2(acc[8], acc[9]));
    conv_load<6, 0, 9>(c, q); conv_load<7, 0, 9>(c, r);
    conv_flush<1, 0>(c, f, gy, 0u);
    fg(IC<7>());
    wg_wait0();
    conv_rename<12>(acc);
    conv_frag<6, 0, 4>(c, q, a, DEP); conv_frag<7, 0, 4>(c, r, a + 16, DEP);
    wg_fence(); conv_mma<6, 12, 0, 4>(acc, c, a); conv_mma<7, 12, 0, 4>(acc, c, a + 16); GO();
    park(SLOT(10), pk2(acc[10], acc[11]));
    bar_sync(bid, 128);
    flush_load<2>(c, pl, f);
    conv_flush<2, 0>(c, f, gy, 0u);
    fg(IC<8>());
    wg_wait0();
    park(SLOT(12), pk2(acc[12], acc[13])); park(SLOT(14), pk2(acc[14], acc[15]));
    bar_sync(bid, 128);
    flush_load<3>(c, pl, f);
    conv_flush<3, 0>(c, f, gy, 0u);
}
template <class FG>
__device__ __forceinline__ void conv_outer(Conv& c, uint32_t pl, unsigned char* gy, uint32_t rx, FG fg) {
    float acc[16][4];
    uint32_t q[9], r[9], a[32];
    uint2 f[4], f2[4];
    const int bid = 1 + (c.warp >> 2);
    conv_head(c, acc, q, r, a, [&](auto gi) { if (decltype(gi)::value == 2) fg(IC<2, true>()); }, [&]() {}, [&](auto i) { if (decltype(i)::value == 0) conv_selectors8(c); else conv_load<6, 0, 9>(c, q); });
    park(SLOT(2), pk2(acc[2], acc[3])); park(SLOT(4), pk2(acc[4], acc[5]));
    const Pk k = pk2(acc[6], acc[7]);
    park(SLOT(6), k);
    conv_load<7, 0, 9>(c, r);
    conv_rename<12>(acc);
    conv_frag<6, 0, 4>(c, q, a, __uint_as_float(k.w[3])); conv_frag<7, 0, 4>(c, r, a + 16, __uint_as_float(k.w[3]));
    wg_fence(); conv_mma<6, 12, 0, 4>(acc, c, a); conv_mma<7, 12, 0, 4>(acc, c, a + 16); GO();
    flush_setup(c);
    bar_sync(bid, 128);
    flush_load<0>(c, pl, f); flush_load<1>(c, pl, f2);
    conv_flush<1, 1>(c, f2, gy, rx);
    conv_flush<0, 1>(c, f, gy, rx);
    wg_wait0();
    bar_sync(bid, 128);
    park(c.ps, k); park(SLOT(8), pk2(acc[8], acc[9])); park(SLOT(10), pk2(acc[10], acc[11]));
    park(SLOT(12), pk2(acc[12], acc[13])); park(SLOT(14), pk2(acc[14], acc[15]));
    bar_sync(bid, 128);
    flush_load<2>(c, pl, f); flush_load<3>(c, pl, f2);
    conv_flush<2, 1>(c, f, gy, rx);
    conv_flush<3, 1>(c, f2, gy, rx);
}
template <class FG>
__device__ __forceinline__ void conv_inner(Conv& c, uint32_t pl, unsigned char* gy, uint32_t rx, FG fg) {
    float acc[16][4];
    uint32_t q[9], a[16];
    uint2 f[4], f2[4];
    const int bid = 1 + (c.warp >> 2);
    c.id = 0x3210u + (c.warp >> 8);
    conv_selectors4(c);
    conv_load<2, 0, 9>(c, q);
    conv_frag<2, 0, 4>(c, q, a, 0.f);
    wg_fence(); wg_first<4>(acc, a, c.d0); conv_mma<2, 4, 1, 4>(acc, c, a + 4); GO();
    conv_load<3, 0, 9>(c, q);
    park(SLOT(2), Pk{{0u, 0u, 0u, 0u}});
    fg(IC<2, true>());
    wg_wait0();
    conv_rename<6>(acc);
    conv_frag<3, 0, 4>(c, q, a, DEP);
    wg_fence(); conv_mma<3, 6, 0, 4>(acc, c, a); GO();
    park(SLOT(4), pk2(acc[4], acc[5]));
    conv_load<4, 0, 9>(c, q);
    conv_selectors8(c);
    wg_wait0();
    conv_rename<8>(acc);
    conv_frag<4, 0, 4>(c, q, a, DEP);
    wg_fence(); conv_mma<4, 8, 0, 4>(acc, c, a); GO();
    const Pk k = pk2(acc[6], acc[7]);
    park(SLOT(6), k); park(c.ps, k);
    conv_load<5, 0, 9>(c, q);
    flush_setup(c);
    wg_wait0();
    conv_rename<10>(acc);
    conv_frag<5, 0, 4>(c, q, a, DEP);
    wg_fence(); conv_mma<5, 10, 0, 4>(acc, c, a); GO();
    park(SLOT(8), pk2(acc[8], acc[9]));
    bar_sync(bid, 128);
    flush_load<1>(c, pl, f);
    mbar_wait(rx);
    conv_flush<1, 2>(c, f, gy, rx);
    wg_wait0();
    bar_sync(bid, 128);
    park(SLOT(10), pk2(acc[10], acc[11])); park(SLOT(12), pk2(acc[12], acc[13])); park(SLOT(14), pk2(acc[14], acc[15]));
    bar_sync(bid, 128);
    flush_load<3>(c, pl, f); flush_load<2>(c, pl, f2);
    mbar_wait(rx + 8);
    conv_flush<3, 2>(c, f, gy, rx);
    conv_flush<2, 2>(c, f2, gy, rx);
}
#undef SLOT
#undef GO
#undef DEP
template <int U0, int U1>
__device__ __forceinline__ void weight_units(uint32_t sb, const CUtensorMap* tg, const CUtensorMap* tu, const CUtensorMap* td, bool w) {
    if (U1 > U0 && w && elect_one()) {
#pragma unroll
        for (int n = U0; n < U1; n++) {
            const int i = n;
            if (i < 12) tma_2d(sb + SM_WG + i * 6912, i < 6 ? tg : tu, 72 * (blockIdx.x >> 1), 288 * (blockIdx.x & 1) + (i % 6) * 48, sb + SM_MISC + 328);
            else tma_2d(sb + SM_WD + (i - 12) * 4736, td, 144 * (blockIdx.x & 1), 72 * (blockIdx.x >> 1) + 8 * (i - 12), sb + SM_MISC + 336);
        }
    }
}
#define WS 1111121111122004100
__device__ constexpr int wsched(int i) {
    unsigned long long v = WS;
    int n = 0;
    for (int k = 19; k >= 1; k--) { if (k < i) n += (int)(v % 10); v /= 10; }
    return n;
}
static_assert(wsched(20) == 21 && wsched(6) <= 7 && wsched(11) <= 12 && wsched(16) <= 17 && wsched(16) == wsched(15) && wsched(19) == 21, "");
__device__ __forceinline__ void weight_prefetch(const Params& p, int u, int lane) {
    const int b = blockIdx.x;
    const char* a = u < 12 ? reinterpret_cast<const char*>(u < 6 ? p.wg : p.wu) + ((b >> 6) * 288 + (u % 6) * 48) * (FF * 2) + (b & 63) * 6912
                           : reinterpret_cast<const char*>(p.wd) + (72 * (b >> 1) + 8 * (u - 12)) * 1152 + (b & 1) * 4608;
    asm volatile("prefetch.global.L2 [%0];\n" ::"l"(a + lane * 128));
    if (lane < (u < 12 ? 22 : 4)) asm volatile("prefetch.global.L2 [%0];\n" ::"l"(a + 4096 + lane * 128));
}
#define PF0 0
#define PF1 0
#define WPOINT(i, w) do { weight_units<wsched(i), wsched(i + 1)>(sb, &tm_g, &tm_u, &tm_d, w); } while (0)

__global__ void __launch_bounds__(NTHR, 1) __cluster_dims__(2, 1, 1)
fused_kernel(const Params p, const __grid_constant__ CUtensorMap tm_g, const __grid_constant__ CUtensorMap tm_u, const __grid_constant__ CUtensorMap tm_d, const __grid_constant__ CUtensorMap tm_x) {
    extern __shared__ __align__(1024) unsigned char smem[];
    const uint32_t sb = smem_u32(smem);
    const int tid = threadIdx.x, warp = __shfl_sync(0xffffffffu, tid >> 5, 0), lane = tid & 31;
    const int b = blockIdx.x, P = b >> 1, odd = b & 1;
    const int g = lane >> 2, t = lane & 3;
    const int wg = warp >> 2, t128 = tid & 127;
    const uint32_t s_stat = sb + SM_MISC;
    const uint32_t s_key = sb + SM_MISC + 128;
    const uint32_t s_rank = sb + SM_MISC + 256;
    const uint32_t s_k16 = sb + SM_MISC + 192;
    const uint32_t s_cnt = sb + SM_MISC + 320;
    const uint32_t bar_w = sb + SM_MISC + 328, bar_d = bar_w + 8, bar_g = bar_w + 16, bar_x = bar_w + 24, bar_t = bar_w + 32;
    STAMP(0);

    if (warp == 19) {
        if (lane == 0) {
            mbar_init(bar_w, 1); mbar_init(bar_d, 1); mbar_init(bar_g, 1); mbar_init(sb + SM_RX, 1); mbar_init(sb + SM_RX + 8, 1);
            mbar_init(bar_x, 1); mbar_init(bar_t, 1); mbar_expect(bar_x, 32768);
            asm volatile("fence.mbarrier_init.release.cluster;\n" ::: "memory");
            mbar_expect(bar_w, 82944); mbar_expect(bar_d, 72 * WD_PITCH); mbar_expect(bar_g, 9216); mbar_expect(bar_t, 18 * 1152); mbar_expect(sb + SM_RX, 1024); mbar_expect(sb + SM_RX + 8, 2048);
        }
        __syncwarp();
    } else if (warp == 18) {
#pragma unroll
        for (int i = 0; i < 9; i++) sts128(sb + SM_ZERO + (i * 32 + lane) * 16, 0u, 0u, 0u, 0u);
        fence_async();
        __syncwarp();
    }
    const int ch = wg < 4 ? 4 * b + wg : 512 + P;
    const bf16 *q0 = p.lar + ch * NST, *q1 = p.aim + ch * NST, *q2 = p.cre + ch * NST, *q3 = p.cim + ch * NST;
    asm volatile("" : "+l"(q0), "+l"(q1), "+l"(q2), "+l"(q3));
    const uint32_t ldt = ldo16(p.ldt + ch), pl = ldo16(q0 + t128), pa2 = ldo16(q1 + t128);
    const uint32_t pc = ldo16(q2 + t128), pi = ldo16(q3 + t128);
    const uint2 call_re = ldo64(q2 + 4 * lane), call_im = ldo64(q3 + 4 * lane);
    if (PBAR) { if (wg == 4) bar_sync(0, NWRK); else bar_arrive(0, NWRK); }
    uint4 xv[9], xu[2];
    if (wg == 4) {
        const bf16* xp = p.x + (size_t)(16 * b + 4 * (warp & 3) + (g & 3)) * DM + 288 * (g >> 2) + 8 * t;
#pragma unroll
        for (int c = 0; c < 9; c++) xv[c] = ldo128(xp + c * 32);
        if (warp < 18) {
            const bf16* xq = p.x + (size_t)(16 * b + TOK(g)) * DM + 32 * warp + 8 * t;
            xu[0] = ldo128(xq); xu[1] = ldo128(xq + 2 * DM);
        }
    }
    auto xcols = [&](int z) {
        if (MC) {
            asm volatile("barrier.cluster.wait.aligned;\n" ::: "memory");
            if (elect_one()) tma_4d_mc(sb + SM_XC + odd * 16384, &tm_x, 8 * P + z, 2 * odd, bar_x);
        } else if (elect_one()) tma_4d(sb + SM_XC, &tm_x, 8 * P + z, 0, bar_x);
        __syncwarp();
    };
    if (MC) asm volatile("barrier.cluster.arrive.relaxed.aligned;\n" ::: "memory");
    if (warp == 18) {
        if (lane == 0) bulk_s2g(reinterpret_cast<unsigned char*>(p.s->y) + 96 * 18432 + b * 4608, sb + SM_ZERO, 4608);
        bar_arrive(12, 64);
    }
    if (warp == 19) { bar_sync(12, 64); xcols(0); }
    const uint32_t kw = sb + SM_KW + wg * KW_B;
    const uint32_t tb = table_buf(sb, warp);
    if (wg == 4) {
        const int wq = warp & 3;
        const uint32_t epl = ld_poll32(p.s->hint + (b & 7) * 32 + 1);
        unsigned char* const ud = reinterpret_cast<unsigned char*>(p.s->uT) + (size_t)(8 * wq + 2 * (g >> 1)) * 16384 + b * 128 + (g & 1) * 32 + t * 8;
        uint32_t* const sd_ = p.s->stat + 16 * b + 4 * wq + g;
        const bool own = g < 4 && t == (g >> 1);
        if (own) *reinterpret_cast<volatile uint32_t*>(sd_) = 0u;
        if (wq < 2) {
#pragma unroll
            for (int k = 0; k < 4; k++) *reinterpret_cast<volatile unsigned long long*>(ud + (k >> 1) * 16384 + (k & 1) * 64) = 0ull;
        }
        if (wq == 1) conv_constants(sb + SM_LC, lane);
        uint32_t one;
        asm volatile("st.volatile.shared.u32 [%1], 0x3f803f80;\nld.volatile.shared.u32 %0, [%1];\n" : "=r"(one) : "r"(tb + lane * 4) : "memory");
        float cs[2][4] = {}, d1[2][4] = {}, d2[2][4] = {};
#pragma unroll
        for (int c = 0; c < 9; c++) {
            const uint4 v = xv[c];
            mma_bf16(cs[c & 1], v.x, v.y, v.z, v.w, one, one);
            mma_bf16(d1[c & 1], v.x, v.y, v.z, v.w, v.x, v.z); mma_bf16(d2[c & 1], v.x, v.y, v.z, v.w, v.y, v.w);
        }
        STAMP(27);
        float sm = (cs[0][0] + cs[0][2]) + (cs[1][0] + cs[1][2]);
        float sq = (g & 1) ? (d1[0][1] + d2[0][3]) + (d1[1][1] + d2[1][3]) : (d1[0][0] + d2[0][2]) + (d1[1][0] + d2[1][2]);
        sm += __shfl_xor_sync(0xffffffffu, sm, 18); sq += __shfl_xor_sync(0xffffffffu, sq, 18);
        if (HOLD == 1) bar_arrive(6 + wq, 160);
        float mb, sd;
        ln_stats(sm, sq, mb, sd);
        if (own) *sd_ = (__float_as_uint(mb) >> 16) | (__float_as_uint(sd) & 0x7fff0000u) | (epl << 31);
        STAMPX(22);
        if (wq < PF0) weight_prefetch(p, wq, lane);
        if (HOLD == 2) bar_arrive(6 + wq, 160);
        if (own) stat_store(s_stat + (2 * wq + (g & 1) + 8 * (g >> 1)) * 8, mb, rcp_approx(sd), 0u);
        if (lane == 1) sts32(s_cnt + 4, epl);
        if (wq == 2) asm volatile("cp.async.bulk.wait_group 0;\n" ::: "memory");
        bar_sync(5, 128);
        STAMP(28);
        if (wq >= 2) { bar_arrive(2 * wq - 3, 160); bar_arrive(2 * wq - 2, 160); }
        WPOINT(1, wq == 3);
        if (wq == 2 && lane < 8) p.s->key[8 * b + lane] = epl & 1u;
        if (wq < 2) {
            const uint32_t utag = (epl % 7u + 1u) * 0x10001u;
            uint32_t U[2][4];
#pragma unroll
            for (int hf = 0; hf < 2; hf++) {
                const uint2 st = lds64(s_stat + (g + 8 * hf) * 8);
                const uint32_t X[4] = {xu[hf].x, xu[hf].y, xu[hf].z, xu[hf].w};
#pragma unroll
                for (int k = 0; k < 4; k++) {
                    const uint32_t u = ln_apply(X[k], STAT_M(st), STAT_H(st), STAT_L(st));
                    U[hf][k] = movm((pack_f16(bf_lo(u), bf_hi(u)) & 0xfff8fff8u) | utag);
                }
            }
#pragma unroll
            for (int k = 0; k < 4; k++) stg64(ud + (k >> 1) * 16384 + (k & 1) * 64, U[0][k], U[1][k]);
        }
    } else if (warp == 0) {
#pragma unroll
        for (int i = 0; i < 7; i++) sts128(sb + SM_LNP + (i * 32 + lane) * 16, 0u, 0u, 0u, 0u);
    }
    if (t128 < 2 * UPAD) sts128(sb + SM_U + wg * USLOT_B + (t128 & 1) * ULO_B + (t128 >> 1) * 16, 0u, 0u, 0u, 0u);
    if (t128 >= 124) sts128(kw + (t128 & 1) * 16 + (t128 & 2) * (KW_PL / 2), 0u, 0u, 0u, 0u);
    uint32_t co, cn, cd;
    combine_setup(sb, warp, lane, kw, co, cn, cd);
    const uint4* usrc = wg < 4 ? reinterpret_cast<const uint4*>(p.s->stat) + tid
                               : reinterpret_cast<const uint4*>(p.s->uT) + (P >> 2) * 1024 + (t128 >> 1) * 8 + (P & 3) * 2 + (t128 & 1);
    uint32_t zero;
    {
        uint32_t uo = (uint32_t)(reinterpret_cast<const char*>(usrc) - reinterpret_cast<const char*>(p.s)), pk = (cn - co + 1024) | ((cd - kw) << 16);
        asm volatile("st.volatile.shared.v4.u32 [%4], {0, %1, %2, %3};\nld.volatile.shared.v4.u32 {%0, %1, %2, %3}, [%4];\n" : "=r"(zero), "+r"(co), "+r"(pk), "+r"(uo) : "r"(tb + lane * 16) : "memory");
        cn = co + (pk & 0xffffu) - 1024; cd = kw + (pk >> 16);
        usrc = reinterpret_cast<const uint4*>(reinterpret_cast<const char*>(p.s) + uo);
    }
    const float dt = exp_bf(__uint_as_float(__byte_perm(ldt, zero, 0x1044)));
    STAMP(1);
    if (wg < 4) { STAMPX(16); }
    KGen kg;
    kgen_setup(kg, __uint_as_float(__byte_perm(pl, zero, 0x1044)), __uint_as_float(__byte_perm(pa2, zero, 0x1044)), dt);
    kgen_rows(kg, tb, lane);
    STAMP(2);
    const int E = min(max(c_exponent(call_re, call_im, dt) - 243, -120), 120);
    kgen_chain(kg, pc, pi, dt * __uint_as_float((uint32_t)(128 - E) << 23));
    STAMP(3);
    WPOINT(2, warp == 19);
    kgen_cols(kg, tb, lane);
    STAMP(4);
    WPOINT(3, warp == 19);
    if (wg < 4) { STAMPX(17); }
    if (HOLD && wg < 4) bar_sync(6 + (warp & 3), 160);
    if (wg < 4) { STAMPX(19); }
    kgen_mma(kg, tb, lane);
    if (wg < 4) { STAMPX(20); }
    STAMP(5);
    WPOINT(4, warp == 19);
    if (wg < 4) bar_sync(1 + wg, 160); else bar_sync(5, 128);
    if (wg < 4) { STAMPX(21); }
    uint4 uv0, uv1;
    if (PEARLY) { uv0 = ld_poll(usrc); if (wg == 4) uv1 = ld_poll(usrc + 512); }
    kgen_combine(warp & 3, lane, co, cn, cd);
    const uint32_t ep = lds32(s_cnt + 4);
    if (!PEARLY) { uv0 = ld_poll(usrc); if (wg == 4) uv1 = ld_poll(usrc + 512); }
    STAMP(6);
    if (wg < 4) { STAMPX(18); }
    WPOINT(5, warp == 19);
    if (MC && warp != 19) asm volatile("barrier.cluster.wait.aligned;\n" ::: "memory");
    uint2 yv[4] = {};
    {
        const int wq = warp & 3;
        Conv c;
        const uint32_t pln = sb + SM_PL + wg * PL_B;
        const int e = g - 2 * t + 7;
        c.kw = kw; c.wa = kw + ((e >> 2) & 1) * KW_PL + (8 * wq + (e >> 3)) * 16 + (e & 3) * 4;
        c.ps = mov_v(pln + wq * PLW_B + ((lane >> 3) & 1) * PL_HALF + ((lane >> 4) * 8 + (lane & 7)) * 16); c.warp = warp;
        c.lc = sb + SM_LC; c.fs = (uint32_t)(127 + E) * 0x800080u; c.yp = (__shfl_sync(0xffffffffu, ep, 0) & 1u) * (NCTA * 18432u);
        c.d0 = ((uint64_t)(ULO_B >> 4) << 16) | ((uint64_t)(128 >> 4) << 32) | (uint64_t)(((sb + SM_U + wg * USLOT_B + UPAD * 16) & 0x3FFFF) >> 4);
        unsigned char* gy = reinterpret_cast<unsigned char*>(p.s->y) + ((size_t)(4 * wq) * DM + ch) * 64;
        auto hook = [&](auto gi) {
                     constexpr int G = decltype(gi)::value;
                     if (G == (wg_is4<decltype(gi)>() ? 2 : 5)) asm volatile("barrier.cluster.wait.aligned;\n" ::: "memory");
                     if (!wg_is4<decltype(gi)>() && G < 4 && warp == HW) {
                         const int l2 = lane_v();
                         unsigned char* const sc = reinterpret_cast<unsigned char*>(p.s);
                         if (G == 0 && l2 < 2) bulk_s2g(sc + offsetof(Scratch, rows) + b * 4608 + l2 * 2304, sb + SM_LNP, 2304);
                         if (b < 96 && l2 < (G ? 3 : 1))
                             bulk_s2g(l2 ? sc + offsetof(Scratch, y) + (NCTA * 18432u - c.yp) + b * 18432 + (2 * G + l2 - 3) * 3072 : sc + offsetof(Scratch, part) + b * 12288 + G * 3072,
                                      sb + SM_LNP, 3072);
                         __syncwarp();
                     }
                     if (!wg_is4<decltype(gi)>() && PF1 && G >= PF1 && G < PF1 + 2 && (warp >> 1) == 2) weight_prefetch(p, 17 + 2 * (G - PF1) + (warp & 1), lane_v());
                     if (!wg_is4<decltype(gi)>()) WPOINT(6 + G, warp == 12 + (G & 3));
                     if (YPRE && G == 8 && b < YPRE) {
                         const int l2 = lane_v();
                         const unsigned char* ys = reinterpret_cast<const unsigned char*>(p.s->y) + c.yp + ((P * DM + 32 * warp + (l2 & 24) + ((l2 >> 2) & 1)) * 64 + odd * 32 + (l2 & 3) * 8);
#pragma unroll
                         for (int k = 0; k < 4; k++) yv[k] = ld_poll64(ys + k * 128);
                     }
                     if (!wg_is4<decltype(gi)>() && G == XG && warp == HW) { asm volatile("cp.async.bulk.wait_group 0;\n" ::: "memory"); __syncwarp(); }
                     if (!wg_is4<decltype(gi)>() && G == XG && warp == HW && elect_one()) {
                         bulk_g2s(sb + SM_XT, p.x + (size_t)16 * b * DM, 16 * 1152, bar_t);
                         bulk_g2s(sb + SM_XT + 16 * 1152, p.dsk, 1152, bar_t);
                         bulk_g2s(sb + SM_XT + 17 * 1152, p.wr, 1152, bar_t);
                     }
                 };
        bar_sync(1 + wg, 128);
        if (wg < 4) {
            asm volatile("barrier.cluster.arrive.relaxed.aligned;\n" ::: "memory");
            conv_run(c, pln + wq * 128, gy, hook, [&]() {
                STAMPX(23);
                mbar_wait(bar_x);
                STAMP(9);
                STAMPX(24);
                uint2 xc[4];
                uint32_t xw[4][2];
#pragma unroll
                for (int j = 0; j < 4; j++) xc[j] = lds64(sb + SM_XC + wg * 8192 + j * 2048 + t128 * 16 + odd * 8);
#pragma unroll
                for (int i = 0; i < 8; i++) {
                    const int k = i >> 1, h = i & 1;
                    xw[k][h] = prmt_v(k < 2 ? xc[2 * h].x : xc[2 * h].y, k < 2 ? xc[2 * h + 1].x : xc[2 * h + 1].y, (k & 1) ? 0x7632 : 0x5410);
                }
                const uint32_t ub = mov_v(sb + SM_U + UPAD * 16 + ((tid >> 1) & 1) * ULO_B + (tid >> 2) * 16 + (tid & 1) * 8), tag = ep << 31;
                int it = 0;
                while (min(min((int)(uv0.x ^ tag), (int)(uv0.y ^ tag)), min((int)(uv0.z ^ tag), (int)(uv0.w ^ tag))) < 0x10000) {
                    if (++it > SPIN_LIMIT) TRAP();
                    uv0 = ld_poll(usrc);
                }
                STAMP(8);
                STAMPX(26);
                const float r0 = rcp_approx(fabsf(bf_hi(uv0.x))), r1 = rcp_approx(fabsf(bf_hi(uv0.y))), r2 = rcp_approx(fabsf(bf_hi(uv0.z))), r3 = rcp_approx(fabsf(bf_hi(uv0.w)));
                const uint32_t m[2] = {__byte_perm(uv0.x, uv0.y, 0x5410), __byte_perm(uv0.z, uv0.w, 0x5410)};
                const uint32_t rh[2] = {pack_bf16(r0, r1), pack_bf16(r2, r3)};
                const uint32_t rl[2] = {pack_bf16(r0 - bf_lo(rh[0]), r1 - bf_hi(rh[0])), pack_bf16(r2 - bf_lo(rh[1]), r3 - bf_hi(rh[1]))};
#pragma unroll
                for (int k = 0; k < 4; k++) {
                    const uint32_t u0 = ln_apply(xw[k][0], m[0], rh[0], rl[0]), u1 = ln_apply(xw[k][1], m[1], rh[1], rl[1]);
                    sts64(ub + k * USLOT_B, pack_f16(bf_lo(u0), bf_hi(u0)), pack_f16(bf_lo(u1), bf_hi(u1)));
                }
                STAMPX(29);
                fence_async();
                bar_sync(14, 512);
                STAMP(7);
            });
        } else {
            auto stage = [&]() {
                const uint32_t tag = (ep % 7u + 1u) * 0x10001u;
                int it = 0;
                while (true) {
                    uv0.x ^= tag; uv0.y ^= tag; uv0.z ^= tag; uv0.w ^= tag; uv1.x ^= tag; uv1.y ^= tag; uv1.z ^= tag; uv1.w ^= tag;
                    if ((((uv0.x | uv0.y | uv0.z) | (uv0.w | uv1.x | uv1.y) | (uv1.z | uv1.w)) & 0x70007u) == 0) break;
                    if (++it > SPIN_LIMIT) TRAP();
                    uv0 = ld_poll(usrc); uv1 = ld_poll(usrc + 512);
                }
                STAMP(8);
                const uint32_t ub = sb + SM_U + UPAD * 16 + 4 * USLOT_B + (t128 & 1) * ULO_B + (t128 >> 1) * 16;
                sts128(ub, uv0.x, uv0.y, uv0.z, uv0.w);
                sts128(ub + 1024, uv1.x, uv1.y, uv1.z, uv1.w);
                fence_async();
                asm volatile("barrier.cluster.arrive.relaxed.aligned;\n" ::: "memory");
                bar_sync(5, 128);
                STAMP(7);
            };
            stage();
            if (odd) conv_inner(c, pln + wq * 128, gy, sb + SM_RX, hook);
            else conv_outer(c, pln + wq * 128, gy, sb + SM_RX, hook);
        }
        STAMP(10);
    }
    {
    const int lane = lane_v(), tid = 32 * warp + lane, g = lane >> 2, t = lane & 3;
    const uint32_t par = ~lds32(s_cnt + 4) & 1u;
    if (CBAR) bar_sync(0, NWRK);
    STAMP(11);
    uint32_t H[2][4] = {}, U2[2][4] = {};
    uint32_t WA[9][4], WD[18];
    auto publish = [&](bool hi, int slot) {
        uint4* rowp = reinterpret_cast<uint4*>(p.s->rows) + slot * 144 + warp * 4 + t;
        stg128(rowp, nzw(hi ? U2[1][0] : U2[0][0]), nzw(hi ? U2[1][1] : U2[0][1]), nzw(hi ? U2[1][2] : U2[0][2]), nzw(hi ? U2[1][3] : U2[0][3]));
        stg128(rowp + 72, nzw(hi ? H[1][0] : H[0][0]), nzw(hi ? H[1][1] : H[0][1]), nzw(hi ? H[1][2] : H[0][2]), nzw(hi ? H[1][3] : H[0][3]));
    };
#define KTOK(k) (2047 - (int)(((k) >> 5) & 0x7ffu))
#define KLATE(k) (((k) & 0x1cu) != 0)
#define KSLOT(k, s) (KLATE(k) ? 2 * NCTA + (s) : 2 * (KTOK(k) >> 4) + (int)(((k) >> 1) & 1u))
    const uint4* const rsrc = reinterpret_cast<const uint4*>(p.s->rows) + 36 * odd;
    auto gather = [&](uint32_t mine) {
        int it = 0;
        uint32_t mn;
        do {
            mn = 1;
#pragma unroll 1
            for (int r = 0; r < 9; r++) {
                const uint32_t k = __shfl_sync(0xffffffffu, mine, r < 8 ? 4 * r : lane);
                const int row = r < 8 ? r : g, c = r < 8 ? lane : 32 + t;
                asm volatile("cp.async.cg.shared.global [%0], [%1], 16;\n" ::"r"(sb + SM_XS + row * XS_PITCH + c * 16), "l"(rsrc + KSLOT(k, row) * 144 + c) : "memory");
            }
            asm volatile("cp.async.wait_all;\n" ::: "memory");
#pragma unroll 1
            for (int r = 0; r < 9; r++) mn = min(mn, min4(lds128(sb + SM_XS + (r < 8 ? r * XS_PITCH + lane * 16 : g * XS_PITCH + (32 + t) * 16))));
            if (++it > SPIN_LIMIT) TRAP();
        } while (__any_sync(0xffffffffu, mn == 0));
    };
    auto late_rows = [&](auto role) {
        const uint32_t kk = lds32(s_key + (lane & 7) * 4), ep = lds32(s_cnt + 4);
        const bool own = KLATE(kk) && (KTOK(kk) >> 4) == b;
        uint32_t todo = __ballot_sync(0xffffffffu, own) & 0xffu;
        if (decltype(role)::value == 0 && todo) {
#pragma unroll
            for (int hf = 0; hf < 2; hf++) {
                const uint4 h = lds128(sb + SM_U + hf * 9216 + tid * 16);
                const uint2 st = lds64(s_stat + (g + 8 * hf) * 8);
                H[hf][0] = h.x; H[hf][1] = h.y; H[hf][2] = h.z; H[hf][3] = h.w;
#pragma unroll
                for (int k = 0; k < 4; k++) U2[hf][k] = ln_apply(H[hf][k], STAT_M(st), STAT_H(st), STAT_L(st));
            }
#pragma unroll 1
            while (todo) {
                const int s = __ffs(todo) - 1, tk = KTOK(__shfl_sync(0xffffffffu, kk, s));
                todo &= todo - 1;
                if ((tk & 13) == TOK(g)) publish(tk & 2, 2 * NCTA + s);
            }
            __threadfence();
        }
        bar_sync(0, NWRK);
        if (decltype(role)::value == 1) {
            if (lane < NSEL && own) *reinterpret_cast<volatile unsigned*>(p.s->flag + lane) = ep + 1u;
            int it = 0;
            while (__any_sync(0xffffffffu, KLATE(kk) && ld_acquire32(p.s->flag + (lane & 7)) != ep + 1u)) { if (++it > SPIN_LIMIT) TRAP(); }
            gather(__shfl_sync(0xffffffffu, kk, g));
        }
        bar_sync(0, NWRK);
    };
    if (warp < 18) {
        const unsigned char* ys = reinterpret_cast<const unsigned char*>(p.s->y) + (b < 96 ? (par ^ 1u) * (NCTA * 18432u) : 0u) +
                                  ((P * DM + 32 * warp + 8 * (g >> 1) + (g & 1)) * 64 + odd * 32 + t * 8);
        if (YDLY == 0 || b < YFROM) {
#pragma unroll
            for (int k = 0; k < 4; k++) yv[k] = ld_poll64(ys + k * 128);
        } else if (YDLY > 1) delay(YDLY);
        mbar_wait(bar_t);
        const uint32_t xa = sb + SM_XT + warp * 64 + t * 16;
        const uint4 x0 = lds128(xa + TOK(g) * 1152), x1 = lds128(xa + (TOK(g) + 2) * 1152), dk = lds128(xa + 16 * 1152);
        uint4 wr = make_uint4(0u, 0u, 0u, 0u);
        if (g == 0) wr = lds128(xa + 17 * 1152);
        const uint32_t Z[2][4] = {{x0.x, x0.y, x0.z, x0.w}, {x1.x, x1.y, x1.z, x1.w}}, D4[4] = {dk.x, dk.y, dk.z, dk.w};
#pragma unroll
        for (int hf = 0; hf < 2; hf++) {
            const uint2 st = lds64(s_stat + (g + 8 * hf) * 8);
#pragma unroll
            for (int k = 0; k < 4; k++) H[hf][k] = hmul2_bf(ln_apply(Z[hf][k], STAT_M(st), STAT_H(st), STAT_L(st)), D4[k]);
        }
        int it = 0;
        while (__any_sync(0xffffffffu, min(min(min(yv[0].x, yv[0].y), min(yv[1].x, yv[1].y)), min(min(yv[2].x, yv[2].y), min(yv[3].x, yv[3].y))) == 0)) {
#pragma unroll
            for (int k = 0; k < 4; k++) yv[k] = ld_poll64(ys + k * 128);
            if (++it > SPIN_LIMIT) TRAP();
        }
        STAMP(12);
#pragma unroll
        for (int k = 0; k < 4; k++) {
            H[0][k] = hadd2_bf(Z[0][k], hadd2_bf(movm(yv[k].x ^ YKEY), H[0][k]));
            H[1][k] = hadd2_bf(Z[1][k], hadd2_bf(movm(yv[k].y ^ YKEY), H[1][k]));
        }
        ln_partial(H, sb + SM_LNP, warp, g, t);
        bar_arrive(6, NWRK);
        STAMP(13);
        bar_sync(7, 608);
        STAMP(14);
#pragma unroll
        for (int hf = 0; hf < 2; hf++) {
            const uint2 st = lds64(s_stat + (g + 8 * hf) * 8);
#pragma unroll
            for (int k = 0; k < 4; k++) U2[hf][k] = ln_apply(H[hf][k], STAT_M(st), STAT_H(st), STAT_L(st));
        }
        {
            float cs[4] = {0.f, 0.f, 0.f, 0.f};
            mma_bf16(cs, U2[0][0], U2[1][0], U2[0][1], U2[1][1], wr.x, wr.y);
            mma_bf16(cs, U2[0][2], U2[1][2], U2[0][3], U2[1][3], wr.z, wr.w);
            if (t == 0) { stsf(sb + SM_LNP + ((32 + g) * 20 + warp) * 4, cs[0]); stsf(sb + SM_LNP + ((40 + g) * 20 + warp) * 4, cs[2]); }
            bar_arrive(8, 608);
        }
        bar_sync(9, 608);
        const uint32_t rk[2] = {lds32(s_rank + g * 4), lds32(s_rank + 32 + g * 4)};
#pragma unroll
        for (int hf = 0; hf < 2; hf++)
            sts128(sb + SM_OUT + (TOK(g) + 2 * hf) * (DM * 2) + warp * 64 + t * 16,
                   hadd2_bf(H[hf][0], U2[hf][0]), hadd2_bf(H[hf][1], U2[hf][1]), hadd2_bf(H[hf][2], U2[hf][2]), hadd2_bf(H[hf][3], U2[hf][3]));
        fence_async();
        uint32_t lo = min(rk[0], rk[1]), hi = max(rk[0], rk[1]);
#pragma unroll 1
        while (lo < 2) { publish(lo == rk[1], 2 * b + lo); lo = hi; hi = 16; }
        sts128(sb + SM_U + tid * 16, H[0][0], H[0][1], H[0][2], H[0][3]);
        sts128(sb + SM_U + 9216 + tid * 16, H[1][0], H[1][1], H[1][2], H[1][3]);
        STAMP(15);
        {
            const int mi = lane >> 3, rr = lane & 7;
            mbar_wait(bar_w);
            const uint32_t aad = sb + SM_WG + (mi & 1) * SM_WU + ((warp & 1) * 144 + rr + 8 * (mi >> 1)) * W_PITCH + (warp >> 1) * 16;
#pragma unroll
            for (int k = 0; k < 9; k++) ldsm_x4_t(WA[k][0], WA[k][1], WA[k][2], WA[k][3], aad + k * 16 * W_PITCH);
        }
        {
            const int mi = lane >> 3, rr = lane & 7;
            mbar_wait(bar_d);
            const uint32_t base = sb + SM_WD + (2 * warp + (mi & 1)) * 16 + rr * WD_PITCH;
#pragma unroll
            for (int k = 0; k < 4; k++) ldsm_x4_t(WD[4 * k], WD[4 * k + 1], WD[4 * k + 2], WD[4 * k + 3], base + (k * 16 + 8 * (mi >> 1)) * WD_PITCH);
            ldsm_x2_t(WD[16], WD[17], base + 64 * WD_PITCH);
        }
        const uint32_t bad = pin(sb + SM_XS + (lane & 7) * XS_PITCH + ((warp & 1) * 144 + 8 * (lane >> 3)) * 2);
        const uint32_t ex = pin(sb + SM_EX + (2 * odd + (warp & 1)) * 4608 + (warp >> 1) * 512 + lane * 16);
        const uint32_t po = pin((((8 * (18 * odd + warp) + g) * 64 + P) * 16 + t * 4) * 4);
        STAMP2(17);
        if (bar_or(11, NWRK, false)) late_rows(IC<0>());
        STAMP2(19);
        {
            float c4[3][4] = {}, e4[4];
#pragma unroll
            for (int k = 0; k < 9; k += 2) {
                uint32_t b0, b1, b2, b3;
                ldsm_x4(b0, b1, b2, b3, bad + k * 32);
                mma_bf16(c4[k % 3], WA[k][0], WA[k][1], WA[k][2], WA[k][3], b0, b1);
                if (k < 8) mma_bf16(c4[(k + 1) % 3], WA[k + 1][0], WA[k + 1][1], WA[k + 1][2], WA[k + 1][3], b2, b3);
            }
#pragma unroll
            for (int j = 0; j < 4; j++) e4[j] = c4[0][j] + c4[1][j] + c4[2][j];
            asm volatile("st.async.shared::cluster.mbarrier::complete_tx::bytes.v4.f32 [%0], {%1,%2,%3,%4}, [%5];\n"
                         ::"r"(ex ^ 0x1000000u), "f"(e4[0]), "f"(e4[1]), "f"(e4[2]), "f"(e4[3]), "r"(bar_g ^ 0x1000000u) : "memory");
            sts128f(ex, e4);
        }
        if (warp < 9) {
            bar_sync(12, 576);
            STAMP2(20);
            const uint32_t er = sb + SM_EX + tid * 16;
            const uint4 a = lds128(er + odd * 9216), c = lds128(er + odd * 9216 + 4608);
            mbar_wait(bar_g);
            const uint4 d = lds128(er + (odd ^ 1) * 9216), e = lds128(er + (odd ^ 1) * 9216 + 4608);
#define S4(f) ((__uint_as_float(a.f) + __uint_as_float(c.f)) + (__uint_as_float(d.f) + __uint_as_float(e.f)))
            const uint32_t G = pack_bf16(S4(x), S4(y)), U = pack_bf16(S4(z), S4(w));
#undef S4
            sts32(sb + SM_GU + tid * 4, hmul2_bf(pack_bf16(bf_lo(G) * sigmoid_f(bf_lo(G)), bf_hi(G) * sigmoid_f(bf_hi(G))), U));
        } else bar_arrive(12, 576);
        bar_sync(13, NWRK);
        STAMP2(21);
        {
            uint32_t gb[9];
            ldsm_x4_t(gb[0], gb[1], gb[2], gb[3], sb + SM_GU + lane * 16);
            ldsm_x4_t(gb[4], gb[5], gb[6], gb[7], sb + SM_GU + 512 + lane * 16);
            ldsm_x1_t(gb[8], sb + SM_GU + 1024 + lane * 16);
            float c4[4] = {}, d4[4] = {}, e4[4] = {};
            mma_bf16(c4, WD[0], WD[1], WD[2], WD[3], gb[0], gb[1]);
            mma_bf16(d4, WD[4], WD[5], WD[6], WD[7], gb[2], gb[3]);
            mma_bf16(e4, WD[8], WD[9], WD[10], WD[11], gb[4], gb[5]);
            mma_bf16(c4, WD[12], WD[13], WD[14], WD[15], gb[6], gb[7]);
            mma_bf16_k8(d4, WD[16], WD[17], gb[8]);
            stg128(reinterpret_cast<unsigned char*>(p.s->part) + po, __float_as_uint(e4[0] + c4[0] + d4[0]) | 1u, __float_as_uint(e4[1] + c4[1] + d4[1]) | 1u,
                   __float_as_uint(e4[2] + c4[2] + d4[2]) | 1u, __float_as_uint(e4[3] + c4[3] + d4[3]) | 1u);
        }
        STAMP2(22);
    } else if (warp == 18) {
        bar_sync(6, NWRK);
        {
            float mb, rc;
            ln_finish(sum18(sb + SM_LNP + lane * 80), lane, mb, rc);
            if (lane < 16) stat_store(s_stat + lane * 8, mb, rc, 0u);
        }
        bar_arrive(7, 608);
        const uint4* ksrc = reinterpret_cast<const uint4*>(p.s->key) + lane;
        const uint32_t klo = (uint32_t)(2047 - 16 * b - ROWTOK(lane & 15)) << 5 | par;
        bar_sync(8, 608);
        {
            const float r = sum18(sb + SM_LNP + (32 + (lane & 15)) * 80);
            const uint32_t bits = pack_bf16(0.f, r);
            const uint32_t me = ((bits ^ ((uint32_t)((int)bits >> 31) | 0x80000000u)) & 0xffff0000u) | klo;
            sts32(s_k16 + (lane & 15) * 4, me);
            __syncwarp();
            const uint4 v = lds128(s_k16 + (lane & 16) * 2), w = lds128(s_k16 + (lane & 16) * 2 + 16);
            int rank = ((v.x > me) + (v.y > me)) + ((v.z > me) + (v.w > me)) + (((w.x > me) + (w.y > me)) + ((w.z > me) + (w.w > me)));
            rank += __shfl_xor_sync(0xffffffffu, rank, 16);
            if (lane < 16 && rank < 8) p.s->key[8 * b + rank] = me | (rank << 1);
            if (lane >= 16) sts32(s_rank + (lane & 15) * 4, rank);
        }
        bar_arrive(9, 608);
        uint4 kq[4];
        int it = 0;
        if (KDLY) delay(KDLY);
        do {
#pragma unroll
            for (int i = 0; i < 4; i++) kq[i] = ld_poll(ksrc + lane + 64 * i);
            if (++it > SPIN_LIMIT) TRAP();
        } while (__any_sync(0xffffffffu, ((and3(and3(kq[0].x, kq[0].y, kq[0].z), and3(kq[1].x, kq[1].y, kq[1].z), and3(and3(kq[2].x, kq[2].y, kq[2].z), kq[3].x, kq[3].y) & kq[3].z) ^ par) |
                                          (or3(or3(kq[0].x, kq[0].y, kq[0].z), or3(kq[1].x, kq[1].y, kq[1].z), or3(or3(kq[2].x, kq[2].y, kq[2].z), kq[3].x, kq[3].y) | kq[3].z) ^ par)) & 1u));
        STAMPW(16);
        uint32_t u[4], mine = 0, m;
        {
            uint32_t S[2][4];
#pragma unroll
            for (int i = 0; i < 2; i++) {
                const uint4 &c = kq[2 * i], &d = kq[2 * i + 1];
                const uint32_t m1 = min(c.x, d.x), m2 = max(c.y, d.y);
                S[i][0] = max(c.x, d.x); S[i][1] = max(m1, m2); S[i][2] = min(m1, m2); S[i][3] = min(c.y, d.y);
            }
            const uint32_t a0 = max(S[0][0], S[1][3]), a1 = max(S[0][1], S[1][2]), a2 = max(S[0][2], S[1][1]), a3 = max(S[0][3], S[1][0]);
            const uint32_t b0 = max(a0, a2), b2 = min(a0, a2), b1 = max(a1, a3), b3 = min(a1, a3);
            u[0] = max(b0, b1); u[1] = min(b0, b1); u[2] = max(b2, b3); u[3] = min(b2, b3);
        }
        uint4 v[9];
#pragma unroll
        for (int r = 0; r < 8; r++) {
            m = __reduce_max_sync(0xffffffffu, u[0]);
            if (u[0] == m) { u[0] = u[1]; u[1] = u[2]; u[2] = u[3]; u[3] = 0; }
            if (g == r) mine = m;
            v[r] = ld_poll(rsrc + (2 * (KTOK(m) >> 4) + ((m >> 1) & 1u)) * 144 + lane);
        }
        v[8] = ld_poll(rsrc + (2 * (KTOK(mine) >> 4) + ((mine >> 1) & 1u)) * 144 + 32 + t);
        bool again = __any_sync(0xffffffffu, u[0] == 0 || max(max(kq[0].z, kq[1].z), max(kq[2].z, kq[3].z)) > m);
        if (again) {
#pragma unroll 1
            for (int i = 0; i < 8; i++) {
                uint4 k;
                do { k = ld_poll(ksrc + 32 * i); if (++it > SPIN_LIMIT) TRAP(); } while (((k.x ^ par) | (k.y ^ par) | (k.z ^ par) | (k.w ^ par)) & 1u);
                sts128(sb + SM_KEYS + (32 * i + lane) * 16, k.x, k.y, k.z, k.w);
            }
            m = 0xffffffffu;
#pragma unroll 1
            for (int r = 0; r < 8; r++) {
                uint32_t c = 0;
#pragma unroll 2
                for (int i = 0; i < 8; i++) {
                    const uint4 k = lds128(sb + SM_KEYS + (32 * i + lane) * 16);
                    c = max(max(c, k.x < m ? k.x : 0u), max(k.y < m ? k.y : 0u, max(k.z < m ? k.z : 0u, k.w < m ? k.w : 0u)));
                }
                m = __reduce_max_sync(0xffffffffu, c);
                if (g == r) mine = m;
            }
        }
        if (t == 0) sts32(s_key + g * 4, mine);
        uint32_t mn = 1;
#pragma unroll
        for (int r = 0; r < 9; r++) {
            sts128(sb + SM_XS + (r < 8 ? r * XS_PITCH + lane * 16 : g * XS_PITCH + (32 + t) * 16), v[r].x, v[r].y, v[r].z, v[r].w);
            mn = min(mn, min4(v[r]));
        }
        if ((again || __any_sync(0xffffffffu, mn == 0)) && !__any_sync(0xffffffffu, KLATE(mine))) gather(mine);
        STAMPW(18);
        if (bar_or(11, NWRK, KLATE(mine))) late_rows(IC<1>());
    } else {
        bar_sync(6, NWRK);
        WPOINT(16, true);
        if (wsched(18) > wsched(17)) delay(WDLY);
        WPOINT(17, true);
        if (wsched(19) > wsched(18)) delay(WDLY);
        WPOINT(18, true);
        if (bar_or(11, NWRK, false)) late_rows(IC<2>());
        const int tk = KTOK(lds32(s_key + (lane & 7) * 4));
        const uint32_t sel = __reduce_or_sync(0xffffffffu, (tk >> 4) == b ? 1u << (tk & 15) : 0u);
        if (sel ? lane < 16 && !((sel >> lane) & 1u) : lane == 0) bulk_s2g(p.out + (size_t)(16 * b + lane) * DM, sb + SM_OUT + lane * (DM * 2), sel ? DM * 2 : 16 * DM * 2);
        __syncwarp();
    }
    if (warp >= 17) {
        const int grp = 3 * b + warp - 17, fsl = 2 * t + ((lane >> 3) & 1), fc = 16 * (grp >> 3) + (grp & 7) + 8 * (lane >> 4);
        const uint32_t fk = lds32(s_key + fsl * 4);
        float hv = 0.f, u2 = 0.f;
        int it = 0;
        if (b < 96) {
            const uint32_t* const fsrc = p.s->rows + KSLOT(fk, fsl) * DM + (fc >> 1);
            uint32_t hw, uw;
            do { hw = ld_poll32(fsrc + 288); uw = ld_poll32(fsrc); if (++it > SPIN_LIMIT) TRAP(); } while (!hw || !uw);
            hv = (fc & 1) ? bf_hi(hw) : bf_lo(hw); u2 = (fc & 1) ? bf_hi(uw) : bf_lo(uw);
        }
        const float rs = rbf(sigmoid_f(__uint_as_float((fk ^ ((uint32_t)((int)~fk >> 31) | 0x80000000u)) & 0xffff0000u)));
        const uint32_t dof = pin(KTOK(fk) * DM + fc), so = pin(grp * 256 + lane);
        if (warp > 17) bar_sync(13, NWRK);
        if (b < 96) {
            delay(warp > 17 ? FDLY : FDLY2);
            const uint4* src = reinterpret_cast<const uint4*>(p.s->part) + so;
            uint4 a[8];
#define A4(i) and3(and3(a[i].x, a[i].y, a[i].z), and3(a[i].w, a[i + 1].x, a[i + 1].y), a[i + 1].z & a[i + 1].w)
            do {
#pragma unroll
                for (int i = 0; i < 8; i++) a[i] = ld_poll(src + 32 * i);
                if (++it > SPIN_LIMIT) TRAP();
            } while (__any_sync(0xffffffffu, !(and3(A4(0), A4(2), and3(A4(4), A4(6), 1u)))));
#undef A4
            STAMP2(24);
#define S8(f) (((__uint_as_float(a[0].f) + __uint_as_float(a[1].f)) + (__uint_as_float(a[2].f) + __uint_as_float(a[3].f))) + \
               ((__uint_as_float(a[4].f) + __uint_as_float(a[5].f)) + (__uint_as_float(a[6].f) + __uint_as_float(a[7].f))))
            const float s0 = S8(x), s1 = S8(y), s2 = S8(z), s3 = S8(w);
#undef S8
            const bool up = lane & 16, od = lane & 8;
            const float r0 = (up ? s2 : s0) + __shfl_xor_sync(0xffffffffu, up ? s0 : s2, 16), r1 = (up ? s3 : s1) + __shfl_xor_sync(0xffffffffu, up ? s1 : s3, 16);
            float y = (od ? r1 : r0) + __shfl_xor_sync(0xffffffffu, od ? r0 : r1, 8);
            y += __shfl_xor_sync(0xffffffffu, y, 4);
            p.out[dof] = __float2bfloat16_rn(hv + rbf(u2 + rbf(rbf(y) * rs)));
        }
    }
    if (warp == 19) asm volatile("cp.async.bulk.wait_group.read 0;\n" ::: "memory");
    if (b == 0 && tid < 8) *reinterpret_cast<volatile unsigned*>(p.s->hint + tid * 32 + 1) = lds32(s_cnt + 4) + 1u;
    STAMP(25);
    }
}

typedef CUresult (*PFN_tmEncode)(CUtensorMap*, CUtensorMapDataType, cuuint32_t, void*, const cuuint64_t*, const cuuint64_t*, const cuuint32_t*,
                                 const cuuint32_t*, CUtensorMapInterleave, CUtensorMapSwizzle, CUtensorMapL2promotion, CUtensorMapFloatOOBfill);

extern "C" void kernel_launch(void* const* d_in, const int* in_sizes, int n_in, void* d_out, int out_size) {
    Params p;
    p.x = (const bf16*)d_in[0];
    p.lar = (const bf16*)d_in[1];
    p.aim = (const bf16*)d_in[2];
    p.cre = (const bf16*)d_in[3];
    p.cim = (const bf16*)d_in[4];
    p.ldt = (const bf16*)d_in[5];
    p.dsk = (const bf16*)d_in[6];
    p.wr = (const bf16*)d_in[8];
    p.wg = (const bf16*)d_in[9];
    p.wu = (const bf16*)d_in[10];
    p.wd = (const bf16*)d_in[11];
    p.out = (bf16*)d_out;
    static PFN_tmEncode enc = nullptr;
    static void* scratch = nullptr;
    if (!enc) {
        cudaFuncSetAttribute(fused_kernel, cudaFuncAttributeMaxDynamicSharedMemorySize, SMEM_TOTAL);
        void* fn = nullptr;
        cudaDriverEntryPointQueryResult qr;
        cudaGetDriverEntryPoint("cuTensorMapEncodeTiled", &fn, cudaEnableDefault, &qr);
        enc = (PFN_tmEncode)fn;
        cudaGetSymbolAddress(&scratch, g_scratch);
    }
    p.s = (Scratch*)scratch;
    CUtensorMap tm_g, tm_u, tm_d, tm_x;
    const cuuint64_t dims[2] = {FF, DM}, strides[1] = {FF * 2};
    const cuuint32_t box[2] = {72, 48}, es[2] = {1, 1};
    enc(&tm_g, CU_TENSOR_MAP_DATA_TYPE_BFLOAT16, 2, d_in[9], dims, strides, box, es, CU_TENSOR_MAP_INTERLEAVE_NONE, CU_TENSOR_MAP_SWIZZLE_NONE,
        CU_TENSOR_MAP_L2_PROMOTION_NONE, CU_TENSOR_MAP_FLOAT_OOB_FILL_NONE);
    enc(&tm_u, CU_TENSOR_MAP_DATA_TYPE_BFLOAT16, 2, d_in[10], dims, strides, box, es, CU_TENSOR_MAP_INTERLEAVE_NONE, CU_TENSOR_MAP_SWIZZLE_NONE,
        CU_TENSOR_MAP_L2_PROMOTION_NONE, CU_TENSOR_MAP_FLOAT_OOB_FILL_NONE);
    const cuuint64_t ddims[2] = {DM / 2, FF}, dstrides[1] = {DM * 2};
    const cuuint32_t dbox[2] = {WD_PITCH / 4, 8};
    enc(&tm_d, CU_TENSOR_MAP_DATA_TYPE_UINT32, 2, d_in[11], ddims, dstrides, dbox, es, CU_TENSOR_MAP_INTERLEAVE_NONE, CU_TENSOR_MAP_SWIZZLE_NONE,
        CU_TENSOR_MAP_L2_PROMOTION_NONE, CU_TENSOR_MAP_FLOAT_OOB_FILL_NONE);
    const cuuint64_t xdims[4] = {DM, 128, 4, 4}, xstrides[3] = {DM * 8, DM * 2, DM * 1024};
    const cuuint32_t xbox[4] = {8, 128, 4, MC ? 2 : 4}, xes[4] = {1, 1, 1, 1};
    enc(&tm_x, CU_TENSOR_MAP_DATA_TYPE_BFLOAT16, 4, d_in[0], xdims, xstrides, xbox, xes, CU_TENSOR_MAP_INTERLEAVE_NONE, CU_TENSOR_MAP_SWIZZLE_NONE,
        CU_TENSOR_MAP_L2_PROMOTION_NONE, CU_TENSOR_MAP_FLOAT_OOB_FILL_NONE);
    fused_kernel<<<NCTA, NTHR, SMEM_TOTAL>>>(p, tm_g, tm_u, tm_d, tm_x);
}
```

```cpp
#include <cuda_runtime.h>
#include <cuda.h>
#include <cuda_fp16.h>
#include <cuda_bf16.h>
#include <stdint.h>

#define LSEQ 2048
#define DM 576
#define NST 128
#define FF 4608
#define NSEL 8
#define NCTA 128
#define NTHR 640
#define NWRK 640

typedef __nv_bfloat16 bf16;

#define SM_WG 0
#define SM_WU 41472
#define SM_XC (82944 - 32768)
#define SM_WD 82944
#define W_PITCH 144
#define WD_PITCH 592
#define SM_XT (SM_PL - 18 * 1152)
#define SM_PL (SM_WD + 46080)
#define PL_HALF 1344
#define PLW_B 2624
#define PL_B (4 * PLW_B)
#define SM_U (SM_PL + 5 * PL_B)
#define UPAD 20
#define ULO_B ((UPAD + 128) * 16)
#define USLOT_B (2 * ULO_B)
#define SM_ZERO (SM_U + 4 * USLOT_B + 128)
#define SM_KW (SM_U + 5 * USLOT_B)
#define KW_B 3712
#define KW_PL 1216
#define KW_P 2400
#define KW_H 3440
#define SM_MISC (SM_KW + 5 * KW_B)
#define SM_LC (SM_MISC + 384)
#define SM_LNP (SM_LC + 768)
#define SM_RX (SM_LNP + 3840)
#define SMEM_TOTAL (SM_RX + 3088)
#define YKEY 0xffc1ffc1u
#define TBW PLW_B
#define SM_OUT SM_PL
#define SM_XS (SM_PL + 18432)
#define XS_PITCH 592
#define SM_GU (SM_PL + 23296)
#define SM_EX (SM_PL + 24576)
#define SM_KEYS SM_KW

struct __align__(128) Scratch {
    unsigned hint[8 * 32];
    unsigned flag[32];
    uint32_t key[NCTA * 8];
    uint32_t stat[LSEQ];
    uint32_t uT[64 * (LSEQ / 2)];
    uint32_t y[(NCTA + 96) * DM * 8];
    uint32_t part[288 * 64 * 16];
    uint32_t rows[(2 * NCTA + NSEL) * DM];
};
__device__ Scratch g_scratch;
#define STAMP(i)
#define STAMPX(i)
#define STAMPY(i)

__device__ __forceinline__ float rbf(float x) {
    uint32_t r;
    asm("cvt.rn.bf16x2.f32 %0, %1, %2;\n" : "=r"(r) : "f"(x), "f"(0.f));
    return __uint_as_float(r & 0xffff0000u);
}
__device__ __forceinline__ uint32_t pack_bf16(float lo, float hi) {
    uint32_t r;
    asm("cvt.rn.bf16x2.f32 %0, %1, %2;\n" : "=r"(r) : "f"(hi), "f"(lo));
    return r;
}
__device__ __forceinline__ uint32_t pack_f16(float lo, float hi) {
    uint32_t r;
    asm("cvt.rn.f16x2.f32 %0, %1, %2;\n" : "=r"(r) : "f"(hi), "f"(lo));
    return r;
}
__device__ __forceinline__ uint32_t pack_f16_rz(float lo, float hi) {
    uint32_t r;
    asm("cvt.rz.f16x2.f32 %0, %1, %2;\n" : "=r"(r) : "f"(hi), "f"(lo));
    return r;
}
__device__ __forceinline__ float bf_lo(uint32_t w) { return __uint_as_float(w << 16); }
__device__ __forceinline__ float bf_hi(uint32_t w) { return __uint_as_float(w & 0xffff0000u); }
__device__ __forceinline__ uint32_t hadd2_bf(uint32_t a, uint32_t b) {
    __nv_bfloat162 r = __hadd2_rn(*reinterpret_cast<__nv_bfloat162*>(&a), *reinterpret_cast<__nv_bfloat162*>(&b));
    return *reinterpret_cast<uint32_t*>(&r);
}
__device__ __forceinline__ uint32_t hsub2_bf(uint32_t a, uint32_t b) {
    __nv_bfloat162 r = __hsub2_rn(*reinterpret_cast<__nv_bfloat162*>(&a), *reinterpret_cast<__nv_bfloat162*>(&b));
    return *reinterpret_cast<uint32_t*>(&r);
}
__device__ __forceinline__ uint32_t hmul2_bf(uint32_t a, uint32_t b) {
    __nv_bfloat162 r = __hmul2_rn(*reinterpret_cast<__nv_bfloat162*>(&a), *reinterpret_cast<__nv_bfloat162*>(&b));
    return *reinterpret_cast<uint32_t*>(&r);
}
__device__ __forceinline__ uint32_t hfma2_bf(uint32_t a, uint32_t b, uint32_t c) { uint32_t r; asm("fma.rn.bf16x2 %0, %1, %2, %3;\n" : "=r"(r) : "r"(a), "r"(b), "r"(c)); return r; }
__device__ __forceinline__ uint32_t hmul2(uint32_t a, uint32_t b) { uint32_t r; asm("mul.rn.f16x2 %0, %1, %2;\n" : "=r"(r) : "r"(a), "r"(b)); return r; }
__device__ __forceinline__ uint32_t hadd2(uint32_t a, uint32_t b) { uint32_t r; asm("add.rn.f16x2 %0, %1, %2;\n" : "=r"(r) : "r"(a), "r"(b)); return r; }
__device__ __forceinline__ uint32_t hfma2(uint32_t a, uint32_t b, uint32_t c) { uint32_t r; asm("fma.rn.f16x2 %0, %1, %2, %3;\n" : "=r"(r) : "r"(a), "r"(b), "r"(c)); return r; }
__device__ __forceinline__ uint32_t hfms2(uint32_t a, uint32_t b, uint32_t c) {
    uint32_t r;
    asm("{\n.reg .b32 n;\nneg.f16x2 n, %2;\nfma.rn.f16x2 %0, %1, n, %3;\n}\n" : "=r"(r) : "r"(a), "r"(b), "r"(c));
    return r;
}
__device__ __forceinline__ uint32_t nzw(uint32_t w) { return w ? w : 0x8000u; }
__device__ __forceinline__ uint32_t nzf(float f) { const uint32_t w = __float_as_uint(f); return w ? w : 0x80000000u; }
__device__ __forceinline__ uint32_t smem_u32(const void* p) { return (uint32_t)__cvta_generic_to_shared(p); }
__device__ __forceinline__ uint32_t lds32(uint32_t addr) {
    uint32_t v;
    asm volatile("ld.shared.u32 %0, [%1];\n" : "=r"(v) : "r"(addr) : "memory");
    return v;
}
__device__ __forceinline__ uint32_t lds16(uint32_t addr) {
    unsigned short v;
    asm volatile("ld.shared.u16 %0, [%1];\n" : "=h"(v) : "r"(addr) : "memory");
    return v;
}
__device__ __forceinline__ uint2 lds64(uint32_t addr) {
    uint2 v;
    asm volatile("ld.shared.v2.u32 {%0,%1}, [%2];\n" : "=r"(v.x), "=r"(v.y) : "r"(addr) : "memory");
    return v;
}
__device__ __forceinline__ uint4 lds128(uint32_t addr) {
    uint4 v;
    asm volatile("ld.shared.v4.u32 {%0,%1,%2,%3}, [%4];\n" : "=r"(v.x), "=r"(v.y), "=r"(v.z), "=r"(v.w) : "r"(addr) : "memory");
    return v;
}
__device__ __forceinline__ float ldsf(uint32_t addr) { return __uint_as_float(lds32(addr)); }
__device__ __forceinline__ void sts32(uint32_t addr, uint32_t v) { asm volatile("st.shared.u32 [%0], %1;\n" ::"r"(addr), "r"(v) : "memory"); }
__device__ __forceinline__ void sts16(uint32_t addr, uint32_t v) { asm volatile("st.shared.u16 [%0], %1;\n" ::"r"(addr), "h"((unsigned short)v) : "memory"); }
__device__ __forceinline__ void stsf(uint32_t addr, float v) { sts32(addr, __float_as_uint(v)); }
__device__ __forceinline__ void sts64(uint32_t addr, uint32_t a, uint32_t b) { asm volatile("st.shared.v2.u32 [%0], {%1,%2};\n" ::"r"(addr), "r"(a), "r"(b) : "memory"); }
__device__ __forceinline__ void sts64f(uint32_t addr, float a, float b) { sts64(addr, __float_as_uint(a), __float_as_uint(b)); }
__device__ __forceinline__ void sts128(uint32_t addr, uint32_t a, uint32_t b, uint32_t c, uint32_t d) {
    asm volatile("st.shared.v4.u32 [%0], {%1,%2,%3,%4};\n" ::"r"(addr), "r"(a), "r"(b), "r"(c), "r"(d) : "memory");
}
__device__ __forceinline__ void sts128f(uint32_t addr, const float (&v)[4]) {
    sts128(addr, __float_as_uint(v[0]), __float_as_uint(v[1]), __float_as_uint(v[2]), __float_as_uint(v[3]));
}
__device__ __forceinline__ void ldsm_x4(uint32_t& r0, uint32_t& r1, uint32_t& r2, uint32_t& r3, uint32_t addr) {
    asm volatile("ldmatrix.sync.aligned.m8n8.x4.shared.b16 {%0,%1,%2,%3}, [%4];\n"
                 : "=r"(r0), "=r"(r1), "=r"(r2), "=r"(r3) : "r"(addr) : "memory");
}
__device__ __forceinline__ void ldsm_x4_t(uint32_t& r0, uint32_t& r1, uint32_t& r2, uint32_t& r3, uint32_t addr) {
    asm volatile("ldmatrix.sync.aligned.m8n8.x4.trans.shared.b16 {%0,%1,%2,%3}, [%4];\n"
                 : "=r"(r0), "=r"(r1), "=r"(r2), "=r"(r3) : "r"(addr) : "memory");
}
__device__ __forceinline__ void ldsm_x2_t(uint32_t& r0, uint32_t& r1, uint32_t addr) {
    asm volatile("ldmatrix.sync.aligned.m8n8.x2.trans.shared.b16 {%0,%1}, [%2];\n" : "=r"(r0), "=r"(r1) : "r"(addr) : "memory");
}
__device__ __forceinline__ void ldsm_x1_t(uint32_t& r0, uint32_t addr) {
    asm volatile("ldmatrix.sync.aligned.m8n8.x1.trans.shared.b16 {%0}, [%1];\n" : "=r"(r0) : "r"(addr) : "memory");
}
__device__ __forceinline__ void stsm_x4(uint32_t addr, uint32_t r0, uint32_t r1, uint32_t r2, uint32_t r3) {
    asm volatile("stmatrix.sync.aligned.m8n8.x4.shared.b16 [%0], {%1,%2,%3,%4};\n" ::"r"(addr), "r"(r0), "r"(r1), "r"(r2), "r"(r3) : "memory");
}
__device__ __forceinline__ void stsm_x4_t(uint32_t addr, uint32_t r0, uint32_t r1, uint32_t r2, uint32_t r3) {
    asm volatile("stmatrix.sync.aligned.m8n8.x4.trans.shared.b16 [%0], {%1,%2,%3,%4};\n" ::"r"(addr), "r"(r0), "r"(r1), "r"(r2), "r"(r3) : "memory");
}
__device__ __forceinline__ uint32_t movm(uint32_t a) {
    uint32_t d;
    asm volatile("movmatrix.sync.aligned.m8n8.trans.b16 %0, %1;\n" : "=r"(d) : "r"(a));
    return d;
}
__device__ __forceinline__ void mma_f16(float (&c)[4], uint32_t a0, uint32_t a1, uint32_t a2, uint32_t a3, uint32_t b0, uint32_t b1) {
    asm volatile(
        "mma.sync.aligned.m16n8k16.row.col.f32.f16.f16.f32 {%0,%1,%2,%3}, {%4,%5,%6,%7}, {%8,%9}, {%0,%1,%2,%3};\n"
        : "+f"(c[0]), "+f"(c[1]), "+f"(c[2]), "+f"(c[3])
        : "r"(a0), "r"(a1), "r"(a2), "r"(a3), "r"(b0), "r"(b1));
}
__device__ __forceinline__ void mma_bf16(float (&c)[4], uint32_t a0, uint32_t a1, uint32_t a2, uint32_t a3, uint32_t b0, uint32_t b1) {
    asm volatile(
        "mma.sync.aligned.m16n8k16.row.col.f32.bf16.bf16.f32 {%0,%1,%2,%3}, {%4,%5,%6,%7}, {%8,%9}, {%0,%1,%2,%3};\n"
        : "+f"(c[0]), "+f"(c[1]), "+f"(c[2]), "+f"(c[3])
        : "r"(a0), "r"(a1), "r"(a2), "r"(a3), "r"(b0), "r"(b1));
}
__device__ __forceinline__ void mma_bf16_k8(float (&c)[4], uint32_t a0, uint32_t a1, uint32_t b0) {
    asm volatile("mma.sync.aligned.m16n8k8.row.col.f32.bf16.bf16.f32 {%0,%1,%2,%3}, {%4,%5}, {%6}, {%0,%1,%2,%3};\n"
                 : "+f"(c[0]), "+f"(c[1]), "+f"(c[2]), "+f"(c[3]) : "r"(a0), "r"(a1), "r"(b0));
}
__device__ __forceinline__ void bar_sync(int id, int n) { asm volatile("bar.sync %0, %1;\n" ::"r"(id), "r"(n) : "memory"); }
__device__ __forceinline__ void bar_arrive(int id, int n) { asm volatile("bar.arrive %0, %1;\n" ::"r"(id), "r"(n) : "memory"); }
__device__ __forceinline__ bool bar_or(int id, int n, bool v) {
    uint32_t r;
    asm volatile("{\n.reg .pred p, q;\nsetp.ne.u32 p, %3, 0;\nbar.red.or.pred q, %1, %2, p;\nselp.u32 %0, 1, 0, q;\n}\n" : "=r"(r) : "r"(id), "r"(n), "r"((uint32_t)v) : "memory");
    return r;
}
__device__ __forceinline__ uint32_t and3(uint32_t a, uint32_t b, uint32_t c) { uint32_t r; asm("lop3.b32 %0, %1, %2, %3, 0x80;\n" : "=r"(r) : "r"(a), "r"(b), "r"(c)); return r; }
__device__ __forceinline__ uint32_t or3(uint32_t a, uint32_t b, uint32_t c) { uint32_t r; asm("lop3.b32 %0, %1, %2, %3, 0xfe;\n" : "=r"(r) : "r"(a), "r"(b), "r"(c)); return r; }
__device__ __forceinline__ uint32_t pin(uint32_t v) { uint32_t r; asm volatile("shfl.sync.bfly.b32 %0, %1, 0, 0x1f, 0xffffffff;\n" : "=r"(r) : "r"(v) : "memory"); return r; }
__device__ __forceinline__ uint4 ld_poll(const void* p) {
    uint4 v;
    asm volatile("ld.relaxed.gpu.global.v4.u32 {%0,%1,%2,%3}, [%4];\n" : "=r"(v.x), "=r"(v.y), "=r"(v.z), "=r"(v.w) : "l"(p) : "memory");
    return v;
}
__device__ __forceinline__ uint2 ld_poll64(const void* p) {
    uint2 v;
    asm volatile("ld.relaxed.gpu.global.v2.u32 {%0,%1}, [%2];\n" : "=r"(v.x), "=r"(v.y) : "l"(p) : "memory");
    return v;
}
__device__ __forceinline__ uint32_t ld_poll32(const void* p) {
    uint32_t v;
    asm volatile("ld.relaxed.gpu.global.u32 %0, [%1];\n" : "=r"(v) : "l"(p) : "memory");
    return v;
}
__device__ __forceinline__ uint32_t ld_acquire32(const void* p) {
    uint32_t v;
    asm volatile("ld.acquire.gpu.global.u32 %0, [%1];\n" : "=r"(v) : "l"(p) : "memory");
    return v;
}
__device__ __forceinline__ uint4 ldg128(const void* p) {
    uint4 v;
    asm volatile("ld.global.nc.v4.u32 {%0,%1,%2,%3}, [%4];\n" : "=r"(v.x), "=r"(v.y), "=r"(v.z), "=r"(v.w) : "l"(p));
    return v;
}
__device__ __forceinline__ uint2 ldg64(const void* p) {
    uint2 v;
    asm volatile("ld.global.nc.v2.u32 {%0,%1}, [%2];\n" : "=r"(v.x), "=r"(v.y) : "l"(p));
    return v;
}
__device__ __forceinline__ uint32_t ldg16(const void* p) {
    uint32_t v;
    asm volatile("ld.global.nc.u16 %0, [%1];\n" : "=r"(v) : "l"(p));
    return v;
}
__device__ __forceinline__ uint4 ldo128(const void* p) {
    uint4 v;
    asm volatile("ld.relaxed.cta.global.v4.u32 {%0,%1,%2,%3}, [%4];\n" : "=r"(v.x), "=r"(v.y), "=r"(v.z), "=r"(v.w) : "l"(p) : "memory");
    return v;
}
__device__ __forceinline__ uint2 ldo64(const void* p) {
    uint2 v;
    asm volatile("ld.relaxed.cta.global.v2.u32 {%0,%1}, [%2];\n" : "=r"(v.x), "=r"(v.y) : "l"(p) : "memory");
    return v;
}
__device__ __forceinline__ uint32_t ldo16(const void* p) {
    uint32_t v;
    asm volatile("ld.relaxed.cta.global.u16 %0, [%1];\n" : "=r"(v) : "l"(p) : "memory");
    return v;
}
__device__ __forceinline__ void stg128(void* p, uint32_t a, uint32_t b, uint32_t c, uint32_t d) {
    asm volatile("st.global.v4.u32 [%0], {%1,%2,%3,%4};\n" ::"l"(p), "r"(a), "r"(b), "r"(c), "r"(d) : "memory");
}
__device__ __forceinline__ void stg64(void* p, uint32_t a, uint32_t b) { asm volatile("st.global.v2.u32 [%0], {%1,%2};\n" ::"l"(p), "r"(a), "r"(b) : "memory"); }
__device__ __forceinline__ uint32_t min4(const uint4& v) { return min(min(v.x, v.y), min(v.z, v.w)); }
#define SPIN_LIMIT (1 << 21)
#define TRAP() __trap()
__device__ __forceinline__ void mbar_init(uint32_t bar, uint32_t cnt) { asm volatile("mbarrier.init.shared::cta.b64 [%0], %1;\n" ::"r"(bar), "r"(cnt) : "memory"); }
__device__ __forceinline__ void mbar_expect(uint32_t bar, uint32_t bytes) {
    asm volatile("mbarrier.arrive.expect_tx.shared::cta.b64 _, [%0], %1;\n" ::"r"(bar), "r"(bytes) : "memory");
}
__device__ __forceinline__ void mbar_arrive(uint32_t bar) { asm volatile("mbarrier.arrive.shared::cta.b64 _, [%0];\n" ::"r"(bar) : "memory"); }
__device__ __forceinline__ void mbar_wait_cluster(uint32_t bar) {
    asm volatile(
        "{\n.reg .pred p;\n"
        "W_%=:\n"
        "mbarrier.try_wait.parity.acquire.cluster.shared::cta.b64 p, [%0], 0;\n"
        "@!p bra W_%=;\n}\n" ::"r"(bar) : "memory");
}
__device__ __forceinline__ void mbar_wait(uint32_t bar) {
    asm volatile(
        "{\n.reg .pred p;\n"
        "W_%=:\n"
        "mbarrier.try_wait.parity.shared::cta.b64 p, [%0], 0;\n"
        "@!p bra W_%=;\n}\n" ::"r"(bar) : "memory");
}
__device__ __forceinline__ void mbar_wait1(uint32_t bar) {
    asm volatile(
        "{\n.reg .pred p;\n"
        "W_%=:\n"
        "mbarrier.try_wait.parity.shared::cta.b64 p, [%0], 1;\n"
        "@!p bra W_%=;\n}\n" ::"r"(bar) : "memory");
}
__device__ __forceinline__ bool mbar_test(uint32_t bar) {
    uint32_t r;
    asm volatile("{\n.reg .pred p;\nmbarrier.test_wait.parity.shared::cta.b64 p, [%1], 0;\nselp.u32 %0, 1, 0, p;\n}\n" : "=r"(r) : "r"(bar) : "memory");
    return __any_sync(0xffffffffu, r);
}
__device__ __forceinline__ void bulk_g2s(uint32_t dst, const void* src, uint32_t bytes, uint32_t bar) {
    asm volatile("cp.async.bulk.shared::cluster.global.mbarrier::complete_tx::bytes [%0], [%1], %2, [%3];\n" ::"r"(dst), "l"(src), "r"(bytes), "r"(bar) : "memory");
}
__device__ __forceinline__ void bulk_s2g(void* dst, uint32_t src, uint32_t bytes) {
    asm volatile("cp.async.bulk.global.shared::cta.bulk_group [%0], [%1], %2;\ncp.async.bulk.commit_group;\n" ::"l"(dst), "r"(src), "r"(bytes) : "memory");
}
__device__ __forceinline__ void tma_2d(uint32_t dst, const CUtensorMap* tm, int c0, int c1, uint32_t bar) {
    asm volatile("cp.async.bulk.tensor.2d.shared::cluster.global.mbarrier::complete_tx::bytes [%0], [%1, {%3, %4}], [%2];\n"
                 ::"r"(dst), "l"(tm), "r"(bar), "r"(c0), "r"(c1) : "memory");
}
__device__ __forceinline__ void tma_4d(uint32_t dst, const CUtensorMap* tm, int c0, int c3, uint32_t bar) {
    asm volatile("cp.async.bulk.tensor.4d.shared::cluster.global.mbarrier::complete_tx::bytes [%0], [%1, {%3, %4, %4, %5}], [%2];\n"
                 ::"r"(dst), "l"(tm), "r"(bar), "r"(c0), "r"(0), "r"(c3) : "memory");
}
__device__ __forceinline__ void tma_4d_mc(uint32_t dst, const CUtensorMap* tm, int c0, int c3, uint32_t bar) {
    asm volatile("cp.async.bulk.tensor.4d.shared::cluster.global.mbarrier::complete_tx::bytes.multicast::cluster [%0], [%1, {%3, %4, %4, %5}], [%2], %6;\n"
                 ::"r"(dst), "l"(tm), "r"(bar), "r"(c0), "r"(0), "r"(c3), "h"((unsigned short)3) : "memory");
}
__device__ __forceinline__ void l2_prefetch(const void* src, uint32_t bytes) {
    asm volatile("cp.async.bulk.prefetch.L2.global [%0], %1;\n" ::"l"(src), "r"(bytes) : "memory");
}
__device__ __forceinline__ bool elect_one() {
    uint32_t r;
    asm volatile("{\n.reg .pred p;\nelect.sync _|p, 0xffffffff;\nselp.u32 %0, 1, 0, p;\n}\n" : "=r"(r));
    return r;
}
__device__ __forceinline__ void delay(uint32_t clks) {
    uint32_t t0, t1;
    asm volatile("mov.u32 %0, %%clock;" : "=r"(t0) :: "memory");
    do { asm volatile("mov.u32 %0, %%clock;" : "=r"(t1) :: "memory"); } while (t1 - t0 < clks);
}
__device__ __forceinline__ void fence_async() { asm volatile("fence.proxy.async.shared::cta;\n" ::: "memory"); }

__device__ __forceinline__ float2 cmul(float2 a, float2 b) {
    return make_float2(fmaf(a.x, b.x, -a.y * b.y), fmaf(a.x, b.y, a.y * b.x));
}
__device__ __forceinline__ float2 csq(float2 a) {
    float p = a.x * a.y;
    return make_float2(fmaf(a.x, a.x, -a.y * a.y), p + p);
}
__device__ __forceinline__ float ex2_approx(float x) { float r; asm("ex2.approx.ftz.f32 %0, %1;\n" : "=f"(r) : "f"(x)); return r; }
__device__ __forceinline__ float exp_bf(float x) { return rbf(ex2_approx(__fmul_ru(x, 1.4426950408889634f))); }
__device__ __forceinline__ float2 cexp_e(float lr2, float li, float e) {
    const float m = ex2_approx(lr2 * e);
    return make_float2(m * __cosf(li * e), m * __sinf(li * e));
}
__device__ __forceinline__ float rcp_approx(float x) { float r; asm("rcp.approx.ftz.f32 %0, %1;\n" : "=f"(r) : "f"(x)); return r; }
__device__ __forceinline__ float sigmoid_f(float x) { return rcp_approx(1.0f + ex2_approx(x * -1.4426950408889634f)); }
__device__ __forceinline__ float sqrt_approx(float x) { float r; asm("sqrt.approx.ftz.f32 %0, %1;\n" : "=f"(r) : "f"(x)); return r; }

__device__ __forceinline__ void wg_fence() { asm volatile("wgmma.fence.sync.aligned;\n" ::: "memory"); }
__device__ __forceinline__ void wg_commit() { asm volatile("wgmma.commit_group.sync.aligned;\n" ::: "memory"); }
__device__ __forceinline__ void wg_wait0() { asm volatile("wgmma.wait_group.sync.aligned 0;\n" ::: "memory"); }
template <int T> __device__ __forceinline__ void wg_mma(float (&acc)[16][4], const uint32_t* a, uint64_t desc);
template <int T> __device__ __forceinline__ void wg_first(float (&acc)[16][4], const uint32_t* a, uint64_t desc);
template <> __device__ __forceinline__ void wg_mma<0>(float (&acc)[16][4], const uint32_t* a, uint64_t desc) {
    asm volatile("wgmma.mma_async.sync.aligned.m64n128k16.f32.f16.f16 {%0,%1,%2,%3,%4,%5,%6,%7,%8,%9,%10,%11,%12,%13,%14,%15,%16,%17,%18,%19,%20,%21,%22,%23,%24,%25,%26,%27,%28,%29,%30,%31,%32,%33,%34,%35,%36,%37,%38,%39,%40,%41,%42,%43,%44,%45,%46,%47,%48,%49,%50,%51,%52,%53,%54,%55,%56,%57,%58,%59,%60,%61,%62,%63}, {%64,%65,%66,%67}, %68, 1, 1, 1, 0;\n"
                 : "+f"(acc[0][0]), "+f"(acc[0][1]), "+f"(acc[0][2]), "+f"(acc[0][3]), "+f"(acc[1][0]), "+f"(acc[1][1]), "+f"(acc[1][2]), "+f"(acc[1][3]), "+f"(acc[2][0]), "+f"(acc[2][1]), "+f"(acc[2][2]), "+f"(acc[2][3]), "+f"(acc[3][0]), "+f"(acc[3][1]), "+f"(acc[3][2]), "+f"(acc[3][3]), "+f"(acc[4][0]), "+f"(acc[4][1]), "+f"(acc[4][2]), "+f"(acc[4][3]), "+f"(acc[5][0]), "+f"(acc[5][1]), "+f"(acc[5][2]), "+f"(acc[5][3]), "+f"(acc[6][0]), "+f"(acc[6][1]), "+f"(acc[6][2]), "+f"(acc[6][3]), "+f"(acc[7][0]), "+f"(acc[7][1]), "+f"(acc[7][2]), "+f"(acc[7][3]), "+f"(acc[8][0]), "+f"(acc[8][1]), "+f"(acc[8][2]), "+f"(acc[8][3]), "+f"(acc[9][0]), "+f"(acc[9][1]), "+f"(acc[9][2]), "+f"(acc[9][3]), "+f"(acc[10][0]), "+f"(acc[10][1]), "+f"(acc[10][2]), "+f"(acc[10][3]), "+f"(acc[11][0]), "+f"(acc[11][1]), "+f"(acc[11][2]), "+f"(acc[11][3]), "+f"(acc[12][0]), "+f"(acc[12][1]), "+f"(acc[12][2]), "+f"(acc[12][3]), "+f"(acc[13][0]), "+f"(acc[13][1]), "+f"(acc[13][2]), "+f"(acc[13][3]), "+f"(acc[14][0]), "+f"(acc[14][1]), "+f"(acc[14][2]), "+f"(acc[14][3]), "+f"(acc[15][0]), "+f"(acc[15][1]), "+f"(acc[15][2]), "+f"(acc[15][3])
                 : "r"(a[0]), "r"(a[1]), "r"(a[2]), "r"(a[3]), "l"(desc));
}
template <> __device__ __forceinline__ void wg_mma<2>(float (&acc)[16][4], const uint32_t* a, uint64_t desc) {
    asm volatile("wgmma.mma_async.sync.aligned.m64n112k16.f32.f16.f16 {%0,%1,%2,%3,%4,%5,%6,%7,%8,%9,%10,%11,%12,%13,%14,%15,%16,%17,%18,%19,%20,%21,%22,%23,%24,%25,%26,%27,%28,%29,%30,%31,%32,%33,%34,%35,%36,%37,%38,%39,%40,%41,%42,%43,%44,%45,%46,%47,%48,%49,%50,%51,%52,%53,%54,%55}, {%56,%57,%58,%59}, %60, 1, 1, 1, 0;\n"
                 : "+f"(acc[2][0]), "+f"(acc[2][1]), "+f"(acc[2][2]), "+f"(acc[2][3]), "+f"(acc[3][0]), "+f"(acc[3][1]), "+f"(acc[3][2]), "+f"(acc[3][3]), "+f"(acc[4][0]), "+f"(acc[4][1]), "+f"(acc[4][2]), "+f"(acc[4][3]), "+f"(acc[5][0]), "+f"(acc[5][1]), "+f"(acc[5][2]), "+f"(acc[5][3]), "+f"(acc[6][0]), "+f"(acc[6][1]), "+f"(acc[6][2]), "+f"(acc[6][3]), "+f"(acc[7][0]), "+f"(acc[7][1]), "+f"(acc[7][2]), "+f"(acc[7][3]), "+f"(acc[8][0]), "+f"(acc[8][1]), "+f"(acc[8][2]), "+f"(acc[8][3]), "+f"(acc[9][0]), "+f"(acc[9][1]), "+f"(acc[9][2]), "+f"(acc[9][3]), "+f"(acc[10][0]), "+f"(acc[10][1]), "+f"(acc[10][2]), "+f"(acc[10][3]), "+f"(acc[11][0]), "+f"(acc[11][1]), "+f"(acc[11][2]), "+f"(acc[11][3]), "+f"(acc[12][0]), "+f"(acc[12][1]), "+f"(acc[12][2]), "+f"(acc[12][3]), "+f"(acc[13][0]), "+f"(acc[13][1]), "+f"(acc[13][2]), "+f"(acc[13][3]), "+f"(acc[14][0]), "+f"(acc[14][1]), "+f"(acc[14][2]), "+f"(acc[14][3]), "+f"(acc[15][0]), "+f"(acc[15][1]), "+f"(acc[15][2]), "+f"(acc[15][3])
                 : "r"(a[0]), "r"(a[1]), "r"(a[2]), "r"(a[3]), "l"(desc));
}
template <> __device__ __forceinline__ void wg_mma<4>(float (&acc)[16][4], const uint32_t* a, uint64_t desc) {
    asm volatile("wgmma.mma_async.sync.aligned.m64n96k16.f32.f16.f16 {%0,%1,%2,%3,%4,%5,%6,%7,%8,%9,%10,%11,%12,%13,%14,%15,%16,%17,%18,%19,%20,%21,%22,%23,%24,%25,%26,%27,%28,%29,%30,%31,%32,%33,%34,%35,%36,%37,%38,%39,%40,%41,%42,%43,%44,%45,%46,%47}, {%48,%49,%50,%51}, %52, 1, 1, 1, 0;\n"
                 : "+f"(acc[4][0]), "+f"(acc[4][1]), "+f"(acc[4][2]), "+f"(acc[4][3]), "+f"(acc[5][0]), "+f"(acc[5][1]), "+f"(acc[5][2]), "+f"(acc[5][3]), "+f"(acc[6][0]), "+f"(acc[6][1]), "+f"(acc[6][2]), "+f"(acc[6][3]), "+f"(acc[7][0]), "+f"(acc[7][1]), "+f"(acc[7][2]), "+f"(acc[7][3]), "+f"(acc[8][0]), "+f"(acc[8][1]), "+f"(acc[8][2]), "+f"(acc[8][3]), "+f"(acc[9][0]), "+f"(acc[9][1]), "+f"(acc[9][2]), "+f"(acc[9][3]), "+f"(acc[10][0]), "+f"(acc[10][1]), "+f"(acc[10][2]), "+f"(acc[10][3]), "+f"(acc[11][0]), "+f"(acc[11][1]), "+f"(acc[11][2]), "+f"(acc[11][3]), "+f"(acc[12][0]), "+f"(acc[12][1]), "+f"(acc[12][2]), "+f"(acc[12][3]), "+f"(acc[13][0]), "+f"(acc[13][1]), "+f"(acc[13][2]), "+f"(acc[13][3]), "+f"(acc[14][0]), "+f"(acc[14][1]), "+f"(acc[14][2]), "+f"(acc[14][3]), "+f"(acc[15][0]), "+f"(acc[15][1]), "+f"(acc[15][2]), "+f"(acc[15][3])
                 : "r"(a[0]), "r"(a[1]), "r"(a[2]), "r"(a[3]), "l"(desc));
}
template <> __device__ __forceinline__ void wg_mma<6>(float (&acc)[16][4], const uint32_t* a, uint64_t desc) {
    asm volatile("wgmma.mma_async.sync.aligned.m64n80k16.f32.f16.f16 {%0,%1,%2,%3,%4,%5,%6,%7,%8,%9,%10,%11,%12,%13,%14,%15,%16,%17,%18,%19,%20,%21,%22,%23,%24,%25,%26,%27,%28,%29,%30,%31,%32,%33,%34,%35,%36,%37,%38,%39}, {%40,%41,%42,%43}, %44, 1, 1, 1, 0;\n"
                 : "+f"(acc[6][0]), "+f"(acc[6][1]), "+f"(acc[6][2]), "+f"(acc[6][3]), "+f"(acc[7][0]), "+f"(acc[7][1]), "+f"(acc[7][2]), "+f"(acc[7][3]), "+f"(acc[8][0]), "+f"(acc[8][1]), "+f"(acc[8][2]), "+f"(acc[8][3]), "+f"(acc[9][0]), "+f"(acc[9][1]), "+f"(acc[9][2]), "+f"(acc[9][3]), "+f"(acc[10][0]), "+f"(acc[10][1]), "+f"(acc[10][2]), "+f"(acc[10][3]), "+f"(acc[11][0]), "+f"(acc[11][1]), "+f"(acc[11][2]), "+f"(acc[11][3]), "+f"(acc[12][0]), "+f"(acc[12][1]), "+f"(acc[12][2]), "+f"(acc[12][3]), "+f"(acc[13][0]), "+f"(acc[13][1]), "+f"(acc[13][2]), "+f"(acc[13][3]), "+f"(acc[14][0]), "+f"(acc[14][1]), "+f"(acc[14][2]), "+f"(acc[14][3]), "+f"(acc[15][0]), "+f"(acc[15][1]), "+f"(acc[15][2]), "+f"(acc[15][3])
                 : "r"(a[0]), "r"(a[1]), "r"(a[2]), "r"(a[3]), "l"(desc));
}
template <> __device__ __forceinline__ void wg_mma<8>(float (&acc)[16][4], const uint32_t* a, uint64_t desc) {
    asm volatile("wgmma.mma_async.sync.aligned.m64n64k16.f32.f16.f16 {%0,%1,%2,%3,%4,%5,%6,%7,%8,%9,%10,%11,%12,%13,%14,%15,%16,%17,%18,%19,%20,%21,%22,%23,%24,%25,%26,%27,%28,%29,%30,%31}, {%32,%33,%34,%35}, %36, 1, 1, 1, 0;\n"
                 : "+f"(acc[8][0]), "+f"(acc[8][1]), "+f"(acc[8][2]), "+f"(acc[8][3]), "+f"(acc[9][0]), "+f"(acc[9][1]), "+f"(acc[9][2]), "+f"(acc[9][3]), "+f"(acc[10][0]), "+f"(acc[10][1]), "+f"(acc[10][2]), "+f"(acc[10][3]), "+f"(acc[11][0]), "+f"(acc[11][1]), "+f"(acc[11][2]), "+f"(acc[11][3]), "+f"(acc[12][0]), "+f"(acc[12][1]), "+f"(acc[12][2]), "+f"(acc[12][3]), "+f"(acc[13][0]), "+f"(acc[13][1]), "+f"(acc[13][2]), "+f"(acc[13][3]), "+f"(acc[14][0]), "+f"(acc[14][1]), "+f"(acc[14][2]), "+f"(acc[14][3]), "+f"(acc[15][0]), "+f"(acc[15][1]), "+f"(acc[15][2]), "+f"(acc[15][3])
                 : "r"(a[0]), "r"(a[1]), "r"(a[2]), "r"(a[3]), "l"(desc));
}
template <> __device__ __forceinline__ void wg_mma<10>(float (&acc)[16][4], const uint32_t* a, uint64_t desc) {
    asm volatile("wgmma.mma_async.sync.aligned.m64n48k16.f32.f16.f16 {%0,%1,%2,%3,%4,%5,%6,%7,%8,%9,%10,%11,%12,%13,%14,%15,%16,%17,%18,%19,%20,%21,%22,%23}, {%24,%25,%26,%27}, %28, 1, 1, 1, 0;\n"
                 : "+f"(acc[10][0]), "+f"(acc[10][1]), "+f"(acc[10][2]), "+f"(acc[10][3]), "+f"(acc[11][0]), "+f"(acc[11][1]), "+f"(acc[11][2]), "+f"(acc[11][3]), "+f"(acc[12][0]), "+f"(acc[12][1]), "+f"(acc[12][2]), "+f"(acc[12][3]), "+f"(acc[13][0]), "+f"(acc[13][1]), "+f"(acc[13][2]), "+f"(acc[13][3]), "+f"(acc[14][0]), "+f"(acc[14][1]), "+f"(acc[14][2]), "+f"(acc[14][3]), "+f"(acc[15][0]), "+f"(acc[15][1]), "+f"(acc[15][2]), "+f"(acc[15][3])
                 : "r"(a[0]), "r"(a[1]), "r"(a[2]), "r"(a[3]), "l"(desc));
}
template <> __device__ __forceinline__ void wg_mma<12>(float (&acc)[16][4], const uint32_t* a, uint64_t desc) {
    asm volatile("wgmma.mma_async.sync.aligned.m64n32k16.f32.f16.f16 {%0,%1,%2,%3,%4,%5,%6,%7,%8,%9,%10,%11,%12,%13,%14,%15}, {%16,%17,%18,%19}, %20, 1, 1, 1, 0;\n"
                 : "+f"(acc[12][0]), "+f"(acc[12][1]), "+f"(acc[12][2]), "+f"(acc[12][3]), "+f"(acc[13][0]), "+f"(acc[13][1]), "+f"(acc[13][2]), "+f"(acc[13][3]), "+f"(acc[14][0]), "+f"(acc[14][1]), "+f"(acc[14][2]), "+f"(acc[14][3]), "+f"(acc[15][0]), "+f"(acc[15][1]), "+f"(acc[15][2]), "+f"(acc[15][3])
                 : "r"(a[0]), "r"(a[1]), "r"(a[2]), "r"(a[3]), "l"(desc));
}
template <> __device__ __forceinline__ void wg_mma<14>(float (&acc)[16][4], const uint32_t* a, uint64_t desc) {
    asm volatile("wgmma.mma_async.sync.aligned.m64n16k16.f32.f16.f16 {%0,%1,%2,%3,%4,%5,%6,%7}, {%8,%9,%10,%11}, %12, 1, 1, 1, 0;\n"
                 : "+f"(acc[14][0]), "+f"(acc[14][1]), "+f"(acc[14][2]), "+f"(acc[14][3]), "+f"(acc[15][0]), "+f"(acc[15][1]), "+f"(acc[15][2]), "+f"(acc[15][3])
                 : "r"(a[0]), "r"(a[1]), "r"(a[2]), "r"(a[3]), "l"(desc));
}
template <> __device__ __forceinline__ void wg_first<0>(float (&acc)[16][4], const uint32_t* a, uint64_t desc) {
    asm volatile("wgmma.mma_async.sync.aligned.m64n128k16.f32.f16.f16 {%0,%1,%2,%3,%4,%5,%6,%7,%8,%9,%10,%11,%12,%13,%14,%15,%16,%17,%18,%19,%20,%21,%22,%23,%24,%25,%26,%27,%28,%29,%30,%31,%32,%33,%34,%35,%36,%37,%38,%39,%40,%41,%42,%43,%44,%45,%46,%47,%48,%49,%50,%51,%52,%53,%54,%55,%56,%57,%58,%59,%60,%61,%62,%63}, {%64,%65,%66,%67}, %68, 0, 1, 1, 0;\n"
                 : "=f"(acc[0][0]), "=f"(acc[0][1]), "=f"(acc[0][2]), "=f"(acc[0][3]), "=f"(acc[1][0]), "=f"(acc[1][1]), "=f"(acc[1][2]), "=f"(acc[1][3]), "=f"(acc[2][0]), "=f"(acc[2][1]), "=f"(acc[2][2]), "=f"(acc[2][3]), "=f"(acc[3][0]), "=f"(acc[3][1]), "=f"(acc[3][2]), "=f"(acc[3][3]), "=f"(acc[4][0]), "=f"(acc[4][1]), "=f"(acc[4][2]), "=f"(acc[4][3]), "=f"(acc[5][0]), "=f"(acc[5][1]), "=f"(acc[5][2]), "=f"(acc[5][3]), "=f"(acc[6][0]), "=f"(acc[6][1]), "=f"(acc[6][2]), "=f"(acc[6][3]), "=f"(acc[7][0]), "=f"(acc[7][1]), "=f"(acc[7][2]), "=f"(acc[7][3]), "=f"(acc[8][0]), "=f"(acc[8][1]), "=f"(acc[8][2]), "=f"(acc[8][3]), "=f"(acc[9][0]), "=f"(acc[9][1]), "=f"(acc[9][2]), "=f"(acc[9][3]), "=f"(acc[10][0]), "=f"(acc[10][1]), "=f"(acc[10][2]), "=f"(acc[10][3]), "=f"(acc[11][0]), "=f"(acc[11][1]), "=f"(acc[11][2]), "=f"(acc[11][3]), "=f"(acc[12][0]), "=f"(acc[12][1]), "=f"(acc[12][2]), "=f"(acc[12][3]), "=f"(acc[13][0]), "=f"(acc[13][1]), "=f"(acc[13][2]), "=f"(acc[13][3]), "=f"(acc[14][0]), "=f"(acc[14][1]), "=f"(acc[14][2]), "=f"(acc[14][3]), "=f"(acc[15][0]), "=f"(acc[15][1]), "=f"(acc[15][2]), "=f"(acc[15][3])
                 : "r"(a[0]), "r"(a[1]), "r"(a[2]), "r"(a[3]), "l"(desc));
}
template <> __device__ __forceinline__ void wg_first<4>(float (&acc)[16][4], const uint32_t* a, uint64_t desc) {
    asm volatile("wgmma.mma_async.sync.aligned.m64n96k16.f32.f16.f16 {%0,%1,%2,%3,%4,%5,%6,%7,%8,%9,%10,%11,%12,%13,%14,%15,%16,%17,%18,%19,%20,%21,%22,%23,%24,%25,%26,%27,%28,%29,%30,%31,%32,%33,%34,%35,%36,%37,%38,%39,%40,%41,%42,%43,%44,%45,%46,%47}, {%48,%49,%50,%51}, %52, 0, 1, 1, 0;\n"
                 : "=f"(acc[4][0]), "=f"(acc[4][1]), "=f"(acc[4][2]), "=f"(acc[4][3]), "=f"(acc[5][0]), "=f"(acc[5][1]), "=f"(acc[5][2]), "=f"(acc[5][3]), "=f"(acc[6][0]), "=f"(acc[6][1]), "=f"(acc[6][2]), "=f"(acc[6][3]), "=f"(acc[7][0]), "=f"(acc[7][1]), "=f"(acc[7][2]), "=f"(acc[7][3]), "=f"(acc[8][0]), "=f"(acc[8][1]), "=f"(acc[8][2]), "=f"(acc[8][3]), "=f"(acc[9][0]), "=f"(acc[9][1]), "=f"(acc[9][2]), "=f"(acc[9][3]), "=f"(acc[10][0]), "=f"(acc[10][1]), "=f"(acc[10][2]), "=f"(acc[10][3]), "=f"(acc[11][0]), "=f"(acc[11][1]), "=f"(acc[11][2]), "=f"(acc[11][3]), "=f"(acc[12][0]), "=f"(acc[12][1]), "=f"(acc[12][2]), "=f"(acc[12][3]), "=f"(acc[13][0]), "=f"(acc[13][1]), "=f"(acc[13][2]), "=f"(acc[13][3]), "=f"(acc[14][0]), "=f"(acc[14][1]), "=f"(acc[14][2]), "=f"(acc[14][3]), "=f"(acc[15][0]), "=f"(acc[15][1]), "=f"(acc[15][2]), "=f"(acc[15][3])
                 : "r"(a[0]), "r"(a[1]), "r"(a[2]), "r"(a[3]), "l"(desc));
}

#define EARLYN 2
#define K8 0
#define HOLD 3
#define MC 1
#define STAMPW(i) STAMPY(i)
#define STAMP2(i) STAMP(i)
#undef STAMPX
#define STAMPX(i)
#define PBAR 1
#define WDLY 500
#define CBAR 1
#define FDLY 900
#define FDLY2 0
#define YDLY 1
#define YFROM 0
#define YPRE 0
#define KDLY 850
#define OEARLY 0
#define ODLY 0
#define SORD 1
#define SDLY 900
#define UDLY 1400
#define XCP 1
#define DEFER 0
#define EXP 0
#define XWHEN 0
#define RWHEN 0
#define HW 11
#define PEARLY 1
#define XG 6
struct Params {
    const bf16 *x, *lar, *aim, *cre, *cim, *ldt, *dsk;
    Scratch* s;
    const bf16 *wr, *wg, *wu, *wd;
    bf16* out;
};

#define TOK(g) (2 * (g) - ((g) & 1))
#define ROWTOK(r) (TOK((r) & 7) + (((r) >> 2) & 2))
__device__ __forceinline__ void ln_partial(const uint32_t (&H)[2][4], uint32_t lp, int warp, int g, int t) {
    float cs[4] = {0.f, 0.f, 0.f, 0.f}, cl[4] = {0.f, 0.f, 0.f, 0.f}, ch[4] = {0.f, 0.f, 0.f, 0.f};
#pragma unroll
    for (int k = 0; k < 4; k += 2) {
        mma_bf16(cs, H[0][k], H[1][k], H[0][k + 1], H[1][k + 1], 0x3f803f80u, 0x3f803f80u);
        mma_bf16(cl, H[0][k], H[1][k], H[0][k + 1], H[1][k + 1], H[0][k], H[0][k + 1]);
        mma_bf16(ch, H[0][k], H[1][k], H[0][k + 1], H[1][k + 1], H[1][k], H[1][k + 1]);
    }
    const uint32_t a = lp + (g * 20 + warp) * 4;
    if (t == (g >> 1)) { stsf(a, cs[0]); stsf(a + 8 * 80, cs[2]); stsf(a + 16 * 80, (g & 1) ? cl[1] : cl[0]); stsf(a + 24 * 80, (g & 1) ? ch[3] : ch[2]); }
}
__device__ __forceinline__ float sum18(uint32_t a) {
    const uint4 p = lds128(a), q = lds128(a + 16), r = lds128(a + 32), s = lds128(a + 48);
    const uint2 u = lds64(a + 64);
#define F(x) __uint_as_float(x)
    return (((F(p.x) + F(p.y)) + (F(p.z) + F(p.w))) + ((F(q.x) + F(q.y)) + (F(q.z) + F(q.w)))) +
           (((F(r.x) + F(r.y)) + (F(r.z) + F(r.w))) + ((F(s.x) + F(s.y)) + (F(s.z) + F(s.w))) + (F(u.x) + F(u.y)));
#undef F
}
__device__ __forceinline__ void ln_stats(float sm, float sq, float& mb, float& sd) {
    const float m0 = sm * (1.0f / 576.0f);
    const float mean = fmaf(fmaf(-m0, 576.0f, sm), 1.0f / 576.0f, m0);
    const float var = fmaxf(fmaf(-mean, mean, sq * (1.0f / 576.0f)), 0.f);
    mb = rbf(mean);
    sd = rbf(sqrt_approx(rbf(rbf(var) + 1e-5f)));
}
__device__ __forceinline__ void ln_finish(float v, int lane, float& mb, float& rc) {
    const float o = __shfl_xor_sync(0xffffffffu, v, 16);
    float sd;
    ln_stats(lane < 16 ? v : o, lane < 16 ? o : v, mb, sd);
    rc = rcp_approx(sd);
}
__device__ __forceinline__ uint32_t ln_apply(uint32_t w, uint32_t m2, uint32_t rh, uint32_t rl) {
    const uint32_t d = hsub2_bf(w, m2);
    return hfma2_bf(d, rh, hmul2_bf(d, rl));
}
__device__ __forceinline__ void stat_store(uint32_t a, float mb, float rc, uint32_t extra) {
    const float rh = rbf(rc);
    sts64(a, (__float_as_uint(mb) >> 16) | (extra << 16), pack_bf16(rh, rc - rh));
}
#define STAT_M(s) __byte_perm((s).x, (s).x, 0x1010)
#define STAT_H(s) __byte_perm((s).y, (s).y, 0x1010)
#define STAT_L(s) __byte_perm((s).y, (s).y, 0x3232)

__device__ __forceinline__ void hcmul(uint32_t re, uint32_t im, uint32_t zx, uint32_t zy, uint32_t& ore, uint32_t& oim) {
    ore = hfms2(im, zy, hmul2(re, zx));
    oim = hfma2(re, zy, hmul2(im, zx));
}

struct KGen {
    uint32_t A[2][4][4];
    float2 z1, z8, z64, z128, T[9];
};
__device__ __forceinline__ void kgen_setup(KGen& k, float lar, float aim, float dt) {
    const float lr2 = -(exp_bf(lar) * dt) * 1.4426950408889634f, li = aim * dt;
    k.z1 = cexp_e(lr2, li, 1.0f);
    k.z8 = cexp_e(lr2, li, 8.0f);
    k.z64 = cexp_e(lr2, li, 64.0f);
}
__device__ __forceinline__ void kgen_rows(KGen& k, uint32_t tb, int lane) {
    const float2 z8 = k.z8, z64 = k.z64;
    const uint32_t row = tb + lane * 16;
    k.z128 = csq(z64);
    const float2 z16 = csq(z8), z24 = cmul(z16, z8), z32 = csq(z16), z40 = cmul(z32, z8), z48 = csq(z24), z56 = cmul(z32, z24);
    uint32_t re[4], im[4], a[4], b[4];
    re[0] = pack_f16(1.0f, z8.x); im[0] = pack_f16(0.0f, z8.y);
    re[1] = pack_f16(z16.x, z24.x); im[1] = pack_f16(z16.y, z24.y);
    re[2] = pack_f16(z32.x, z40.x); im[2] = pack_f16(z32.y, z40.y);
    re[3] = pack_f16(z48.x, z56.x); im[3] = pack_f16(z48.y, z56.y);
    sts128(row, re[0], re[1], re[2], re[3]);
    sts128(row + 1024, im[0], im[1], im[2], im[3]);
    const uint32_t zx = pack_f16(z64.x, z64.x), zy = pack_f16(z64.y, z64.y), zw = pack_f16(k.z128.x, k.z128.y);
#pragma unroll
    for (int j = 0; j < 4; j++) hcmul(re[j], im[j], zx, zy, a[j], b[j]);
    sts128(row + 512, a[0], a[1], a[2], a[3]);
    sts128(row + 1536, b[0], b[1], b[2], b[3]);
    const int mi = lane >> 3;
    const uint32_t zd = tb + 2048 + mi * 16;
    sts16(tb + 2048 + lane * 2, zw); sts16(tb + 2112 + lane * 2, zw >> 16);
    __syncwarp();
    const uint32_t ad = tb + (lane & 7) * 16 + mi * 512;
    ldsm_x4(a[0], a[1], a[2], a[3], zd);
    ldsm_x4(b[0], b[1], b[2], b[3], zd + 64);
#pragma unroll
    for (int ks = 0; ks < 4; ks++) {
        ldsm_x4_t(k.A[0][ks][0], k.A[0][ks][1], k.A[0][ks][2], k.A[0][ks][3], ad + ks * 128);
        hcmul(k.A[0][ks][0], k.A[0][ks][2], a[ks], b[ks], k.A[1][ks][0], k.A[1][ks][2]);
        hcmul(k.A[0][ks][1], k.A[0][ks][3], a[ks], b[ks], k.A[1][ks][1], k.A[1][ks][3]);
    }
}
__device__ __forceinline__ void kgen_chain(KGen& k, uint32_t cr, uint32_t ci, float cs) {
    k.T[0] = make_float2(bf_lo(cr) * cs, -bf_lo(ci) * cs);
    const float2 y1 = make_float2(k.z1.x, -k.z1.y);
#pragma unroll
    for (int c = 1; c < 8; c++) k.T[c] = cmul(k.T[c - 1], y1);
    k.T[8] = cmul(k.T[0], make_float2(k.z8.x, -k.z8.y));
}
__device__ __forceinline__ void kgen_cols(KGen& k, uint32_t tb, uint32_t t5, int lane) {
    const uint32_t row = tb + lane * 16;
    const float2 (&T)[9] = k.T;
    const float2 y128 = make_float2(k.z128.x, -k.z128.y);
    const float2 y256 = csq(y128), y512 = csq(y256), y768 = cmul(y512, y256), y1024 = csq(y512);
    const float2 c1032 = cmul(T[8], y1024);
    __syncwarp();
    sts128(row, pack_f16(T[0].x, T[1].x), pack_f16(T[2].x, T[3].x), pack_f16(T[4].x, T[5].x), pack_f16(T[6].x, T[7].x));
    sts128(row + 512, pack_f16(T[0].y, T[1].y), pack_f16(T[2].y, T[3].y), pack_f16(T[4].y, T[5].y), pack_f16(T[6].y, T[7].y));
    uint32_t a[4], b[4];
    {
        const uint32_t zx = pack_f16(y256.x, y256.x), zy = pack_f16(y256.y, y256.y);
        hcmul(pack_f16(T[0].x, T[2].x), pack_f16(T[0].y, T[2].y), zx, zy, a[0], b[0]);
        hcmul(pack_f16(T[4].x, T[6].x), pack_f16(T[4].y, T[6].y), zx, zy, a[1], b[1]);
        const uint32_t r04 = pack_f16(T[0].x, T[4].x), i04 = pack_f16(T[0].y, T[4].y);
        hcmul(r04, i04, pack_f16(y512.x, y512.x), pack_f16(y512.y, y512.y), a[2], b[2]);
        hcmul(r04, i04, pack_f16(y768.x, y768.x), pack_f16(y768.y, y768.y), a[3], b[3]);
    }
    sts128(row + 1024, a[0], a[1], a[2], a[3]);
    sts128(row + 1536, b[0], b[1], b[2], b[3]);
    {
        const uint32_t r0 = pack_f16(1.0f, y256.x), i0 = pack_f16(0.0f, y256.y), r1 = pack_f16(y512.x, y768.x), i1 = pack_f16(y512.y, y768.y);
        const uint32_t zx = pack_f16(T[8].x, T[8].x), zy = pack_f16(T[8].y, T[8].y), wx = pack_f16(c1032.x, c1032.x), wy = pack_f16(c1032.y, c1032.y);
        hcmul(r0, i0, zx, zy, a[0], b[0]); hcmul(r1, i1, zx, zy, a[1], b[1]);
        hcmul(r0, i0, wx, wy, a[2], b[2]); hcmul(r1, i1, wx, wy, a[3], b[3]);
    }
    sts128(row + 2048, a[0], a[1], a[2], a[3]);
    sts128(t5 + lane * 16, b[0], b[1], b[2], b[3]);
}
__device__ __forceinline__ void kgen_mma(const KGen& k, uint32_t tb, uint32_t t5, int lane, uint32_t hb) {
    __syncwarp();
    float acc[2][3][4];
#pragma unroll
    for (int i = 0; i < 6; i++)
#pragma unroll
        for (int j = 0; j < 4; j++) acc[i / 3][i % 3][j] = 0.f;
    const int mi = lane >> 3;
    const uint32_t ro = ((lane & 7) + 8 * (mi >> 1)) * 16, bd = tb + ro + (mi & 1) * 512, b2 = ro + ((mi & 1) ? t5 : tb + 2048);
#pragma unroll
    for (int kp = 0; kp < 2; kp++)
#pragma unroll
        for (int j = 0; j < 3; j++) {
            uint32_t b[4];
            if (HOLD == 5 && kp == 1 && j == 0) mbar_wait1(hb);
            ldsm_x4_t(b[0], b[1], b[2], b[3], (j < 2 ? bd + j * 1024 : b2) + kp * 256);
#pragma unroll
            for (int h = 0; h < 2; h++)
#pragma unroll
                for (int m = 0; m < 2; m++) {
                    const uint32_t (&A)[4] = k.A[m][2 * kp + h];
                    mma_f16(acc[m][j], A[0], A[1], A[2], A[3], b[2 * h], b[2 * h + 1]);
                }
        }
    __syncwarp();
#define PK(j) pack_f16(acc[0][j][0], acc[0][j][1]), pack_f16(acc[0][j][2], acc[0][j][3]), pack_f16(acc[1][j][0], acc[1][j][1]), pack_f16(acc[1][j][2], acc[1][j][3])
    stsm_x4(tb + lane * 16, PK(0));
    stsm_x4(tb + 512 + lane * 16, PK(1));
    stsm_x4_t(tb + 1024 + (lane & 7) * 80 + mi * 16, PK(2));
#undef PK
}
__device__ __forceinline__ uint32_t table_buf(uint32_t sb, int warp) { return sb + SM_PL + warp * TBW; }

__device__ __forceinline__ uint4 lds16x4(uint32_t a) { return make_uint4(lds16(a), lds16(a + TBW), lds16(a + 2 * TBW), lds16(a + 3 * TBW)); }
__device__ __forceinline__ void combine_setup(uint32_t sb, int warp, int lane, uint32_t kw, uint32_t& o, uint32_t& n, uint32_t& d) {
    const int wq = warp & 3;
    const uint32_t a = table_buf(sb, warp & ~3);
    o = wq == 3 ? a + 1024 + 320 + (lane >> 3) * 80 + (lane & 7) * 8 : a + (wq ? 504 + wq * 8 : 0) + lane * 16;
    n = a + 1024 + wq * 80 + lane * 2;
    d = wq < 3 ? kw + (wq == 2 ? KW_P : 32 + wq * 512) + lane * 16 : kw + KW_H + 8 + lane * 8;
}
__device__ __forceinline__ void kgen_combine(int wq, int lane, uint32_t o, uint32_t na, uint32_t d) {
#define S4(f) hadd2(hadd2(u.f, v.f), hadd2(w.f, x.f))
#define H4(v) hadd2(hadd2(v.x, v.y), hadd2(v.z, v.w))
#define BP __byte_perm
    if (wq == 0) {
        const uint4 u = lds128(o), v = lds128(o + TBW), w = lds128(o + 2 * TBW), x = lds128(o + 3 * TBW), nn = lds16x4(na);
        const uint32_t n = H4(nn), k0 = S4(x), k2 = S4(y), k4 = S4(z), k6 = S4(w);
        sts128(d, BP(k0, k0, 0x1032), BP(k0, k2, 0x3254), BP(k2, k2, 0x1032), BP(k2, k4, 0x3254));
        sts128(d + KW_PL, BP(k4, k4, 0x1032), BP(k4, k6, 0x3254), BP(k6, k6, 0x1032), BP(k6, n, 0x3254));
        if (lane == 0) sts32(d + KW_PL - 4, k0 & 0xffffu);
    } else {
        const uint2 u = lds64(o), v = lds64(o + TBW), w = lds64(o + 2 * TBW), x = lds64(o + 3 * TBW);
        uint4 nn = make_uint4(0u, 0u, 0u, 0u), mm = nn;
        if (wq < 3) nn = lds16x4(na);
        if (wq == 2) mm = lds16x4(na + 80);
        const uint32_t k0 = S4(x), k2 = S4(y), n = H4(nn), m = H4(mm);
        if (wq == 3) {
            sts64(d, k0, k2);
        } else if (wq == 1) {
            const uint32_t cc = BP(k2, k2, 0x1010);
            sts128(d, BP(k0, k0, 0x1010), BP(k0, k0, 0x1032), BP(k0, k2, 0x3254), cc);
            sts128(d + KW_PL, cc, BP(k2, k2, 0x1032), BP(k2, n, 0x3254), BP(n, n, 0x1010));
        } else {
            const uint32_t w40 = BP(k0, k0, 0x1032), w84 = BP(k0, n, 0x3254), w0 = BP(k0, k0, 0x1010), w4 = BP(k0, k0, 0x3232), w8 = BP(n, n, 0x1010);
            sts64(d, w40, w84);
            sts64(d + 512, BP(k2, k2, 0x1032), BP(k2, m, 0x3254));
            if (lane < 8) { sts128(d - (KW_P - 1056), w0, w0, w40, w4); sts128(d - (KW_P - 1056 - KW_PL), w4, w84, w8, w8); }
            if (lane == 31) sts16(d + (KW_H + 6 - KW_P - 496), m);
        }
    }
#undef S4
#undef H4
#undef BP
}

__device__ __forceinline__ int c_exponent(const uint2& r, const uint2& i, float dt) {
    const uint32_t mx = __vmaxu2(__vmaxu2(r.x & 0x7fff7fffu, r.y & 0x7fff7fffu), __vmaxu2(i.x & 0x7fff7fffu, i.y & 0x7fff7fffu));
    return __reduce_max_sync(0xffffffffu, max(mx, mx << 16) + (__float_as_uint(dt) & 0x7f800000u)) >> 23;
}

#define ONEBAR 1
__device__ __forceinline__ int warp_v() { int l; asm volatile("mov.u32 %0, %%tid.x;" : "=r"(l)); return __shfl_sync(0xffffffffu, l >> 5, 0); }
__device__ __forceinline__ int lane_v() { int l; asm volatile("mov.u32 %0, %%laneid;" : "=r"(l)); return l; }
__device__ __forceinline__ uint32_t prmt_v(uint32_t a, uint32_t b, uint32_t s) { uint32_t d; asm volatile("prmt.b32 %0, %1, %2, %3;\n" : "=r"(d) : "r"(a), "r"(b), "r"(s)); return d; }
__device__ __forceinline__ uint32_t mov_v(uint32_t a) { uint32_t d; asm volatile("mov.b32 %0, %1;\n" : "=r"(d) : "r"(a)); return d; }
template <int G>
__device__ __forceinline__ void conv_rename(float (&acc)[16][4]) {
#pragma unroll
    for (int i = G; i < 16; i++)
#pragma unroll
        for (int j = 0; j < 4; j++) { float v; asm volatile("mov.b32 %0, %1;\n" : "=f"(v) : "f"(acc[i][j])); acc[i][j] = v; }
}
struct Conv {
    uint32_t kw;
    uint32_t wa;
    uint32_t pa, s2;
    uint32_t s8;
    uint32_t id;
    uint32_t lc;
    uint32_t fs;
    uint32_t fl, yo;
    uint32_t yp;
    size_t ycopy;
    uint32_t ps;
    uint64_t d0;
    int warp;
};
struct Pk { uint32_t w[4]; };
__device__ __forceinline__ Pk pk2(const float (&u)[4], const float (&v)[4]) {
    Pk r;
    r.w[0] = pack_f16(u[0], u[1]); r.w[1] = pack_f16(u[2], u[3]); r.w[2] = pack_f16(v[0], v[1]); r.w[3] = pack_f16(v[2], v[3]);
    return r;
}
__device__ __forceinline__ void park(uint32_t a, const Pk& v) {
    asm volatile("stmatrix.sync.aligned.m8n8.x4.trans.shared.b16 [%0], {%1,%2,%3,%4};\n" ::"r"(a), "r"(v.w[0]), "r"(v.w[1]), "r"(v.w[2]), "r"(v.w[3]) : "memory");
}
__device__ __forceinline__ void conv_constants(uint32_t lc, int l) {
    const int d = (l >> 2) - 2 * (l & 3);
    const int e = d + 8, r4 = (e + 1 + ((e >> 2) & 1)) >> 2, p4 = (e + (((e - 1) >> 2) & 1)) >> 2;
    const uint32_t s2 = r4 == p4 ? 0x1010u : 0x3210u;
    sts64(lc + l * 8, KW_P + ((r4 - 5) >> 1) * 16 + ((r4 - 5) & 1) * 4, s2 | ((d < 0 ? s2 : 0x7654u) << 16));
    const int lo = (d >= 4) - (d < -3), ho = (d >= 5) - (d < -2), le = (d > 4) - (d < -4), he = (d > 5) - (d < -3);
    sts32(lc + 512 + l * 8, (0x5454u + lo * 0x22 + ho * 0x2200) | ((0x3232u + le * 0x22 + he * 0x2200) << 16));
    const int cc = l >> 2, j = l & 3;
    sts64(lc + 256 + l * 8, (j >> 1) * PL_HALF + (16 + cc) * 16 + (j & 1) * 8, (cc >> 1) * (DM * 64) + (cc & 1) * 32 + j * 8);
}
__device__ __forceinline__ void conv_selectors4(Conv& c) {
    const uint2 v = lds64(c.lc + lane_v() * 8);
    c.pa = v.x; c.s2 = v.y;
}
__device__ __forceinline__ void conv_selectors8(Conv& c) { c.s8 = lds32(c.lc + 512 + lane_v() * 8); }
template <int G, int I0, int I1>
__device__ __forceinline__ void conv_load(const Conv& c, uint32_t (&q)[9]) {
    const int wq = c.warp & 3;
    if (G < 2) {
#pragma unroll
        for (int i = I0; i < I1; i++) q[i] = lds32(c.wa + G * 512 + i * 16);
    } else if (G < 4) {
        const uint32_t a = (G == 2 && wq == 0) ? c.wa + 1024 : c.pa + c.kw + wq * 128 + (G < 2 ? 0 : G - 2) * 512;
#pragma unroll
        for (int i = I0; i < I1; i++) q[i] = lds32(a + i * 16);
    } else {
        const uint4 u = lds128(c.kw + KW_H + (G < 4 ? 0 : G - 4) * 64 + wq * 16);
        const uint2 v = lds64(c.kw + KW_H + (G < 4 ? 0 : G - 4) * 64 + wq * 16 + 16);
        q[0] = u.x; q[1] = u.y; q[2] = u.z; q[3] = u.w; q[4] = v.x; q[5] = v.y;
        if (G == 4 && wq == 0) { q[6] = lds32(c.pa + c.kw + 1024); q[7] = lds32(c.pa + c.kw + 1040); }
    }
}
template <int G, int J0, int J1>
__device__ __forceinline__ void conv_frag(const Conv& c, const uint32_t (&q)[9], uint32_t* a, const Pk& dp) {
    const uint32_t dep = dp.w[0];
    if (G < 4) {
        const uint32_t s = (G < 2 || (G == 2 && (c.warp & 3) == 0)) ? c.id : c.s2;
#pragma unroll
        for (int j = J0; j < J1; j++) {
            uint32_t* o = a + 4 * (j - J0);
            o[0] = prmt_v(q[2 * j + 1], dp.w[0], s); o[1] = prmt_v(q[2 * j + 2], dp.w[1], s); o[2] = prmt_v(q[2 * j], dp.w[2], s); o[3] = prmt_v(q[2 * j + 1], dp.w[3], s);
        }
    } else {
        const uint32_t so = prmt_v(c.s8, dep, c.id), se = prmt_v(c.s8, dep, c.id + 0x22);
#pragma unroll
        for (int j = J0; j < J1; j++) {
            uint32_t* o = a + 4 * (j - J0);
            o[0] = prmt_v(q[j + 1], q[j + 2], se); o[1] = prmt_v(q[j + 1], q[j + 2], so); o[2] = prmt_v(q[j], q[j + 1], so);
            if (G == 4 && j == 0 && (c.warp & 3) == 0) {
                o[2] = prmt_v(q[6], dep, c.s2);
                o[0] = prmt_v(q[7], o[0], c.s2 >> 16);
            }
            o[3] = mov_v(o[0]);
        }
    }
}
template <int G, int J0, int J1>
__device__ __forceinline__ void conv_frag(const Conv& c, const uint32_t (&q)[9], uint32_t* a, float depf) {
    const uint32_t d = __float_as_uint(depf);
    conv_frag<G, J0, J1>(c, q, a, Pk{{d, d, d, d}});
}
template <int G, int T, int J0, int J1>
__device__ __forceinline__ void conv_mma(float (&acc)[16][4], const Conv& c, const uint32_t* a) {
#pragma unroll
    for (int j = J0; j < J1; j++) wg_mma<T>(acc, a + 4 * (j - J0), c.d0 - 8 * (2 * G - T) - j);
}
__device__ __forceinline__ float h_lo(uint32_t w) { return __half2float(__ushort_as_half((unsigned short)(w & 0xffffu))); }
__device__ __forceinline__ float h_hi(uint32_t w) { return __half2float(__ushort_as_half((unsigned short)(w >> 16))); }
__device__ __forceinline__ void flush_setup(Conv& c) {
    const uint2 v = lds64(c.lc + 256 + lane_v() * 8);
    c.fl = v.x; c.yo = v.y;
}
template <int Q>
__device__ __forceinline__ void flush_load(const Conv& c, uint32_t pl, uint2 (&f)[4]) {
#pragma unroll
    for (int w = 0; w < 4; w++) f[w] = lds64(c.fl + pl + (Q & 1) * 512 + w * (PLW_B - 64));
}
template <int Q>
__device__ __forceinline__ void flush_load_first(const Conv& c, uint32_t pl, uint2 (&f)[4], float depf) {
    const uint32_t p = prmt_v(c.fl, __float_as_uint(depf), c.id) + pl + (Q & 1) * 512;
#define LDV64(d, a) asm volatile("ld.volatile.shared.v2.u32 {%0,%1}, [%2];\n" : "=r"(d.x), "=r"(d.y) : "r"(a) : "memory")
    LDV64(f[0], p); LDV64(f[1], p + (PLW_B - 64)); LDV64(f[2], p + 2 * (PLW_B - 64)); LDV64(f[3], p + 3 * (PLW_B - 64));
}
#define FDEP __uint_as_float(f[3].y)
template <int Q, int mode>
__device__ __forceinline__ void conv_flush(const Conv& c, const uint2 (&f)[4], unsigned char* gy, uint32_t rx) {
    const uint32_t a0 = hadd2(f[0].x, f[1].x), a1 = hadd2(f[2].x, f[3].x), b0 = hadd2(f[0].y, f[1].y), b1 = hadd2(f[2].y, f[3].y);
    if (Q > 0 && mode == 1) {
        const uint32_t ra = rx + 16 + (Q > 0 ? Q - 1 : 0) * 1024 + (c.warp & 3) * 256 + lane_v() * 8;
        asm volatile("st.async.shared::cluster.mbarrier::complete_tx::bytes.v2.b32 [%0], {%1,%2}, [%3];\n"
                     ::"r"(ra ^ 0x1000000u), "r"(hadd2(a0, a1)), "r"(hadd2(b0, b1)), "r"((rx + (Q > 1 ? 8 : 0)) ^ 0x1000000u) : "memory");
        return;
    }
    float v0 = h_lo(a0) + h_lo(a1), v1 = h_hi(a0) + h_hi(a1), v2 = h_lo(b0) + h_lo(b1), v3 = h_hi(b0) + h_hi(b1);
    if (Q > 0 && mode == 2) {
        const uint2 o = lds64(rx + 16 + (Q > 0 ? Q - 1 : 0) * 1024 + (c.warp & 3) * 256 + lane_v() * 8);
        v0 += h_lo(o.x); v1 += h_hi(o.x); v2 += h_lo(o.y); v3 += h_hi(o.y);
    }
    const uint32_t lo = hmul2_bf(pack_bf16(v0, v1), c.fs), hi = hmul2_bf(pack_bf16(v2, v3), c.fs);
    stg64(gy + Q * 32 * DM * 32 + (c.yo + (Q < 3 ? c.yp : 0u)), lo ^ YKEY, hi ^ YKEY);
}
template <int I, bool S = false> struct IC { static constexpr int value = I; static constexpr bool shared = S; };
template <class T> __device__ constexpr bool wg_is4() { return T::shared; }
#define SLOT(n) (c.ps + (2 + ((n) & 7)) * 128)
#define GO() do { wg_commit(); __syncwarp(); } while (0)
#define DEP acc[15][3]
template <class FG, class FP, class FN>
__device__ __forceinline__ void conv_head(Conv& c, float (&acc)[16][4], uint32_t (&q)[9], uint32_t (&r)[9], uint32_t* a, FG fg, FP pre, FN next) {
    c.id = 0x3210u + (c.warp >> 8);
    if (ONEBAR) pre();
    conv_load<0, 0, 9>(c, q);
    conv_frag<0, 0, 1>(c, q, a, 0.f);
    if (!ONEBAR) pre();
    wg_fence(); wg_first<0>(acc, a, c.d0); GO();
    park(c.ps, Pk{{0u, 0u, 0u, 0u}});
    wg_wait0();
    conv_frag<0, 1, 2>(c, q, a, DEP);
    wg_fence(); conv_mma<0, 0, 1, 2>(acc, c, a); GO();
    fg(IC<0>());
    wg_wait0();
    conv_frag<0, 2, 3>(c, q, a, DEP);
    wg_fence(); conv_mma<0, 0, 2, 3>(acc, c, a); GO();
    conv_load<1, 0, 5>(c, r);
    wg_wait0();
    conv_frag<0, 3, 4>(c, q, a, DEP);
    wg_fence(); conv_mma<0, 0, 3, 4>(acc, c, a); GO();
    conv_load<1, 5, 9>(c, r);
    fg(IC<1>());
    wg_wait0();
    const Pk k = pk2(acc[0], acc[1]);
    conv_rename<2>(acc);
    conv_frag<1, 0, 2>(c, r, a, k);
    wg_fence(); conv_mma<1, 2, 0, 2>(acc, c, a); GO();
    park(SLOT(0), k);
    next(IC<0>());
    fg(IC<2>());
    wg_wait0();
    conv_frag<1, 2, 4>(c, r, a, DEP);
    wg_fence(); conv_mma<1, 2, 2, 4>(acc, c, a); GO();
    next(IC<1>());
    fg(IC<3>());
    wg_wait0();
}
template <class FG, class FP>
__device__ __forceinline__ void conv_run(Conv& c, uint32_t pl, unsigned char* gy, FG fg, FP pre) {
    float acc[16][4];
    uint32_t q[9], r[9], a[32];
    uint2 f[4];
    const int bid = 1 + (c.warp >> 2);
    conv_head(c, acc, q, r, a, fg, pre, [&](auto i) { if (decltype(i)::value == 0) conv_selectors4(c); else conv_load<2, 0, 9>(c, q); });
    Pk k = pk2(acc[2], acc[3]);
    conv_rename<4>(acc);
    conv_frag<2, 0, 4>(c, q, a, k);
    wg_fence(); conv_mma<2, 4, 0, 4>(acc, c, a); GO();
    park(SLOT(2), k);
    conv_load<3, 0, 9>(c, q);
    flush_setup(c);
    bar_sync(bid, 128);
    fg(IC<4>());
    wg_wait0();
    conv_rename<6>(acc);
    flush_load_first<0>(c, pl, f, DEP);
    conv_frag<3, 0, 4>(c, q, a, FDEP);
    wg_fence(); conv_mma<3, 6, 0, 4>(acc, c, a); GO();
    park(SLOT(4), pk2(acc[4], acc[5]));
    conv_load<4, 0, 9>(c, q);
    conv_selectors8(c);
    conv_flush<0, 0>(c, f, gy, 0u);
    fg(IC<5>());
    wg_wait0();
    conv_rename<8>(acc);
    conv_frag<4, 0, 4>(c, q, a, DEP);
    wg_fence(); conv_mma<4, 8, 0, 4>(acc, c, a); GO();
    k = pk2(acc[6], acc[7]);
    park(SLOT(6), k); park(c.ps, k);
    conv_load<5, 0, 9>(c, q);
    bar_sync(bid, 128);
    fg(IC<6>());
    wg_wait0();
    conv_rename<10>(acc);
    flush_load_first<1>(c, pl, f, DEP);
    conv_frag<5, 0, 4>(c, q, a, FDEP);
    wg_fence(); conv_mma<5, 10, 0, 4>(acc, c, a); GO();
    park(SLOT(8), pk2(acc[8], acc[9]));
    conv_load<6, 0, 9>(c, q); conv_load<7, 0, 9>(c, r);
    conv_flush<1, 0>(c, f, gy, 0u);
    fg(IC<7>());
    wg_wait0();
    conv_rename<12>(acc);
    conv_frag<6, 0, 4>(c, q, a, DEP); conv_frag<7, 0, 4>(c, r, a + 16, DEP);
    wg_fence(); conv_mma<6, 12, 0, 4>(acc, c, a); conv_mma<7, 12, 0, 4>(acc, c, a + 16); GO();
    park(SLOT(10), pk2(acc[10], acc[11]));
    bar_sync(bid, 128);
    flush_load<2>(c, pl, f);
    conv_flush<2, 0>(c, f, gy, 0u);
    fg(IC<8>());
    wg_wait0();
    park(SLOT(12), pk2(acc[12], acc[13])); park(SLOT(14), pk2(acc[14], acc[15]));
    bar_sync(bid, 128);
    flush_load<3>(c, pl, f);
    conv_flush<3, 0>(c, f, gy, 0u);
}
template <class FG>
__device__ __forceinline__ void conv_outer(Conv& c, uint32_t pl, unsigned char* gy, uint32_t rx, FG fg) {
    float acc[16][4];
    uint32_t q[9], r[9], a[32];
    uint2 f[4], f2[4];
    const int bid = 1 + (c.warp >> 2);
    conv_head(c, acc, q, r, a, [&](auto gi) { if (decltype(gi)::value == 2) fg(IC<2, true>()); }, [&]() {}, [&](auto i) { if (decltype(i)::value == 0) conv_selectors8(c); else conv_load<6, 0, 9>(c, q); });
    park(SLOT(2), pk2(acc[2], acc[3])); park(SLOT(4), pk2(acc[4], acc[5]));
    const Pk k = pk2(acc[6], acc[7]);
    park(SLOT(6), k);
    conv_load<7, 0, 9>(c, r);
    conv_rename<12>(acc);
    conv_frag<6, 0, 4>(c, q, a, __uint_as_float(k.w[3])); conv_frag<7, 0, 4>(c, r, a + 16, __uint_as_float(k.w[3]));
    wg_fence(); conv_mma<6, 12, 0, 4>(acc, c, a); conv_mma<7, 12, 0, 4>(acc, c, a + 16); GO();
    flush_setup(c);
    bar_sync(bid, 128);
    flush_load<0>(c, pl, f); flush_load<1>(c, pl, f2);
    conv_flush<1, 1>(c, f2, gy, rx);
    conv_flush<0, 1>(c, f, gy, rx);
    wg_wait0();
    bar_sync(bid, 128);
    park(c.ps, k); park(SLOT(8), pk2(acc[8], acc[9])); park(SLOT(10), pk2(acc[10], acc[11]));
    park(SLOT(12), pk2(acc[12], acc[13])); park(SLOT(14), pk2(acc[14], acc[15]));
    bar_sync(bid, 128);
    flush_load<2>(c, pl, f); flush_load<3>(c, pl, f2);
    conv_flush<2, 1>(c, f, gy, rx);
    conv_flush<3, 1>(c, f2, gy, rx);
}
template <class FG>
__device__ __forceinline__ void conv_inner(Conv& c, uint32_t pl, unsigned char* gy, uint32_t rx, FG fg) {
    float acc[16][4];
    uint32_t q[9], a[16];
    uint2 f[4], f2[4];
    const int bid = 1 + (c.warp >> 2);
    c.id = 0x3210u + (c.warp >> 8);
    conv_selectors4(c);
    conv_load<2, 0, 9>(c, q);
    conv_frag<2, 0, 4>(c, q, a, 0.f);
    wg_fence(); wg_first<4>(acc, a, c.d0); conv_mma<2, 4, 1, 4>(acc, c, a + 4); GO();
    conv_load<3, 0, 9>(c, q);
    park(SLOT(2), Pk{{0u, 0u, 0u, 0u}});
    fg(IC<2, true>());
    wg_wait0();
    conv_rename<6>(acc);
    conv_frag<3, 0, 4>(c, q, a, DEP);
    wg_fence(); conv_mma<3, 6, 0, 4>(acc, c, a); GO();
    park(SLOT(4), pk2(acc[4], acc[5]));
    conv_load<4, 0, 9>(c, q);
    conv_selectors8(c);
    wg_wait0();
    conv_rename<8>(acc);
    conv_frag<4, 0, 4>(c, q, a, DEP);
    wg_fence(); conv_mma<4, 8, 0, 4>(acc, c, a); GO();
    const Pk k = pk2(acc[6], acc[7]);
    park(SLOT(6), k); park(c.ps, k);
    conv_load<5, 0, 9>(c, q);
    flush_setup(c);
    wg_wait0();
    conv_rename<10>(acc);
    conv_frag<5, 0, 4>(c, q, a, DEP);
    wg_fence(); conv_mma<5, 10, 0, 4>(acc, c, a); GO();
    park(SLOT(8), pk2(acc[8], acc[9]));
    bar_sync(bid, 128);
    flush_load<1>(c, pl, f);
    mbar_wait(rx);
    conv_flush<1, 2>(c, f, gy, rx);
    wg_wait0();
    bar_sync(bid, 128);
    park(SLOT(10), pk2(acc[10], acc[11])); park(SLOT(12), pk2(acc[12], acc[13])); park(SLOT(14), pk2(acc[14], acc[15]));
    bar_sync(bid, 128);
    flush_load<3>(c, pl, f); flush_load<2>(c, pl, f2);
    mbar_wait(rx + 8);
    conv_flush<3, 2>(c, f, gy, rx);
    conv_flush<2, 2>(c, f2, gy, rx);
}
#undef SLOT
#undef GO
#undef DEP
template <int U0, int U1>
__device__ __forceinline__ void weight_units(uint32_t sb, const CUtensorMap* tg, const CUtensorMap* tu, const CUtensorMap* td, bool w) {
    if (U1 > U0 && w && elect_one()) {
#pragma unroll
        for (int n = U0; n < U1; n++) {
            const int i = n;
            if (i < 12) tma_2d(sb + SM_WG + i * 6912, i < 6 ? tg : tu, 72 * (blockIdx.x >> 1), 288 * (blockIdx.x & 1) + (i % 6) * 48, sb + SM_MISC + 328);
            else tma_2d(sb + SM_WD + (i - 12) * 4736, td, 144 * (blockIdx.x & 1), 72 * (blockIdx.x >> 1) + 8 * (i - 12), sb + SM_MISC + 336);
        }
    }
}
#define WS 1111121111122004100
__device__ constexpr int wsched(int i) {
    unsigned long long v = WS;
    int n = 0;
    for (int k = 19; k >= 1; k--) { if (k < i) n += (int)(v % 10); v /= 10; }
    return n;
}
static_assert(wsched(20) == 21 && wsched(6) <= 7 && wsched(11) <= 12 && wsched(16) <= 17 && wsched(16) == wsched(15) && wsched(19) == 21, "");
__device__ __forceinline__ void weight_prefetch(const Params& p, int u, int lane) {
    const int b = blockIdx.x;
    const char* a = u < 12 ? reinterpret_cast<const char*>(u < 6 ? p.wg : p.wu) + ((b >> 6) * 288 + (u % 6) * 48) * (FF * 2) + (b & 63) * 6912
                           : reinterpret_cast<const char*>(p.wd) + (72 * (b >> 1) + 8 * (u - 12)) * 1152 + (b & 1) * 4608;
    asm volatile("prefetch.global.L2 [%0];\n" ::"l"(a + lane * 128));
    if (lane < (u < 12 ? 22 : 4)) asm volatile("prefetch.global.L2 [%0];\n" ::"l"(a + 4096 + lane * 128));
}
#define PF0 0
#define PF1 0
#define WPOINT(i, w) do { weight_units<wsched(i), wsched(i + 1)>(sb, &tm_g, &tm_u, &tm_d, w); } while (0)

__global__ void __launch_bounds__(NTHR, 1) __cluster_dims__(2, 1, 1)
fused_kernel(const Params p, const __grid_constant__ CUtensorMap tm_g, const __grid_constant__ CUtensorMap tm_u, const __grid_constant__ CUtensorMap tm_d, const __grid_constant__ CUtensorMap tm_x) {
    extern __shared__ __align__(1024) unsigned char smem[];
    const uint32_t sb = smem_u32(smem);
    const int tid = threadIdx.x, warp = __shfl_sync(0xffffffffu, tid >> 5, 0), lane = tid & 31;
    const int b = blockIdx.x, P = b >> 1, odd = b & 1;
    const int g = lane >> 2, t = lane & 3;
    const int wg = warp >> 2, t128 = tid & 127;
    const uint32_t s_stat = sb + SM_MISC;
    const uint32_t s_key = sb + SM_MISC + 128;
    const uint32_t s_rank = sb + SM_MISC + 256;
    const uint32_t s_k16 = sb + SM_MISC + 192;
    const uint32_t s_cnt = sb + SM_MISC + 320;
    const uint32_t bar_w = sb + SM_MISC + 328, bar_d = bar_w + 8, bar_g = bar_w + 16, bar_x = bar_w + 24, bar_t = bar_w + 32, bar_s = bar_w + 40, bar_v = bar_w + 48, bar_h = sb + SM_MISC + 160;
    STAMP(0);

    if (warp == 19) {
        if (lane == 0) {
            mbar_init(bar_w, 1); mbar_init(bar_d, 1); mbar_init(bar_g, 1); mbar_init(sb + SM_RX, 1); mbar_init(sb + SM_RX + 8, 1);
            mbar_init(bar_x, 1); mbar_init(bar_t, 1); mbar_init(bar_s, 1); mbar_init(bar_v, 2); if (HOLD >= 2) { mbar_init(bar_h, 1); mbar_init(bar_h + 8, 1); mbar_init(bar_h + 16, 1); mbar_init(bar_h + 24, 1); } mbar_expect(bar_x, 32768);
            asm volatile("fence.mbarrier_init.release.cluster;\n" ::: "memory");
            mbar_expect(bar_w, 82944); mbar_expect(bar_d, 72 * WD_PITCH); mbar_expect(bar_g, 9216); mbar_expect(bar_t, 16 * 1152); mbar_expect(bar_v, 2 * 1152); mbar_expect(sb + SM_RX, 1024); mbar_expect(sb + SM_RX + 8, 2048);
        }
        __syncwarp();
    } else if (warp == 18) {
#pragma unroll
        for (int i = 0; i < 9; i++) sts128(sb + SM_ZERO + (i * 32 + lane) * 16, 0u, 0u, 0u, 0u);
        fence_async();
        __syncwarp();
    }
    const int ch = wg < 4 ? 4 * b + wg : 512 + P;
    const bf16 *q0 = p.lar + ch * NST, *q1 = p.aim + ch * NST, *q2 = p.cre + ch * NST, *q3 = p.cim + ch * NST;
    asm volatile("" : "+l"(q0), "+l"(q1), "+l"(q2), "+l"(q3));
    const uint32_t ldt = ldo16(p.ldt + ch), pl = ldo16(q0 + t128), pa2 = ldo16(q1 + t128);
    const uint32_t pc = ldo16(q2 + t128), pi = ldo16(q3 + t128);
    const uint2 call_re = ldo64(q2 + 4 * lane), call_im = ldo64(q3 + 4 * lane);
    const uint32_t epl = ld_poll32(p.s->hint + (b & 7) * 32 + 1);
    bar_sync(0, NWRK);
    if (XCP && wg == 4) {
        const int o = (4 * (warp & 3) + (g >> 1)) * 1152 + (g & 1) * 576 + t * 16;
#pragma unroll
        for (int c = 0; c < 9; c++)
            asm volatile("cp.async.cg.shared.global [%0], [%1], 16;\n" ::"r"(sb + SM_XT + o + c * 64), "l"(reinterpret_cast<const char*>(p.x) + b * 18432 + o + c * 64) : "memory");
        asm volatile("cp.async.commit_group;\n" ::: "memory");
    }
    asm volatile("barrier.cluster.arrive.relaxed.aligned;\n" ::: "memory");
    if (warp == 18) {
        if (lane == 0) {
            if (!XCP) bulk_g2s(sb + SM_XT, p.x + (size_t)16 * b * DM, 16 * 1152, bar_t);
            bulk_s2g(reinterpret_cast<unsigned char*>(p.s->y) + 96 * 18432 + b * 4608, sb + SM_ZERO, 4608);
        }
        bar_arrive(12, 64);
    }
    if (warp == 19) {
        bar_sync(12, 64);
        asm volatile("barrier.cluster.wait.aligned;\n" ::: "memory");
        if (EXP & 4) { if (elect_one()) asm volatile("mbarrier.complete_tx.relaxed.cta.shared::cta.b64 [%0], %1;" :: "r"(bar_x), "r"(32768) : "memory"); }
        else if (EXP & 8) { if (elect_one()) { tma_4d(sb + SM_XC + odd * 16384, &tm_x, 8 * P, 2 * odd, bar_x); asm volatile("mbarrier.complete_tx.relaxed.cta.shared::cta.b64 [%0], %1;" :: "r"(bar_x), "r"(16384) : "memory"); } }
        else
        if (elect_one()) tma_4d_mc(sb + SM_XC + odd * 16384, &tm_x, 8 * P, 2 * odd, bar_x);
        __syncwarp();
    }
    const uint32_t kw = sb + SM_KW + wg * KW_B;
    const uint32_t tb = table_buf(sb, warp), t5 = sb + SM_WD + warp * 512;
    if (wg == 4) {
        if (!(g & 1) && t == (g >> 1)) *reinterpret_cast<volatile uint32_t*>(p.s->stat + 16 * b + 4 * (warp & 3) + t) = 0u;
        if (warp < 18) {
            unsigned char* const ud = reinterpret_cast<unsigned char*>(p.s->uT) + (size_t)(8 * (warp & 1) + 2 * (g >> 1)) * 16384 + b * 128 + (g & 1) * 32 + t * 8;
#pragma unroll
            for (int k = 0; k < 4; k++) *reinterpret_cast<volatile unsigned long long*>(ud + (k >> 1) * 16384 + (k & 1) * 64) = 0ull;
        }
        if (warp == 17) conv_constants(sb + SM_LC, lane);
    } else if (warp == 0) {
#pragma unroll
        for (int i = 0; i < 6; i++) sts128(sb + SM_LNP + (i * 32 + lane) * 16, 0u, 0u, 0u, 0u);
    }
    if (t128 < 2 * UPAD) sts128(sb + SM_U + wg * USLOT_B + (t128 & 1) * ULO_B + (t128 >> 1) * 16, 0u, 0u, 0u, 0u);
    if (t128 >= 124) sts128(kw + (t128 & 1) * 16 + (t128 & 2) * (KW_PL / 2), 0u, 0u, 0u, 0u);
    uint32_t co, cn, cd;
    combine_setup(sb, warp, lane, kw, co, cn, cd);
    const uint4* usrc = wg < 4 ? reinterpret_cast<const uint4*>(p.s->stat) + tid
                               : reinterpret_cast<const uint4*>(p.s->uT) + (P >> 2) * 1024 + (t128 >> 1) * 8 + (P & 3) * 2 + (t128 & 1);
    uint32_t zero;
    {
        uint32_t uo = (uint32_t)(reinterpret_cast<const char*>(usrc) - reinterpret_cast<const char*>(p.s)), pk = (cn - co + 1024) | ((cd - kw) << 16);
        asm volatile("st.volatile.shared.v4.u32 [%4], {0, %1, %2, %3};\nld.volatile.shared.v4.u32 {%0, %1, %2, %3}, [%4];\n" : "=r"(zero), "+r"(co), "+r"(pk), "+r"(uo) : "r"(tb + lane * 16) : "memory");
        cn = co + (pk & 0xffffu) - 1024; cd = kw + (pk >> 16);
        usrc = reinterpret_cast<const uint4*>(reinterpret_cast<const char*>(p.s) + uo);
    }
    const float dt = exp_bf(__uint_as_float(__byte_perm(ldt, zero, 0x1044)));
    const uint32_t ep = __reduce_or_sync(0xffffffffu, epl | zero);
    auto stats = [&]() {
        const int wq = warp & 3;
        const uint32_t xa = sb + SM_XT + (4 * wq + (g >> 1)) * 1152 + (g & 1) * 576 + t * 16;
        const bool own = !(g & 1) && t == (g >> 1);
        float d[4][4] = {};
        if (XCP) asm volatile("cp.async.wait_group 0;\n" ::: "memory"); else mbar_wait(bar_t);
        if ((HOLD == 2 || HOLD == 5) && lane == 0) mbar_arrive(bar_h + 8 * wq);
        STAMP(26);
        uint4 v[9];
#pragma unroll
        for (int c = 0; c < 9; c++) v[c] = lds128(xa + c * 64);
#pragma unroll
        for (int c = 0; c < 9; c++) {
            mma_bf16(d[2 * (c & 1)], v[c].x, 0x3f803f80u, v[c].y, 0x3f803f80u, v[c].x, v[c].y);
            mma_bf16(d[2 * (c & 1) + 1], v[c].z, 0x3f803f80u, v[c].w, 0x3f803f80u, v[c].z, v[c].w);
        }
        STAMP(27);
        float sm = (g & 1) ? (d[0][3] + d[1][3]) + (d[2][3] + d[3][3]) : (d[0][2] + d[1][2]) + (d[2][2] + d[3][2]);
        float sq = (g & 1) ? (d[0][1] + d[1][1]) + (d[2][1] + d[3][1]) : (d[0][0] + d[1][0]) + (d[2][0] + d[3][0]);
        sm += __shfl_xor_sync(0xffffffffu, sm, 4); sq += __shfl_xor_sync(0xffffffffu, sq, 4);
        if (HOLD == 1) bar_arrive(6 + wq, 160);
        if (HOLD >= 2 && HOLD != 4 && lane == 0) mbar_arrive(bar_h + 8 * wq);
        float mb, sd;
        ln_stats(sm, sq, mb, sd);
        if (own) p.s->stat[16 * b + 4 * wq + t] = (__float_as_uint(mb) >> 16) | (__float_as_uint(sd) & 0x7fff0000u) | (ep << 31);
        STAMPX(22);
        if (HOLD == 4 && lane == 0) mbar_arrive(bar_h + 8 * wq);
        if (own) stat_store(s_stat + (2 * wq + (t & 1) + 8 * (t >> 1)) * 8, mb, rcp_approx(sd), 0u);
        if (wq == 2) asm volatile("cp.async.bulk.wait_group 0;\n" ::: "memory");
        bar_sync(5, 128);
        STAMP(28);
        if (wq == 2) {
            if (lane < 8) p.s->key[8 * b + lane] = ep & 1u;
            if (lane == 0) {
                uint32_t now;
                asm volatile("mov.u32 %0, %%clock;" : "=r"(now));
                sts64(s_cnt, now, ep);
                mbar_arrive(bar_s);
                bulk_g2s(sb + SM_XT + 16 * 1152, p.dsk, 1152, bar_v);
                bulk_g2s(sb + SM_XT + 17 * 1152, p.wr, 1152, bar_v);
            }
            __syncwarp();
        }
        WPOINT(1, wq == 3);
        if (wq < 2) {
            unsigned char* const ud = reinterpret_cast<unsigned char*>(p.s->uT) + (size_t)(8 * wq + 2 * (g >> 1)) * 16384 + b * 128 + (g & 1) * 32 + t * 8;
            const uint32_t utag = (ep % 7u + 1u) * 0x10001u;
            uint32_t U[2][4];
#pragma unroll
            for (int hf = 0; hf < 2; hf++) {
                const uint2 st = lds64(s_stat + (g + 8 * hf) * 8);
                const uint4 xu = lds128(sb + SM_XT + (TOK(g) + 2 * hf) * 1152 + warp * 64 + t * 16);
                const uint32_t X[4] = {xu.x, xu.y, xu.z, xu.w};
#pragma unroll
                for (int k = 0; k < 4; k++) {
                    const uint32_t u = ln_apply(X[k], STAT_M(st), STAT_H(st), STAT_L(st));
                    U[hf][k] = movm((pack_f16(bf_lo(u), bf_hi(u)) & 0xfff8fff8u) | utag);
                }
            }
#pragma unroll
            for (int k = 0; k < 4; k++) stg64(ud + (k >> 1) * 16384 + (k & 1) * 64, U[0][k], U[1][k]);
        }
    };
    STAMP(1);
    if (wg < 4) { STAMPX(16); }
    if (SORD == 0 && wg == 4) stats();
    KGen kg;
    kgen_setup(kg, __uint_as_float(__byte_perm(pl, zero, 0x1044)), __uint_as_float(__byte_perm(pa2, zero, 0x1044)), dt);
    kgen_rows(kg, tb, lane);
    STAMP(2);
    const int E = min(max(c_exponent(call_re, call_im, dt) - 243, -120), 120);
    kgen_chain(kg, pc, pi, dt * __uint_as_float((uint32_t)(128 - E) << 23));
    STAMP(3);
    kgen_cols(kg, tb, t5, lane);
    STAMP(4);
    if (SORD == 1 && wg == 4) stats();
    if (warp != 19) asm volatile("barrier.cluster.wait.aligned;\n" ::: "memory");
    if (wg < 4) { STAMPX(17); }
    if (HOLD == 1 && wg < 4) bar_sync(6 + (warp & 3), 160);
    if ((HOLD == 3 || HOLD == 4) && wg < 4) mbar_wait(bar_h + 8 * (warp & 3));
    if (HOLD == 2 || HOLD == 5) mbar_wait1(bar_h + 8 * (warp & 3));
    if (wg < 4) { STAMPX(19); }
    if (DEFER == 1 && wg == 4) bar_sync(14, NWRK);
    if (DEFER > 1 && wg == 4) bar_sync(15, NWRK);
    kgen_mma(kg, tb, t5, lane, bar_h + 8 * (warp & 3));
    if (wg < 4) { STAMPX(20); }
    if (DEFER == 3 && wg < 4) bar_arrive(15, NWRK);
    STAMP(5);
    if (SORD == 2 && wg == 4) stats();
    uint4 uv0, uv1;
    auto first_poll = [&](uint32_t dly) {
        mbar_wait(bar_s);
        const uint32_t t0 = lds32(s_cnt);
        uint32_t now;
        do { asm volatile("mov.u32 %0, %%clock;" : "=r"(now) :: "memory"); } while (now - t0 < dly);
        uv0 = ld_poll(usrc);
    };
    WPOINT(2, warp == 19);
    if (PEARLY == 3 && wg < 4) first_poll(SDLY);
    bar_sync(1 + wg, 128);
    if (PEARLY == 2 && wg < 4) first_poll(SDLY);
    if (wg < 4) { STAMPX(21); }
    kgen_combine(warp & 3, lane, co, cn, cd);
    STAMP(6);
    if (wg < 4) { STAMPX(18); }
    if (DEFER == 2 && wg < 4) bar_arrive(15, NWRK);
    WPOINT(3, warp == 19);
    if (PEARLY == 1 && wg < 4) first_poll(SDLY);
    {
        const int wq = warp & 3;
        Conv c;
        const uint32_t pln = sb + SM_PL + wg * PL_B;
        const int e = g - 2 * t + 7;
        c.kw = kw; c.wa = pin(kw + ((e >> 2) & 1) * KW_PL + (8 * wq + (e >> 3)) * 16 + (e & 3) * 4);
        c.ps = mov_v(pln + wq * PLW_B + ((lane >> 3) & 1) * PL_HALF + ((lane >> 4) * 8 + (lane & 7)) * 16); c.warp = warp;
        c.lc = sb + SM_LC; c.fs = (uint32_t)(127 + E) * 0x800080u; c.yp = (ep & 1u) * (NCTA * 18432u);
        c.d0 = ((uint64_t)(ULO_B >> 4) << 16) | ((uint64_t)(128 >> 4) << 32) | (uint64_t)(((sb + SM_U + wg * USLOT_B + UPAD * 16) & 0x3FFFF) >> 4);
        unsigned char* gy = reinterpret_cast<unsigned char*>(p.s->y) + ((size_t)(4 * wq) * DM + ch) * 64;
        auto hook = [&](auto gi) {
                     constexpr int G = decltype(gi)::value;
                     if (G == (wg_is4<decltype(gi)>() ? 2 : 5)) asm volatile("barrier.cluster.wait.aligned;\n" ::: "memory");
                     if (!wg_is4<decltype(gi)>() && G < 4 && warp == HW) {
                         const int l2 = lane_v();
                         unsigned char* const sc = reinterpret_cast<unsigned char*>(p.s);
                         if (G == 0 && l2 < 2) bulk_s2g(sc + offsetof(Scratch, rows) + b * 4608 + l2 * 2304, sb + SM_LNP, 2304);
                         if (b < 96 && l2 < ((G && !(EXP & 2)) ? 3 : 1))
                             bulk_s2g(l2 ? sc + offsetof(Scratch, y) + (NCTA * 18432u - c.yp) + b * 18432 + (2 * G + l2 - 3) * 3072 : sc + offsetof(Scratch, part) + b * 12288 + G * 3072,
                                      sb + SM_LNP, 3072);
                         __syncwarp();
                     }
                     if (!wg_is4<decltype(gi)>() && PF1 && G >= PF1 && G < PF1 + 2 && (warp >> 1) == 2) weight_prefetch(p, 17 + 2 * (G - PF1) + (warp & 1), lane_v());
                     if (!wg_is4<decltype(gi)>()) WPOINT(6 + G, warp == 12 + (G & 3));
                     if (!wg_is4<decltype(gi)>() && G == XG && warp == HW) {
                         asm volatile("cp.async.bulk.wait_group 0;\n" ::: "memory");
                         __syncwarp();
                         if (elect_one()) mbar_arrive(bar_v);
                     }
                 };
        if (!ONEBAR) bar_sync(1 + wg, 128);
        if (wg < 4) {
            asm volatile("barrier.cluster.arrive.relaxed.aligned;\n" ::: "memory");
            conv_run(c, pln + wq * 128, gy, hook, [&]() {
                STAMPX(23);
                mbar_wait(bar_x);
                STAMP(9);
                STAMPX(24);
                uint2 xc[4];
                uint32_t xw[4][2];
#pragma unroll
                for (int j = 0; j < 4; j++) xc[j] = lds64(sb + SM_XC + wg * 8192 + j * 2048 + t128 * 16 + odd * 8);
#pragma unroll
                for (int i = 0; i < 8; i++) {
                    const int k = i >> 1, h = i & 1;
                    xw[k][h] = prmt_v(k < 2 ? xc[2 * h].x : xc[2 * h].y, k < 2 ? xc[2 * h + 1].x : xc[2 * h + 1].y, (k & 1) ? 0x7632 : 0x5410);
                }
                const uint32_t ub = mov_v(sb + SM_U + UPAD * 16 + ((tid >> 1) & 1) * ULO_B + (tid >> 2) * 16 + (tid & 1) * 8), tag = ep << 31;
                int it = 0;
                if (!PEARLY) first_poll(SDLY);
                while (min(min((int)(uv0.x ^ tag), (int)(uv0.y ^ tag)), min((int)(uv0.z ^ tag), (int)(uv0.w ^ tag))) < 0x10000) {
                    if (++it > SPIN_LIMIT) TRAP();
                    uv0 = ld_poll(usrc);
                }
                STAMP(8);
                STAMPX(26);
                const float r0 = rcp_approx(fabsf(bf_hi(uv0.x))), r1 = rcp_approx(fabsf(bf_hi(uv0.y))), r2 = rcp_approx(fabsf(bf_hi(uv0.z))), r3 = rcp_approx(fabsf(bf_hi(uv0.w)));
                const uint32_t m[2] = {__byte_perm(uv0.x, uv0.y, 0x5410), __byte_perm(uv0.z, uv0.w, 0x5410)};
                const uint32_t rh[2] = {pack_bf16(r0, r1), pack_bf16(r2, r3)};
                const uint32_t rl[2] = {pack_bf16(r0 - bf_lo(rh[0]), r1 - bf_hi(rh[0])), pack_bf16(r2 - bf_lo(rh[1]), r3 - bf_hi(rh[1]))};
#pragma unroll
                for (int k = 0; k < 4; k++) {
                    const uint32_t u0 = ln_apply(xw[k][0], m[0], rh[0], rl[0]), u1 = ln_apply(xw[k][1], m[1], rh[1], rl[1]);
                    sts64(ub + k * USLOT_B, pack_f16(bf_lo(u0), bf_hi(u0)), pack_f16(bf_lo(u1), bf_hi(u1)));
                }
                STAMPX(29);
                fence_async();
                bar_sync(14, DEFER == 1 ? NWRK : 512);
                STAMP(7);
            });
        } else {
            auto stage = [&]() {
                const uint32_t tag = (ep % 7u + 1u) * 0x10001u;
                int it = 0;
                WPOINT(4, warp == 19);
                first_poll(UDLY);
                uv1 = ld_poll(usrc + 512);
                WPOINT(5, warp == 19);
                while (true) {
                    uv0.x ^= tag; uv0.y ^= tag; uv0.z ^= tag; uv0.w ^= tag; uv1.x ^= tag; uv1.y ^= tag; uv1.z ^= tag; uv1.w ^= tag;
                    if ((((uv0.x | uv0.y | uv0.z) | (uv0.w | uv1.x | uv1.y) | (uv1.z | uv1.w)) & 0x70007u) == 0) break;
                    if (++it > SPIN_LIMIT) TRAP();
                    uv0 = ld_poll(usrc); uv1 = ld_poll(usrc + 512);
                }
                STAMP(8);
                const uint32_t ub = sb + SM_U + UPAD * 16 + 4 * USLOT_B + (t128 & 1) * ULO_B + (t128 >> 1) * 16;
                sts128(ub, uv0.x, uv0.y, uv0.z, uv0.w);
                sts128(ub + 1024, uv1.x, uv1.y, uv1.z, uv1.w);
                fence_async();
                asm volatile("barrier.cluster.arrive.relaxed.aligned;\n" ::: "memory");
                bar_sync(5, 128);
                STAMP(7);
            };
            stage();
            if (odd) conv_inner(c, pln + wq * 128, gy, sb + SM_RX, hook);
            else conv_outer(c, pln + wq * 128, gy, sb + SM_RX, hook);
        }
        STAMP(10);
    }
    {
    const int lane = lane_v(), tid = 32 * warp + lane, g = lane >> 2, t = lane & 3;
    const uint32_t par = ~ep & 1u;
    if (CBAR) bar_sync(0, NWRK);
    STAMP(11);
    uint32_t H[2][4] = {}, U2[2][4] = {};
    uint32_t WA[9][4], WD[18];
    auto publish = [&](bool hi, int slot) {
        uint4* rowp = reinterpret_cast<uint4*>(p.s->rows) + slot * 144 + warp * 4 + t;
        stg128(rowp, nzw(hi ? U2[1][0] : U2[0][0]), nzw(hi ? U2[1][1] : U2[0][1]), nzw(hi ? U2[1][2] : U2[0][2]), nzw(hi ? U2[1][3] : U2[0][3]));
        stg128(rowp + 72, nzw(hi ? H[1][0] : H[0][0]), nzw(hi ? H[1][1] : H[0][1]), nzw(hi ? H[1][2] : H[0][2]), nzw(hi ? H[1][3] : H[0][3]));
    };
#define KTOK(k) (2047 - (int)(((k) >> 5) & 0x7ffu))
#define KLATE(k) (((k) & 0x1cu) != 0)
#define KSLOT(k, s) (KLATE(k) ? 2 * NCTA + (s) : 2 * (KTOK(k) >> 4) + (int)(((k) >> 1) & 1u))
    const uint4* const rsrc = reinterpret_cast<const uint4*>(p.s->rows) + 36 * odd;
    auto gather = [&](uint32_t mine) {
        int it = 0;
        uint32_t mn;
        do {
            mn = 1;
#pragma unroll 1
            for (int r = 0; r < 9; r++) {
                const uint32_t k = __shfl_sync(0xffffffffu, mine, r < 8 ? 4 * r : lane);
                const int row = r < 8 ? r : g, c = r < 8 ? lane : 32 + t;
                asm volatile("cp.async.cg.shared.global [%0], [%1], 16;\n" ::"r"(sb + SM_XS + row * XS_PITCH + c * 16), "l"(rsrc + KSLOT(k, row) * 144 + c) : "memory");
            }
            asm volatile("cp.async.wait_all;\n" ::: "memory");
#pragma unroll 1
            for (int r = 0; r < 9; r++) mn = min(mn, min4(lds128(sb + SM_XS + (r < 8 ? r * XS_PITCH + lane * 16 : g * XS_PITCH + (32 + t) * 16))));
            if (++it > SPIN_LIMIT) TRAP();
        } while (__any_sync(0xffffffffu, mn == 0));
    };
    auto late_rows = [&](auto role) {
        const uint32_t kk = lds32(s_key + (lane & 7) * 4), ep = lds32(s_cnt + 4);
        const bool own = KLATE(kk) && (KTOK(kk) >> 4) == b;
        uint32_t todo = __ballot_sync(0xffffffffu, own) & 0xffu;
        if (decltype(role)::value == 0 && todo) {
#pragma unroll
            for (int hf = 0; hf < 2; hf++) {
                const uint4 h = lds128(sb + SM_U + hf * 9216 + tid * 16);
                const uint2 st = lds64(s_stat + (g + 8 * hf) * 8);
                H[hf][0] = h.x; H[hf][1] = h.y; H[hf][2] = h.z; H[hf][3] = h.w;
#pragma unroll
                for (int k = 0; k < 4; k++) U2[hf][k] = ln_apply(H[hf][k], STAT_M(st), STAT_H(st), STAT_L(st));
            }
#pragma unroll 1
            while (todo) {
                const int s = __ffs(todo) - 1, tk = KTOK(__shfl_sync(0xffffffffu, kk, s));
                todo &= todo - 1;
                if ((tk & 13) == TOK(g)) publish(tk & 2, 2 * NCTA + s);
            }
            __threadfence();
        }
        bar_sync(0, NWRK);
        if (decltype(role)::value == 1) {
            if (lane < NSEL && own) *reinterpret_cast<volatile unsigned*>(p.s->flag + lane) = ep + 1u;
            int it = 0;
            while (__any_sync(0xffffffffu, KLATE(kk) && ld_acquire32(p.s->flag + (lane & 7)) != ep + 1u)) { if (++it > SPIN_LIMIT) TRAP(); }
            gather(__shfl_sync(0xffffffffu, kk, g));
        }
        bar_sync(0, NWRK);
    };
    if (warp < 18) {
        const unsigned char* ys = reinterpret_cast<const unsigned char*>(p.s->y) + (b < 96 ? (par ^ 1u) * (NCTA * 18432u) : 0u) +
                                  ((P * DM + 32 * warp + 8 * (g >> 1) + (g & 1)) * 64 + odd * 32 + t * 8);
        uint2 yv[4] = {};
        if (YDLY == 0 || b < YFROM) {
#pragma unroll
            for (int k = 0; k < 4; k++) yv[k] = ld_poll64(ys + k * 128);
        } else if (YDLY > 1) delay(YDLY);
        mbar_wait(bar_v);
        const uint32_t xa = sb + SM_XT + warp * 64 + t * 16;
        const uint4 x0 = lds128(xa + TOK(g) * 1152), x1 = lds128(xa + (TOK(g) + 2) * 1152), dk = lds128(xa + 16 * 1152);
        uint4 wr = make_uint4(0u, 0u, 0u, 0u);
        if (g == 0) wr = lds128(xa + 17 * 1152);
        const uint32_t Z[2][4] = {{x0.x, x0.y, x0.z, x0.w}, {x1.x, x1.y, x1.z, x1.w}}, D4[4] = {dk.x, dk.y, dk.z, dk.w};
#pragma unroll
        for (int hf = 0; hf < 2; hf++) {
            const uint2 st = lds64(s_stat + (g + 8 * hf) * 8);
#pragma unroll
            for (int k = 0; k < 4; k++) H[hf][k] = hmul2_bf(ln_apply(Z[hf][k], STAT_M(st), STAT_H(st), STAT_L(st)), D4[k]);
        }
        int it = 0;
        while (__any_sync(0xffffffffu, min(min(min(yv[0].x, yv[0].y), min(yv[1].x, yv[1].y)), min(min(yv[2].x, yv[2].y), min(yv[3].x, yv[3].y))) == 0)) {
#pragma unroll
            for (int k = 0; k < 4; k++) yv[k] = ld_poll64(ys + k * 128);
            if (++it > SPIN_LIMIT) TRAP();
        }
        STAMP(12);
#pragma unroll
        for (int k = 0; k < 4; k++) {
            H[0][k] = hadd2_bf(Z[0][k], hadd2_bf(movm(yv[k].x ^ YKEY), H[0][k]));
            H[1][k] = hadd2_bf(Z[1][k], hadd2_bf(movm(yv[k].y ^ YKEY), H[1][k]));
        }
        ln_partial(H, sb + SM_LNP, warp, g, t);
        bar_arrive(6, NWRK);
        STAMP(13);
        bar_sync(7, 608);
        STAMP(14);
#pragma unroll
        for (int hf = 0; hf < 2; hf++) {
            const uint2 st = lds64(s_stat + (g + 8 * hf) * 8);
#pragma unroll
            for (int k = 0; k < 4; k++) U2[hf][k] = ln_apply(H[hf][k], STAT_M(st), STAT_H(st), STAT_L(st));
        }
        {
            float cs[4] = {0.f, 0.f, 0.f, 0.f};
            mma_bf16(cs, U2[0][0], U2[1][0], U2[0][1], U2[1][1], wr.x, wr.y);
            mma_bf16(cs, U2[0][2], U2[1][2], U2[0][3], U2[1][3], wr.z, wr.w);
            if (t == 0) { stsf(sb + SM_LNP + ((32 + g) * 20 + warp) * 4, cs[0]); stsf(sb + SM_LNP + ((40 + g) * 20 + warp) * 4, cs[2]); }
            bar_arrive(8, 608);
        }
        bar_sync(9, 608);
        const uint32_t rk[2] = {lds32(s_rank + g * 4), lds32(s_rank + 32 + g * 4)};
#pragma unroll
        for (int hf = 0; hf < 2; hf++)
            sts128(sb + SM_OUT + (TOK(g) + 2 * hf) * (DM * 2) + warp * 64 + t * 16,
                   hadd2_bf(H[hf][0], U2[hf][0]), hadd2_bf(H[hf][1], U2[hf][1]), hadd2_bf(H[hf][2], U2[hf][2]), hadd2_bf(H[hf][3], U2[hf][3]));
        fence_async();
        uint32_t lo = min(rk[0], rk[1]), hi = max(rk[0], rk[1]);
#pragma unroll 1
        while (lo < 2) { publish(lo == rk[1], 2 * b + lo); lo = hi; hi = 16; }
        sts128(sb + SM_U + tid * 16, H[0][0], H[0][1], H[0][2], H[0][3]);
        sts128(sb + SM_U + 9216 + tid * 16, H[1][0], H[1][1], H[1][2], H[1][3]);
        STAMP(15);
        {
            const int mi = lane >> 3, rr = lane & 7;
            mbar_wait(bar_w);
            const uint32_t aad = sb + SM_WG + (mi & 1) * SM_WU + ((warp & 1) * 144 + rr + 8 * (mi >> 1)) * W_PITCH + (warp >> 1) * 16;
#pragma unroll
            for (int k = 0; k < 9; k++) ldsm_x4_t(WA[k][0], WA[k][1], WA[k][2], WA[k][3], aad + k * 16 * W_PITCH);
        }
        {
            const int mi = lane >> 3, rr = lane & 7;
            mbar_wait(bar_d);
            const uint32_t base = sb + SM_WD + (2 * warp + (mi & 1)) * 16 + rr * WD_PITCH;
#pragma unroll
            for (int k = 0; k < 4; k++) ldsm_x4_t(WD[4 * k], WD[4 * k + 1], WD[4 * k + 2], WD[4 * k + 3], base + (k * 16 + 8 * (mi >> 1)) * WD_PITCH);
            ldsm_x2_t(WD[16], WD[17], base + 64 * WD_PITCH);
        }
        const uint32_t bad = pin(sb + SM_XS + (lane & 7) * XS_PITCH + ((warp & 1) * 144 + 8 * (lane >> 3)) * 2);
        const uint32_t ex = pin(sb + SM_EX + (2 * odd + (warp & 1)) * 4608 + (warp >> 1) * 512 + lane * 16);
        const uint32_t po = pin((((8 * (18 * odd + warp) + g) * 64 + P) * 16 + t * 4) * 4);
        STAMP2(17);
        if (bar_or(11, NWRK, false)) late_rows(IC<0>());
        STAMP2(19);
        {
            float c4[3][4] = {}, e4[4];
#pragma unroll
            for (int k = 0; k < 9; k += 2) {
                uint32_t b0, b1, b2, b3;
                ldsm_x4(b0, b1, b2, b3, bad + k * 32);
                mma_bf16(c4[k % 3], WA[k][0], WA[k][1], WA[k][2], WA[k][3], b0, b1);
                if (k < 8) mma_bf16(c4[(k + 1) % 3], WA[k + 1][0], WA[k + 1][1], WA[k + 1][2], WA[k + 1][3], b2, b3);
            }
#pragma unroll
            for (int j = 0; j < 4; j++) e4[j] = c4[0][j] + c4[1][j] + c4[2][j];
            asm volatile("st.async.shared::cluster.mbarrier::complete_tx::bytes.v4.f32 [%0], {%1,%2,%3,%4}, [%5];\n"
                         ::"r"(ex ^ 0x1000000u), "f"(e4[0]), "f"(e4[1]), "f"(e4[2]), "f"(e4[3]), "r"(bar_g ^ 0x1000000u) : "memory");
            sts128f(ex, e4);
        }
        if (warp < 9) {
            bar_sync(12, 576);
            STAMP2(20);
            const uint32_t er = sb + SM_EX + tid * 16;
            const uint4 a = lds128(er + odd * 9216), c = lds128(er + odd * 9216 + 4608);
            mbar_wait(bar_g);
            const uint4 d = lds128(er + (odd ^ 1) * 9216), e = lds128(er + (odd ^ 1) * 9216 + 4608);
#define S4(f) ((__uint_as_float(a.f) + __uint_as_float(c.f)) + (__uint_as_float(d.f) + __uint_as_float(e.f)))
            const uint32_t G = pack_bf16(S4(x), S4(y)), U = pack_bf16(S4(z), S4(w));
#undef S4
            sts32(sb + SM_GU + tid * 4, hmul2_bf(pack_bf16(bf_lo(G) * sigmoid_f(bf_lo(G)), bf_hi(G) * sigmoid_f(bf_hi(G))), U));
        } else bar_arrive(12, 576);
        bar_sync(13, NWRK);
        STAMP2(21);
        {
            uint32_t gb[9];
            ldsm_x4_t(gb[0], gb[1], gb[2], gb[3], sb + SM_GU + lane * 16);
            ldsm_x4_t(gb[4], gb[5], gb[6], gb[7], sb + SM_GU + 512 + lane * 16);
            ldsm_x1_t(gb[8], sb + SM_GU + 1024 + lane * 16);
            float c4[4] = {}, d4[4] = {}, e4[4] = {};
            mma_bf16(c4, WD[0], WD[1], WD[2], WD[3], gb[0], gb[1]);
            mma_bf16(d4, WD[4], WD[5], WD[6], WD[7], gb[2], gb[3]);
            mma_bf16(e4, WD[8], WD[9], WD[10], WD[11], gb[4], gb[5]);
            mma_bf16(c4, WD[12], WD[13], WD[14], WD[15], gb[6], gb[7]);
            mma_bf16_k8(d4, WD[16], WD[17], gb[8]);
            stg128(reinterpret_cast<unsigned char*>(p.s->part) + po, __float_as_uint(e4[0] + c4[0] + d4[0]) | 1u, __float_as_uint(e4[1] + c4[1] + d4[1]) | 1u,
                   __float_as_uint(e4[2] + c4[2] + d4[2]) | 1u, __float_as_uint(e4[3] + c4[3] + d4[3]) | 1u);
        }
        STAMP2(22);
    } else if (warp == 18) {
        bar_sync(6, NWRK);
        {
            float mb, rc;
            ln_finish(sum18(sb + SM_LNP + lane * 80), lane, mb, rc);
            if (lane < 16) stat_store(s_stat + lane * 8, mb, rc, 0u);
        }
        bar_arrive(7, 608);
        const uint4* ksrc = reinterpret_cast<const uint4*>(p.s->key) + lane;
        const uint32_t klo = (uint32_t)(2047 - 16 * b - ROWTOK(lane & 15)) << 5 | par;
        bar_sync(8, 608);
        {
            const float r = sum18(sb + SM_LNP + (32 + (lane & 15)) * 80);
            const uint32_t bits = pack_bf16(0.f, r);
            const uint32_t me = ((bits ^ ((uint32_t)((int)bits >> 31) | 0x80000000u)) & 0xffff0000u) | klo;
            sts32(s_k16 + (lane & 15) * 4, me);
            __syncwarp();
            const uint4 v = lds128(s_k16 + (lane & 16) * 2), w = lds128(s_k16 + (lane & 16) * 2 + 16);
            int rank = ((v.x > me) + (v.y > me)) + ((v.z > me) + (v.w > me)) + (((w.x > me) + (w.y > me)) + ((w.z > me) + (w.w > me)));
            rank += __shfl_xor_sync(0xffffffffu, rank, 16);
            if (lane < 16 && rank < 8) p.s->key[8 * b + rank] = me | (rank << 1);
            if (lane >= 16) sts32(s_rank + (lane & 15) * 4, rank);
        }
        bar_arrive(9, 608);
        uint4 kq[4];
        int it = 0;
        if (KDLY) delay(KDLY);
        do {
#pragma unroll
            for (int i = 0; i < 4; i++) kq[i] = ld_poll(ksrc + lane + 64 * i);
            if (++it > SPIN_LIMIT) TRAP();
        } while (__any_sync(0xffffffffu, ((and3(and3(kq[0].x, kq[0].y, kq[0].z), and3(kq[1].x, kq[1].y, kq[1].z), and3(and3(kq[2].x, kq[2].y, kq[2].z), kq[3].x, kq[3].y) & kq[3].z) ^ par) |
                                          (or3(or3(kq[0].x, kq[0].y, kq[0].z), or3(kq[1].x, kq[1].y, kq[1].z), or3(or3(kq[2].x, kq[2].y, kq[2].z), kq[3].x, kq[3].y) | kq[3].z) ^ par)) & 1u));
        STAMPW(16);
        uint32_t u[4], mine = 0, m;
        {
            uint32_t S[2][4];
#pragma unroll
            for (int i = 0; i < 2; i++) {
                const uint4 &c = kq[2 * i], &d = kq[2 * i + 1];
                const uint32_t m1 = min(c.x, d.x), m2 = max(c.y, d.y);
                S[i][0] = max(c.x, d.x); S[i][1] = max(m1, m2); S[i][2] = min(m1, m2); S[i][3] = min(c.y, d.y);
            }
            const uint32_t a0 = max(S[0][0], S[1][3]), a1 = max(S[0][1], S[1][2]), a2 = max(S[0][2], S[1][1]), a3 = max(S[0][3], S[1][0]);
            const uint32_t b0 = max(a0, a2), b2 = min(a0, a2), b1 = max(a1, a3), b3 = min(a1, a3);
            u[0] = max(b0, b1); u[1] = min(b0, b1); u[2] = max(b2, b3); u[3] = min(b2, b3);
        }
        uint4 v[9];
#pragma unroll
        for (int r = 0; r < 8; r++) {
            m = __reduce_max_sync(0xffffffffu, u[0]);
            if (u[0] == m) { u[0] = u[1]; u[1] = u[2]; u[2] = u[3]; u[3] = 0; }
            if (g == r) mine = m;
            v[r] = ld_poll(rsrc + (2 * (KTOK(m) >> 4) + ((m >> 1) & 1u)) * 144 + lane);
        }
        v[8] = ld_poll(rsrc + (2 * (KTOK(mine) >> 4) + ((mine >> 1) & 1u)) * 144 + 32 + t);
        bool again = __any_sync(0xffffffffu, u[0] == 0 || max(max(kq[0].z, kq[1].z), max(kq[2].z, kq[3].z)) > m);
        if (again) {
#pragma unroll 1
            for (int i = 0; i < 8; i++) {
                uint4 k;
                do { k = ld_poll(ksrc + 32 * i); if (++it > SPIN_LIMIT) TRAP(); } while (((k.x ^ par) | (k.y ^ par) | (k.z ^ par) | (k.w ^ par)) & 1u);
                sts128(sb + SM_KEYS + (32 * i + lane) * 16, k.x, k.y, k.z, k.w);
            }
            m = 0xffffffffu;
#pragma unroll 1
            for (int r = 0; r < 8; r++) {
                uint32_t c = 0;
#pragma unroll 2
                for (int i = 0; i < 8; i++) {
                    const uint4 k = lds128(sb + SM_KEYS + (32 * i + lane) * 16);
                    c = max(max(c, k.x < m ? k.x : 0u), max(k.y < m ? k.y : 0u, max(k.z < m ? k.z : 0u, k.w < m ? k.w : 0u)));
                }
                m = __reduce_max_sync(0xffffffffu, c);
                if (g == r) mine = m;
            }
        }
        if (t == 0) sts32(s_key + g * 4, mine);
        uint32_t mn = 1;
#pragma unroll
        for (int r = 0; r < 9; r++) {
            sts128(sb + SM_XS + (r < 8 ? r * XS_PITCH + lane * 16 : g * XS_PITCH + (32 + t) * 16), v[r].x, v[r].y, v[r].z, v[r].w);
            mn = min(mn, min4(v[r]));
        }
        if ((again || __any_sync(0xffffffffu, mn == 0)) && !__any_sync(0xffffffffu, KLATE(mine))) gather(mine);
        STAMPW(18);
        if (bar_or(11, NWRK, KLATE(mine))) late_rows(IC<1>());
    } else {
        bar_sync(6, NWRK);
        WPOINT(16, true);
        if (wsched(18) > wsched(17)) delay(WDLY);
        WPOINT(17, true);
        if (wsched(19) > wsched(18)) delay(WDLY);
        WPOINT(18, true);
        if (bar_or(11, NWRK, false)) late_rows(IC<2>());
        const int tk = KTOK(lds32(s_key + (lane & 7) * 4));
        const uint32_t sel = __reduce_or_sync(0xffffffffu, (tk >> 4) == b ? 1u << (tk & 15) : 0u);
        if (ODLY) delay(ODLY);
        if (!(EXP & 1)) if (sel ? lane < 16 && !((sel >> lane) & 1u) : lane == 0) bulk_s2g(p.out + (size_t)(16 * b + lane) * DM, sb + SM_OUT + lane * (DM * 2), sel ? DM * 2 : 16 * DM * 2);
        __syncwarp();
    }
    if (warp >= 17) {
        const int grp = 3 * b + warp - 17, fsl = 2 * t + ((lane >> 3) & 1), fc = 16 * (grp >> 3) + (grp & 7) + 8 * (lane >> 4);
        const uint32_t fk = lds32(s_key + fsl * 4);
        float hv = 0.f, u2 = 0.f;
        int it = 0;
        if (b < 96) {
            const uint32_t* const fsrc = p.s->rows + KSLOT(fk, fsl) * DM + (fc >> 1);
            uint32_t hw, uw;
            do { hw = ld_poll32(fsrc + 288); uw = ld_poll32(fsrc); if (++it > SPIN_LIMIT) TRAP(); } while (!hw || !uw);
            hv = (fc & 1) ? bf_hi(hw) : bf_lo(hw); u2 = (fc & 1) ? bf_hi(uw) : bf_lo(uw);
        }
        const float rs = rbf(sigmoid_f(__uint_as_float((fk ^ ((uint32_t)((int)~fk >> 31) | 0x80000000u)) & 0xffff0000u)));
        const uint32_t dof = pin(KTOK(fk) * DM + fc), so = pin(grp * 256 + lane);
        if (warp > 17) bar_sync(13, NWRK);
        if (b < 96) {
            delay(warp > 17 ? FDLY : FDLY2);
            const uint4* src = reinterpret_cast<const uint4*>(p.s->part) + so;
            uint4 a[8];
#define A4(i) and3(and3(a[i].x, a[i].y, a[i].z), and3(a[i].w, a[i + 1].x, a[i + 1].y), a[i + 1].z & a[i + 1].w)
            do {
#pragma unroll
                for (int i = 0; i < 8; i++) a[i] = ld_poll(src + 32 * i);
                if (++it > SPIN_LIMIT) TRAP();
            } while (__any_sync(0xffffffffu, !(and3(A4(0), A4(2), and3(A4(4), A4(6), 1u)))));
#undef A4
            STAMP2(24);
#define S8(f) (((__uint_as_float(a[0].f) + __uint_as_float(a[1].f)) + (__uint_as_float(a[2].f) + __uint_as_float(a[3].f))) + \
               ((__uint_as_float(a[4].f) + __uint_as_float(a[5].f)) + (__uint_as_float(a[6].f) + __uint_as_float(a[7].f))))
            const float s0 = S8(x), s1 = S8(y), s2 = S8(z), s3 = S8(w);
#undef S8
            const bool up = lane & 16, od = lane & 8;
            const float r0 = (up ? s2 : s0) + __shfl_xor_sync(0xffffffffu, up ? s0 : s2, 16), r1 = (up ? s3 : s1) + __shfl_xor_sync(0xffffffffu, up ? s1 : s3, 16);
            float y = (od ? r1 : r0) + __shfl_xor_sync(0xffffffffu, od ? r0 : r1, 8);
            y += __shfl_xor_sync(0xffffffffu, y, 4);
            p.out[dof] = __float2bfloat16_rn(hv + rbf(u2 + rbf(rbf(y) * rs)));
        }
    }
    if (warp == 19) asm volatile("cp.async.bulk.wait_group.read 0;\n" ::: "memory");
    if (b == 0 && tid < 8) *reinterpret_cast<volatile unsigned*>(p.s->hint + tid * 32 + 1) = lds32(s_cnt + 4) + 1u;
    STAMP(25);
    }
}

typedef CUresult (*PFN_tmEncode)(CUtensorMap*, CUtensorMapDataType, cuuint32_t, void*, const cuuint64_t*, const cuuint64_t*, const cuuint32_t*,
                                 const cuuint32_t*, CUtensorMapInterleave, CUtensorMapSwizzle, CUtensorMapL2promotion, CUtensorMapFloatOOBfill);

extern "C" void kernel_launch(void* const* d_in, const int* in_sizes, int n_in, void* d_out, int out_size) {
    Params p;
    p.x = (const bf16*)d_in[0];
    p.lar = (const bf16*)d_in[1];
    p.aim = (const bf16*)d_in[2];
    p.cre = (const bf16*)d_in[3];
    p.cim = (const bf16*)d_in[4];
    p.ldt = (const bf16*)d_in[5];
    p.dsk = (const bf16*)d_in[6];
    p.wr = (const bf16*)d_in[8];
    p.wg = (const bf16*)d_in[9];
    p.wu = (const bf16*)d_in[10];
    p.wd = (const bf16*)d_in[11];
    p.out = (bf16*)d_out;
    static PFN_tmEncode enc = nullptr;
    static void* scratch = nullptr;
    if (!enc) {
        cudaFuncSetAttribute(fused_kernel, cudaFuncAttributeMaxDynamicSharedMemorySize, SMEM_TOTAL);
        void* fn = nullptr;
        cudaDriverEntryPointQueryResult qr;
        cudaGetDriverEntryPoint("cuTensorMapEncodeTiled", &fn, cudaEnableDefault, &qr);
        enc = (PFN_tmEncode)fn;
        cudaGetSymbolAddress(&scratch, g_scratch);
    }
    p.s = (Scratch*)scratch;
    CUtensorMap tm_g, tm_u, tm_d, tm_x;
    const cuuint64_t dims[2] = {FF, DM}, strides[1] = {FF * 2};
    const cuuint32_t box[2] = {72, 48}, es[2] = {1, 1};
    enc(&tm_g, CU_TENSOR_MAP_DATA_TYPE_BFLOAT16, 2, d_in[9], dims, strides, box, es, CU_TENSOR_MAP_INTERLEAVE_NONE, CU_TENSOR_MAP_SWIZZLE_NONE,
        CU_TENSOR_MAP_L2_PROMOTION_NONE, CU_TENSOR_MAP_FLOAT_OOB_FILL_NONE);
    enc(&tm_u, CU_TENSOR_MAP_DATA_TYPE_BFLOAT16, 2, d_in[10], dims, strides, box, es, CU_TENSOR_MAP_INTERLEAVE_NONE, CU_TENSOR_MAP_SWIZZLE_NONE,
        CU_TENSOR_MAP_L2_PROMOTION_NONE, CU_TENSOR_MAP_FLOAT_OOB_FILL_NONE);
    const cuuint64_t ddims[2] = {DM / 2, FF}, dstrides[1] = {DM * 2};
    const cuuint32_t dbox[2] = {WD_PITCH / 4, 8};
    enc(&tm_d, CU_TENSOR_MAP_DATA_TYPE_UINT32, 2, d_in[11], ddims, dstrides, dbox, es, CU_TENSOR_MAP_INTERLEAVE_NONE, CU_TENSOR_MAP_SWIZZLE_NONE,
        CU_TENSOR_MAP_L2_PROMOTION_NONE, CU_TENSOR_MAP_FLOAT_OOB_FILL_NONE);
    const cuuint64_t xdims[4] = {DM, 128, 4, 4}, xstrides[3] = {DM * 8, DM * 2, DM * 1024};
    const cuuint32_t xbox[4] = {8, 128, 4, 2}, xes[4] = {1, 1, 1, 1};
    enc(&tm_x, CU_TENSOR_MAP_DATA_TYPE_BFLOAT16, 4, d_in[0], xdims, xstrides, xbox, xes, CU_TENSOR_MAP_INTERLEAVE_NONE, CU_TENSOR_MAP_SWIZZLE_NONE,
        CU_TENSOR_MAP_L2_PROMOTION_NONE, CU_TENSOR_MAP_FLOAT_OOB_FILL_NONE);
    fused_kernel<<<NCTA, NTHR, SMEM_TOTAL>>>(p, tm_g, tm_u, tm_d, tm_x);
}
```

```cpp
#include <cuda_runtime.h>
#include <cuda.h>
#include <cuda_fp16.h>
#include <cuda_bf16.h>
#include <stdint.h>

#define LSEQ 2048
#define DM 576
#define NST 128
#define FF 4608
#define NSEL 8
#define NCTA 128
#define NTHR 640
#define NWRK 640

typedef __nv_bfloat16 bf16;

#define SM_WG 0
#define SM_WU 41472
#define SM_XC (82944 - 32768)
#define SM_WD 82944
#define W_PITCH 144
#define WD_PITCH 592
#define SM_XT (SM_PL - 18 * 1152)
#define SM_PL (SM_WD + 46080)
#define PL_HALF 1344
#define PLW_B 2624
#define PL_B (4 * PLW_B)
#define SM_U (SM_PL + 5 * PL_B)
#define UPAD 20
#define ULO_B ((UPAD + 128) * 16)
#define USLOT_B (2 * ULO_B)
#define SM_ZERO (SM_U + 4 * USLOT_B + 128)
#define SM_KW (SM_U + 5 * USLOT_B)
#define KW_B 3712
#define KW_PL 1216
#define KW_P 2400
#define KW_H 3440
#define SM_MISC (SM_KW + 5 * KW_B)
#define SM_LC (SM_MISC + 384)
#define SM_LNP (SM_LC + 768)
#define SM_RX (SM_LNP + 3840)
#define SMEM_TOTAL (SM_RX + 3088)
#define TBW PLW_B
#define SM_OUT SM_PL
#define SM_XS (SM_PL + 18432)
#define XS_PITCH 592
#define SM_GU (SM_PL + 23296)
#define SM_EX (SM_PL + 24576)
#define SM_KEYS SM_KW

struct __align__(128) Scratch {
    unsigned hint[8 * 32];
    unsigned flag[32];
    uint32_t key3[NCTA * 8];
    uint32_t key[NCTA * 8];
    uint32_t stat[LSEQ];
    uint32_t uT[64 * (LSEQ / 2)];
    uint32_t y[(NCTA + 96) * DM * 8];
    uint32_t part[288 * 64 * 16];
    uint32_t rows[(2 * NCTA + NSEL) * DM];
};
__device__ Scratch g_scratch;
#define STAMP(i)
#define STAMPX(i)
#define STAMPY(i)

__device__ __forceinline__ float rbf(float x) {
    uint32_t r;
    asm("cvt.rn.bf16x2.f32 %0, %1, %2;\n" : "=r"(r) : "f"(x), "f"(0.f));
    return __uint_as_float(r);
}
__device__ __forceinline__ uint32_t pack_bf16(float lo, float hi) {
    uint32_t r;
    asm("cvt.rn.bf16x2.f32 %0, %1, %2;\n" : "=r"(r) : "f"(hi), "f"(lo));
    return r;
}
__device__ __forceinline__ uint32_t pack_f16(float lo, float hi) {
    uint32_t r;
    asm("cvt.rn.f16x2.f32 %0, %1, %2;\n" : "=r"(r) : "f"(hi), "f"(lo));
    return r;
}
__device__ __forceinline__ uint32_t pack_f16_rz(float lo, float hi) {
    uint32_t r;
    asm("cvt.rz.f16x2.f32 %0, %1, %2;\n" : "=r"(r) : "f"(hi), "f"(lo));
    return r;
}
__device__ __forceinline__ float bf_lo(uint32_t w) { return __uint_as_float(w << 16); }
__device__ __forceinline__ float bf_hi(uint32_t w) { return __uint_as_float(w & 0xffff0000u); }
__device__ __forceinline__ uint32_t hadd2_bf(uint32_t a, uint32_t b) {
    __nv_bfloat162 r = __hadd2_rn(*reinterpret_cast<__nv_bfloat162*>(&a), *reinterpret_cast<__nv_bfloat162*>(&b));
    return *reinterpret_cast<uint32_t*>(&r);
}
__device__ __forceinline__ uint32_t hsub2_bf(uint32_t a, uint32_t b) {
    __nv_bfloat162 r = __hsub2_rn(*reinterpret_cast<__nv_bfloat162*>(&a), *reinterpret_cast<__nv_bfloat162*>(&b));
    return *reinterpret_cast<uint32_t*>(&r);
}
__device__ __forceinline__ uint32_t hmul2_bf(uint32_t a, uint32_t b) {
    __nv_bfloat162 r = __hmul2_rn(*reinterpret_cast<__nv_bfloat162*>(&a), *reinterpret_cast<__nv_bfloat162*>(&b));
    return *reinterpret_cast<uint32_t*>(&r);
}
__device__ __forceinline__ uint32_t hfma2_bf(uint32_t a, uint32_t b, uint32_t c) { uint32_t r; asm("fma.rn.bf16x2 %0, %1, %2, %3;\n" : "=r"(r) : "r"(a), "r"(b), "r"(c)); return r; }
__device__ __forceinline__ uint32_t hmul2(uint32_t a, uint32_t b) { uint32_t r; asm("mul.rn.f16x2 %0, %1, %2;\n" : "=r"(r) : "r"(a), "r"(b)); return r; }
__device__ __forceinline__ uint32_t hadd2(uint32_t a, uint32_t b) { uint32_t r; asm("add.rn.f16x2 %0, %1, %2;\n" : "=r"(r) : "r"(a), "r"(b)); return r; }
__device__ __forceinline__ uint32_t hfma2(uint32_t a, uint32_t b, uint32_t c) { uint32_t r; asm("fma.rn.f16x2 %0, %1, %2, %3;\n" : "=r"(r) : "r"(a), "r"(b), "r"(c)); return r; }
__device__ __forceinline__ uint32_t hfms2(uint32_t a, uint32_t b, uint32_t c) {
    uint32_t r;
    asm("{\n.reg .b32 n;\nneg.f16x2 n, %2;\nfma.rn.f16x2 %0, %1, n, %3;\n}\n" : "=r"(r) : "r"(a), "r"(b), "r"(c));
    return r;
}
__device__ __forceinline__ uint32_t nzw(uint32_t w) { return max(w, 1u); }
__device__ __forceinline__ uint32_t nzf(float f) { const uint32_t w = __float_as_uint(f); return w ? w : 0x80000000u; }
__device__ __forceinline__ uint32_t smem_u32(const void* p) { return (uint32_t)__cvta_generic_to_shared(p); }
__device__ __forceinline__ uint32_t lds32(uint32_t addr) {
    uint32_t v;
    asm volatile("ld.shared.u32 %0, [%1];\n" : "=r"(v) : "r"(addr) : "memory");
    return v;
}
__device__ __forceinline__ uint32_t lds16(uint32_t addr) {
    unsigned short v;
    asm volatile("ld.shared.u16 %0, [%1];\n" : "=h"(v) : "r"(addr) : "memory");
    return v;
}
__device__ __forceinline__ uint2 lds64(uint32_t addr) {
    uint2 v;
    asm volatile("ld.shared.v2.u32 {%0,%1}, [%2];\n" : "=r"(v.x), "=r"(v.y) : "r"(addr) : "memory");
    return v;
}
__device__ __forceinline__ uint4 lds128(uint32_t addr) {
    uint4 v;
    asm volatile("ld.shared.v4.u32 {%0,%1,%2,%3}, [%4];\n" : "=r"(v.x), "=r"(v.y), "=r"(v.z), "=r"(v.w) : "r"(addr) : "memory");
    return v;
}
__device__ __forceinline__ float ldsf(uint32_t addr) { return __uint_as_float(lds32(addr)); }
__device__ __forceinline__ void sts32(uint32_t addr, uint32_t v) { asm volatile("st.shared.u32 [%0], %1;\n" ::"r"(addr), "r"(v) : "memory"); }
__device__ __forceinline__ void sts16(uint32_t addr, uint32_t v) { asm volatile("st.shared.u16 [%0], %1;\n" ::"r"(addr), "h"((unsigned short)v) : "memory"); }
__device__ __forceinline__ void stsf(uint32_t addr, float v) { sts32(addr, __float_as_uint(v)); }
__device__ __forceinline__ void sts64(uint32_t addr, uint32_t a, uint32_t b) { asm volatile("st.shared.v2.u32 [%0], {%1,%2};\n" ::"r"(addr), "r"(a), "r"(b) : "memory"); }
__device__ __forceinline__ void sts64f(uint32_t addr, float a, float b) { sts64(addr, __float_as_uint(a), __float_as_uint(b)); }
__device__ __forceinline__ void sts128(uint32_t addr, uint32_t a, uint32_t b, uint32_t c, uint32_t d) {
    asm volatile("st.shared.v4.u32 [%0], {%1,%2,%3,%4};\n" ::"r"(addr), "r"(a), "r"(b), "r"(c), "r"(d) : "memory");
}
__device__ __forceinline__ void sts128f(uint32_t addr, const float (&v)[4]) {
    sts128(addr, __float_as_uint(v[0]), __float_as_uint(v[1]), __float_as_uint(v[2]), __float_as_uint(v[3]));
}
__device__ __forceinline__ void ldsm_x4(uint32_t& r0, uint32_t& r1, uint32_t& r2, uint32_t& r3, uint32_t addr) {
    asm volatile("ldmatrix.sync.aligned.m8n8.x4.shared.b16 {%0,%1,%2,%3}, [%4];\n"
                 : "=r"(r0), "=r"(r1), "=r"(r2), "=r"(r3) : "r"(addr) : "memory");
}
__device__ __forceinline__ void ldsm_x4_t(uint32_t& r0, uint32_t& r1, uint32_t& r2, uint32_t& r3, uint32_t addr) {
    asm volatile("ldmatrix.sync.aligned.m8n8.x4.trans.shared.b16 {%0,%1,%2,%3}, [%4];\n"
                 : "=r"(r0), "=r"(r1), "=r"(r2), "=r"(r3) : "r"(addr) : "memory");
}
__device__ __forceinline__ void ldsm_x2_t(uint32_t& r0, uint32_t& r1, uint32_t addr) {
    asm volatile("ldmatrix.sync.aligned.m8n8.x2.trans.shared.b16 {%0,%1}, [%2];\n" : "=r"(r0), "=r"(r1) : "r"(addr) : "memory");
}
__device__ __forceinline__ void ldsm_x1_t(uint32_t& r0, uint32_t addr) {
    asm volatile("ldmatrix.sync.aligned.m8n8.x1.trans.shared.b16 {%0}, [%1];\n" : "=r"(r0) : "r"(addr) : "memory");
}
__device__ __forceinline__ void stsm_x4(uint32_t addr, uint32_t r0, uint32_t r1, uint32_t r2, uint32_t r3) {
    asm volatile("stmatrix.sync.aligned.m8n8.x4.shared.b16 [%0], {%1,%2,%3,%4};\n" ::"r"(addr), "r"(r0), "r"(r1), "r"(r2), "r"(r3) : "memory");
}
__device__ __forceinline__ void stsm_x4_t(uint32_t addr, uint32_t r0, uint32_t r1, uint32_t r2, uint32_t r3) {
    asm volatile("stmatrix.sync.aligned.m8n8.x4.trans.shared.b16 [%0], {%1,%2,%3,%4};\n" ::"r"(addr), "r"(r0), "r"(r1), "r"(r2), "r"(r3) : "memory");
}
__device__ __forceinline__ uint32_t movm(uint32_t a) {
    uint32_t d;
    asm volatile("movmatrix.sync.aligned.m8n8.trans.b16 %0, %1;\n" : "=r"(d) : "r"(a));
    return d;
}
__device__ __forceinline__ void mma_f16(float (&c)[4], uint32_t a0, uint32_t a1, uint32_t a2, uint32_t a3, uint32_t b0, uint32_t b1) {
    asm volatile(
        "mma.sync.aligned.m16n8k16.row.col.f32.f16.f16.f32 {%0,%1,%2,%3}, {%4,%5,%6,%7}, {%8,%9}, {%0,%1,%2,%3};\n"
        : "+f"(c[0]), "+f"(c[1]), "+f"(c[2]), "+f"(c[3])
        : "r"(a0), "r"(a1), "r"(a2), "r"(a3), "r"(b0), "r"(b1));
}
__device__ __forceinline__ void mma_bf16(float (&c)[4], uint32_t a0, uint32_t a1, uint32_t a2, uint32_t a3, uint32_t b0, uint32_t b1) {
    asm volatile(
        "mma.sync.aligned.m16n8k16.row.col.f32.bf16.bf16.f32 {%0,%1,%2,%3}, {%4,%5,%6,%7}, {%8,%9}, {%0,%1,%2,%3};\n"
        : "+f"(c[0]), "+f"(c[1]), "+f"(c[2]), "+f"(c[3])
        : "r"(a0), "r"(a1), "r"(a2), "r"(a3), "r"(b0), "r"(b1));
}
__device__ __forceinline__ void mma_bf16_k8(float (&c)[4], uint32_t a0, uint32_t a1, uint32_t b0) {
    asm volatile("mma.sync.aligned.m16n8k8.row.col.f32.bf16.bf16.f32 {%0,%1,%2,%3}, {%4,%5}, {%6}, {%0,%1,%2,%3};\n"
                 : "+f"(c[0]), "+f"(c[1]), "+f"(c[2]), "+f"(c[3]) : "r"(a0), "r"(a1), "r"(b0));
}
__device__ __forceinline__ void bar_sync(int id, int n) { asm volatile("bar.sync %0, %1;\n" ::"r"(id), "r"(n) : "memory"); }
__device__ __forceinline__ void bar_arrive(int id, int n) { asm volatile("bar.arrive %0, %1;\n" ::"r"(id), "r"(n) : "memory"); }
__device__ __forceinline__ bool bar_or(int id, int n, bool v) {
    uint32_t r;
    asm volatile("{\n.reg .pred p, q;\nsetp.ne.u32 p, %3, 0;\nbar.red.or.pred q, %1, %2, p;\nselp.u32 %0, 1, 0, q;\n}\n" : "=r"(r) : "r"(id), "r"(n), "r"((uint32_t)v) : "memory");
    return r;
}
__device__ __forceinline__ uint32_t and3(uint32_t a, uint32_t b, uint32_t c) { uint32_t r; asm("lop3.b32 %0, %1, %2, %3, 0x80;\n" : "=r"(r) : "r"(a), "r"(b), "r"(c)); return r; }
__device__ __forceinline__ uint32_t or3(uint32_t a, uint32_t b, uint32_t c) { uint32_t r; asm("lop3.b32 %0, %1, %2, %3, 0xfe;\n" : "=r"(r) : "r"(a), "r"(b), "r"(c)); return r; }
__device__ __forceinline__ uint32_t xor_or(uint32_t a, uint32_t b, uint32_t c) { uint32_t r; asm("lop3.b32 %0, %1, %2, %3, 0x7e;\n" : "=r"(r) : "r"(a), "r"(b), "r"(c)); return r; }
__device__ __forceinline__ uint32_t pin(uint32_t v) { uint32_t r; asm volatile("shfl.sync.bfly.b32 %0, %1, 0, 0x1f, 0xffffffff;\n" : "=r"(r) : "r"(v) : "memory"); return r; }
__device__ __forceinline__ uint4 ld_poll(const void* p) {
    uint4 v;
    asm volatile("ld.relaxed.gpu.global.v4.u32 {%0,%1,%2,%3}, [%4];\n" : "=r"(v.x), "=r"(v.y), "=r"(v.z), "=r"(v.w) : "l"(p) : "memory");
    return v;
}
__device__ __forceinline__ uint2 ld_poll64(const void* p) {
    uint2 v;
    asm volatile("ld.relaxed.gpu.global.v2.u32 {%0,%1}, [%2];\n" : "=r"(v.x), "=r"(v.y) : "l"(p) : "memory");
    return v;
}
__device__ __forceinline__ uint32_t ld_poll32(const void* p) {
    uint32_t v;
    asm volatile("ld.relaxed.gpu.global.u32 %0, [%1];\n" : "=r"(v) : "l"(p) : "memory");
    return v;
}
__device__ __forceinline__ uint32_t ld_acquire32(const void* p) {
    uint32_t v;
    asm volatile("ld.acquire.gpu.global.u32 %0, [%1];\n" : "=r"(v) : "l"(p) : "memory");
    return v;
}
__device__ __forceinline__ uint4 ldg128(const void* p) {
    uint4 v;
    asm volatile("ld.global.nc.v4.u32 {%0,%1,%2,%3}, [%4];\n" : "=r"(v.x), "=r"(v.y), "=r"(v.z), "=r"(v.w) : "l"(p));
    return v;
}
__device__ __forceinline__ uint2 ldg64(const void* p) {
    uint2 v;
    asm volatile("ld.global.nc.v2.u32 {%0,%1}, [%2];\n" : "=r"(v.x), "=r"(v.y) : "l"(p));
    return v;
}
__device__ __forceinline__ uint32_t ldg16(const void* p) {
    uint32_t v;
    asm volatile("ld.global.nc.u16 %0, [%1];\n" : "=r"(v) : "l"(p));
    return v;
}
__device__ __forceinline__ uint4 ldo128(const void* p) {
    uint4 v;
    asm volatile("ld.relaxed.cta.global.v4.u32 {%0,%1,%2,%3}, [%4];\n" : "=r"(v.x), "=r"(v.y), "=r"(v.z), "=r"(v.w) : "l"(p) : "memory");
    return v;
}
__device__ __forceinline__ uint2 ldo64(const void* p) {
    uint2 v;
    asm volatile("ld.relaxed.cta.global.v2.u32 {%0,%1}, [%2];\n" : "=r"(v.x), "=r"(v.y) : "l"(p) : "memory");
    return v;
}
__device__ __forceinline__ uint32_t ldo16(const void* p) {
    uint32_t v;
    asm volatile("ld.relaxed.cta.global.u16 %0, [%1];\n" : "=r"(v) : "l"(p) : "memory");
    return v;
}
__device__ __forceinline__ void stg128(void* p, uint32_t a, uint32_t b, uint32_t c, uint32_t d) {
    asm volatile("st.global.v4.u32 [%0], {%1,%2,%3,%4};\n" ::"l"(p), "r"(a), "r"(b), "r"(c), "r"(d) : "memory");
}
__device__ __forceinline__ void stg64(void* p, uint32_t a, uint32_t b) { asm volatile("st.global.v2.u32 [%0], {%1,%2};\n" ::"l"(p), "r"(a), "r"(b) : "memory"); }
__device__ __forceinline__ uint32_t min4(const uint4& v) { return min(min(v.x, v.y), min(v.z, v.w)); }
#define SPIN_LIMIT (1 << 21)
#define TRAP() __trap()
__device__ __forceinline__ void mbar_init(uint32_t bar, uint32_t cnt) { asm volatile("mbarrier.init.shared::cta.b64 [%0], %1;\n" ::"r"(bar), "r"(cnt) : "memory"); }
__device__ __forceinline__ void mbar_expect(uint32_t bar, uint32_t bytes) {
    asm volatile("mbarrier.arrive.expect_tx.shared::cta.b64 _, [%0], %1;\n" ::"r"(bar), "r"(bytes) : "memory");
}
__device__ __forceinline__ void mbar_arrive(uint32_t bar) { asm volatile("mbarrier.arrive.shared::cta.b64 _, [%0];\n" ::"r"(bar) : "memory"); }
__device__ __forceinline__ void mbar_wait_cluster(uint32_t bar) {
    asm volatile(
        "{\n.reg .pred p;\n"
        "W_%=:\n"
        "mbarrier.try_wait.parity.acquire.cluster.shared::cta.b64 p, [%0], 0;\n"
        "@!p bra W_%=;\n}\n" ::"r"(bar) : "memory");
}
__device__ __forceinline__ void mbar_wait(uint32_t bar) {
    asm volatile(
        "{\n.reg .pred p;\n"
        "W_%=:\n"
        "mbarrier.try_wait.parity.shared::cta.b64 p, [%0], 0;\n"
        "@!p bra W_%=;\n}\n" ::"r"(bar) : "memory");
}
__device__ __forceinline__ void mbar_wait1(uint32_t bar) {
    asm volatile(
        "{\n.reg .pred p;\n"
        "W_%=:\n"
        "mbarrier.try_wait.parity.shared::cta.b64 p, [%0], 1;\n"
        "@!p bra W_%=;\n}\n" ::"r"(bar) : "memory");
}
__device__ __forceinline__ bool mbar_test(uint32_t bar) {
    uint32_t r;
    asm volatile("{\n.reg .pred p;\nmbarrier.test_wait.parity.shared::cta.b64 p, [%1], 0;\nselp.u32 %0, 1, 0, p;\n}\n" : "=r"(r) : "r"(bar) : "memory");
    return __any_sync(0xffffffffu, r);
}
__device__ __forceinline__ void bulk_g2s(uint32_t dst, const void* src, uint32_t bytes, uint32_t bar) {
    asm volatile("cp.async.bulk.shared::cluster.global.mbarrier::complete_tx::bytes [%0], [%1], %2, [%3];\n" ::"r"(dst), "l"(src), "r"(bytes), "r"(bar) : "memory");
}
__device__ __forceinline__ void bulk_s2g(void* dst, uint32_t src, uint32_t bytes) {
    asm volatile("cp.async.bulk.global.shared::cta.bulk_group [%0], [%1], %2;\ncp.async.bulk.commit_group;\n" ::"l"(dst), "r"(src), "r"(bytes) : "memory");
}
__device__ __forceinline__ void tma_2d(uint32_t dst, const CUtensorMap* tm, int c0, int c1, uint32_t bar) {
    asm volatile("cp.async.bulk.tensor.2d.shared::cluster.global.mbarrier::complete_tx::bytes [%0], [%1, {%3, %4}], [%2];\n"
                 ::"r"(dst), "l"(tm), "r"(bar), "r"(c0), "r"(c1) : "memory");
}
__device__ __forceinline__ void tma_4d(uint32_t dst, const CUtensorMap* tm, int c0, int c3, uint32_t bar) {
    asm volatile("cp.async.bulk.tensor.4d.shared::cluster.global.mbarrier::complete_tx::bytes [%0], [%1, {%3, %4, %4, %5}], [%2];\n"
                 ::"r"(dst), "l"(tm), "r"(bar), "r"(c0), "r"(0), "r"(c3) : "memory");
}
__device__ __forceinline__ void tma_4d_mc(uint32_t dst, const CUtensorMap* tm, int c0, int c3, uint32_t bar) {
    asm volatile("cp.async.bulk.tensor.4d.shared::cluster.global.mbarrier::complete_tx::bytes.multicast::cluster [%0], [%1, {%3, %4, %4, %5}], [%2], %6;\n"
                 ::"r"(dst), "l"(tm), "r"(bar), "r"(c0), "r"(0), "r"(c3), "h"((unsigned short)3) : "memory");
}
__device__ __forceinline__ void l2_prefetch(const void* src, uint32_t bytes) {
    asm volatile("cp.async.bulk.prefetch.L2.global [%0], %1;\n" ::"l"(src), "r"(bytes) : "memory");
}
__device__ __forceinline__ bool elect_one() {
    uint32_t r;
    asm volatile("{\n.reg .pred p;\nelect.sync _|p, 0xffffffff;\nselp.u32 %0, 1, 0, p;\n}\n" : "=r"(r));
    return r;
}
__device__ __forceinline__ void delay(uint32_t clks) {
    uint32_t t0, t1;
    asm volatile("mov.u32 %0, %%clock;" : "=r"(t0) :: "memory");
    do { asm volatile("mov.u32 %0, %%clock;" : "=r"(t1) :: "memory"); } while (t1 - t0 < clks);
}
__device__ __forceinline__ void fence_async() { asm volatile("fence.proxy.async.shared::cta;\n" ::: "memory"); }

__device__ __forceinline__ float2 cmul(float2 a, float2 b) {
    return make_float2(fmaf(a.x, b.x, -a.y * b.y), fmaf(a.x, b.y, a.y * b.x));
}
__device__ __forceinline__ float2 csq(float2 a) {
    float p = a.x * a.y;
    return make_float2(fmaf(a.x, a.x, -a.y * a.y), p + p);
}
__device__ __forceinline__ float ex2_approx(float x) { float r; asm("ex2.approx.ftz.f32 %0, %1;\n" : "=f"(r) : "f"(x)); return r; }
__device__ __forceinline__ float exp_bf(float x) { return rbf(ex2_approx(__fmul_ru(x, 1.4426950408889634f))); }
__device__ __forceinline__ float2 cexp_e(float lr2, float li, float e) {
    const float m = ex2_approx(lr2 * e);
    return make_float2(m * __cosf(li * e), m * __sinf(li * e));
}
__device__ __forceinline__ float rcp_approx(float x) { float r; asm("rcp.approx.ftz.f32 %0, %1;\n" : "=f"(r) : "f"(x)); return r; }
__device__ __forceinline__ float sigmoid_f(float x) { return rcp_approx(1.0f + ex2_approx(x * -1.4426950408889634f)); }
__device__ __forceinline__ float sqrt_approx(float x) { float r; asm("sqrt.approx.ftz.f32 %0, %1;\n" : "=f"(r) : "f"(x)); return r; }

__device__ __forceinline__ void wg_fence() { asm volatile("wgmma.fence.sync.aligned;\n" ::: "memory"); }
__device__ __forceinline__ void wg_commit() { asm volatile("wgmma.commit_group.sync.aligned;\n" ::: "memory"); }
__device__ __forceinline__ void wg_wait0() { asm volatile("wgmma.wait_group.sync.aligned 0;\n" ::: "memory"); }
template <int T> __device__ __forceinline__ void wg_mma(float (&acc)[16][4], const uint32_t* a, uint64_t desc);
template <int T> __device__ __forceinline__ void wg_first(float (&acc)[16][4], const uint32_t* a, uint64_t desc);
template <> __device__ __forceinline__ void wg_mma<0>(float (&acc)[16][4], const uint32_t* a, uint64_t desc) {
    asm volatile("wgmma.mma_async.sync.aligned.m64n128k16.f32.f16.f16 {%0,%1,%2,%3,%4,%5,%6,%7,%8,%9,%10,%11,%12,%13,%14,%15,%16,%17,%18,%19,%20,%21,%22,%23,%24,%25,%26,%27,%28,%29,%30,%31,%32,%33,%34,%35,%36,%37,%38,%39,%40,%41,%42,%43,%44,%45,%46,%47,%48,%49,%50,%51,%52,%53,%54,%55,%56,%57,%58,%59,%60,%61,%62,%63}, {%64,%65,%66,%67}, %68, 1, 1, 1, 0;\n"
                 : "+f"(acc[0][0]), "+f"(acc[0][1]), "+f"(acc[0][2]), "+f"(acc[0][3]), "+f"(acc[1][0]), "+f"(acc[1][1]), "+f"(acc[1][2]), "+f"(acc[1][3]), "+f"(acc[2][0]), "+f"(acc[2][1]), "+f"(acc[2][2]), "+f"(acc[2][3]), "+f"(acc[3][0]), "+f"(acc[3][1]), "+f"(acc[3][2]), "+f"(acc[3][3]), "+f"(acc[4][0]), "+f"(acc[4][1]), "+f"(acc[4][2]), "+f"(acc[4][3]), "+f"(acc[5][0]), "+f"(acc[5][1]), "+f"(acc[5][2]), "+f"(acc[5][3]), "+f"(acc[6][0]), "+f"(acc[6][1]), "+f"(acc[6][2]), "+f"(acc[6][3]), "+f"(acc[7][0]), "+f"(acc[7][1]), "+f"(acc[7][2]), "+f"(acc[7][3]), "+f"(acc[8][0]), "+f"(acc[8][1]), "+f"(acc[8][2]), "+f"(acc[8][3]), "+f"(acc[9][0]), "+f"(acc[9][1]), "+f"(acc[9][2]), "+f"(acc[9][3]), "+f"(acc[10][0]), "+f"(acc[10][1]), "+f"(acc[10][2]), "+f"(acc[10][3]), "+f"(acc[11][0]), "+f"(acc[11][1]), "+f"(acc[11][2]), "+f"(acc[11][3]), "+f"(acc[12][0]), "+f"(acc[12][1]), "+f"(acc[12][2]), "+f"(acc[12][3]), "+f"(acc[13][0]), "+f"(acc[13][1]), "+f"(acc[13][2]), "+f"(acc[13][3]), "+f"(acc[14][0]), "+f"(acc[14][1]), "+f"(acc[14][2]), "+f"(acc[14][3]), "+f"(acc[15][0]), "+f"(acc[15][1]), "+f"(acc[15][2]), "+f"(acc[15][3])
                 : "r"(a[0]), "r"(a[1]), "r"(a[2]), "r"(a[3]), "l"(desc));
}
template <> __device__ __forceinline__ void wg_mma<2>(float (&acc)[16][4], const uint32_t* a, uint64_t desc) {
    asm volatile("wgmma.mma_async.sync.aligned.m64n112k16.f32.f16.f16 {%0,%1,%2,%3,%4,%5,%6,%7,%8,%9,%10,%11,%12,%13,%14,%15,%16,%17,%18,%19,%20,%21,%22,%23,%24,%25,%26,%27,%28,%29,%30,%31,%32,%33,%34,%35,%36,%37,%38,%39,%40,%41,%42,%43,%44,%45,%46,%47,%48,%49,%50,%51,%52,%53,%54,%55}, {%56,%57,%58,%59}, %60, 1, 1, 1, 0;\n"
                 : "+f"(acc[2][0]), "+f"(acc[2][1]), "+f"(acc[2][2]), "+f"(acc[2][3]), "+f"(acc[3][0]), "+f"(acc[3][1]), "+f"(acc[3][2]), "+f"(acc[3][3]), "+f"(acc[4][0]), "+f"(acc[4][1]), "+f"(acc[4][2]), "+f"(acc[4][3]), "+f"(acc[5][0]), "+f"(acc[5][1]), "+f"(acc[5][2]), "+f"(acc[5][3]), "+f"(acc[6][0]), "+f"(acc[6][1]), "+f"(acc[6][2]), "+f"(acc[6][3]), "+f"(acc[7][0]), "+f"(acc[7][1]), "+f"(acc[7][2]), "+f"(acc[7][3]), "+f"(acc[8][0]), "+f"(acc[8][1]), "+f"(acc[8][2]), "+f"(acc[8][3]), "+f"(acc[9][0]), "+f"(acc[9][1]), "+f"(acc[9][2]), "+f"(acc[9][3]), "+f"(acc[10][0]), "+f"(acc[10][1]), "+f"(acc[10][2]), "+f"(acc[10][3]), "+f"(acc[11][0]), "+f"(acc[11][1]), "+f"(acc[11][2]), "+f"(acc[11][3]), "+f"(acc[12][0]), "+f"(acc[12][1]), "+f"(acc[12][2]), "+f"(acc[12][3]), "+f"(acc[13][0]), "+f"(acc[13][1]), "+f"(acc[13][2]), "+f"(acc[13][3]), "+f"(acc[14][0]), "+f"(acc[14][1]), "+f"(acc[14][2]), "+f"(acc[14][3]), "+f"(acc[15][0]), "+f"(acc[15][1]), "+f"(acc[15][2]), "+f"(acc[15][3])
                 : "r"(a[0]), "r"(a[1]), "r"(a[2]), "r"(a[3]), "l"(desc));
}
template <> __device__ __forceinline__ void wg_mma<4>(float (&acc)[16][4], const uint32_t* a, uint64_t desc) {
    asm volatile("wgmma.mma_async.sync.aligned.m64n96k16.f32.f16.f16 {%0,%1,%2,%3,%4,%5,%6,%7,%8,%9,%10,%11,%12,%13,%14,%15,%16,%17,%18,%19,%20,%21,%22,%23,%24,%25,%26,%27,%28,%29,%30,%31,%32,%33,%34,%35,%36,%37,%38,%39,%40,%41,%42,%43,%44,%45,%46,%47}, {%48,%49,%50,%51}, %52, 1, 1, 1, 0;\n"
                 : "+f"(acc[4][0]), "+f"(acc[4][1]), "+f"(acc[4][2]), "+f"(acc[4][3]), "+f"(acc[5][0]), "+f"(acc[5][1]), "+f"(acc[5][2]), "+f"(acc[5][3]), "+f"(acc[6][0]), "+f"(acc[6][1]), "+f"(acc[6][2]), "+f"(acc[6][3]), "+f"(acc[7][0]), "+f"(acc[7][1]), "+f"(acc[7][2]), "+f"(acc[7][3]), "+f"(acc[8][0]), "+f"(acc[8][1]), "+f"(acc[8][2]), "+f"(acc[8][3]), "+f"(acc[9][0]), "+f"(acc[9][1]), "+f"(acc[9][2]), "+f"(acc[9][3]), "+f"(acc[10][0]), "+f"(acc[10][1]), "+f"(acc[10][2]), "+f"(acc[10][3]), "+f"(acc[11][0]), "+f"(acc[11][1]), "+f"(acc[11][2]), "+f"(acc[11][3]), "+f"(acc[12][0]), "+f"(acc[12][1]), "+f"(acc[12][2]), "+f"(acc[12][3]), "+f"(acc[13][0]), "+f"(acc[13][1]), "+f"(acc[13][2]), "+f"(acc[13][3]), "+f"(acc[14][0]), "+f"(acc[14][1]), "+f"(acc[14][2]), "+f"(acc[14][3]), "+f"(acc[15][0]), "+f"(acc[15][1]), "+f"(acc[15][2]), "+f"(acc[15][3])
                 : "r"(a[0]), "r"(a[1]), "r"(a[2]), "r"(a[3]), "l"(desc));
}
template <> __device__ __forceinline__ void wg_mma<6>(float (&acc)[16][4], const uint32_t* a, uint64_t desc) {
    asm volatile("wgmma.mma_async.sync.aligned.m64n80k16.f32.f16.f16 {%0,%1,%2,%3,%4,%5,%6,%7,%8,%9,%10,%11,%12,%13,%14,%15,%16,%17,%18,%19,%20,%21,%22,%23,%24,%25,%26,%27,%28,%29,%30,%31,%32,%33,%34,%35,%36,%37,%38,%39}, {%40,%41,%42,%43}, %44, 1, 1, 1, 0;\n"
                 : "+f"(acc[6][0]), "+f"(acc[6][1]), "+f"(acc[6][2]), "+f"(acc[6][3]), "+f"(acc[7][0]), "+f"(acc[7][1]), "+f"(acc[7][2]), "+f"(acc[7][3]), "+f"(acc[8][0]), "+f"(acc[8][1]), "+f"(acc[8][2]), "+f"(acc[8][3]), "+f"(acc[9][0]), "+f"(acc[9][1]), "+f"(acc[9][2]), "+f"(acc[9][3]), "+f"(acc[10][0]), "+f"(acc[10][1]), "+f"(acc[10][2]), "+f"(acc[10][3]), "+f"(acc[11][0]), "+f"(acc[11][1]), "+f"(acc[11][2]), "+f"(acc[11][3]), "+f"(acc[12][0]), "+f"(acc[12][1]), "+f"(acc[12][2]), "+f"(acc[12][3]), "+f"(acc[13][0]), "+f"(acc[13][1]), "+f"(acc[13][2]), "+f"(acc[13][3]), "+f"(acc[14][0]), "+f"(acc[14][1]), "+f"(acc[14][2]), "+f"(acc[14][3]), "+f"(acc[15][0]), "+f"(acc[15][1]), "+f"(acc[15][2]), "+f"(acc[15][3])
                 : "r"(a[0]), "r"(a[1]), "r"(a[2]), "r"(a[3]), "l"(desc));
}
template <> __device__ __forceinline__ void wg_mma<8>(float (&acc)[16][4], const uint32_t* a, uint64_t desc) {
    asm volatile("wgmma.mma_async.sync.aligned.m64n64k16.f32.f16.f16 {%0,%1,%2,%3,%4,%5,%6,%7,%8,%9,%10,%11,%12,%13,%14,%15,%16,%17,%18,%19,%20,%21,%22,%23,%24,%25,%26,%27,%28,%29,%30,%31}, {%32,%33,%34,%35}, %36, 1, 1, 1, 0;\n"
                 : "+f"(acc[8][0]), "+f"(acc[8][1]), "+f"(acc[8][2]), "+f"(acc[8][3]), "+f"(acc[9][0]), "+f"(acc[9][1]), "+f"(acc[9][2]), "+f"(acc[9][3]), "+f"(acc[10][0]), "+f"(acc[10][1]), "+f"(acc[10][2]), "+f"(acc[10][3]), "+f"(acc[11][0]), "+f"(acc[11][1]), "+f"(acc[11][2]), "+f"(acc[11][3]), "+f"(acc[12][0]), "+f"(acc[12][1]), "+f"(acc[12][2]), "+f"(acc[12][3]), "+f"(acc[13][0]), "+f"(acc[13][1]), "+f"(acc[13][2]), "+f"(acc[13][3]), "+f"(acc[14][0]), "+f"(acc[14][1]), "+f"(acc[14][2]), "+f"(acc[14][3]), "+f"(acc[15][0]), "+f"(acc[15][1]), "+f"(acc[15][2]), "+f"(acc[15][3])
                 : "r"(a[0]), "r"(a[1]), "r"(a[2]), "r"(a[3]), "l"(desc));
}
template <> __device__ __forceinline__ void wg_mma<10>(float (&acc)[16][4], const uint32_t* a, uint64_t desc) {
    asm volatile("wgmma.mma_async.sync.aligned.m64n48k16.f32.f16.f16 {%0,%1,%2,%3,%4,%5,%6,%7,%8,%9,%10,%11,%12,%13,%14,%15,%16,%17,%18,%19,%20,%21,%22,%23}, {%24,%25,%26,%27}, %28, 1, 1, 1, 0;\n"
                 : "+f"(acc[10][0]), "+f"(acc[10][1]), "+f"(acc[10][2]), "+f"(acc[10][3]), "+f"(acc[11][0]), "+f"(acc[11][1]), "+f"(acc[11][2]), "+f"(acc[11][3]), "+f"(acc[12][0]), "+f"(acc[12][1]), "+f"(acc[12][2]), "+f"(acc[12][3]), "+f"(acc[13][0]), "+f"(acc[13][1]), "+f"(acc[13][2]), "+f"(acc[13][3]), "+f"(acc[14][0]), "+f"(acc[14][1]), "+f"(acc[14][2]), "+f"(acc[14][3]), "+f"(acc[15][0]), "+f"(acc[15][1]), "+f"(acc[15][2]), "+f"(acc[15][3])
                 : "r"(a[0]), "r"(a[1]), "r"(a[2]), "r"(a[3]), "l"(desc));
}
template <> __device__ __forceinline__ void wg_mma<12>(float (&acc)[16][4], const uint32_t* a, uint64_t desc) {
    asm volatile("wgmma.mma_async.sync.aligned.m64n32k16.f32.f16.f16 {%0,%1,%2,%3,%4,%5,%6,%7,%8,%9,%10,%11,%12,%13,%14,%15}, {%16,%17,%18,%19}, %20, 1, 1, 1, 0;\n"
                 : "+f"(acc[12][0]), "+f"(acc[12][1]), "+f"(acc[12][2]), "+f"(acc[12][3]), "+f"(acc[13][0]), "+f"(acc[13][1]), "+f"(acc[13][2]), "+f"(acc[13][3]), "+f"(acc[14][0]), "+f"(acc[14][1]), "+f"(acc[14][2]), "+f"(acc[14][3]), "+f"(acc[15][0]), "+f"(acc[15][1]), "+f"(acc[15][2]), "+f"(acc[15][3])
                 : "r"(a[0]), "r"(a[1]), "r"(a[2]), "r"(a[3]), "l"(desc));
}
template <> __device__ __forceinline__ void wg_mma<14>(float (&acc)[16][4], const uint32_t* a, uint64_t desc) {
    asm volatile("wgmma.mma_async.sync.aligned.m64n16k16.f32.f16.f16 {%0,%1,%2,%3,%4,%5,%6,%7}, {%8,%9,%10,%11}, %12, 1, 1, 1, 0;\n"
                 : "+f"(acc[14][0]), "+f"(acc[14][1]), "+f"(acc[14][2]), "+f"(acc[14][3]), "+f"(acc[15][0]), "+f"(acc[15][1]), "+f"(acc[15][2]), "+f"(acc[15][3])
                 : "r"(a[0]), "r"(a[1]), "r"(a[2]), "r"(a[3]), "l"(desc));
}
template <> __device__ __forceinline__ void wg_first<0>(float (&acc)[16][4], const uint32_t* a, uint64_t desc) {
    asm volatile("wgmma.mma_async.sync.aligned.m64n128k16.f32.f16.f16 {%0,%1,%2,%3,%4,%5,%6,%7,%8,%9,%10,%11,%12,%13,%14,%15,%16,%17,%18,%19,%20,%21,%22,%23,%24,%25,%26,%27,%28,%29,%30,%31,%32,%33,%34,%35,%36,%37,%38,%39,%40,%41,%42,%43,%44,%45,%46,%47,%48,%49,%50,%51,%52,%53,%54,%55,%56,%57,%58,%59,%60,%61,%62,%63}, {%64,%65,%66,%67}, %68, 0, 1, 1, 0;\n"
                 : "=f"(acc[0][0]), "=f"(acc[0][1]), "=f"(acc[0][2]), "=f"(acc[0][3]), "=f"(acc[1][0]), "=f"(acc[1][1]), "=f"(acc[1][2]), "=f"(acc[1][3]), "=f"(acc[2][0]), "=f"(acc[2][1]), "=f"(acc[2][2]), "=f"(acc[2][3]), "=f"(acc[3][0]), "=f"(acc[3][1]), "=f"(acc[3][2]), "=f"(acc[3][3]), "=f"(acc[4][0]), "=f"(acc[4][1]), "=f"(acc[4][2]), "=f"(acc[4][3]), "=f"(acc[5][0]), "=f"(acc[5][1]), "=f"(acc[5][2]), "=f"(acc[5][3]), "=f"(acc[6][0]), "=f"(acc[6][1]), "=f"(acc[6][2]), "=f"(acc[6][3]), "=f"(acc[7][0]), "=f"(acc[7][1]), "=f"(acc[7][2]), "=f"(acc[7][3]), "=f"(acc[8][0]), "=f"(acc[8][1]), "=f"(acc[8][2]), "=f"(acc[8][3]), "=f"(acc[9][0]), "=f"(acc[9][1]), "=f"(acc[9][2]), "=f"(acc[9][3]), "=f"(acc[10][0]), "=f"(acc[10][1]), "=f"(acc[10][2]), "=f"(acc[10][3]), "=f"(acc[11][0]), "=f"(acc[11][1]), "=f"(acc[11][2]), "=f"(acc[11][3]), "=f"(acc[12][0]), "=f"(acc[12][1]), "=f"(acc[12][2]), "=f"(acc[12][3]), "=f"(acc[13][0]), "=f"(acc[13][1]), "=f"(acc[13][2]), "=f"(acc[13][3]), "=f"(acc[14][0]), "=f"(acc[14][1]), "=f"(acc[14][2]), "=f"(acc[14][3]), "=f"(acc[15][0]), "=f"(acc[15][1]), "=f"(acc[15][2]), "=f"(acc[15][3])
                 : "r"(a[0]), "r"(a[1]), "r"(a[2]), "r"(a[3]), "l"(desc));
}
template <> __device__ __forceinline__ void wg_first<4>(float (&acc)[16][4], const uint32_t* a, uint64_t desc) {
    asm volatile("wgmma.mma_async.sync.aligned.m64n96k16.f32.f16.f16 {%0,%1,%2,%3,%4,%5,%6,%7,%8,%9,%10,%11,%12,%13,%14,%15,%16,%17,%18,%19,%20,%21,%22,%23,%24,%25,%26,%27,%28,%29,%30,%31,%32,%33,%34,%35,%36,%37,%38,%39,%40,%41,%42,%43,%44,%45,%46,%47}, {%48,%49,%50,%51}, %52, 0, 1, 1, 0;\n"
                 : "=f"(acc[4][0]), "=f"(acc[4][1]), "=f"(acc[4][2]), "=f"(acc[4][3]), "=f"(acc[5][0]), "=f"(acc[5][1]), "=f"(acc[5][2]), "=f"(acc[5][3]), "=f"(acc[6][0]), "=f"(acc[6][1]), "=f"(acc[6][2]), "=f"(acc[6][3]), "=f"(acc[7][0]), "=f"(acc[7][1]), "=f"(acc[7][2]), "=f"(acc[7][3]), "=f"(acc[8][0]), "=f"(acc[8][1]), "=f"(acc[8][2]), "=f"(acc[8][3]), "=f"(acc[9][0]), "=f"(acc[9][1]), "=f"(acc[9][2]), "=f"(acc[9][3]), "=f"(acc[10][0]), "=f"(acc[10][1]), "=f"(acc[10][2]), "=f"(acc[10][3]), "=f"(acc[11][0]), "=f"(acc[11][1]), "=f"(acc[11][2]), "=f"(acc[11][3]), "=f"(acc[12][0]), "=f"(acc[12][1]), "=f"(acc[12][2]), "=f"(acc[12][3]), "=f"(acc[13][0]), "=f"(acc[13][1]), "=f"(acc[13][2]), "=f"(acc[13][3]), "=f"(acc[14][0]), "=f"(acc[14][1]), "=f"(acc[14][2]), "=f"(acc[14][3]), "=f"(acc[15][0]), "=f"(acc[15][1]), "=f"(acc[15][2]), "=f"(acc[15][3])
                 : "r"(a[0]), "r"(a[1]), "r"(a[2]), "r"(a[3]), "l"(desc));
}

#define EARLYN 2
#define K8 0
#define HOLD 3
#define MC 1
#define STAMPW(i) STAMPY(i)
#define STAMP2(i) STAMP(i)
#undef STAMPX
#define STAMPX(i)
#define PBAR 1
#define WDLY 500
#define CBAR 1
#define FDLY 900
#define FDLY2 0
#define YDLY 1
#define YFROM 0
#define YPRE 0
#define KDLY 850
#define OEARLY 0
#define ODLY 0
#define SORD 1
#define SDLY 900
#define UDLY 1400
#define XCP 1
#define DEFER 0
#define EXP 0
#define XWHEN 0
#define RWHEN 0
#define HW 11
#define PEARLY 1
#define XG 6
struct Params {
    const bf16 *x, *lar, *aim, *cre, *cim, *ldt, *dsk;
    Scratch* s;
    const bf16 *wr, *wg, *wu, *wd;
    bf16* out;
};

#define TOK(g) (2 * (g) - ((g) & 1))
#define ROWTOK(r) (TOK((r) & 7) + (((r) >> 2) & 2))
__device__ __forceinline__ void ln_partial(const uint32_t (&H)[2][4], float (&d)[2][4]) {
#pragma unroll
    for (int hf = 0; hf < 2; hf++) {
        d[hf][0] = d[hf][1] = d[hf][2] = d[hf][3] = 0.f;
        mma_bf16(d[hf], H[hf][0], 0x3f803f80u, H[hf][1], 0x3f803f80u, H[hf][0], H[hf][1]);
    }
#pragma unroll
    for (int hf = 0; hf < 2; hf++) mma_bf16(d[hf], H[hf][2], 0x3f803f80u, H[hf][3], 0x3f803f80u, H[hf][2], H[hf][3]);
}
__device__ __forceinline__ float sum18(uint32_t a) {
    const uint4 p = lds128(a), q = lds128(a + 16), r = lds128(a + 32), s = lds128(a + 48);
    const uint2 u = lds64(a + 64);
#define F(x) __uint_as_float(x)
    return (((F(p.x) + F(p.y)) + (F(p.z) + F(p.w))) + ((F(q.x) + F(q.y)) + (F(q.z) + F(q.w)))) +
           (((F(r.x) + F(r.y)) + (F(r.z) + F(r.w))) + ((F(s.x) + F(s.y)) + (F(s.z) + F(s.w))) + (F(u.x) + F(u.y)));
#undef F
}
__device__ __forceinline__ void ln_stats(float sm, float sq, float& mb, float& sd) {
    const float m0 = sm * (1.0f / 576.0f);
    const float mean = fmaf(fmaf(-m0, 576.0f, sm), 1.0f / 576.0f, m0);
    const float var = fmaxf(fmaf(-mean, mean, sq * (1.0f / 576.0f)), 0.f);
    mb = rbf(mean);
    sd = rbf(sqrt_approx(rbf(rbf(var) + 1e-5f)));
}
__device__ __forceinline__ void ln_finish(float v, int lane, float& mb, float& rc) {
    const float o = __shfl_xor_sync(0xffffffffu, v, 16);
    float sd;
    ln_stats(lane < 16 ? v : o, lane < 16 ? o : v, mb, sd);
    rc = rcp_approx(sd);
}
__device__ __forceinline__ uint32_t ln_apply(uint32_t w, uint32_t m2, uint32_t rh, uint32_t rl) {
    const uint32_t d = hsub2_bf(w, m2);
    return hfma2_bf(d, rh, hmul2_bf(d, rl));
}
__device__ __forceinline__ void stat_store(uint32_t a, float mb, float rc, uint32_t extra) {
    const float rh = rbf(rc);
    sts64(a, (__float_as_uint(mb) >> 16) | (extra << 16), pack_bf16(rh, rc - rh));
}
#define STAT_M(s) __byte_perm((s).x, (s).x, 0x1010)
#define STAT_H(s) __byte_perm((s).y, (s).y, 0x1010)
#define STAT_L(s) __byte_perm((s).y, (s).y, 0x3232)

__device__ __forceinline__ void hcmul(uint32_t re, uint32_t im, uint32_t zx, uint32_t zy, uint32_t& ore, uint32_t& oim) {
    ore = hfms2(im, zy, hmul2(re, zx));
    oim = hfma2(re, zy, hmul2(im, zx));
}

struct KGen {
    uint32_t A[2][4][4];
    float2 z1, z8, z64, z128, T[9];
};
__device__ __forceinline__ void kgen_setup(KGen& k, float lar, float aim, float dt) {
    const float lr2 = -(exp_bf(lar) * dt) * 1.4426950408889634f, li = aim * dt;
    k.z1 = cexp_e(lr2, li, 1.0f);
    k.z8 = cexp_e(lr2, li, 8.0f);
    k.z64 = cexp_e(lr2, li, 64.0f);
}
__device__ __forceinline__ void kgen_rows(KGen& k, uint32_t tb, int lane) {
    const float2 z8 = k.z8, z64 = k.z64;
    const uint32_t row = tb + lane * 16;
    k.z128 = csq(z64);
    const float2 z16 = csq(z8), z24 = cmul(z16, z8), z32 = csq(z16), z40 = cmul(z32, z8), z48 = csq(z24), z56 = cmul(z32, z24);
    uint32_t re[4], im[4], a[4], b[4];
    re[0] = pack_f16(1.0f, z8.x); im[0] = pack_f16(0.0f, z8.y);
    re[1] = pack_f16(z16.x, z24.x); im[1] = pack_f16(z16.y, z24.y);
    re[2] = pack_f16(z32.x, z40.x); im[2] = pack_f16(z32.y, z40.y);
    re[3] = pack_f16(z48.x, z56.x); im[3] = pack_f16(z48.y, z56.y);
    sts128(row, re[0], re[1], re[2], re[3]);
    sts128(row + 1024, im[0], im[1], im[2], im[3]);
    const uint32_t zx = pack_f16(z64.x, z64.x), zy = pack_f16(z64.y, z64.y), zw = pack_f16(k.z128.x, k.z128.y);
#pragma unroll
    for (int j = 0; j < 4; j++) hcmul(re[j], im[j], zx, zy, a[j], b[j]);
    sts128(row + 512, a[0], a[1], a[2], a[3]);
    sts128(row + 1536, b[0], b[1], b[2], b[3]);
    const int mi = lane >> 3;
    const uint32_t zd = tb + 2048 + mi * 16;
    sts16(tb + 2048 + lane * 2, zw); sts16(tb + 2112 + lane * 2, zw >> 16);
    __syncwarp();
    const uint32_t ad = tb + (lane & 7) * 16 + mi * 512;
    ldsm_x4(a[0], a[1], a[2], a[3], zd);
    ldsm_x4(b[0], b[1], b[2], b[3], zd + 64);
#pragma unroll
    for (int ks = 0; ks < 4; ks++) {
        ldsm_x4_t(k.A[0][ks][0], k.A[0][ks][1], k.A[0][ks][2], k.A[0][ks][3], ad + ks * 128);
        hcmul(k.A[0][ks][0], k.A[0][ks][2], a[ks], b[ks], k.A[1][ks][0], k.A[1][ks][2]);
        hcmul(k.A[0][ks][1], k.A[0][ks][3], a[ks], b[ks], k.A[1][ks][1], k.A[1][ks][3]);
    }
}
__device__ __forceinline__ void kgen_chain(KGen& k, uint32_t cr, uint32_t ci, float cs) {
    k.T[0] = make_float2(bf_lo(cr) * cs, -bf_lo(ci) * cs);
    const float2 y1 = make_float2(k.z1.x, -k.z1.y);
#pragma unroll
    for (int c = 1; c < 8; c++) k.T[c] = cmul(k.T[c - 1], y1);
    k.T[8] = cmul(k.T[0], make_float2(k.z8.x, -k.z8.y));
}
__device__ __forceinline__ void kgen_cols(KGen& k, uint32_t tb, uint32_t t5, int lane) {
    const uint32_t row = tb + lane * 16;
    const float2 (&T)[9] = k.T;
    const float2 y128 = make_float2(k.z128.x, -k.z128.y);
    const float2 y256 = csq(y128), y512 = csq(y256), y768 = cmul(y512, y256), y1024 = csq(y512);
    const float2 c1032 = cmul(T[8], y1024);
    __syncwarp();
    sts128(row, pack_f16(T[0].x, T[1].x), pack_f16(T[2].x, T[3].x), pack_f16(T[4].x, T[5].x), pack_f16(T[6].x, T[7].x));
    sts128(row + 512, pack_f16(T[0].y, T[1].y), pack_f16(T[2].y, T[3].y), pack_f16(T[4].y, T[5].y), pack_f16(T[6].y, T[7].y));
    uint32_t a[4], b[4];
    {
        const uint32_t zx = pack_f16(y256.x, y256.x), zy = pack_f16(y256.y, y256.y);
        hcmul(pack_f16(T[0].x, T[2].x), pack_f16(T[0].y, T[2].y), zx, zy, a[0], b[0]);
        hcmul(pack_f16(T[4].x, T[6].x), pack_f16(T[4].y, T[6].y), zx, zy, a[1], b[1]);
        const uint32_t r04 = pack_f16(T[0].x, T[4].x), i04 = pack_f16(T[0].y, T[4].y);
        hcmul(r04, i04, pack_f16(y512.x, y512.x), pack_f16(y512.y, y512.y), a[2], b[2]);
        hcmul(r04, i04, pack_f16(y768.x, y768.x), pack_f16(y768.y, y768.y), a[3], b[3]);
    }
    sts128(row + 1024, a[0], a[1], a[2], a[3]);
    sts128(row + 1536, b[0], b[1], b[2], b[3]);
    {
        const uint32_t r0 = pack_f16(1.0f, y256.x), i0 = pack_f16(0.0f, y256.y), r1 = pack_f16(y512.x, y768.x), i1 = pack_f16(y512.y, y768.y);
        const uint32_t zx = pack_f16(T[8].x, T[8].x), zy = pack_f16(T[8].y, T[8].y), wx = pack_f16(c1032.x, c1032.x), wy = pack_f16(c1032.y, c1032.y);
        hcmul(r0, i0, zx, zy, a[0], b[0]); hcmul(r1, i1, zx, zy, a[1], b[1]);
        hcmul(r0, i0, wx, wy, a[2], b[2]); hcmul(r1, i1, wx, wy, a[3], b[3]);
    }
    sts128(row + 2048, a[0], a[1], a[2], a[3]);
    sts128(t5 + lane * 16, b[0], b[1], b[2], b[3]);
}
__device__ __forceinline__ void kgen_mma(const KGen& k, uint32_t tb, uint32_t t5, int lane, uint32_t hb) {
    __syncwarp();
    float acc[2][3][4];
#pragma unroll
    for (int i = 0; i < 6; i++)
#pragma unroll
        for (int j = 0; j < 4; j++) acc[i / 3][i % 3][j] = 0.f;
    const int mi = lane >> 3;
    const uint32_t ro = ((lane & 7) + 8 * (mi >> 1)) * 16, bd = tb + ro + (mi & 1) * 512, b2 = ro + ((mi & 1) ? t5 : tb + 2048);
#pragma unroll
    for (int kp = 0; kp < 2; kp++)
#pragma unroll
        for (int j = 0; j < 3; j++) {
            uint32_t b[4];
            if (HOLD == 5 && kp == 1 && j == 0) mbar_wait1(hb);
            ldsm_x4_t(b[0], b[1], b[2], b[3], (j < 2 ? bd + j * 1024 : b2) + kp * 256);
#pragma unroll
            for (int h = 0; h < 2; h++)
#pragma unroll
                for (int m = 0; m < 2; m++) {
                    const uint32_t (&A)[4] = k.A[m][2 * kp + h];
                    mma_f16(acc[m][j], A[0], A[1], A[2], A[3], b[2 * h], b[2 * h + 1]);
                }
        }
    __syncwarp();
#define PK(j) pack_f16(acc[0][j][0], acc[0][j][1]), pack_f16(acc[0][j][2], acc[0][j][3]), pack_f16(acc[1][j][0], acc[1][j][1]), pack_f16(acc[1][j][2], acc[1][j][3])
    stsm_x4(tb + lane * 16, PK(0));
    stsm_x4(tb + 512 + lane * 16, PK(1));
    stsm_x4_t(tb + 1024 + (lane & 7) * 80 + mi * 16, PK(2));
#undef PK
}
__device__ __forceinline__ uint32_t table_buf(uint32_t sb, int warp) { return sb + SM_PL + warp * TBW; }

__device__ __forceinline__ uint4 lds16x4(uint32_t a) { return make_uint4(lds16(a), lds16(a + TBW), lds16(a + 2 * TBW), lds16(a + 3 * TBW)); }
__device__ __forceinline__ void combine_setup(uint32_t sb, int warp, int lane, uint32_t kw, uint32_t& o, uint32_t& n, uint32_t& d) {
    const int wq = warp & 3;
    const uint32_t a = table_buf(sb, warp & ~3);
    o = wq == 3 ? a + 1024 + 320 + (lane >> 3) * 80 + (lane & 7) * 8 : a + (wq ? 504 + wq * 8 : 0) + lane * 16;
    n = a + 1024 + wq * 80 + lane * 2;
    d = wq < 3 ? kw + (wq == 2 ? KW_P : 32 + wq * 512) + lane * 16 : kw + KW_H + 8 + lane * 8;
}
__device__ __forceinline__ void kgen_combine(int wq, int lane, uint32_t o, uint32_t na, uint32_t d) {
#define S4(f) hadd2(hadd2(u.f, v.f), hadd2(w.f, x.f))
#define H4(v) hadd2(hadd2(v.x, v.y), hadd2(v.z, v.w))
#define BP __byte_perm
    if (wq == 0) {
        const uint4 u = lds128(o), v = lds128(o + TBW), w = lds128(o + 2 * TBW), x = lds128(o + 3 * TBW), nn = lds16x4(na);
        const uint32_t n = H4(nn), k0 = S4(x), k2 = S4(y), k4 = S4(z), k6 = S4(w);
        sts128(d, BP(k0, k0, 0x1032), BP(k0, k2, 0x3254), BP(k2, k2, 0x1032), BP(k2, k4, 0x3254));
        sts128(d + KW_PL, BP(k4, k4, 0x1032), BP(k4, k6, 0x3254), BP(k6, k6, 0x1032), BP(k6, n, 0x3254));
        if (lane == 0) sts32(d + KW_PL - 4, k0 & 0xffffu);
    } else {
        const uint2 u = lds64(o), v = lds64(o + TBW), w = lds64(o + 2 * TBW), x = lds64(o + 3 * TBW);
        uint4 nn = make_uint4(0u, 0u, 0u, 0u), mm = nn;
        if (wq < 3) nn = lds16x4(na);
        if (wq == 2) mm = lds16x4(na + 80);
        const uint32_t k0 = S4(x), k2 = S4(y), n = H4(nn), m = H4(mm);
        if (wq == 3) {
            sts64(d, k0, k2);
        } else if (wq == 1) {
            const uint32_t cc = BP(k2, k2, 0x1010);
            sts128(d, BP(k0, k0, 0x1010), BP(k0, k0, 0x1032), BP(k0, k2, 0x3254), cc);
            sts128(d + KW_PL, cc, BP(k2, k2, 0x1032), BP(k2, n, 0x3254), BP(n, n, 0x1010));
        } else {
            const uint32_t w40 = BP(k0, k0, 0x1032), w84 = BP(k0, n, 0x3254), w0 = BP(k0, k0, 0x1010), w4 = BP(k0, k0, 0x3232), w8 = BP(n, n, 0x1010);
            sts64(d, w40, w84);
            sts64(d + 512, BP(k2, k2, 0x1032), BP(k2, m, 0x3254));
            if (lane < 8) { sts128(d - (KW_P - 1056), w0, w0, w40, w4); sts128(d - (KW_P - 1056 - KW_PL), w4, w84, w8, w8); }
            if (lane == 31) sts16(d + (KW_H + 6 - KW_P - 496), m);
        }
    }
#undef S4
#undef H4
#undef BP
}

__device__ __forceinline__ int c_exponent(const uint2& r, const uint2& i, float dt) {
    const uint32_t mx = __vmaxu2(__vmaxu2(r.x & 0x7fff7fffu, r.y & 0x7fff7fffu), __vmaxu2(i.x & 0x7fff7fffu, i.y & 0x7fff7fffu));
    return __reduce_max_sync(0xffffffffu, max(mx, mx << 16) + (__float_as_uint(dt) & 0x7f800000u)) >> 23;
}

#define ONEBAR 1
__device__ __forceinline__ int warp_v() { int l; asm volatile("mov.u32 %0, %%tid.x;" : "=r"(l)); return __shfl_sync(0xffffffffu, l >> 5, 0); }
__device__ __forceinline__ int lane_v() { int l; asm volatile("mov.u32 %0, %%laneid;" : "=r"(l)); return l; }
__device__ __forceinline__ uint32_t prmt_v(uint32_t a, uint32_t b, uint32_t s) { uint32_t d; asm volatile("prmt.b32 %0, %1, %2, %3;\n" : "=r"(d) : "r"(a), "r"(b), "r"(s)); return d; }
__device__ __forceinline__ uint32_t mov_v(uint32_t a) { uint32_t d; asm volatile("mov.b32 %0, %1;\n" : "=r"(d) : "r"(a)); return d; }
template <int G>
__device__ __forceinline__ void conv_rename(float (&acc)[16][4]) {
#pragma unroll
    for (int i = G; i < 16; i++)
#pragma unroll
        for (int j = 0; j < 4; j++) { float v; asm volatile("mov.b32 %0, %1;\n" : "=f"(v) : "f"(acc[i][j])); acc[i][j] = v; }
}
struct Conv {
    uint32_t kw;
    uint32_t wa;
    uint32_t pa, s2;
    uint32_t s8;
    uint32_t id;
    uint32_t lc;
    uint32_t fs;
    uint32_t fl, yo;
    uint32_t yp;
    size_t ycopy;
    uint32_t ps;
    uint64_t d0;
    int warp;
};
struct Pk { uint32_t w[4]; };
__device__ __forceinline__ Pk pk2(const float (&u)[4], const float (&v)[4]) {
    Pk r;
    r.w[0] = pack_f16(u[0], u[1]); r.w[1] = pack_f16(u[2], u[3]); r.w[2] = pack_f16(v[0], v[1]); r.w[3] = pack_f16(v[2], v[3]);
    return r;
}
__device__ __forceinline__ void park(uint32_t a, const Pk& v) {
    asm volatile("stmatrix.sync.aligned.m8n8.x4.trans.shared.b16 [%0], {%1,%2,%3,%4};\n" ::"r"(a), "r"(v.w[0]), "r"(v.w[1]), "r"(v.w[2]), "r"(v.w[3]) : "memory");
}
__device__ __forceinline__ void conv_constants(uint32_t lc, int l) {
    const int d = (l >> 2) - 2 * (l & 3);
    const int e = d + 8, r4 = (e + 1 + ((e >> 2) & 1)) >> 2, p4 = (e + (((e - 1) >> 2) & 1)) >> 2;
    const uint32_t s2 = r4 == p4 ? 0x1010u : 0x3210u;
    sts64(lc + l * 8, KW_P + ((r4 - 5) >> 1) * 16 + ((r4 - 5) & 1) * 4, s2 | ((d < 0 ? s2 : 0x7654u) << 16));
    const int lo = (d >= 4) - (d < -3), ho = (d >= 5) - (d < -2), le = (d > 4) - (d < -4), he = (d > 5) - (d < -3);
    sts32(lc + 512 + l * 8, (0x5454u + lo * 0x22 + ho * 0x2200) | ((0x3232u + le * 0x22 + he * 0x2200) << 16));
    const int cc = l >> 2, j = l & 3;
    sts64(lc + 256 + l * 8, (j >> 1) * PL_HALF + (16 + cc) * 16 + (j & 1) * 8, (cc >> 1) * (DM * 64) + (cc & 1) * 32 + j * 8);
}
__device__ __forceinline__ void conv_selectors4(Conv& c) {
    const uint2 v = lds64(c.lc + lane_v() * 8);
    c.pa = v.x; c.s2 = v.y;
}
__device__ __forceinline__ void conv_selectors8(Conv& c) { c.s8 = lds32(c.lc + 512 + lane_v() * 8); }
template <int G, int I0, int I1>
__device__ __forceinline__ void conv_load(const Conv& c, uint32_t (&q)[9]) {
    const int wq = c.warp & 3;
    if (G < 2) {
#pragma unroll
        for (int i = I0; i < I1; i++) q[i] = lds32(c.wa + G * 512 + i * 16);
    } else if (G < 4) {
        const uint32_t a = (G == 2 && wq == 0) ? c.wa + 1024 : c.pa + c.kw + wq * 128 + (G < 2 ? 0 : G - 2) * 512;
#pragma unroll
        for (int i = I0; i < I1; i++) q[i] = lds32(a + i * 16);
    } else {
        const uint4 u = lds128(c.kw + KW_H + (G < 4 ? 0 : G - 4) * 64 + wq * 16);
        const uint2 v = lds64(c.kw + KW_H + (G < 4 ? 0 : G - 4) * 64 + wq * 16 + 16);
        q[0] = u.x; q[1] = u.y; q[2] = u.z; q[3] = u.w; q[4] = v.x; q[5] = v.y;
        if (G == 4 && wq == 0) { q[6] = lds32(c.pa + c.kw + 1024); q[7] = lds32(c.pa + c.kw + 1040); }
    }
}
template <int G, int J0, int J1>
__device__ __forceinline__ void conv_frag(const Conv& c, const uint32_t (&q)[9], uint32_t* a, const Pk& dp) {
    const uint32_t dep = dp.w[0];
    if (G < 4) {
        const uint32_t s = (G < 2 || (G == 2 && (c.warp & 3) == 0)) ? c.id : c.s2;
#pragma unroll
        for (int j = J0; j < J1; j++) {
            uint32_t* o = a + 4 * (j - J0);
            o[0] = prmt_v(q[2 * j + 1], dp.w[0], s); o[1] = prmt_v(q[2 * j + 2], dp.w[1], s); o[2] = prmt_v(q[2 * j], dp.w[2], s); o[3] = prmt_v(q[2 * j + 1], dp.w[3], s);
        }
    } else {
        const uint32_t so = prmt_v(c.s8, dep, c.id), se = prmt_v(c.s8, dep, c.id + 0x22);
#pragma unroll
        for (int j = J0; j < J1; j++) {
            uint32_t* o = a + 4 * (j - J0);
            o[0] = prmt_v(q[j + 1], q[j + 2], se); o[1] = prmt_v(q[j + 1], q[j + 2], so); o[2] = prmt_v(q[j], q[j + 1], so);
            if (G == 4 && j == 0 && (c.warp & 3) == 0) {
                o[2] = prmt_v(q[6], dep, c.s2);
                o[0] = prmt_v(q[7], o[0], c.s2 >> 16);
            }
            o[3] = mov_v(o[0]);
        }
    }
}
template <int G, int J0, int J1>
__device__ __forceinline__ void conv_frag(const Conv& c, const uint32_t (&q)[9], uint32_t* a, float depf) {
    const uint32_t d = __float_as_uint(depf);
    conv_frag<G, J0, J1>(c, q, a, Pk{{d, d, d, d}});
}
template <int G, int T, int J0, int J1>
__device__ __forceinline__ void conv_mma(float (&acc)[16][4], const Conv& c, const uint32_t* a) {
#pragma unroll
    for (int j = J0; j < J1; j++) wg_mma<T>(acc, a + 4 * (j - J0), c.d0 - 8 * (2 * G - T) - j);
}
__device__ __forceinline__ float h_lo(uint32_t w) { return __half2float(__ushort_as_half((unsigned short)(w & 0xffffu))); }
__device__ __forceinline__ float h_hi(uint32_t w) { return __half2float(__ushort_as_half((unsigned short)(w >> 16))); }
__device__ __forceinline__ void flush_setup(Conv& c) {
    const uint2 v = lds64(c.lc + 256 + lane_v() * 8);
    c.fl = v.x; c.yo = v.y;
}
template <int Q>
__device__ __forceinline__ void flush_load(const Conv& c, uint32_t pl, uint2 (&f)[4]) {
#pragma unroll
    for (int w = 0; w < 4; w++) f[w] = lds64(c.fl + pl + (Q & 1) * 512 + w * (PLW_B - 64));
}
template <int Q>
__device__ __forceinline__ void flush_load_first(const Conv& c, uint32_t pl, uint2 (&f)[4], float depf) {
    const uint32_t p = prmt_v(c.fl, __float_as_uint(depf), c.id) + pl + (Q & 1) * 512;
#define LDV64(d, a) asm volatile("ld.volatile.shared.v2.u32 {%0,%1}, [%2];\n" : "=r"(d.x), "=r"(d.y) : "r"(a) : "memory")
    LDV64(f[0], p); LDV64(f[1], p + (PLW_B - 64)); LDV64(f[2], p + 2 * (PLW_B - 64)); LDV64(f[3], p + 3 * (PLW_B - 64));
}
#define FDEP __uint_as_float(f[3].y)
template <int Q, int mode>
__device__ __forceinline__ void conv_flush(const Conv& c, const uint2 (&f)[4], unsigned char* gy, uint32_t rx) {
    const uint32_t a0 = hadd2(f[0].x, f[1].x), a1 = hadd2(f[2].x, f[3].x), b0 = hadd2(f[0].y, f[1].y), b1 = hadd2(f[2].y, f[3].y);
    if (Q > 0 && mode == 1) {
        const uint32_t ra = rx + 16 + (Q > 0 ? Q - 1 : 0) * 1024 + (c.warp & 3) * 256 + lane_v() * 8;
        asm volatile("st.async.shared::cluster.mbarrier::complete_tx::bytes.v2.b32 [%0], {%1,%2}, [%3];\n"
                     ::"r"(ra ^ 0x1000000u), "r"(hadd2(a0, a1)), "r"(hadd2(b0, b1)), "r"((rx + (Q > 1 ? 8 : 0)) ^ 0x1000000u) : "memory");
        return;
    }
    float v0 = h_lo(a0) + h_lo(a1), v1 = h_hi(a0) + h_hi(a1), v2 = h_lo(b0) + h_lo(b1), v3 = h_hi(b0) + h_hi(b1);
    if (Q > 0 && mode == 2) {
        const uint2 o = lds64(rx + 16 + (Q > 0 ? Q - 1 : 0) * 1024 + (c.warp & 3) * 256 + lane_v() * 8);
        v0 += h_lo(o.x); v1 += h_hi(o.x); v2 += h_lo(o.y); v3 += h_hi(o.y);
    }
    const uint32_t lo = hmul2_bf(pack_bf16(v0, v1), c.fs), hi = hmul2_bf(pack_bf16(v2, v3), c.fs);
    stg64(gy + Q * 32 * DM * 32 + (c.yo + (Q < 3 ? c.yp : 0u)), nzw(lo), nzw(hi));
}
template <int I, bool S = false> struct IC { static constexpr int value = I; static constexpr bool shared = S; };
template <class T> __device__ constexpr bool wg_is4() { return T::shared; }
#define SLOT(n) (c.ps + (2 + ((n) & 7)) * 128)
#define GO() do { wg_commit(); __syncwarp(); } while (0)
#define DEP acc[15][3]
template <class FG, class FP, class FN>
__device__ __forceinline__ void conv_head(Conv& c, float (&acc)[16][4], uint32_t (&q)[9], uint32_t (&r)[9], uint32_t* a, FG fg, FP pre, FN next) {
    c.id = 0x3210u + (c.warp >> 8);
    if (ONEBAR) pre();
    conv_load<0, 0, 9>(c, q);
    conv_frag<0, 0, 1>(c, q, a, 0.f);
    if (!ONEBAR) pre();
    wg_fence(); wg_first<0>(acc, a, c.d0); GO();
    park(c.ps, Pk{{0u, 0u, 0u, 0u}});
    wg_wait0();
    conv_frag<0, 1, 2>(c, q, a, DEP);
    wg_fence(); conv_mma<0, 0, 1, 2>(acc, c, a); GO();
    fg(IC<0>());
    wg_wait0();
    conv_frag<0, 2, 3>(c, q, a, DEP);
    wg_fence(); conv_mma<0, 0, 2, 3>(acc, c, a); GO();
    conv_load<1, 0, 5>(c, r);
    wg_wait0();
    conv_frag<0, 3, 4>(c, q, a, DEP);
    wg_fence(); conv_mma<0, 0, 3, 4>(acc, c, a); GO();
    conv_load<1, 5, 9>(c, r);
    fg(IC<1>());
    wg_wait0();
    const Pk k = pk2(acc[0], acc[1]);
    conv_rename<2>(acc);
    conv_frag<1, 0, 2>(c, r, a, k);
    wg_fence(); conv_mma<1, 2, 0, 2>(acc, c, a); GO();
    park(SLOT(0), k);
    next(IC<0>());
    fg(IC<2>());
    wg_wait0();
    conv_frag<1, 2, 4>(c, r, a, DEP);
    wg_fence(); conv_mma<1, 2, 2, 4>(acc, c, a); GO();
    next(IC<1>());
    fg(IC<3>());
    wg_wait0();
}
template <class FG, class FP>
__device__ __forceinline__ void conv_run(Conv& c, uint32_t pl, unsigned char* gy, FG fg, FP pre) {
    float acc[16][4];
    uint32_t q[9], r[9], a[32];
    uint2 f[4];
    const int bid = 1 + (c.warp >> 2);
    conv_head(c, acc, q, r, a, fg, pre, [&](auto i) { if (decltype(i)::value == 0) conv_selectors4(c); else conv_load<2, 0, 9>(c, q); });
    Pk k = pk2(acc[2], acc[3]);
    conv_rename<4>(acc);
    conv_frag<2, 0, 4>(c, q, a, k);
    wg_fence(); conv_mma<2, 4, 0, 4>(acc, c, a); GO();
    park(SLOT(2), k);
    conv_load<3, 0, 9>(c, q);
    flush_setup(c);
    bar_sync(bid, 128);
    fg(IC<4>());
    wg_wait0();
    conv_rename<6>(acc);
    flush_load_first<0>(c, pl, f, DEP);
    conv_frag<3, 0, 4>(c, q, a, FDEP);
    wg_fence(); conv_mma<3, 6, 0, 4>(acc, c, a); GO();
    park(SLOT(4), pk2(acc[4], acc[5]));
    conv_load<4, 0, 9>(c, q);
    conv_selectors8(c);
    conv_flush<0, 0>(c, f, gy, 0u);
    fg(IC<5>());
    wg_wait0();
    conv_rename<8>(acc);
    conv_frag<4, 0, 4>(c, q, a, DEP);
    wg_fence(); conv_mma<4, 8, 0, 4>(acc, c, a); GO();
    k = pk2(acc[6], acc[7]);
    park(SLOT(6), k); park(c.ps, k);
    conv_load<5, 0, 9>(c, q);
    bar_sync(bid, 128);
    fg(IC<6>());
    wg_wait0();
    conv_rename<10>(acc);
    flush_load_first<1>(c, pl, f, DEP);
    conv_frag<5, 0, 4>(c, q, a, FDEP);
    wg_fence(); conv_mma<5, 10, 0, 4>(acc, c, a); GO();
    park(SLOT(8), pk2(acc[8], acc[9]));
    conv_load<6, 0, 9>(c, q); conv_load<7, 0, 9>(c, r);
    conv_flush<1, 0>(c, f, gy, 0u);
    fg(IC<7>());
    wg_wait0();
    conv_rename<12>(acc);
    conv_frag<6, 0, 4>(c, q, a, DEP); conv_frag<7, 0, 4>(c, r, a + 16, DEP);
    wg_fence(); conv_mma<6, 12, 0, 4>(acc, c, a); conv_mma<7, 12, 0, 4>(acc, c, a + 16); GO();
    park(SLOT(10), pk2(acc[10], acc[11]));
    bar_sync(bid, 128);
    flush_load<2>(c, pl, f);
    conv_flush<2, 0>(c, f, gy, 0u);
    fg(IC<8>());
    wg_wait0();
    park(SLOT(12), pk2(acc[12], acc[13])); park(SLOT(14), pk2(acc[14], acc[15]));
    bar_sync(bid, 128);
    flush_load<3>(c, pl, f);
    conv_flush<3, 0>(c, f, gy, 0u);
}
template <class FG>
__device__ __forceinline__ void conv_outer(Conv& c, uint32_t pl, unsigned char* gy, uint32_t rx, FG fg) {
    float acc[16][4];
    uint32_t q[9], r[9], a[32];
    uint2 f[4], f2[4];
    const int bid = 1 + (c.warp >> 2);
    conv_head(c, acc, q, r, a, [&](auto gi) { if (decltype(gi)::value == 2) fg(IC<2, true>()); }, [&]() {}, [&](auto i) { if (decltype(i)::value == 0) conv_selectors8(c); else conv_load<6, 0, 9>(c, q); });
    park(SLOT(2), pk2(acc[2], acc[3])); park(SLOT(4), pk2(acc[4], acc[5]));
    const Pk k = pk2(acc[6], acc[7]);
    park(SLOT(6), k);
    conv_load<7, 0, 9>(c, r);
    conv_rename<12>(acc);
    conv_frag<6, 0, 4>(c, q, a, __uint_as_float(k.w[3])); conv_frag<7, 0, 4>(c, r, a + 16, __uint_as_float(k.w[3]));
    wg_fence(); conv_mma<6, 12, 0, 4>(acc, c, a); conv_mma<7, 12, 0, 4>(acc, c, a + 16); GO();
    flush_setup(c);
    bar_sync(bid, 128);
    flush_load<0>(c, pl, f); flush_load<1>(c, pl, f2);
    conv_flush<1, 1>(c, f2, gy, rx);
    conv_flush<0, 1>(c, f, gy, rx);
    wg_wait0();
    bar_sync(bid, 128);
    park(c.ps, k); park(SLOT(8), pk2(acc[8], acc[9])); park(SLOT(10), pk2(acc[10], acc[11]));
    park(SLOT(12), pk2(acc[12], acc[13])); park(SLOT(14), pk2(acc[14], acc[15]));
    bar_sync(bid, 128);
    flush_load<2>(c, pl, f); flush_load<3>(c, pl, f2);
    conv_flush<2, 1>(c, f, gy, rx);
    conv_flush<3, 1>(c, f2, gy, rx);
}
template <class FG>
__device__ __forceinline__ void conv_inner(Conv& c, uint32_t pl, unsigned char* gy, uint32_t rx, FG fg) {
    float acc[16][4];
    uint32_t q[9], a[16];
    uint2 f[4], f2[4];
    const int bid = 1 + (c.warp >> 2);
    c.id = 0x3210u + (c.warp >> 8);
    conv_selectors4(c);
    conv_load<2, 0, 9>(c, q);
    conv_frag<2, 0, 4>(c, q, a, 0.f);
    wg_fence(); wg_first<4>(acc, a, c.d0); conv_mma<2, 4, 1, 4>(acc, c, a + 4); GO();
    conv_load<3, 0, 9>(c, q);
    park(SLOT(2), Pk{{0u, 0u, 0u, 0u}});
    fg(IC<2, true>());
    wg_wait0();
    conv_rename<6>(acc);
    conv_frag<3, 0, 4>(c, q, a, DEP);
    wg_fence(); conv_mma<3, 6, 0, 4>(acc, c, a); GO();
    park(SLOT(4), pk2(acc[4], acc[5]));
    conv_load<4, 0, 9>(c, q);
    conv_selectors8(c);
    wg_wait0();
    conv_rename<8>(acc);
    conv_frag<4, 0, 4>(c, q, a, DEP);
    wg_fence(); conv_mma<4, 8, 0, 4>(acc, c, a); GO();
    const Pk k = pk2(acc[6], acc[7]);
    park(SLOT(6), k); park(c.ps, k);
    conv_load<5, 0, 9>(c, q);
    flush_setup(c);
    wg_wait0();
    conv_rename<10>(acc);
    conv_frag<5, 0, 4>(c, q, a, DEP);
    wg_fence(); conv_mma<5, 10, 0, 4>(acc, c, a); GO();
    park(SLOT(8), pk2(acc[8], acc[9]));
    bar_sync(bid, 128);
    flush_load<1>(c, pl, f);
    mbar_wait(rx);
    conv_flush<1, 2>(c, f, gy, rx);
    wg_wait0();
    bar_sync(bid, 128);
    park(SLOT(10), pk2(acc[10], acc[11])); park(SLOT(12), pk2(acc[12], acc[13])); park(SLOT(14), pk2(acc[14], acc[15]));
    bar_sync(bid, 128);
    flush_load<3>(c, pl, f); flush_load<2>(c, pl, f2);
    mbar_wait(rx + 8);
    conv_flush<3, 2>(c, f, gy, rx);
    conv_flush<2, 2>(c, f2, gy, rx);
}
#undef SLOT
#undef GO
#undef DEP
template <int U0, int U1>
__device__ __forceinline__ void weight_units(uint32_t sb, const CUtensorMap* tg, const CUtensorMap* tu, const CUtensorMap* td, bool w) {
    if (U1 > U0 && w && elect_one()) {
#pragma unroll
        for (int n = U0; n < U1; n++) {
            const int i = n;
            if (i < 12) tma_2d(sb + SM_WG + i * 6912, i < 6 ? tg : tu, 72 * (blockIdx.x >> 1), 288 * (blockIdx.x & 1) + (i % 6) * 48, sb + SM_MISC + 328);
            else tma_2d(sb + SM_WD + (i - 12) * 4736, td, 144 * (blockIdx.x & 1), 72 * (blockIdx.x >> 1) + 8 * (i - 12), sb + SM_MISC + 336);
        }
    }
}
#define WS 1111121111122004100
__device__ constexpr int wsched(int i) {
    unsigned long long v = WS;
    int n = 0;
    for (int k = 19; k >= 1; k--) { if (k < i) n += (int)(v % 10); v /= 10; }
    return n;
}
static_assert(wsched(20) == 21 && wsched(6) <= 7 && wsched(11) <= 12 && wsched(16) <= 17 && wsched(16) == wsched(15) && wsched(19) == 21, "");
__device__ __forceinline__ void weight_prefetch(const Params& p, int u, int lane) {
    const int b = blockIdx.x;
    const char* a = u < 12 ? reinterpret_cast<const char*>(u < 6 ? p.wg : p.wu) + ((b >> 6) * 288 + (u % 6) * 48) * (FF * 2) + (b & 63) * 6912
                           : reinterpret_cast<const char*>(p.wd) + (72 * (b >> 1) + 8 * (u - 12)) * 1152 + (b & 1) * 4608;
    asm volatile("prefetch.global.L2 [%0];\n" ::"l"(a + lane * 128));
    if (lane < (u < 12 ? 22 : 4)) asm volatile("prefetch.global.L2 [%0];\n" ::"l"(a + 4096 + lane * 128));
}
#define PF0 0
#define PF1 0
#define WPOINT(i, w) do { weight_units<wsched(i), wsched(i + 1)>(sb, &tm_g, &tm_u, &tm_d, w); } while (0)

__global__ void __launch_bounds__(NTHR, 1) __cluster_dims__(2, 1, 1)
fused_kernel(const Params p, const __grid_constant__ CUtensorMap tm_g, const __grid_constant__ CUtensorMap tm_u, const __grid_constant__ CUtensorMap tm_d, const __grid_constant__ CUtensorMap tm_x) {
    extern __shared__ __align__(1024) unsigned char smem[];
    const uint32_t sb = smem_u32(smem);
    const int tid = threadIdx.x, warp = __shfl_sync(0xffffffffu, tid >> 5, 0), lane = tid & 31;
    const int b = blockIdx.x, P = b >> 1, odd = b & 1;
    const int g = lane >> 2, t = lane & 3;
    const int wg = warp >> 2, t128 = tid & 127;
    const uint32_t s_stat = sb + SM_MISC;
    const uint32_t s_key = sb + SM_MISC + 128;
    const uint32_t s_rank = sb + SM_MISC + 256;
    const uint32_t s_k16 = sb + SM_MISC + 192;
    const uint32_t s_cnt = sb + SM_MISC + 320;
    const uint32_t bar_w = sb + SM_MISC + 328, bar_d = bar_w + 8, bar_g = bar_w + 16, bar_x = bar_w + 24, bar_t = bar_w + 32, bar_s = bar_w + 40, bar_v = bar_w + 48, bar_h = sb + SM_MISC + 160;
    STAMP(0);

    if (warp == 19) {
        if (lane == 0) {
            mbar_init(bar_w, 1); mbar_init(bar_d, 1); mbar_init(bar_g, 1); mbar_init(sb + SM_RX, 1); mbar_init(sb + SM_RX + 8, 1);
            mbar_init(bar_x, 1); mbar_init(bar_t, 1); mbar_init(bar_s, 1); mbar_init(bar_v, 2); if (HOLD >= 2) { mbar_init(bar_h, 1); mbar_init(bar_h + 8, 1); mbar_init(bar_h + 16, 1); mbar_init(bar_h + 24, 1); } mbar_expect(bar_x, 32768);
            asm volatile("fence.mbarrier_init.release.cluster;\n" ::: "memory");
            mbar_expect(bar_w, 82944); mbar_expect(bar_d, 72 * WD_PITCH); mbar_expect(bar_g, 9216); mbar_expect(bar_t, 16 * 1152); mbar_expect(bar_v, 2 * 1152); mbar_expect(sb + SM_RX, 1024); mbar_expect(sb + SM_RX + 8, 2048);
        }
        __syncwarp();
    } else if (warp == 18) {
#pragma unroll
        for (int i = 0; i < 9; i++) sts128(sb + SM_ZERO + (i * 32 + lane) * 16, 0u, 0u, 0u, 0u);
        fence_async();
        __syncwarp();
    }
    const int ch = wg < 4 ? 4 * b + wg : 512 + P;
    const bf16 *q0 = p.lar + ch * NST, *q1 = p.aim + ch * NST, *q2 = p.cre + ch * NST, *q3 = p.cim + ch * NST;
    asm volatile("" : "+l"(q0), "+l"(q1), "+l"(q2), "+l"(q3));
    const uint32_t ldt = ldo16(p.ldt + ch), pl = ldo16(q0 + t128), pa2 = ldo16(q1 + t128);
    const uint32_t pc = ldo16(q2 + t128), pi = ldo16(q3 + t128);
    const uint2 call_re = ldo64(q2 + 4 * lane), call_im = ldo64(q3 + 4 * lane);
    const uint32_t epl = ld_poll32(p.s->hint + (b & 7) * 32 + 1);
    bar_sync(0, NWRK);
    if (XCP && wg == 4) {
        const int o = (4 * (warp & 3) + (g >> 1)) * 1152 + (g & 1) * 576 + t * 16;
#pragma unroll
        for (int c = 0; c < 9; c++)
            asm volatile("cp.async.cg.shared.global [%0], [%1], 16;\n" ::"r"(sb + SM_XT + o + c * 64), "l"(reinterpret_cast<const char*>(p.x) + b * 18432 + o + c * 64) : "memory");
        asm volatile("cp.async.commit_group;\n" ::: "memory");
    }
    asm volatile("barrier.cluster.arrive.relaxed.aligned;\n" ::: "memory");
    if (warp == 18) {
        if (lane == 0) {
            if (!XCP) bulk_g2s(sb + SM_XT, p.x + (size_t)16 * b * DM, 16 * 1152, bar_t);
            bulk_s2g(reinterpret_cast<unsigned char*>(p.s->y) + 96 * 18432 + b * 4608, sb + SM_ZERO, 4608);
        }
        bar_arrive(12, 64);
    }
    if (warp == 19) {
        bar_sync(12, 64);
        asm volatile("barrier.cluster.wait.aligned;\n" ::: "memory");
        if (EXP & 4) { if (elect_one()) asm volatile("mbarrier.complete_tx.relaxed.cta.shared::cta.b64 [%0], %1;" :: "r"(bar_x), "r"(32768) : "memory"); }
        else if (EXP & 8) { if (elect_one()) { tma_4d(sb + SM_XC + odd * 16384, &tm_x, 8 * P, 2 * odd, bar_x); asm volatile("mbarrier.complete_tx.relaxed.cta.shared::cta.b64 [%0], %1;" :: "r"(bar_x), "r"(16384) : "memory"); } }
        else
        if (elect_one()) tma_4d_mc(sb + SM_XC + odd * 16384, &tm_x, 8 * P, 2 * odd, bar_x);
        __syncwarp();
    }
    const uint32_t kw = sb + SM_KW + wg * KW_B;
    const uint32_t tb = table_buf(sb, warp), t5 = sb + SM_WD + warp * 512;
    if (wg == 4) {
        if (!(g & 1) && t == (g >> 1)) *reinterpret_cast<volatile uint32_t*>(p.s->stat + 16 * b + 4 * (warp & 3) + t) = 0u;
        if (warp < 18) {
            unsigned char* const ud = reinterpret_cast<unsigned char*>(p.s->uT) + (size_t)(8 * (warp & 1) + 2 * (g >> 1)) * 16384 + b * 128 + (g & 1) * 32 + t * 8;
#pragma unroll
            for (int k = 0; k < 4; k++) *reinterpret_cast<volatile unsigned long long*>(ud + (k >> 1) * 16384 + (k & 1) * 64) = 0ull;
        }
        if (warp == 17) conv_constants(sb + SM_LC, lane);
    } else if (warp == 0) {
#pragma unroll
        for (int i = 0; i < 6; i++) sts128(sb + SM_LNP + (i * 32 + lane) * 16, 0u, 0u, 0u, 0u);
    }
    if (t128 < 2 * UPAD) sts128(sb + SM_U + wg * USLOT_B + (t128 & 1) * ULO_B + (t128 >> 1) * 16, 0u, 0u, 0u, 0u);
    if (t128 >= 124) sts128(kw + (t128 & 1) * 16 + (t128 & 2) * (KW_PL / 2), 0u, 0u, 0u, 0u);
    uint32_t co, cn, cd;
    combine_setup(sb, warp, lane, kw, co, cn, cd);
    const uint4* usrc = wg < 4 ? reinterpret_cast<const uint4*>(p.s->stat) + tid
                               : reinterpret_cast<const uint4*>(p.s->uT) + (P >> 2) * 1024 + (t128 >> 1) * 8 + (P & 3) * 2 + (t128 & 1);
    uint32_t zero;
    {
        uint32_t uo = (uint32_t)(reinterpret_cast<const char*>(usrc) - reinterpret_cast<const char*>(p.s)), pk = (cn - co + 1024) | ((cd - kw) << 16);
        asm volatile("st.volatile.shared.v4.u32 [%4], {0, %1, %2, %3};\nld.volatile.shared.v4.u32 {%0, %1, %2, %3}, [%4];\n" : "=r"(zero), "+r"(co), "+r"(pk), "+r"(uo) : "r"(tb + lane * 16) : "memory");
        cn = co + (pk & 0xffffu) - 1024; cd = kw + (pk >> 16);
        usrc = reinterpret_cast<const uint4*>(reinterpret_cast<const char*>(p.s) + uo);
    }
    const float dt = exp_bf(__uint_as_float(__byte_perm(ldt, zero, 0x1044)));
    const uint32_t ep = __reduce_or_sync(0xffffffffu, epl | zero);
    auto stats = [&]() {
        const int wq = warp & 3;
        const uint32_t xa = sb + SM_XT + (4 * wq + (g >> 1)) * 1152 + (g & 1) * 576 + t * 16;
        const bool own = !(g & 1) && t == (g >> 1);
        float d[4][4] = {};
        if (XCP) asm volatile("cp.async.wait_group 0;\n" ::: "memory"); else mbar_wait(bar_t);
        if ((HOLD == 2 || HOLD == 5) && lane == 0) mbar_arrive(bar_h + 8 * wq);
        STAMP(26);
        uint4 v[9];
#pragma unroll
        for (int c = 0; c < 9; c++) v[c] = lds128(xa + c * 64);
#pragma unroll
        for (int c = 0; c < 9; c++) {
            mma_bf16(d[2 * (c & 1)], v[c].x, 0x3f803f80u, v[c].y, 0x3f803f80u, v[c].x, v[c].y);
            mma_bf16(d[2 * (c & 1) + 1], v[c].z, 0x3f803f80u, v[c].w, 0x3f803f80u, v[c].z, v[c].w);
        }
        STAMP(27);
        float sm = (g & 1) ? (d[0][3] + d[1][3]) + (d[2][3] + d[3][3]) : (d[0][2] + d[1][2]) + (d[2][2] + d[3][2]);
        float sq = (g & 1) ? (d[0][1] + d[1][1]) + (d[2][1] + d[3][1]) : (d[0][0] + d[1][0]) + (d[2][0] + d[3][0]);
        sm += __shfl_xor_sync(0xffffffffu, sm, 4); sq += __shfl_xor_sync(0xffffffffu, sq, 4);
        if (HOLD == 1) bar_arrive(6 + wq, 160);
        if (HOLD >= 2 && HOLD != 4 && lane == 0) mbar_arrive(bar_h + 8 * wq);
        float mb, sd;
        ln_stats(sm, sq, mb, sd);
        if (own) p.s->stat[16 * b + 4 * wq + t] = (__float_as_uint(mb) >> 16) | (__float_as_uint(sd) & 0x7fff0000u) | (ep << 31);
        STAMPX(22);
        if (HOLD == 4 && lane == 0) mbar_arrive(bar_h + 8 * wq);
        if (own) stat_store(s_stat + (2 * wq + (t & 1) + 8 * (t >> 1)) * 8, mb, rcp_approx(sd), 0u);
        if (wq == 2) asm volatile("cp.async.bulk.wait_group 0;\n" ::: "memory");
        bar_sync(5, 128);
        STAMP(28);
        if (wq == 2) {
            if (lane < 8) p.s->key3[8 * b + lane] = ep & 1u;
            if (lane == 0) {
                uint32_t now;
                asm volatile("mov.u32 %0, %%clock;" : "=r"(now));
                sts64(s_cnt, now, ep);
                mbar_arrive(bar_s);
                bulk_g2s(sb + SM_XT + 16 * 1152, p.dsk, 1152, bar_v);
                bulk_g2s(sb + SM_XT + 17 * 1152, p.wr, 1152, bar_v);
            }
            __syncwarp();
        }
        WPOINT(1, wq == 3);
        if (wq < 2) {
            unsigned char* const ud = reinterpret_cast<unsigned char*>(p.s->uT) + (size_t)(8 * wq + 2 * (g >> 1)) * 16384 + b * 128 + (g & 1) * 32 + t * 8;
            const uint32_t utag = (ep % 7u + 1u) * 0x10001u;
            uint32_t U[2][4];
#pragma unroll
            for (int hf = 0; hf < 2; hf++) {
                const uint2 st = lds64(s_stat + (g + 8 * hf) * 8);
                const uint4 xu = lds128(sb + SM_XT + (TOK(g) + 2 * hf) * 1152 + warp * 64 + t * 16);
                const uint32_t X[4] = {xu.x, xu.y, xu.z, xu.w};
#pragma unroll
                for (int k = 0; k < 4; k++) {
                    const uint32_t u = ln_apply(X[k], STAT_M(st), STAT_H(st), STAT_L(st));
                    U[hf][k] = movm((pack_f16(bf_lo(u), bf_hi(u)) & 0xfff8fff8u) | utag);
                }
            }
#pragma unroll
            for (int k = 0; k < 4; k++) stg64(ud + (k >> 1) * 16384 + (k & 1) * 64, U[0][k], U[1][k]);
        }
    };
    STAMP(1);
    if (wg < 4) { STAMPX(16); }
    if (SORD == 0 && wg == 4) stats();
    KGen kg;
    kgen_setup(kg, __uint_as_float(__byte_perm(pl, zero, 0x1044)), __uint_as_float(__byte_perm(pa2, zero, 0x1044)), dt);
    kgen_rows(kg, tb, lane);
    STAMP(2);
    const int E = min(max(c_exponent(call_re, call_im, dt) - 243, -120), 120);
    kgen_chain(kg, pc, pi, dt * __uint_as_float((uint32_t)(128 - E) << 23));
    STAMP(3);
    kgen_cols(kg, tb, t5, lane);
    STAMP(4);
    if (SORD == 1 && wg == 4) stats();
    if (warp != 19) asm volatile("barrier.cluster.wait.aligned;\n" ::: "memory");
    if (wg < 4) { STAMPX(17); }
    if (HOLD == 1 && wg < 4) bar_sync(6 + (warp & 3), 160);
    if ((HOLD == 3 || HOLD == 4) && wg < 4) mbar_wait(bar_h + 8 * (warp & 3));
    if (HOLD == 2 || HOLD == 5) mbar_wait1(bar_h + 8 * (warp & 3));
    if (wg < 4) { STAMPX(19); }
    if (DEFER == 1 && wg == 4) bar_sync(14, NWRK);
    if (DEFER > 1 && wg == 4) bar_sync(15, NWRK);
    kgen_mma(kg, tb, t5, lane, bar_h + 8 * (warp & 3));
    if (wg < 4) { STAMPX(20); }
    if (DEFER == 3 && wg < 4) bar_arrive(15, NWRK);
    STAMP(5);
    if (SORD == 2 && wg == 4) stats();
    uint4 uv0, uv1;
    auto first_poll = [&](uint32_t dly) {
        mbar_wait(bar_s);
        const uint32_t t0 = lds32(s_cnt);
        uint32_t now;
        do { asm volatile("mov.u32 %0, %%clock;" : "=r"(now) :: "memory"); } while (now - t0 < dly);
        uv0 = ld_poll(usrc);
    };
    WPOINT(2, warp == 19);
    if (PEARLY == 3 && wg < 4) first_poll(SDLY);
    bar_sync(1 + wg, 128);
    if (PEARLY == 2 && wg < 4) first_poll(SDLY);
    if (wg < 4) { STAMPX(21); }
    kgen_combine(warp & 3, lane, co, cn, cd);
    STAMP(6);
    if (wg < 4) { STAMPX(18); }
    if (DEFER == 2 && wg < 4) bar_arrive(15, NWRK);
    WPOINT(3, warp == 19);
    if (PEARLY == 1 && wg < 4) first_poll(SDLY);
    {
        const int wq = warp & 3;
        Conv c;
        const uint32_t pln = sb + SM_PL + wg * PL_B;
        const int e = g - 2 * t + 7;
        c.kw = kw; c.wa = pin(kw + ((e >> 2) & 1) * KW_PL + (8 * wq + (e >> 3)) * 16 + (e & 3) * 4);
        c.ps = mov_v(pln + wq * PLW_B + ((lane >> 3) & 1) * PL_HALF + ((lane >> 4) * 8 + (lane & 7)) * 16); c.warp = warp;
        c.lc = sb + SM_LC; c.fs = (uint32_t)(127 + E) * 0x800080u; c.yp = (ep & 1u) * (NCTA * 18432u);
        c.d0 = ((uint64_t)(ULO_B >> 4) << 16) | ((uint64_t)(128 >> 4) << 32) | (uint64_t)(((sb + SM_U + wg * USLOT_B + UPAD * 16) & 0x3FFFF) >> 4);
        unsigned char* gy = reinterpret_cast<unsigned char*>(p.s->y) + ((size_t)(4 * wq) * DM + ch) * 64;
        auto hook = [&](auto gi) {
                     constexpr int G = decltype(gi)::value;
                     if (G == (wg_is4<decltype(gi)>() ? 2 : 5)) asm volatile("barrier.cluster.wait.aligned;\n" ::: "memory");
                     if (!wg_is4<decltype(gi)>() && G < 4 && warp == HW) {
                         const int l2 = lane_v();
                         unsigned char* const sc = reinterpret_cast<unsigned char*>(p.s);
                         if (G == 0 && l2 < 2) bulk_s2g(sc + offsetof(Scratch, rows) + (127 - b) * 4608 + l2 * 2304, sb + SM_LNP, 2304);
                         if (b < 96 && l2 < ((G && !(EXP & 2)) ? 3 : 1))
                             bulk_s2g(l2 ? sc + offsetof(Scratch, y) + (NCTA * 18432u - c.yp) + b * 18432 + (2 * G + l2 - 3) * 3072 : sc + offsetof(Scratch, part) + b * 12288 + G * 3072,
                                      sb + SM_LNP, 3072);
                         __syncwarp();
                     }
                     if (!wg_is4<decltype(gi)>() && PF1 && G >= PF1 && G < PF1 + 2 && (warp >> 1) == 2) weight_prefetch(p, 17 + 2 * (G - PF1) + (warp & 1), lane_v());
                     if (!wg_is4<decltype(gi)>()) WPOINT(6 + G, warp == 12 + (G & 3));
                     if (!wg_is4<decltype(gi)>() && G == XG && warp == HW) {
                         asm volatile("cp.async.bulk.wait_group 0;\n" ::: "memory");
                         __syncwarp();
                         if (elect_one()) mbar_arrive(bar_v);
                     }
                 };
        if (!ONEBAR) bar_sync(1 + wg, 128);
        if (wg < 4) {
            asm volatile("barrier.cluster.arrive.relaxed.aligned;\n" ::: "memory");
            conv_run(c, pln + wq * 128, gy, hook, [&]() {
                STAMPX(23);
                mbar_wait(bar_x);
                STAMP(9);
                STAMPX(24);
                uint2 xc[4];
                uint32_t xw[4][2];
#pragma unroll
                for (int j = 0; j < 4; j++) xc[j] = lds64(sb + SM_XC + wg * 8192 + j * 2048 + t128 * 16 + odd * 8);
#pragma unroll
                for (int i = 0; i < 8; i++) {
                    const int k = i >> 1, h = i & 1;
                    xw[k][h] = prmt_v(k < 2 ? xc[2 * h].x : xc[2 * h].y, k < 2 ? xc[2 * h + 1].x : xc[2 * h + 1].y, (k & 1) ? 0x7632 : 0x5410);
                }
                const uint32_t ub = mov_v(sb + SM_U + UPAD * 16 + ((tid >> 1) & 1) * ULO_B + (tid >> 2) * 16 + (tid & 1) * 8), tag = ep << 31;
                int it = 0;
                if (!PEARLY) first_poll(SDLY);
                while (min(min((int)(uv0.x ^ tag), (int)(uv0.y ^ tag)), min((int)(uv0.z ^ tag), (int)(uv0.w ^ tag))) < 0x10000) {
                    if (++it > SPIN_LIMIT) TRAP();
                    uv0 = ld_poll(usrc);
                }
                STAMP(8);
                STAMPX(26);
                const float r0 = rcp_approx(fabsf(bf_hi(uv0.x))), r1 = rcp_approx(fabsf(bf_hi(uv0.y))), r2 = rcp_approx(fabsf(bf_hi(uv0.z))), r3 = rcp_approx(fabsf(bf_hi(uv0.w)));
                const uint32_t m[2] = {__byte_perm(uv0.x, uv0.y, 0x5410), __byte_perm(uv0.z, uv0.w, 0x5410)};
                const uint32_t rh[2] = {pack_bf16(r0, r1), pack_bf16(r2, r3)};
                const uint32_t rl[2] = {pack_bf16(r0 - bf_lo(rh[0]), r1 - bf_hi(rh[0])), pack_bf16(r2 - bf_lo(rh[1]), r3 - bf_hi(rh[1]))};
#pragma unroll
                for (int k = 0; k < 4; k++) {
                    const uint32_t u0 = ln_apply(xw[k][0], m[0], rh[0], rl[0]), u1 = ln_apply(xw[k][1], m[1], rh[1], rl[1]);
                    sts64(ub + k * USLOT_B, pack_f16(bf_lo(u0), bf_hi(u0)), pack_f16(bf_lo(u1), bf_hi(u1)));
                }
                STAMPX(29);
                fence_async();
                bar_sync(14, DEFER == 1 ? NWRK : 512);
                STAMP(7);
            });
        } else {
            auto stage = [&]() {
                const uint32_t tag = (ep % 7u + 1u) * 0x10001u;
                int it = 0;
                WPOINT(4, warp == 19);
                first_poll(UDLY);
                uv1 = ld_poll(usrc + 512);
                WPOINT(5, warp == 19);
                while (true) {
                    uv0.x ^= tag; uv0.y ^= tag; uv0.z ^= tag; uv0.w ^= tag; uv1.x ^= tag; uv1.y ^= tag; uv1.z ^= tag; uv1.w ^= tag;
                    if ((((uv0.x | uv0.y | uv0.z) | (uv0.w | uv1.x | uv1.y) | (uv1.z | uv1.w)) & 0x70007u) == 0) break;
                    if (++it > SPIN_LIMIT) TRAP();
                    uv0 = ld_poll(usrc); uv1 = ld_poll(usrc + 512);
                }
                STAMP(8);
                const uint32_t ub = sb + SM_U + UPAD * 16 + 4 * USLOT_B + (t128 & 1) * ULO_B + (t128 >> 1) * 16;
                sts128(ub, uv0.x, uv0.y, uv0.z, uv0.w);
                sts128(ub + 1024, uv1.x, uv1.y, uv1.z, uv1.w);
                fence_async();
                asm volatile("barrier.cluster.arrive.relaxed.aligned;\n" ::: "memory");
                bar_sync(5, 128);
                STAMP(7);
            };
            stage();
            if (odd) conv_inner(c, pln + wq * 128, gy, sb + SM_RX, hook);
            else conv_outer(c, pln + wq * 128, gy, sb + SM_RX, hook);
        }
        STAMP(10);
    }
    {
    const int lane = lane_v(), tid = 32 * warp + lane, g = lane >> 2, t = lane & 3;
    const uint32_t par = ~ep & 1u;
    if (CBAR) bar_sync(0, NWRK);
    STAMP(11);
    uint32_t H[2][4] = {}, U2[2][4] = {};
    uint32_t WA[9][4], WD[18];
    auto publish = [&](bool hi, int slot) {
        uint4* rowp = reinterpret_cast<uint4*>(p.s->rows) + slot * 144 + warp * 4 + t;
        stg128(rowp, nzw(hi ? U2[1][0] : U2[0][0]), nzw(hi ? U2[1][1] : U2[0][1]), nzw(hi ? U2[1][2] : U2[0][2]), nzw(hi ? U2[1][3] : U2[0][3]));
        stg128(rowp + 72, nzw(hi ? H[1][0] : H[0][0]), nzw(hi ? H[1][1] : H[0][1]), nzw(hi ? H[1][2] : H[0][2]), nzw(hi ? H[1][3] : H[0][3]));
    };
#define KTOK(k) (int)(((~(k) >> 5) & 0x7f0u) | (((k) >> 1) & 15u))
#define KLATE(k) (((k) & 0x1e0u) < 0xe0u)
#define KSLOT(k, s) (KLATE(k) ? 2 * NCTA + (s) : (int)(((k) >> 8) & 0xffu))
    const uint4* const rsrc = reinterpret_cast<const uint4*>(p.s->rows) + 36 * odd;
    auto gather = [&](uint32_t mine) {
        int it = 0;
        uint32_t mn;
        do {
            mn = 1;
#pragma unroll 1
            for (int r = 0; r < 9; r++) {
                const uint32_t k = __shfl_sync(0xffffffffu, mine, r < 8 ? 4 * r : lane);
                const int row = r < 8 ? r : g, c = r < 8 ? lane : 32 + t;
                asm volatile("cp.async.cg.shared.global [%0], [%1], 16;\n" ::"r"(sb + SM_XS + row * XS_PITCH + c * 16), "l"(rsrc + KSLOT(k, row) * 144 + c) : "memory");
            }
            asm volatile("cp.async.wait_all;\n" ::: "memory");
#pragma unroll 1
            for (int r = 0; r < 9; r++) mn = min(mn, min4(lds128(sb + SM_XS + (r < 8 ? r * XS_PITCH + lane * 16 : g * XS_PITCH + (32 + t) * 16))));
            if (++it > SPIN_LIMIT) TRAP();
        } while (__any_sync(0xffffffffu, mn == 0));
    };
    auto late_rows = [&](auto role) {
        const uint32_t kk = lds32(s_key + (lane & 7) * 4), ep = lds32(s_cnt + 4);
        const bool own = KLATE(kk) && (KTOK(kk) >> 4) == b;
        uint32_t todo = __ballot_sync(0xffffffffu, own) & 0xffu;
        if (decltype(role)::value == 0 && todo) {
#pragma unroll
            for (int hf = 0; hf < 2; hf++) {
                const uint4 h = lds128(sb + SM_U + hf * 9216 + tid * 16);
                const uint2 st = lds64(s_stat + (g + 8 * hf) * 8);
                H[hf][0] = h.x; H[hf][1] = h.y; H[hf][2] = h.z; H[hf][3] = h.w;
#pragma unroll
                for (int k = 0; k < 4; k++) U2[hf][k] = ln_apply(H[hf][k], STAT_M(st), STAT_H(st), STAT_L(st));
            }
#pragma unroll 1
            while (todo) {
                const int s = __ffs(todo) - 1, tk = KTOK(__shfl_sync(0xffffffffu, kk, s));
                todo &= todo - 1;
                if ((tk & 13) == TOK(g)) publish(tk & 2, 2 * NCTA + s);
            }
            __threadfence();
        }
        bar_sync(0, NWRK);
        if (decltype(role)::value == 1) {
            if (lane < NSEL && own) *reinterpret_cast<volatile unsigned*>(p.s->flag + lane) = ep + 1u;
            int it = 0;
            while (__any_sync(0xffffffffu, KLATE(kk) && ld_acquire32(p.s->flag + (lane & 7)) != ep + 1u)) { if (++it > SPIN_LIMIT) TRAP(); }
            gather(__shfl_sync(0xffffffffu, kk, g));
        }
        bar_sync(0, NWRK);
    };
    if (warp < 18) {
        const unsigned char* ys = reinterpret_cast<const unsigned char*>(p.s->y) + (b < 96 ? (par ^ 1u) * (NCTA * 18432u) : 0u) +
                                  ((P * DM + 32 * warp + 8 * (g >> 1) + (g & 1)) * 64 + odd * 32 + t * 8);
        mbar_wait(bar_v);
        const uint32_t xa = sb + SM_XT + warp * 64 + t * 16;
        const uint4 x0 = lds128(xa + TOK(g) * 1152), x1 = lds128(xa + (TOK(g) + 2) * 1152), dk = lds128(xa + 16 * 1152);
        uint4 wr = make_uint4(0u, 0u, 0u, 0u);
        if (g == 0) wr = lds128(xa + 17 * 1152);
        const uint32_t Z[2][4] = {{x0.x, x0.y, x0.z, x0.w}, {x1.x, x1.y, x1.z, x1.w}}, D4[4] = {dk.x, dk.y, dk.z, dk.w};
#pragma unroll
        for (int hf = 0; hf < 2; hf++) {
            const uint2 st = lds64(s_stat + (g + 8 * hf) * 8);
#pragma unroll
            for (int k = 0; k < 4; k++) U2[hf][k] = hmul2_bf(ln_apply(Z[hf][k], STAT_M(st), STAT_H(st), STAT_L(st)), D4[k]);
        }
        const uint32_t la = pin(sb + SM_LNP + (g * 20 + warp) * 4 + (U2[0][3] & U2[1][3] & (warp >> 8)));
        if (YDLY > 1) delay(YDLY);
        int it = 0;
        float d[2][4];
        uint32_t mn;
        do {
            uint2 yv[4];
#pragma unroll
            for (int k = 0; k < 4; k++) yv[k] = ld_poll64(ys + k * 128);
            if (++it > SPIN_LIMIT) TRAP();
            mn = min(min(min(yv[0].x, yv[0].y), min(yv[1].x, yv[1].y)), min(min(yv[2].x, yv[2].y), min(yv[3].x, yv[3].y)));
#pragma unroll
            for (int k = 0; k < 4; k++) {
                H[0][k] = hadd2_bf(Z[0][k], hadd2_bf(movm(yv[k].x), U2[0][k]));
                H[1][k] = hadd2_bf(Z[1][k], hadd2_bf(movm(yv[k].y), U2[1][k]));
            }
            ln_partial(H, d);
        } while (__any_sync(0xffffffffu, mn == 0));
        STAMP(12);
        if (t == (g >> 1)) {
            stsf(la, (g & 1) ? d[0][3] : d[0][2]); stsf(la + 8 * 80, (g & 1) ? d[1][3] : d[1][2]);
            stsf(la + 16 * 80, (g & 1) ? d[0][1] : d[0][0]); stsf(la + 24 * 80, (g & 1) ? d[1][1] : d[1][0]);
        }
        bar_arrive(6, NWRK);
        STAMP(13);
        bar_sync(7, 608);
        STAMP(14);
#pragma unroll
        for (int hf = 0; hf < 2; hf++) {
            const uint2 st = lds64(s_stat + (g + 8 * hf) * 8);
#pragma unroll
            for (int k = 0; k < 4; k++) U2[hf][k] = ln_apply(H[hf][k], STAT_M(st), STAT_H(st), STAT_L(st));
        }
        {
            float cs[4] = {0.f, 0.f, 0.f, 0.f};
            mma_bf16(cs, U2[0][0], U2[1][0], U2[0][1], U2[1][1], wr.x, wr.y);
            mma_bf16(cs, U2[0][2], U2[1][2], U2[0][3], U2[1][3], wr.z, wr.w);
            if (t == 0) { stsf(la + 32 * 80, cs[0]); stsf(la + 40 * 80, cs[2]); }
            bar_arrive(8, 608);
        }
        bar_sync(9, 608);
        {
            const uint2 best = lds64(s_rank);
            if ((best.x & 26u) == 2 * TOK(g)) publish(best.x & 4u, 255 - 2 * b);
            if ((best.y & 26u) == 2 * TOK(g)) publish(best.y & 4u, 254 - 2 * b);
        }
#pragma unroll
        for (int hf = 0; hf < 2; hf++) {
            sts128(sb + SM_OUT + (TOK(g) + 2 * hf) * (DM * 2) + warp * 64 + t * 16,
                   hadd2_bf(H[hf][0], U2[hf][0]), hadd2_bf(H[hf][1], U2[hf][1]), hadd2_bf(H[hf][2], U2[hf][2]), hadd2_bf(H[hf][3], U2[hf][3]));
            sts128(sb + SM_U + hf * 9216 + tid * 16, H[hf][0], H[hf][1], H[hf][2], H[hf][3]);
        }
        STAMP(15);
        {
            const int mi = lane >> 3, rr = lane & 7;
            mbar_wait(bar_w);
            const uint32_t aad = sb + SM_WG + (mi & 1) * SM_WU + ((warp & 1) * 144 + rr + 8 * (mi >> 1)) * W_PITCH + (warp >> 1) * 16;
#pragma unroll
            for (int k = 0; k < 9; k++) ldsm_x4_t(WA[k][0], WA[k][1], WA[k][2], WA[k][3], aad + k * 16 * W_PITCH);
        }
        {
            const int mi = lane >> 3, rr = lane & 7;
            mbar_wait(bar_d);
            const uint32_t base = sb + SM_WD + (2 * warp + (mi & 1)) * 16 + rr * WD_PITCH;
#pragma unroll
            for (int k = 0; k < 4; k++) ldsm_x4_t(WD[4 * k], WD[4 * k + 1], WD[4 * k + 2], WD[4 * k + 3], base + (k * 16 + 8 * (mi >> 1)) * WD_PITCH);
            ldsm_x2_t(WD[16], WD[17], base + 64 * WD_PITCH);
        }
        const uint32_t bad = pin(sb + SM_XS + (lane & 7) * XS_PITCH + ((warp & 1) * 144 + 8 * (lane >> 3)) * 2);
        const uint32_t ex = pin(sb + SM_EX + (2 * odd + (warp & 1)) * 4608 + (warp >> 1) * 512 + lane * 16);
        const uint32_t po = pin((((8 * (18 * odd + warp) + g) * 64 + P) * 16 + t * 4) * 4);
        fence_async();
        STAMP2(17);
        if (bar_or(11, NWRK, false)) late_rows(IC<0>());
        STAMP2(19);
        {
            float c4[3][4] = {}, e4[4];
#pragma unroll
            for (int k = 0; k < 9; k += 2) {
                uint32_t b0, b1, b2, b3;
                ldsm_x4(b0, b1, b2, b3, bad + k * 32);
                mma_bf16(c4[k % 3], WA[k][0], WA[k][1], WA[k][2], WA[k][3], b0, b1);
                if (k < 8) mma_bf16(c4[(k + 1) % 3], WA[k + 1][0], WA[k + 1][1], WA[k + 1][2], WA[k + 1][3], b2, b3);
            }
#pragma unroll
            for (int j = 0; j < 4; j++) e4[j] = c4[0][j] + c4[1][j] + c4[2][j];
            asm volatile("st.async.shared::cluster.mbarrier::complete_tx::bytes.v4.f32 [%0], {%1,%2,%3,%4}, [%5];\n"
                         ::"r"(ex ^ 0x1000000u), "f"(e4[0]), "f"(e4[1]), "f"(e4[2]), "f"(e4[3]), "r"(bar_g ^ 0x1000000u) : "memory");
            sts128f(ex, e4);
        }
        if (warp < 9) {
            bar_sync(12, 576);
            STAMP2(20);
            const uint32_t er = sb + SM_EX + tid * 16;
            const uint4 a = lds128(er + odd * 9216), c = lds128(er + odd * 9216 + 4608);
            mbar_wait(bar_g);
            const uint4 d = lds128(er + (odd ^ 1) * 9216), e = lds128(er + (odd ^ 1) * 9216 + 4608);
#define S4(f) ((__uint_as_float(a.f) + __uint_as_float(c.f)) + (__uint_as_float(d.f) + __uint_as_float(e.f)))
            const uint32_t G = pack_bf16(S4(x), S4(y)), U = pack_bf16(S4(z), S4(w));
#undef S4
            sts32(sb + SM_GU + tid * 4, hmul2_bf(pack_bf16(bf_lo(G) * sigmoid_f(bf_lo(G)), bf_hi(G) * sigmoid_f(bf_hi(G))), U));
        } else bar_arrive(12, 576);
        bar_sync(13, NWRK);
        STAMP2(21);
        {
            uint32_t gb[9];
            ldsm_x4_t(gb[0], gb[1], gb[2], gb[3], sb + SM_GU + lane * 16);
            ldsm_x4_t(gb[4], gb[5], gb[6], gb[7], sb + SM_GU + 512 + lane * 16);
            ldsm_x1_t(gb[8], sb + SM_GU + 1024 + lane * 16);
            float c4[4] = {}, d4[4] = {}, e4[4] = {};
            mma_bf16(c4, WD[0], WD[1], WD[2], WD[3], gb[0], gb[1]);
            mma_bf16(d4, WD[4], WD[5], WD[6], WD[7], gb[2], gb[3]);
            mma_bf16(e4, WD[8], WD[9], WD[10], WD[11], gb[4], gb[5]);
            mma_bf16(c4, WD[12], WD[13], WD[14], WD[15], gb[6], gb[7]);
            mma_bf16_k8(d4, WD[16], WD[17], gb[8]);
            stg128(reinterpret_cast<unsigned char*>(p.s->part) + po, __float_as_uint(e4[0] + c4[0] + d4[0]) | 1u, __float_as_uint(e4[1] + c4[1] + d4[1]) | 1u,
                   __float_as_uint(e4[2] + c4[2] + d4[2]) | 1u, __float_as_uint(e4[3] + c4[3] + d4[3]) | 1u);
        }
        STAMP2(22);
    } else if (warp == 18) {
        bar_sync(6, NWRK);
        {
            float mb, rc;
            ln_finish(sum18(sb + SM_LNP + lane * 80), lane, mb, rc);
            if (lane < 16) stat_store(s_stat + lane * 8, mb, rc, 0u);
        }
        bar_arrive(7, 608);
        const uint32_t klo = pin((uint32_t)(127 - b) << 9 | (uint32_t)(15 - ROWTOK(lane & 15)) << 1 | par), ra = pin(sb + SM_LNP + (32 + (lane & 15)) * 80);
        uint4* const kdst = reinterpret_cast<uint4*>(p.s->key3) + pin(2 * b + (lane & 1));
        bar_sync(8, 608);
        uint32_t t0;
        {
            const uint32_t bits = __float_as_uint(rbf(sum18(ra)));
            const uint32_t me = ((bits ^ ((uint32_t)((int)bits >> 31) | 0x80000000u)) & 0xffff0000u) | klo;
            const uint32_t k0 = __reduce_max_sync(0xffffffffu, me), k1 = __reduce_max_sync(0xffffffffu, me == k0 ? 0u : me);
            const uint32_t k2 = __reduce_max_sync(0xffffffffu, me >= k1 ? 0u : me);
            if (lane < 2) stg128(kdst, k0 ^ 0x11eu, k1 ^ 0xfeu, k2 ^ 0xdeu, par);
            asm volatile("mov.u32 %0, %%clock;" : "=r"(t0) :: "memory");
            if (lane == 0) sts64(s_rank, ~k0, ~k1);
            bar_arrive(9, 608);
            sts32(s_k16 + (lane & 15) * 4, me);
            __syncwarp();
            const uint4 v = lds128(s_k16 + (lane & 16) * 2), w = lds128(s_k16 + (lane & 16) * 2 + 16);
            int rank = ((v.x > me) + (v.y > me)) + ((v.z > me) + (v.w > me)) + (((w.x > me) + (w.y > me)) + ((w.z > me) + (w.w > me)));
            rank += __shfl_xor_sync(0xffffffffu, rank, 16);
            if (lane < 16 && rank < 8) p.s->key[8 * b + rank] = (me ^ 0x1eu) | ((8 - rank) << 5);
        }
        const uint4* const ksrc = reinterpret_cast<const uint4*>(p.s->key3) + pin(2 * lane);
        const unsigned char* const rl = reinterpret_cast<const unsigned char*>(rsrc) + pin(lane * 16);
        uint4 kq[4];
        uint32_t u[4], mine = 0, m;
        int it = 0;
        { uint32_t now; do { asm volatile("mov.u32 %0, %%clock;" : "=r"(now) :: "memory"); } while (now - t0 < KDLY); }
        do {
#pragma unroll
            for (int i = 0; i < 4; i++) kq[i] = ld_poll(ksrc + 64 * i);
            if (++it > SPIN_LIMIT) TRAP();
            uint32_t S[2][4];
#pragma unroll
            for (int i = 0; i < 2; i++) {
                const uint4 &c = kq[2 * i], &d = kq[2 * i + 1];
                const uint32_t m1 = min(c.x, d.x), m2 = max(c.y, d.y);
                S[i][0] = max(c.x, d.x); S[i][1] = max(m1, m2); S[i][2] = min(m1, m2); S[i][3] = min(c.y, d.y);
            }
            const uint32_t a0 = max(S[0][0], S[1][3]), a1 = max(S[0][1], S[1][2]), a2 = max(S[0][2], S[1][1]), a3 = max(S[0][3], S[1][0]);
            const uint32_t b0 = max(a0, a2), b2 = min(a0, a2), b1 = max(a1, a3), b3 = min(a1, a3);
            u[0] = max(b0, b1); u[1] = min(b0, b1); u[2] = max(b2, b3); u[3] = min(b2, b3);
        } while (__any_sync(0xffffffffu, and3(or3(or3(xor_or(kq[0].x, kq[0].y, par), xor_or(kq[0].z, kq[1].x, par), xor_or(kq[1].y, kq[1].z, par)),
                                                  xor_or(kq[2].x, kq[2].y, par), xor_or(kq[2].z, kq[3].x, par)) | xor_or(kq[3].y, kq[3].z, par), 1u, 1u)));
        STAMPW(16);
        uint4 v[9];
#pragma unroll
        for (int r = 0; r < 8; r++) {
            m = __reduce_max_sync(0xffffffffu, u[0]);
            if (u[0] == m) { u[0] = u[1]; u[1] = u[2]; u[2] = u[3]; u[3] = 0; }
            if (g == r) mine = m;
            v[r] = ld_poll(rl + (size_t)((m >> 8) & 0xffu) * 2304u);
        }
        v[8] = ld_poll(reinterpret_cast<const unsigned char*>(rsrc) + (((mine >> 8) & 0xffu) * 2304u + (32 + t) * 16));
        bool again = __any_sync(0xffffffffu, u[0] == 0 || max(max(kq[0].z, kq[1].z), max(kq[2].z, kq[3].z)) > m);
        if (again) {
#pragma unroll 1
            for (int i = 0; i < 8; i++) {
                uint4 k;
                do { k = ld_poll(reinterpret_cast<const uint4*>(p.s->key) + 32 * i + lane); if (++it > SPIN_LIMIT) TRAP(); } while (((k.x ^ par) | (k.y ^ par) | (k.z ^ par) | (k.w ^ par)) & 1u);
                sts128(sb + SM_KEYS + (32 * i + lane) * 16, k.x, k.y, k.z, k.w);
            }
            m = 0xffffffffu;
#pragma unroll 1
            for (int r = 0; r < 8; r++) {
                uint32_t c = 0;
#pragma unroll 2
                for (int i = 0; i < 8; i++) {
                    const uint4 k = lds128(sb + SM_KEYS + (32 * i + lane) * 16);
                    c = max(max(c, k.x < m ? k.x : 0u), max(k.y < m ? k.y : 0u, max(k.z < m ? k.z : 0u, k.w < m ? k.w : 0u)));
                }
                m = __reduce_max_sync(0xffffffffu, c);
                if (g == r) mine = m;
            }
        }
        if (t == 0) sts32(s_key + g * 4, mine);
        uint32_t mn = 1;
#pragma unroll
        for (int r = 0; r < 9; r++) {
            sts128(sb + SM_XS + (r < 8 ? r * XS_PITCH + lane * 16 : g * XS_PITCH + (32 + t) * 16), v[r].x, v[r].y, v[r].z, v[r].w);
            mn = min(mn, min4(v[r]));
        }
        if ((again || __any_sync(0xffffffffu, mn == 0)) && !__any_sync(0xffffffffu, KLATE(mine))) gather(mine);
        STAMPW(18);
        if (bar_or(11, NWRK, KLATE(mine))) late_rows(IC<1>());
    } else {
        bar_sync(6, NWRK);
        WPOINT(16, true);
        if (wsched(18) > wsched(17)) delay(WDLY);
        WPOINT(17, true);
        if (wsched(19) > wsched(18)) delay(WDLY);
        WPOINT(18, true);
        if (bar_or(11, NWRK, false)) late_rows(IC<2>());
        const int tk = KTOK(lds32(s_key + (lane & 7) * 4));
        const uint32_t sel = __reduce_or_sync(0xffffffffu, (tk >> 4) == b ? 1u << (tk & 15) : 0u);
        if (ODLY) delay(ODLY);
        if (!(EXP & 1)) if (sel ? lane < 16 && !((sel >> lane) & 1u) : lane == 0) bulk_s2g(p.out + (size_t)(16 * b + lane) * DM, sb + SM_OUT + lane * (DM * 2), sel ? DM * 2 : 16 * DM * 2);
        __syncwarp();
    }
    if (warp >= 17) {
        const int grp = 3 * b + warp - 17, fsl = 2 * t + ((lane >> 3) & 1), fc = 16 * (grp >> 3) + (grp & 7) + 8 * (lane >> 4);
        const uint32_t fk = lds32(s_key + fsl * 4);
        float hv = 0.f, u2 = 0.f;
        int it = 0;
        if (b < 96) {
            const uint32_t* const fsrc = p.s->rows + KSLOT(fk, fsl) * DM + (fc >> 1);
            uint32_t hw, uw;
            do { hw = ld_poll32(fsrc + 288); uw = ld_poll32(fsrc); if (++it > SPIN_LIMIT) TRAP(); } while (!hw || !uw);
            hv = (fc & 1) ? bf_hi(hw) : bf_lo(hw); u2 = (fc & 1) ? bf_hi(uw) : bf_lo(uw);
        }
        const float rs = rbf(sigmoid_f(__uint_as_float((fk ^ ((uint32_t)((int)~fk >> 31) | 0x80000000u)) & 0xffff0000u)));
        const uint32_t dof = pin(KTOK(fk) * DM + fc), so = pin(grp * 256 + lane);
        if (warp > 17) bar_sync(13, NWRK);
        if (b < 96) {
            delay(warp > 17 ? FDLY : FDLY2);
            const uint4* src = reinterpret_cast<const uint4*>(p.s->part) + so;
            float s0, s1, s2, s3;
            uint32_t ok;
            do {
                uint4 a[8];
#pragma unroll
                for (int i = 0; i < 8; i++) a[i] = ld_poll(src + 32 * i);
                if (++it > SPIN_LIMIT) TRAP();
#define A4(i) and3(and3(a[i].x, a[i].y, a[i].z), and3(a[i].w, a[i + 1].x, a[i + 1].y), a[i + 1].z & a[i + 1].w)
#define S8(f) (((__uint_as_float(a[0].f) + __uint_as_float(a[1].f)) + (__uint_as_float(a[2].f) + __uint_as_float(a[3].f))) + \
               ((__uint_as_float(a[4].f) + __uint_as_float(a[5].f)) + (__uint_as_float(a[6].f) + __uint_as_float(a[7].f))))
                ok = and3(A4(0), A4(2), and3(A4(4), A4(6), 1u));
                s0 = S8(x); s1 = S8(y); s2 = S8(z); s3 = S8(w);
                asm volatile("" : "+f"(s0), "+f"(s1), "+f"(s2), "+f"(s3));
#undef A4
#undef S8
            } while (__any_sync(0xffffffffu, !ok));
            STAMP2(24);
            const bool up = lane & 16, od = lane & 8;
            const float r0 = (up ? s2 : s0) + __shfl_xor_sync(0xffffffffu, up ? s0 : s2, 16), r1 = (up ? s3 : s1) + __shfl_xor_sync(0xffffffffu, up ? s1 : s3, 16);
            float y = (od ? r1 : r0) + __shfl_xor_sync(0xffffffffu, od ? r0 : r1, 8);
            y += __shfl_xor_sync(0xffffffffu, y, 4);
            p.out[dof] = __float2bfloat16_rn(hv + rbf(u2 + rbf(rbf(y) * rs)));
        }
    }
    if (warp == 19) asm volatile("cp.async.bulk.wait_group.read 0;\n" ::: "memory");
    if (b == 0 && tid < 8) *reinterpret_cast<volatile unsigned*>(p.s->hint + tid * 32 + 1) = lds32(s_cnt + 4) + 1u;
    STAMP(25);
    }
}

typedef CUresult (*PFN_tmEncode)(CUtensorMap*, CUtensorMapDataType, cuuint32_t, void*, const cuuint64_t*, const cuuint64_t*, const cuuint32_t*,
                                 const cuuint32_t*, CUtensorMapInterleave, CUtensorMapSwizzle, CUtensorMapL2promotion, CUtensorMapFloatOOBfill);

extern "C" void kernel_launch(void* const* d_in, const int* in_sizes, int n_in, void* d_out, int out_size) {
    Params p;
    p.x = (const bf16*)d_in[0];
    p.lar = (const bf16*)d_in[1];
    p.aim = (const bf16*)d_in[2];
    p.cre = (const bf16*)d_in[3];
    p.cim = (const bf16*)d_in[4];
    p.ldt = (const bf16*)d_in[5];
    p.dsk = (const bf16*)d_in[6];
    p.wr = (const bf16*)d_in[8];
    p.wg = (const bf16*)d_in[9];
    p.wu = (const bf16*)d_in[10];
    p.wd = (const bf16*)d_in[11];
    p.out = (bf16*)d_out;
    static PFN_tmEncode enc = nullptr;
    static void* scratch = nullptr;
    if (!enc) {
        cudaFuncSetAttribute(fused_kernel, cudaFuncAttributeMaxDynamicSharedMemorySize, SMEM_TOTAL);
        void* fn = nullptr;
        cudaDriverEntryPointQueryResult qr;
        cudaGetDriverEntryPoint("cuTensorMapEncodeTiled", &fn, cudaEnableDefault, &qr);
        enc = (PFN_tmEncode)fn;
        cudaGetSymbolAddress(&scratch, g_scratch);
    }
    p.s = (Scratch*)scratch;
    CUtensorMap tm_g, tm_u, tm_d, tm_x;
    const cuuint64_t dims[2] = {FF, DM}, strides[1] = {FF * 2};
    const cuuint32_t box[2] = {72, 48}, es[2] = {1, 1};
    enc(&tm_g, CU_TENSOR_MAP_DATA_TYPE_BFLOAT16, 2, d_in[9], dims, strides, box, es, CU_TENSOR_MAP_INTERLEAVE_NONE, CU_TENSOR_MAP_SWIZZLE_NONE,
        CU_TENSOR_MAP_L2_PROMOTION_NONE, CU_TENSOR_MAP_FLOAT_OOB_FILL_NONE);
    enc(&tm_u, CU_TENSOR_MAP_DATA_TYPE_BFLOAT16, 2, d_in[10], dims, strides, box, es, CU_TENSOR_MAP_INTERLEAVE_NONE, CU_TENSOR_MAP_SWIZZLE_NONE,
        CU_TENSOR_MAP_L2_PROMOTION_NONE, CU_TENSOR_MAP_FLOAT_OOB_FILL_NONE);
    const cuuint64_t ddims[2] = {DM / 2, FF}, dstrides[1] = {DM * 2};
    const cuuint32_t dbox[2] = {WD_PITCH / 4, 8};
    enc(&tm_d, CU_TENSOR_MAP_DATA_TYPE_UINT32, 2, d_in[11], ddims, dstrides, dbox, es, CU_TENSOR_MAP_INTERLEAVE_NONE, CU_TENSOR_MAP_SWIZZLE_NONE,
        CU_TENSOR_MAP_L2_PROMOTION_NONE, CU_TENSOR_MAP_FLOAT_OOB_FILL_NONE);
    const cuuint64_t xdims[4] = {DM, 128, 4, 4}, xstrides[3] = {DM * 8, DM * 2, DM * 1024};
    const cuuint32_t xbox[4] = {8, 128, 4, 2}, xes[4] = {1, 1, 1, 1};
    enc(&tm_x, CU_TENSOR_MAP_DATA_TYPE_BFLOAT16, 4, d_in[0], xdims, xstrides, xbox, xes, CU_TENSOR_MAP_INTERLEAVE_NONE, CU_TENSOR_MAP_SWIZZLE_NONE,
        CU_TENSOR_MAP_L2_PROMOTION_NONE, CU_TENSOR_MAP_FLOAT_OOB_FILL_NONE);
    fused_kernel<<<NCTA, NTHR, SMEM_TOTAL>>>(p, tm_g, tm_u, tm_d, tm_x);
}
```

```cpp
#include <cuda_runtime.h>
#include <cuda.h>
#include <cuda_fp16.h>
#include <cuda_bf16.h>
#include <stdint.h>

#define LSEQ 2048
#define DM 576
#define NST 128
#define FF 4608
#define NSEL 8
#define NCTA 128
#define NTHR 640
#define NWRK 640

typedef __nv_bfloat16 bf16;

#define SM_WG 0
#define SM_WU 41472
#define SM_XC (82944 - 32768)
#define SM_WD 82944
#define W_PITCH 144
#define WD_PITCH 592
#define SM_Z2 (SM_WD + 10240)
#define SM_XT (SM_PL - 18 * 1152)
#define SM_PL (SM_WD + 46080)
#define PL_HALF 1344
#define PLW_B 2624
#define PL_B (4 * PLW_B)
#define SM_U (SM_PL + 5 * PL_B)
#define UPAD 20
#define ULO_B ((UPAD + 128) * 16)
#define USLOT_B (2 * ULO_B)
#define SM_KW (SM_U + 5 * USLOT_B)
#define KW_B 3712
#define KW_PL 1216
#define KW_P 2400
#define KW_H 3440
#define SM_MISC (SM_KW + 5 * KW_B)
#define SM_LC (SM_MISC + 384)
#define SM_LNP (SM_LC + 768)
#define SM_RX (SM_LNP + 3840)
#define SMEM_TOTAL (SM_RX + 3088)
#define TBW PLW_B
#define SM_OUT SM_PL
#define SM_XS (SM_PL + 18432)
#define XS_PITCH 592
#define SM_GU (SM_PL + 23296)
#define SM_EX (SM_PL + 24576)
#define SM_KEYS SM_KW

struct __align__(128) Scratch {
    unsigned hint[8 * 32];
    unsigned flag[32];
    uint32_t key3[NCTA * 8];
    uint32_t key[NCTA * 8];
    uint32_t stat[LSEQ];
    uint32_t uT[64 * (LSEQ / 2)];
    uint32_t y[(NCTA + 96) * DM * 8];
    uint32_t part[288 * 64 * 16];
    uint32_t rows[(2 * NCTA + NSEL) * DM];
};
__device__ Scratch g_scratch;
#define STAMP(i)
#define STAMPX(i)
#define STAMPY(i)

__device__ __forceinline__ float rbf(float x) {
    uint32_t r;
    asm("cvt.rn.bf16x2.f32 %0, %1, %2;\n" : "=r"(r) : "f"(x), "f"(0.f));
    return __uint_as_float(r);
}
__device__ __forceinline__ uint32_t pack_bf16(float lo, float hi) {
    uint32_t r;
    asm("cvt.rn.bf16x2.f32 %0, %1, %2;\n" : "=r"(r) : "f"(hi), "f"(lo));
    return r;
}
__device__ __forceinline__ uint32_t pack_f16(float lo, float hi) {
    uint32_t r;
    asm("cvt.rn.f16x2.f32 %0, %1, %2;\n" : "=r"(r) : "f"(hi), "f"(lo));
    return r;
}
__device__ __forceinline__ uint32_t pack_f16_rz(float lo, float hi) {
    uint32_t r;
    asm("cvt.rz.f16x2.f32 %0, %1, %2;\n" : "=r"(r) : "f"(hi), "f"(lo));
    return r;
}
__device__ __forceinline__ float bf_lo(uint32_t w) { return __uint_as_float(w << 16); }
__device__ __forceinline__ float bf_hi(uint32_t w) { return __uint_as_float(w & 0xffff0000u); }
__device__ __forceinline__ uint32_t hadd2_bf(uint32_t a, uint32_t b) {
    __nv_bfloat162 r = __hadd2_rn(*reinterpret_cast<__nv_bfloat162*>(&a), *reinterpret_cast<__nv_bfloat162*>(&b));
    return *reinterpret_cast<uint32_t*>(&r);
}
__device__ __forceinline__ uint32_t hsub2_bf(uint32_t a, uint32_t b) {
    __nv_bfloat162 r = __hsub2_rn(*reinterpret_cast<__nv_bfloat162*>(&a), *reinterpret_cast<__nv_bfloat162*>(&b));
    return *reinterpret_cast<uint32_t*>(&r);
}
__device__ __forceinline__ uint32_t hmul2_bf(uint32_t a, uint32_t b) {
    __nv_bfloat162 r = __hmul2_rn(*reinterpret_cast<__nv_bfloat162*>(&a), *reinterpret_cast<__nv_bfloat162*>(&b));
    return *reinterpret_cast<uint32_t*>(&r);
}
__device__ __forceinline__ uint32_t hfma2_bf(uint32_t a, uint32_t b, uint32_t c) { uint32_t r; asm("fma.rn.bf16x2 %0, %1, %2, %3;\n" : "=r"(r) : "r"(a), "r"(b), "r"(c)); return r; }
__device__ __forceinline__ uint32_t hmul2(uint32_t a, uint32_t b) { uint32_t r; asm("mul.rn.f16x2 %0, %1, %2;\n" : "=r"(r) : "r"(a), "r"(b)); return r; }
__device__ __forceinline__ uint32_t hadd2(uint32_t a, uint32_t b) { uint32_t r; asm("add.rn.f16x2 %0, %1, %2;\n" : "=r"(r) : "r"(a), "r"(b)); return r; }
__device__ __forceinline__ uint32_t hfma2(uint32_t a, uint32_t b, uint32_t c) { uint32_t r; asm("fma.rn.f16x2 %0, %1, %2, %3;\n" : "=r"(r) : "r"(a), "r"(b), "r"(c)); return r; }
__device__ __forceinline__ uint32_t hfms2(uint32_t a, uint32_t b, uint32_t c) {
    uint32_t r;
    asm("{\n.reg .b32 n;\nneg.f16x2 n, %2;\nfma.rn.f16x2 %0, %1, n, %3;\n}\n" : "=r"(r) : "r"(a), "r"(b), "r"(c));
    return r;
}
__device__ __forceinline__ uint32_t nzw(uint32_t w) { return max(w, 1u); }
__device__ __forceinline__ uint32_t nzf(float f) { const uint32_t w = __float_as_uint(f); return w ? w : 0x80000000u; }
__device__ __forceinline__ uint32_t smem_u32(const void* p) { return (uint32_t)__cvta_generic_to_shared(p); }
__device__ __forceinline__ uint32_t lds32(uint32_t addr) {
    uint32_t v;
    asm volatile("ld.shared.u32 %0, [%1];\n" : "=r"(v) : "r"(addr) : "memory");
    return v;
}
__device__ __forceinline__ uint32_t lds16(uint32_t addr) {
    unsigned short v;
    asm volatile("ld.shared.u16 %0, [%1];\n" : "=h"(v) : "r"(addr) : "memory");
    return v;
}
__device__ __forceinline__ uint2 lds64(uint32_t addr) {
    uint2 v;
    asm volatile("ld.shared.v2.u32 {%0,%1}, [%2];\n" : "=r"(v.x), "=r"(v.y) : "r"(addr) : "memory");
    return v;
}
__device__ __forceinline__ uint4 lds128(uint32_t addr) {
    uint4 v;
    asm volatile("ld.shared.v4.u32 {%0,%1,%2,%3}, [%4];\n" : "=r"(v.x), "=r"(v.y), "=r"(v.z), "=r"(v.w) : "r"(addr) : "memory");
    return v;
}
__device__ __forceinline__ float ldsf(uint32_t addr) { return __uint_as_float(lds32(addr)); }
__device__ __forceinline__ void sts32(uint32_t addr, uint32_t v) { asm volatile("st.shared.u32 [%0], %1;\n" ::"r"(addr), "r"(v) : "memory"); }
__device__ __forceinline__ void sts16(uint32_t addr, uint32_t v) { asm volatile("st.shared.u16 [%0], %1;\n" ::"r"(addr), "h"((unsigned short)v) : "memory"); }
__device__ __forceinline__ void stsf(uint32_t addr, float v) { sts32(addr, __float_as_uint(v)); }
__device__ __forceinline__ void sts64(uint32_t addr, uint32_t a, uint32_t b) { asm volatile("st.shared.v2.u32 [%0], {%1,%2};\n" ::"r"(addr), "r"(a), "r"(b) : "memory"); }
__device__ __forceinline__ void sts64f(uint32_t addr, float a, float b) { sts64(addr, __float_as_uint(a), __float_as_uint(b)); }
__device__ __forceinline__ void sts128(uint32_t addr, uint32_t a, uint32_t b, uint32_t c, uint32_t d) {
    asm volatile("st.shared.v4.u32 [%0], {%1,%2,%3,%4};\n" ::"r"(addr), "r"(a), "r"(b), "r"(c), "r"(d) : "memory");
}
__device__ __forceinline__ void sts128f(uint32_t addr, const float (&v)[4]) {
    sts128(addr, __float_as_uint(v[0]), __float_as_uint(v[1]), __float_as_uint(v[2]), __float_as_uint(v[3]));
}
__device__ __forceinline__ void ldsm_x4(uint32_t& r0, uint32_t& r1, uint32_t& r2, uint32_t& r3, uint32_t addr) {
    asm volatile("ldmatrix.sync.aligned.m8n8.x4.shared.b16 {%0,%1,%2,%3}, [%4];\n"
                 : "=r"(r0), "=r"(r1), "=r"(r2), "=r"(r3) : "r"(addr) : "memory");
}
__device__ __forceinline__ void ldsm_x4_t(uint32_t& r0, uint32_t& r1, uint32_t& r2, uint32_t& r3, uint32_t addr) {
    asm volatile("ldmatrix.sync.aligned.m8n8.x4.trans.shared.b16 {%0,%1,%2,%3}, [%4];\n"
                 : "=r"(r0), "=r"(r1), "=r"(r2), "=r"(r3) : "r"(addr) : "memory");
}
__device__ __forceinline__ void ldsm_x2_t(uint32_t& r0, uint32_t& r1, uint32_t addr) {
    asm volatile("ldmatrix.sync.aligned.m8n8.x2.trans.shared.b16 {%0,%1}, [%2];\n" : "=r"(r0), "=r"(r1) : "r"(addr) : "memory");
}
__device__ __forceinline__ void ldsm_x1_t(uint32_t& r0, uint32_t addr) {
    asm volatile("ldmatrix.sync.aligned.m8n8.x1.trans.shared.b16 {%0}, [%1];\n" : "=r"(r0) : "r"(addr) : "memory");
}
__device__ __forceinline__ void stsm_x4(uint32_t addr, uint32_t r0, uint32_t r1, uint32_t r2, uint32_t r3) {
    asm volatile("stmatrix.sync.aligned.m8n8.x4.shared.b16 [%0], {%1,%2,%3,%4};\n" ::"r"(addr), "r"(r0), "r"(r1), "r"(r2), "r"(r3) : "memory");
}
__device__ __forceinline__ void stsm_x4_t(uint32_t addr, uint32_t r0, uint32_t r1, uint32_t r2, uint32_t r3) {
    asm volatile("stmatrix.sync.aligned.m8n8.x4.trans.shared.b16 [%0], {%1,%2,%3,%4};\n" ::"r"(addr), "r"(r0), "r"(r1), "r"(r2), "r"(r3) : "memory");
}
__device__ __forceinline__ uint32_t movm(uint32_t a) {
    uint32_t d;
    asm volatile("movmatrix.sync.aligned.m8n8.trans.b16 %0, %1;\n" : "=r"(d) : "r"(a));
    return d;
}
__device__ __forceinline__ void mma_f16(float (&c)[4], uint32_t a0, uint32_t a1, uint32_t a2, uint32_t a3, uint32_t b0, uint32_t b1) {
    asm volatile(
        "mma.sync.aligned.m16n8k16.row.col.f32.f16.f16.f32 {%0,%1,%2,%3}, {%4,%5,%6,%7}, {%8,%9}, {%0,%1,%2,%3};\n"
        : "+f"(c[0]), "+f"(c[1]), "+f"(c[2]), "+f"(c[3])
        : "r"(a0), "r"(a1), "r"(a2), "r"(a3), "r"(b0), "r"(b1));
}
__device__ __forceinline__ void mma_bf16(float (&c)[4], uint32_t a0, uint32_t a1, uint32_t a2, uint32_t a3, uint32_t b0, uint32_t b1) {
    asm volatile(
        "mma.sync.aligned.m16n8k16.row.col.f32.bf16.bf16.f32 {%0,%1,%2,%3}, {%4,%5,%6,%7}, {%8,%9}, {%0,%1,%2,%3};\n"
        : "+f"(c[0]), "+f"(c[1]), "+f"(c[2]), "+f"(c[3])
        : "r"(a0), "r"(a1), "r"(a2), "r"(a3), "r"(b0), "r"(b1));
}
__device__ __forceinline__ void mma_bf16_k8(float (&c)[4], uint32_t a0, uint32_t a1, uint32_t b0) {
    asm volatile("mma.sync.aligned.m16n8k8.row.col.f32.bf16.bf16.f32 {%0,%1,%2,%3}, {%4,%5}, {%6}, {%0,%1,%2,%3};\n"
                 : "+f"(c[0]), "+f"(c[1]), "+f"(c[2]), "+f"(c[3]) : "r"(a0), "r"(a1), "r"(b0));
}
__device__ __forceinline__ void bar_sync(int id, int n) { asm volatile("bar.sync %0, %1;\n" ::"r"(id), "r"(n) : "memory"); }
__device__ __forceinline__ void bar_arrive(int id, int n) { asm volatile("bar.arrive %0, %1;\n" ::"r"(id), "r"(n) : "memory"); }
__device__ __forceinline__ bool bar_or(int id, int n, bool v) {
    uint32_t r;
    asm volatile("{\n.reg .pred p, q;\nsetp.ne.u32 p, %3, 0;\nbar.red.or.pred q, %1, %2, p;\nselp.u32 %0, 1, 0, q;\n}\n" : "=r"(r) : "r"(id), "r"(n), "r"((uint32_t)v) : "memory");
    return r;
}
__device__ __forceinline__ uint32_t and3(uint32_t a, uint32_t b, uint32_t c) { uint32_t r; asm("lop3.b32 %0, %1, %2, %3, 0x80;\n" : "=r"(r) : "r"(a), "r"(b), "r"(c)); return r; }
__device__ __forceinline__ uint32_t or3(uint32_t a, uint32_t b, uint32_t c) { uint32_t r; asm("lop3.b32 %0, %1, %2, %3, 0xfe;\n" : "=r"(r) : "r"(a), "r"(b), "r"(c)); return r; }
__device__ __forceinline__ uint32_t xor_or(uint32_t a, uint32_t b, uint32_t c) { uint32_t r; asm("lop3.b32 %0, %1, %2, %3, 0x7e;\n" : "=r"(r) : "r"(a), "r"(b), "r"(c)); return r; }
__device__ __forceinline__ uint32_t pin(uint32_t v) { uint32_t r; asm volatile("shfl.sync.bfly.b32 %0, %1, 0, 0x1f, 0xffffffff;\n" : "=r"(r) : "r"(v) : "memory"); return r; }
__device__ __forceinline__ uint4 ld_poll(const void* p) {
    uint4 v;
    asm volatile("ld.relaxed.gpu.global.v4.u32 {%0,%1,%2,%3}, [%4];\n" : "=r"(v.x), "=r"(v.y), "=r"(v.z), "=r"(v.w) : "l"(p) : "memory");
    return v;
}
__device__ __forceinline__ uint2 ld_poll64(const void* p) {
    uint2 v;
    asm volatile("ld.relaxed.gpu.global.v2.u32 {%0,%1}, [%2];\n" : "=r"(v.x), "=r"(v.y) : "l"(p) : "memory");
    return v;
}
__device__ __forceinline__ uint32_t ld_poll32(const void* p) {
    uint32_t v;
    asm volatile("ld.relaxed.gpu.global.u32 %0, [%1];\n" : "=r"(v) : "l"(p) : "memory");
    return v;
}
__device__ __forceinline__ uint32_t ld_acquire32(const void* p) {
    uint32_t v;
    asm volatile("ld.acquire.gpu.global.u32 %0, [%1];\n" : "=r"(v) : "l"(p) : "memory");
    return v;
}
__device__ __forceinline__ uint4 ldg128(const void* p) {
    uint4 v;
    asm volatile("ld.global.nc.v4.u32 {%0,%1,%2,%3}, [%4];\n" : "=r"(v.x), "=r"(v.y), "=r"(v.z), "=r"(v.w) : "l"(p));
    return v;
}
__device__ __forceinline__ uint2 ldg64(const void* p) {
    uint2 v;
    asm volatile("ld.global.nc.v2.u32 {%0,%1}, [%2];\n" : "=r"(v.x), "=r"(v.y) : "l"(p));
    return v;
}
__device__ __forceinline__ uint32_t ldg16(const void* p) {
    uint32_t v;
    asm volatile("ld.global.nc.u16 %0, [%1];\n" : "=r"(v) : "l"(p));
    return v;
}
__device__ __forceinline__ uint4 ldo128(const void* p) {
    uint4 v;
    asm volatile("ld.relaxed.cta.global.v4.u32 {%0,%1,%2,%3}, [%4];\n" : "=r"(v.x), "=r"(v.y), "=r"(v.z), "=r"(v.w) : "l"(p) : "memory");
    return v;
}
__device__ __forceinline__ uint2 ldo64(const void* p) {
    uint2 v;
    asm volatile("ld.relaxed.cta.global.v2.u32 {%0,%1}, [%2];\n" : "=r"(v.x), "=r"(v.y) : "l"(p) : "memory");
    return v;
}
__device__ __forceinline__ uint32_t ldo16(const void* p) {
    uint32_t v;
    asm volatile("ld.relaxed.cta.global.u16 %0, [%1];\n" : "=r"(v) : "l"(p) : "memory");
    return v;
}
__device__ __forceinline__ void stg128(void* p, uint32_t a, uint32_t b, uint32_t c, uint32_t d) {
    asm volatile("st.global.v4.u32 [%0], {%1,%2,%3,%4};\n" ::"l"(p), "r"(a), "r"(b), "r"(c), "r"(d) : "memory");
}
__device__ __forceinline__ void stg64(void* p, uint32_t a, uint32_t b) { asm volatile("st.global.v2.u32 [%0], {%1,%2};\n" ::"l"(p), "r"(a), "r"(b) : "memory"); }
__device__ __forceinline__ uint32_t min4(const uint4& v) { return min(min(v.x, v.y), min(v.z, v.w)); }
#define SPIN_LIMIT (1 << 21)
#define TRAP() __trap()
__device__ __forceinline__ void mbar_init(uint32_t bar, uint32_t cnt) { asm volatile("mbarrier.init.shared::cta.b64 [%0], %1;\n" ::"r"(bar), "r"(cnt) : "memory"); }
__device__ __forceinline__ void mbar_expect(uint32_t bar, uint32_t bytes) {
    asm volatile("mbarrier.arrive.expect_tx.shared::cta.b64 _, [%0], %1;\n" ::"r"(bar), "r"(bytes) : "memory");
}
__device__ __forceinline__ void mbar_arrive(uint32_t bar) { asm volatile("mbarrier.arrive.shared::cta.b64 _, [%0];\n" ::"r"(bar) : "memory"); }
__device__ __forceinline__ void mbar_wait_cluster(uint32_t bar) {
    asm volatile(
        "{\n.reg .pred p;\n"
        "W_%=:\n"
        "mbarrier.try_wait.parity.acquire.cluster.shared::cta.b64 p, [%0], 0;\n"
        "@!p bra W_%=;\n}\n" ::"r"(bar) : "memory");
}
__device__ __forceinline__ void mbar_wait(uint32_t bar) {
    asm volatile(
        "{\n.reg .pred p;\n"
        "W_%=:\n"
        "mbarrier.try_wait.parity.shared::cta.b64 p, [%0], 0;\n"
        "@!p bra W_%=;\n}\n" ::"r"(bar) : "memory");
}
__device__ __forceinline__ void mbar_wait1(uint32_t bar) {
    asm volatile(
        "{\n.reg .pred p;\n"
        "W_%=:\n"
        "mbarrier.try_wait.parity.shared::cta.b64 p, [%0], 1;\n"
        "@!p bra W_%=;\n}\n" ::"r"(bar) : "memory");
}
__device__ __forceinline__ bool mbar_test(uint32_t bar) {
    uint32_t r;
    asm volatile("{\n.reg .pred p;\nmbarrier.test_wait.parity.shared::cta.b64 p, [%1], 0;\nselp.u32 %0, 1, 0, p;\n}\n" : "=r"(r) : "r"(bar) : "memory");
    return __any_sync(0xffffffffu, r);
}
__device__ __forceinline__ void bulk_g2s(uint32_t dst, const void* src, uint32_t bytes, uint32_t bar) {
    asm volatile("cp.async.bulk.shared::cluster.global.mbarrier::complete_tx::bytes [%0], [%1], %2, [%3];\n" ::"r"(dst), "l"(src), "r"(bytes), "r"(bar) : "memory");
}
__device__ __forceinline__ void bulk_s2g(void* dst, uint32_t src, uint32_t bytes) {
    asm volatile("cp.async.bulk.global.shared::cta.bulk_group [%0], [%1], %2;\ncp.async.bulk.commit_group;\n" ::"l"(dst), "r"(src), "r"(bytes) : "memory");
}
__device__ __forceinline__ void bulk_s2g_nc(void* dst, uint32_t src, uint32_t bytes) {
    asm volatile("cp.async.bulk.global.shared::cta.bulk_group [%0], [%1], %2;\n" ::"l"(dst), "r"(src), "r"(bytes) : "memory");
}
__device__ __forceinline__ void tma_2d(uint32_t dst, const CUtensorMap* tm, int c0, int c1, uint32_t bar) {
    asm volatile("cp.async.bulk.tensor.2d.shared::cluster.global.mbarrier::complete_tx::bytes [%0], [%1, {%3, %4}], [%2];\n"
                 ::"r"(dst), "l"(tm), "r"(bar), "r"(c0), "r"(c1) : "memory");
}
__device__ __forceinline__ void tma_4d(uint32_t dst, const CUtensorMap* tm, int c0, int c3, uint32_t bar) {
    asm volatile("cp.async.bulk.tensor.4d.shared::cluster.global.mbarrier::complete_tx::bytes [%0], [%1, {%3, %4, %4, %5}], [%2];\n"
                 ::"r"(dst), "l"(tm), "r"(bar), "r"(c0), "r"(0), "r"(c3) : "memory");
}
__device__ __forceinline__ void tma_4d_mc(uint32_t dst, const CUtensorMap* tm, int c0, int c3, uint32_t bar) {
    asm volatile("cp.async.bulk.tensor.4d.shared::cluster.global.mbarrier::complete_tx::bytes.multicast::cluster [%0], [%1, {%3, %4, %4, %5}], [%2], %6;\n"
                 ::"r"(dst), "l"(tm), "r"(bar), "r"(c0), "r"(0), "r"(c3), "h"((unsigned short)3) : "memory");
}
__device__ __forceinline__ void l2_prefetch(const void* src, uint32_t bytes) {
    asm volatile("cp.async.bulk.prefetch.L2.global [%0], %1;\n" ::"l"(src), "r"(bytes) : "memory");
}
__device__ __forceinline__ bool elect_one() {
    uint32_t r;
    asm volatile("{\n.reg .pred p;\nelect.sync _|p, 0xffffffff;\nselp.u32 %0, 1, 0, p;\n}\n" : "=r"(r));
    return r;
}
__device__ __forceinline__ void delay(uint32_t clks) {
    uint32_t t0, t1;
    asm volatile("mov.u32 %0, %%clock;" : "=r"(t0) :: "memory");
    do { asm volatile("mov.u32 %0, %%clock;" : "=r"(t1) :: "memory"); } while (t1 - t0 < clks);
}
__device__ __forceinline__ void fence_async() { asm volatile("fence.proxy.async.shared::cta;\n" ::: "memory"); }

__device__ __forceinline__ float2 cmul(float2 a, float2 b) {
    return make_float2(fmaf(a.x, b.x, -a.y * b.y), fmaf(a.x, b.y, a.y * b.x));
}
__device__ __forceinline__ float2 csq(float2 a) {
    float p = a.x * a.y;
    return make_float2(fmaf(a.x, a.x, -a.y * a.y), p + p);
}
__device__ __forceinline__ float ex2_approx(float x) { float r; asm("ex2.approx.ftz.f32 %0, %1;\n" : "=f"(r) : "f"(x)); return r; }
__device__ __forceinline__ float exp_bf(float x) { return rbf(ex2_approx(__fmul_ru(x, 1.4426950408889634f))); }
__device__ __forceinline__ float2 cexp_e(float lr2, float li, float e) {
    const float m = ex2_approx(lr2 * e);
    return make_float2(m * __cosf(li * e), m * __sinf(li * e));
}
__device__ __forceinline__ float rcp_approx(float x) { float r; asm("rcp.approx.ftz.f32 %0, %1;\n" : "=f"(r) : "f"(x)); return r; }
__device__ __forceinline__ float sigmoid_f(float x) { return rcp_approx(1.0f + ex2_approx(x * -1.4426950408889634f)); }
__device__ __forceinline__ float sqrt_approx(float x) { float r; asm("sqrt.approx.ftz.f32 %0, %1;\n" : "=f"(r) : "f"(x)); return r; }

__device__ __forceinline__ void wg_fence() { asm volatile("wgmma.fence.sync.aligned;\n" ::: "memory"); }
__device__ __forceinline__ void wg_commit() { asm volatile("wgmma.commit_group.sync.aligned;\n" ::: "memory"); }
__device__ __forceinline__ void wg_wait0() { asm volatile("wgmma.wait_group.sync.aligned 0;\n" ::: "memory"); }
template <int T> __device__ __forceinline__ void wg_mma(float (&acc)[16][4], const uint32_t* a, uint64_t desc);
template <int T> __device__ __forceinline__ void wg_first(float (&acc)[16][4], const uint32_t* a, uint64_t desc);
template <> __device__ __forceinline__ void wg_mma<0>(float (&acc)[16][4], const uint32_t* a, uint64_t desc) {
    asm volatile("wgmma.mma_async.sync.aligned.m64n128k16.f32.f16.f16 {%0,%1,%2,%3,%4,%5,%6,%7,%8,%9,%10,%11,%12,%13,%14,%15,%16,%17,%18,%19,%20,%21,%22,%23,%24,%25,%26,%27,%28,%29,%30,%31,%32,%33,%34,%35,%36,%37,%38,%39,%40,%41,%42,%43,%44,%45,%46,%47,%48,%49,%50,%51,%52,%53,%54,%55,%56,%57,%58,%59,%60,%61,%62,%63}, {%64,%65,%66,%67}, %68, 1, 1, 1, 0;\n"
                 : "+f"(acc[0][0]), "+f"(acc[0][1]), "+f"(acc[0][2]), "+f"(acc[0][3]), "+f"(acc[1][0]), "+f"(acc[1][1]), "+f"(acc[1][2]), "+f"(acc[1][3]), "+f"(acc[2][0]), "+f"(acc[2][1]), "+f"(acc[2][2]), "+f"(acc[2][3]), "+f"(acc[3][0]), "+f"(acc[3][1]), "+f"(acc[3][2]), "+f"(acc[3][3]), "+f"(acc[4][0]), "+f"(acc[4][1]), "+f"(acc[4][2]), "+f"(acc[4][3]), "+f"(acc[5][0]), "+f"(acc[5][1]), "+f"(acc[5][2]), "+f"(acc[5][3]), "+f"(acc[6][0]), "+f"(acc[6][1]), "+f"(acc[6][2]), "+f"(acc[6][3]), "+f"(acc[7][0]), "+f"(acc[7][1]), "+f"(acc[7][2]), "+f"(acc[7][3]), "+f"(acc[8][0]), "+f"(acc[8][1]), "+f"(acc[8][2]), "+f"(acc[8][3]), "+f"(acc[9][0]), "+f"(acc[9][1]), "+f"(acc[9][2]), "+f"(acc[9][3]), "+f"(acc[10][0]), "+f"(acc[10][1]), "+f"(acc[10][2]), "+f"(acc[10][3]), "+f"(acc[11][0]), "+f"(acc[11][1]), "+f"(acc[11][2]), "+f"(acc[11][3]), "+f"(acc[12][0]), "+f"(acc[12][1]), "+f"(acc[12][2]), "+f"(acc[12][3]), "+f"(acc[13][0]), "+f"(acc[13][1]), "+f"(acc[13][2]), "+f"(acc[13][3]), "+f"(acc[14][0]), "+f"(acc[14][1]), "+f"(acc[14][2]), "+f"(acc[14][3]), "+f"(acc[15][0]), "+f"(acc[15][1]), "+f"(acc[15][2]), "+f"(acc[15][3])
                 : "r"(a[0]), "r"(a[1]), "r"(a[2]), "r"(a[3]), "l"(desc));
}
template <> __device__ __forceinline__ void wg_mma<2>(float (&acc)[16][4], const uint32_t* a, uint64_t desc) {
    asm volatile("wgmma.mma_async.sync.aligned.m64n112k16.f32.f16.f16 {%0,%1,%2,%3,%4,%5,%6,%7,%8,%9,%10,%11,%12,%13,%14,%15,%16,%17,%18,%19,%20,%21,%22,%23,%24,%25,%26,%27,%28,%29,%30,%31,%32,%33,%34,%35,%36,%37,%38,%39,%40,%41,%42,%43,%44,%45,%46,%47,%48,%49,%50,%51,%52,%53,%54,%55}, {%56,%57,%58,%59}, %60, 1, 1, 1, 0;\n"
                 : "+f"(acc[2][0]), "+f"(acc[2][1]), "+f"(acc[2][2]), "+f"(acc[2][3]), "+f"(acc[3][0]), "+f"(acc[3][1]), "+f"(acc[3][2]), "+f"(acc[3][3]), "+f"(acc[4][0]), "+f"(acc[4][1]), "+f"(acc[4][2]), "+f"(acc[4][3]), "+f"(acc[5][0]), "+f"(acc[5][1]), "+f"(acc[5][2]), "+f"(acc[5][3]), "+f"(acc[6][0]), "+f"(acc[6][1]), "+f"(acc[6][2]), "+f"(acc[6][3]), "+f"(acc[7][0]), "+f"(acc[7][1]), "+f"(acc[7][2]), "+f"(acc[7][3]), "+f"(acc[8][0]), "+f"(acc[8][1]), "+f"(acc[8][2]), "+f"(acc[8][3]), "+f"(acc[9][0]), "+f"(acc[9][1]), "+f"(acc[9][2]), "+f"(acc[9][3]), "+f"(acc[10][0]), "+f"(acc[10][1]), "+f"(acc[10][2]), "+f"(acc[10][3]), "+f"(acc[11][0]), "+f"(acc[11][1]), "+f"(acc[11][2]), "+f"(acc[11][3]), "+f"(acc[12][0]), "+f"(acc[12][1]), "+f"(acc[12][2]), "+f"(acc[12][3]), "+f"(acc[13][0]), "+f"(acc[13][1]), "+f"(acc[13][2]), "+f"(acc[13][3]), "+f"(acc[14][0]), "+f"(acc[14][1]), "+f"(acc[14][2]), "+f"(acc[14][3]), "+f"(acc[15][0]), "+f"(acc[15][1]), "+f"(acc[15][2]), "+f"(acc[15][3])
                 : "r"(a[0]), "r"(a[1]), "r"(a[2]), "r"(a[3]), "l"(desc));
}
template <> __device__ __forceinline__ void wg_mma<4>(float (&acc)[16][4], const uint32_t* a, uint64_t desc) {
    asm volatile("wgmma.mma_async.sync.aligned.m64n96k16.f32.f16.f16 {%0,%1,%2,%3,%4,%5,%6,%7,%8,%9,%10,%11,%12,%13,%14,%15,%16,%17,%18,%19,%20,%21,%22,%23,%24,%25,%26,%27,%28,%29,%30,%31,%32,%33,%34,%35,%36,%37,%38,%39,%40,%41,%42,%43,%44,%45,%46,%47}, {%48,%49,%50,%51}, %52, 1, 1, 1, 0;\n"
                 : "+f"(acc[4][0]), "+f"(acc[4][1]), "+f"(acc[4][2]), "+f"(acc[4][3]), "+f"(acc[5][0]), "+f"(acc[5][1]), "+f"(acc[5][2]), "+f"(acc[5][3]), "+f"(acc[6][0]), "+f"(acc[6][1]), "+f"(acc[6][2]), "+f"(acc[6][3]), "+f"(acc[7][0]), "+f"(acc[7][1]), "+f"(acc[7][2]), "+f"(acc[7][3]), "+f"(acc[8][0]), "+f"(acc[8][1]), "+f"(acc[8][2]), "+f"(acc[8][3]), "+f"(acc[9][0]), "+f"(acc[9][1]), "+f"(acc[9][2]), "+f"(acc[9][3]), "+f"(acc[10][0]), "+f"(acc[10][1]), "+f"(acc[10][2]), "+f"(acc[10][3]), "+f"(acc[11][0]), "+f"(acc[11][1]), "+f"(acc[11][2]), "+f"(acc[11][3]), "+f"(acc[12][0]), "+f"(acc[12][1]), "+f"(acc[12][2]), "+f"(acc[12][3]), "+f"(acc[13][0]), "+f"(acc[13][1]), "+f"(acc[13][2]), "+f"(acc[13][3]), "+f"(acc[14][0]), "+f"(acc[14][1]), "+f"(acc[14][2]), "+f"(acc[14][3]), "+f"(acc[15][0]), "+f"(acc[15][1]), "+f"(acc[15][2]), "+f"(acc[15][3])
                 : "r"(a[0]), "r"(a[1]), "r"(a[2]), "r"(a[3]), "l"(desc));
}
template <> __device__ __forceinline__ void wg_mma<6>(float (&acc)[16][4], const uint32_t* a, uint64_t desc) {
    asm volatile("wgmma.mma_async.sync.aligned.m64n80k16.f32.f16.f16 {%0,%1,%2,%3,%4,%5,%6,%7,%8,%9,%10,%11,%12,%13,%14,%15,%16,%17,%18,%19,%20,%21,%22,%23,%24,%25,%26,%27,%28,%29,%30,%31,%32,%33,%34,%35,%36,%37,%38,%39}, {%40,%41,%42,%43}, %44, 1, 1, 1, 0;\n"
                 : "+f"(acc[6][0]), "+f"(acc[6][1]), "+f"(acc[6][2]), "+f"(acc[6][3]), "+f"(acc[7][0]), "+f"(acc[7][1]), "+f"(acc[7][2]), "+f"(acc[7][3]), "+f"(acc[8][0]), "+f"(acc[8][1]), "+f"(acc[8][2]), "+f"(acc[8][3]), "+f"(acc[9][0]), "+f"(acc[9][1]), "+f"(acc[9][2]), "+f"(acc[9][3]), "+f"(acc[10][0]), "+f"(acc[10][1]), "+f"(acc[10][2]), "+f"(acc[10][3]), "+f"(acc[11][0]), "+f"(acc[11][1]), "+f"(acc[11][2]), "+f"(acc[11][3]), "+f"(acc[12][0]), "+f"(acc[12][1]), "+f"(acc[12][2]), "+f"(acc[12][3]), "+f"(acc[13][0]), "+f"(acc[13][1]), "+f"(acc[13][2]), "+f"(acc[13][3]), "+f"(acc[14][0]), "+f"(acc[14][1]), "+f"(acc[14][2]), "+f"(acc[14][3]), "+f"(acc[15][0]), "+f"(acc[15][1]), "+f"(acc[15][2]), "+f"(acc[15][3])
                 : "r"(a[0]), "r"(a[1]), "r"(a[2]), "r"(a[3]), "l"(desc));
}
template <> __device__ __forceinline__ void wg_mma<8>(float (&acc)[16][4], const uint32_t* a, uint64_t desc) {
    asm volatile("wgmma.mma_async.sync.aligned.m64n64k16.f32.f16.f16 {%0,%1,%2,%3,%4,%5,%6,%7,%8,%9,%10,%11,%12,%13,%14,%15,%16,%17,%18,%19,%20,%21,%22,%23,%24,%25,%26,%27,%28,%29,%30,%31}, {%32,%33,%34,%35}, %36, 1, 1, 1, 0;\n"
                 : "+f"(acc[8][0]), "+f"(acc[8][1]), "+f"(acc[8][2]), "+f"(acc[8][3]), "+f"(acc[9][0]), "+f"(acc[9][1]), "+f"(acc[9][2]), "+f"(acc[9][3]), "+f"(acc[10][0]), "+f"(acc[10][1]), "+f"(acc[10][2]), "+f"(acc[10][3]), "+f"(acc[11][0]), "+f"(acc[11][1]), "+f"(acc[11][2]), "+f"(acc[11][3]), "+f"(acc[12][0]), "+f"(acc[12][1]), "+f"(acc[12][2]), "+f"(acc[12][3]), "+f"(acc[13][0]), "+f"(acc[13][1]), "+f"(acc[13][2]), "+f"(acc[13][3]), "+f"(acc[14][0]), "+f"(acc[14][1]), "+f"(acc[14][2]), "+f"(acc[14][3]), "+f"(acc[15][0]), "+f"(acc[15][1]), "+f"(acc[15][2]), "+f"(acc[15][3])
                 : "r"(a[0]), "r"(a[1]), "r"(a[2]), "r"(a[3]), "l"(desc));
}
template <> __device__ __forceinline__ void wg_mma<10>(float (&acc)[16][4], const uint32_t* a, uint64_t desc) {
    asm volatile("wgmma.mma_async.sync.aligned.m64n48k16.f32.f16.f16 {%0,%1,%2,%3,%4,%5,%6,%7,%8,%9,%10,%11,%12,%13,%14,%15,%16,%17,%18,%19,%20,%21,%22,%23}, {%24,%25,%26,%27}, %28, 1, 1, 1, 0;\n"
                 : "+f"(acc[10][0]), "+f"(acc[10][1]), "+f"(acc[10][2]), "+f"(acc[10][3]), "+f"(acc[11][0]), "+f"(acc[11][1]), "+f"(acc[11][2]), "+f"(acc[11][3]), "+f"(acc[12][0]), "+f"(acc[12][1]), "+f"(acc[12][2]), "+f"(acc[12][3]), "+f"(acc[13][0]), "+f"(acc[13][1]), "+f"(acc[13][2]), "+f"(acc[13][3]), "+f"(acc[14][0]), "+f"(acc[14][1]), "+f"(acc[14][2]), "+f"(acc[14][3]), "+f"(acc[15][0]), "+f"(acc[15][1]), "+f"(acc[15][2]), "+f"(acc[15][3])
                 : "r"(a[0]), "r"(a[1]), "r"(a[2]), "r"(a[3]), "l"(desc));
}
template <> __device__ __forceinline__ void wg_mma<12>(float (&acc)[16][4], const uint32_t* a, uint64_t desc) {
    asm volatile("wgmma.mma_async.sync.aligned.m64n32k16.f32.f16.f16 {%0,%1,%2,%3,%4,%5,%6,%7,%8,%9,%10,%11,%12,%13,%14,%15}, {%16,%17,%18,%19}, %20, 1, 1, 1, 0;\n"
                 : "+f"(acc[12][0]), "+f"(acc[12][1]), "+f"(acc[12][2]), "+f"(acc[12][3]), "+f"(acc[13][0]), "+f"(acc[13][1]), "+f"(acc[13][2]), "+f"(acc[13][3]), "+f"(acc[14][0]), "+f"(acc[14][1]), "+f"(acc[14][2]), "+f"(acc[14][3]), "+f"(acc[15][0]), "+f"(acc[15][1]), "+f"(acc[15][2]), "+f"(acc[15][3])
                 : "r"(a[0]), "r"(a[1]), "r"(a[2]), "r"(a[3]), "l"(desc));
}
template <> __device__ __forceinline__ void wg_mma<14>(float (&acc)[16][4], const uint32_t* a, uint64_t desc) {
    asm volatile("wgmma.mma_async.sync.aligned.m64n16k16.f32.f16.f16 {%0,%1,%2,%3,%4,%5,%6,%7}, {%8,%9,%10,%11}, %12, 1, 1, 1, 0;\n"
                 : "+f"(acc[14][0]), "+f"(acc[14][1]), "+f"(acc[14][2]), "+f"(acc[14][3]), "+f"(acc[15][0]), "+f"(acc[15][1]), "+f"(acc[15][2]), "+f"(acc[15][3])
                 : "r"(a[0]), "r"(a[1]), "r"(a[2]), "r"(a[3]), "l"(desc));
}
template <> __device__ __forceinline__ void wg_first<0>(float (&acc)[16][4], const uint32_t* a, uint64_t desc) {
    asm volatile("wgmma.mma_async.sync.aligned.m64n128k16.f32.f16.f16 {%0,%1,%2,%3,%4,%5,%6,%7,%8,%9,%10,%11,%12,%13,%14,%15,%16,%17,%18,%19,%20,%21,%22,%23,%24,%25,%26,%27,%28,%29,%30,%31,%32,%33,%34,%35,%36,%37,%38,%39,%40,%41,%42,%43,%44,%45,%46,%47,%48,%49,%50,%51,%52,%53,%54,%55,%56,%57,%58,%59,%60,%61,%62,%63}, {%64,%65,%66,%67}, %68, 0, 1, 1, 0;\n"
                 : "=f"(acc[0][0]), "=f"(acc[0][1]), "=f"(acc[0][2]), "=f"(acc[0][3]), "=f"(acc[1][0]), "=f"(acc[1][1]), "=f"(acc[1][2]), "=f"(acc[1][3]), "=f"(acc[2][0]), "=f"(acc[2][1]), "=f"(acc[2][2]), "=f"(acc[2][3]), "=f"(acc[3][0]), "=f"(acc[3][1]), "=f"(acc[3][2]), "=f"(acc[3][3]), "=f"(acc[4][0]), "=f"(acc[4][1]), "=f"(acc[4][2]), "=f"(acc[4][3]), "=f"(acc[5][0]), "=f"(acc[5][1]), "=f"(acc[5][2]), "=f"(acc[5][3]), "=f"(acc[6][0]), "=f"(acc[6][1]), "=f"(acc[6][2]), "=f"(acc[6][3]), "=f"(acc[7][0]), "=f"(acc[7][1]), "=f"(acc[7][2]), "=f"(acc[7][3]), "=f"(acc[8][0]), "=f"(acc[8][1]), "=f"(acc[8][2]), "=f"(acc[8][3]), "=f"(acc[9][0]), "=f"(acc[9][1]), "=f"(acc[9][2]), "=f"(acc[9][3]), "=f"(acc[10][0]), "=f"(acc[10][1]), "=f"(acc[10][2]), "=f"(acc[10][3]), "=f"(acc[11][0]), "=f"(acc[11][1]), "=f"(acc[11][2]), "=f"(acc[11][3]), "=f"(acc[12][0]), "=f"(acc[12][1]), "=f"(acc[12][2]), "=f"(acc[12][3]), "=f"(acc[13][0]), "=f"(acc[13][1]), "=f"(acc[13][2]), "=f"(acc[13][3]), "=f"(acc[14][0]), "=f"(acc[14][1]), "=f"(acc[14][2]), "=f"(acc[14][3]), "=f"(acc[15][0]), "=f"(acc[15][1]), "=f"(acc[15][2]), "=f"(acc[15][3])
                 : "r"(a[0]), "r"(a[1]), "r"(a[2]), "r"(a[3]), "l"(desc));
}
template <> __device__ __forceinline__ void wg_first<4>(float (&acc)[16][4], const uint32_t* a, uint64_t desc) {
    asm volatile("wgmma.mma_async.sync.aligned.m64n96k16.f32.f16.f16 {%0,%1,%2,%3,%4,%5,%6,%7,%8,%9,%10,%11,%12,%13,%14,%15,%16,%17,%18,%19,%20,%21,%22,%23,%24,%25,%26,%27,%28,%29,%30,%31,%32,%33,%34,%35,%36,%37,%38,%39,%40,%41,%42,%43,%44,%45,%46,%47}, {%48,%49,%50,%51}, %52, 0, 1, 1, 0;\n"
                 : "=f"(acc[4][0]), "=f"(acc[4][1]), "=f"(acc[4][2]), "=f"(acc[4][3]), "=f"(acc[5][0]), "=f"(acc[5][1]), "=f"(acc[5][2]), "=f"(acc[5][3]), "=f"(acc[6][0]), "=f"(acc[6][1]), "=f"(acc[6][2]), "=f"(acc[6][3]), "=f"(acc[7][0]), "=f"(acc[7][1]), "=f"(acc[7][2]), "=f"(acc[7][3]), "=f"(acc[8][0]), "=f"(acc[8][1]), "=f"(acc[8][2]), "=f"(acc[8][3]), "=f"(acc[9][0]), "=f"(acc[9][1]), "=f"(acc[9][2]), "=f"(acc[9][3]), "=f"(acc[10][0]), "=f"(acc[10][1]), "=f"(acc[10][2]), "=f"(acc[10][3]), "=f"(acc[11][0]), "=f"(acc[11][1]), "=f"(acc[11][2]), "=f"(acc[11][3]), "=f"(acc[12][0]), "=f"(acc[12][1]), "=f"(acc[12][2]), "=f"(acc[12][3]), "=f"(acc[13][0]), "=f"(acc[13][1]), "=f"(acc[13][2]), "=f"(acc[13][3]), "=f"(acc[14][0]), "=f"(acc[14][1]), "=f"(acc[14][2]), "=f"(acc[14][3]), "=f"(acc[15][0]), "=f"(acc[15][1]), "=f"(acc[15][2]), "=f"(acc[15][3])
                 : "r"(a[0]), "r"(a[1]), "r"(a[2]), "r"(a[3]), "l"(desc));
}

#define EARLYN 2
#define K8 0
#define HOLD 3
#define MC 1
#define STAMPW(i) STAMPY(i)
#define STAMP2(i) STAMP(i)
#undef STAMPX
#define STAMPX(i)
#define PBAR 1
#define WDLY 500
#define CBAR 1
#define FDLY 900
#define FDLY2 300
#define YDLY 1
#define YFROM 0
#define YPRE 0
#define KDLY 850
#define OEARLY 0
#define ODLY 0
#define SORD 1
#define SDLY 900
#define UDLY 1400
#define XCP 1
#define DEFER 0
#define WAE 0
#define RG0 0
#define RG1 2
#define WSP 1
#define EXP 0
#define XWHEN 0
#define RWHEN 0
#define HW 15
#define PEARLY 1
#define XG 6
struct Params {
    const bf16 *x, *lar, *aim, *cre, *cim, *ldt, *dsk;
    Scratch* s;
    const bf16 *wr, *wg, *wu, *wd;
    bf16* out;
};

#define TOK(g) (2 * (g) - ((g) & 1))
#define ROWTOK(r) (TOK((r) & 7) + (((r) >> 2) & 2))
__device__ __forceinline__ void ln_partial(const uint32_t (&H)[2][4], float (&d)[2][4]) {
#pragma unroll
    for (int hf = 0; hf < 2; hf++) {
        d[hf][0] = d[hf][1] = d[hf][2] = d[hf][3] = 0.f;
        mma_bf16(d[hf], H[hf][0], 0x3f803f80u, H[hf][1], 0x3f803f80u, H[hf][0], H[hf][1]);
    }
#pragma unroll
    for (int hf = 0; hf < 2; hf++) mma_bf16(d[hf], H[hf][2], 0x3f803f80u, H[hf][3], 0x3f803f80u, H[hf][2], H[hf][3]);
}
__device__ __forceinline__ float sum18(uint32_t a) {
    const uint4 p = lds128(a), q = lds128(a + 16), r = lds128(a + 32), s = lds128(a + 48);
    const uint2 u = lds64(a + 64);
#define F(x) __uint_as_float(x)
    return (((F(p.x) + F(p.y)) + (F(p.z) + F(p.w))) + ((F(q.x) + F(q.y)) + (F(q.z) + F(q.w)))) +
           (((F(r.x) + F(r.y)) + (F(r.z) + F(r.w))) + ((F(s.x) + F(s.y)) + (F(s.z) + F(s.w))) + (F(u.x) + F(u.y)));
#undef F
}
__device__ __forceinline__ void ln_stats(float sm, float sq, float& mb, float& sd) {
    const float m0 = sm * (1.0f / 576.0f);
    const float mean = fmaf(fmaf(-m0, 576.0f, sm), 1.0f / 576.0f, m0);
    const float var = fmaxf(fmaf(-mean, mean, sq * (1.0f / 576.0f)), 0.f);
    mb = rbf(mean);
    sd = rbf(sqrt_approx(rbf(rbf(var) + 1e-5f)));
}
__device__ __forceinline__ void ln_finish(float v, int lane, float& mb, float& rc) {
    const float o = __shfl_xor_sync(0xffffffffu, v, 16);
    float sd;
    ln_stats(lane < 16 ? v : o, lane < 16 ? o : v, mb, sd);
    rc = rcp_approx(sd);
}
__device__ __forceinline__ uint32_t ln_apply(uint32_t w, uint32_t m2, uint32_t rh, uint32_t rl) {
    const uint32_t d = hsub2_bf(w, m2);
    return hfma2_bf(d, rh, hmul2_bf(d, rl));
}
__device__ __forceinline__ void stat_store(uint32_t a, float mb, float rc, uint32_t extra) {
    const float rh = rbf(rc);
    sts64(a, (__float_as_uint(mb) >> 16) | (extra << 16), pack_bf16(rh, rc - rh));
}
#define STAT_M(s) __byte_perm((s).x, (s).x, 0x1010)
#define STAT_H(s) __byte_perm((s).y, (s).y, 0x1010)
#define STAT_L(s) __byte_perm((s).y, (s).y, 0x3232)

__device__ __forceinline__ void hcmul(uint32_t re, uint32_t im, uint32_t zx, uint32_t zy, uint32_t& ore, uint32_t& oim) {
    ore = hfms2(im, zy, hmul2(re, zx));
    oim = hfma2(re, zy, hmul2(im, zx));
}

struct KGen {
    uint32_t A[2][4][4];
    float2 z1, z8, z64, z128, T[9];
};
__device__ __forceinline__ void kgen_setup(KGen& k, float lar, float aim, float dt) {
    const float lr2 = -(exp_bf(lar) * dt) * 1.4426950408889634f, li = aim * dt;
    k.z1 = cexp_e(lr2, li, 1.0f);
    k.z8 = cexp_e(lr2, li, 8.0f);
    k.z64 = cexp_e(lr2, li, 64.0f);
}
__device__ __forceinline__ void kgen_rows(KGen& k, uint32_t tb, int lane) {
    const float2 z8 = k.z8, z64 = k.z64;
    const uint32_t row = tb + lane * 16;
    k.z128 = csq(z64);
    const float2 z16 = csq(z8), z24 = cmul(z16, z8), z32 = csq(z16), z40 = cmul(z32, z8), z48 = csq(z24), z56 = cmul(z32, z24);
    uint32_t re[4], im[4], a[4], b[4];
    re[0] = pack_f16(1.0f, z8.x); im[0] = pack_f16(0.0f, z8.y);
    re[1] = pack_f16(z16.x, z24.x); im[1] = pack_f16(z16.y, z24.y);
    re[2] = pack_f16(z32.x, z40.x); im[2] = pack_f16(z32.y, z40.y);
    re[3] = pack_f16(z48.x, z56.x); im[3] = pack_f16(z48.y, z56.y);
    sts128(row, re[0], re[1], re[2], re[3]);
    sts128(row + 1024, im[0], im[1], im[2], im[3]);
    const uint32_t zx = pack_f16(z64.x, z64.x), zy = pack_f16(z64.y, z64.y), zw = pack_f16(k.z128.x, k.z128.y);
#pragma unroll
    for (int j = 0; j < 4; j++) hcmul(re[j], im[j], zx, zy, a[j], b[j]);
    sts128(row + 512, a[0], a[1], a[2], a[3]);
    sts128(row + 1536, b[0], b[1], b[2], b[3]);
    const int mi = lane >> 3;
    const uint32_t zd = tb + 2048 + mi * 16;
    sts16(tb + 2048 + lane * 2, zw); sts16(tb + 2112 + lane * 2, zw >> 16);
    __syncwarp();
    const uint32_t ad = tb + (lane & 7) * 16 + mi * 512;
    ldsm_x4(a[0], a[1], a[2], a[3], zd);
    ldsm_x4(b[0], b[1], b[2], b[3], zd + 64);
#pragma unroll
    for (int ks = 0; ks < 4; ks++) {
        ldsm_x4_t(k.A[0][ks][0], k.A[0][ks][1], k.A[0][ks][2], k.A[0][ks][3], ad + ks * 128);
        hcmul(k.A[0][ks][0], k.A[0][ks][2], a[ks], b[ks], k.A[1][ks][0], k.A[1][ks][2]);
        hcmul(k.A[0][ks][1], k.A[0][ks][3], a[ks], b[ks], k.A[1][ks][1], k.A[1][ks][3]);
    }
}
__device__ __forceinline__ void kgen_chain(KGen& k, uint32_t cr, uint32_t ci, float cs) {
    k.T[0] = make_float2(bf_lo(cr) * cs, -bf_lo(ci) * cs);
    const float2 y1 = make_float2(k.z1.x, -k.z1.y);
#pragma unroll
    for (int c = 1; c < 8; c++) k.T[c] = cmul(k.T[c - 1], y1);
    k.T[8] = cmul(k.T[0], make_float2(k.z8.x, -k.z8.y));
}
__device__ __forceinline__ void kgen_cols(KGen& k, uint32_t tb, uint32_t t5, int lane) {
    const uint32_t row = tb + lane * 16;
    const float2 (&T)[9] = k.T;
    const float2 y128 = make_float2(k.z128.x, -k.z128.y);
    const float2 y256 = csq(y128), y512 = csq(y256), y768 = cmul(y512, y256), y1024 = csq(y512);
    const float2 c1032 = cmul(T[8], y1024);
    __syncwarp();
    sts128(row, pack_f16(T[0].x, T[1].x), pack_f16(T[2].x, T[3].x), pack_f16(T[4].x, T[5].x), pack_f16(T[6].x, T[7].x));
    sts128(row + 512, pack_f16(T[0].y, T[1].y), pack_f16(T[2].y, T[3].y), pack_f16(T[4].y, T[5].y), pack_f16(T[6].y, T[7].y));
    uint32_t a[4], b[4];
    {
        const uint32_t zx = pack_f16(y256.x, y256.x), zy = pack_f16(y256.y, y256.y);
        hcmul(pack_f16(T[0].x, T[2].x), pack_f16(T[0].y, T[2].y), zx, zy, a[0], b[0]);
        hcmul(pack_f16(T[4].x, T[6].x), pack_f16(T[4].y, T[6].y), zx, zy, a[1], b[1]);
        const uint32_t r04 = pack_f16(T[0].x, T[4].x), i04 = pack_f16(T[0].y, T[4].y);
        hcmul(r04, i04, pack_f16(y512.x, y512.x), pack_f16(y512.y, y512.y), a[2], b[2]);
        hcmul(r04, i04, pack_f16(y768.x, y768.x), pack_f16(y768.y, y768.y), a[3], b[3]);
    }
    sts128(row + 1024, a[0], a[1], a[2], a[3]);
    sts128(row + 1536, b[0], b[1], b[2], b[3]);
    {
        const uint32_t r0 = pack_f16(1.0f, y256.x), i0 = pack_f16(0.0f, y256.y), r1 = pack_f16(y512.x, y768.x), i1 = pack_f16(y512.y, y768.y);
        const uint32_t zx = pack_f16(T[8].x, T[8].x), zy = pack_f16(T[8].y, T[8].y), wx = pack_f16(c1032.x, c1032.x), wy = pack_f16(c1032.y, c1032.y);
        hcmul(r0, i0, zx, zy, a[0], b[0]); hcmul(r1, i1, zx, zy, a[1], b[1]);
        hcmul(r0, i0, wx, wy, a[2], b[2]); hcmul(r1, i1, wx, wy, a[3], b[3]);
    }
    sts128(row + 2048, a[0], a[1], a[2], a[3]);
    sts128(t5 + lane * 16, b[0], b[1], b[2], b[3]);
}
__device__ __forceinline__ void kgen_mma(const KGen& k, uint32_t tb, uint32_t t5, int lane, uint32_t hb) {
    __syncwarp();
    float acc[2][3][4];
#pragma unroll
    for (int i = 0; i < 6; i++)
#pragma unroll
        for (int j = 0; j < 4; j++) acc[i / 3][i % 3][j] = 0.f;
    const int mi = lane >> 3;
    const uint32_t ro = ((lane & 7) + 8 * (mi >> 1)) * 16, bd = tb + ro + (mi & 1) * 512, b2 = ro + ((mi & 1) ? t5 : tb + 2048);
#pragma unroll
    for (int kp = 0; kp < 2; kp++)
#pragma unroll
        for (int j = 0; j < 3; j++) {
            uint32_t b[4];
            if (HOLD == 5 && kp == 1 && j == 0) mbar_wait1(hb);
            ldsm_x4_t(b[0], b[1], b[2], b[3], (j < 2 ? bd + j * 1024 : b2) + kp * 256);
#pragma unroll
            for (int h = 0; h < 2; h++)
#pragma unroll
                for (int m = 0; m < 2; m++) {
                    const uint32_t (&A)[4] = k.A[m][2 * kp + h];
                    mma_f16(acc[m][j], A[0], A[1], A[2], A[3], b[2 * h], b[2 * h + 1]);
                }
        }
    __syncwarp();
#define PK(j) pack_f16(acc[0][j][0], acc[0][j][1]), pack_f16(acc[0][j][2], acc[0][j][3]), pack_f16(acc[1][j][0], acc[1][j][1]), pack_f16(acc[1][j][2], acc[1][j][3])
    stsm_x4(tb + lane * 16, PK(0));
    stsm_x4(tb + 512 + lane * 16, PK(1));
    stsm_x4_t(tb + 1024 + (lane & 7) * 80 + mi * 16, PK(2));
#undef PK
}
__device__ __forceinline__ uint32_t table_buf(uint32_t sb, int warp) { return sb + SM_PL + warp * TBW; }

__device__ __forceinline__ uint4 lds16x4(uint32_t a) { return make_uint4(lds16(a), lds16(a + TBW), lds16(a + 2 * TBW), lds16(a + 3 * TBW)); }
__device__ __forceinline__ void combine_setup(uint32_t sb, int warp, int lane, uint32_t kw, uint32_t& o, uint32_t& n, uint32_t& d) {
    const int wq = warp & 3;
    const uint32_t a = table_buf(sb, warp & ~3);
    o = wq == 3 ? a + 1024 + 320 + (lane >> 3) * 80 + (lane & 7) * 8 : a + (wq ? 504 + wq * 8 : 0) + lane * 16;
    n = a + 1024 + wq * 80 + lane * 2;
    d = wq < 3 ? kw + (wq == 2 ? KW_P : 32 + wq * 512) + lane * 16 : kw + KW_H + 8 + lane * 8;
}
__device__ __forceinline__ void kgen_combine(int wq, int lane, uint32_t o, uint32_t na, uint32_t d) {
#define S4(f) hadd2(hadd2(u.f, v.f), hadd2(w.f, x.f))
#define H4(v) hadd2(hadd2(v.x, v.y), hadd2(v.z, v.w))
#define BP __byte_perm
    if (wq == 0) {
        const uint4 u = lds128(o), v = lds128(o + TBW), w = lds128(o + 2 * TBW), x = lds128(o + 3 * TBW), nn = lds16x4(na);
        const uint32_t n = H4(nn), k0 = S4(x), k2 = S4(y), k4 = S4(z), k6 = S4(w);
        sts128(d, BP(k0, k0, 0x1032), BP(k0, k2, 0x3254), BP(k2, k2, 0x1032), BP(k2, k4, 0x3254));
        sts128(d + KW_PL, BP(k4, k4, 0x1032), BP(k4, k6, 0x3254), BP(k6, k6, 0x1032), BP(k6, n, 0x3254));
        if (lane == 0) sts32(d + KW_PL - 4, k0 & 0xffffu);
    } else {
        const uint2 u = lds64(o), v = lds64(o + TBW), w = lds64(o + 2 * TBW), x = lds64(o + 3 * TBW);
        uint4 nn = make_uint4(0u, 0u, 0u, 0u), mm = nn;
        if (wq < 3) nn = lds16x4(na);
        if (wq == 2) mm = lds16x4(na + 80);
        const uint32_t k0 = S4(x), k2 = S4(y), n = H4(nn), m = H4(mm);
        if (wq == 3) {
            sts64(d, k0, k2);
        } else if (wq == 1) {
            const uint32_t cc = BP(k2, k2, 0x1010);
            sts128(d, BP(k0, k0, 0x1010), BP(k0, k0, 0x1032), BP(k0, k2, 0x3254), cc);
            sts128(d + KW_PL, cc, BP(k2, k2, 0x1032), BP(k2, n, 0x3254), BP(n, n, 0x1010));
        } else {
            const uint32_t w40 = BP(k0, k0, 0x1032), w84 = BP(k0, n, 0x3254), w0 = BP(k0, k0, 0x1010), w4 = BP(k0, k0, 0x3232), w8 = BP(n, n, 0x1010);
            sts64(d, w40, w84);
            sts64(d + 512, BP(k2, k2, 0x1032), BP(k2, m, 0x3254));
            if (lane < 8) { sts128(d - (KW_P - 1056), w0, w0, w40, w4); sts128(d - (KW_P - 1056 - KW_PL), w4, w84, w8, w8); }
            if (lane == 31) sts16(d + (KW_H + 6 - KW_P - 496), m);
        }
    }
#undef S4
#undef H4
#undef BP
}

__device__ __forceinline__ int c_exponent(const uint2& r, const uint2& i, float dt) {
    const uint32_t mx = __vmaxu2(__vmaxu2(r.x & 0x7fff7fffu, r.y & 0x7fff7fffu), __vmaxu2(i.x & 0x7fff7fffu, i.y & 0x7fff7fffu));
    return __reduce_max_sync(0xffffffffu, max(mx, mx << 16) + (__float_as_uint(dt) & 0x7f800000u)) >> 23;
}

#define ONEBAR 1
__device__ __forceinline__ int warp_v() { int l; asm volatile("mov.u32 %0, %%tid.x;" : "=r"(l)); return __shfl_sync(0xffffffffu, l >> 5, 0); }
__device__ __forceinline__ int lane_v() { int l; asm volatile("mov.u32 %0, %%laneid;" : "=r"(l)); return l; }
__device__ __forceinline__ uint32_t prmt_v(uint32_t a, uint32_t b, uint32_t s) { uint32_t d; asm volatile("prmt.b32 %0, %1, %2, %3;\n" : "=r"(d) : "r"(a), "r"(b), "r"(s)); return d; }
__device__ __forceinline__ uint32_t mov_v(uint32_t a) { uint32_t d; asm volatile("mov.b32 %0, %1;\n" : "=r"(d) : "r"(a)); return d; }
template <int G>
__device__ __forceinline__ void conv_rename(float (&acc)[16][4]) {
#pragma unroll
    for (int i = G; i < 16; i++)
#pragma unroll
        for (int j = 0; j < 4; j++) { float v; asm volatile("mov.b32 %0, %1;\n" : "=f"(v) : "f"(acc[i][j])); acc[i][j] = v; }
}
struct Conv {
    uint32_t kw;
    uint32_t wa;
    uint32_t pa, s2;
    uint32_t s8;
    uint32_t id;
    uint32_t lc;
    uint32_t fs;
    uint32_t fl, yo;
    uint32_t yp;
    size_t ycopy;
    uint32_t ps;
    uint64_t d0;
    int warp;
};
struct Pk { uint32_t w[4]; };
__device__ __forceinline__ Pk pk2(const float (&u)[4], const float (&v)[4]) {
    Pk r;
    r.w[0] = pack_f16(u[0], u[1]); r.w[1] = pack_f16(u[2], u[3]); r.w[2] = pack_f16(v[0], v[1]); r.w[3] = pack_f16(v[2], v[3]);
    return r;
}
__device__ __forceinline__ void park(uint32_t a, const Pk& v) {
    asm volatile("stmatrix.sync.aligned.m8n8.x4.trans.shared.b16 [%0], {%1,%2,%3,%4};\n" ::"r"(a), "r"(v.w[0]), "r"(v.w[1]), "r"(v.w[2]), "r"(v.w[3]) : "memory");
}
__device__ __forceinline__ void conv_constants(uint32_t lc, int l) {
    const int d = (l >> 2) - 2 * (l & 3);
    const int e = d + 8, r4 = (e + 1 + ((e >> 2) & 1)) >> 2, p4 = (e + (((e - 1) >> 2) & 1)) >> 2;
    const uint32_t s2 = r4 == p4 ? 0x1010u : 0x3210u;
    sts64(lc + l * 8, KW_P + ((r4 - 5) >> 1) * 16 + ((r4 - 5) & 1) * 4, s2 | ((d < 0 ? s2 : 0x7654u) << 16));
    const int lo = (d >= 4) - (d < -3), ho = (d >= 5) - (d < -2), le = (d > 4) - (d < -4), he = (d > 5) - (d < -3);
    sts32(lc + 512 + l * 8, (0x5454u + lo * 0x22 + ho * 0x2200) | ((0x3232u + le * 0x22 + he * 0x2200) << 16));
    const int cc = l >> 2, j = l & 3;
    sts64(lc + 256 + l * 8, (j >> 1) * PL_HALF + (16 + cc) * 16 + (j & 1) * 8, (cc >> 1) * (DM * 64) + (cc & 1) * 32 + j * 8);
}
__device__ __forceinline__ void conv_selectors4(Conv& c) {
    const uint2 v = lds64(c.lc + lane_v() * 8);
    c.pa = v.x; c.s2 = v.y;
}
__device__ __forceinline__ void conv_selectors8(Conv& c) { c.s8 = lds32(c.lc + 512 + lane_v() * 8); }
template <int G, int I0, int I1>
__device__ __forceinline__ void conv_load(const Conv& c, uint32_t (&q)[9]) {
    const int wq = c.warp & 3;
    if (G < 2) {
#pragma unroll
        for (int i = I0; i < I1; i++) q[i] = lds32(c.wa + G * 512 + i * 16);
    } else if (G < 4) {
        const uint32_t a = (G == 2 && wq == 0) ? c.wa + 1024 : c.pa + c.kw + wq * 128 + (G < 2 ? 0 : G - 2) * 512;
#pragma unroll
        for (int i = I0; i < I1; i++) q[i] = lds32(a + i * 16);
    } else {
        const uint4 u = lds128(c.kw + KW_H + (G < 4 ? 0 : G - 4) * 64 + wq * 16);
        const uint2 v = lds64(c.kw + KW_H + (G < 4 ? 0 : G - 4) * 64 + wq * 16 + 16);
        q[0] = u.x; q[1] = u.y; q[2] = u.z; q[3] = u.w; q[4] = v.x; q[5] = v.y;
        if (G == 4 && wq == 0) { q[6] = lds32(c.pa + c.kw + 1024); q[7] = lds32(c.pa + c.kw + 1040); }
    }
}
template <int G, int J0, int J1>
__device__ __forceinline__ void conv_frag(const Conv& c, const uint32_t (&q)[9], uint32_t* a, const Pk& dp) {
    const uint32_t dep = dp.w[0];
    if (G < 4) {
        const uint32_t s = (G < 2 || (G == 2 && (c.warp & 3) == 0)) ? c.id : c.s2;
#pragma unroll
        for (int j = J0; j < J1; j++) {
            uint32_t* o = a + 4 * (j - J0);
            o[0] = prmt_v(q[2 * j + 1], dp.w[0], s); o[1] = prmt_v(q[2 * j + 2], dp.w[1], s); o[2] = prmt_v(q[2 * j], dp.w[2], s); o[3] = prmt_v(q[2 * j + 1], dp.w[3], s);
        }
    } else {
        const uint32_t so = prmt_v(c.s8, dep, c.id), se = prmt_v(c.s8, dep, c.id + 0x22);
#pragma unroll
        for (int j = J0; j < J1; j++) {
            uint32_t* o = a + 4 * (j - J0);
            o[0] = prmt_v(q[j + 1], q[j + 2], se); o[1] = prmt_v(q[j + 1], q[j + 2], so); o[2] = prmt_v(q[j], q[j + 1], so);
            if (G == 4 && j == 0 && (c.warp & 3) == 0) {
                o[2] = prmt_v(q[6], dep, c.s2);
                o[0] = prmt_v(q[7], o[0], c.s2 >> 16);
            }
            o[3] = mov_v(o[0]);
        }
    }
}
template <int G, int J0, int J1>
__device__ __forceinline__ void conv_frag(const Conv& c, const uint32_t (&q)[9], uint32_t* a, float depf) {
    const uint32_t d = __float_as_uint(depf);
    conv_frag<G, J0, J1>(c, q, a, Pk{{d, d, d, d}});
}
template <int G, int T, int J0, int J1>
__device__ __forceinline__ void conv_mma(float (&acc)[16][4], const Conv& c, const uint32_t* a) {
#pragma unroll
    for (int j = J0; j < J1; j++) wg_mma<T>(acc, a + 4 * (j - J0), c.d0 - 8 * (2 * G - T) - j);
}
__device__ __forceinline__ float h_lo(uint32_t w) { return __half2float(__ushort_as_half((unsigned short)(w & 0xffffu))); }
__device__ __forceinline__ float h_hi(uint32_t w) { return __half2float(__ushort_as_half((unsigned short)(w >> 16))); }
__device__ __forceinline__ void flush_setup(Conv& c) {
    const uint2 v = lds64(c.lc + 256 + lane_v() * 8);
    c.fl = v.x; c.yo = v.y;
}
template <int Q>
__device__ __forceinline__ void flush_load(const Conv& c, uint32_t pl, uint2 (&f)[4]) {
#pragma unroll
    for (int w = 0; w < 4; w++) f[w] = lds64(c.fl + pl + (Q & 1) * 512 + w * (PLW_B - 64));
}
template <int Q>
__device__ __forceinline__ void flush_load_first(const Conv& c, uint32_t pl, uint2 (&f)[4], float depf) {
    const uint32_t p = prmt_v(c.fl, __float_as_uint(depf), c.id) + pl + (Q & 1) * 512;
#define LDV64(d, a) asm volatile("ld.volatile.shared.v2.u32 {%0,%1}, [%2];\n" : "=r"(d.x), "=r"(d.y) : "r"(a) : "memory")
    LDV64(f[0], p); LDV64(f[1], p + (PLW_B - 64)); LDV64(f[2], p + 2 * (PLW_B - 64)); LDV64(f[3], p + 3 * (PLW_B - 64));
}
#define FDEP __uint_as_float(f[3].y)
template <int Q, int mode>
__device__ __forceinline__ void conv_flush(const Conv& c, const uint2 (&f)[4], unsigned char* gy, uint32_t rx) {
    const uint32_t a0 = hadd2(f[0].x, f[1].x), a1 = hadd2(f[2].x, f[3].x), b0 = hadd2(f[0].y, f[1].y), b1 = hadd2(f[2].y, f[3].y);
    if (Q > 0 && mode == 1) {
        const uint32_t ra = rx + 16 + (Q > 0 ? Q - 1 : 0) * 1024 + (c.warp & 3) * 256 + lane_v() * 8;
        asm volatile("st.async.shared::cluster.mbarrier::complete_tx::bytes.v2.b32 [%0], {%1,%2}, [%3];\n"
                     ::"r"(ra ^ 0x1000000u), "r"(hadd2(a0, a1)), "r"(hadd2(b0, b1)), "r"((rx + (Q > 1 ? 8 : 0)) ^ 0x1000000u) : "memory");
        return;
    }
    float v0 = h_lo(a0) + h_lo(a1), v1 = h_hi(a0) + h_hi(a1), v2 = h_lo(b0) + h_lo(b1), v3 = h_hi(b0) + h_hi(b1);
    if (Q > 0 && mode == 2) {
        const uint2 o = lds64(rx + 16 + (Q > 0 ? Q - 1 : 0) * 1024 + (c.warp & 3) * 256 + lane_v() * 8);
        v0 += h_lo(o.x); v1 += h_hi(o.x); v2 += h_lo(o.y); v3 += h_hi(o.y);
    }
    const uint32_t lo = hmul2_bf(pack_bf16(v0, v1), c.fs), hi = hmul2_bf(pack_bf16(v2, v3), c.fs);
    stg64(gy + Q * 32 * DM * 32 + (c.yo + (Q < 3 ? c.yp : 0u)), nzw(lo), nzw(hi));
}
template <int I, bool S = false> struct IC { static constexpr int value = I; static constexpr bool shared = S; };
template <class T> __device__ constexpr bool wg_is4() { return T::shared; }
#define SLOT(n) (c.ps + (2 + ((n) & 7)) * 128)
#define GO() do { wg_commit(); __syncwarp(); } while (0)
#define DEP acc[15][3]
template <class FG, class FP, class FN>
__device__ __forceinline__ void conv_head(Conv& c, float (&acc)[16][4], uint32_t (&q)[9], uint32_t (&r)[9], uint32_t* a, FG fg, FP pre, FN next) {
    c.id = 0x3210u + (c.warp >> 8);
    if (ONEBAR) pre();
    conv_load<0, 0, 9>(c, q);
    conv_frag<0, 0, 1>(c, q, a, 0.f);
    if (!ONEBAR) pre();
    wg_fence(); wg_first<0>(acc, a, c.d0); GO();
    park(c.ps, Pk{{0u, 0u, 0u, 0u}});
    wg_wait0();
    conv_frag<0, 1, 2>(c, q, a, DEP);
    wg_fence(); conv_mma<0, 0, 1, 2>(acc, c, a); GO();
    fg(IC<0>());
    wg_wait0();
    conv_frag<0, 2, 3>(c, q, a, DEP);
    wg_fence(); conv_mma<0, 0, 2, 3>(acc, c, a); GO();
    conv_load<1, 0, 5>(c, r);
    wg_wait0();
    conv_frag<0, 3, 4>(c, q, a, DEP);
    wg_fence(); conv_mma<0, 0, 3, 4>(acc, c, a); GO();
    conv_load<1, 5, 9>(c, r);
    fg(IC<1>());
    wg_wait0();
    const Pk k = pk2(acc[0], acc[1]);
    conv_rename<2>(acc);
    conv_frag<1, 0, 2>(c, r, a, k);
    wg_fence(); conv_mma<1, 2, 0, 2>(acc, c, a); GO();
    park(SLOT(0), k);
    next(IC<0>());
    fg(IC<2>());
    wg_wait0();
    conv_frag<1, 2, 4>(c, r, a, DEP);
    wg_fence(); conv_mma<1, 2, 2, 4>(acc, c, a); GO();
    next(IC<1>());
    fg(IC<3>());
    wg_wait0();
}
template <class FG, class FP>
__device__ __forceinline__ void conv_run(Conv& c, uint32_t pl, unsigned char* gy, FG fg, FP pre) {
    float acc[16][4];
    uint32_t q[9], r[9], a[32];
    uint2 f[4];
    const int bid = 1 + (c.warp >> 2);
    conv_head(c, acc, q, r, a, fg, pre, [&](auto i) { if (decltype(i)::value == 0) conv_selectors4(c); else conv_load<2, 0, 9>(c, q); });
    Pk k = pk2(acc[2], acc[3]);
    conv_rename<4>(acc);
    conv_frag<2, 0, 4>(c, q, a, k);
    wg_fence(); conv_mma<2, 4, 0, 4>(acc, c, a); GO();
    park(SLOT(2), k);
    conv_load<3, 0, 9>(c, q);
    flush_setup(c);
    bar_sync(bid, 128);
    fg(IC<4>());
    wg_wait0();
    conv_rename<6>(acc);
    flush_load_first<0>(c, pl, f, DEP);
    conv_frag<3, 0, 4>(c, q, a, FDEP);
    wg_fence(); conv_mma<3, 6, 0, 4>(acc, c, a); GO();
    park(SLOT(4), pk2(acc[4], acc[5]));
    conv_load<4, 0, 9>(c, q);
    conv_selectors8(c);
    conv_flush<0, 0>(c, f, gy, 0u);
    fg(IC<5>());
    wg_wait0();
    conv_rename<8>(acc);
    conv_frag<4, 0, 4>(c, q, a, DEP);
    wg_fence(); conv_mma<4, 8, 0, 4>(acc, c, a); GO();
    k = pk2(acc[6], acc[7]);
    park(SLOT(6), k); park(c.ps, k);
    conv_load<5, 0, 9>(c, q);
    bar_sync(bid, 128);
    fg(IC<6>());
    wg_wait0();
    conv_rename<10>(acc);
    flush_load_first<1>(c, pl, f, DEP);
    conv_frag<5, 0, 4>(c, q, a, FDEP);
    wg_fence(); conv_mma<5, 10, 0, 4>(acc, c, a); GO();
    park(SLOT(8), pk2(acc[8], acc[9]));
    conv_load<6, 0, 9>(c, q); conv_load<7, 0, 9>(c, r);
    conv_flush<1, 0>(c, f, gy, 0u);
    fg(IC<7>());
    wg_wait0();
    conv_rename<12>(acc);
    conv_frag<6, 0, 4>(c, q, a, DEP); conv_frag<7, 0, 4>(c, r, a + 16, DEP);
    wg_fence(); conv_mma<6, 12, 0, 4>(acc, c, a); conv_mma<7, 12, 0, 4>(acc, c, a + 16); GO();
    park(SLOT(10), pk2(acc[10], acc[11]));
    bar_sync(bid, 128);
    flush_load<2>(c, pl, f);
    conv_flush<2, 0>(c, f, gy, 0u);
    fg(IC<8>());
    wg_wait0();
    park(SLOT(12), pk2(acc[12], acc[13])); park(SLOT(14), pk2(acc[14], acc[15]));
    bar_sync(bid, 128);
    flush_load<3>(c, pl, f);
    conv_flush<3, 0>(c, f, gy, 0u);
}
template <class FG>
__device__ __forceinline__ void conv_outer(Conv& c, uint32_t pl, unsigned char* gy, uint32_t rx, FG fg) {
    float acc[16][4];
    uint32_t q[9], r[9], a[32];
    uint2 f[4], f2[4];
    const int bid = 1 + (c.warp >> 2);
    conv_head(c, acc, q, r, a, [&](auto gi) { if (decltype(gi)::value == 2) fg(IC<2, true>()); }, [&]() {}, [&](auto i) { if (decltype(i)::value == 0) conv_selectors8(c); else conv_load<6, 0, 9>(c, q); });
    park(SLOT(2), pk2(acc[2], acc[3])); park(SLOT(4), pk2(acc[4], acc[5]));
    const Pk k = pk2(acc[6], acc[7]);
    park(SLOT(6), k);
    conv_load<7, 0, 9>(c, r);
    conv_rename<12>(acc);
    conv_frag<6, 0, 4>(c, q, a, __uint_as_float(k.w[3])); conv_frag<7, 0, 4>(c, r, a + 16, __uint_as_float(k.w[3]));
    wg_fence(); conv_mma<6, 12, 0, 4>(acc, c, a); conv_mma<7, 12, 0, 4>(acc, c, a + 16); GO();
    flush_setup(c);
    bar_sync(bid, 128);
    flush_load<0>(c, pl, f); flush_load<1>(c, pl, f2);
    conv_flush<1, 1>(c, f2, gy, rx);
    conv_flush<0, 1>(c, f, gy, rx);
    wg_wait0();
    bar_sync(bid, 128);
    park(c.ps, k); park(SLOT(8), pk2(acc[8], acc[9])); park(SLOT(10), pk2(acc[10], acc[11]));
    park(SLOT(12), pk2(acc[12], acc[13])); park(SLOT(14), pk2(acc[14], acc[15]));
    bar_sync(bid, 128);
    flush_load<2>(c, pl, f); flush_load<3>(c, pl, f2);
    conv_flush<2, 1>(c, f, gy, rx);
    conv_flush<3, 1>(c, f2, gy, rx);
}
template <class FG>
__device__ __forceinline__ void conv_inner(Conv& c, uint32_t pl, unsigned char* gy, uint32_t rx, FG fg) {
    float acc[16][4];
    uint32_t q[9], a[16];
    uint2 f[4], f2[4];
    const int bid = 1 + (c.warp >> 2);
    c.id = 0x3210u + (c.warp >> 8);
    conv_selectors4(c);
    conv_load<2, 0, 9>(c, q);
    conv_frag<2, 0, 4>(c, q, a, 0.f);
    wg_fence(); wg_first<4>(acc, a, c.d0); conv_mma<2, 4, 1, 4>(acc, c, a + 4); GO();
    conv_load<3, 0, 9>(c, q);
    park(SLOT(2), Pk{{0u, 0u, 0u, 0u}});
    fg(IC<2, true>());
    wg_wait0();
    conv_rename<6>(acc);
    conv_frag<3, 0, 4>(c, q, a, DEP);
    wg_fence(); conv_mma<3, 6, 0, 4>(acc, c, a); GO();
    park(SLOT(4), pk2(acc[4], acc[5]));
    conv_load<4, 0, 9>(c, q);
    conv_selectors8(c);
    wg_wait0();
    conv_rename<8>(acc);
    conv_frag<4, 0, 4>(c, q, a, DEP);
    wg_fence(); conv_mma<4, 8, 0, 4>(acc, c, a); GO();
    const Pk k = pk2(acc[6], acc[7]);
    park(SLOT(6), k); park(c.ps, k);
    conv_load<5, 0, 9>(c, q);
    flush_setup(c);
    wg_wait0();
    conv_rename<10>(acc);
    conv_frag<5, 0, 4>(c, q, a, DEP);
    wg_fence(); conv_mma<5, 10, 0, 4>(acc, c, a); GO();
    park(SLOT(8), pk2(acc[8], acc[9]));
    bar_sync(bid, 128);
    flush_load<1>(c, pl, f);
    mbar_wait(rx);
    conv_flush<1, 2>(c, f, gy, rx);
    wg_wait0();
    bar_sync(bid, 128);
    park(SLOT(10), pk2(acc[10], acc[11])); park(SLOT(12), pk2(acc[12], acc[13])); park(SLOT(14), pk2(acc[14], acc[15]));
    bar_sync(bid, 128);
    flush_load<3>(c, pl, f); flush_load<2>(c, pl, f2);
    mbar_wait(rx + 8);
    conv_flush<3, 2>(c, f, gy, rx);
    conv_flush<2, 2>(c, f2, gy, rx);
}
#undef SLOT
#undef GO
#undef DEP
template <int U0, int U1>
__device__ __forceinline__ void weight_units(uint32_t sb, const CUtensorMap* tg, const CUtensorMap* tu, const CUtensorMap* td, bool w) {
    if (U1 > U0 && w && elect_one()) {
#pragma unroll
        for (int n = U0; n < U1; n++) {
            const int i = n;
            if (i < 12) tma_2d(sb + SM_WG + i * 6912, i < 6 ? tg : tu, 72 * (blockIdx.x >> 1), 288 * (blockIdx.x & 1) + (i % 6) * 48, sb + SM_MISC + 328);
            else tma_2d(sb + SM_WD + (i - 12) * 4736, td, 144 * (blockIdx.x & 1), 72 * (blockIdx.x >> 1) + 8 * (i - 12), sb + SM_MISC + 336);
        }
    }
}
#define WS 1111121111122004100
__device__ constexpr int wsched(int i) {
    unsigned long long v = WS;
    int n = 0;
    for (int k = 19; k >= 1; k--) { if (k < i) n += (int)(v % 10); v /= 10; }
    return n;
}
static_assert(wsched(20) == 21 && wsched(6) <= 7 && wsched(11) <= 12 && wsched(13) <= 14 && wsched(16) <= 17 && wsched(16) == wsched(15) && wsched(19) == 21, "");
__device__ __forceinline__ void weight_prefetch(const Params& p, int u, int lane) {
    const int b = blockIdx.x;
    const char* a = u < 12 ? reinterpret_cast<const char*>(u < 6 ? p.wg : p.wu) + ((b >> 6) * 288 + (u % 6) * 48) * (FF * 2) + (b & 63) * 6912
                           : reinterpret_cast<const char*>(p.wd) + (72 * (b >> 1) + 8 * (u - 12)) * 1152 + (b & 1) * 4608;
    asm volatile("prefetch.global.L2 [%0];\n" ::"l"(a + lane * 128));
    if (lane < (u < 12 ? 22 : 4)) asm volatile("prefetch.global.L2 [%0];\n" ::"l"(a + 4096 + lane * 128));
}
#define PF0 0
#define PF1 0
#define WPOINT(i, w) do { weight_units<wsched(i), wsched(i + 1)>(sb, &tm_g, &tm_u, &tm_d, w); } while (0)

__global__ void __launch_bounds__(NTHR, 1) __cluster_dims__(2, 1, 1)
fused_kernel(const Params p, const __grid_constant__ CUtensorMap tm_g, const __grid_constant__ CUtensorMap tm_u, const __grid_constant__ CUtensorMap tm_d, const __grid_constant__ CUtensorMap tm_x) {
    extern __shared__ __align__(1024) unsigned char smem[];
    const uint32_t sb = smem_u32(smem);
    const int tid = threadIdx.x, warp = __shfl_sync(0xffffffffu, tid >> 5, 0), lane = tid & 31;
    const int b = blockIdx.x, P = b >> 1, odd = b & 1;
    const int g = lane >> 2, t = lane & 3;
    const int wg = warp >> 2, t128 = tid & 127;
    const uint32_t s_stat = sb + SM_MISC;
    const uint32_t s_key = sb + SM_MISC + 128;
    const uint32_t s_rank = sb + SM_MISC + 256;
    const uint32_t s_k16 = sb + SM_MISC + 192;
    const uint32_t s_cnt = sb + SM_MISC + 320;
    const uint32_t bar_w = sb + SM_MISC + 328, bar_d = bar_w + 8, bar_g = bar_w + 16, bar_x = bar_w + 24, bar_t = bar_w + 32, bar_s = bar_w + 40, bar_v = bar_w + 48, bar_h = sb + SM_MISC + 160;
    STAMP(0);

    if (warp == 19) {
        if (lane == 0) {
            mbar_init(bar_w, 1); mbar_init(bar_d, 1); mbar_init(bar_g, 1); mbar_init(sb + SM_RX, 1); mbar_init(sb + SM_RX + 8, 1);
            mbar_init(bar_x, 1); mbar_init(bar_t, 1); mbar_init(bar_s, 1); mbar_init(bar_v, 2); if (HOLD >= 2) { mbar_init(bar_h, 1); mbar_init(bar_h + 8, 1); mbar_init(bar_h + 16, 1); mbar_init(bar_h + 24, 1); } mbar_expect(bar_x, 32768);
            asm volatile("fence.mbarrier_init.release.cluster;\n" ::: "memory");
            mbar_expect(bar_w, 82944); mbar_expect(bar_d, 72 * WD_PITCH); mbar_expect(bar_g, 4608); mbar_expect(bar_t, 16 * 1152); mbar_expect(bar_v, 2 * 1152); mbar_expect(sb + SM_RX, 1024); mbar_expect(sb + SM_RX + 8, 2048);
        }
        __syncwarp();
    }
    if (wg < 3) { sts128(sb + SM_Z2 + tid * 16, 0u, 0u, 0u, 0u); sts128(sb + SM_Z2 + 6144 + tid * 16, 0u, 0u, 0u, 0u); fence_async(); }
    const int ch = wg < 4 ? 4 * b + wg : 512 + P;
    const bf16 *q0 = p.lar + ch * NST, *q1 = p.aim + ch * NST, *q2 = p.cre + ch * NST, *q3 = p.cim + ch * NST;
    asm volatile("" : "+l"(q0), "+l"(q1), "+l"(q2), "+l"(q3));
    const uint32_t ldt = ldo16(p.ldt + ch), pl = ldo16(q0 + t128), pa2 = ldo16(q1 + t128);
    const uint32_t pc = ldo16(q2 + t128), pi = ldo16(q3 + t128);
    const uint2 call_re = ldo64(q2 + 4 * lane), call_im = ldo64(q3 + 4 * lane);
    const uint32_t epl = ld_poll32(p.s->hint + (b & 7) * 32 + 1);
    bar_sync(0, NWRK);
    if (XCP && wg == 4) {
        const int o = (4 * (warp & 3) + (g >> 1)) * 1152 + (g & 1) * 576 + t * 16;
#pragma unroll
        for (int c = 0; c < 9; c++)
            asm volatile("cp.async.cg.shared.global [%0], [%1], 16;\n" ::"r"(sb + SM_XT + o + c * 64), "l"(reinterpret_cast<const char*>(p.x) + b * 18432 + o + c * 64) : "memory");
        asm volatile("cp.async.commit_group;\n" ::: "memory");
    }
    asm volatile("barrier.cluster.arrive.relaxed.aligned;\n" ::: "memory");
    if (warp == 18) {
        if (lane == 0) {
            if (!XCP) bulk_g2s(sb + SM_XT, p.x + (size_t)16 * b * DM, 16 * 1152, bar_t);
            bulk_s2g(reinterpret_cast<unsigned char*>(p.s->y) + 96 * 18432 + b * 4608, sb + SM_Z2, 4608);
        }
        bar_arrive(12, 64);
    }
    if (warp == 19) {
        bar_sync(12, 64);
        asm volatile("barrier.cluster.wait.aligned;\n" ::: "memory");
        if (EXP & 4) { if (elect_one()) asm volatile("mbarrier.complete_tx.relaxed.cta.shared::cta.b64 [%0], %1;" :: "r"(bar_x), "r"(32768) : "memory"); }
        else if (EXP & 8) { if (elect_one()) { tma_4d(sb + SM_XC + odd * 16384, &tm_x, 8 * P, 2 * odd, bar_x); asm volatile("mbarrier.complete_tx.relaxed.cta.shared::cta.b64 [%0], %1;" :: "r"(bar_x), "r"(16384) : "memory"); } }
        else
        if (elect_one()) tma_4d_mc(sb + SM_XC + odd * 16384, &tm_x, 8 * P, 2 * odd, bar_x);
        __syncwarp();
    }
    const uint32_t kw = sb + SM_KW + wg * KW_B;
    const uint32_t tb = table_buf(sb, warp), t5 = sb + SM_WD + warp * 512;
    if (wg == 4) {
        if (!(g & 1) && t == (g >> 1)) *reinterpret_cast<volatile uint32_t*>(p.s->stat + 16 * b + 4 * (warp & 3) + t) = 0u;
        if (warp < 18) {
            unsigned char* const ud = reinterpret_cast<unsigned char*>(p.s->uT) + (size_t)(8 * (warp & 1) + 2 * (g >> 1)) * 16384 + b * 128 + (g & 1) * 32 + t * 8;
#pragma unroll
            for (int k = 0; k < 4; k++) *reinterpret_cast<volatile unsigned long long*>(ud + (k >> 1) * 16384 + (k & 1) * 64) = 0ull;
        }
        if (warp == 17) conv_constants(sb + SM_LC, lane);
    }
    if (t128 < 2 * UPAD) sts128(sb + SM_U + wg * USLOT_B + (t128 & 1) * ULO_B + (t128 >> 1) * 16, 0u, 0u, 0u, 0u);
    if (t128 >= 124) sts128(kw + (t128 & 1) * 16 + (t128 & 2) * (KW_PL / 2), 0u, 0u, 0u, 0u);
    uint32_t co, cn, cd;
    combine_setup(sb, warp, lane, kw, co, cn, cd);
    const uint4* usrc = wg < 4 ? reinterpret_cast<const uint4*>(p.s->stat) + tid
                               : reinterpret_cast<const uint4*>(p.s->uT) + (P >> 2) * 1024 + (t128 >> 1) * 8 + (P & 3) * 2 + (t128 & 1);
    uint32_t zero;
    {
        uint32_t uo = (uint32_t)(reinterpret_cast<const char*>(usrc) - reinterpret_cast<const char*>(p.s)), pk = (cn - co + 1024) | ((cd - kw) << 16);
        asm volatile("st.volatile.shared.v4.u32 [%4], {0, %1, %2, %3};\nld.volatile.shared.v4.u32 {%0, %1, %2, %3}, [%4];\n" : "=r"(zero), "+r"(co), "+r"(pk), "+r"(uo) : "r"(tb + lane * 16) : "memory");
        cn = co + (pk & 0xffffu) - 1024; cd = kw + (pk >> 16);
        usrc = reinterpret_cast<const uint4*>(reinterpret_cast<const char*>(p.s) + uo);
    }
    const float dt = exp_bf(__uint_as_float(__byte_perm(ldt, zero, 0x1044)));
    const uint32_t ep = __reduce_or_sync(0xffffffffu, epl | zero);
    auto stats = [&]() {
        const int wq = warp & 3;
        const uint32_t xa = sb + SM_XT + (4 * wq + (g >> 1)) * 1152 + (g & 1) * 576 + t * 16;
        const bool own = !(g & 1) && t == (g >> 1);
        float d[4][4] = {};
        if (XCP) asm volatile("cp.async.wait_group 0;\n" ::: "memory"); else mbar_wait(bar_t);
        if ((HOLD == 2 || HOLD == 5) && lane == 0) mbar_arrive(bar_h + 8 * wq);
        STAMP(26);
        uint4 v[9];
#pragma unroll
        for (int c = 0; c < 9; c++) v[c] = lds128(xa + c * 64);
#pragma unroll
        for (int c = 0; c < 9; c++) {
            mma_bf16(d[2 * (c & 1)], v[c].x, 0x3f803f80u, v[c].y, 0x3f803f80u, v[c].x, v[c].y);
            mma_bf16(d[2 * (c & 1) + 1], v[c].z, 0x3f803f80u, v[c].w, 0x3f803f80u, v[c].z, v[c].w);
        }
        STAMP(27);
        float sm = (g & 1) ? (d[0][3] + d[1][3]) + (d[2][3] + d[3][3]) : (d[0][2] + d[1][2]) + (d[2][2] + d[3][2]);
        float sq = (g & 1) ? (d[0][1] + d[1][1]) + (d[2][1] + d[3][1]) : (d[0][0] + d[1][0]) + (d[2][0] + d[3][0]);
        sm += __shfl_xor_sync(0xffffffffu, sm, 4); sq += __shfl_xor_sync(0xffffffffu, sq, 4);
        if (HOLD == 1) bar_arrive(6 + wq, 160);
        if (HOLD >= 2 && HOLD != 4 && lane == 0) mbar_arrive(bar_h + 8 * wq);
        float mb, sd;
        ln_stats(sm, sq, mb, sd);
        if (own) p.s->stat[16 * b + 4 * wq + t] = (__float_as_uint(mb) >> 16) | (__float_as_uint(sd) & 0x7fff0000u) | (ep << 31);
        STAMPX(22);
        if (HOLD == 4 && lane == 0) mbar_arrive(bar_h + 8 * wq);
        if (own) stat_store(s_stat + (2 * wq + (t & 1) + 8 * (t >> 1)) * 8, mb, rcp_approx(sd), 0u);
        if (wq == 2) asm volatile("cp.async.bulk.wait_group 0;\n" ::: "memory");
        bar_sync(5, 128);
        STAMP(28);
        if (wq == 2) {
            if (lane < 8) p.s->key3[8 * b + lane] = ep & 1u;
            if (lane == 0) {
                uint32_t now;
                asm volatile("mov.u32 %0, %%clock;" : "=r"(now));
                sts64(s_cnt, now, ep);
                mbar_arrive(bar_s);
                bulk_g2s(sb + SM_XT + 16 * 1152, p.dsk, 1152, bar_v);
                bulk_g2s(sb + SM_XT + 17 * 1152, p.wr, 1152, bar_v);
            }
            __syncwarp();
        }
        WPOINT(1, wq == 3);
        if (wq < 2) {
            unsigned char* const ud = reinterpret_cast<unsigned char*>(p.s->uT) + (size_t)(8 * wq + 2 * (g >> 1)) * 16384 + b * 128 + (g & 1) * 32 + t * 8;
            const uint32_t utag = (ep % 7u + 1u) * 0x10001u;
            uint32_t U[2][4];
#pragma unroll
            for (int hf = 0; hf < 2; hf++) {
                const uint2 st = lds64(s_stat + (g + 8 * hf) * 8);
                const uint4 xu = lds128(sb + SM_XT + (TOK(g) + 2 * hf) * 1152 + warp * 64 + t * 16);
                const uint32_t X[4] = {xu.x, xu.y, xu.z, xu.w};
#pragma unroll
                for (int k = 0; k < 4; k++) {
                    const uint32_t u = ln_apply(X[k], STAT_M(st), STAT_H(st), STAT_L(st));
                    U[hf][k] = movm((pack_f16(bf_lo(u), bf_hi(u)) & 0xfff8fff8u) | utag);
                }
            }
#pragma unroll
            for (int k = 0; k < 4; k++) stg64(ud + (k >> 1) * 16384 + (k & 1) * 64, U[0][k], U[1][k]);
        }
    };
    STAMP(1);
    if (wg < 4) { STAMPX(16); }
    if (SORD == 0 && wg == 4) stats();
    KGen kg;
    kgen_setup(kg, __uint_as_float(__byte_perm(pl, zero, 0x1044)), __uint_as_float(__byte_perm(pa2, zero, 0x1044)), dt);
    kgen_rows(kg, tb, lane);
    STAMP(2);
    const int E = min(max(c_exponent(call_re, call_im, dt) - 243, -120), 120);
    kgen_chain(kg, pc, pi, dt * __uint_as_float((uint32_t)(128 - E) << 23));
    STAMP(3);
    kgen_cols(kg, tb, t5, lane);
    STAMP(4);
    if (SORD == 1 && wg == 4) stats();
    if (warp != 19) asm volatile("barrier.cluster.wait.aligned;\n" ::: "memory");
    if (wg < 4) { STAMPX(17); }
    if (HOLD == 1 && wg < 4) bar_sync(6 + (warp & 3), 160);
    if ((HOLD == 3 || HOLD == 4) && wg < 4) mbar_wait(bar_h + 8 * (warp & 3));
    if (HOLD == 2 || HOLD == 5) mbar_wait1(bar_h + 8 * (warp & 3));
    if (wg < 4) { STAMPX(19); }
    if (DEFER == 1 && wg == 4) bar_sync(14, NWRK);
    if (DEFER > 1 && wg == 4) bar_sync(15, NWRK);
    kgen_mma(kg, tb, t5, lane, bar_h + 8 * (warp & 3));
    if (wg < 4) { STAMPX(20); }
    if (DEFER == 3 && wg < 4) bar_arrive(15, NWRK);
    STAMP(5);
    if (SORD == 2 && wg == 4) stats();
    uint4 uv0, uv1;
    auto first_poll = [&](uint32_t dly) {
        mbar_wait(bar_s);
        const uint32_t t0 = lds32(s_cnt);
        uint32_t now;
        do { asm volatile("mov.u32 %0, %%clock;" : "=r"(now) :: "memory"); } while (now - t0 < dly);
        uv0 = ld_poll(usrc);
    };
    WPOINT(2, warp == 19);
    if (PEARLY == 3 && wg < 4) first_poll(SDLY);
    bar_sync(1 + wg, 128);
    if (PEARLY == 2 && wg < 4) first_poll(SDLY);
    if (wg < 4) { STAMPX(21); }
    kgen_combine(warp & 3, lane, co, cn, cd);
    STAMP(6);
    if (wg < 4) { STAMPX(18); }
    if (DEFER == 2 && wg < 4) bar_arrive(15, NWRK);
    WPOINT(3, warp == 19);
    if (PEARLY == 1 && wg < 4) first_poll(SDLY);
    {
        const int wq = warp & 3;
        Conv c;
        const uint32_t pln = sb + SM_PL + wg * PL_B;
        const int e = g - 2 * t + 7;
        c.kw = kw; c.wa = pin(kw + ((e >> 2) & 1) * KW_PL + (8 * wq + (e >> 3)) * 16 + (e & 3) * 4);
        c.ps = mov_v(pln + wq * PLW_B + ((lane >> 3) & 1) * PL_HALF + ((lane >> 4) * 8 + (lane & 7)) * 16); c.warp = warp;
        c.lc = sb + SM_LC; c.fs = (uint32_t)(127 + E) * 0x800080u; c.yp = (ep & 1u) * (NCTA * 18432u);
        c.d0 = ((uint64_t)(ULO_B >> 4) << 16) | ((uint64_t)(128 >> 4) << 32) | (uint64_t)(((sb + SM_U + wg * USLOT_B + UPAD * 16) & 0x3FFFF) >> 4);
        unsigned char* gy = reinterpret_cast<unsigned char*>(p.s->y) + ((size_t)(4 * wq) * DM + ch) * 64;
        auto hook = [&](auto gi) {
                     constexpr int G = decltype(gi)::value;
                     if (G == (wg_is4<decltype(gi)>() ? 2 : 5)) asm volatile("barrier.cluster.wait.aligned;\n" ::: "memory");
                     if (!wg_is4<decltype(gi)>() && (G == RG0 || G == RG1) && warp == HW && elect_one()) {
                         unsigned char* const sc = reinterpret_cast<unsigned char*>(p.s);
                         if (G == RG0) {
                             if (b < 96) bulk_s2g_nc(sc + offsetof(Scratch, part) + b * 12288, sb + SM_Z2, 12288);
                             bulk_s2g(sc + offsetof(Scratch, rows) + (127 - b) * 4608, sb + SM_Z2, 4608);
                         }
                         if (G == RG1) {
                             bulk_s2g_nc(sc + offsetof(Scratch, y) + (NCTA * 18432u - c.yp) + b * 13824, sb + SM_Z2, 6912);
                             bulk_s2g(sc + offsetof(Scratch, y) + (NCTA * 18432u - c.yp) + b * 13824 + 6912, sb + SM_Z2, 6912);
                         }
                     }
                     if (!wg_is4<decltype(gi)>() && PF1 && G >= PF1 && G < PF1 + 2 && (warp >> 1) == 2) weight_prefetch(p, 17 + 2 * (G - PF1) + (warp & 1), lane_v());
                     if (!wg_is4<decltype(gi)>()) WPOINT(6 + G, warp == (G >= 7 ? HW : WSP ? 4 * (G % 3) + 1 : 12 + (G & 3)));
                     if (!wg_is4<decltype(gi)>() && G == XG && warp == HW) {
                         asm volatile("cp.async.bulk.wait_group 0;\n" ::: "memory");
                         __syncwarp();
                         if (elect_one()) mbar_arrive(bar_v);
                     }
                 };
        if (!ONEBAR) bar_sync(1 + wg, 128);
        if (wg < 4) {
            asm volatile("barrier.cluster.arrive.relaxed.aligned;\n" ::: "memory");
            conv_run(c, pln + wq * 128, gy, hook, [&]() {
                STAMPX(23);
                mbar_wait(bar_x);
                STAMP(9);
                STAMPX(24);
                uint2 xc[4];
                uint32_t xw[4][2];
#pragma unroll
                for (int j = 0; j < 4; j++) xc[j] = lds64(sb + SM_XC + wg * 8192 + j * 2048 + t128 * 16 + odd * 8);
#pragma unroll
                for (int i = 0; i < 8; i++) {
                    const int k = i >> 1, h = i & 1;
                    xw[k][h] = prmt_v(k < 2 ? xc[2 * h].x : xc[2 * h].y, k < 2 ? xc[2 * h + 1].x : xc[2 * h + 1].y, (k & 1) ? 0x7632 : 0x5410);
                }
                const uint32_t ub = mov_v(sb + SM_U + UPAD * 16 + ((tid >> 1) & 1) * ULO_B + (tid >> 2) * 16 + (tid & 1) * 8), tag = ep << 31;
                int it = 0;
                if (!PEARLY) first_poll(SDLY);
                while (min(min((int)(uv0.x ^ tag), (int)(uv0.y ^ tag)), min((int)(uv0.z ^ tag), (int)(uv0.w ^ tag))) < 0x10000) {
                    if (++it > SPIN_LIMIT) TRAP();
                    uv0 = ld_poll(usrc);
                }
                STAMP(8);
                STAMPX(26);
                const float r0 = rcp_approx(fabsf(bf_hi(uv0.x))), r1 = rcp_approx(fabsf(bf_hi(uv0.y))), r2 = rcp_approx(fabsf(bf_hi(uv0.z))), r3 = rcp_approx(fabsf(bf_hi(uv0.w)));
                const uint32_t m[2] = {__byte_perm(uv0.x, uv0.y, 0x5410), __byte_perm(uv0.z, uv0.w, 0x5410)};
                const uint32_t rh[2] = {pack_bf16(r0, r1), pack_bf16(r2, r3)};
                const uint32_t rl[2] = {pack_bf16(r0 - bf_lo(rh[0]), r1 - bf_hi(rh[0])), pack_bf16(r2 - bf_lo(rh[1]), r3 - bf_hi(rh[1]))};
#pragma unroll
                for (int k = 0; k < 4; k++) {
                    const uint32_t u0 = ln_apply(xw[k][0], m[0], rh[0], rl[0]), u1 = ln_apply(xw[k][1], m[1], rh[1], rl[1]);
                    sts64(ub + k * USLOT_B, pack_f16(bf_lo(u0), bf_hi(u0)), pack_f16(bf_lo(u1), bf_hi(u1)));
                }
                STAMPX(29);
                fence_async();
                bar_sync(14, DEFER == 1 ? NWRK : 512);
                STAMP(7);
            });
        } else {
            auto stage = [&]() {
                const uint32_t tag = (ep % 7u + 1u) * 0x10001u;
                int it = 0;
                WPOINT(4, warp == 19);
                first_poll(UDLY);
                uv1 = ld_poll(usrc + 512);
                WPOINT(5, warp == 19);
                while (true) {
                    uv0.x ^= tag; uv0.y ^= tag; uv0.z ^= tag; uv0.w ^= tag; uv1.x ^= tag; uv1.y ^= tag; uv1.z ^= tag; uv1.w ^= tag;
                    if ((((uv0.x | uv0.y | uv0.z) | (uv0.w | uv1.x | uv1.y) | (uv1.z | uv1.w)) & 0x70007u) == 0) break;
                    if (++it > SPIN_LIMIT) TRAP();
                    uv0 = ld_poll(usrc); uv1 = ld_poll(usrc + 512);
                }
                STAMP(8);
                const uint32_t ub = sb + SM_U + UPAD * 16 + 4 * USLOT_B + (t128 & 1) * ULO_B + (t128 >> 1) * 16;
                sts128(ub, uv0.x, uv0.y, uv0.z, uv0.w);
                sts128(ub + 1024, uv1.x, uv1.y, uv1.z, uv1.w);
                fence_async();
                asm volatile("barrier.cluster.arrive.relaxed.aligned;\n" ::: "memory");
                bar_sync(5, 128);
                STAMP(7);
            };
            stage();
            if (odd) conv_inner(c, pln + wq * 128, gy, sb + SM_RX, hook);
            else conv_outer(c, pln + wq * 128, gy, sb + SM_RX, hook);
        }
        STAMP(10);
    }
    {
    const int lane = lane_v(), tid = 32 * warp + lane, g = lane >> 2, t = lane & 3;
    const uint32_t par = ~ep & 1u;
    if (CBAR) bar_sync(0, NWRK);
    STAMP(11);
    uint32_t H[2][4] = {}, U2[2][4] = {};
    auto publish = [&](bool hi, int slot) {
        uint4* rowp = reinterpret_cast<uint4*>(p.s->rows) + slot * 144 + warp * 4 + t;
        stg128(rowp, nzw(hi ? U2[1][0] : U2[0][0]), nzw(hi ? U2[1][1] : U2[0][1]), nzw(hi ? U2[1][2] : U2[0][2]), nzw(hi ? U2[1][3] : U2[0][3]));
        stg128(rowp + 72, nzw(hi ? H[1][0] : H[0][0]), nzw(hi ? H[1][1] : H[0][1]), nzw(hi ? H[1][2] : H[0][2]), nzw(hi ? H[1][3] : H[0][3]));
    };
#define KTOK(k) (int)(((~(k) >> 5) & 0x7f0u) | (((k) >> 1) & 15u))
#define KLATE(k) (((k) & 0x1e0u) < 0xe0u)
#define KSLOT(k, s) (KLATE(k) ? 2 * NCTA + (s) : (int)(((k) >> 8) & 0xffu))
    const uint4* const rsrc = reinterpret_cast<const uint4*>(p.s->rows) + 36 * odd;
    auto gather = [&](uint32_t mine) {
        int it = 0;
        uint32_t mn;
        do {
            mn = 1;
#pragma unroll 1
            for (int r = 0; r < 9; r++) {
                const uint32_t k = __shfl_sync(0xffffffffu, mine, r < 8 ? 4 * r : lane);
                const int row = r < 8 ? r : g, c = r < 8 ? lane : 32 + t;
                asm volatile("cp.async.cg.shared.global [%0], [%1], 16;\n" ::"r"(sb + SM_XS + row * XS_PITCH + c * 16), "l"(rsrc + KSLOT(k, row) * 144 + c) : "memory");
            }
            asm volatile("cp.async.wait_all;\n" ::: "memory");
#pragma unroll 1
            for (int r = 0; r < 9; r++) mn = min(mn, min4(lds128(sb + SM_XS + (r < 8 ? r * XS_PITCH + lane * 16 : g * XS_PITCH + (32 + t) * 16))));
            if (++it > SPIN_LIMIT) TRAP();
        } while (__any_sync(0xffffffffu, mn == 0));
    };
    auto late_rows = [&](auto role) {
        const uint32_t kk = lds32(s_key + (lane & 7) * 4), ep = lds32(s_cnt + 4);
        const bool own = KLATE(kk) && (KTOK(kk) >> 4) == b;
        uint32_t todo = __ballot_sync(0xffffffffu, own) & 0xffu;
        if (decltype(role)::value == 0 && todo) {
#pragma unroll
            for (int hf = 0; hf < 2; hf++) {
                const uint4 h = lds128(sb + SM_U + hf * 9216 + tid * 16);
                const uint2 st = lds64(s_stat + (g + 8 * hf) * 8);
                H[hf][0] = h.x; H[hf][1] = h.y; H[hf][2] = h.z; H[hf][3] = h.w;
#pragma unroll
                for (int k = 0; k < 4; k++) U2[hf][k] = ln_apply(H[hf][k], STAT_M(st), STAT_H(st), STAT_L(st));
            }
#pragma unroll 1
            while (todo) {
                const int s = __ffs(todo) - 1, tk = KTOK(__shfl_sync(0xffffffffu, kk, s));
                todo &= todo - 1;
                if ((tk & 13) == TOK(g)) publish(tk & 2, 2 * NCTA + s);
            }
            __threadfence();
        }
        bar_sync(0, NWRK);
        if (decltype(role)::value == 1) {
            if (lane < NSEL && own) *reinterpret_cast<volatile unsigned*>(p.s->flag + lane) = ep + 1u;
            int it = 0;
            while (__any_sync(0xffffffffu, KLATE(kk) && ld_acquire32(p.s->flag + (lane & 7)) != ep + 1u)) { if (++it > SPIN_LIMIT) TRAP(); }
            gather(__shfl_sync(0xffffffffu, kk, g));
        }
        bar_sync(0, NWRK);
    };
    if (warp < 18) {
        const unsigned char* ys = reinterpret_cast<const unsigned char*>(p.s->y) + (b < 96 ? (par ^ 1u) * (NCTA * 18432u) : 0u) +
                                  ((P * DM + 32 * warp + 8 * (g >> 1) + (g & 1)) * 64 + odd * 32 + t * 8);
        mbar_wait(bar_v);
        const uint32_t xa = sb + SM_XT + warp * 64 + t * 16;
        const uint4 x0 = lds128(xa + TOK(g) * 1152), x1 = lds128(xa + (TOK(g) + 2) * 1152), dk = lds128(xa + 16 * 1152);
        uint4 wr = make_uint4(0u, 0u, 0u, 0u);
        if (g == 0) wr = lds128(xa + 17 * 1152);
        const uint32_t Z[2][4] = {{x0.x, x0.y, x0.z, x0.w}, {x1.x, x1.y, x1.z, x1.w}}, D4[4] = {dk.x, dk.y, dk.z, dk.w};
#pragma unroll
        for (int hf = 0; hf < 2; hf++) {
            const uint2 st = lds64(s_stat + (g + 8 * hf) * 8);
#pragma unroll
            for (int k = 0; k < 4; k++) U2[hf][k] = hmul2_bf(ln_apply(Z[hf][k], STAT_M(st), STAT_H(st), STAT_L(st)), D4[k]);
        }
        const uint32_t la = pin(sb + SM_LNP + (g * 20 + warp) * 4 + (U2[0][3] & U2[1][3] & (warp >> 8)));
        if (YDLY > 1) delay(YDLY);
        int it = 0;
        float d[2][4];
        uint32_t mn;
        do {
            uint2 yv[4];
#pragma unroll
            for (int k = 0; k < 4; k++) yv[k] = ld_poll64(ys + k * 128);
            if (++it > SPIN_LIMIT) TRAP();
            mn = min(min(min(yv[0].x, yv[0].y), min(yv[1].x, yv[1].y)), min(min(yv[2].x, yv[2].y), min(yv[3].x, yv[3].y)));
#pragma unroll
            for (int k = 0; k < 4; k++) {
                H[0][k] = hadd2_bf(Z[0][k], hadd2_bf(movm(yv[k].x), U2[0][k]));
                H[1][k] = hadd2_bf(Z[1][k], hadd2_bf(movm(yv[k].y), U2[1][k]));
            }
            ln_partial(H, d);
        } while (__any_sync(0xffffffffu, mn == 0));
        STAMP(12);
        if (t == (g >> 1)) {
            stsf(la, (g & 1) ? d[0][3] : d[0][2]); stsf(la + 8 * 80, (g & 1) ? d[1][3] : d[1][2]);
            stsf(la + 16 * 80, (g & 1) ? d[0][1] : d[0][0]); stsf(la + 24 * 80, (g & 1) ? d[1][1] : d[1][0]);
        }
        bar_arrive(6, NWRK);
        STAMP(13);
        bar_sync(7, 608);
        STAMP(14);
#pragma unroll
        for (int hf = 0; hf < 2; hf++) {
            const uint2 st = lds64(s_stat + (g + 8 * hf) * 8);
#pragma unroll
            for (int k = 0; k < 4; k++) U2[hf][k] = ln_apply(H[hf][k], STAT_M(st), STAT_H(st), STAT_L(st));
        }
        {
            float cs[4] = {0.f, 0.f, 0.f, 0.f};
            mma_bf16(cs, U2[0][0], U2[1][0], U2[0][1], U2[1][1], wr.x, wr.y);
            mma_bf16(cs, U2[0][2], U2[1][2], U2[0][3], U2[1][3], wr.z, wr.w);
            if (t == 0) { stsf(la + 32 * 80, cs[0]); stsf(la + 40 * 80, cs[2]); }
            bar_arrive(8, 608);
        }
        bar_sync(9, 608);
        {
            const uint2 best = lds64(s_rank);
            if ((best.x & 26u) == 2 * TOK(g)) publish(best.x & 4u, 255 - 2 * b);
            if ((best.y & 26u) == 2 * TOK(g)) publish(best.y & 4u, 254 - 2 * b);
        }
#pragma unroll
        for (int hf = 0; hf < 2; hf++) {
            sts128(sb + SM_OUT + (TOK(g) + 2 * hf) * (DM * 2) + warp * 64 + t * 16,
                   hadd2_bf(H[hf][0], U2[hf][0]), hadd2_bf(H[hf][1], U2[hf][1]), hadd2_bf(H[hf][2], U2[hf][2]), hadd2_bf(H[hf][3], U2[hf][3]));
            sts128(sb + SM_U + hf * 9216 + tid * 16, H[hf][0], H[hf][1], H[hf][2], H[hf][3]);
        }
        STAMP(15);
        fence_async();
        const int mi = lane >> 3, rr = lane & 7;
        if (warp < 9) {
            uint32_t W[18][4];
            mbar_wait(bar_w);
            const uint32_t aad = sb + SM_WG + (mi & 1) * SM_WU + (rr + 8 * (mi >> 1)) * W_PITCH + warp * 16;
#pragma unroll
            for (int k = 0; k < 18; k++) ldsm_x4_t(W[k][0], W[k][1], W[k][2], W[k][3], aad + k * 16 * W_PITCH);
            const uint32_t bad = pin(sb + SM_XS + rr * XS_PITCH + mi * 16);
            STAMP2(17);
            if (bar_or(11, NWRK, false)) {
                late_rows(IC<0>());
#pragma unroll
                for (int k = 0; k < 18; k++) ldsm_x4_t(W[k][0], W[k][1], W[k][2], W[k][3], aad + k * 16 * W_PITCH);
            }
            STAMP2(19);
            float c4[2][4] = {};
#pragma unroll
            for (int k = 0; k < 18; k += 2) {
                uint32_t b0, b1, b2, b3;
                ldsm_x4(b0, b1, b2, b3, bad + k * 32);
                mma_bf16(c4[0], W[k][0], W[k][1], W[k][2], W[k][3], b0, b1);
                mma_bf16(c4[1], W[k + 1][0], W[k + 1][1], W[k + 1][2], W[k + 1][3], b2, b3);
            }
            const uint32_t ex = sb + SM_EX + tid * 16;
            const float e0 = c4[0][0] + c4[1][0], e1 = c4[0][1] + c4[1][1], e2 = c4[0][2] + c4[1][2], e3 = c4[0][3] + c4[1][3];
            asm volatile("st.async.shared::cluster.mbarrier::complete_tx::bytes.v4.f32 [%0], {%1,%2,%3,%4}, [%5];\n"
                         ::"r"(ex ^ 0x1000000u), "f"(e0), "f"(e1), "f"(e2), "f"(e3), "r"(bar_g ^ 0x1000000u) : "memory");
            STAMP2(20);
            mbar_wait(bar_g);
            const uint4 o = lds128(ex);
            const uint32_t G = pack_bf16(e0 + __uint_as_float(o.x), e1 + __uint_as_float(o.y)), U = pack_bf16(e2 + __uint_as_float(o.z), e3 + __uint_as_float(o.w));
            sts32(sb + SM_GU + tid * 4, hmul2_bf(pack_bf16(bf_lo(G) * sigmoid_f(bf_lo(G)), bf_hi(G) * sigmoid_f(bf_hi(G))), U));
            bar_arrive(13, NWRK);
        } else {
            uint32_t W[2][18];
            mbar_wait(bar_d);
            const uint32_t base = sb + SM_WD + (4 * (warp - 9) + (mi & 1)) * 16 + rr * WD_PITCH;
#pragma unroll
            for (int j = 0; j < 2; j++) {
#pragma unroll
                for (int k = 0; k < 4; k++) ldsm_x4_t(W[j][4 * k], W[j][4 * k + 1], W[j][4 * k + 2], W[j][4 * k + 3], base + j * 32 + (k * 16 + 8 * (mi >> 1)) * WD_PITCH);
                ldsm_x2_t(W[j][16], W[j][17], base + j * 32 + 64 * WD_PITCH);
            }
            const uint32_t po = pin((((8 * (18 * odd + 2 * (warp - 9)) + g) * 64 + P) * 16 + t * 4) * 4);
            STAMP2(17);
            if (bar_or(11, NWRK, false)) late_rows(IC<0>());
            bar_sync(13, NWRK);
            STAMP2(21);
            uint32_t gb[9];
            ldsm_x4_t(gb[0], gb[1], gb[2], gb[3], sb + SM_GU + lane * 16);
            ldsm_x4_t(gb[4], gb[5], gb[6], gb[7], sb + SM_GU + 512 + lane * 16);
            ldsm_x1_t(gb[8], sb + SM_GU + 1024 + lane * 16);
            float c4[2][4] = {}, d4[2][4] = {};
#pragma unroll
            for (int k = 0; k < 4; k += 2)
#pragma unroll
                for (int j = 0; j < 2; j++) {
                    mma_bf16(c4[j], W[j][4 * k], W[j][4 * k + 1], W[j][4 * k + 2], W[j][4 * k + 3], gb[2 * k], gb[2 * k + 1]);
                    mma_bf16(d4[j], W[j][4 * k + 4], W[j][4 * k + 5], W[j][4 * k + 6], W[j][4 * k + 7], gb[2 * k + 2], gb[2 * k + 3]);
                }
#pragma unroll
            for (int j = 0; j < 2; j++) mma_bf16_k8(c4[j], W[j][16], W[j][17], gb[8]);
#pragma unroll
            for (int j = 0; j < 2; j++)
                stg128(reinterpret_cast<unsigned char*>(p.s->part) + po + j * 32768, __float_as_uint(c4[j][0] + d4[j][0]) | 1u, __float_as_uint(c4[j][1] + d4[j][1]) | 1u,
                       __float_as_uint(c4[j][2] + d4[j][2]) | 1u, __float_as_uint(c4[j][3] + d4[j][3]) | 1u);
        }
        STAMP2(22);
    } else if (warp == 18) {
        bar_sync(6, NWRK);
        {
            float mb, rc;
            ln_finish(sum18(sb + SM_LNP + lane * 80), lane, mb, rc);
            if (lane < 16) stat_store(s_stat + lane * 8, mb, rc, 0u);
        }
        bar_arrive(7, 608);
        const uint32_t klo = pin((uint32_t)(127 - b) << 9 | (uint32_t)(15 - ROWTOK(lane & 15)) << 1 | par), ra = pin(sb + SM_LNP + (32 + (lane & 15)) * 80);
        uint4* const kdst = reinterpret_cast<uint4*>(p.s->key3) + pin(2 * b + (lane & 1));
        bar_sync(8, 608);
        uint32_t t0;
        {
            const uint32_t bits = __float_as_uint(rbf(sum18(ra)));
            const uint32_t me = ((bits ^ ((uint32_t)((int)bits >> 31) | 0x80000000u)) & 0xffff0000u) | klo;
            const uint32_t k0 = __reduce_max_sync(0xffffffffu, me), k1 = __reduce_max_sync(0xffffffffu, me == k0 ? 0u : me);
            const uint32_t k2 = __reduce_max_sync(0xffffffffu, me >= k1 ? 0u : me);
            if (lane < 2) stg128(kdst, k0 ^ 0x11eu, k1 ^ 0xfeu, k2 ^ 0xdeu, par);
            asm volatile("mov.u32 %0, %%clock;" : "=r"(t0) :: "memory");
            STAMPW(23);
            if (lane == 0) sts64(s_rank, ~k0, ~k1);
            bar_arrive(9, 608);
            sts32(s_k16 + (lane & 15) * 4, me);
            __syncwarp();
            const uint4 v = lds128(s_k16 + (lane & 16) * 2), w = lds128(s_k16 + (lane & 16) * 2 + 16);
            int rank = ((v.x > me) + (v.y > me)) + ((v.z > me) + (v.w > me)) + (((w.x > me) + (w.y > me)) + ((w.z > me) + (w.w > me)));
            rank += __shfl_xor_sync(0xffffffffu, rank, 16);
            if (lane < 16 && rank < 8) p.s->key[8 * b + rank] = (me ^ 0x1eu) | ((8 - rank) << 5);
        }
        const uint4* const ksrc = reinterpret_cast<const uint4*>(p.s->key3) + pin(2 * lane);
        const unsigned char* const rl = reinterpret_cast<const unsigned char*>(rsrc) + pin(lane * 16);
        uint4 kq[4];
        uint32_t u[4], mine = 0, m;
        int it = 0;
        { uint32_t now; do { asm volatile("mov.u32 %0, %%clock;" : "=r"(now) :: "memory"); } while (now - t0 < KDLY); }
        do {
#pragma unroll
            for (int i = 0; i < 4; i++) kq[i] = ld_poll(ksrc + 64 * i);
            if (++it > SPIN_LIMIT) TRAP();
            uint32_t S[2][4];
#pragma unroll
            for (int i = 0; i < 2; i++) {
                const uint4 &c = kq[2 * i], &d = kq[2 * i + 1];
                const uint32_t m1 = min(c.x, d.x), m2 = max(c.y, d.y);
                S[i][0] = max(c.x, d.x); S[i][1] = max(m1, m2); S[i][2] = min(m1, m2); S[i][3] = min(c.y, d.y);
            }
            const uint32_t a0 = max(S[0][0], S[1][3]), a1 = max(S[0][1], S[1][2]), a2 = max(S[0][2], S[1][1]), a3 = max(S[0][3], S[1][0]);
            const uint32_t b0 = max(a0, a2), b2 = min(a0, a2), b1 = max(a1, a3), b3 = min(a1, a3);
            u[0] = max(b0, b1); u[1] = min(b0, b1); u[2] = max(b2, b3); u[3] = min(b2, b3);
        } while (__any_sync(0xffffffffu, and3(or3(or3(xor_or(kq[0].x, kq[0].y, par), xor_or(kq[0].z, kq[1].x, par), xor_or(kq[1].y, kq[1].z, par)),
                                                  xor_or(kq[2].x, kq[2].y, par), xor_or(kq[2].z, kq[3].x, par)) | xor_or(kq[3].y, kq[3].z, par), 1u, 1u)));
        STAMPW(16);
        uint4 v[9];
#pragma unroll
        for (int r = 0; r < 8; r++) {
            m = __reduce_max_sync(0xffffffffu, u[0]);
            if (u[0] == m) { u[0] = u[1]; u[1] = u[2]; u[2] = u[3]; u[3] = 0; }
            if (g == r) mine = m;
            v[r] = ld_poll(rl + (size_t)((m >> 8) & 0xffu) * 2304u);
        }
        v[8] = ld_poll(reinterpret_cast<const unsigned char*>(rsrc) + (((mine >> 8) & 0xffu) * 2304u + (32 + t) * 16));
        bool again = __any_sync(0xffffffffu, u[0] == 0 || max(max(kq[0].z, kq[1].z), max(kq[2].z, kq[3].z)) > m);
        if (again) {
#pragma unroll 1
            for (int i = 0; i < 8; i++) {
                uint4 k;
                do { k = ld_poll(reinterpret_cast<const uint4*>(p.s->key) + 32 * i + lane); if (++it > SPIN_LIMIT) TRAP(); } while (((k.x ^ par) | (k.y ^ par) | (k.z ^ par) | (k.w ^ par)) & 1u);
                sts128(sb + SM_KEYS + (32 * i + lane) * 16, k.x, k.y, k.z, k.w);
            }
            m = 0xffffffffu;
#pragma unroll 1
            for (int r = 0; r < 8; r++) {
                uint32_t c = 0;
#pragma unroll 2
                for (int i = 0; i < 8; i++) {
                    const uint4 k = lds128(sb + SM_KEYS + (32 * i + lane) * 16);
                    c = max(max(c, k.x < m ? k.x : 0u), max(k.y < m ? k.y : 0u, max(k.z < m ? k.z : 0u, k.w < m ? k.w : 0u)));
                }
                m = __reduce_max_sync(0xffffffffu, c);
                if (g == r) mine = m;
            }
        }
        if (t == 0) sts32(s_key + g * 4, mine);
        uint32_t mn = 1;
#pragma unroll
        for (int r = 0; r < 9; r++) {
            sts128(sb + SM_XS + (r < 8 ? r * XS_PITCH + lane * 16 : g * XS_PITCH + (32 + t) * 16), v[r].x, v[r].y, v[r].z, v[r].w);
            mn = min(mn, min4(v[r]));
        }
        if ((again || __any_sync(0xffffffffu, mn == 0)) && !__any_sync(0xffffffffu, KLATE(mine))) gather(mine);
        STAMPW(18);
        if (bar_or(11, NWRK, KLATE(mine))) late_rows(IC<1>());
    } else {
        bar_sync(6, NWRK);
        WPOINT(16, true);
        if (wsched(18) > wsched(17)) delay(WDLY);
        WPOINT(17, true);
        if (wsched(19) > wsched(18)) delay(WDLY);
        WPOINT(18, true);
        if (bar_or(11, NWRK, false)) late_rows(IC<2>());
        const int tk = KTOK(lds32(s_key + (lane & 7) * 4));
        const uint32_t sel = __reduce_or_sync(0xffffffffu, (tk >> 4) == b ? 1u << (tk & 15) : 0u);
        if (ODLY) delay(ODLY);
        if (!(EXP & 1)) if (sel ? lane < 16 && !((sel >> lane) & 1u) : lane == 0) bulk_s2g(p.out + (size_t)(16 * b + lane) * DM, sb + SM_OUT + lane * (DM * 2), sel ? DM * 2 : 16 * DM * 2);
        __syncwarp();
    }
    if (warp == 8 || warp >= 18) {
        const int grp = 3 * b + (warp == 8 ? 0 : warp - 17), fsl = 2 * t + ((lane >> 3) & 1), fc = 16 * (grp >> 3) + (grp & 7) + 8 * (lane >> 4);
        const uint32_t fk = lds32(s_key + fsl * 4);
        float hv = 0.f, u2 = 0.f;
        int it = 0;
        if (b < 96) {
            const uint32_t* const fsrc = p.s->rows + KSLOT(fk, fsl) * DM + (fc >> 1);
            uint32_t hw, uw;
            do { hw = ld_poll32(fsrc + 288); uw = ld_poll32(fsrc); if (++it > SPIN_LIMIT) TRAP(); } while (!hw || !uw);
            hv = (fc & 1) ? bf_hi(hw) : bf_lo(hw); u2 = (fc & 1) ? bf_hi(uw) : bf_lo(uw);
        }
        const float rs = rbf(sigmoid_f(__uint_as_float((fk ^ ((uint32_t)((int)~fk >> 31) | 0x80000000u)) & 0xffff0000u)));
        const uint32_t dof = pin(KTOK(fk) * DM + fc), so = pin(grp * 256 + lane);
        if (warp > 17) bar_sync(13, NWRK);
        if (b < 96) {
            delay(warp > 17 ? FDLY : FDLY2);
            const uint4* src = reinterpret_cast<const uint4*>(p.s->part) + so;
            float s0, s1, s2, s3;
            uint32_t ok;
            do {
                uint4 a[8];
#pragma unroll
                for (int i = 0; i < 8; i++) a[i] = ld_poll(src + 32 * i);
                if (++it > SPIN_LIMIT) TRAP();
#define A4(i) and3(and3(a[i].x, a[i].y, a[i].z), and3(a[i].w, a[i + 1].x, a[i + 1].y), a[i + 1].z & a[i + 1].w)
#define S8(f) (((__uint_as_float(a[0].f) + __uint_as_float(a[1].f)) + (__uint_as_float(a[2].f) + __uint_as_float(a[3].f))) + \
               ((__uint_as_float(a[4].f) + __uint_as_float(a[5].f)) + (__uint_as_float(a[6].f) + __uint_as_float(a[7].f))))
                ok = and3(A4(0), A4(2), and3(A4(4), A4(6), 1u));
                s0 = S8(x); s1 = S8(y); s2 = S8(z); s3 = S8(w);
                asm volatile("" : "+f"(s0), "+f"(s1), "+f"(s2), "+f"(s3));
#undef A4
#undef S8
            } while (__any_sync(0xffffffffu, !ok));
            STAMP2(24);
            const bool up = lane & 16, od = lane & 8;
            const float r0 = (up ? s2 : s0) + __shfl_xor_sync(0xffffffffu, up ? s0 : s2, 16), r1 = (up ? s3 : s1) + __shfl_xor_sync(0xffffffffu, up ? s1 : s3, 16);
            float y = (od ? r1 : r0) + __shfl_xor_sync(0xffffffffu, od ? r0 : r1, 8);
            y += __shfl_xor_sync(0xffffffffu, y, 4);
            p.out[dof] = __float2bfloat16_rn(hv + rbf(u2 + rbf(rbf(y) * rs)));
        }
    }
    if (warp == 19) asm volatile("cp.async.bulk.wait_group.read 0;\n" ::: "memory");
    if (b == 0 && tid < 8) *reinterpret_cast<volatile unsigned*>(p.s->hint + tid * 32 + 1) = lds32(s_cnt + 4) + 1u;
    STAMP(25);
    }
}

typedef CUresult (*PFN_tmEncode)(CUtensorMap*, CUtensorMapDataType, cuuint32_t, void*, const cuuint64_t*, const cuuint64_t*, const cuuint32_t*,
                                 const cuuint32_t*, CUtensorMapInterleave, CUtensorMapSwizzle, CUtensorMapL2promotion, CUtensorMapFloatOOBfill);

extern "C" void kernel_launch(void* const* d_in, const int* in_sizes, int n_in, void* d_out, int out_size) {
    Params p;
    p.x = (const bf16*)d_in[0];
    p.lar = (const bf16*)d_in[1];
    p.aim = (const bf16*)d_in[2];
    p.cre = (const bf16*)d_in[3];
    p.cim = (const bf16*)d_in[4];
    p.ldt = (const bf16*)d_in[5];
    p.dsk = (const bf16*)d_in[6];
    p.wr = (const bf16*)d_in[8];
    p.wg = (const bf16*)d_in[9];
    p.wu = (const bf16*)d_in[10];
    p.wd = (const bf16*)d_in[11];
    p.out = (bf16*)d_out;
    static PFN_tmEncode enc = nullptr;
    static void* scratch = nullptr;
    if (!enc) {
        cudaFuncSetAttribute(fused_kernel, cudaFuncAttributeMaxDynamicSharedMemorySize, SMEM_TOTAL);
        void* fn = nullptr;
        cudaDriverEntryPointQueryResult qr;
        cudaGetDriverEntryPoint("cuTensorMapEncodeTiled", &fn, cudaEnableDefault, &qr);
        enc = (PFN_tmEncode)fn;
        cudaGetSymbolAddress(&scratch, g_scratch);
    }
    p.s = (Scratch*)scratch;
    CUtensorMap tm_g, tm_u, tm_d, tm_x;
    const cuuint64_t dims[2] = {FF, DM}, strides[1] = {FF * 2};
    const cuuint32_t box[2] = {72, 48}, es[2] = {1, 1};
    enc(&tm_g, CU_TENSOR_MAP_DATA_TYPE_BFLOAT16, 2, d_in[9], dims, strides, box, es, CU_TENSOR_MAP_INTERLEAVE_NONE, CU_TENSOR_MAP_SWIZZLE_NONE,
        CU_TENSOR_MAP_L2_PROMOTION_NONE, CU_TENSOR_MAP_FLOAT_OOB_FILL_NONE);
    enc(&tm_u, CU_TENSOR_MAP_DATA_TYPE_BFLOAT16, 2, d_in[10], dims, strides, box, es, CU_TENSOR_MAP_INTERLEAVE_NONE, CU_TENSOR_MAP_SWIZZLE_NONE,
        CU_TENSOR_MAP_L2_PROMOTION_NONE, CU_TENSOR_MAP_FLOAT_OOB_FILL_NONE);
    const cuuint64_t ddims[2] = {DM / 2, FF}, dstrides[1] = {DM * 2};
    const cuuint32_t dbox[2] = {WD_PITCH / 4, 8};
    enc(&tm_d, CU_TENSOR_MAP_DATA_TYPE_UINT32, 2, d_in[11], ddims, dstrides, dbox, es, CU_TENSOR_MAP_INTERLEAVE_NONE, CU_TENSOR_MAP_SWIZZLE_NONE,
        CU_TENSOR_MAP_L2_PROMOTION_NONE, CU_TENSOR_MAP_FLOAT_OOB_FILL_NONE);
    const cuuint64_t xdims[4] = {DM, 128, 4, 4}, xstrides[3] = {DM * 8, DM * 2, DM * 1024};
    const cuuint32_t xbox[4] = {8, 128, 4, 2}, xes[4] = {1, 1, 1, 1};
    enc(&tm_x, CU_TENSOR_MAP_DATA_TYPE_BFLOAT16, 4, d_in[0], xdims, xstrides, xbox, xes, CU_TENSOR_MAP_INTERLEAVE_NONE, CU_TENSOR_MAP_SWIZZLE_NONE,
        CU_TENSOR_MAP_L2_PROMOTION_NONE, CU_TENSOR_MAP_FLOAT_OOB_FILL_NONE);
    fused_kernel<<<NCTA, NTHR, SMEM_TOTAL>>>(p, tm_g, tm_u, tm_d, tm_x);
}
```

```cpp
#include <cuda_runtime.h>
#include <cuda.h>
#include <cuda_fp16.h>
#include <cuda_bf16.h>
#include <stdint.h>

#define LSEQ 2048
#define DM 576
#define NST 128
#define FF 4608
#define NSEL 8
#define NCTA 128
#define NTHR 640
#define NWRK 640

typedef __nv_bfloat16 bf16;

#define SM_WG 0
#define SM_WU 41472
#define SM_XC (82944 - 32768)
#define SM_WD 82944
#define W_PITCH 144
#define WD_PITCH 592
#define SM_Z2 (SM_WD + 10240)
#define SM_XT (SM_PL - 18 * 1152)
#define SM_PL (SM_WD + 46080)
#define PL_HALF 1344
#define PLW_B 2624
#define PL_B (4 * PLW_B)
#define SM_U (SM_PL + 5 * PL_B)
#define UPAD 20
#define ULO_B ((UPAD + 128) * 16)
#define USLOT_B (2 * ULO_B)
#define SM_KW (SM_U + 5 * USLOT_B)
#define KW_B 3712
#define KW_PL 1216
#define KW_P 2400
#define KW_H 3440
#define SM_MISC (SM_KW + 5 * KW_B)
#define SM_LC (SM_MISC + 384)
#define SM_LNP (SM_LC + 768)
#define SM_RX (SM_LNP + 3840)
#define SMEM_TOTAL (SM_RX + 3088)
#define TBW PLW_B
#define SM_OUT SM_PL
#define SM_XS (SM_PL + 18432)
#define XS_PITCH 592
#define SM_GU (SM_PL + 23296)
#define SM_EX (SM_PL + 24576)
#define SM_KEYS SM_KW

struct __align__(128) Scratch {
    unsigned hint[8 * 32];
    unsigned flag[32];
    uint32_t key3[NCTA * 8];
    uint32_t key[NCTA * 8];
    uint32_t stat[LSEQ];
    uint32_t uT[64 * (LSEQ / 2)];
    uint32_t y[(NCTA + 96) * DM * 8];
    uint32_t part[288 * 64 * 16];
    uint32_t rows[(2 * NCTA + NSEL) * DM];
};
__device__ Scratch g_scratch;
#define STAMP(i)
#define STAMPX(i)
#define STAMPY(i)

__device__ __forceinline__ float rbf(float x) {
    uint32_t r;
    asm("cvt.rn.bf16x2.f32 %0, %1, %2;\n" : "=r"(r) : "f"(x), "f"(0.f));
    return __uint_as_float(r);
}
__device__ __forceinline__ uint32_t pack_bf16(float lo, float hi) {
    uint32_t r;
    asm("cvt.rn.bf16x2.f32 %0, %1, %2;\n" : "=r"(r) : "f"(hi), "f"(lo));
    return r;
}
__device__ __forceinline__ uint32_t pack_f16(float lo, float hi) {
    uint32_t r;
    asm("cvt.rn.f16x2.f32 %0, %1, %2;\n" : "=r"(r) : "f"(hi), "f"(lo));
    return r;
}
__device__ __forceinline__ uint32_t pack_f16_rz(float lo, float hi) {
    uint32_t r;
    asm("cvt.rz.f16x2.f32 %0, %1, %2;\n" : "=r"(r) : "f"(hi), "f"(lo));
    return r;
}
__device__ __forceinline__ float bf_lo(uint32_t w) { return __uint_as_float(w << 16); }
__device__ __forceinline__ float bf_hi(uint32_t w) { return __uint_as_float(w & 0xffff0000u); }
__device__ __forceinline__ uint32_t hadd2_bf(uint32_t a, uint32_t b) {
    __nv_bfloat162 r = __hadd2_rn(*reinterpret_cast<__nv_bfloat162*>(&a), *reinterpret_cast<__nv_bfloat162*>(&b));
    return *reinterpret_cast<uint32_t*>(&r);
}
__device__ __forceinline__ uint32_t hsub2_bf(uint32_t a, uint32_t b) {
    __nv_bfloat162 r = __hsub2_rn(*reinterpret_cast<__nv_bfloat162*>(&a), *reinterpret_cast<__nv_bfloat162*>(&b));
    return *reinterpret_cast<uint32_t*>(&r);
}
__device__ __forceinline__ uint32_t hmul2_bf(uint32_t a, uint32_t b) {
    __nv_bfloat162 r = __hmul2_rn(*reinterpret_cast<__nv_bfloat162*>(&a), *reinterpret_cast<__nv_bfloat162*>(&b));
    return *reinterpret_cast<uint32_t*>(&r);
}
__device__ __forceinline__ uint32_t hfma2_bf(uint32_t a, uint32_t b, uint32_t c) { uint32_t r; asm("fma.rn.bf16x2 %0, %1, %2, %3;\n" : "=r"(r) : "r"(a), "r"(b), "r"(c)); return r; }
__device__ __forceinline__ uint32_t hmul2(uint32_t a, uint32_t b) { uint32_t r; asm("mul.rn.f16x2 %0, %1, %2;\n" : "=r"(r) : "r"(a), "r"(b)); return r; }
__device__ __forceinline__ uint32_t hadd2(uint32_t a, uint32_t b) { uint32_t r; asm("add.rn.f16x2 %0, %1, %2;\n" : "=r"(r) : "r"(a), "r"(b)); return r; }
__device__ __forceinline__ uint32_t hfma2(uint32_t a, uint32_t b, uint32_t c) { uint32_t r; asm("fma.rn.f16x2 %0, %1, %2, %3;\n" : "=r"(r) : "r"(a), "r"(b), "r"(c)); return r; }
__device__ __forceinline__ uint32_t hfms2(uint32_t a, uint32_t b, uint32_t c) {
    uint32_t r;
    asm("{\n.reg .b32 n;\nneg.f16x2 n, %2;\nfma.rn.f16x2 %0, %1, n, %3;\n}\n" : "=r"(r) : "r"(a), "r"(b), "r"(c));
    return r;
}
__device__ __forceinline__ uint32_t nzw(uint32_t w) { return max(w, 1u); }
__device__ __forceinline__ uint32_t nzf(float f) { const uint32_t w = __float_as_uint(f); return w ? w : 0x80000000u; }
__device__ __forceinline__ uint32_t smem_u32(const void* p) { return (uint32_t)__cvta_generic_to_shared(p); }
__device__ __forceinline__ uint32_t lds32(uint32_t addr) {
    uint32_t v;
    asm volatile("ld.shared.u32 %0, [%1];\n" : "=r"(v) : "r"(addr) : "memory");
    return v;
}
__device__ __forceinline__ uint32_t lds16(uint32_t addr) {
    unsigned short v;
    asm volatile("ld.shared.u16 %0, [%1];\n" : "=h"(v) : "r"(addr) : "memory");
    return v;
}
__device__ __forceinline__ uint2 lds64(uint32_t addr) {
    uint2 v;
    asm volatile("ld.shared.v2.u32 {%0,%1}, [%2];\n" : "=r"(v.x), "=r"(v.y) : "r"(addr) : "memory");
    return v;
}
__device__ __forceinline__ uint4 lds128(uint32_t addr) {
    uint4 v;
    asm volatile("ld.shared.v4.u32 {%0,%1,%2,%3}, [%4];\n" : "=r"(v.x), "=r"(v.y), "=r"(v.z), "=r"(v.w) : "r"(addr) : "memory");
    return v;
}
__device__ __forceinline__ float ldsf(uint32_t addr) { return __uint_as_float(lds32(addr)); }
__device__ __forceinline__ void sts32(uint32_t addr, uint32_t v) { asm volatile("st.shared.u32 [%0], %1;\n" ::"r"(addr), "r"(v) : "memory"); }
__device__ __forceinline__ void sts16(uint32_t addr, uint32_t v) { asm volatile("st.shared.u16 [%0], %1;\n" ::"r"(addr), "h"((unsigned short)v) : "memory"); }
__device__ __forceinline__ void stsf(uint32_t addr, float v) { sts32(addr, __float_as_uint(v)); }
__device__ __forceinline__ void sts64(uint32_t addr, uint32_t a, uint32_t b) { asm volatile("st.shared.v2.u32 [%0], {%1,%2};\n" ::"r"(addr), "r"(a), "r"(b) : "memory"); }
__device__ __forceinline__ void sts64f(uint32_t addr, float a, float b) { sts64(addr, __float_as_uint(a), __float_as_uint(b)); }
__device__ __forceinline__ void sts128(uint32_t addr, uint32_t a, uint32_t b, uint32_t c, uint32_t d) {
    asm volatile("st.shared.v4.u32 [%0], {%1,%2,%3,%4};\n" ::"r"(addr), "r"(a), "r"(b), "r"(c), "r"(d) : "memory");
}
__device__ __forceinline__ void sts128f(uint32_t addr, const float (&v)[4]) {
    sts128(addr, __float_as_uint(v[0]), __float_as_uint(v[1]), __float_as_uint(v[2]), __float_as_uint(v[3]));
}
__device__ __forceinline__ void ldsm_x4(uint32_t& r0, uint32_t& r1, uint32_t& r2, uint32_t& r3, uint32_t addr) {
    asm volatile("ldmatrix.sync.aligned.m8n8.x4.shared.b16 {%0,%1,%2,%3}, [%4];\n"
                 : "=r"(r0), "=r"(r1), "=r"(r2), "=r"(r3) : "r"(addr) : "memory");
}
__device__ __forceinline__ void ldsm_x4_t(uint32_t& r0, uint32_t& r1, uint32_t& r2, uint32_t& r3, uint32_t addr) {
    asm volatile("ldmatrix.sync.aligned.m8n8.x4.trans.shared.b16 {%0,%1,%2,%3}, [%4];\n"
                 : "=r"(r0), "=r"(r1), "=r"(r2), "=r"(r3) : "r"(addr) : "memory");
}
__device__ __forceinline__ void ldsm_x2_t(uint32_t& r0, uint32_t& r1, uint32_t addr) {
    asm volatile("ldmatrix.sync.aligned.m8n8.x2.trans.shared.b16 {%0,%1}, [%2];\n" : "=r"(r0), "=r"(r1) : "r"(addr) : "memory");
}
__device__ __forceinline__ void ldsm_x1_t(uint32_t& r0, uint32_t addr) {
    asm volatile("ldmatrix.sync.aligned.m8n8.x1.trans.shared.b16 {%0}, [%1];\n" : "=r"(r0) : "r"(addr) : "memory");
}
__device__ __forceinline__ void stsm_x4(uint32_t addr, uint32_t r0, uint32_t r1, uint32_t r2, uint32_t r3) {
    asm volatile("stmatrix.sync.aligned.m8n8.x4.shared.b16 [%0], {%1,%2,%3,%4};\n" ::"r"(addr), "r"(r0), "r"(r1), "r"(r2), "r"(r3) : "memory");
}
__device__ __forceinline__ void stsm_x4_t(uint32_t addr, uint32_t r0, uint32_t r1, uint32_t r2, uint32_t r3) {
    asm volatile("stmatrix.sync.aligned.m8n8.x4.trans.shared.b16 [%0], {%1,%2,%3,%4};\n" ::"r"(addr), "r"(r0), "r"(r1), "r"(r2), "r"(r3) : "memory");
}
__device__ __forceinline__ uint32_t movm(uint32_t a) {
    uint32_t d;
    asm volatile("movmatrix.sync.aligned.m8n8.trans.b16 %0, %1;\n" : "=r"(d) : "r"(a));
    return d;
}
__device__ __forceinline__ void mma_f16(float (&c)[4], uint32_t a0, uint32_t a1, uint32_t a2, uint32_t a3, uint32_t b0, uint32_t b1) {
    asm volatile(
        "mma.sync.aligned.m16n8k16.row.col.f32.f16.f16.f32 {%0,%1,%2,%3}, {%4,%5,%6,%7}, {%8,%9}, {%0,%1,%2,%3};\n"
        : "+f"(c[0]), "+f"(c[1]), "+f"(c[2]), "+f"(c[3])
        : "r"(a0), "r"(a1), "r"(a2), "r"(a3), "r"(b0), "r"(b1));
}
__device__ __forceinline__ void mma_bf16(float (&c)[4], uint32_t a0, uint32_t a1, uint32_t a2, uint32_t a3, uint32_t b0, uint32_t b1) {
    asm volatile(
        "mma.sync.aligned.m16n8k16.row.col.f32.bf16.bf16.f32 {%0,%1,%2,%3}, {%4,%5,%6,%7}, {%8,%9}, {%0,%1,%2,%3};\n"
        : "+f"(c[0]), "+f"(c[1]), "+f"(c[2]), "+f"(c[3])
        : "r"(a0), "r"(a1), "r"(a2), "r"(a3), "r"(b0), "r"(b1));
}
__device__ __forceinline__ void mma_bf16_k8(float (&c)[4], uint32_t a0, uint32_t a1, uint32_t b0) {
    asm volatile("mma.sync.aligned.m16n8k8.row.col.f32.bf16.bf16.f32 {%0,%1,%2,%3}, {%4,%5}, {%6}, {%0,%1,%2,%3};\n"
                 : "+f"(c[0]), "+f"(c[1]), "+f"(c[2]), "+f"(c[3]) : "r"(a0), "r"(a1), "r"(b0));
}
__device__ __forceinline__ void bar_sync(int id, int n) { asm volatile("bar.sync %0, %1;\n" ::"r"(id), "r"(n) : "memory"); }
__device__ __forceinline__ void bar_arrive(int id, int n) { asm volatile("bar.arrive %0, %1;\n" ::"r"(id), "r"(n) : "memory"); }
__device__ __forceinline__ bool bar_or(int id, int n, bool v) {
    uint32_t r;
    asm volatile("{\n.reg .pred p, q;\nsetp.ne.u32 p, %3, 0;\nbar.red.or.pred q, %1, %2, p;\nselp.u32 %0, 1, 0, q;\n}\n" : "=r"(r) : "r"(id), "r"(n), "r"((uint32_t)v) : "memory");
    return r;
}
__device__ __forceinline__ uint32_t and3(uint32_t a, uint32_t b, uint32_t c) { uint32_t r; asm("lop3.b32 %0, %1, %2, %3, 0x80;\n" : "=r"(r) : "r"(a), "r"(b), "r"(c)); return r; }
__device__ __forceinline__ uint32_t or3(uint32_t a, uint32_t b, uint32_t c) { uint32_t r; asm("lop3.b32 %0, %1, %2, %3, 0xfe;\n" : "=r"(r) : "r"(a), "r"(b), "r"(c)); return r; }
__device__ __forceinline__ uint32_t xor_or(uint32_t a, uint32_t b, uint32_t c) { uint32_t r; asm("lop3.b32 %0, %1, %2, %3, 0x7e;\n" : "=r"(r) : "r"(a), "r"(b), "r"(c)); return r; }
__device__ __forceinline__ uint32_t pin(uint32_t v) { uint32_t r; asm volatile("shfl.sync.bfly.b32 %0, %1, 0, 0x1f, 0xffffffff;\n" : "=r"(r) : "r"(v) : "memory"); return r; }
__device__ __forceinline__ uint4 ld_poll(const void* p) {
    uint4 v;
    asm volatile("ld.relaxed.gpu.global.v4.u32 {%0,%1,%2,%3}, [%4];\n" : "=r"(v.x), "=r"(v.y), "=r"(v.z), "=r"(v.w) : "l"(p) : "memory");
    return v;
}
__device__ __forceinline__ uint2 ld_poll64(const void* p) {
    uint2 v;
    asm volatile("ld.relaxed.gpu.global.v2.u32 {%0,%1}, [%2];\n" : "=r"(v.x), "=r"(v.y) : "l"(p) : "memory");
    return v;
}
__device__ __forceinline__ uint32_t ld_poll32(const void* p) {
    uint32_t v;
    asm volatile("ld.relaxed.gpu.global.u32 %0, [%1];\n" : "=r"(v) : "l"(p) : "memory");
    return v;
}
__device__ __forceinline__ uint32_t ld_acquire32(const void* p) {
    uint32_t v;
    asm volatile("ld.acquire.gpu.global.u32 %0, [%1];\n" : "=r"(v) : "l"(p) : "memory");
    return v;
}
__device__ __forceinline__ uint4 ldg128(const void* p) {
    uint4 v;
    asm volatile("ld.global.nc.v4.u32 {%0,%1,%2,%3}, [%4];\n" : "=r"(v.x), "=r"(v.y), "=r"(v.z), "=r"(v.w) : "l"(p));
    return v;
}
__device__ __forceinline__ uint2 ldg64(const void* p) {
    uint2 v;
    asm volatile("ld.global.nc.v2.u32 {%0,%1}, [%2];\n" : "=r"(v.x), "=r"(v.y) : "l"(p));
    return v;
}
__device__ __forceinline__ uint32_t ldg16(const void* p) {
    uint32_t v;
    asm volatile("ld.global.nc.u16 %0, [%1];\n" : "=r"(v) : "l"(p));
    return v;
}
__device__ __forceinline__ uint4 ldo128(const void* p) {
    uint4 v;
    asm volatile("ld.relaxed.cta.global.v4.u32 {%0,%1,%2,%3}, [%4];\n" : "=r"(v.x), "=r"(v.y), "=r"(v.z), "=r"(v.w) : "l"(p) : "memory");
    return v;
}
__device__ __forceinline__ uint2 ldo64(const void* p) {
    uint2 v;
    asm volatile("ld.relaxed.cta.global.v2.u32 {%0,%1}, [%2];\n" : "=r"(v.x), "=r"(v.y) : "l"(p) : "memory");
    return v;
}
__device__ __forceinline__ uint32_t ldo16(const void* p) {
    uint32_t v;
    asm volatile("ld.relaxed.cta.global.u16 %0, [%1];\n" : "=r"(v) : "l"(p) : "memory");
    return v;
}
__device__ __forceinline__ void stg128(void* p, uint32_t a, uint32_t b, uint32_t c, uint32_t d) {
    asm volatile("st.global.v4.u32 [%0], {%1,%2,%3,%4};\n" ::"l"(p), "r"(a), "r"(b), "r"(c), "r"(d) : "memory");
}
__device__ __forceinline__ void stg64(void* p, uint32_t a, uint32_t b) { asm volatile("st.global.v2.u32 [%0], {%1,%2};\n" ::"l"(p), "r"(a), "r"(b) : "memory"); }
__device__ __forceinline__ uint32_t min4(const uint4& v) { return min(min(v.x, v.y), min(v.z, v.w)); }
#define SPIN_LIMIT (1 << 21)
#define TRAP() __trap()
__device__ __forceinline__ void mbar_init(uint32_t bar, uint32_t cnt) { asm volatile("mbarrier.init.shared::cta.b64 [%0], %1;\n" ::"r"(bar), "r"(cnt) : "memory"); }
__device__ __forceinline__ void mbar_expect(uint32_t bar, uint32_t bytes) {
    asm volatile("mbarrier.arrive.expect_tx.shared::cta.b64 _, [%0], %1;\n" ::"r"(bar), "r"(bytes) : "memory");
}
__device__ __forceinline__ void mbar_arrive(uint32_t bar) { asm volatile("mbarrier.arrive.shared::cta.b64 _, [%0];\n" ::"r"(bar) : "memory"); }
__device__ __forceinline__ void mbar_wait_cluster(uint32_t bar) {
    asm volatile(
        "{\n.reg .pred p;\n"
        "W_%=:\n"
        "mbarrier.try_wait.parity.acquire.cluster.shared::cta.b64 p, [%0], 0;\n"
        "@!p bra W_%=;\n}\n" ::"r"(bar) : "memory");
}
__device__ __forceinline__ void mbar_wait(uint32_t bar) {
    asm volatile(
        "{\n.reg .pred p;\n"
        "W_%=:\n"
        "mbarrier.try_wait.parity.shared::cta.b64 p, [%0], 0;\n"
        "@!p bra W_%=;\n}\n" ::"r"(bar) : "memory");
}
__device__ __forceinline__ void mbar_wait1(uint32_t bar) {
    asm volatile(
        "{\n.reg .pred p;\n"
        "W_%=:\n"
        "mbarrier.try_wait.parity.shared::cta.b64 p, [%0], 1;\n"
        "@!p bra W_%=;\n}\n" ::"r"(bar) : "memory");
}
__device__ __forceinline__ bool mbar_test(uint32_t bar) {
    uint32_t r;
    asm volatile("{\n.reg .pred p;\nmbarrier.test_wait.parity.shared::cta.b64 p, [%1], 0;\nselp.u32 %0, 1, 0, p;\n}\n" : "=r"(r) : "r"(bar) : "memory");
    return __any_sync(0xffffffffu, r);
}
__device__ __forceinline__ void bulk_g2s(uint32_t dst, const void* src, uint32_t bytes, uint32_t bar) {
    asm volatile("cp.async.bulk.shared::cluster.global.mbarrier::complete_tx::bytes [%0], [%1], %2, [%3];\n" ::"r"(dst), "l"(src), "r"(bytes), "r"(bar) : "memory");
}
__device__ __forceinline__ void bulk_s2g(void* dst, uint32_t src, uint32_t bytes) {
    asm volatile("cp.async.bulk.global.shared::cta.bulk_group [%0], [%1], %2;\ncp.async.bulk.commit_group;\n" ::"l"(dst), "r"(src), "r"(bytes) : "memory");
}
__device__ __forceinline__ void bulk_s2g_nc(void* dst, uint32_t src, uint32_t bytes) {
    asm volatile("cp.async.bulk.global.shared::cta.bulk_group [%0], [%1], %2;\n" ::"l"(dst), "r"(src), "r"(bytes) : "memory");
}
__device__ __forceinline__ void tma_2d(uint32_t dst, const CUtensorMap* tm, int c0, int c1, uint32_t bar) {
    asm volatile("cp.async.bulk.tensor.2d.shared::cluster.global.mbarrier::complete_tx::bytes [%0], [%1, {%3, %4}], [%2];\n"
                 ::"r"(dst), "l"(tm), "r"(bar), "r"(c0), "r"(c1) : "memory");
}
__device__ __forceinline__ void tma_4d(uint32_t dst, const CUtensorMap* tm, int c0, int c3, uint32_t bar) {
    asm volatile("cp.async.bulk.tensor.4d.shared::cluster.global.mbarrier::complete_tx::bytes [%0], [%1, {%3, %4, %4, %5}], [%2];\n"
                 ::"r"(dst), "l"(tm), "r"(bar), "r"(c0), "r"(0), "r"(c3) : "memory");
}
__device__ __forceinline__ void tma_4d_mc(uint32_t dst, const CUtensorMap* tm, int c0, int c3, uint32_t bar) {
    asm volatile("cp.async.bulk.tensor.4d.shared::cluster.global.mbarrier::complete_tx::bytes.multicast::cluster [%0], [%1, {%3, %4, %4, %5}], [%2], %6;\n"
                 ::"r"(dst), "l"(tm), "r"(bar), "r"(c0), "r"(0), "r"(c3), "h"((unsigned short)3) : "memory");
}
__device__ __forceinline__ void l2_prefetch(const void* src, uint32_t bytes) {
    asm volatile("cp.async.bulk.prefetch.L2.global [%0], %1;\n" ::"l"(src), "r"(bytes) : "memory");
}
__device__ __forceinline__ bool elect_one() {
    uint32_t r;
    asm volatile("{\n.reg .pred p;\nelect.sync _|p, 0xffffffff;\nselp.u32 %0, 1, 0, p;\n}\n" : "=r"(r));
    return r;
}
__device__ __forceinline__ void delay(uint32_t clks) {
    uint32_t t0, t1;
    asm volatile("mov.u32 %0, %%clock;" : "=r"(t0) :: "memory");
    do { asm volatile("mov.u32 %0, %%clock;" : "=r"(t1) :: "memory"); } while (t1 - t0 < clks);
}
__device__ __forceinline__ void fence_async() { asm volatile("fence.proxy.async.shared::cta;\n" ::: "memory"); }

__device__ __forceinline__ float2 cmul(float2 a, float2 b) {
    return make_float2(fmaf(a.x, b.x, -a.y * b.y), fmaf(a.x, b.y, a.y * b.x));
}
__device__ __forceinline__ float2 csq(float2 a) {
    float p = a.x * a.y;
    return make_float2(fmaf(a.x, a.x, -a.y * a.y), p + p);
}
__device__ __forceinline__ float ex2_approx(float x) { float r; asm("ex2.approx.ftz.f32 %0, %1;\n" : "=f"(r) : "f"(x)); return r; }
__device__ __forceinline__ float exp_bf(float x) { return rbf(ex2_approx(__fmul_ru(x, 1.4426950408889634f))); }
__device__ __forceinline__ float2 cexp_e(float lr2, float li, float e) {
    const float m = ex2_approx(lr2 * e);
    return make_float2(m * __cosf(li * e), m * __sinf(li * e));
}
__device__ __forceinline__ float rcp_approx(float x) { float r; asm("rcp.approx.ftz.f32 %0, %1;\n" : "=f"(r) : "f"(x)); return r; }
__device__ __forceinline__ float sigmoid_f(float x) { return rcp_approx(1.0f + ex2_approx(x * -1.4426950408889634f)); }
__device__ __forceinline__ float sqrt_approx(float x) { float r; asm("sqrt.approx.ftz.f32 %0, %1;\n" : "=f"(r) : "f"(x)); return r; }

__device__ __forceinline__ void wg_fence() { asm volatile("wgmma.fence.sync.aligned;\n" ::: "memory"); }
__device__ __forceinline__ void wg_commit() { asm volatile("wgmma.commit_group.sync.aligned;\n" ::: "memory"); }
__device__ __forceinline__ void wg_wait0() { asm volatile("wgmma.wait_group.sync.aligned 0;\n" ::: "memory"); }
template <int T> __device__ __forceinline__ void wg_mma(float (&acc)[16][4], const uint32_t* a, uint64_t desc);
template <int T> __device__ __forceinline__ void wg_first(float (&acc)[16][4], const uint32_t* a, uint64_t desc);
template <> __device__ __forceinline__ void wg_mma<0>(float (&acc)[16][4], const uint32_t* a, uint64_t desc) {
    asm volatile("wgmma.mma_async.sync.aligned.m64n128k16.f32.f16.f16 {%0,%1,%2,%3,%4,%5,%6,%7,%8,%9,%10,%11,%12,%13,%14,%15,%16,%17,%18,%19,%20,%21,%22,%23,%24,%25,%26,%27,%28,%29,%30,%31,%32,%33,%34,%35,%36,%37,%38,%39,%40,%41,%42,%43,%44,%45,%46,%47,%48,%49,%50,%51,%52,%53,%54,%55,%56,%57,%58,%59,%60,%61,%62,%63}, {%64,%65,%66,%67}, %68, 1, 1, 1, 0;\n"
                 : "+f"(acc[0][0]), "+f"(acc[0][1]), "+f"(acc[0][2]), "+f"(acc[0][3]), "+f"(acc[1][0]), "+f"(acc[1][1]), "+f"(acc[1][2]), "+f"(acc[1][3]), "+f"(acc[2][0]), "+f"(acc[2][1]), "+f"(acc[2][2]), "+f"(acc[2][3]), "+f"(acc[3][0]), "+f"(acc[3][1]), "+f"(acc[3][2]), "+f"(acc[3][3]), "+f"(acc[4][0]), "+f"(acc[4][1]), "+f"(acc[4][2]), "+f"(acc[4][3]), "+f"(acc[5][0]), "+f"(acc[5][1]), "+f"(acc[5][2]), "+f"(acc[5][3]), "+f"(acc[6][0]), "+f"(acc[6][1]), "+f"(acc[6][2]), "+f"(acc[6][3]), "+f"(acc[7][0]), "+f"(acc[7][1]), "+f"(acc[7][2]), "+f"(acc[7][3]), "+f"(acc[8][0]), "+f"(acc[8][1]), "+f"(acc[8][2]), "+f"(acc[8][3]), "+f"(acc[9][0]), "+f"(acc[9][1]), "+f"(acc[9][2]), "+f"(acc[9][3]), "+f"(acc[10][0]), "+f"(acc[10][1]), "+f"(acc[10][2]), "+f"(acc[10][3]), "+f"(acc[11][0]), "+f"(acc[11][1]), "+f"(acc[11][2]), "+f"(acc[11][3]), "+f"(acc[12][0]), "+f"(acc[12][1]), "+f"(acc[12][2]), "+f"(acc[12][3]), "+f"(acc[13][0]), "+f"(acc[13][1]), "+f"(acc[13][2]), "+f"(acc[13][3]), "+f"(acc[14][0]), "+f"(acc[14][1]), "+f"(acc[14][2]), "+f"(acc[14][3]), "+f"(acc[15][0]), "+f"(acc[15][1]), "+f"(acc[15][2]), "+f"(acc[15][3])
                 : "r"(a[0]), "r"(a[1]), "r"(a[2]), "r"(a[3]), "l"(desc));
}
template <> __device__ __forceinline__ void wg_mma<2>(float (&acc)[16][4], const uint32_t* a, uint64_t desc) {
    asm volatile("wgmma.mma_async.sync.aligned.m64n112k16.f32.f16.f16 {%0,%1,%2,%3,%4,%5,%6,%7,%8,%9,%10,%11,%12,%13,%14,%15,%16,%17,%18,%19,%20,%21,%22,%23,%24,%25,%26,%27,%28,%29,%30,%31,%32,%33,%34,%35,%36,%37,%38,%39,%40,%41,%42,%43,%44,%45,%46,%47,%48,%49,%50,%51,%52,%53,%54,%55}, {%56,%57,%58,%59}, %60, 1, 1, 1, 0;\n"
                 : "+f"(acc[2][0]), "+f"(acc[2][1]), "+f"(acc[2][2]), "+f"(acc[2][3]), "+f"(acc[3][0]), "+f"(acc[3][1]), "+f"(acc[3][2]), "+f"(acc[3][3]), "+f"(acc[4][0]), "+f"(acc[4][1]), "+f"(acc[4][2]), "+f"(acc[4][3]), "+f"(acc[5][0]), "+f"(acc[5][1]), "+f"(acc[5][2]), "+f"(acc[5][3]), "+f"(acc[6][0]), "+f"(acc[6][1]), "+f"(acc[6][2]), "+f"(acc[6][3]), "+f"(acc[7][0]), "+f"(acc[7][1]), "+f"(acc[7][2]), "+f"(acc[7][3]), "+f"(acc[8][0]), "+f"(acc[8][1]), "+f"(acc[8][2]), "+f"(acc[8][3]), "+f"(acc[9][0]), "+f"(acc[9][1]), "+f"(acc[9][2]), "+f"(acc[9][3]), "+f"(acc[10][0]), "+f"(acc[10][1]), "+f"(acc[10][2]), "+f"(acc[10][3]), "+f"(acc[11][0]), "+f"(acc[11][1]), "+f"(acc[11][2]), "+f"(acc[11][3]), "+f"(acc[12][0]), "+f"(acc[12][1]), "+f"(acc[12][2]), "+f"(acc[12][3]), "+f"(acc[13][0]), "+f"(acc[13][1]), "+f"(acc[13][2]), "+f"(acc[13][3]), "+f"(acc[14][0]), "+f"(acc[14][1]), "+f"(acc[14][2]), "+f"(acc[14][3]), "+f"(acc[15][0]), "+f"(acc[15][1]), "+f"(acc[15][2]), "+f"(acc[15][3])
                 : "r"(a[0]), "r"(a[1]), "r"(a[2]), "r"(a[3]), "l"(desc));
}
template <> __device__ __forceinline__ void wg_mma<4>(float (&acc)[16][4], const uint32_t* a, uint64_t desc) {
    asm volatile("wgmma.mma_async.sync.aligned.m64n96k16.f32.f16.f16 {%0,%1,%2,%3,%4,%5,%6,%7,%8,%9,%10,%11,%12,%13,%14,%15,%16,%17,%18,%19,%20,%21,%22,%23,%24,%25,%26,%27,%28,%29,%30,%31,%32,%33,%34,%35,%36,%37,%38,%39,%40,%41,%42,%43,%44,%45,%46,%47}, {%48,%49,%50,%51}, %52, 1, 1, 1, 0;\n"
                 : "+f"(acc[4][0]), "+f"(acc[4][1]), "+f"(acc[4][2]), "+f"(acc[4][3]), "+f"(acc[5][0]), "+f"(acc[5][1]), "+f"(acc[5][2]), "+f"(acc[5][3]), "+f"(acc[6][0]), "+f"(acc[6][1]), "+f"(acc[6][2]), "+f"(acc[6][3]), "+f"(acc[7][0]), "+f"(acc[7][1]), "+f"(acc[7][2]), "+f"(acc[7][3]), "+f"(acc[8][0]), "+f"(acc[8][1]), "+f"(acc[8][2]), "+f"(acc[8][3]), "+f"(acc[9][0]), "+f"(acc[9][1]), "+f"(acc[9][2]), "+f"(acc[9][3]), "+f"(acc[10][0]), "+f"(acc[10][1]), "+f"(acc[10][2]), "+f"(acc[10][3]), "+f"(acc[11][0]), "+f"(acc[11][1]), "+f"(acc[11][2]), "+f"(acc[11][3]), "+f"(acc[12][0]), "+f"(acc[12][1]), "+f"(acc[12][2]), "+f"(acc[12][3]), "+f"(acc[13][0]), "+f"(acc[13][1]), "+f"(acc[13][2]), "+f"(acc[13][3]), "+f"(acc[14][0]), "+f"(acc[14][1]), "+f"(acc[14][2]), "+f"(acc[14][3]), "+f"(acc[15][0]), "+f"(acc[15][1]), "+f"(acc[15][2]), "+f"(acc[15][3])
                 : "r"(a[0]), "r"(a[1]), "r"(a[2]), "r"(a[3]), "l"(desc));
}
template <> __device__ __forceinline__ void wg_mma<6>(float (&acc)[16][4], const uint32_t* a, uint64_t desc) {
    asm volatile("wgmma.mma_async.sync.aligned.m64n80k16.f32.f16.f16 {%0,%1,%2,%3,%4,%5,%6,%7,%8,%9,%10,%11,%12,%13,%14,%15,%16,%17,%18,%19,%20,%21,%22,%23,%24,%25,%26,%27,%28,%29,%30,%31,%32,%33,%34,%35,%36,%37,%38,%39}, {%40,%41,%42,%43}, %44, 1, 1, 1, 0;\n"
                 : "+f"(acc[6][0]), "+f"(acc[6][1]), "+f"(acc[6][2]), "+f"(acc[6][3]), "+f"(acc[7][0]), "+f"(acc[7][1]), "+f"(acc[7][2]), "+f"(acc[7][3]), "+f"(acc[8][0]), "+f"(acc[8][1]), "+f"(acc[8][2]), "+f"(acc[8][3]), "+f"(acc[9][0]), "+f"(acc[9][1]), "+f"(acc[9][2]), "+f"(acc[9][3]), "+f"(acc[10][0]), "+f"(acc[10][1]), "+f"(acc[10][2]), "+f"(acc[10][3]), "+f"(acc[11][0]), "+f"(acc[11][1]), "+f"(acc[11][2]), "+f"(acc[11][3]), "+f"(acc[12][0]), "+f"(acc[12][1]), "+f"(acc[12][2]), "+f"(acc[12][3]), "+f"(acc[13][0]), "+f"(acc[13][1]), "+f"(acc[13][2]), "+f"(acc[13][3]), "+f"(acc[14][0]), "+f"(acc[14][1]), "+f"(acc[14][2]), "+f"(acc[14][3]), "+f"(acc[15][0]), "+f"(acc[15][1]), "+f"(acc[15][2]), "+f"(acc[15][3])
                 : "r"(a[0]), "r"(a[1]), "r"(a[2]), "r"(a[3]), "l"(desc));
}
template <> __device__ __forceinline__ void wg_mma<8>(float (&acc)[16][4], const uint32_t* a, uint64_t desc) {
    asm volatile("wgmma.mma_async.sync.aligned.m64n64k16.f32.f16.f16 {%0,%1,%2,%3,%4,%5,%6,%7,%8,%9,%10,%11,%12,%13,%14,%15,%16,%17,%18,%19,%20,%21,%22,%23,%24,%25,%26,%27,%28,%29,%30,%31}, {%32,%33,%34,%35}, %36, 1, 1, 1, 0;\n"
                 : "+f"(acc[8][0]), "+f"(acc[8][1]), "+f"(acc[8][2]), "+f"(acc[8][3]), "+f"(acc[9][0]), "+f"(acc[9][1]), "+f"(acc[9][2]), "+f"(acc[9][3]), "+f"(acc[10][0]), "+f"(acc[10][1]), "+f"(acc[10][2]), "+f"(acc[10][3]), "+f"(acc[11][0]), "+f"(acc[11][1]), "+f"(acc[11][2]), "+f"(acc[11][3]), "+f"(acc[12][0]), "+f"(acc[12][1]), "+f"(acc[12][2]), "+f"(acc[12][3]), "+f"(acc[13][0]), "+f"(acc[13][1]), "+f"(acc[13][2]), "+f"(acc[13][3]), "+f"(acc[14][0]), "+f"(acc[14][1]), "+f"(acc[14][2]), "+f"(acc[14][3]), "+f"(acc[15][0]), "+f"(acc[15][1]), "+f"(acc[15][2]), "+f"(acc[15][3])
                 : "r"(a[0]), "r"(a[1]), "r"(a[2]), "r"(a[3]), "l"(desc));
}
template <> __device__ __forceinline__ void wg_mma<10>(float (&acc)[16][4], const uint32_t* a, uint64_t desc) {
    asm volatile("wgmma.mma_async.sync.aligned.m64n48k16.f32.f16.f16 {%0,%1,%2,%3,%4,%5,%6,%7,%8,%9,%10,%11,%12,%13,%14,%15,%16,%17,%18,%19,%20,%21,%22,%23}, {%24,%25,%26,%27}, %28, 1, 1, 1, 0;\n"
                 : "+f"(acc[10][0]), "+f"(acc[10][1]), "+f"(acc[10][2]), "+f"(acc[10][3]), "+f"(acc[11][0]), "+f"(acc[11][1]), "+f"(acc[11][2]), "+f"(acc[11][3]), "+f"(acc[12][0]), "+f"(acc[12][1]), "+f"(acc[12][2]), "+f"(acc[12][3]), "+f"(acc[13][0]), "+f"(acc[13][1]), "+f"(acc[13][2]), "+f"(acc[13][3]), "+f"(acc[14][0]), "+f"(acc[14][1]), "+f"(acc[14][2]), "+f"(acc[14][3]), "+f"(acc[15][0]), "+f"(acc[15][1]), "+f"(acc[15][2]), "+f"(acc[15][3])
                 : "r"(a[0]), "r"(a[1]), "r"(a[2]), "r"(a[3]), "l"(desc));
}
template <> __device__ __forceinline__ void wg_mma<12>(float (&acc)[16][4], const uint32_t* a, uint64_t desc) {
    asm volatile("wgmma.mma_async.sync.aligned.m64n32k16.f32.f16.f16 {%0,%1,%2,%3,%4,%5,%6,%7,%8,%9,%10,%11,%12,%13,%14,%15}, {%16,%17,%18,%19}, %20, 1, 1, 1, 0;\n"
                 : "+f"(acc[12][0]), "+f"(acc[12][1]), "+f"(acc[12][2]), "+f"(acc[12][3]), "+f"(acc[13][0]), "+f"(acc[13][1]), "+f"(acc[13][2]), "+f"(acc[13][3]), "+f"(acc[14][0]), "+f"(acc[14][1]), "+f"(acc[14][2]), "+f"(acc[14][3]), "+f"(acc[15][0]), "+f"(acc[15][1]), "+f"(acc[15][2]), "+f"(acc[15][3])
                 : "r"(a[0]), "r"(a[1]), "r"(a[2]), "r"(a[3]), "l"(desc));
}
template <> __device__ __forceinline__ void wg_mma<14>(float (&acc)[16][4], const uint32_t* a, uint64_t desc) {
    asm volatile("wgmma.mma_async.sync.aligned.m64n16k16.f32.f16.f16 {%0,%1,%2,%3,%4,%5,%6,%7}, {%8,%9,%10,%11}, %12, 1, 1, 1, 0;\n"
                 : "+f"(acc[14][0]), "+f"(acc[14][1]), "+f"(acc[14][2]), "+f"(acc[14][3]), "+f"(acc[15][0]), "+f"(acc[15][1]), "+f"(acc[15][2]), "+f"(acc[15][3])
                 : "r"(a[0]), "r"(a[1]), "r"(a[2]), "r"(a[3]), "l"(desc));
}
template <> __device__ __forceinline__ void wg_first<0>(float (&acc)[16][4], const uint32_t* a, uint64_t desc) {
    asm volatile("wgmma.mma_async.sync.aligned.m64n128k16.f32.f16.f16 {%0,%1,%2,%3,%4,%5,%6,%7,%8,%9,%10,%11,%12,%13,%14,%15,%16,%17,%18,%19,%20,%21,%22,%23,%24,%25,%26,%27,%28,%29,%30,%31,%32,%33,%34,%35,%36,%37,%38,%39,%40,%41,%42,%43,%44,%45,%46,%47,%48,%49,%50,%51,%52,%53,%54,%55,%56,%57,%58,%59,%60,%61,%62,%63}, {%64,%65,%66,%67}, %68, 0, 1, 1, 0;\n"
                 : "=f"(acc[0][0]), "=f"(acc[0][1]), "=f"(acc[0][2]), "=f"(acc[0][3]), "=f"(acc[1][0]), "=f"(acc[1][1]), "=f"(acc[1][2]), "=f"(acc[1][3]), "=f"(acc[2][0]), "=f"(acc[2][1]), "=f"(acc[2][2]), "=f"(acc[2][3]), "=f"(acc[3][0]), "=f"(acc[3][1]), "=f"(acc[3][2]), "=f"(acc[3][3]), "=f"(acc[4][0]), "=f"(acc[4][1]), "=f"(acc[4][2]), "=f"(acc[4][3]), "=f"(acc[5][0]), "=f"(acc[5][1]), "=f"(acc[5][2]), "=f"(acc[5][3]), "=f"(acc[6][0]), "=f"(acc[6][1]), "=f"(acc[6][2]), "=f"(acc[6][3]), "=f"(acc[7][0]), "=f"(acc[7][1]), "=f"(acc[7][2]), "=f"(acc[7][3]), "=f"(acc[8][0]), "=f"(acc[8][1]), "=f"(acc[8][2]), "=f"(acc[8][3]), "=f"(acc[9][0]), "=f"(acc[9][1]), "=f"(acc[9][2]), "=f"(acc[9][3]), "=f"(acc[10][0]), "=f"(acc[10][1]), "=f"(acc[10][2]), "=f"(acc[10][3]), "=f"(acc[11][0]), "=f"(acc[11][1]), "=f"(acc[11][2]), "=f"(acc[11][3]), "=f"(acc[12][0]), "=f"(acc[12][1]), "=f"(acc[12][2]), "=f"(acc[12][3]), "=f"(acc[13][0]), "=f"(acc[13][1]), "=f"(acc[13][2]), "=f"(acc[13][3]), "=f"(acc[14][0]), "=f"(acc[14][1]), "=f"(acc[14][2]), "=f"(acc[14][3]), "=f"(acc[15][0]), "=f"(acc[15][1]), "=f"(acc[15][2]), "=f"(acc[15][3])
                 : "r"(a[0]), "r"(a[1]), "r"(a[2]), "r"(a[3]), "l"(desc));
}
template <> __device__ __forceinline__ void wg_first<4>(float (&acc)[16][4], const uint32_t* a, uint64_t desc) {
    asm volatile("wgmma.mma_async.sync.aligned.m64n96k16.f32.f16.f16 {%0,%1,%2,%3,%4,%5,%6,%7,%8,%9,%10,%11,%12,%13,%14,%15,%16,%17,%18,%19,%20,%21,%22,%23,%24,%25,%26,%27,%28,%29,%30,%31,%32,%33,%34,%35,%36,%37,%38,%39,%40,%41,%42,%43,%44,%45,%46,%47}, {%48,%49,%50,%51}, %52, 0, 1, 1, 0;\n"
                 : "=f"(acc[4][0]), "=f"(acc[4][1]), "=f"(acc[4][2]), "=f"(acc[4][3]), "=f"(acc[5][0]), "=f"(acc[5][1]), "=f"(acc[5][2]), "=f"(acc[5][3]), "=f"(acc[6][0]), "=f"(acc[6][1]), "=f"(acc[6][2]), "=f"(acc[6][3]), "=f"(acc[7][0]), "=f"(acc[7][1]), "=f"(acc[7][2]), "=f"(acc[7][3]), "=f"(acc[8][0]), "=f"(acc[8][1]), "=f"(acc[8][2]), "=f"(acc[8][3]), "=f"(acc[9][0]), "=f"(acc[9][1]), "=f"(acc[9][2]), "=f"(acc[9][3]), "=f"(acc[10][0]), "=f"(acc[10][1]), "=f"(acc[10][2]), "=f"(acc[10][3]), "=f"(acc[11][0]), "=f"(acc[11][1]), "=f"(acc[11][2]), "=f"(acc[11][3]), "=f"(acc[12][0]), "=f"(acc[12][1]), "=f"(acc[12][2]), "=f"(acc[12][3]), "=f"(acc[13][0]), "=f"(acc[13][1]), "=f"(acc[13][2]), "=f"(acc[13][3]), "=f"(acc[14][0]), "=f"(acc[14][1]), "=f"(acc[14][2]), "=f"(acc[14][3]), "=f"(acc[15][0]), "=f"(acc[15][1]), "=f"(acc[15][2]), "=f"(acc[15][3])
                 : "r"(a[0]), "r"(a[1]), "r"(a[2]), "r"(a[3]), "l"(desc));
}

#define EARLYN 2
#define K8 0
#define HOLD 3
#define MC 1
#define STAMPW(i) STAMPY(i)
#define STAMP2(i) STAMP(i)
#undef STAMPX
#define STAMPX(i)
#define PBAR 1
#define WDLY 500
#define CBAR 1
#define FDLY 1000
#define FDLY2 400
#define YDLY 1
#define YFROM 64
#define YPRE 0
#define KDLY 950
#define OEARLY 0
#define ODLY 0
#define SORD 1
#define SDLY 900
#define UDLY 1400
#define XCP 1
#define DEFER 0
#define WAE 0
#define RG0 0
#define RG1 2
#define WSP 1
#define EXP 0
#define XWHEN 0
#define RWHEN 0
#define HW 15
#define PEARLY 1
#define XG 6
struct Params {
    const bf16 *x, *lar, *aim, *cre, *cim, *ldt, *dsk;
    Scratch* s;
    const bf16 *wr, *wg, *wu, *wd;
    bf16* out;
};

#define TOK(g) (2 * (g) - ((g) & 1))
#define ROWTOK(r) (TOK((r) & 7) + (((r) >> 2) & 2))
__device__ __forceinline__ void ln_partial(const uint32_t (&H)[2][4], float (&d)[2][4]) {
#pragma unroll
    for (int hf = 0; hf < 2; hf++) {
        d[hf][0] = d[hf][1] = d[hf][2] = d[hf][3] = 0.f;
        mma_bf16(d[hf], H[hf][0], 0x3f803f80u, H[hf][1], 0x3f803f80u, H[hf][0], H[hf][1]);
    }
#pragma unroll
    for (int hf = 0; hf < 2; hf++) mma_bf16(d[hf], H[hf][2], 0x3f803f80u, H[hf][3], 0x3f803f80u, H[hf][2], H[hf][3]);
}
__device__ __forceinline__ float sum18(uint32_t a) {
    const uint4 p = lds128(a), q = lds128(a + 16), r = lds128(a + 32), s = lds128(a + 48);
    const uint2 u = lds64(a + 64);
#define F(x) __uint_as_float(x)
    return (((F(p.x) + F(p.y)) + (F(p.z) + F(p.w))) + ((F(q.x) + F(q.y)) + (F(q.z) + F(q.w)))) +
           (((F(r.x) + F(r.y)) + (F(r.z) + F(r.w))) + ((F(s.x) + F(s.y)) + (F(s.z) + F(s.w))) + (F(u.x) + F(u.y)));
#undef F
}
__device__ __forceinline__ void ln_stats(float sm, float sq, float& mb, float& sd) {
    const float m0 = sm * (1.0f / 576.0f);
    const float mean = fmaf(fmaf(-m0, 576.0f, sm), 1.0f / 576.0f, m0);
    const float var = fmaxf(fmaf(-mean, mean, sq * (1.0f / 576.0f)), 0.f);
    mb = rbf(mean);
    sd = rbf(sqrt_approx(rbf(rbf(var) + 1e-5f)));
}
__device__ __forceinline__ void ln_finish(float v, int lane, float& mb, float& rc) {
    const float o = __shfl_xor_sync(0xffffffffu, v, 16);
    float sd;
    ln_stats(lane < 16 ? v : o, lane < 16 ? o : v, mb, sd);
    rc = rcp_approx(sd);
}
__device__ __forceinline__ uint32_t ln_apply(uint32_t w, uint32_t m2, uint32_t rh, uint32_t rl) {
    const uint32_t d = hsub2_bf(w, m2);
    return hfma2_bf(d, rh, hmul2_bf(d, rl));
}
__device__ __forceinline__ void stat_store(uint32_t a, float mb, float rc, uint32_t extra) {
    const float rh = rbf(rc);
    sts64(a, (__float_as_uint(mb) >> 16) | (extra << 16), pack_bf16(rh, rc - rh));
}
#define STAT_M(s) __byte_perm((s).x, (s).x, 0x1010)
#define STAT_H(s) __byte_perm((s).y, (s).y, 0x1010)
#define STAT_L(s) __byte_perm((s).y, (s).y, 0x3232)

__device__ __forceinline__ void hcmul(uint32_t re, uint32_t im, uint32_t zx, uint32_t zy, uint32_t& ore, uint32_t& oim) {
    ore = hfms2(im, zy, hmul2(re, zx));
    oim = hfma2(re, zy, hmul2(im, zx));
}

struct KGen {
    uint32_t A[2][4][4];
    float2 z1, z8, z64, z128, T[9];
};
__device__ __forceinline__ void kgen_setup(KGen& k, float lar, float aim, float dt) {
    const float lr2 = -(exp_bf(lar) * dt) * 1.4426950408889634f, li = aim * dt;
    k.z1 = cexp_e(lr2, li, 1.0f);
    k.z8 = cexp_e(lr2, li, 8.0f);
    k.z64 = cexp_e(lr2, li, 64.0f);
}
__device__ __forceinline__ void kgen_rows(KGen& k, uint32_t tb, int lane) {
    const float2 z8 = k.z8, z64 = k.z64;
    const uint32_t row = tb + lane * 16;
    k.z128 = csq(z64);
    const float2 z16 = csq(z8), z24 = cmul(z16, z8), z32 = csq(z16), z40 = cmul(z32, z8), z48 = csq(z24), z56 = cmul(z32, z24);
    uint32_t re[4], im[4], a[4], b[4];
    re[0] = pack_f16(1.0f, z8.x); im[0] = pack_f16(0.0f, z8.y);
    re[1] = pack_f16(z16.x, z24.x); im[1] = pack_f16(z16.y, z24.y);
    re[2] = pack_f16(z32.x, z40.x); im[2] = pack_f16(z32.y, z40.y);
    re[3] = pack_f16(z48.x, z56.x); im[3] = pack_f16(z48.y, z56.y);
    sts128(row, re[0], re[1], re[2], re[3]);
    sts128(row + 1024, im[0], im[1], im[2], im[3]);
    const uint32_t zx = pack_f16(z64.x, z64.x), zy = pack_f16(z64.y, z64.y), zw = pack_f16(k.z128.x, k.z128.y);
#pragma unroll
    for (int j = 0; j < 4; j++) hcmul(re[j], im[j], zx, zy, a[j], b[j]);
    sts128(row + 512, a[0], a[1], a[2], a[3]);
    sts128(row + 1536, b[0], b[1], b[2], b[3]);
    const int mi = lane >> 3;
    const uint32_t zd = tb + 2048 + mi * 16;
    sts16(tb + 2048 + lane * 2, zw); sts16(tb + 2112 + lane * 2, zw >> 16);
    __syncwarp();
    const uint32_t ad = tb + (lane & 7) * 16 + mi * 512;
    ldsm_x4(a[0], a[1], a[2], a[3], zd);
    ldsm_x4(b[0], b[1], b[2], b[3], zd + 64);
#pragma unroll
    for (int ks = 0; ks < 4; ks++) {
        ldsm_x4_t(k.A[0][ks][0], k.A[0][ks][1], k.A[0][ks][2], k.A[0][ks][3], ad + ks * 128);
        hcmul(k.A[0][ks][0], k.A[0][ks][2], a[ks], b[ks], k.A[1][ks][0], k.A[1][ks][2]);
        hcmul(k.A[0][ks][1], k.A[0][ks][3], a[ks], b[ks], k.A[1][ks][1], k.A[1][ks][3]);
    }
}
__device__ __forceinline__ void kgen_chain(KGen& k, uint32_t cr, uint32_t ci, float cs) {
    k.T[0] = make_float2(bf_lo(cr) * cs, -bf_lo(ci) * cs);
    const float2 y1 = make_float2(k.z1.x, -k.z1.y);
#pragma unroll
    for (int c = 1; c < 8; c++) k.T[c] = cmul(k.T[c - 1], y1);
    k.T[8] = cmul(k.T[0], make_float2(k.z8.x, -k.z8.y));
}
__device__ __forceinline__ void kgen_cols(KGen& k, uint32_t tb, uint32_t t5, int lane) {
    const uint32_t row = tb + lane * 16;
    const float2 (&T)[9] = k.T;
    const float2 y128 = make_float2(k.z128.x, -k.z128.y);
    const float2 y256 = csq(y128), y512 = csq(y256), y768 = cmul(y512, y256), y1024 = csq(y512);
    const float2 c1032 = cmul(T[8], y1024);
    __syncwarp();
    sts128(row, pack_f16(T[0].x, T[1].x), pack_f16(T[2].x, T[3].x), pack_f16(T[4].x, T[5].x), pack_f16(T[6].x, T[7].x));
    sts128(row + 512, pack_f16(T[0].y, T[1].y), pack_f16(T[2].y, T[3].y), pack_f16(T[4].y, T[5].y), pack_f16(T[6].y, T[7].y));
    uint32_t a[4], b[4];
    {
        const uint32_t zx = pack_f16(y256.x, y256.x), zy = pack_f16(y256.y, y256.y);
        hcmul(pack_f16(T[0].x, T[2].x), pack_f16(T[0].y, T[2].y), zx, zy, a[0], b[0]);
        hcmul(pack_f16(T[4].x, T[6].x), pack_f16(T[4].y, T[6].y), zx, zy, a[1], b[1]);
        const uint32_t r04 = pack_f16(T[0].x, T[4].x), i04 = pack_f16(T[0].y, T[4].y);
        hcmul(r04, i04, pack_f16(y512.x, y512.x), pack_f16(y512.y, y512.y), a[2], b[2]);
        hcmul(r04, i04, pack_f16(y768.x, y768.x), pack_f16(y768.y, y768.y), a[3], b[3]);
    }
    sts128(row + 1024, a[0], a[1], a[2], a[3]);
    sts128(row + 1536, b[0], b[1], b[2], b[3]);
    {
        const uint32_t r0 = pack_f16(1.0f, y256.x), i0 = pack_f16(0.0f, y256.y), r1 = pack_f16(y512.x, y768.x), i1 = pack_f16(y512.y, y768.y);
        const uint32_t zx = pack_f16(T[8].x, T[8].x), zy = pack_f16(T[8].y, T[8].y), wx = pack_f16(c1032.x, c1032.x), wy = pack_f16(c1032.y, c1032.y);
        hcmul(r0, i0, zx, zy, a[0], b[0]); hcmul(r1, i1, zx, zy, a[1], b[1]);
        hcmul(r0, i0, wx, wy, a[2], b[2]); hcmul(r1, i1, wx, wy, a[3], b[3]);
    }
    sts128(row + 2048, a[0], a[1], a[2], a[3]);
    sts128(t5 + lane * 16, b[0], b[1], b[2], b[3]);
}
__device__ __forceinline__ void kgen_mma(const KGen& k, uint32_t tb, uint32_t t5, int lane, uint32_t hb) {
    __syncwarp();
    float acc[2][3][4];
#pragma unroll
    for (int i = 0; i < 6; i++)
#pragma unroll
        for (int j = 0; j < 4; j++) acc[i / 3][i % 3][j] = 0.f;
    const int mi = lane >> 3;
    const uint32_t ro = ((lane & 7) + 8 * (mi >> 1)) * 16, bd = tb + ro + (mi & 1) * 512, b2 = ro + ((mi & 1) ? t5 : tb + 2048);
#pragma unroll
    for (int kp = 0; kp < 2; kp++)
#pragma unroll
        for (int j = 0; j < 3; j++) {
            uint32_t b[4];
            if (HOLD == 5 && kp == 1 && j == 0) mbar_wait1(hb);
            ldsm_x4_t(b[0], b[1], b[2], b[3], (j < 2 ? bd + j * 1024 : b2) + kp * 256);
#pragma unroll
            for (int h = 0; h < 2; h++)
#pragma unroll
                for (int m = 0; m < 2; m++) {
                    const uint32_t (&A)[4] = k.A[m][2 * kp + h];
                    mma_f16(acc[m][j], A[0], A[1], A[2], A[3], b[2 * h], b[2 * h + 1]);
                }
        }
    __syncwarp();
#define PK(j) pack_f16(acc[0][j][0], acc[0][j][1]), pack_f16(acc[0][j][2], acc[0][j][3]), pack_f16(acc[1][j][0], acc[1][j][1]), pack_f16(acc[1][j][2], acc[1][j][3])
    stsm_x4(tb + lane * 16, PK(0));
    stsm_x4(tb + 512 + lane * 16, PK(1));
    stsm_x4_t(tb + 1024 + (lane & 7) * 80 + mi * 16, PK(2));
#undef PK
}
__device__ __forceinline__ uint32_t table_buf(uint32_t sb, int warp) { return sb + SM_PL + warp * TBW; }

__device__ __forceinline__ uint4 lds16x4(uint32_t a) { return make_uint4(lds16(a), lds16(a + TBW), lds16(a + 2 * TBW), lds16(a + 3 * TBW)); }
__device__ __forceinline__ void combine_setup(uint32_t sb, int warp, int lane, uint32_t kw, uint32_t& o, uint32_t& n, uint32_t& d) {
    const int wq = warp & 3;
    const uint32_t a = table_buf(sb, warp & ~3);
    o = wq == 3 ? a + 1024 + 320 + (lane >> 3) * 80 + (lane & 7) * 8 : a + (wq ? 504 + wq * 8 : 0) + lane * 16;
    n = a + 1024 + wq * 80 + lane * 2;
    d = wq < 3 ? kw + (wq == 2 ? KW_P : 32 + wq * 512) + lane * 16 : kw + KW_H + 8 + lane * 8;
}
__device__ __forceinline__ void kgen_combine(int wq, int lane, uint32_t o, uint32_t na, uint32_t d) {
#define S4(f) hadd2(hadd2(u.f, v.f), hadd2(w.f, x.f))
#define H4(v) hadd2(hadd2(v.x, v.y), hadd2(v.z, v.w))
#define BP __byte_perm
    if (wq == 0) {
        const uint4 u = lds128(o), v = lds128(o + TBW), w = lds128(o + 2 * TBW), x = lds128(o + 3 * TBW), nn = lds16x4(na);
        const uint32_t n = H4(nn), k0 = S4(x), k2 = S4(y), k4 = S4(z), k6 = S4(w);
        sts128(d, BP(k0, k0, 0x1032), BP(k0, k2, 0x3254), BP(k2, k2, 0x1032), BP(k2, k4, 0x3254));
        sts128(d + KW_PL, BP(k4, k4, 0x1032), BP(k4, k6, 0x3254), BP(k6, k6, 0x1032), BP(k6, n, 0x3254));
        if (lane == 0) sts32(d + KW_PL - 4, k0 & 0xffffu);
    } else {
        const uint2 u = lds64(o), v = lds64(o + TBW), w = lds64(o + 2 * TBW), x = lds64(o + 3 * TBW);
        uint4 nn = make_uint4(0u, 0u, 0u, 0u), mm = nn;
        if (wq < 3) nn = lds16x4(na);
        if (wq == 2) mm = lds16x4(na + 80);
        const uint32_t k0 = S4(x), k2 = S4(y), n = H4(nn), m = H4(mm);
        if (wq == 3) {
            sts64(d, k0, k2);
        } else if (wq == 1) {
            const uint32_t cc = BP(k2, k2, 0x1010);
            sts128(d, BP(k0, k0, 0x1010), BP(k0, k0, 0x1032), BP(k0, k2, 0x3254), cc);
            sts128(d + KW_PL, cc, BP(k2, k2, 0x1032), BP(k2, n, 0x3254), BP(n, n, 0x1010));
        } else {
            const uint32_t w40 = BP(k0, k0, 0x1032), w84 = BP(k0, n, 0x3254), w0 = BP(k0, k0, 0x1010), w4 = BP(k0, k0, 0x3232), w8 = BP(n, n, 0x1010);
            sts64(d, w40, w84);
            sts64(d + 512, BP(k2, k2, 0x1032), BP(k2, m, 0x3254));
            if (lane < 8) { sts128(d - (KW_P - 1056), w0, w0, w40, w4); sts128(d - (KW_P - 1056 - KW_PL), w4, w84, w8, w8); }
            if (lane == 31) sts16(d + (KW_H + 6 - KW_P - 496), m);
        }
    }
#undef S4
#undef H4
#undef BP
}

__device__ __forceinline__ int c_exponent(const uint2& r, const uint2& i, float dt) {
    const uint32_t mx = __vmaxu2(__vmaxu2(r.x & 0x7fff7fffu, r.y & 0x7fff7fffu), __vmaxu2(i.x & 0x7fff7fffu, i.y & 0x7fff7fffu));
    return __reduce_max_sync(0xffffffffu, max(mx, mx << 16) + (__float_as_uint(dt) & 0x7f800000u)) >> 23;
}

#define Q2FIX 1
#define ONEBAR 1
__device__ __forceinline__ int warp_v() { int l; asm volatile("mov.u32 %0, %%tid.x;" : "=r"(l)); return __shfl_sync(0xffffffffu, l >> 5, 0); }
__device__ __forceinline__ int lane_v() { int l; asm volatile("mov.u32 %0, %%laneid;" : "=r"(l)); return l; }
__device__ __forceinline__ uint32_t prmt_v(uint32_t a, uint32_t b, uint32_t s) { uint32_t d; asm volatile("prmt.b32 %0, %1, %2, %3;\n" : "=r"(d) : "r"(a), "r"(b), "r"(s)); return d; }
__device__ __forceinline__ uint32_t mov_v(uint32_t a) { uint32_t d; asm volatile("mov.b32 %0, %1;\n" : "=r"(d) : "r"(a)); return d; }
template <int G>
__device__ __forceinline__ void conv_rename(float (&acc)[16][4]) {
#pragma unroll
    for (int i = G; i < 16; i++)
#pragma unroll
        for (int j = 0; j < 4; j++) { float v; asm volatile("mov.b32 %0, %1;\n" : "=f"(v) : "f"(acc[i][j])); acc[i][j] = v; }
}
struct Conv {
    uint32_t kw;
    uint32_t wa;
    uint32_t pa, s2;
    uint32_t s8;
    uint32_t id;
    uint32_t lc;
    uint32_t fs;
    uint32_t fl, yo;
    uint32_t yp;
    size_t ycopy;
    uint32_t ps;
    uint64_t d0;
    int warp;
};
struct Pk { uint32_t w[4]; };
__device__ __forceinline__ Pk pk2(const float (&u)[4], const float (&v)[4]) {
    Pk r;
    r.w[0] = pack_f16(u[0], u[1]); r.w[1] = pack_f16(u[2], u[3]); r.w[2] = pack_f16(v[0], v[1]); r.w[3] = pack_f16(v[2], v[3]);
    return r;
}
__device__ __forceinline__ void park(uint32_t a, const Pk& v) {
    asm volatile("stmatrix.sync.aligned.m8n8.x4.trans.shared.b16 [%0], {%1,%2,%3,%4};\n" ::"r"(a), "r"(v.w[0]), "r"(v.w[1]), "r"(v.w[2]), "r"(v.w[3]) : "memory");
}
__device__ __forceinline__ void conv_constants(uint32_t lc, int l) {
    const int d = (l >> 2) - 2 * (l & 3);
    const int e = d + 8, r4 = (e + 1 + ((e >> 2) & 1)) >> 2, p4 = (e + (((e - 1) >> 2) & 1)) >> 2;
    const uint32_t s2 = r4 == p4 ? 0x1010u : 0x3210u;
    sts64(lc + l * 8, KW_P + ((r4 - 5) >> 1) * 16 + ((r4 - 5) & 1) * 4, s2 | ((d < 0 ? s2 : 0x7654u) << 16));
    const int lo = (d >= 4) - (d < -3), ho = (d >= 5) - (d < -2), le = (d > 4) - (d < -4), he = (d > 5) - (d < -3);
    sts32(lc + 512 + l * 8, (0x5454u + lo * 0x22 + ho * 0x2200) | ((0x3232u + le * 0x22 + he * 0x2200) << 16));
    const int cc = l >> 2, j = l & 3;
    sts64(lc + 256 + l * 8, (j >> 1) * PL_HALF + (16 + cc) * 16 + (j & 1) * 8, (cc >> 1) * (DM * 64) + (cc & 1) * 32 + j * 8);
}
__device__ __forceinline__ void conv_selectors4(Conv& c) {
    const uint2 v = lds64(c.lc + lane_v() * 8);
    c.pa = v.x; c.s2 = v.y;
}
__device__ __forceinline__ void conv_selectors8(Conv& c) { c.s8 = lds32(c.lc + 512 + lane_v() * 8); }
template <int G, int I0, int I1>
__device__ __forceinline__ void conv_load(const Conv& c, uint32_t (&q)[9]) {
    const int wq = c.warp & 3;
    if (G < 2) {
#pragma unroll
        for (int i = I0; i < I1; i++) q[i] = lds32(c.wa + G * 512 + i * 16);
    } else if (G < 4) {
        const uint32_t a = (G == 2 && wq == 0) ? c.wa + 1024 : c.pa + c.kw + wq * 128 + (G < 2 ? 0 : G - 2) * 512;
#pragma unroll
        for (int i = I0; i < I1; i++) q[i] = lds32(a + i * 16);
    } else {
        const uint4 u = lds128(c.kw + KW_H + (G < 4 ? 0 : G - 4) * 64 + wq * 16);
        const uint2 v = lds64(c.kw + KW_H + (G < 4 ? 0 : G - 4) * 64 + wq * 16 + 16);
        q[0] = u.x; q[1] = u.y; q[2] = u.z; q[3] = u.w; q[4] = v.x; q[5] = v.y;
        if (G == 4 && wq == 0) { q[6] = lds32(c.pa + c.kw + 1024); q[7] = lds32(c.pa + c.kw + 1040); }
    }
}
template <int G, int J0, int J1>
__device__ __forceinline__ void conv_frag(const Conv& c, const uint32_t (&q)[9], uint32_t* a, const Pk& dp) {
    const uint32_t dep = dp.w[0];
    if (G < 4) {
        const uint32_t s = (G < 2 || (G == 2 && (c.warp & 3) == 0)) ? c.id : c.s2;
#pragma unroll
        for (int j = J0; j < J1; j++) {
            uint32_t* o = a + 4 * (j - J0);
            o[0] = prmt_v(q[2 * j + 1], dp.w[0], s); o[1] = prmt_v(q[2 * j + 2], dp.w[1], s); o[2] = prmt_v(q[2 * j], dp.w[2], s); o[3] = prmt_v(q[2 * j + 1], dp.w[3], s);
        }
    } else {
        const uint32_t so = prmt_v(c.s8, dep, c.id), se = prmt_v(c.s8, dep, c.id + 0x22);
#pragma unroll
        for (int j = J0; j < J1; j++) {
            uint32_t* o = a + 4 * (j - J0);
            o[0] = prmt_v(q[j + 1], q[j + 2], se); o[1] = prmt_v(q[j + 1], q[j + 2], so); o[2] = prmt_v(q[j], q[j + 1], so);
            if (G == 4 && j == 0 && (c.warp & 3) == 0) {
                o[2] = prmt_v(q[6], dep, c.s2);
                o[0] = prmt_v(q[7], o[0], c.s2 >> 16);
            }
            o[3] = mov_v(o[0]);
        }
    }
}
template <int G, int J0, int J1>
__device__ __forceinline__ void conv_frag(const Conv& c, const uint32_t (&q)[9], uint32_t* a, float depf) {
    const uint32_t d = __float_as_uint(depf);
    conv_frag<G, J0, J1>(c, q, a, Pk{{d, d, d, d}});
}
template <int G, int T, int J0, int J1>
__device__ __forceinline__ void conv_mma(float (&acc)[16][4], const Conv& c, const uint32_t* a) {
#pragma unroll
    for (int j = J0; j < J1; j++) wg_mma<T>(acc, a + 4 * (j - J0), c.d0 - 8 * (2 * G - T) - j);
}
__device__ __forceinline__ float h_lo(uint32_t w) { return __half2float(__ushort_as_half((unsigned short)(w & 0xffffu))); }
__device__ __forceinline__ float h_hi(uint32_t w) { return __half2float(__ushort_as_half((unsigned short)(w >> 16))); }
__device__ __forceinline__ void flush_setup(Conv& c) {
    const uint2 v = lds64(c.lc + 256 + lane_v() * 8);
    c.fl = v.x; c.yo = v.y;
}
template <int Q>
__device__ __forceinline__ void flush_load(const Conv& c, uint32_t pl, uint2 (&f)[4]) {
#pragma unroll
    for (int w = 0; w < 4; w++) f[w] = lds64(c.fl + pl + (Q & 1) * 512 + w * (PLW_B - 64));
}
template <int Q>
__device__ __forceinline__ void flush_load_first(const Conv& c, uint32_t pl, uint2 (&f)[4], float depf) {
    const uint32_t p = prmt_v(c.fl, __float_as_uint(depf), c.id) + pl + (Q & 1) * 512;
#define LDV64(d, a) asm volatile("ld.volatile.shared.v2.u32 {%0,%1}, [%2];\n" : "=r"(d.x), "=r"(d.y) : "r"(a) : "memory")
    LDV64(f[0], p); LDV64(f[1], p + (PLW_B - 64)); LDV64(f[2], p + 2 * (PLW_B - 64)); LDV64(f[3], p + 3 * (PLW_B - 64));
}
#define FDEP __uint_as_float(f[3].y)
template <int Q, int mode>
__device__ __forceinline__ void conv_flush(const Conv& c, const uint2 (&f)[4], unsigned char* gy, uint32_t rx) {
    const uint32_t a0 = hadd2(f[0].x, f[1].x), a1 = hadd2(f[2].x, f[3].x), b0 = hadd2(f[0].y, f[1].y), b1 = hadd2(f[2].y, f[3].y);
    if (Q > 0 && mode == 1) {
        const uint32_t ra = rx + 16 + (Q > 0 ? Q - 1 : 0) * 1024 + (c.warp & 3) * 256 + lane_v() * 8;
        asm volatile("st.async.shared::cluster.mbarrier::complete_tx::bytes.v2.b32 [%0], {%1,%2}, [%3];\n"
                     ::"r"(ra ^ 0x1000000u), "r"(hadd2(a0, a1)), "r"(hadd2(b0, b1)), "r"((rx + (Q > 1 ? 8 : 0)) ^ 0x1000000u) : "memory");
        return;
    }
    float v0 = h_lo(a0) + h_lo(a1), v1 = h_hi(a0) + h_hi(a1), v2 = h_lo(b0) + h_lo(b1), v3 = h_hi(b0) + h_hi(b1);
    if (Q > 0 && mode == 2) {
        const uint2 o = lds64(rx + 16 + (Q > 0 ? Q - 1 : 0) * 1024 + (c.warp & 3) * 256 + lane_v() * 8);
        v0 += h_lo(o.x); v1 += h_hi(o.x); v2 += h_lo(o.y); v3 += h_hi(o.y);
    }
    const uint32_t lo = hmul2_bf(pack_bf16(v0, v1), c.fs), hi = hmul2_bf(pack_bf16(v2, v3), c.fs);
    stg64(gy + Q * 32 * DM * 32 + (c.yo + (Q < 3 ? c.yp : 0u)), nzw(lo), nzw(hi));
}
template <int I, bool S = false> struct IC { static constexpr int value = I; static constexpr bool shared = S; };
template <class T> __device__ constexpr bool wg_is4() { return T::shared; }
#define SLOT(n) (c.ps + (2 + ((n) & 7)) * 128)
#define GO() do { wg_commit(); __syncwarp(); } while (0)
#define DEP acc[15][3]
template <class FG, class FP, class FN>
__device__ __forceinline__ void conv_head(Conv& c, float (&acc)[16][4], uint32_t (&q)[9], uint32_t (&r)[9], uint32_t* a, FG fg, FP pre, FN next) {
    c.id = 0x3210u + (c.warp >> 8);
    if (ONEBAR) pre();
    conv_load<0, 0, 9>(c, q);
    conv_frag<0, 0, 1>(c, q, a, 0.f);
    if (!ONEBAR) pre();
    wg_fence(); wg_first<0>(acc, a, c.d0); GO();
    park(c.ps, Pk{{0u, 0u, 0u, 0u}});
    wg_wait0();
    conv_frag<0, 1, 2>(c, q, a, DEP);
    wg_fence(); conv_mma<0, 0, 1, 2>(acc, c, a); GO();
    fg(IC<0>());
    wg_wait0();
    conv_frag<0, 2, 3>(c, q, a, DEP);
    wg_fence(); conv_mma<0, 0, 2, 3>(acc, c, a); GO();
    conv_load<1, 0, 5>(c, r);
    wg_wait0();
    conv_frag<0, 3, 4>(c, q, a, DEP);
    wg_fence(); conv_mma<0, 0, 3, 4>(acc, c, a); GO();
    conv_load<1, 5, 9>(c, r);
    fg(IC<1>());
    wg_wait0();
    const Pk k = pk2(acc[0], acc[1]);
    conv_rename<2>(acc);
    conv_frag<1, 0, 2>(c, r, a, k);
    wg_fence(); conv_mma<1, 2, 0, 2>(acc, c, a); GO();
    park(SLOT(0), k);
    next(IC<0>());
    fg(IC<2>());
    wg_wait0();
    conv_frag<1, 2, 4>(c, r, a, DEP);
    wg_fence(); conv_mma<1, 2, 2, 4>(acc, c, a); GO();
    next(IC<1>());
    fg(IC<3>());
    wg_wait0();
}
template <class FG, class FP>
__device__ __forceinline__ void conv_run(Conv& c, uint32_t pl, unsigned char* gy, FG fg, FP pre) {
    float acc[16][4];
    uint32_t q[9], r[9], a[32];
    uint2 f[4];
    const int bid = 1 + (c.warp >> 2);
    conv_head(c, acc, q, r, a, fg, pre, [&](auto i) { if (decltype(i)::value == 0) conv_selectors4(c); else conv_load<2, 0, 9>(c, q); });
    Pk k = pk2(acc[2], acc[3]);
    conv_rename<4>(acc);
    conv_frag<2, 0, 4>(c, q, a, k);
    wg_fence(); conv_mma<2, 4, 0, 4>(acc, c, a); GO();
    park(SLOT(2), k);
    conv_load<3, 0, 9>(c, q);
    flush_setup(c);
    bar_sync(bid, 128);
    fg(IC<4>());
    wg_wait0();
    conv_rename<6>(acc);
    flush_load_first<0>(c, pl, f, DEP);
    conv_frag<3, 0, 4>(c, q, a, FDEP);
    wg_fence(); conv_mma<3, 6, 0, 4>(acc, c, a); GO();
    park(SLOT(4), pk2(acc[4], acc[5]));
    conv_load<4, 0, 9>(c, q);
    conv_selectors8(c);
    conv_flush<0, 0>(c, f, gy, 0u);
    fg(IC<5>());
    wg_wait0();
    conv_rename<8>(acc);
    conv_frag<4, 0, 4>(c, q, a, DEP);
    wg_fence(); conv_mma<4, 8, 0, 4>(acc, c, a); GO();
    k = pk2(acc[6], acc[7]);
    park(SLOT(6), k); park(c.ps, k);
    conv_load<5, 0, 9>(c, q);
    bar_sync(bid, 128);
    fg(IC<6>());
    wg_wait0();
    conv_rename<10>(acc);
    flush_load_first<1>(c, pl, f, DEP);
    conv_frag<5, 0, 4>(c, q, a, FDEP);
    wg_fence(); conv_mma<5, 10, 0, 4>(acc, c, a); GO();
    park(SLOT(8), pk2(acc[8], acc[9]));
    conv_load<6, 0, 9>(c, q); conv_load<7, 0, 9>(c, r);
    conv_flush<1, 0>(c, f, gy, 0u);
    fg(IC<7>());
    wg_wait0();
    conv_rename<12>(acc);
    conv_frag<6, 0, 4>(c, q, a, DEP); conv_frag<7, 0, 4>(c, r, a + 16, DEP);
    wg_fence(); conv_mma<6, 12, 0, 4>(acc, c, a); conv_mma<7, 12, 0, 4>(acc, c, a + 16); GO();
    park(SLOT(10), pk2(acc[10], acc[11]));
    bar_sync(bid, 128);
    flush_load<2>(c, pl, f);
    conv_flush<2, 0>(c, f, gy, 0u);
    fg(IC<8>());
    if (Q2FIX && c.id == 0) TRAP();
    wg_wait0();
    park(SLOT(12), pk2(acc[12], acc[13])); park(SLOT(14), pk2(acc[14], acc[15]));
    bar_sync(bid, 128);
    flush_load<3>(c, pl, f);
    conv_flush<3, 0>(c, f, gy, 0u);
}
template <class FG>
__device__ __forceinline__ void conv_outer(Conv& c, uint32_t pl, unsigned char* gy, uint32_t rx, FG fg) {
    float acc[16][4];
    uint32_t q[9], r[9], a[32];
    uint2 f[4], f2[4];
    const int bid = 1 + (c.warp >> 2);
    conv_head(c, acc, q, r, a, [&](auto gi) { if (decltype(gi)::value == 2) fg(IC<2, true>()); }, [&]() {}, [&](auto i) { if (decltype(i)::value == 0) conv_selectors8(c); else conv_load<6, 0, 9>(c, q); });
    park(SLOT(2), pk2(acc[2], acc[3])); park(SLOT(4), pk2(acc[4], acc[5]));
    const Pk k = pk2(acc[6], acc[7]);
    park(SLOT(6), k);
    conv_load<7, 0, 9>(c, r);
    conv_rename<12>(acc);
    conv_frag<6, 0, 4>(c, q, a, __uint_as_float(k.w[3])); conv_frag<7, 0, 4>(c, r, a + 16, __uint_as_float(k.w[3]));
    wg_fence(); conv_mma<6, 12, 0, 4>(acc, c, a); conv_mma<7, 12, 0, 4>(acc, c, a + 16); GO();
    flush_setup(c);
    bar_sync(bid, 128);
    flush_load<0>(c, pl, f); flush_load<1>(c, pl, f2);
    conv_flush<1, 1>(c, f2, gy, rx);
    conv_flush<0, 1>(c, f, gy, rx);
    wg_wait0();
    bar_sync(bid, 128);
    park(c.ps, k); park(SLOT(8), pk2(acc[8], acc[9])); park(SLOT(10), pk2(acc[10], acc[11]));
    park(SLOT(12), pk2(acc[12], acc[13])); park(SLOT(14), pk2(acc[14], acc[15]));
    bar_sync(bid, 128);
    flush_load<2>(c, pl, f); flush_load<3>(c, pl, f2);
    conv_flush<2, 1>(c, f, gy, rx);
    conv_flush<3, 1>(c, f2, gy, rx);
}
template <class FG>
__device__ __forceinline__ void conv_inner(Conv& c, uint32_t pl, unsigned char* gy, uint32_t rx, FG fg) {
    float acc[16][4];
    uint32_t q[9], a[16];
    uint2 f[4], f2[4];
    const int bid = 1 + (c.warp >> 2);
    c.id = 0x3210u + (c.warp >> 8);
    conv_selectors4(c);
    conv_load<2, 0, 9>(c, q);
    conv_frag<2, 0, 4>(c, q, a, 0.f);
    wg_fence(); wg_first<4>(acc, a, c.d0); conv_mma<2, 4, 1, 4>(acc, c, a + 4); GO();
    conv_load<3, 0, 9>(c, q);
    park(SLOT(2), Pk{{0u, 0u, 0u, 0u}});
    fg(IC<2, true>());
    wg_wait0();
    conv_rename<6>(acc);
    conv_frag<3, 0, 4>(c, q, a, DEP);
    wg_fence(); conv_mma<3, 6, 0, 4>(acc, c, a); GO();
    park(SLOT(4), pk2(acc[4], acc[5]));
    conv_load<4, 0, 9>(c, q);
    conv_selectors8(c);
    wg_wait0();
    conv_rename<8>(acc);
    conv_frag<4, 0, 4>(c, q, a, DEP);
    wg_fence(); conv_mma<4, 8, 0, 4>(acc, c, a); GO();
    const Pk k = pk2(acc[6], acc[7]);
    park(SLOT(6), k); park(c.ps, k);
    conv_load<5, 0, 9>(c, q);
    flush_setup(c);
    wg_wait0();
    conv_rename<10>(acc);
    conv_frag<5, 0, 4>(c, q, a, DEP);
    wg_fence(); conv_mma<5, 10, 0, 4>(acc, c, a); GO();
    park(SLOT(8), pk2(acc[8], acc[9]));
    bar_sync(bid, 128);
    flush_load<1>(c, pl, f);
    mbar_wait(rx);
    conv_flush<1, 2>(c, f, gy, rx);
    wg_wait0();
    bar_sync(bid, 128);
    park(SLOT(10), pk2(acc[10], acc[11])); park(SLOT(12), pk2(acc[12], acc[13])); park(SLOT(14), pk2(acc[14], acc[15]));
    bar_sync(bid, 128);
    flush_load<3>(c, pl, f); flush_load<2>(c, pl, f2);
    mbar_wait(rx + 8);
    conv_flush<3, 2>(c, f, gy, rx);
    conv_flush<2, 2>(c, f2, gy, rx);
}
#undef SLOT
#undef GO
#undef DEP
template <int U0, int U1>
__device__ __forceinline__ void weight_units(uint32_t sb, const CUtensorMap* tg, const CUtensorMap* tu, const CUtensorMap* td, bool w) {
    if (U1 > U0 && w && elect_one()) {
#pragma unroll
        for (int n = U0; n < U1; n++) {
            const int i = n;
            if (i < 12) tma_2d(sb + SM_WG + i * 6912, i < 6 ? tg : tu, 72 * (blockIdx.x >> 1), 288 * (blockIdx.x & 1) + (i % 6) * 48, sb + SM_MISC + 328);
            else tma_2d(sb + SM_WD + (i - 12) * 4736, td, 144 * (blockIdx.x & 1), 72 * (blockIdx.x >> 1) + 8 * (i - 12), sb + SM_MISC + 336);
        }
    }
}
#define WS 1111121111122004100
__device__ constexpr int wsched(int i) {
    unsigned long long v = WS;
    int n = 0;
    for (int k = 19; k >= 1; k--) { if (k < i) n += (int)(v % 10); v /= 10; }
    return n;
}
static_assert(wsched(20) == 21 && wsched(6) <= 7 && wsched(11) <= 12 && wsched(13) <= 14 && wsched(16) <= 17 && wsched(16) == wsched(15) && wsched(19) == 21, "");
__device__ __forceinline__ void weight_prefetch(const Params& p, int u, int lane) {
    const int b = blockIdx.x;
    const char* a = u < 12 ? reinterpret_cast<const char*>(u < 6 ? p.wg : p.wu) + ((b >> 6) * 288 + (u % 6) * 48) * (FF * 2) + (b & 63) * 6912
                           : reinterpret_cast<const char*>(p.wd) + (72 * (b >> 1) + 8 * (u - 12)) * 1152 + (b & 1) * 4608;
    asm volatile("prefetch.global.L2 [%0];\n" ::"l"(a + lane * 128));
    if (lane < (u < 12 ? 22 : 4)) asm volatile("prefetch.global.L2 [%0];\n" ::"l"(a + 4096 + lane * 128));
}
#define PF0 0
#define PF1 0
#define WPOINT(i, w) do { weight_units<wsched(i), wsched(i + 1)>(sb, &tm_g, &tm_u, &tm_d, w); } while (0)

__global__ void __launch_bounds__(NTHR, 1) __cluster_dims__(2, 1, 1)
fused_kernel(const Params p, const __grid_constant__ CUtensorMap tm_g, const __grid_constant__ CUtensorMap tm_u, const __grid_constant__ CUtensorMap tm_d, const __grid_constant__ CUtensorMap tm_x) {
    extern __shared__ __align__(1024) unsigned char smem[];
    const uint32_t sb = smem_u32(smem);
    const int tid = threadIdx.x, warp = __shfl_sync(0xffffffffu, tid >> 5, 0), lane = tid & 31;
    const int b = blockIdx.x, P = b >> 1, odd = b & 1;
    const int g = lane >> 2, t = lane & 3;
    const int wg = warp >> 2, t128 = tid & 127;
    const uint32_t s_stat = sb + SM_MISC;
    const uint32_t s_key = sb + SM_MISC + 128;
    const uint32_t s_rank = sb + SM_MISC + 256;
    const uint32_t s_k16 = sb + SM_MISC + 192;
    const uint32_t s_cnt = sb + SM_MISC + 320;
    const uint32_t bar_w = sb + SM_MISC + 328, bar_d = bar_w + 8, bar_g = bar_w + 16, bar_x = bar_w + 24, bar_t = bar_w + 32, bar_s = bar_w + 40, bar_v = bar_w + 48, bar_h = sb + SM_MISC + 160;
    STAMP(0);

    if (warp == 19) {
        if (lane == 0) {
            mbar_init(bar_w, 1); mbar_init(bar_d, 1); mbar_init(bar_g, 1); mbar_init(sb + SM_RX, 1); mbar_init(sb + SM_RX + 8, 1);
            mbar_init(bar_x, 1); mbar_init(bar_t, 1); mbar_init(bar_s, 1); mbar_init(bar_v, 2); if (HOLD >= 2) { mbar_init(bar_h, 1); mbar_init(bar_h + 8, 1); mbar_init(bar_h + 16, 1); mbar_init(bar_h + 24, 1); } mbar_expect(bar_x, 32768);
            asm volatile("fence.mbarrier_init.release.cluster;\n" ::: "memory");
            mbar_expect(bar_w, 82944); mbar_expect(bar_d, 72 * WD_PITCH); mbar_expect(bar_g, 4608); mbar_expect(bar_t, 16 * 1152); mbar_expect(bar_v, 2 * 1152); mbar_expect(sb + SM_RX, 1024); mbar_expect(sb + SM_RX + 8, 2048);
        }
        __syncwarp();
    }
    if (wg < 3) { sts128(sb + SM_Z2 + tid * 16, 0u, 0u, 0u, 0u); sts128(sb + SM_Z2 + 6144 + tid * 16, 0u, 0u, 0u, 0u); fence_async(); }
    const int ch = wg < 4 ? 4 * b + wg : 512 + P;
    const bf16 *q0 = p.lar + ch * NST, *q1 = p.aim + ch * NST, *q2 = p.cre + ch * NST, *q3 = p.cim + ch * NST;
    asm volatile("" : "+l"(q0), "+l"(q1), "+l"(q2), "+l"(q3));
    const uint32_t ldt = ldo16(p.ldt + ch), pl = ldo16(q0 + t128), pa2 = ldo16(q1 + t128);
    const uint32_t pc = ldo16(q2 + t128), pi = ldo16(q3 + t128);
    const uint2 call_re = ldo64(q2 + 4 * lane), call_im = ldo64(q3 + 4 * lane);
    const uint32_t epl = ld_poll32(p.s->hint + (b & 7) * 32 + 1);
    bar_sync(0, NWRK);
    if (XCP && wg == 4) {
        const int o = (4 * (warp & 3) + (g >> 1)) * 1152 + (g & 1) * 576 + t * 16;
#pragma unroll
        for (int c = 0; c < 9; c++)
            asm volatile("cp.async.cg.shared.global [%0], [%1], 16;\n" ::"r"(sb + SM_XT + o + c * 64), "l"(reinterpret_cast<const char*>(p.x) + b * 18432 + o + c * 64) : "memory");
        asm volatile("cp.async.commit_group;\n" ::: "memory");
    }
    asm volatile("barrier.cluster.arrive.relaxed.aligned;\n" ::: "memory");
    if (warp == 18) {
        if (lane == 0) {
            if (!XCP) bulk_g2s(sb + SM_XT, p.x + (size_t)16 * b * DM, 16 * 1152, bar_t);
            bulk_s2g(reinterpret_cast<unsigned char*>(p.s->y) + 96 * 18432 + b * 4608, sb + SM_Z2, 4608);
        }
        bar_arrive(12, 64);
    }
    if (warp == 19) {
        bar_sync(12, 64);
        asm volatile("barrier.cluster.wait.aligned;\n" ::: "memory");
        if (EXP & 4) { if (elect_one()) asm volatile("mbarrier.complete_tx.relaxed.cta.shared::cta.b64 [%0], %1;" :: "r"(bar_x), "r"(32768) : "memory"); }
        else if (EXP & 8) { if (elect_one()) { tma_4d(sb + SM_XC + odd * 16384, &tm_x, 8 * P, 2 * odd, bar_x); asm volatile("mbarrier.complete_tx.relaxed.cta.shared::cta.b64 [%0], %1;" :: "r"(bar_x), "r"(16384) : "memory"); } }
        else
        if (elect_one()) tma_4d_mc(sb + SM_XC + odd * 16384, &tm_x, 8 * P, 2 * odd, bar_x);
        __syncwarp();
    }
    const uint32_t kw = sb + SM_KW + wg * KW_B;
    const uint32_t tb = table_buf(sb, warp), t5 = sb + SM_WD + warp * 512;
    if (wg == 4) {
        if (!(g & 1) && t == (g >> 1)) *reinterpret_cast<volatile uint32_t*>(p.s->stat + 16 * b + 4 * (warp & 3) + t) = 0u;
        if (warp < 18) {
            unsigned char* const ud = reinterpret_cast<unsigned char*>(p.s->uT) + (size_t)(8 * (warp & 1) + 2 * (g >> 1)) * 16384 + b * 128 + (g & 1) * 32 + t * 8;
#pragma unroll
            for (int k = 0; k < 4; k++) *reinterpret_cast<volatile unsigned long long*>(ud + (k >> 1) * 16384 + (k & 1) * 64) = 0ull;
        }
        if (warp == 17) conv_constants(sb + SM_LC, lane);
    }
    if (t128 < 2 * UPAD) sts128(sb + SM_U + wg * USLOT_B + (t128 & 1) * ULO_B + (t128 >> 1) * 16, 0u, 0u, 0u, 0u);
    if (t128 >= 124) sts128(kw + (t128 & 1) * 16 + (t128 & 2) * (KW_PL / 2), 0u, 0u, 0u, 0u);
    uint32_t co, cn, cd;
    combine_setup(sb, warp, lane, kw, co, cn, cd);
    const uint4* usrc = wg < 4 ? reinterpret_cast<const uint4*>(p.s->stat) + tid
                               : reinterpret_cast<const uint4*>(p.s->uT) + (P >> 2) * 1024 + (t128 >> 1) * 8 + (P & 3) * 2 + (t128 & 1);
    uint32_t zero;
    {
        uint32_t uo = (uint32_t)(reinterpret_cast<const char*>(usrc) - reinterpret_cast<const char*>(p.s)), pk = (cn - co + 1024) | ((cd - kw) << 16);
        asm volatile("st.volatile.shared.v4.u32 [%4], {0, %1, %2, %3};\nld.volatile.shared.v4.u32 {%0, %1, %2, %3}, [%4];\n" : "=r"(zero), "+r"(co), "+r"(pk), "+r"(uo) : "r"(tb + lane * 16) : "memory");
        cn = co + (pk & 0xffffu) - 1024; cd = kw + (pk >> 16);
        usrc = reinterpret_cast<const uint4*>(reinterpret_cast<const char*>(p.s) + uo);
    }
    const float dt = exp_bf(__uint_as_float(__byte_perm(ldt, zero, 0x1044)));
    const uint32_t ep = __reduce_or_sync(0xffffffffu, epl | zero);
    auto stats = [&]() {
        const int wq = warp & 3;
        const uint32_t xa = sb + SM_XT + (4 * wq + (g >> 1)) * 1152 + (g & 1) * 576 + t * 16;
        const bool own = !(g & 1) && t == (g >> 1);
        float d[4][4] = {};
        if (XCP) asm volatile("cp.async.wait_group 0;\n" ::: "memory"); else mbar_wait(bar_t);
        if ((HOLD == 2 || HOLD == 5) && lane == 0) mbar_arrive(bar_h + 8 * wq);
        STAMP(26);
        uint4 v[9];
#pragma unroll
        for (int c = 0; c < 9; c++) v[c] = lds128(xa + c * 64);
#pragma unroll
        for (int c = 0; c < 9; c++) {
            mma_bf16(d[2 * (c & 1)], v[c].x, 0x3f803f80u, v[c].y, 0x3f803f80u, v[c].x, v[c].y);
            mma_bf16(d[2 * (c & 1) + 1], v[c].z, 0x3f803f80u, v[c].w, 0x3f803f80u, v[c].z, v[c].w);
        }
        STAMP(27);
        float sm = (g & 1) ? (d[0][3] + d[1][3]) + (d[2][3] + d[3][3]) : (d[0][2] + d[1][2]) + (d[2][2] + d[3][2]);
        float sq = (g & 1) ? (d[0][1] + d[1][1]) + (d[2][1] + d[3][1]) : (d[0][0] + d[1][0]) + (d[2][0] + d[3][0]);
        sm += __shfl_xor_sync(0xffffffffu, sm, 4); sq += __shfl_xor_sync(0xffffffffu, sq, 4);
        if (HOLD == 1) bar_arrive(6 + wq, 160);
        if (HOLD >= 2 && HOLD != 4 && lane == 0) mbar_arrive(bar_h + 8 * wq);
        float mb, sd;
        ln_stats(sm, sq, mb, sd);
        if (own) p.s->stat[16 * b + 4 * wq + t] = (__float_as_uint(mb) >> 16) | (__float_as_uint(sd) & 0x7fff0000u) | (ep << 31);
        STAMPX(22);
        if (HOLD == 4 && lane == 0) mbar_arrive(bar_h + 8 * wq);
        if (own) stat_store(s_stat + (2 * wq + (t & 1) + 8 * (t >> 1)) * 8, mb, rcp_approx(sd), 0u);
        if (wq == 2) asm volatile("cp.async.bulk.wait_group 0;\n" ::: "memory");
        bar_sync(5, 128);
        STAMP(28);
        if (wq == 2) {
            if (lane < 8) p.s->key3[8 * b + lane] = ep & 1u;
            if (lane == 0) {
                uint32_t now;
                asm volatile("mov.u32 %0, %%clock;" : "=r"(now));
                sts64(s_cnt, now, ep);
                mbar_arrive(bar_s);
                bulk_g2s(sb + SM_XT + 16 * 1152, p.dsk, 1152, bar_v);
                bulk_g2s(sb + SM_XT + 17 * 1152, p.wr, 1152, bar_v);
            }
            __syncwarp();
        }
        WPOINT(1, wq == 3);
        if (wq < 2) {
            unsigned char* const ud = reinterpret_cast<unsigned char*>(p.s->uT) + (size_t)(8 * wq + 2 * (g >> 1)) * 16384 + b * 128 + (g & 1) * 32 + t * 8;
            const uint32_t utag = (ep % 7u + 1u) * 0x10001u;
            uint32_t U[2][4];
#pragma unroll
            for (int hf = 0; hf < 2; hf++) {
                const uint2 st = lds64(s_stat + (g + 8 * hf) * 8);
                const uint4 xu = lds128(sb + SM_XT + (TOK(g) + 2 * hf) * 1152 + warp * 64 + t * 16);
                const uint32_t X[4] = {xu.x, xu.y, xu.z, xu.w};
#pragma unroll
                for (int k = 0; k < 4; k++) {
                    const uint32_t u = ln_apply(X[k], STAT_M(st), STAT_H(st), STAT_L(st));
                    U[hf][k] = movm((pack_f16(bf_lo(u), bf_hi(u)) & 0xfff8fff8u) | utag);
                }
            }
#pragma unroll
            for (int k = 0; k < 4; k++) stg64(ud + (k >> 1) * 16384 + (k & 1) * 64, U[0][k], U[1][k]);
        }
    };
    STAMP(1);
    if (wg < 4) { STAMPX(16); }
    if (SORD == 0 && wg == 4) stats();
    KGen kg;
    kgen_setup(kg, __uint_as_float(__byte_perm(pl, zero, 0x1044)), __uint_as_float(__byte_perm(pa2, zero, 0x1044)), dt);
    kgen_rows(kg, tb, lane);
    STAMP(2);
    const int E = min(max(c_exponent(call_re, call_im, dt) - 243, -120), 120);
    kgen_chain(kg, pc, pi, dt * __uint_as_float((uint32_t)(128 - E) << 23));
    STAMP(3);
    kgen_cols(kg, tb, t5, lane);
    STAMP(4);
    if (SORD == 1 && wg == 4) stats();
    if (warp != 19) asm volatile("barrier.cluster.wait.aligned;\n" ::: "memory");
    if (wg < 4) { STAMPX(17); }
    if (HOLD == 1 && wg < 4) bar_sync(6 + (warp & 3), 160);
    if ((HOLD == 3 || HOLD == 4) && wg < 4) mbar_wait(bar_h + 8 * (warp & 3));
    if (HOLD == 2 || HOLD == 5) mbar_wait1(bar_h + 8 * (warp & 3));
    if (wg < 4) { STAMPX(19); }
    if (DEFER == 1 && wg == 4) bar_sync(14, NWRK);
    if (DEFER > 1 && wg == 4) bar_sync(15, NWRK);
    kgen_mma(kg, tb, t5, lane, bar_h + 8 * (warp & 3));
    if (wg < 4) { STAMPX(20); }
    if (DEFER == 3 && wg < 4) bar_arrive(15, NWRK);
    STAMP(5);
    if (SORD == 2 && wg == 4) stats();
    uint4 uv0, uv1;
    auto first_poll = [&](uint32_t dly) {
        mbar_wait(bar_s);
        const uint32_t t0 = lds32(s_cnt);
        uint32_t now;
        do { asm volatile("mov.u32 %0, %%clock;" : "=r"(now) :: "memory"); } while (now - t0 < dly);
        uv0 = ld_poll(usrc);
    };
    WPOINT(2, warp == 19);
    if (PEARLY == 3 && wg < 4) first_poll(SDLY);
    bar_sync(1 + wg, 128);
    if (PEARLY == 2 && wg < 4) first_poll(SDLY);
    if (wg < 4) { STAMPX(21); }
    kgen_combine(warp & 3, lane, co, cn, cd);
    STAMP(6);
    if (wg < 4) { STAMPX(18); }
    if (DEFER == 2 && wg < 4) bar_arrive(15, NWRK);
    WPOINT(3, warp == 19);
    if (PEARLY == 1 && wg < 4) first_poll(SDLY);
    {
        const int wq = warp & 3;
        Conv c;
        const uint32_t pln = sb + SM_PL + wg * PL_B;
        const int e = g - 2 * t + 7;
        c.kw = kw; c.wa = pin(kw + ((e >> 2) & 1) * KW_PL + (8 * wq + (e >> 3)) * 16 + (e & 3) * 4);
        c.ps = mov_v(pln + wq * PLW_B + ((lane >> 3) & 1) * PL_HALF + ((lane >> 4) * 8 + (lane & 7)) * 16); c.warp = warp;
        c.lc = sb + SM_LC; c.fs = (uint32_t)(127 + E) * 0x800080u; c.yp = (ep & 1u) * (NCTA * 18432u);
        c.d0 = ((uint64_t)(ULO_B >> 4) << 16) | ((uint64_t)(128 >> 4) << 32) | (uint64_t)(((sb + SM_U + wg * USLOT_B + UPAD * 16) & 0x3FFFF) >> 4);
        unsigned char* gy = reinterpret_cast<unsigned char*>(p.s->y) + ((size_t)(4 * wq) * DM + ch) * 64;
        auto hook = [&](auto gi) {
                     constexpr int G = decltype(gi)::value;
                     if (G == (wg_is4<decltype(gi)>() ? 2 : 5)) asm volatile("barrier.cluster.wait.aligned;\n" ::: "memory");
                     if (!wg_is4<decltype(gi)>() && (G == RG0 || G == RG1) && warp == HW && elect_one()) {
                         unsigned char* const sc = reinterpret_cast<unsigned char*>(p.s);
                         if (G == RG0) {
                             if (b < 96) bulk_s2g_nc(sc + offsetof(Scratch, part) + b * 12288, sb + SM_Z2, 12288);
                             bulk_s2g(sc + offsetof(Scratch, rows) + (127 - b) * 4608, sb + SM_Z2, 4608);
                         }
                         if (G == RG1) {
                             bulk_s2g_nc(sc + offsetof(Scratch, y) + (NCTA * 18432u - c.yp) + b * 13824, sb + SM_Z2, 6912);
                             bulk_s2g(sc + offsetof(Scratch, y) + (NCTA * 18432u - c.yp) + b * 13824 + 6912, sb + SM_Z2, 6912);
                         }
                     }
                     if (!wg_is4<decltype(gi)>() && PF1 && G >= PF1 && G < PF1 + 2 && (warp >> 1) == 2) weight_prefetch(p, 17 + 2 * (G - PF1) + (warp & 1), lane_v());
                     if (!wg_is4<decltype(gi)>()) WPOINT(6 + G, warp == (G >= 7 ? HW : WSP ? 4 * (G % 3) + 1 : 12 + (G & 3)));
                     if (!wg_is4<decltype(gi)>() && G == XG && warp == HW) {
                         asm volatile("cp.async.bulk.wait_group 0;\n" ::: "memory");
                         __syncwarp();
                         if (elect_one()) mbar_arrive(bar_v);
                     }
                 };
        if (!ONEBAR) bar_sync(1 + wg, 128);
        if (wg < 4) {
            asm volatile("barrier.cluster.arrive.relaxed.aligned;\n" ::: "memory");
            conv_run(c, pln + wq * 128, gy, hook, [&]() {
                STAMPX(23);
                mbar_wait(bar_x);
                STAMP(9);
                STAMPX(24);
                uint2 xc[4];
                uint32_t xw[4][2];
#pragma unroll
                for (int j = 0; j < 4; j++) xc[j] = lds64(sb + SM_XC + wg * 8192 + j * 2048 + t128 * 16 + odd * 8);
#pragma unroll
                for (int i = 0; i < 8; i++) {
                    const int k = i >> 1, h = i & 1;
                    xw[k][h] = prmt_v(k < 2 ? xc[2 * h].x : xc[2 * h].y, k < 2 ? xc[2 * h + 1].x : xc[2 * h + 1].y, (k & 1) ? 0x7632 : 0x5410);
                }
                const uint32_t ub = mov_v(sb + SM_U + UPAD * 16 + ((tid >> 1) & 1) * ULO_B + (tid >> 2) * 16 + (tid & 1) * 8), tag = ep << 31;
                int it = 0;
                if (!PEARLY) first_poll(SDLY);
                while (min(min((int)(uv0.x ^ tag), (int)(uv0.y ^ tag)), min((int)(uv0.z ^ tag), (int)(uv0.w ^ tag))) < 0x10000) {
                    if (++it > SPIN_LIMIT) TRAP();
                    uv0 = ld_poll(usrc);
                }
                STAMP(8);
                STAMPX(26);
                const float r0 = rcp_approx(fabsf(bf_hi(uv0.x))), r1 = rcp_approx(fabsf(bf_hi(uv0.y))), r2 = rcp_approx(fabsf(bf_hi(uv0.z))), r3 = rcp_approx(fabsf(bf_hi(uv0.w)));
                const uint32_t m[2] = {__byte_perm(uv0.x, uv0.y, 0x5410), __byte_perm(uv0.z, uv0.w, 0x5410)};
                const uint32_t rh[2] = {pack_bf16(r0, r1), pack_bf16(r2, r3)};
                const uint32_t rl[2] = {pack_bf16(r0 - bf_lo(rh[0]), r1 - bf_hi(rh[0])), pack_bf16(r2 - bf_lo(rh[1]), r3 - bf_hi(rh[1]))};
#pragma unroll
                for (int k = 0; k < 4; k++) {
                    const uint32_t u0 = ln_apply(xw[k][0], m[0], rh[0], rl[0]), u1 = ln_apply(xw[k][1], m[1], rh[1], rl[1]);
                    sts64(ub + k * USLOT_B, pack_f16(bf_lo(u0), bf_hi(u0)), pack_f16(bf_lo(u1), bf_hi(u1)));
                }
                STAMPX(29);
                fence_async();
                bar_sync(14, DEFER == 1 ? NWRK : 512);
                STAMP(7);
            });
        } else {
            auto stage = [&]() {
                const uint32_t tag = (ep % 7u + 1u) * 0x10001u;
                int it = 0;
                WPOINT(4, warp == 19);
                first_poll(UDLY);
                uv1 = ld_poll(usrc + 512);
                WPOINT(5, warp == 19);
                while (true) {
                    uv0.x ^= tag; uv0.y ^= tag; uv0.z ^= tag; uv0.w ^= tag; uv1.x ^= tag; uv1.y ^= tag; uv1.z ^= tag; uv1.w ^= tag;
                    if ((((uv0.x | uv0.y | uv0.z) | (uv0.w | uv1.x | uv1.y) | (uv1.z | uv1.w)) & 0x70007u) == 0) break;
                    if (++it > SPIN_LIMIT) TRAP();
                    uv0 = ld_poll(usrc); uv1 = ld_poll(usrc + 512);
                }
                STAMP(8);
                const uint32_t ub = sb + SM_U + UPAD * 16 + 4 * USLOT_B + (t128 & 1) * ULO_B + (t128 >> 1) * 16;
                sts128(ub, uv0.x, uv0.y, uv0.z, uv0.w);
                sts128(ub + 1024, uv1.x, uv1.y, uv1.z, uv1.w);
                fence_async();
                asm volatile("barrier.cluster.arrive.relaxed.aligned;\n" ::: "memory");
                bar_sync(5, 128);
                STAMP(7);
            };
            stage();
            if (odd) conv_inner(c, pln + wq * 128, gy, sb + SM_RX, hook);
            else conv_outer(c, pln + wq * 128, gy, sb + SM_RX, hook);
        }
        STAMP(10);
    }
    {
    const int lane = lane_v(), tid = 32 * warp + lane, g = lane >> 2, t = lane & 3;
    const uint32_t par = ~ep & 1u;
    if (CBAR) bar_sync(0, NWRK);
    STAMP(11);
    uint32_t H[2][4] = {}, U2[2][4] = {};
    auto publish = [&](bool hi, int slot) {
        uint4* rowp = reinterpret_cast<uint4*>(p.s->rows) + slot * 144 + warp * 4 + t;
        stg128(rowp, nzw(hi ? U2[1][0] : U2[0][0]), nzw(hi ? U2[1][1] : U2[0][1]), nzw(hi ? U2[1][2] : U2[0][2]), nzw(hi ? U2[1][3] : U2[0][3]));
        stg128(rowp + 72, nzw(hi ? H[1][0] : H[0][0]), nzw(hi ? H[1][1] : H[0][1]), nzw(hi ? H[1][2] : H[0][2]), nzw(hi ? H[1][3] : H[0][3]));
    };
#define KTOK(k) (int)(((~(k) >> 5) & 0x7f0u) | (((k) >> 1) & 15u))
#define KLATE(k) (((k) & 0x1e0u) < 0xe0u)
#define KSLOT(k, s) (KLATE(k) ? 2 * NCTA + (s) : (int)(((k) >> 8) & 0xffu))
    const uint4* const rsrc = reinterpret_cast<const uint4*>(p.s->rows) + 36 * odd;
    auto gather = [&](uint32_t mine) {
        int it = 0;
        uint32_t mn;
        do {
            mn = 1;
#pragma unroll 1
            for (int r = 0; r < 9; r++) {
                const uint32_t k = __shfl_sync(0xffffffffu, mine, r < 8 ? 4 * r : lane);
                const int row = r < 8 ? r : g, c = r < 8 ? lane : 32 + t;
                asm volatile("cp.async.cg.shared.global [%0], [%1], 16;\n" ::"r"(sb + SM_XS + row * XS_PITCH + c * 16), "l"(rsrc + KSLOT(k, row) * 144 + c) : "memory");
            }
            asm volatile("cp.async.wait_all;\n" ::: "memory");
#pragma unroll 1
            for (int r = 0; r < 9; r++) mn = min(mn, min4(lds128(sb + SM_XS + (r < 8 ? r * XS_PITCH + lane * 16 : g * XS_PITCH + (32 + t) * 16))));
            if (++it > SPIN_LIMIT) TRAP();
        } while (__any_sync(0xffffffffu, mn == 0));
    };
    auto late_rows = [&](auto role) {
        const uint32_t kk = lds32(s_key + (lane & 7) * 4), ep = lds32(s_cnt + 4);
        const bool own = KLATE(kk) && (KTOK(kk) >> 4) == b;
        uint32_t todo = __ballot_sync(0xffffffffu, own) & 0xffu;
        if (decltype(role)::value == 0 && todo) {
#pragma unroll
            for (int hf = 0; hf < 2; hf++) {
                const uint4 h = lds128(sb + SM_U + hf * 9216 + tid * 16);
                const uint2 st = lds64(s_stat + (g + 8 * hf) * 8);
                H[hf][0] = h.x; H[hf][1] = h.y; H[hf][2] = h.z; H[hf][3] = h.w;
#pragma unroll
                for (int k = 0; k < 4; k++) U2[hf][k] = ln_apply(H[hf][k], STAT_M(st), STAT_H(st), STAT_L(st));
            }
#pragma unroll 1
            while (todo) {
                const int s = __ffs(todo) - 1, tk = KTOK(__shfl_sync(0xffffffffu, kk, s));
                todo &= todo - 1;
                if ((tk & 13) == TOK(g)) publish(tk & 2, 2 * NCTA + s);
            }
            __threadfence();
        }
        bar_sync(0, NWRK);
        if (decltype(role)::value == 1) {
            if (lane < NSEL && own) *reinterpret_cast<volatile unsigned*>(p.s->flag + lane) = ep + 1u;
            int it = 0;
            while (__any_sync(0xffffffffu, KLATE(kk) && ld_acquire32(p.s->flag + (lane & 7)) != ep + 1u)) { if (++it > SPIN_LIMIT) TRAP(); }
            gather(__shfl_sync(0xffffffffu, kk, g));
        }
        bar_sync(0, NWRK);
    };
    if (warp < 18) {
        const unsigned char* ys = reinterpret_cast<const unsigned char*>(p.s->y) + (b < 96 ? (par ^ 1u) * (NCTA * 18432u) : 0u) +
                                  ((P * DM + 32 * warp + 8 * (g >> 1) + (g & 1)) * 64 + odd * 32 + t * 8);
        uint2 yv[4];
        const bool early = YFROM && b < YFROM && warp < 16;
        if (early) {
#pragma unroll
            for (int k = 0; k < 4; k++) yv[k] = ld_poll64(ys + k * 128);
        }
        mbar_wait(bar_v);
        const uint32_t xa = sb + SM_XT + warp * 64 + t * 16;
        const uint4 x0 = lds128(xa + TOK(g) * 1152), x1 = lds128(xa + (TOK(g) + 2) * 1152), dk = lds128(xa + 16 * 1152);
        uint4 wr = make_uint4(0u, 0u, 0u, 0u);
        if (g == 0) wr = lds128(xa + 17 * 1152);
        const uint32_t Z[2][4] = {{x0.x, x0.y, x0.z, x0.w}, {x1.x, x1.y, x1.z, x1.w}}, D4[4] = {dk.x, dk.y, dk.z, dk.w};
#pragma unroll
        for (int hf = 0; hf < 2; hf++) {
            const uint2 st = lds64(s_stat + (g + 8 * hf) * 8);
#pragma unroll
            for (int k = 0; k < 4; k++) U2[hf][k] = hmul2_bf(ln_apply(Z[hf][k], STAT_M(st), STAT_H(st), STAT_L(st)), D4[k]);
        }
        const uint32_t la = pin(sb + SM_LNP + (g * 20 + warp) * 4 + (U2[0][3] & U2[1][3] & (warp >> 8)));
        if (YDLY > 1) delay(YDLY);
        int it = 0;
        float d[2][4];
        uint32_t mn;
        do {
            if (!early || it) {
#pragma unroll
                for (int k = 0; k < 4; k++) yv[k] = ld_poll64(ys + k * 128);
            }
            if (++it > SPIN_LIMIT) TRAP();
            mn = min(min(min(yv[0].x, yv[0].y), min(yv[1].x, yv[1].y)), min(min(yv[2].x, yv[2].y), min(yv[3].x, yv[3].y)));
#pragma unroll
            for (int k = 0; k < 4; k++) {
                H[0][k] = hadd2_bf(Z[0][k], hadd2_bf(movm(yv[k].x), U2[0][k]));
                H[1][k] = hadd2_bf(Z[1][k], hadd2_bf(movm(yv[k].y), U2[1][k]));
            }
            ln_partial(H, d);
        } while (__any_sync(0xffffffffu, mn == 0));
        STAMP(12);
        if (t == (g >> 1)) {
            stsf(la, (g & 1) ? d[0][3] : d[0][2]); stsf(la + 8 * 80, (g & 1) ? d[1][3] : d[1][2]);
            stsf(la + 16 * 80, (g & 1) ? d[0][1] : d[0][0]); stsf(la + 24 * 80, (g & 1) ? d[1][1] : d[1][0]);
        }
        bar_arrive(6, NWRK);
        STAMP(13);
        bar_sync(7, 608);
        STAMP(14);
#pragma unroll
        for (int hf = 0; hf < 2; hf++) {
            const uint2 st = lds64(s_stat + (g + 8 * hf) * 8);
#pragma unroll
            for (int k = 0; k < 4; k++) U2[hf][k] = ln_apply(H[hf][k], STAT_M(st), STAT_H(st), STAT_L(st));
        }
        {
            float cs[4] = {0.f, 0.f, 0.f, 0.f};
            mma_bf16(cs, U2[0][0], U2[1][0], U2[0][1], U2[1][1], wr.x, wr.y);
            mma_bf16(cs, U2[0][2], U2[1][2], U2[0][3], U2[1][3], wr.z, wr.w);
            if (t == 0) { stsf(la + 32 * 80, cs[0]); stsf(la + 40 * 80, cs[2]); }
            bar_arrive(8, 608);
        }
        bar_sync(9, 608);
        {
            const uint2 best = lds64(s_rank);
            if ((best.x & 26u) == 2 * TOK(g)) publish(best.x & 4u, 255 - 2 * b);
            if ((best.y & 26u) == 2 * TOK(g)) publish(best.y & 4u, 254 - 2 * b);
        }
#pragma unroll
        for (int hf = 0; hf < 2; hf++) {
            sts128(sb + SM_OUT + (TOK(g) + 2 * hf) * (DM * 2) + warp * 64 + t * 16,
                   hadd2_bf(H[hf][0], U2[hf][0]), hadd2_bf(H[hf][1], U2[hf][1]), hadd2_bf(H[hf][2], U2[hf][2]), hadd2_bf(H[hf][3], U2[hf][3]));
            sts128(sb + SM_U + hf * 9216 + tid * 16, H[hf][0], H[hf][1], H[hf][2], H[hf][3]);
        }
        STAMP(15);
        fence_async();
        const int mi = lane >> 3, rr = lane & 7;
        if (warp < 9) {
            uint32_t W[18][4];
            mbar_wait(bar_w);
            const uint32_t aad = sb + SM_WG + (mi & 1) * SM_WU + (rr + 8 * (mi >> 1)) * W_PITCH + warp * 16;
#pragma unroll
            for (int k = 0; k < 18; k++) ldsm_x4_t(W[k][0], W[k][1], W[k][2], W[k][3], aad + k * 16 * W_PITCH);
            const uint32_t bad = pin(sb + SM_XS + rr * XS_PITCH + mi * 16);
            STAMP2(17);
            if (bar_or(11, NWRK, false)) {
                late_rows(IC<0>());
#pragma unroll
                for (int k = 0; k < 18; k++) ldsm_x4_t(W[k][0], W[k][1], W[k][2], W[k][3], aad + k * 16 * W_PITCH);
            }
            STAMP2(19);
            float c4[2][4] = {};
#pragma unroll
            for (int k = 0; k < 18; k += 2) {
                uint32_t b0, b1, b2, b3;
                ldsm_x4(b0, b1, b2, b3, bad + k * 32);
                mma_bf16(c4[0], W[k][0], W[k][1], W[k][2], W[k][3], b0, b1);
                mma_bf16(c4[1], W[k + 1][0], W[k + 1][1], W[k + 1][2], W[k + 1][3], b2, b3);
            }
            const uint32_t ex = sb + SM_EX + tid * 16;
            const float e0 = c4[0][0] + c4[1][0], e1 = c4[0][1] + c4[1][1], e2 = c4[0][2] + c4[1][2], e3 = c4[0][3] + c4[1][3];
            asm volatile("st.async.shared::cluster.mbarrier::complete_tx::bytes.v4.f32 [%0], {%1,%2,%3,%4}, [%5];\n"
                         ::"r"(ex ^ 0x1000000u), "f"(e0), "f"(e1), "f"(e2), "f"(e3), "r"(bar_g ^ 0x1000000u) : "memory");
            STAMP2(20);
            mbar_wait(bar_g);
            const uint4 o = lds128(ex);
            const uint32_t G = pack_bf16(e0 + __uint_as_float(o.x), e1 + __uint_as_float(o.y)), U = pack_bf16(e2 + __uint_as_float(o.z), e3 + __uint_as_float(o.w));
            sts32(sb + SM_GU + tid * 4, hmul2_bf(pack_bf16(bf_lo(G) * sigmoid_f(bf_lo(G)), bf_hi(G) * sigmoid_f(bf_hi(G))), U));
            bar_arrive(13, NWRK);
        } else {
            uint32_t W[2][18];
            mbar_wait(bar_d);
            const uint32_t base = sb + SM_WD + (4 * (warp - 9) + (mi & 1)) * 16 + rr * WD_PITCH;
#pragma unroll
            for (int j = 0; j < 2; j++) {
#pragma unroll
                for (int k = 0; k < 4; k++) ldsm_x4_t(W[j][4 * k], W[j][4 * k + 1], W[j][4 * k + 2], W[j][4 * k + 3], base + j * 32 + (k * 16 + 8 * (mi >> 1)) * WD_PITCH);
                ldsm_x2_t(W[j][16], W[j][17], base + j * 32 + 64 * WD_PITCH);
            }
            const uint32_t po = pin((((8 * (18 * odd + 2 * (warp - 9)) + g) * 64 + P) * 16 + t * 4) * 4);
            STAMP2(17);
            if (bar_or(11, NWRK, false)) late_rows(IC<0>());
            bar_sync(13, NWRK);
            STAMP2(21);
            uint32_t gb[9];
            ldsm_x4_t(gb[0], gb[1], gb[2], gb[3], sb + SM_GU + lane * 16);
            ldsm_x4_t(gb[4], gb[5], gb[6], gb[7], sb + SM_GU + 512 + lane * 16);
            ldsm_x1_t(gb[8], sb + SM_GU + 1024 + lane * 16);
            float c4[2][4] = {}, d4[2][4] = {};
#pragma unroll
            for (int k = 0; k < 4; k += 2)
#pragma unroll
                for (int j = 0; j < 2; j++) {
                    mma_bf16(c4[j], W[j][4 * k], W[j][4 * k + 1], W[j][4 * k + 2], W[j][4 * k + 3], gb[2 * k], gb[2 * k + 1]);
                    mma_bf16(d4[j], W[j][4 * k + 4], W[j][4 * k + 5], W[j][4 * k + 6], W[j][4 * k + 7], gb[2 * k + 2], gb[2 * k + 3]);
                }
#pragma unroll
            for (int j = 0; j < 2; j++) mma_bf16_k8(c4[j], W[j][16], W[j][17], gb[8]);
#pragma unroll
            for (int j = 0; j < 2; j++)
                stg128(reinterpret_cast<unsigned char*>(p.s->part) + po + j * 32768, __float_as_uint(c4[j][0] + d4[j][0]) | 1u, __float_as_uint(c4[j][1] + d4[j][1]) | 1u,
                       __float_as_uint(c4[j][2] + d4[j][2]) | 1u, __float_as_uint(c4[j][3] + d4[j][3]) | 1u);
        }
        STAMP2(22);
    } else if (warp == 18) {
        bar_sync(6, NWRK);
        {
            float mb, rc;
            ln_finish(sum18(sb + SM_LNP + lane * 80), lane, mb, rc);
            if (lane < 16) stat_store(s_stat + lane * 8, mb, rc, 0u);
        }
        bar_arrive(7, 608);
        const uint32_t klo = pin((uint32_t)(127 - b) << 9 | (uint32_t)(15 - ROWTOK(lane & 15)) << 1 | par), ra = pin(sb + SM_LNP + (32 + (lane & 15)) * 80);
        uint4* const kdst = reinterpret_cast<uint4*>(p.s->key3) + pin(2 * b + (lane & 1));
        bar_sync(8, 608);
        uint32_t t0;
        {
            const uint32_t bits = __float_as_uint(rbf(sum18(ra)));
            const uint32_t me = ((bits ^ ((uint32_t)((int)bits >> 31) | 0x80000000u)) & 0xffff0000u) | klo;
            const uint32_t k0 = __reduce_max_sync(0xffffffffu, me), k1 = __reduce_max_sync(0xffffffffu, me == k0 ? 0u : me);
            const uint32_t k2 = __reduce_max_sync(0xffffffffu, me >= k1 ? 0u : me);
            if (lane < 2) stg128(kdst, k0 ^ 0x11eu, k1 ^ 0xfeu, k2 ^ 0xdeu, par);
            asm volatile("mov.u32 %0, %%clock;" : "=r"(t0) :: "memory");
            STAMPW(23);
            if (lane == 0) sts64(s_rank, ~k0, ~k1);
            bar_arrive(9, 608);
            sts32(s_k16 + (lane & 15) * 4, me);
            __syncwarp();
            const uint4 v = lds128(s_k16 + (lane & 16) * 2), w = lds128(s_k16 + (lane & 16) * 2 + 16);
            int rank = ((v.x > me) + (v.y > me)) + ((v.z > me) + (v.w > me)) + (((w.x > me) + (w.y > me)) + ((w.z > me) + (w.w > me)));
            rank += __shfl_xor_sync(0xffffffffu, rank, 16);
            if (lane < 16 && rank < 8) p.s->key[8 * b + rank] = (me ^ 0x1eu) | ((8 - rank) << 5);
        }
        const uint4* const ksrc = reinterpret_cast<const uint4*>(p.s->key3) + pin(2 * lane);
        const unsigned char* const rl = reinterpret_cast<const unsigned char*>(rsrc) + pin(lane * 16);
        uint4 kq[4];
        uint32_t u[4], mine = 0, m;
        int it = 0;
        { uint32_t now; do { asm volatile("mov.u32 %0, %%clock;" : "=r"(now) :: "memory"); } while (now - t0 < KDLY); }
        do {
#pragma unroll
            for (int i = 0; i < 4; i++) kq[i] = ld_poll(ksrc + 64 * i);
            if (++it > SPIN_LIMIT) TRAP();
            uint32_t S[2][4];
#pragma unroll
            for (int i = 0; i < 2; i++) {
                const uint4 &c = kq[2 * i], &d = kq[2 * i + 1];
                const uint32_t m1 = min(c.x, d.x), m2 = max(c.y, d.y);
                S[i][0] = max(c.x, d.x); S[i][1] = max(m1, m2); S[i][2] = min(m1, m2); S[i][3] = min(c.y, d.y);
            }
            const uint32_t a0 = max(S[0][0], S[1][3]), a1 = max(S[0][1], S[1][2]), a2 = max(S[0][2], S[1][1]), a3 = max(S[0][3], S[1][0]);
            const uint32_t b0 = max(a0, a2), b2 = min(a0, a2), b1 = max(a1, a3), b3 = min(a1, a3);
            u[0] = max(b0, b1); u[1] = min(b0, b1); u[2] = max(b2, b3); u[3] = min(b2, b3);
        } while (__any_sync(0xffffffffu, and3(or3(or3(xor_or(kq[0].x, kq[0].y, par), xor_or(kq[0].z, kq[1].x, par), xor_or(kq[1].y, kq[1].z, par)),
                                                  xor_or(kq[2].x, kq[2].y, par), xor_or(kq[2].z, kq[3].x, par)) | xor_or(kq[3].y, kq[3].z, par), 1u, 1u)));
        STAMPW(16);
        uint4 v[9];
#pragma unroll
        for (int r = 0; r < 8; r++) {
            m = __reduce_max_sync(0xffffffffu, u[0]);
            if (u[0] == m) { u[0] = u[1]; u[1] = u[2]; u[2] = u[3]; u[3] = 0; }
            if (g == r) mine = m;
            v[r] = ld_poll(rl + (size_t)((m >> 8) & 0xffu) * 2304u);
        }
        v[8] = ld_poll(reinterpret_cast<const unsigned char*>(rsrc) + (((mine >> 8) & 0xffu) * 2304u + (32 + t) * 16));
        bool again = __any_sync(0xffffffffu, u[0] == 0 || max(max(kq[0].z, kq[1].z), max(kq[2].z, kq[3].z)) > m);
        if (again) {
#pragma unroll 1
            for (int i = 0; i < 8; i++) {
                uint4 k;
                do { k = ld_poll(reinterpret_cast<const uint4*>(p.s->key) + 32 * i + lane); if (++it > SPIN_LIMIT) TRAP(); } while (((k.x ^ par) | (k.y ^ par) | (k.z ^ par) | (k.w ^ par)) & 1u);
                sts128(sb + SM_KEYS + (32 * i + lane) * 16, k.x, k.y, k.z, k.w);
            }
            m = 0xffffffffu;
#pragma unroll 1
            for (int r = 0; r < 8; r++) {
                uint32_t c = 0;
#pragma unroll 2
                for (int i = 0; i < 8; i++) {
                    const uint4 k = lds128(sb + SM_KEYS + (32 * i + lane) * 16);
                    c = max(max(c, k.x < m ? k.x : 0u), max(k.y < m ? k.y : 0u, max(k.z < m ? k.z : 0u, k.w < m ? k.w : 0u)));
                }
                m = __reduce_max_sync(0xffffffffu, c);
                if (g == r) mine = m;
            }
        }
        if (t == 0) sts32(s_key + g * 4, mine);
        uint32_t mn = 1;
#pragma unroll
        for (int r = 0; r < 9; r++) {
            sts128(sb + SM_XS + (r < 8 ? r * XS_PITCH + lane * 16 : g * XS_PITCH + (32 + t) * 16), v[r].x, v[r].y, v[r].z, v[r].w);
            mn = min(mn, min4(v[r]));
        }
        if ((again || __any_sync(0xffffffffu, mn == 0)) && !__any_sync(0xffffffffu, KLATE(mine))) gather(mine);
        STAMPW(18);
        if (bar_or(11, NWRK, KLATE(mine))) late_rows(IC<1>());
    } else {
        bar_sync(6, NWRK);
        WPOINT(16, true);
        if (wsched(18) > wsched(17)) delay(WDLY);
        WPOINT(17, true);
        if (wsched(19) > wsched(18)) delay(WDLY);
        WPOINT(18, true);
        if (bar_or(11, NWRK, false)) late_rows(IC<2>());
        const int tk = KTOK(lds32(s_key + (lane & 7) * 4));
        const uint32_t sel = __reduce_or_sync(0xffffffffu, (tk >> 4) == b ? 1u << (tk & 15) : 0u);
        if (ODLY) delay(ODLY);
        if (!(EXP & 1)) if (sel ? lane < 16 && !((sel >> lane) & 1u) : lane == 0) bulk_s2g(p.out + (size_t)(16 * b + lane) * DM, sb + SM_OUT + lane * (DM * 2), sel ? DM * 2 : 16 * DM * 2);
        __syncwarp();
    }
    if (warp == 8 || warp >= 18) {
        const int grp = 3 * b + (warp == 8 ? 0 : warp - 17), fsl = 2 * t + ((lane >> 3) & 1), fc = 16 * (grp >> 3) + (grp & 7) + 8 * (lane >> 4);
        const uint32_t fk = lds32(s_key + fsl * 4);
        float hv = 0.f, u2 = 0.f;
        int it = 0;
        if (b < 96) {
            const uint32_t* const fsrc = p.s->rows + KSLOT(fk, fsl) * DM + (fc >> 1);
            uint32_t hw, uw;
            do { hw = ld_poll32(fsrc + 288); uw = ld_poll32(fsrc); if (++it > SPIN_LIMIT) TRAP(); } while (!hw || !uw);
            hv = (fc & 1) ? bf_hi(hw) : bf_lo(hw); u2 = (fc & 1) ? bf_hi(uw) : bf_lo(uw);
        }
        const float rs = rbf(sigmoid_f(__uint_as_float((fk ^ ((uint32_t)((int)~fk >> 31) | 0x80000000u)) & 0xffff0000u)));
        const uint32_t dof = pin(KTOK(fk) * DM + fc), so = pin(grp * 256 + lane);
        if (warp > 17) bar_sync(13, NWRK);
        if (b < 96) {
            delay(warp > 17 ? FDLY : FDLY2);
            const uint4* src = reinterpret_cast<const uint4*>(p.s->part) + so;
            float s0, s1, s2, s3;
            uint32_t ok;
            do {
                uint4 a[8];
#pragma unroll
                for (int i = 0; i < 8; i++) a[i] = ld_poll(src + 32 * i);
                if (++it > SPIN_LIMIT) TRAP();
#define A4(i) and3(and3(a[i].x, a[i].y, a[i].z), and3(a[i].w, a[i + 1].x, a[i + 1].y), a[i + 1].z & a[i + 1].w)
#define S8(f) (((__uint_as_float(a[0].f) + __uint_as_float(a[1].f)) + (__uint_as_float(a[2].f) + __uint_as_float(a[3].f))) + \
               ((__uint_as_float(a[4].f) + __uint_as_float(a[5].f)) + (__uint_as_float(a[6].f) + __uint_as_float(a[7].f))))
                ok = and3(A4(0), A4(2), and3(A4(4), A4(6), 1u));
                s0 = S8(x); s1 = S8(y); s2 = S8(z); s3 = S8(w);
                asm volatile("" : "+f"(s0), "+f"(s1), "+f"(s2), "+f"(s3));
#undef A4
#undef S8
            } while (__any_sync(0xffffffffu, !ok));
            STAMP2(24);
            const bool up = lane & 16, od = lane & 8;
            const float r0 = (up ? s2 : s0) + __shfl_xor_sync(0xffffffffu, up ? s0 : s2, 16), r1 = (up ? s3 : s1) + __shfl_xor_sync(0xffffffffu, up ? s1 : s3, 16);
            float y = (od ? r1 : r0) + __shfl_xor_sync(0xffffffffu, od ? r0 : r1, 8);
            y += __shfl_xor_sync(0xffffffffu, y, 4);
            p.out[dof] = __float2bfloat16_rn(hv + rbf(u2 + rbf(rbf(y) * rs)));
        }
    }
    if (warp == 19) asm volatile("cp.async.bulk.wait_group.read 0;\n" ::: "memory");
    if (b == 0 && tid < 8) *reinterpret_cast<volatile unsigned*>(p.s->hint + tid * 32 + 1) = lds32(s_cnt + 4) + 1u;
    STAMP(25);
    }
}

typedef CUresult (*PFN_tmEncode)(CUtensorMap*, CUtensorMapDataType, cuuint32_t, void*, const cuuint64_t*, const cuuint64_t*, const cuuint32_t*,
                                 const cuuint32_t*, CUtensorMapInterleave, CUtensorMapSwizzle, CUtensorMapL2promotion, CUtensorMapFloatOOBfill);

extern "C" void kernel_launch(void* const* d_in, const int* in_sizes, int n_in, void* d_out, int out_size) {
    Params p;
    p.x = (const bf16*)d_in[0];
    p.lar = (const bf16*)d_in[1];
    p.aim = (const bf16*)d_in[2];
    p.cre = (const bf16*)d_in[3];
    p.cim = (const bf16*)d_in[4];
    p.ldt = (const bf16*)d_in[5];
    p.dsk = (const bf16*)d_in[6];
    p.wr = (const bf16*)d_in[8];
    p.wg = (const bf16*)d_in[9];
    p.wu = (const bf16*)d_in[10];
    p.wd = (const bf16*)d_in[11];
    p.out = (bf16*)d_out;
    static PFN_tmEncode enc = nullptr;
    static void* scratch = nullptr;
    if (!enc) {
        cudaFuncSetAttribute(fused_kernel, cudaFuncAttributeMaxDynamicSharedMemorySize, SMEM_TOTAL);
        void* fn = nullptr;
        cudaDriverEntryPointQueryResult qr;
        cudaGetDriverEntryPoint("cuTensorMapEncodeTiled", &fn, cudaEnableDefault, &qr);
        enc = (PFN_tmEncode)fn;
        cudaGetSymbolAddress(&scratch, g_scratch);
    }
    p.s = (Scratch*)scratch;
    CUtensorMap tm_g, tm_u, tm_d, tm_x;
    const cuuint64_t dims[2] = {FF, DM}, strides[1] = {FF * 2};
    const cuuint32_t box[2] = {72, 48}, es[2] = {1, 1};
    enc(&tm_g, CU_TENSOR_MAP_DATA_TYPE_BFLOAT16, 2, d_in[9], dims, strides, box, es, CU_TENSOR_MAP_INTERLEAVE_NONE, CU_TENSOR_MAP_SWIZZLE_NONE,
        CU_TENSOR_MAP_L2_PROMOTION_NONE, CU_TENSOR_MAP_FLOAT_OOB_FILL_NONE);
    enc(&tm_u, CU_TENSOR_MAP_DATA_TYPE_BFLOAT16, 2, d_in[10], dims, strides, box, es, CU_TENSOR_MAP_INTERLEAVE_NONE, CU_TENSOR_MAP_SWIZZLE_NONE,
        CU_TENSOR_MAP_L2_PROMOTION_NONE, CU_TENSOR_MAP_FLOAT_OOB_FILL_NONE);
    const cuuint64_t ddims[2] = {DM / 2, FF}, dstrides[1] = {DM * 2};
    const cuuint32_t dbox[2] = {WD_PITCH / 4, 8};
    enc(&tm_d, CU_TENSOR_MAP_DATA_TYPE_UINT32, 2, d_in[11], ddims, dstrides, dbox, es, CU_TENSOR_MAP_INTERLEAVE_NONE, CU_TENSOR_MAP_SWIZZLE_NONE,
        CU_TENSOR_MAP_L2_PROMOTION_NONE, CU_TENSOR_MAP_FLOAT_OOB_FILL_NONE);
    const cuuint64_t xdims[4] = {DM, 128, 4, 4}, xstrides[3] = {DM * 8, DM * 2, DM * 1024};
    const cuuint32_t xbox[4] = {8, 128, 4, 2}, xes[4] = {1, 1, 1, 1};
    enc(&tm_x, CU_TENSOR_MAP_DATA_TYPE_BFLOAT16, 4, d_in[0], xdims, xstrides, xbox, xes, CU_TENSOR_MAP_INTERLEAVE_NONE, CU_TENSOR_MAP_SWIZZLE_NONE,
        CU_TENSOR_MAP_L2_PROMOTION_NONE, CU_TENSOR_MAP_FLOAT_OOB_FILL_NONE);
    fused_kernel<<<NCTA, NTHR, SMEM_TOTAL>>>(p, tm_g, tm_u, tm_d, tm_x);
}
```

```cpp
#include <cuda_runtime.h>
#include <cuda.h>
#include <cuda_fp16.h>
#include <cuda_bf16.h>
#include <stdint.h>

#define LSEQ 2048
#define DM 576
#define NST 128
#define FF 4608
#define NSEL 8
#define NCTA 128
#define NTHR 640
#define NWRK 640

typedef __nv_bfloat16 bf16;

#define SM_WG 0
#define SM_WU 41472
#define SM_XC (82944 - 32768)
#define SM_WD 82944
#define W_PITCH 144
#define WD_PITCH 592
#define SM_Z2 (SM_WD + 10240)
#define SM_XT (SM_PL - 18 * 1152)
#define SM_PL (SM_WD + 46080)
#define PL_HALF 1344
#define PLW_B 2624
#define PL_B (4 * PLW_B)
#define SM_U (SM_PL + 5 * PL_B)
#define UPAD 20
#define ULO_B ((UPAD + 128) * 16)
#define USLOT_B (2 * ULO_B)
#define SM_KW (SM_U + 5 * USLOT_B)
#define KW_B 3712
#define KW_PL 1216
#define KW_P 2400
#define KW_H 3440
#define SM_MISC (SM_KW + 5 * KW_B)
#define SM_LC (SM_MISC + 384)
#define SM_LNP (SM_LC + 768)
#define SM_RX (SM_LNP + 3840)
#define SMEM_TOTAL (SM_RX + 3088)
#define TBW PLW_B
#define SM_OUT SM_PL
#define SM_XS (SM_PL + 18432)
#define XS_PITCH 592
#define SM_GU (SM_PL + 23296)
#define SM_EX (SM_PL + 24576)
#define SM_KEYS SM_KW

#define KA 1
#define SA 1
struct __align__(128) Scratch {
    unsigned hint[8 * 32];
    unsigned flag[32];
    uint32_t key3[KA * NCTA * 8];
    uint32_t key[NCTA * 8];
    uint32_t stat[SA * LSEQ];
    uint32_t uT[64 * (LSEQ / 2)];
    uint32_t y[(NCTA + 96) * DM * 8];
    uint32_t part[288 * 64 * 16];
    uint32_t rows[(2 * NCTA + NSEL) * DM];
};
__device__ Scratch g_scratch;
#define STAMP(i)
#define STAMPX(i)
#define STAMPY(i)

__device__ __forceinline__ float rbf(float x) {
    uint32_t r;
    asm("cvt.rn.bf16x2.f32 %0, %1, %2;\n" : "=r"(r) : "f"(x), "f"(0.f));
    return __uint_as_float(r);
}
__device__ __forceinline__ uint32_t pack_bf16(float lo, float hi) {
    uint32_t r;
    asm("cvt.rn.bf16x2.f32 %0, %1, %2;\n" : "=r"(r) : "f"(hi), "f"(lo));
    return r;
}
__device__ __forceinline__ uint32_t pack_f16(float lo, float hi) {
    uint32_t r;
    asm("cvt.rn.f16x2.f32 %0, %1, %2;\n" : "=r"(r) : "f"(hi), "f"(lo));
    return r;
}
__device__ __forceinline__ uint32_t pack_f16_rz(float lo, float hi) {
    uint32_t r;
    asm("cvt.rz.f16x2.f32 %0, %1, %2;\n" : "=r"(r) : "f"(hi), "f"(lo));
    return r;
}
__device__ __forceinline__ float bf_lo(uint32_t w) { return __uint_as_float(w << 16); }
__device__ __forceinline__ float bf_hi(uint32_t w) { return __uint_as_float(w & 0xffff0000u); }
__device__ __forceinline__ uint32_t hadd2_bf(uint32_t a, uint32_t b) {
    __nv_bfloat162 r = __hadd2_rn(*reinterpret_cast<__nv_bfloat162*>(&a), *reinterpret_cast<__nv_bfloat162*>(&b));
    return *reinterpret_cast<uint32_t*>(&r);
}
__device__ __forceinline__ uint32_t hsub2_bf(uint32_t a, uint32_t b) {
    __nv_bfloat162 r = __hsub2_rn(*reinterpret_cast<__nv_bfloat162*>(&a), *reinterpret_cast<__nv_bfloat162*>(&b));
    return *reinterpret_cast<uint32_t*>(&r);
}
__device__ __forceinline__ uint32_t hmul2_bf(uint32_t a, uint32_t b) {
    __nv_bfloat162 r = __hmul2_rn(*reinterpret_cast<__nv_bfloat162*>(&a), *reinterpret_cast<__nv_bfloat162*>(&b));
    return *reinterpret_cast<uint32_t*>(&r);
}
__device__ __forceinline__ uint32_t hfma2_bf(uint32_t a, uint32_t b, uint32_t c) { uint32_t r; asm("fma.rn.bf16x2 %0, %1, %2, %3;\n" : "=r"(r) : "r"(a), "r"(b), "r"(c)); return r; }
__device__ __forceinline__ uint32_t hmul2(uint32_t a, uint32_t b) { uint32_t r; asm("mul.rn.f16x2 %0, %1, %2;\n" : "=r"(r) : "r"(a), "r"(b)); return r; }
__device__ __forceinline__ uint32_t hadd2(uint32_t a, uint32_t b) { uint32_t r; asm("add.rn.f16x2 %0, %1, %2;\n" : "=r"(r) : "r"(a), "r"(b)); return r; }
__device__ __forceinline__ uint32_t hfma2(uint32_t a, uint32_t b, uint32_t c) { uint32_t r; asm("fma.rn.f16x2 %0, %1, %2, %3;\n" : "=r"(r) : "r"(a), "r"(b), "r"(c)); return r; }
__device__ __forceinline__ uint32_t hfms2(uint32_t a, uint32_t b, uint32_t c) {
    uint32_t r;
    asm("{\n.reg .b32 n;\nneg.f16x2 n, %2;\nfma.rn.f16x2 %0, %1, n, %3;\n}\n" : "=r"(r) : "r"(a), "r"(b), "r"(c));
    return r;
}
__device__ __forceinline__ uint32_t nzw(uint32_t w) { return max(w, 1u); }
__device__ __forceinline__ uint32_t nzf(float f) { const uint32_t w = __float_as_uint(f); return w ? w : 0x80000000u; }
__device__ __forceinline__ uint32_t smem_u32(const void* p) { return (uint32_t)__cvta_generic_to_shared(p); }
__device__ __forceinline__ uint32_t lds32(uint32_t addr) {
    uint32_t v;
    asm volatile("ld.shared.u32 %0, [%1];\n" : "=r"(v) : "r"(addr) : "memory");
    return v;
}
__device__ __forceinline__ uint32_t lds16(uint32_t addr) {
    unsigned short v;
    asm volatile("ld.shared.u16 %0, [%1];\n" : "=h"(v) : "r"(addr) : "memory");
    return v;
}
__device__ __forceinline__ uint2 lds64(uint32_t addr) {
    uint2 v;
    asm volatile("ld.shared.v2.u32 {%0,%1}, [%2];\n" : "=r"(v.x), "=r"(v.y) : "r"(addr) : "memory");
    return v;
}
__device__ __forceinline__ uint4 lds128(uint32_t addr) {
    uint4 v;
    asm volatile("ld.shared.v4.u32 {%0,%1,%2,%3}, [%4];\n" : "=r"(v.x), "=r"(v.y), "=r"(v.z), "=r"(v.w) : "r"(addr) : "memory");
    return v;
}
__device__ __forceinline__ float ldsf(uint32_t addr) { return __uint_as_float(lds32(addr)); }
__device__ __forceinline__ void sts32(uint32_t addr, uint32_t v) { asm volatile("st.shared.u32 [%0], %1;\n" ::"r"(addr), "r"(v) : "memory"); }
__device__ __forceinline__ void sts16(uint32_t addr, uint32_t v) { asm volatile("st.shared.u16 [%0], %1;\n" ::"r"(addr), "h"((unsigned short)v) : "memory"); }
__device__ __forceinline__ void stsf(uint32_t addr, float v) { sts32(addr, __float_as_uint(v)); }
__device__ __forceinline__ void sts64(uint32_t addr, uint32_t a, uint32_t b) { asm volatile("st.shared.v2.u32 [%0], {%1,%2};\n" ::"r"(addr), "r"(a), "r"(b) : "memory"); }
__device__ __forceinline__ void sts64f(uint32_t addr, float a, float b) { sts64(addr, __float_as_uint(a), __float_as_uint(b)); }
__device__ __forceinline__ void sts128(uint32_t addr, uint32_t a, uint32_t b, uint32_t c, uint32_t d) {
    asm volatile("st.shared.v4.u32 [%0], {%1,%2,%3,%4};\n" ::"r"(addr), "r"(a), "r"(b), "r"(c), "r"(d) : "memory");
}
__device__ __forceinline__ void sts128f(uint32_t addr, const float (&v)[4]) {
    sts128(addr, __float_as_uint(v[0]), __float_as_uint(v[1]), __float_as_uint(v[2]), __float_as_uint(v[3]));
}
__device__ __forceinline__ void ldsm_x4(uint32_t& r0, uint32_t& r1, uint32_t& r2, uint32_t& r3, uint32_t addr) {
    asm volatile("ldmatrix.sync.aligned.m8n8.x4.shared.b16 {%0,%1,%2,%3}, [%4];\n"
                 : "=r"(r0), "=r"(r1), "=r"(r2), "=r"(r3) : "r"(addr) : "memory");
}
__device__ __forceinline__ void ldsm_x4_t(uint32_t& r0, uint32_t& r1, uint32_t& r2, uint32_t& r3, uint32_t addr) {
    asm volatile("ldmatrix.sync.aligned.m8n8.x4.trans.shared.b16 {%0,%1,%2,%3}, [%4];\n"
                 : "=r"(r0), "=r"(r1), "=r"(r2), "=r"(r3) : "r"(addr) : "memory");
}
__device__ __forceinline__ void ldsm_x2_t(uint32_t& r0, uint32_t& r1, uint32_t addr) {
    asm volatile("ldmatrix.sync.aligned.m8n8.x2.trans.shared.b16 {%0,%1}, [%2];\n" : "=r"(r0), "=r"(r1) : "r"(addr) : "memory");
}
__device__ __forceinline__ void ldsm_x1_t(uint32_t& r0, uint32_t addr) {
    asm volatile("ldmatrix.sync.aligned.m8n8.x1.trans.shared.b16 {%0}, [%1];\n" : "=r"(r0) : "r"(addr) : "memory");
}
__device__ __forceinline__ void stsm_x4(uint32_t addr, uint32_t r0, uint32_t r1, uint32_t r2, uint32_t r3) {
    asm volatile("stmatrix.sync.aligned.m8n8.x4.shared.b16 [%0], {%1,%2,%3,%4};\n" ::"r"(addr), "r"(r0), "r"(r1), "r"(r2), "r"(r3) : "memory");
}
__device__ __forceinline__ void stsm_x4_t(uint32_t addr, uint32_t r0, uint32_t r1, uint32_t r2, uint32_t r3) {
    asm volatile("stmatrix.sync.aligned.m8n8.x4.trans.shared.b16 [%0], {%1,%2,%3,%4};\n" ::"r"(addr), "r"(r0), "r"(r1), "r"(r2), "r"(r3) : "memory");
}
__device__ __forceinline__ uint32_t movm(uint32_t a) {
    uint32_t d;
    asm volatile("movmatrix.sync.aligned.m8n8.trans.b16 %0, %1;\n" : "=r"(d) : "r"(a));
    return d;
}
__device__ __forceinline__ void mma_f16(float (&c)[4], uint32_t a0, uint32_t a1, uint32_t a2, uint32_t a3, uint32_t b0, uint32_t b1) {
    asm volatile(
        "mma.sync.aligned.m16n8k16.row.col.f32.f16.f16.f32 {%0,%1,%2,%3}, {%4,%5,%6,%7}, {%8,%9}, {%0,%1,%2,%3};\n"
        : "+f"(c[0]), "+f"(c[1]), "+f"(c[2]), "+f"(c[3])
        : "r"(a0), "r"(a1), "r"(a2), "r"(a3), "r"(b0), "r"(b1));
}
__device__ __forceinline__ void mma_bf16(float (&c)[4], uint32_t a0, uint32_t a1, uint32_t a2, uint32_t a3, uint32_t b0, uint32_t b1) {
    asm volatile(
        "mma.sync.aligned.m16n8k16.row.col.f32.bf16.bf16.f32 {%0,%1,%2,%3}, {%4,%5,%6,%7}, {%8,%9}, {%0,%1,%2,%3};\n"
        : "+f"(c[0]), "+f"(c[1]), "+f"(c[2]), "+f"(c[3])
        : "r"(a0), "r"(a1), "r"(a2), "r"(a3), "r"(b0), "r"(b1));
}
__device__ __forceinline__ void mma_bf16_k8(float (&c)[4], uint32_t a0, uint32_t a1, uint32_t b0) {
    asm volatile("mma.sync.aligned.m16n8k8.row.col.f32.bf16.bf16.f32 {%0,%1,%2,%3}, {%4,%5}, {%6}, {%0,%1,%2,%3};\n"
                 : "+f"(c[0]), "+f"(c[1]), "+f"(c[2]), "+f"(c[3]) : "r"(a0), "r"(a1), "r"(b0));
}
__device__ __forceinline__ void bar_sync(int id, int n) { asm volatile("bar.sync %0, %1;\n" ::"r"(id), "r"(n) : "memory"); }
__device__ __forceinline__ void bar_arrive(int id, int n) { asm volatile("bar.arrive %0, %1;\n" ::"r"(id), "r"(n) : "memory"); }
__device__ __forceinline__ bool bar_or(int id, int n, bool v) {
    uint32_t r;
    asm volatile("{\n.reg .pred p, q;\nsetp.ne.u32 p, %3, 0;\nbar.red.or.pred q, %1, %2, p;\nselp.u32 %0, 1, 0, q;\n}\n" : "=r"(r) : "r"(id), "r"(n), "r"((uint32_t)v) : "memory");
    return r;
}
__device__ __forceinline__ uint32_t and3(uint32_t a, uint32_t b, uint32_t c) { uint32_t r; asm("lop3.b32 %0, %1, %2, %3, 0x80;\n" : "=r"(r) : "r"(a), "r"(b), "r"(c)); return r; }
__device__ __forceinline__ uint32_t or3(uint32_t a, uint32_t b, uint32_t c) { uint32_t r; asm("lop3.b32 %0, %1, %2, %3, 0xfe;\n" : "=r"(r) : "r"(a), "r"(b), "r"(c)); return r; }
__device__ __forceinline__ uint32_t xor_or(uint32_t a, uint32_t b, uint32_t c) { uint32_t r; asm("lop3.b32 %0, %1, %2, %3, 0x7e;\n" : "=r"(r) : "r"(a), "r"(b), "r"(c)); return r; }
__device__ __forceinline__ uint32_t pin(uint32_t v) { uint32_t r; asm volatile("shfl.sync.bfly.b32 %0, %1, 0, 0x1f, 0xffffffff;\n" : "=r"(r) : "r"(v) : "memory"); return r; }
__device__ __forceinline__ uint4 ld_poll(const void* p) {
    uint4 v;
    asm volatile("ld.relaxed.gpu.global.v4.u32 {%0,%1,%2,%3}, [%4];\n" : "=r"(v.x), "=r"(v.y), "=r"(v.z), "=r"(v.w) : "l"(p) : "memory");
    return v;
}
__device__ __forceinline__ uint2 ld_poll64(const void* p) {
    uint2 v;
    asm volatile("ld.relaxed.gpu.global.v2.u32 {%0,%1}, [%2];\n" : "=r"(v.x), "=r"(v.y) : "l"(p) : "memory");
    return v;
}
__device__ __forceinline__ uint32_t ld_poll32(const void* p) {
    uint32_t v;
    asm volatile("ld.relaxed.gpu.global.u32 %0, [%1];\n" : "=r"(v) : "l"(p) : "memory");
    return v;
}
__device__ __forceinline__ uint32_t ld_acquire32(const void* p) {
    uint32_t v;
    asm volatile("ld.acquire.gpu.global.u32 %0, [%1];\n" : "=r"(v) : "l"(p) : "memory");
    return v;
}
__device__ __forceinline__ uint4 ldg128(const void* p) {
    uint4 v;
    asm volatile("ld.global.nc.v4.u32 {%0,%1,%2,%3}, [%4];\n" : "=r"(v.x), "=r"(v.y), "=r"(v.z), "=r"(v.w) : "l"(p));
    return v;
}
__device__ __forceinline__ uint2 ldg64(const void* p) {
    uint2 v;
    asm volatile("ld.global.nc.v2.u32 {%0,%1}, [%2];\n" : "=r"(v.x), "=r"(v.y) : "l"(p));
    return v;
}
__device__ __forceinline__ uint32_t ldg16(const void* p) {
    uint32_t v;
    asm volatile("ld.global.nc.u16 %0, [%1];\n" : "=r"(v) : "l"(p));
    return v;
}
__device__ __forceinline__ uint4 ldo128(const void* p) {
    uint4 v;
    asm volatile("ld.relaxed.cta.global.v4.u32 {%0,%1,%2,%3}, [%4];\n" : "=r"(v.x), "=r"(v.y), "=r"(v.z), "=r"(v.w) : "l"(p) : "memory");
    return v;
}
__device__ __forceinline__ uint2 ldo64(const void* p) {
    uint2 v;
    asm volatile("ld.relaxed.cta.global.v2.u32 {%0,%1}, [%2];\n" : "=r"(v.x), "=r"(v.y) : "l"(p) : "memory");
    return v;
}
__device__ __forceinline__ uint32_t ldo16(const void* p) {
    uint32_t v;
    asm volatile("ld.relaxed.cta.global.u16 %0, [%1];\n" : "=r"(v) : "l"(p) : "memory");
    return v;
}
__device__ __forceinline__ void stg128(void* p, uint32_t a, uint32_t b, uint32_t c, uint32_t d) {
    asm volatile("st.global.v4.u32 [%0], {%1,%2,%3,%4};\n" ::"l"(p), "r"(a), "r"(b), "r"(c), "r"(d) : "memory");
}
__device__ __forceinline__ void stg64(void* p, uint32_t a, uint32_t b) { asm volatile("st.global.v2.u32 [%0], {%1,%2};\n" ::"l"(p), "r"(a), "r"(b) : "memory"); }
__device__ __forceinline__ uint32_t min4(const uint4& v) { return min(min(v.x, v.y), min(v.z, v.w)); }
#define SPIN_LIMIT (1 << 21)
#define TRAP() __trap()
__device__ __forceinline__ void mbar_init(uint32_t bar, uint32_t cnt) { asm volatile("mbarrier.init.shared::cta.b64 [%0], %1;\n" ::"r"(bar), "r"(cnt) : "memory"); }
__device__ __forceinline__ void mbar_expect(uint32_t bar, uint32_t bytes) {
    asm volatile("mbarrier.arrive.expect_tx.shared::cta.b64 _, [%0], %1;\n" ::"r"(bar), "r"(bytes) : "memory");
}
__device__ __forceinline__ void mbar_arrive(uint32_t bar) { asm volatile("mbarrier.arrive.shared::cta.b64 _, [%0];\n" ::"r"(bar) : "memory"); }
__device__ __forceinline__ void mbar_wait_cluster(uint32_t bar) {
    asm volatile(
        "{\n.reg .pred p;\n"
        "W_%=:\n"
        "mbarrier.try_wait.parity.acquire.cluster.shared::cta.b64 p, [%0], 0;\n"
        "@!p bra W_%=;\n}\n" ::"r"(bar) : "memory");
}
__device__ __forceinline__ void mbar_wait(uint32_t bar) {
    asm volatile(
        "{\n.reg .pred p;\n"
        "W_%=:\n"
        "mbarrier.try_wait.parity.shared::cta.b64 p, [%0], 0;\n"
        "@!p bra W_%=;\n}\n" ::"r"(bar) : "memory");
}
__device__ __forceinline__ void mbar_wait1(uint32_t bar) {
    asm volatile(
        "{\n.reg .pred p;\n"
        "W_%=:\n"
        "mbarrier.try_wait.parity.shared::cta.b64 p, [%0], 1;\n"
        "@!p bra W_%=;\n}\n" ::"r"(bar) : "memory");
}
__device__ __forceinline__ bool mbar_test(uint32_t bar) {
    uint32_t r;
    asm volatile("{\n.reg .pred p;\nmbarrier.test_wait.parity.shared::cta.b64 p, [%1], 0;\nselp.u32 %0, 1, 0, p;\n}\n" : "=r"(r) : "r"(bar) : "memory");
    return __any_sync(0xffffffffu, r);
}
__device__ __forceinline__ void bulk_g2s(uint32_t dst, const void* src, uint32_t bytes, uint32_t bar) {
    asm volatile("cp.async.bulk.shared::cluster.global.mbarrier::complete_tx::bytes [%0], [%1], %2, [%3];\n" ::"r"(dst), "l"(src), "r"(bytes), "r"(bar) : "memory");
}
__device__ __forceinline__ void bulk_s2g(void* dst, uint32_t src, uint32_t bytes) {
    asm volatile("cp.async.bulk.global.shared::cta.bulk_group [%0], [%1], %2;\ncp.async.bulk.commit_group;\n" ::"l"(dst), "r"(src), "r"(bytes) : "memory");
}
__device__ __forceinline__ void bulk_s2g_nc(void* dst, uint32_t src, uint32_t bytes) {
    asm volatile("cp.async.bulk.global.shared::cta.bulk_group [%0], [%1], %2;\n" ::"l"(dst), "r"(src), "r"(bytes) : "memory");
}
__device__ __forceinline__ void tma_2d(uint32_t dst, const CUtensorMap* tm, int c0, int c1, uint32_t bar) {
    asm volatile("cp.async.bulk.tensor.2d.shared::cluster.global.mbarrier::complete_tx::bytes [%0], [%1, {%3, %4}], [%2];\n"
                 ::"r"(dst), "l"(tm), "r"(bar), "r"(c0), "r"(c1) : "memory");
}
__device__ __forceinline__ void tma_4d(uint32_t dst, const CUtensorMap* tm, int c0, int c3, uint32_t bar) {
    asm volatile("cp.async.bulk.tensor.4d.shared::cluster.global.mbarrier::complete_tx::bytes [%0], [%1, {%3, %4, %4, %5}], [%2];\n"
                 ::"r"(dst), "l"(tm), "r"(bar), "r"(c0), "r"(0), "r"(c3) : "memory");
}
__device__ __forceinline__ void tma_4d_mc(uint32_t dst, const CUtensorMap* tm, int c0, int c3, uint32_t bar) {
    asm volatile("cp.async.bulk.tensor.4d.shared::cluster.global.mbarrier::complete_tx::bytes.multicast::cluster [%0], [%1, {%3, %4, %4, %5}], [%2], %6;\n"
                 ::"r"(dst), "l"(tm), "r"(bar), "r"(c0), "r"(0), "r"(c3), "h"((unsigned short)3) : "memory");
}
__device__ __forceinline__ void l2_prefetch(const void* src, uint32_t bytes) {
    asm volatile("cp.async.bulk.prefetch.L2.global [%0], %1;\n" ::"l"(src), "r"(bytes) : "memory");
}
__device__ __forceinline__ bool elect_one() {
    uint32_t r;
    asm volatile("{\n.reg .pred p;\nelect.sync _|p, 0xffffffff;\nselp.u32 %0, 1, 0, p;\n}\n" : "=r"(r));
    return r;
}
__device__ __forceinline__ void delay(uint32_t clks) {
    uint32_t t0, t1;
    asm volatile("mov.u32 %0, %%clock;" : "=r"(t0) :: "memory");
    do { asm volatile("mov.u32 %0, %%clock;" : "=r"(t1) :: "memory"); } while (t1 - t0 < clks);
}
__device__ __forceinline__ void fence_async() { asm volatile("fence.proxy.async.shared::cta;\n" ::: "memory"); }

__device__ __forceinline__ float2 cmul(float2 a, float2 b) {
    return make_float2(fmaf(a.x, b.x, -a.y * b.y), fmaf(a.x, b.y, a.y * b.x));
}
__device__ __forceinline__ float2 csq(float2 a) {
    float p = a.x * a.y;
    return make_float2(fmaf(a.x, a.x, -a.y * a.y), p + p);
}
__device__ __forceinline__ float ex2_approx(float x) { float r; asm("ex2.approx.ftz.f32 %0, %1;\n" : "=f"(r) : "f"(x)); return r; }
__device__ __forceinline__ float exp_bf(float x) { return rbf(ex2_approx(__fmul_ru(x, 1.4426950408889634f))); }
__device__ __forceinline__ float2 cexp_e(float lr2, float li, float e) {
    const float m = ex2_approx(lr2 * e);
    return make_float2(m * __cosf(li * e), m * __sinf(li * e));
}
__device__ __forceinline__ float rcp_approx(float x) { float r; asm("rcp.approx.ftz.f32 %0, %1;\n" : "=f"(r) : "f"(x)); return r; }
__device__ __forceinline__ float sigmoid_f(float x) { return rcp_approx(1.0f + ex2_approx(x * -1.4426950408889634f)); }
__device__ __forceinline__ float sqrt_approx(float x) { float r; asm("sqrt.approx.ftz.f32 %0, %1;\n" : "=f"(r) : "f"(x)); return r; }

__device__ __forceinline__ void wg_fence() { asm volatile("wgmma.fence.sync.aligned;\n" ::: "memory"); }
__device__ __forceinline__ void wg_commit() { asm volatile("wgmma.commit_group.sync.aligned;\n" ::: "memory"); }
__device__ __forceinline__ void wg_wait0() { asm volatile("wgmma.wait_group.sync.aligned 0;\n" ::: "memory"); }
template <int T> __device__ __forceinline__ void wg_mma(float (&acc)[16][4], const uint32_t* a, uint64_t desc);
template <int T> __device__ __forceinline__ void wg_first(float (&acc)[16][4], const uint32_t* a, uint64_t desc);
template <> __device__ __forceinline__ void wg_mma<0>(float (&acc)[16][4], const uint32_t* a, uint64_t desc) {
    asm volatile("wgmma.mma_async.sync.aligned.m64n128k16.f32.f16.f16 {%0,%1,%2,%3,%4,%5,%6,%7,%8,%9,%10,%11,%12,%13,%14,%15,%16,%17,%18,%19,%20,%21,%22,%23,%24,%25,%26,%27,%28,%29,%30,%31,%32,%33,%34,%35,%36,%37,%38,%39,%40,%41,%42,%43,%44,%45,%46,%47,%48,%49,%50,%51,%52,%53,%54,%55,%56,%57,%58,%59,%60,%61,%62,%63}, {%64,%65,%66,%67}, %68, 1, 1, 1, 0;\n"
                 : "+f"(acc[0][0]), "+f"(acc[0][1]), "+f"(acc[0][2]), "+f"(acc[0][3]), "+f"(acc[1][0]), "+f"(acc[1][1]), "+f"(acc[1][2]), "+f"(acc[1][3]), "+f"(acc[2][0]), "+f"(acc[2][1]), "+f"(acc[2][2]), "+f"(acc[2][3]), "+f"(acc[3][0]), "+f"(acc[3][1]), "+f"(acc[3][2]), "+f"(acc[3][3]), "+f"(acc[4][0]), "+f"(acc[4][1]), "+f"(acc[4][2]), "+f"(acc[4][3]), "+f"(acc[5][0]), "+f"(acc[5][1]), "+f"(acc[5][2]), "+f"(acc[5][3]), "+f"(acc[6][0]), "+f"(acc[6][1]), "+f"(acc[6][2]), "+f"(acc[6][3]), "+f"(acc[7][0]), "+f"(acc[7][1]), "+f"(acc[7][2]), "+f"(acc[7][3]), "+f"(acc[8][0]), "+f"(acc[8][1]), "+f"(acc[8][2]), "+f"(acc[8][3]), "+f"(acc[9][0]), "+f"(acc[9][1]), "+f"(acc[9][2]), "+f"(acc[9][3]), "+f"(acc[10][0]), "+f"(acc[10][1]), "+f"(acc[10][2]), "+f"(acc[10][3]), "+f"(acc[11][0]), "+f"(acc[11][1]), "+f"(acc[11][2]), "+f"(acc[11][3]), "+f"(acc[12][0]), "+f"(acc[12][1]), "+f"(acc[12][2]), "+f"(acc[12][3]), "+f"(acc[13][0]), "+f"(acc[13][1]), "+f"(acc[13][2]), "+f"(acc[13][3]), "+f"(acc[14][0]), "+f"(acc[14][1]), "+f"(acc[14][2]), "+f"(acc[14][3]), "+f"(acc[15][0]), "+f"(acc[15][1]), "+f"(acc[15][2]), "+f"(acc[15][3])
                 : "r"(a[0]), "r"(a[1]), "r"(a[2]), "r"(a[3]), "l"(desc));
}
template <> __device__ __forceinline__ void wg_mma<2>(float (&acc)[16][4], const uint32_t* a, uint64_t desc) {
    asm volatile("wgmma.mma_async.sync.aligned.m64n112k16.f32.f16.f16 {%0,%1,%2,%3,%4,%5,%6,%7,%8,%9,%10,%11,%12,%13,%14,%15,%16,%17,%18,%19,%20,%21,%22,%23,%24,%25,%26,%27,%28,%29,%30,%31,%32,%33,%34,%35,%36,%37,%38,%39,%40,%41,%42,%43,%44,%45,%46,%47,%48,%49,%50,%51,%52,%53,%54,%55}, {%56,%57,%58,%59}, %60, 1, 1, 1, 0;\n"
                 : "+f"(acc[2][0]), "+f"(acc[2][1]), "+f"(acc[2][2]), "+f"(acc[2][3]), "+f"(acc[3][0]), "+f"(acc[3][1]), "+f"(acc[3][2]), "+f"(acc[3][3]), "+f"(acc[4][0]), "+f"(acc[4][1]), "+f"(acc[4][2]), "+f"(acc[4][3]), "+f"(acc[5][0]), "+f"(acc[5][1]), "+f"(acc[5][2]), "+f"(acc[5][3]), "+f"(acc[6][0]), "+f"(acc[6][1]), "+f"(acc[6][2]), "+f"(acc[6][3]), "+f"(acc[7][0]), "+f"(acc[7][1]), "+f"(acc[7][2]), "+f"(acc[7][3]), "+f"(acc[8][0]), "+f"(acc[8][1]), "+f"(acc[8][2]), "+f"(acc[8][3]), "+f"(acc[9][0]), "+f"(acc[9][1]), "+f"(acc[9][2]), "+f"(acc[9][3]), "+f"(acc[10][0]), "+f"(acc[10][1]), "+f"(acc[10][2]), "+f"(acc[10][3]), "+f"(acc[11][0]), "+f"(acc[11][1]), "+f"(acc[11][2]), "+f"(acc[11][3]), "+f"(acc[12][0]), "+f"(acc[12][1]), "+f"(acc[12][2]), "+f"(acc[12][3]), "+f"(acc[13][0]), "+f"(acc[13][1]), "+f"(acc[13][2]), "+f"(acc[13][3]), "+f"(acc[14][0]), "+f"(acc[14][1]), "+f"(acc[14][2]), "+f"(acc[14][3]), "+f"(acc[15][0]), "+f"(acc[15][1]), "+f"(acc[15][2]), "+f"(acc[15][3])
                 : "r"(a[0]), "r"(a[1]), "r"(a[2]), "r"(a[3]), "l"(desc));
}
template <> __device__ __forceinline__ void wg_mma<4>(float (&acc)[16][4], const uint32_t* a, uint64_t desc) {
    asm volatile("wgmma.mma_async.sync.aligned.m64n96k16.f32.f16.f16 {%0,%1,%2,%3,%4,%5,%6,%7,%8,%9,%10,%11,%12,%13,%14,%15,%16,%17,%18,%19,%20,%21,%22,%23,%24,%25,%26,%27,%28,%29,%30,%31,%32,%33,%34,%35,%36,%37,%38,%39,%40,%41,%42,%43,%44,%45,%46,%47}, {%48,%49,%50,%51}, %52, 1, 1, 1, 0;\n"
                 : "+f"(acc[4][0]), "+f"(acc[4][1]), "+f"(acc[4][2]), "+f"(acc[4][3]), "+f"(acc[5][0]), "+f"(acc[5][1]), "+f"(acc[5][2]), "+f"(acc[5][3]), "+f"(acc[6][0]), "+f"(acc[6][1]), "+f"(acc[6][2]), "+f"(acc[6][3]), "+f"(acc[7][0]), "+f"(acc[7][1]), "+f"(acc[7][2]), "+f"(acc[7][3]), "+f"(acc[8][0]), "+f"(acc[8][1]), "+f"(acc[8][2]), "+f"(acc[8][3]), "+f"(acc[9][0]), "+f"(acc[9][1]), "+f"(acc[9][2]), "+f"(acc[9][3]), "+f"(acc[10][0]), "+f"(acc[10][1]), "+f"(acc[10][2]), "+f"(acc[10][3]), "+f"(acc[11][0]), "+f"(acc[11][1]), "+f"(acc[11][2]), "+f"(acc[11][3]), "+f"(acc[12][0]), "+f"(acc[12][1]), "+f"(acc[12][2]), "+f"(acc[12][3]), "+f"(acc[13][0]), "+f"(acc[13][1]), "+f"(acc[13][2]), "+f"(acc[13][3]), "+f"(acc[14][0]), "+f"(acc[14][1]), "+f"(acc[14][2]), "+f"(acc[14][3]), "+f"(acc[15][0]), "+f"(acc[15][1]), "+f"(acc[15][2]), "+f"(acc[15][3])
                 : "r"(a[0]), "r"(a[1]), "r"(a[2]), "r"(a[3]), "l"(desc));
}
template <> __device__ __forceinline__ void wg_mma<6>(float (&acc)[16][4], const uint32_t* a, uint64_t desc) {
    asm volatile("wgmma.mma_async.sync.aligned.m64n80k16.f32.f16.f16 {%0,%1,%2,%3,%4,%5,%6,%7,%8,%9,%10,%11,%12,%13,%14,%15,%16,%17,%18,%19,%20,%21,%22,%23,%24,%25,%26,%27,%28,%29,%30,%31,%32,%33,%34,%35,%36,%37,%38,%39}, {%40,%41,%42,%43}, %44, 1, 1, 1, 0;\n"
                 : "+f"(acc[6][0]), "+f"(acc[6][1]), "+f"(acc[6][2]), "+f"(acc[6][3]), "+f"(acc[7][0]), "+f"(acc[7][1]), "+f"(acc[7][2]), "+f"(acc[7][3]), "+f"(acc[8][0]), "+f"(acc[8][1]), "+f"(acc[8][2]), "+f"(acc[8][3]), "+f"(acc[9][0]), "+f"(acc[9][1]), "+f"(acc[9][2]), "+f"(acc[9][3]), "+f"(acc[10][0]), "+f"(acc[10][1]), "+f"(acc[10][2]), "+f"(acc[10][3]), "+f"(acc[11][0]), "+f"(acc[11][1]), "+f"(acc[11][2]), "+f"(acc[11][3]), "+f"(acc[12][0]), "+f"(acc[12][1]), "+f"(acc[12][2]), "+f"(acc[12][3]), "+f"(acc[13][0]), "+f"(acc[13][1]), "+f"(acc[13][2]), "+f"(acc[13][3]), "+f"(acc[14][0]), "+f"(acc[14][1]), "+f"(acc[14][2]), "+f"(acc[14][3]), "+f"(acc[15][0]), "+f"(acc[15][1]), "+f"(acc[15][2]), "+f"(acc[15][3])
                 : "r"(a[0]), "r"(a[1]), "r"(a[2]), "r"(a[3]), "l"(desc));
}
template <> __device__ __forceinline__ void wg_mma<8>(float (&acc)[16][4], const uint32_t* a, uint64_t desc) {
    asm volatile("wgmma.mma_async.sync.aligned.m64n64k16.f32.f16.f16 {%0,%1,%2,%3,%4,%5,%6,%7,%8,%9,%10,%11,%12,%13,%14,%15,%16,%17,%18,%19,%20,%21,%22,%23,%24,%25,%26,%27,%28,%29,%30,%31}, {%32,%33,%34,%35}, %36, 1, 1, 1, 0;\n"
                 : "+f"(acc[8][0]), "+f"(acc[8][1]), "+f"(acc[8][2]), "+f"(acc[8][3]), "+f"(acc[9][0]), "+f"(acc[9][1]), "+f"(acc[9][2]), "+f"(acc[9][3]), "+f"(acc[10][0]), "+f"(acc[10][1]), "+f"(acc[10][2]), "+f"(acc[10][3]), "+f"(acc[11][0]), "+f"(acc[11][1]), "+f"(acc[11][2]), "+f"(acc[11][3]), "+f"(acc[12][0]), "+f"(acc[12][1]), "+f"(acc[12][2]), "+f"(acc[12][3]), "+f"(acc[13][0]), "+f"(acc[13][1]), "+f"(acc[13][2]), "+f"(acc[13][3]), "+f"(acc[14][0]), "+f"(acc[14][1]), "+f"(acc[14][2]), "+f"(acc[14][3]), "+f"(acc[15][0]), "+f"(acc[15][1]), "+f"(acc[15][2]), "+f"(acc[15][3])
                 : "r"(a[0]), "r"(a[1]), "r"(a[2]), "r"(a[3]), "l"(desc));
}
template <> __device__ __forceinline__ void wg_mma<10>(float (&acc)[16][4], const uint32_t* a, uint64_t desc) {
    asm volatile("wgmma.mma_async.sync.aligned.m64n48k16.f32.f16.f16 {%0,%1,%2,%3,%4,%5,%6,%7,%8,%9,%10,%11,%12,%13,%14,%15,%16,%17,%18,%19,%20,%21,%22,%23}, {%24,%25,%26,%27}, %28, 1, 1, 1, 0;\n"
                 : "+f"(acc[10][0]), "+f"(acc[10][1]), "+f"(acc[10][2]), "+f"(acc[10][3]), "+f"(acc[11][0]), "+f"(acc[11][1]), "+f"(acc[11][2]), "+f"(acc[11][3]), "+f"(acc[12][0]), "+f"(acc[12][1]), "+f"(acc[12][2]), "+f"(acc[12][3]), "+f"(acc[13][0]), "+f"(acc[13][1]), "+f"(acc[13][2]), "+f"(acc[13][3]), "+f"(acc[14][0]), "+f"(acc[14][1]), "+f"(acc[14][2]), "+f"(acc[14][3]), "+f"(acc[15][0]), "+f"(acc[15][1]), "+f"(acc[15][2]), "+f"(acc[15][3])
                 : "r"(a[0]), "r"(a[1]), "r"(a[2]), "r"(a[3]), "l"(desc));
}
template <> __device__ __forceinline__ void wg_mma<12>(float (&acc)[16][4], const uint32_t* a, uint64_t desc) {
    asm volatile("wgmma.mma_async.sync.aligned.m64n32k16.f32.f16.f16 {%0,%1,%2,%3,%4,%5,%6,%7,%8,%9,%10,%11,%12,%13,%14,%15}, {%16,%17,%18,%19}, %20, 1, 1, 1, 0;\n"
                 : "+f"(acc[12][0]), "+f"(acc[12][1]), "+f"(acc[12][2]), "+f"(acc[12][3]), "+f"(acc[13][0]), "+f"(acc[13][1]), "+f"(acc[13][2]), "+f"(acc[13][3]), "+f"(acc[14][0]), "+f"(acc[14][1]), "+f"(acc[14][2]), "+f"(acc[14][3]), "+f"(acc[15][0]), "+f"(acc[15][1]), "+f"(acc[15][2]), "+f"(acc[15][3])
                 : "r"(a[0]), "r"(a[1]), "r"(a[2]), "r"(a[3]), "l"(desc));
}
template <> __device__ __forceinline__ void wg_mma<14>(float (&acc)[16][4], const uint32_t* a, uint64_t desc) {
    asm volatile("wgmma.mma_async.sync.aligned.m64n16k16.f32.f16.f16 {%0,%1,%2,%3,%4,%5,%6,%7}, {%8,%9,%10,%11}, %12, 1, 1, 1, 0;\n"
                 : "+f"(acc[14][0]), "+f"(acc[14][1]), "+f"(acc[14][2]), "+f"(acc[14][3]), "+f"(acc[15][0]), "+f"(acc[15][1]), "+f"(acc[15][2]), "+f"(acc[15][3])
                 : "r"(a[0]), "r"(a[1]), "r"(a[2]), "r"(a[3]), "l"(desc));
}
template <> __device__ __forceinline__ void wg_first<0>(float (&acc)[16][4], const uint32_t* a, uint64_t desc) {
    asm volatile("wgmma.mma_async.sync.aligned.m64n128k16.f32.f16.f16 {%0,%1,%2,%3,%4,%5,%6,%7,%8,%9,%10,%11,%12,%13,%14,%15,%16,%17,%18,%19,%20,%21,%22,%23,%24,%25,%26,%27,%28,%29,%30,%31,%32,%33,%34,%35,%36,%37,%38,%39,%40,%41,%42,%43,%44,%45,%46,%47,%48,%49,%50,%51,%52,%53,%54,%55,%56,%57,%58,%59,%60,%61,%62,%63}, {%64,%65,%66,%67}, %68, 0, 1, 1, 0;\n"
                 : "=f"(acc[0][0]), "=f"(acc[0][1]), "=f"(acc[0][2]), "=f"(acc[0][3]), "=f"(acc[1][0]), "=f"(acc[1][1]), "=f"(acc[1][2]), "=f"(acc[1][3]), "=f"(acc[2][0]), "=f"(acc[2][1]), "=f"(acc[2][2]), "=f"(acc[2][3]), "=f"(acc[3][0]), "=f"(acc[3][1]), "=f"(acc[3][2]), "=f"(acc[3][3]), "=f"(acc[4][0]), "=f"(acc[4][1]), "=f"(acc[4][2]), "=f"(acc[4][3]), "=f"(acc[5][0]), "=f"(acc[5][1]), "=f"(acc[5][2]), "=f"(acc[5][3]), "=f"(acc[6][0]), "=f"(acc[6][1]), "=f"(acc[6][2]), "=f"(acc[6][3]), "=f"(acc[7][0]), "=f"(acc[7][1]), "=f"(acc[7][2]), "=f"(acc[7][3]), "=f"(acc[8][0]), "=f"(acc[8][1]), "=f"(acc[8][2]), "=f"(acc[8][3]), "=f"(acc[9][0]), "=f"(acc[9][1]), "=f"(acc[9][2]), "=f"(acc[9][3]), "=f"(acc[10][0]), "=f"(acc[10][1]), "=f"(acc[10][2]), "=f"(acc[10][3]), "=f"(acc[11][0]), "=f"(acc[11][1]), "=f"(acc[11][2]), "=f"(acc[11][3]), "=f"(acc[12][0]), "=f"(acc[12][1]), "=f"(acc[12][2]), "=f"(acc[12][3]), "=f"(acc[13][0]), "=f"(acc[13][1]), "=f"(acc[13][2]), "=f"(acc[13][3]), "=f"(acc[14][0]), "=f"(acc[14][1]), "=f"(acc[14][2]), "=f"(acc[14][3]), "=f"(acc[15][0]), "=f"(acc[15][1]), "=f"(acc[15][2]), "=f"(acc[15][3])
                 : "r"(a[0]), "r"(a[1]), "r"(a[2]), "r"(a[3]), "l"(desc));
}
template <> __device__ __forceinline__ void wg_first<4>(float (&acc)[16][4], const uint32_t* a, uint64_t desc) {
    asm volatile("wgmma.mma_async.sync.aligned.m64n96k16.f32.f16.f16 {%0,%1,%2,%3,%4,%5,%6,%7,%8,%9,%10,%11,%12,%13,%14,%15,%16,%17,%18,%19,%20,%21,%22,%23,%24,%25,%26,%27,%28,%29,%30,%31,%32,%33,%34,%35,%36,%37,%38,%39,%40,%41,%42,%43,%44,%45,%46,%47}, {%48,%49,%50,%51}, %52, 0, 1, 1, 0;\n"
                 : "=f"(acc[4][0]), "=f"(acc[4][1]), "=f"(acc[4][2]), "=f"(acc[4][3]), "=f"(acc[5][0]), "=f"(acc[5][1]), "=f"(acc[5][2]), "=f"(acc[5][3]), "=f"(acc[6][0]), "=f"(acc[6][1]), "=f"(acc[6][2]), "=f"(acc[6][3]), "=f"(acc[7][0]), "=f"(acc[7][1]), "=f"(acc[7][2]), "=f"(acc[7][3]), "=f"(acc[8][0]), "=f"(acc[8][1]), "=f"(acc[8][2]), "=f"(acc[8][3]), "=f"(acc[9][0]), "=f"(acc[9][1]), "=f"(acc[9][2]), "=f"(acc[9][3]), "=f"(acc[10][0]), "=f"(acc[10][1]), "=f"(acc[10][2]), "=f"(acc[10][3]), "=f"(acc[11][0]), "=f"(acc[11][1]), "=f"(acc[11][2]), "=f"(acc[11][3]), "=f"(acc[12][0]), "=f"(acc[12][1]), "=f"(acc[12][2]), "=f"(acc[12][3]), "=f"(acc[13][0]), "=f"(acc[13][1]), "=f"(acc[13][2]), "=f"(acc[13][3]), "=f"(acc[14][0]), "=f"(acc[14][1]), "=f"(acc[14][2]), "=f"(acc[14][3]), "=f"(acc[15][0]), "=f"(acc[15][1]), "=f"(acc[15][2]), "=f"(acc[15][3])
                 : "r"(a[0]), "r"(a[1]), "r"(a[2]), "r"(a[3]), "l"(desc));
}
#define KR 1
#define RMAP 1
#define DDLY 300
#define CNT(i, v)
#define WANY(i) (wsched((i) + 1) > wsched(i))
#define FIX(v) do { if ((v) == 1u) TRAP(); } while (0)

#define EARLYN 2
#define K8 0
#define HOLD 3
#define MC 1
#define STAMPW(i) STAMPY(i)
#define STAMP2(i) STAMP(i)
#undef STAMPX
#define STAMPX(i)
#define PBAR 1
#define WDLY 500
#define CBAR 1
#define FDLY 1000
#define FDLY2 400
#define YDLY 1
#define YFROM 64
#define YPRE 0
#define KDLY 950
#define OEARLY 0
#define ODLY 0
#define SORD 1
#define SDLY 900
#define UDLY 1400
#define XCP 1
#define DEFER 0
#define WAE 0
#define RG0 0
#define RG1 2
#define WSP 1
#define EXP 0
#define XWHEN 0
#define RWHEN 0
#define HW 15
#define PEARLY 1
#define XG 6
struct Params {
    const bf16 *x, *lar, *aim, *cre, *cim, *ldt, *dsk;
    Scratch* s;
    const bf16 *wr, *wg, *wu, *wd;
    bf16* out;
};

#define TOK(g) (2 * (g) - ((g) & 1))
#define ROWTOK(r) (TOK((r) & 7) + (((r) >> 2) & 2))
__device__ __forceinline__ void ln_partial(const uint32_t (&H)[2][4], float (&d)[2][4]) {
#pragma unroll
    for (int hf = 0; hf < 2; hf++) {
        d[hf][0] = d[hf][1] = d[hf][2] = d[hf][3] = 0.f;
        mma_bf16(d[hf], H[hf][0], 0x3f803f80u, H[hf][1], 0x3f803f80u, H[hf][0], H[hf][1]);
    }
#pragma unroll
    for (int hf = 0; hf < 2; hf++) mma_bf16(d[hf], H[hf][2], 0x3f803f80u, H[hf][3], 0x3f803f80u, H[hf][2], H[hf][3]);
}
__device__ __forceinline__ float sum18(uint32_t a) {
    const uint4 p = lds128(a), q = lds128(a + 16), r = lds128(a + 32), s = lds128(a + 48);
    const uint2 u = lds64(a + 64);
#define F(x) __uint_as_float(x)
    return (((F(p.x) + F(p.y)) + (F(p.z) + F(p.w))) + ((F(q.x) + F(q.y)) + (F(q.z) + F(q.w)))) +
           (((F(r.x) + F(r.y)) + (F(r.z) + F(r.w))) + ((F(s.x) + F(s.y)) + (F(s.z) + F(s.w))) + (F(u.x) + F(u.y)));
#undef F
}
__device__ __forceinline__ void ln_stats(float sm, float sq, float& mb, float& sd) {
    const float m0 = sm * (1.0f / 576.0f);
    const float mean = fmaf(fmaf(-m0, 576.0f, sm), 1.0f / 576.0f, m0);
    const float var = fmaxf(fmaf(-mean, mean, sq * (1.0f / 576.0f)), 0.f);
    mb = rbf(mean);
    sd = rbf(sqrt_approx(rbf(rbf(var) + 1e-5f)));
}
__device__ __forceinline__ void ln_finish(float v, int lane, float& mb, float& rc) {
    const float o = __shfl_xor_sync(0xffffffffu, v, 16);
    float sd;
    ln_stats(lane < 16 ? v : o, lane < 16 ? o : v, mb, sd);
    rc = rcp_approx(sd);
}
__device__ __forceinline__ uint32_t ln_apply(uint32_t w, uint32_t m2, uint32_t rh, uint32_t rl) {
    const uint32_t d = hsub2_bf(w, m2);
    return hfma2_bf(d, rh, hmul2_bf(d, rl));
}
__device__ __forceinline__ void stat_store(uint32_t a, float mb, float rc, uint32_t extra) {
    const float rh = rbf(rc);
    sts64(a, (__float_as_uint(mb) >> 16) | (extra << 16), pack_bf16(rh, rc - rh));
}
#define STAT_M(s) __byte_perm((s).x, (s).x, 0x1010)
#define STAT_H(s) __byte_perm((s).y, (s).y, 0x1010)
#define STAT_L(s) __byte_perm((s).y, (s).y, 0x3232)

__device__ __forceinline__ void hcmul(uint32_t re, uint32_t im, uint32_t zx, uint32_t zy, uint32_t& ore, uint32_t& oim) {
    ore = hfms2(im, zy, hmul2(re, zx));
    oim = hfma2(re, zy, hmul2(im, zx));
}

struct KGen {
    uint32_t A[2][4][4];
    float2 z1, z8, z64, z128, T[9];
};
__device__ __forceinline__ void kgen_setup(KGen& k, float lar, float aim, float dt) {
    const float lr2 = -(exp_bf(lar) * dt) * 1.4426950408889634f, li = aim * dt;
    k.z1 = cexp_e(lr2, li, 1.0f);
    k.z8 = cexp_e(lr2, li, 8.0f);
    k.z64 = cexp_e(lr2, li, 64.0f);
}
__device__ __forceinline__ void kgen_rows(KGen& k, uint32_t tb, int lane) {
    const float2 z8 = k.z8, z64 = k.z64;
    const uint32_t row = tb + lane * 16;
    k.z128 = csq(z64);
    const float2 z16 = csq(z8), z24 = cmul(z16, z8), z32 = csq(z16), z40 = cmul(z32, z8), z48 = csq(z24), z56 = cmul(z32, z24);
    uint32_t re[4], im[4], a[4], b[4];
    re[0] = pack_f16(1.0f, z8.x); im[0] = pack_f16(0.0f, z8.y);
    re[1] = pack_f16(z16.x, z24.x); im[1] = pack_f16(z16.y, z24.y);
    re[2] = pack_f16(z32.x, z40.x); im[2] = pack_f16(z32.y, z40.y);
    re[3] = pack_f16(z48.x, z56.x); im[3] = pack_f16(z48.y, z56.y);
    sts128(row, re[0], re[1], re[2], re[3]);
    sts128(row + 1024, im[0], im[1], im[2], im[3]);
    const uint32_t zx = pack_f16(z64.x, z64.x), zy = pack_f16(z64.y, z64.y), zw = pack_f16(k.z128.x, k.z128.y);
#pragma unroll
    for (int j = 0; j < 4; j++) hcmul(re[j], im[j], zx, zy, a[j], b[j]);
    sts128(row + 512, a[0], a[1], a[2], a[3]);
    sts128(row + 1536, b[0], b[1], b[2], b[3]);
    const int mi = lane >> 3;
    const uint32_t zd = tb + 2048 + mi * 16;
    sts16(tb + 2048 + lane * 2, zw); sts16(tb + 2112 + lane * 2, zw >> 16);
    __syncwarp();
    const uint32_t ad = tb + (lane & 7) * 16 + mi * 512;
    ldsm_x4(a[0], a[1], a[2], a[3], zd);
    ldsm_x4(b[0], b[1], b[2], b[3], zd + 64);
#pragma unroll
    for (int ks = 0; ks < 4; ks++) {
        ldsm_x4_t(k.A[0][ks][0], k.A[0][ks][1], k.A[0][ks][2], k.A[0][ks][3], ad + ks * 128);
        hcmul(k.A[0][ks][0], k.A[0][ks][2], a[ks], b[ks], k.A[1][ks][0], k.A[1][ks][2]);
        hcmul(k.A[0][ks][1], k.A[0][ks][3], a[ks], b[ks], k.A[1][ks][1], k.A[1][ks][3]);
    }
}
__device__ __forceinline__ void kgen_chain(KGen& k, uint32_t cr, uint32_t ci, float cs) {
    k.T[0] = make_float2(bf_lo(cr) * cs, -bf_lo(ci) * cs);
    const float2 y1 = make_float2(k.z1.x, -k.z1.y);
#pragma unroll
    for (int c = 1; c < 8; c++) k.T[c] = cmul(k.T[c - 1], y1);
    k.T[8] = cmul(k.T[0], make_float2(k.z8.x, -k.z8.y));
}
__device__ __forceinline__ void kgen_cols(KGen& k, uint32_t tb, uint32_t t5, int lane) {
    const uint32_t row = tb + lane * 16;
    const float2 (&T)[9] = k.T;
    const float2 y128 = make_float2(k.z128.x, -k.z128.y);
    const float2 y256 = csq(y128), y512 = csq(y256), y768 = cmul(y512, y256), y1024 = csq(y512);
    const float2 c1032 = cmul(T[8], y1024);
    __syncwarp();
    sts128(row, pack_f16(T[0].x, T[1].x), pack_f16(T[2].x, T[3].x), pack_f16(T[4].x, T[5].x), pack_f16(T[6].x, T[7].x));
    sts128(row + 512, pack_f16(T[0].y, T[1].y), pack_f16(T[2].y, T[3].y), pack_f16(T[4].y, T[5].y), pack_f16(T[6].y, T[7].y));
    uint32_t a[4], b[4];
    {
        const uint32_t zx = pack_f16(y256.x, y256.x), zy = pack_f16(y256.y, y256.y);
        hcmul(pack_f16(T[0].x, T[2].x), pack_f16(T[0].y, T[2].y), zx, zy, a[0], b[0]);
        hcmul(pack_f16(T[4].x, T[6].x), pack_f16(T[4].y, T[6].y), zx, zy, a[1], b[1]);
        const uint32_t r04 = pack_f16(T[0].x, T[4].x), i04 = pack_f16(T[0].y, T[4].y);
        hcmul(r04, i04, pack_f16(y512.x, y512.x), pack_f16(y512.y, y512.y), a[2], b[2]);
        hcmul(r04, i04, pack_f16(y768.x, y768.x), pack_f16(y768.y, y768.y), a[3], b[3]);
    }
    sts128(row + 1024, a[0], a[1], a[2], a[3]);
    sts128(row + 1536, b[0], b[1], b[2], b[3]);
    {
        const uint32_t r0 = pack_f16(1.0f, y256.x), i0 = pack_f16(0.0f, y256.y), r1 = pack_f16(y512.x, y768.x), i1 = pack_f16(y512.y, y768.y);
        const uint32_t zx = pack_f16(T[8].x, T[8].x), zy = pack_f16(T[8].y, T[8].y), wx = pack_f16(c1032.x, c1032.x), wy = pack_f16(c1032.y, c1032.y);
        hcmul(r0, i0, zx, zy, a[0], b[0]); hcmul(r1, i1, zx, zy, a[1], b[1]);
        hcmul(r0, i0, wx, wy, a[2], b[2]); hcmul(r1, i1, wx, wy, a[3], b[3]);
    }
    sts128(row + 2048, a[0], a[1], a[2], a[3]);
    sts128(t5 + lane * 16, b[0], b[1], b[2], b[3]);
}
__device__ __forceinline__ void kgen_mma(const KGen& k, uint32_t tb, uint32_t t5, int lane, uint32_t hb) {
    __syncwarp();
    float acc[2][3][4];
#pragma unroll
    for (int i = 0; i < 6; i++)
#pragma unroll
        for (int j = 0; j < 4; j++) acc[i / 3][i % 3][j] = 0.f;
    const int mi = lane >> 3;
    const uint32_t ro = ((lane & 7) + 8 * (mi >> 1)) * 16, bd = tb + ro + (mi & 1) * 512, b2 = ro + ((mi & 1) ? t5 : tb + 2048);
#pragma unroll
    for (int kp = 0; kp < 2; kp++)
#pragma unroll
        for (int j = 0; j < 3; j++) {
            uint32_t b[4];
            if (HOLD == 5 && kp == 1 && j == 0) mbar_wait1(hb);
            ldsm_x4_t(b[0], b[1], b[2], b[3], (j < 2 ? bd + j * 1024 : b2) + kp * 256);
#pragma unroll
            for (int h = 0; h < 2; h++)
#pragma unroll
                for (int m = 0; m < 2; m++) {
                    const uint32_t (&A)[4] = k.A[m][2 * kp + h];
                    mma_f16(acc[m][j], A[0], A[1], A[2], A[3], b[2 * h], b[2 * h + 1]);
                }
        }
    __syncwarp();
#define PK(j) pack_f16(acc[0][j][0], acc[0][j][1]), pack_f16(acc[0][j][2], acc[0][j][3]), pack_f16(acc[1][j][0], acc[1][j][1]), pack_f16(acc[1][j][2], acc[1][j][3])
    stsm_x4(tb + lane * 16, PK(0));
    stsm_x4(tb + 512 + lane * 16, PK(1));
    stsm_x4_t(tb + 1024 + (lane & 7) * 80 + mi * 16, PK(2));
#undef PK
}
__device__ __forceinline__ uint32_t table_buf(uint32_t sb, int warp) { return sb + SM_PL + warp * TBW; }

__device__ __forceinline__ uint4 lds16x4(uint32_t a) { return make_uint4(lds16(a), lds16(a + TBW), lds16(a + 2 * TBW), lds16(a + 3 * TBW)); }
__device__ __forceinline__ void combine_setup(uint32_t sb, int warp, int lane, uint32_t kw, uint32_t& o, uint32_t& n, uint32_t& d) {
    const int wq = warp & 3;
    const uint32_t a = table_buf(sb, warp & ~3);
    o = wq == 3 ? a + 1024 + 320 + (lane >> 3) * 80 + (lane & 7) * 8 : a + (wq ? 504 + wq * 8 : 0) + lane * 16;
    n = a + 1024 + wq * 80 + lane * 2;
    d = wq < 3 ? kw + (wq == 2 ? KW_P : 32 + wq * 512) + lane * 16 : kw + KW_H + 8 + lane * 8;
}
__device__ __forceinline__ void kgen_combine(int wq, int lane, uint32_t o, uint32_t na, uint32_t d) {
#define S4(f) hadd2(hadd2(u.f, v.f), hadd2(w.f, x.f))
#define H4(v) hadd2(hadd2(v.x, v.y), hadd2(v.z, v.w))
#define BP __byte_perm
    if (wq == 0) {
        const uint4 u = lds128(o), v = lds128(o + TBW), w = lds128(o + 2 * TBW), x = lds128(o + 3 * TBW), nn = lds16x4(na);
        const uint32_t n = H4(nn), k0 = S4(x), k2 = S4(y), k4 = S4(z), k6 = S4(w);
        sts128(d, BP(k0, k0, 0x1032), BP(k0, k2, 0x3254), BP(k2, k2, 0x1032), BP(k2, k4, 0x3254));
        sts128(d + KW_PL, BP(k4, k4, 0x1032), BP(k4, k6, 0x3254), BP(k6, k6, 0x1032), BP(k6, n, 0x3254));
        if (lane == 0) sts32(d + KW_PL - 4, k0 & 0xffffu);
    } else {
        const uint2 u = lds64(o), v = lds64(o + TBW), w = lds64(o + 2 * TBW), x = lds64(o + 3 * TBW);
        uint4 nn = make_uint4(0u, 0u, 0u, 0u), mm = nn;
        if (wq < 3) nn = lds16x4(na);
        if (wq == 2) mm = lds16x4(na + 80);
        const uint32_t k0 = S4(x), k2 = S4(y), n = H4(nn), m = H4(mm);
        if (wq == 3) {
            sts64(d, k0, k2);
        } else if (wq == 1) {
            const uint32_t cc = BP(k2, k2, 0x1010);
            sts128(d, BP(k0, k0, 0x1010), BP(k0, k0, 0x1032), BP(k0, k2, 0x3254), cc);
            sts128(d + KW_PL, cc, BP(k2, k2, 0x1032), BP(k2, n, 0x3254), BP(n, n, 0x1010));
        } else {
            const uint32_t w40 = BP(k0, k0, 0x1032), w84 = BP(k0, n, 0x3254), w0 = BP(k0, k0, 0x1010), w4 = BP(k0, k0, 0x3232), w8 = BP(n, n, 0x1010);
            sts64(d, w40, w84);
            sts64(d + 512, BP(k2, k2, 0x1032), BP(k2, m, 0x3254));
            if (lane < 8) { sts128(d - (KW_P - 1056), w0, w0, w40, w4); sts128(d - (KW_P - 1056 - KW_PL), w4, w84, w8, w8); }
            if (lane == 31) sts16(d + (KW_H + 6 - KW_P - 496), m);
        }
    }
#undef S4
#undef H4
#undef BP
}

__device__ __forceinline__ int c_exponent(const uint2& r, const uint2& i, float dt) {
    const uint32_t mx = __vmaxu2(__vmaxu2(r.x & 0x7fff7fffu, r.y & 0x7fff7fffu), __vmaxu2(i.x & 0x7fff7fffu, i.y & 0x7fff7fffu));
    return __reduce_max_sync(0xffffffffu, max(mx, mx << 16) + (__float_as_uint(dt) & 0x7f800000u)) >> 23;
}

#define Q2FIX 1
#define ONEBAR 1
__device__ __forceinline__ int warp_v() { int l; asm volatile("mov.u32 %0, %%tid.x;" : "=r"(l)); return __shfl_sync(0xffffffffu, l >> 5, 0); }
__device__ __forceinline__ int lane_v() { int l; asm volatile("mov.u32 %0, %%laneid;" : "=r"(l)); return l; }
__device__ __forceinline__ uint32_t prmt_v(uint32_t a, uint32_t b, uint32_t s) { uint32_t d; asm volatile("prmt.b32 %0, %1, %2, %3;\n" : "=r"(d) : "r"(a), "r"(b), "r"(s)); return d; }
__device__ __forceinline__ uint32_t mov_v(uint32_t a) { uint32_t d; asm volatile("mov.b32 %0, %1;\n" : "=r"(d) : "r"(a)); return d; }
template <int G>
__device__ __forceinline__ void conv_rename(float (&acc)[16][4]) {
#pragma unroll
    for (int i = G; i < 16; i++)
#pragma unroll
        for (int j = 0; j < 4; j++) { float v; asm volatile("mov.b32 %0, %1;\n" : "=f"(v) : "f"(acc[i][j])); acc[i][j] = v; }
}
struct Conv {
    uint32_t kw;
    uint32_t wa;
    uint32_t pa, s2;
    uint32_t s8;
    uint32_t id;
    uint32_t lc;
    uint32_t fs;
    uint32_t fl, yo;
    uint32_t yp;
    size_t ycopy;
    uint32_t ps;
    uint64_t d0;
    int warp;
};
struct Pk { uint32_t w[4]; };
__device__ __forceinline__ Pk pk2(const float (&u)[4], const float (&v)[4]) {
    Pk r;
    r.w[0] = pack_f16(u[0], u[1]); r.w[1] = pack_f16(u[2], u[3]); r.w[2] = pack_f16(v[0], v[1]); r.w[3] = pack_f16(v[2], v[3]);
    return r;
}
__device__ __forceinline__ void park(uint32_t a, const Pk& v) {
    asm volatile("stmatrix.sync.aligned.m8n8.x4.trans.shared.b16 [%0], {%1,%2,%3,%4};\n" ::"r"(a), "r"(v.w[0]), "r"(v.w[1]), "r"(v.w[2]), "r"(v.w[3]) : "memory");
}
__device__ __forceinline__ void conv_constants(uint32_t lc, int l) {
    const int d = (l >> 2) - 2 * (l & 3);
    const int e = d + 8, r4 = (e + 1 + ((e >> 2) & 1)) >> 2, p4 = (e + (((e - 1) >> 2) & 1)) >> 2;
    const uint32_t s2 = r4 == p4 ? 0x1010u : 0x3210u;
    sts64(lc + l * 8, KW_P + ((r4 - 5) >> 1) * 16 + ((r4 - 5) & 1) * 4, s2 | ((d < 0 ? s2 : 0x7654u) << 16));
    const int lo = (d >= 4) - (d < -3), ho = (d >= 5) - (d < -2), le = (d > 4) - (d < -4), he = (d > 5) - (d < -3);
    sts32(lc + 512 + l * 8, (0x5454u + lo * 0x22 + ho * 0x2200) | ((0x3232u + le * 0x22 + he * 0x2200) << 16));
    const int cc = l >> 2, j = l & 3;
    sts64(lc + 256 + l * 8, (j >> 1) * PL_HALF + (16 + cc) * 16 + (j & 1) * 8, (cc >> 1) * (DM * 64) + (cc & 1) * 32 + j * 8);
}
__device__ __forceinline__ void conv_selectors4(Conv& c) {
    const uint2 v = lds64(c.lc + lane_v() * 8);
    c.pa = v.x; c.s2 = v.y;
}
__device__ __forceinline__ void conv_selectors8(Conv& c) { c.s8 = lds32(c.lc + 512 + lane_v() * 8); }
template <int G, int I0, int I1>
__device__ __forceinline__ void conv_load(const Conv& c, uint32_t (&q)[9]) {
    const int wq = c.warp & 3;
    if (G < 2) {
#pragma unroll
        for (int i = I0; i < I1; i++) q[i] = lds32(c.wa + G * 512 + i * 16);
    } else if (G < 4) {
        const uint32_t a = (G == 2 && wq == 0) ? c.wa + 1024 : c.pa + c.kw + wq * 128 + (G < 2 ? 0 : G - 2) * 512;
#pragma unroll
        for (int i = I0; i < I1; i++) q[i] = lds32(a + i * 16);
    } else {
        const uint4 u = lds128(c.kw + KW_H + (G < 4 ? 0 : G - 4) * 64 + wq * 16);
        const uint2 v = lds64(c.kw + KW_H + (G < 4 ? 0 : G - 4) * 64 + wq * 16 + 16);
        q[0] = u.x; q[1] = u.y; q[2] = u.z; q[3] = u.w; q[4] = v.x; q[5] = v.y;
        if (G == 4 && wq == 0) { q[6] = lds32(c.pa + c.kw + 1024); q[7] = lds32(c.pa + c.kw + 1040); }
    }
}
template <int G, int J0, int J1>
__device__ __forceinline__ void conv_frag(const Conv& c, const uint32_t (&q)[9], uint32_t* a, const Pk& dp) {
    const uint32_t dep = dp.w[0];
    if (G < 4) {
        const uint32_t s = (G < 2 || (G == 2 && (c.warp & 3) == 0)) ? c.id : c.s2;
#pragma unroll
        for (int j = J0; j < J1; j++) {
            uint32_t* o = a + 4 * (j - J0);
            o[0] = prmt_v(q[2 * j + 1], dp.w[0], s); o[1] = prmt_v(q[2 * j + 2], dp.w[1], s); o[2] = prmt_v(q[2 * j], dp.w[2], s); o[3] = prmt_v(q[2 * j + 1], dp.w[3], s);
        }
    } else {
        const uint32_t so = prmt_v(c.s8, dep, c.id), se = prmt_v(c.s8, dep, c.id + 0x22);
#pragma unroll
        for (int j = J0; j < J1; j++) {
            uint32_t* o = a + 4 * (j - J0);
            o[0] = prmt_v(q[j + 1], q[j + 2], se); o[1] = prmt_v(q[j + 1], q[j + 2], so); o[2] = prmt_v(q[j], q[j + 1], so);
            if (G == 4 && j == 0 && (c.warp & 3) == 0) {
                o[2] = prmt_v(q[6], dep, c.s2);
                o[0] = prmt_v(q[7], o[0], c.s2 >> 16);
            }
            o[3] = mov_v(o[0]);
        }
    }
}
template <int G, int J0, int J1>
__device__ __forceinline__ void conv_frag(const Conv& c, const uint32_t (&q)[9], uint32_t* a, float depf) {
    const uint32_t d = __float_as_uint(depf);
    conv_frag<G, J0, J1>(c, q, a, Pk{{d, d, d, d}});
}
template <int G, int T, int J0, int J1>
__device__ __forceinline__ void conv_mma(float (&acc)[16][4], const Conv& c, const uint32_t* a) {
#pragma unroll
    for (int j = J0; j < J1; j++) wg_mma<T>(acc, a + 4 * (j - J0), c.d0 - 8 * (2 * G - T) - j);
}
__device__ __forceinline__ float h_lo(uint32_t w) { return __half2float(__ushort_as_half((unsigned short)(w & 0xffffu))); }
__device__ __forceinline__ float h_hi(uint32_t w) { return __half2float(__ushort_as_half((unsigned short)(w >> 16))); }
__device__ __forceinline__ void flush_setup(Conv& c) {
    const uint2 v = lds64(c.lc + 256 + lane_v() * 8);
    c.fl = v.x; c.yo = v.y;
}
template <int Q>
__device__ __forceinline__ void flush_load(const Conv& c, uint32_t pl, uint2 (&f)[4]) {
#pragma unroll
    for (int w = 0; w < 4; w++) f[w] = lds64(c.fl + pl + (Q & 1) * 512 + w * (PLW_B - 64));
}
template <int Q>
__device__ __forceinline__ void flush_load_first(const Conv& c, uint32_t pl, uint2 (&f)[4], float depf) {
    const uint32_t p = prmt_v(c.fl, __float_as_uint(depf), c.id) + pl + (Q & 1) * 512;
#define LDV64(d, a) asm volatile("ld.volatile.shared.v2.u32 {%0,%1}, [%2];\n" : "=r"(d.x), "=r"(d.y) : "r"(a) : "memory")
    LDV64(f[0], p); LDV64(f[1], p + (PLW_B - 64)); LDV64(f[2], p + 2 * (PLW_B - 64)); LDV64(f[3], p + 3 * (PLW_B - 64));
}
#define FDEP __uint_as_float(f[3].y)
template <int Q, int mode>
__device__ __forceinline__ void conv_flush(const Conv& c, const uint2 (&f)[4], unsigned char* gy, uint32_t rx) {
    const uint32_t a0 = hadd2(f[0].x, f[1].x), a1 = hadd2(f[2].x, f[3].x), b0 = hadd2(f[0].y, f[1].y), b1 = hadd2(f[2].y, f[3].y);
    if (Q > 0 && mode == 1) {
        const uint32_t ra = rx + 16 + (Q > 0 ? Q - 1 : 0) * 1024 + (c.warp & 3) * 256 + lane_v() * 8;
        asm volatile("st.async.shared::cluster.mbarrier::complete_tx::bytes.v2.b32 [%0], {%1,%2}, [%3];\n"
                     ::"r"(ra ^ 0x1000000u), "r"(hadd2(a0, a1)), "r"(hadd2(b0, b1)), "r"((rx + (Q > 1 ? 8 : 0)) ^ 0x1000000u) : "memory");
        return;
    }
    float v0 = h_lo(a0) + h_lo(a1), v1 = h_hi(a0) + h_hi(a1), v2 = h_lo(b0) + h_lo(b1), v3 = h_hi(b0) + h_hi(b1);
    if (Q > 0 && mode == 2) {
        const uint2 o = lds64(rx + 16 + (Q > 0 ? Q - 1 : 0) * 1024 + (c.warp & 3) * 256 + lane_v() * 8);
        v0 += h_lo(o.x); v1 += h_hi(o.x); v2 += h_lo(o.y); v3 += h_hi(o.y);
    }
    const uint32_t lo = hmul2_bf(pack_bf16(v0, v1), c.fs), hi = hmul2_bf(pack_bf16(v2, v3), c.fs);
    stg64(gy + Q * 32 * DM * 32 + (c.yo + (Q < 3 ? c.yp : 0u)), nzw(lo), nzw(hi));
}
template <int I, bool S = false> struct IC { static constexpr int value = I; static constexpr bool shared = S; };
template <class T> __device__ constexpr bool wg_is4() { return T::shared; }
#define SLOT(n) (c.ps + (2 + ((n) & 7)) * 128)
#define GO() do { wg_commit(); __syncwarp(); } while (0)
#define DEP acc[15][3]
template <class FG, class FP, class FN>
__device__ __forceinline__ void conv_head(Conv& c, float (&acc)[16][4], uint32_t (&q)[9], uint32_t (&r)[9], uint32_t* a, FG fg, FP pre, FN next) {
    c.id = 0x3210u + (c.warp >> 8);
    if (ONEBAR) pre();
    conv_load<0, 0, 9>(c, q);
    conv_frag<0, 0, 1>(c, q, a, 0.f);
    if (!ONEBAR) pre();
    wg_fence(); wg_first<0>(acc, a, c.d0); GO();
    park(c.ps, Pk{{0u, 0u, 0u, 0u}});
    wg_wait0();
    conv_frag<0, 1, 2>(c, q, a, DEP);
    wg_fence(); conv_mma<0, 0, 1, 2>(acc, c, a); GO();
    fg(IC<0>());
    wg_wait0();
    conv_frag<0, 2, 3>(c, q, a, DEP);
    wg_fence(); conv_mma<0, 0, 2, 3>(acc, c, a); GO();
    conv_load<1, 0, 5>(c, r);
    wg_wait0();
    conv_frag<0, 3, 4>(c, q, a, DEP);
    wg_fence(); conv_mma<0, 0, 3, 4>(acc, c, a); GO();
    conv_load<1, 5, 9>(c, r);
    fg(IC<1>());
    wg_wait0();
    const Pk k = pk2(acc[0], acc[1]);
    conv_rename<2>(acc);
    conv_frag<1, 0, 2>(c, r, a, k);
    wg_fence(); conv_mma<1, 2, 0, 2>(acc, c, a); GO();
    park(SLOT(0), k);
    next(IC<0>());
    fg(IC<2>());
    wg_wait0();
    conv_frag<1, 2, 4>(c, r, a, DEP);
    wg_fence(); conv_mma<1, 2, 2, 4>(acc, c, a); GO();
    next(IC<1>());
    fg(IC<3>());
    wg_wait0();
}
template <class FG, class FP>
__device__ __forceinline__ void conv_run(Conv& c, uint32_t pl, unsigned char* gy, FG fg, FP pre) {
    float acc[16][4];
    uint32_t q[9], r[9], a[32];
    uint2 f[4];
    const int bid = 1 + (c.warp >> 2);
    conv_head(c, acc, q, r, a, fg, pre, [&](auto i) { if (decltype(i)::value == 0) conv_selectors4(c); else conv_load<2, 0, 9>(c, q); });
    Pk k = pk2(acc[2], acc[3]);
    conv_rename<4>(acc);
    conv_frag<2, 0, 4>(c, q, a, k);
    wg_fence(); conv_mma<2, 4, 0, 4>(acc, c, a); GO();
    park(SLOT(2), k);
    conv_load<3, 0, 9>(c, q);
    flush_setup(c);
    bar_sync(bid, 128);
    fg(IC<4>());
    wg_wait0();
    conv_rename<6>(acc);
    flush_load_first<0>(c, pl, f, DEP);
    conv_frag<3, 0, 4>(c, q, a, FDEP);
    wg_fence(); conv_mma<3, 6, 0, 4>(acc, c, a); GO();
    park(SLOT(4), pk2(acc[4], acc[5]));
    conv_load<4, 0, 9>(c, q);
    conv_selectors8(c);
    conv_flush<0, 0>(c, f, gy, 0u);
    fg(IC<5>());
    wg_wait0();
    conv_rename<8>(acc);
    conv_frag<4, 0, 4>(c, q, a, DEP);
    wg_fence(); conv_mma<4, 8, 0, 4>(acc, c, a); GO();
    k = pk2(acc[6], acc[7]);
    park(SLOT(6), k); park(c.ps, k);
    conv_load<5, 0, 9>(c, q);
    bar_sync(bid, 128);
    fg(IC<6>());
    wg_wait0();
    conv_rename<10>(acc);
    flush_load_first<1>(c, pl, f, DEP);
    conv_frag<5, 0, 4>(c, q, a, FDEP);
    wg_fence(); conv_mma<5, 10, 0, 4>(acc, c, a); GO();
    park(SLOT(8), pk2(acc[8], acc[9]));
    conv_load<6, 0, 9>(c, q); conv_load<7, 0, 9>(c, r);
    conv_flush<1, 0>(c, f, gy, 0u);
    fg(IC<7>());
    wg_wait0();
    conv_rename<12>(acc);
    conv_frag<6, 0, 4>(c, q, a, DEP); conv_frag<7, 0, 4>(c, r, a + 16, DEP);
    wg_fence(); conv_mma<6, 12, 0, 4>(acc, c, a); conv_mma<7, 12, 0, 4>(acc, c, a + 16); GO();
    park(SLOT(10), pk2(acc[10], acc[11]));
    bar_sync(bid, 128);
    flush_load<2>(c, pl, f);
    conv_flush<2, 0>(c, f, gy, 0u);
    fg(IC<8>());
    if (Q2FIX && c.id == 0) TRAP();
    wg_wait0();
    park(SLOT(12), pk2(acc[12], acc[13])); park(SLOT(14), pk2(acc[14], acc[15]));
    bar_sync(bid, 128);
    flush_load<3>(c, pl, f);
    conv_flush<3, 0>(c, f, gy, 0u);
}
template <class FG>
__device__ __forceinline__ void conv_outer(Conv& c, uint32_t pl, unsigned char* gy, uint32_t rx, FG fg) {
    float acc[16][4];
    uint32_t q[9], r[9], a[32];
    uint2 f[4], f2[4];
    const int bid = 1 + (c.warp >> 2);
    conv_head(c, acc, q, r, a, [&](auto gi) { if (decltype(gi)::value == 2) fg(IC<2, true>()); }, [&]() {}, [&](auto i) { if (decltype(i)::value == 0) conv_selectors8(c); else conv_load<6, 0, 9>(c, q); });
    park(SLOT(2), pk2(acc[2], acc[3])); park(SLOT(4), pk2(acc[4], acc[5]));
    const Pk k = pk2(acc[6], acc[7]);
    park(SLOT(6), k);
    conv_load<7, 0, 9>(c, r);
    conv_rename<12>(acc);
    conv_frag<6, 0, 4>(c, q, a, __uint_as_float(k.w[3])); conv_frag<7, 0, 4>(c, r, a + 16, __uint_as_float(k.w[3]));
    wg_fence(); conv_mma<6, 12, 0, 4>(acc, c, a); conv_mma<7, 12, 0, 4>(acc, c, a + 16); GO();
    flush_setup(c);
    bar_sync(bid, 128);
    flush_load<0>(c, pl, f); flush_load<1>(c, pl, f2);
    conv_flush<1, 1>(c, f2, gy, rx);
    conv_flush<0, 1>(c, f, gy, rx);
    wg_wait0();
    bar_sync(bid, 128);
    park(c.ps, k); park(SLOT(8), pk2(acc[8], acc[9])); park(SLOT(10), pk2(acc[10], acc[11]));
    park(SLOT(12), pk2(acc[12], acc[13])); park(SLOT(14), pk2(acc[14], acc[15]));
    bar_sync(bid, 128);
    flush_load<2>(c, pl, f); flush_load<3>(c, pl, f2);
    conv_flush<2, 1>(c, f, gy, rx);
    conv_flush<3, 1>(c, f2, gy, rx);
}
template <class FG>
__device__ __forceinline__ void conv_inner(Conv& c, uint32_t pl, unsigned char* gy, uint32_t rx, FG fg) {
    float acc[16][4];
    uint32_t q[9], a[16];
    uint2 f[4], f2[4];
    const int bid = 1 + (c.warp >> 2);
    c.id = 0x3210u + (c.warp >> 8);
    conv_selectors4(c);
    conv_load<2, 0, 9>(c, q);
    conv_frag<2, 0, 4>(c, q, a, 0.f);
    wg_fence(); wg_first<4>(acc, a, c.d0); conv_mma<2, 4, 1, 4>(acc, c, a + 4); GO();
    conv_load<3, 0, 9>(c, q);
    park(SLOT(2), Pk{{0u, 0u, 0u, 0u}});
    fg(IC<2, true>());
    wg_wait0();
    conv_rename<6>(acc);
    conv_frag<3, 0, 4>(c, q, a, DEP);
    wg_fence(); conv_mma<3, 6, 0, 4>(acc, c, a); GO();
    park(SLOT(4), pk2(acc[4], acc[5]));
    conv_load<4, 0, 9>(c, q);
    conv_selectors8(c);
    wg_wait0();
    conv_rename<8>(acc);
    conv_frag<4, 0, 4>(c, q, a, DEP);
    wg_fence(); conv_mma<4, 8, 0, 4>(acc, c, a); GO();
    const Pk k = pk2(acc[6], acc[7]);
    park(SLOT(6), k); park(c.ps, k);
    conv_load<5, 0, 9>(c, q);
    flush_setup(c);
    wg_wait0();
    conv_rename<10>(acc);
    conv_frag<5, 0, 4>(c, q, a, DEP);
    wg_fence(); conv_mma<5, 10, 0, 4>(acc, c, a); GO();
    park(SLOT(8), pk2(acc[8], acc[9]));
    bar_sync(bid, 128);
    flush_load<1>(c, pl, f);
    mbar_wait(rx);
    conv_flush<1, 2>(c, f, gy, rx);
    wg_wait0();
    bar_sync(bid, 128);
    park(SLOT(10), pk2(acc[10], acc[11])); park(SLOT(12), pk2(acc[12], acc[13])); park(SLOT(14), pk2(acc[14], acc[15]));
    bar_sync(bid, 128);
    flush_load<3>(c, pl, f); flush_load<2>(c, pl, f2);
    mbar_wait(rx + 8);
    conv_flush<3, 2>(c, f, gy, rx);
    conv_flush<2, 2>(c, f2, gy, rx);
}
#undef SLOT
#undef GO
#undef DEP
template <int U0, int U1>
__device__ __forceinline__ void weight_units(uint32_t sb, const CUtensorMap* tg, const CUtensorMap* tu, const CUtensorMap* td, bool w) {
    if (U1 > U0 && w && elect_one()) {
#pragma unroll
        for (int n = U0; n < U1; n++) {
            const int i = n;
            if (i < 12) tma_2d(sb + SM_WG + i * 6912, i < 6 ? tg : tu, 72 * (blockIdx.x >> 1), 288 * (blockIdx.x & 1) + (i % 6) * 48, sb + SM_MISC + 328);
            else tma_2d(sb + SM_WD + (i - 12) * 4736, td, 144 * (blockIdx.x & 1), 72 * (blockIdx.x >> 1) + 8 * (i - 12), sb + SM_MISC + 336);
        }
    }
}
#define WS 1111121111122004100
__device__ constexpr int wsched(int i) {
    unsigned long long v = WS;
    int n = 0;
    for (int k = 19; k >= 1; k--) { if (k < i) n += (int)(v % 10); v /= 10; }
    return n;
}
static_assert(wsched(20) == 21 && wsched(6) <= 7 && wsched(11) <= 12 && wsched(13) <= 14 && wsched(16) <= 17 && wsched(16) == wsched(15) && wsched(19) == 21, "");
__device__ __forceinline__ void weight_prefetch(const Params& p, int u, int lane) {
    const int b = blockIdx.x;
    const char* a = u < 12 ? reinterpret_cast<const char*>(u < 6 ? p.wg : p.wu) + ((b >> 6) * 288 + (u % 6) * 48) * (FF * 2) + (b & 63) * 6912
                           : reinterpret_cast<const char*>(p.wd) + (72 * (b >> 1) + 8 * (u - 12)) * 1152 + (b & 1) * 4608;
    asm volatile("prefetch.global.L2 [%0];\n" ::"l"(a + lane * 128));
    if (lane < (u < 12 ? 22 : 4)) asm volatile("prefetch.global.L2 [%0];\n" ::"l"(a + 4096 + lane * 128));
}
#define PF0 0
#define PF1 0
#define WPOINT(i, w) do { weight_units<wsched(i), wsched(i + 1)>(sb, &tm_g, &tm_u, &tm_d, w); } while (0)

__global__ void __launch_bounds__(NTHR, 1) __cluster_dims__(2, 1, 1)
fused_kernel(const Params p, const __grid_constant__ CUtensorMap tm_g, const __grid_constant__ CUtensorMap tm_u, const __grid_constant__ CUtensorMap tm_d, const __grid_constant__ CUtensorMap tm_x) {
    extern __shared__ __align__(1024) unsigned char smem[];
    const uint32_t sb = smem_u32(smem);
    const int tid = threadIdx.x, warp = __shfl_sync(0xffffffffu, tid >> 5, 0), lane = tid & 31;
    const int b = blockIdx.x, P = b >> 1, odd = b & 1;
    const int g = lane >> 2, t = lane & 3;
    const int wg = warp >> 2, t128 = tid & 127;
    const uint32_t s_stat = sb + SM_MISC;
    const uint32_t s_key = sb + SM_MISC + 128;
    const uint32_t s_rank = sb + SM_MISC + 256;
    const uint32_t s_k16 = sb + SM_MISC + 192;
    const uint32_t s_cnt = sb + SM_MISC + 320;
    const uint32_t bar_w = sb + SM_MISC + 328, bar_d = bar_w + 8, bar_g = bar_w + 16, bar_x = bar_w + 24, bar_t = bar_w + 32, bar_s = bar_w + 40, bar_v = bar_w + 48, bar_h = sb + SM_MISC + 160;
    STAMP(0);

    if (warp == 19) {
        if (lane == 0) {
            mbar_init(bar_w, 1); mbar_init(bar_d, 1); mbar_init(bar_g, 1); mbar_init(sb + SM_RX, 1); mbar_init(sb + SM_RX + 8, 1);
            mbar_init(bar_x, 1); mbar_init(bar_t, 1); mbar_init(bar_s, 1); mbar_init(bar_v, 2); if (HOLD >= 2) { mbar_init(bar_h, 1); mbar_init(bar_h + 8, 1); mbar_init(bar_h + 16, 1); mbar_init(bar_h + 24, 1); } mbar_expect(bar_x, 32768);
            asm volatile("fence.mbarrier_init.release.cluster;\n" ::: "memory");
            mbar_expect(bar_w, 82944); mbar_expect(bar_d, 72 * WD_PITCH); mbar_expect(bar_g, 4608); mbar_expect(bar_t, 16 * 1152); mbar_expect(bar_v, 2 * 1152); mbar_expect(sb + SM_RX, 1024); mbar_expect(sb + SM_RX + 8, 2048);
        }
        __syncwarp();
    }
    if (wg < 3) { sts128(sb + SM_Z2 + tid * 16, 0u, 0u, 0u, 0u); sts128(sb + SM_Z2 + 6144 + tid * 16, 0u, 0u, 0u, 0u); fence_async(); }
    const int ch = wg < 4 ? 4 * b + wg : 512 + P;
    const bf16 *q0 = p.lar + ch * NST, *q1 = p.aim + ch * NST, *q2 = p.cre + ch * NST, *q3 = p.cim + ch * NST;
    asm volatile("" : "+l"(q0), "+l"(q1), "+l"(q2), "+l"(q3));
    const uint32_t ldt = ldo16(p.ldt + ch), pl = ldo16(q0 + t128), pa2 = ldo16(q1 + t128);
    const uint32_t pc = ldo16(q2 + t128), pi = ldo16(q3 + t128);
    const uint2 call_re = ldo64(q2 + 4 * lane), call_im = ldo64(q3 + 4 * lane);
    const uint32_t epl = ld_poll32(p.s->hint + (b & 7) * 32 + 1);
    bar_sync(0, NWRK);
    if (XCP && wg == 4) {
        const int o = (4 * (warp & 3) + (g >> 1)) * 1152 + (g & 1) * 576 + t * 16;
#pragma unroll
        for (int c = 0; c < 9; c++)
            asm volatile("cp.async.cg.shared.global [%0], [%1], 16;\n" ::"r"(sb + SM_XT + o + c * 64), "l"(reinterpret_cast<const char*>(p.x) + b * 18432 + o + c * 64) : "memory");
        asm volatile("cp.async.commit_group;\n" ::: "memory");
    }
    asm volatile("barrier.cluster.arrive.relaxed.aligned;\n" ::: "memory");
    if (warp == 18) {
        if (lane == 0) {
            if (!XCP) bulk_g2s(sb + SM_XT, p.x + (size_t)16 * b * DM, 16 * 1152, bar_t);
            bulk_s2g(reinterpret_cast<unsigned char*>(p.s->y) + 96 * 18432 + b * 4608, sb + SM_Z2, 4608);
        }
        bar_arrive(12, 64);
    }
    if (warp == 19) {
        bar_sync(12, 64);
        asm volatile("barrier.cluster.wait.aligned;\n" ::: "memory");
        if (EXP & 4) { if (elect_one()) asm volatile("mbarrier.complete_tx.relaxed.cta.shared::cta.b64 [%0], %1;" :: "r"(bar_x), "r"(32768) : "memory"); }
        else if (EXP & 8) { if (elect_one()) { tma_4d(sb + SM_XC + odd * 16384, &tm_x, 8 * P, 2 * odd, bar_x); asm volatile("mbarrier.complete_tx.relaxed.cta.shared::cta.b64 [%0], %1;" :: "r"(bar_x), "r"(16384) : "memory"); } }
        else
        if (elect_one()) tma_4d_mc(sb + SM_XC + odd * 16384, &tm_x, 8 * P, 2 * odd, bar_x);
        __syncwarp();
    }
    const uint32_t kw = sb + SM_KW + wg * KW_B;
    const uint32_t tb = table_buf(sb, warp), t5 = sb + SM_WD + warp * 512;
    if (wg == 4) {
        if (!(g & 1) && t == (g >> 1)) *reinterpret_cast<volatile uint32_t*>(p.s->stat + 16 * b + 4 * (warp & 3) + t) = 0u;
        if (warp < 18) {
            unsigned char* const ud = reinterpret_cast<unsigned char*>(p.s->uT) + (size_t)(8 * (warp & 1) + 2 * (g >> 1)) * 16384 + b * 128 + (g & 1) * 32 + t * 8;
#pragma unroll
            for (int k = 0; k < 4; k++) *reinterpret_cast<volatile unsigned long long*>(ud + (k >> 1) * 16384 + (k & 1) * 64) = 0ull;
        }
        if (warp == 17) conv_constants(sb + SM_LC, lane);
    }
    if (t128 < 2 * UPAD) sts128(sb + SM_U + wg * USLOT_B + (t128 & 1) * ULO_B + (t128 >> 1) * 16, 0u, 0u, 0u, 0u);
    if (t128 >= 124) sts128(kw + (t128 & 1) * 16 + (t128 & 2) * (KW_PL / 2), 0u, 0u, 0u, 0u);
    uint32_t co, cn, cd;
    combine_setup(sb, warp, lane, kw, co, cn, cd);
    const uint4* usrc = wg < 4 ? reinterpret_cast<const uint4*>(p.s->stat) + tid
                               : reinterpret_cast<const uint4*>(p.s->uT) + (P >> 2) * 1024 + (t128 >> 1) * 8 + (P & 3) * 2 + (t128 & 1);
    uint32_t zero;
    {
        uint32_t uo = (uint32_t)(reinterpret_cast<const char*>(usrc) - reinterpret_cast<const char*>(p.s)), pk = (cn - co + 1024) | ((cd - kw) << 16);
        asm volatile("st.volatile.shared.v4.u32 [%4], {0, %1, %2, %3};\nld.volatile.shared.v4.u32 {%0, %1, %2, %3}, [%4];\n" : "=r"(zero), "+r"(co), "+r"(pk), "+r"(uo) : "r"(tb + lane * 16) : "memory");
        cn = co + (pk & 0xffffu) - 1024; cd = kw + (pk >> 16);
        usrc = reinterpret_cast<const uint4*>(reinterpret_cast<const char*>(p.s) + uo);
    }
    const float dt = exp_bf(__uint_as_float(__byte_perm(ldt, zero, 0x1044)));
    const uint32_t ep = __reduce_or_sync(0xffffffffu, epl | zero);
    auto stats = [&]() {
        const int wq = warp & 3;
        const uint32_t xa = sb + SM_XT + (4 * wq + (g >> 1)) * 1152 + (g & 1) * 576 + t * 16;
        const bool own = !(g & 1) && t == (g >> 1);
        float d[4][4] = {};
        if (XCP) asm volatile("cp.async.wait_group 0;\n" ::: "memory"); else mbar_wait(bar_t);
        if ((HOLD == 2 || HOLD == 5) && lane == 0) mbar_arrive(bar_h + 8 * wq);
        STAMP(26);
        uint4 v[9];
#pragma unroll
        for (int c = 0; c < 9; c++) v[c] = lds128(xa + c * 64);
#pragma unroll
        for (int c = 0; c < 9; c++) {
            mma_bf16(d[2 * (c & 1)], v[c].x, 0x3f803f80u, v[c].y, 0x3f803f80u, v[c].x, v[c].y);
            mma_bf16(d[2 * (c & 1) + 1], v[c].z, 0x3f803f80u, v[c].w, 0x3f803f80u, v[c].z, v[c].w);
        }
        STAMP(27);
        float sm = (g & 1) ? (d[0][3] + d[1][3]) + (d[2][3] + d[3][3]) : (d[0][2] + d[1][2]) + (d[2][2] + d[3][2]);
        float sq = (g & 1) ? (d[0][1] + d[1][1]) + (d[2][1] + d[3][1]) : (d[0][0] + d[1][0]) + (d[2][0] + d[3][0]);
        sm += __shfl_xor_sync(0xffffffffu, sm, 4); sq += __shfl_xor_sync(0xffffffffu, sq, 4);
        if (HOLD == 1) bar_arrive(6 + wq, 160);
        if (HOLD >= 2 && HOLD != 4 && lane == 0) mbar_arrive(bar_h + 8 * wq);
        float mb, sd;
        ln_stats(sm, sq, mb, sd);
        if (own) p.s->stat[16 * b + 4 * wq + t] = (__float_as_uint(mb) >> 16) | (__float_as_uint(sd) & 0x7fff0000u) | (ep << 31);
        STAMPX(22);
        if (HOLD == 4 && lane == 0) mbar_arrive(bar_h + 8 * wq);
        if (own) stat_store(s_stat + (2 * wq + (t & 1) + 8 * (t >> 1)) * 8, mb, rcp_approx(sd), 0u);
        if (wq == 2) asm volatile("cp.async.bulk.wait_group 0;\n" ::: "memory");
        bar_sync(5, 128);
        STAMP(28);
        if (wq == 2) {
            if (lane < 8) p.s->key3[8 * b + lane] = ep & 1u;
            if (lane == 0) {
                uint32_t now;
                asm volatile("mov.u32 %0, %%clock;" : "=r"(now));
                sts64(s_cnt, now, ep);
                mbar_arrive(bar_s);
                bulk_g2s(sb + SM_XT + 16 * 1152, p.dsk, 1152, bar_v);
                bulk_g2s(sb + SM_XT + 17 * 1152, p.wr, 1152, bar_v);
            }
            __syncwarp();
        }
        WPOINT(1, wq == 3);
        if (wq < 2) {
            unsigned char* const ud = reinterpret_cast<unsigned char*>(p.s->uT) + (size_t)(8 * wq + 2 * (g >> 1)) * 16384 + b * 128 + (g & 1) * 32 + t * 8;
            const uint32_t utag = (ep % 7u + 1u) * 0x10001u;
            uint32_t U[2][4];
#pragma unroll
            for (int hf = 0; hf < 2; hf++) {
                const uint2 st = lds64(s_stat + (g + 8 * hf) * 8);
                const uint4 xu = lds128(sb + SM_XT + (TOK(g) + 2 * hf) * 1152 + warp * 64 + t * 16);
                const uint32_t X[4] = {xu.x, xu.y, xu.z, xu.w};
#pragma unroll
                for (int k = 0; k < 4; k++) {
                    const uint32_t u = ln_apply(X[k], STAT_M(st), STAT_H(st), STAT_L(st));
                    U[hf][k] = movm((pack_f16(bf_lo(u), bf_hi(u)) & 0xfff8fff8u) | utag);
                }
            }
#pragma unroll
            for (int k = 0; k < 4; k++) stg64(ud + (k >> 1) * 16384 + (k & 1) * 64, U[0][k], U[1][k]);
        }
    };
    STAMP(1);
    if (wg < 4) { STAMPX(16); }
    if (SORD == 0 && wg == 4) stats();
    KGen kg;
    kgen_setup(kg, __uint_as_float(__byte_perm(pl, zero, 0x1044)), __uint_as_float(__byte_perm(pa2, zero, 0x1044)), dt);
    kgen_rows(kg, tb, lane);
    STAMP(2);
    const int E = min(max(c_exponent(call_re, call_im, dt) - 243, -120), 120);
    kgen_chain(kg, pc, pi, dt * __uint_as_float((uint32_t)(128 - E) << 23));
    STAMP(3);
    kgen_cols(kg, tb, t5, lane);
    STAMP(4);
    if (SORD == 1 && wg == 4) stats();
    if (warp != 19) asm volatile("barrier.cluster.wait.aligned;\n" ::: "memory");
    if (wg < 4) { STAMPX(17); }
    if (HOLD == 1 && wg < 4) bar_sync(6 + (warp & 3), 160);
    if ((HOLD == 3 || HOLD == 4) && wg < 4) mbar_wait(bar_h + 8 * (warp & 3));
    if (HOLD == 2 || HOLD == 5) mbar_wait1(bar_h + 8 * (warp & 3));
    if (wg < 4) { STAMPX(19); }
    if (DEFER == 1 && wg == 4) bar_sync(14, NWRK);
    if (DEFER > 1 && wg == 4) bar_sync(15, NWRK);
    kgen_mma(kg, tb, t5, lane, bar_h + 8 * (warp & 3));
    if (wg < 4) { STAMPX(20); }
    if (DEFER == 3 && wg < 4) bar_arrive(15, NWRK);
    STAMP(5);
    if (SORD == 2 && wg == 4) stats();
    uint4 uv0, uv1;
    auto first_poll = [&](uint32_t dly) {
        mbar_wait(bar_s);
        const uint32_t t0 = lds32(s_cnt);
        uint32_t now;
        do { asm volatile("mov.u32 %0, %%clock;" : "=r"(now) :: "memory"); } while (now - t0 < dly);
        uv0 = ld_poll(usrc);
    };
    WPOINT(2, warp == 19);
    if (PEARLY == 3 && wg < 4) first_poll(SDLY);
    bar_sync(1 + wg, 128);
    if (PEARLY == 2 && wg < 4) first_poll(SDLY);
    if (wg < 4) { STAMPX(21); }
    kgen_combine(warp & 3, lane, co, cn, cd);
    STAMP(6);
    if (wg < 4) { STAMPX(18); }
    if (DEFER == 2 && wg < 4) bar_arrive(15, NWRK);
    WPOINT(3, warp == 19);
    if (PEARLY == 1 && wg < 4) first_poll(SDLY);
    {
        const int wq = warp & 3;
        Conv c;
        const uint32_t pln = sb + SM_PL + wg * PL_B;
        const int e = g - 2 * t + 7;
        c.kw = kw; c.wa = pin(kw + ((e >> 2) & 1) * KW_PL + (8 * wq + (e >> 3)) * 16 + (e & 3) * 4);
        c.ps = mov_v(pln + wq * PLW_B + ((lane >> 3) & 1) * PL_HALF + ((lane >> 4) * 8 + (lane & 7)) * 16); c.warp = warp;
        c.lc = sb + SM_LC; c.fs = (uint32_t)(127 + E) * 0x800080u; c.yp = (ep & 1u) * (NCTA * 18432u);
        c.d0 = ((uint64_t)(ULO_B >> 4) << 16) | ((uint64_t)(128 >> 4) << 32) | (uint64_t)(((sb + SM_U + wg * USLOT_B + UPAD * 16) & 0x3FFFF) >> 4);
        unsigned char* gy = reinterpret_cast<unsigned char*>(p.s->y) + ((size_t)(4 * wq) * DM + ch) * 64;
        auto hook = [&](auto gi) {
                     constexpr int G = decltype(gi)::value;
                     if (G == (wg_is4<decltype(gi)>() ? 2 : 5)) asm volatile("barrier.cluster.wait.aligned;\n" ::: "memory");
                     if (!wg_is4<decltype(gi)>() && (G == RG0 || G == RG1) && warp == HW && elect_one()) {
                         unsigned char* const sc = reinterpret_cast<unsigned char*>(p.s);
                         if (G == RG0) {
                             if (b < 96) bulk_s2g_nc(sc + offsetof(Scratch, part) + b * 12288, sb + SM_Z2, 12288);
                             bulk_s2g(sc + offsetof(Scratch, rows) + (127 - b) * 4608, sb + SM_Z2, 4608);
                         }
                         if (G == RG1) {
                             bulk_s2g_nc(sc + offsetof(Scratch, y) + (NCTA * 18432u - c.yp) + b * 13824, sb + SM_Z2, 6912);
                             bulk_s2g(sc + offsetof(Scratch, y) + (NCTA * 18432u - c.yp) + b * 13824 + 6912, sb + SM_Z2, 6912);
                         }
                     }
                     if (!wg_is4<decltype(gi)>() && PF1 && G >= PF1 && G < PF1 + 2 && (warp >> 1) == 2) weight_prefetch(p, 17 + 2 * (G - PF1) + (warp & 1), lane_v());
                     if (!wg_is4<decltype(gi)>()) WPOINT(6 + G, warp == (G >= 7 ? HW : WSP ? 4 * (G % 3) + 1 : 12 + (G & 3)));
                     if (!wg_is4<decltype(gi)>() && G == XG && warp == HW) {
                         asm volatile("cp.async.bulk.wait_group 0;\n" ::: "memory");
                         __syncwarp();
                         if (elect_one()) mbar_arrive(bar_v);
                     }
                 };
        if (!ONEBAR) bar_sync(1 + wg, 128);
        if (wg < 4) {
            asm volatile("barrier.cluster.arrive.relaxed.aligned;\n" ::: "memory");
            conv_run(c, pln + wq * 128, gy, hook, [&]() {
                STAMPX(23);
                mbar_wait(bar_x);
                STAMP(9);
                STAMPX(24);
                uint2 xc[4];
                uint32_t xw[4][2];
#pragma unroll
                for (int j = 0; j < 4; j++) xc[j] = lds64(sb + SM_XC + wg * 8192 + j * 2048 + t128 * 16 + odd * 8);
#pragma unroll
                for (int i = 0; i < 8; i++) {
                    const int k = i >> 1, h = i & 1;
                    xw[k][h] = prmt_v(k < 2 ? xc[2 * h].x : xc[2 * h].y, k < 2 ? xc[2 * h + 1].x : xc[2 * h + 1].y, (k & 1) ? 0x7632 : 0x5410);
                }
                const uint32_t ub = mov_v(sb + SM_U + UPAD * 16 + ((tid >> 1) & 1) * ULO_B + (tid >> 2) * 16 + (tid & 1) * 8), tag = ep << 31;
                int it = 0;
                if (!PEARLY) first_poll(SDLY);
                while (min(min((int)(uv0.x ^ tag), (int)(uv0.y ^ tag)), min((int)(uv0.z ^ tag), (int)(uv0.w ^ tag))) < 0x10000) {
                    if (++it > SPIN_LIMIT) TRAP();
                    uv0 = ld_poll(usrc);
                }
                STAMP(8);
                STAMPX(26);
                const float r0 = rcp_approx(fabsf(bf_hi(uv0.x))), r1 = rcp_approx(fabsf(bf_hi(uv0.y))), r2 = rcp_approx(fabsf(bf_hi(uv0.z))), r3 = rcp_approx(fabsf(bf_hi(uv0.w)));
                const uint32_t m[2] = {__byte_perm(uv0.x, uv0.y, 0x5410), __byte_perm(uv0.z, uv0.w, 0x5410)};
                const uint32_t rh[2] = {pack_bf16(r0, r1), pack_bf16(r2, r3)};
                const uint32_t rl[2] = {pack_bf16(r0 - bf_lo(rh[0]), r1 - bf_hi(rh[0])), pack_bf16(r2 - bf_lo(rh[1]), r3 - bf_hi(rh[1]))};
#pragma unroll
                for (int k = 0; k < 4; k++) {
                    const uint32_t u0 = ln_apply(xw[k][0], m[0], rh[0], rl[0]), u1 = ln_apply(xw[k][1], m[1], rh[1], rl[1]);
                    sts64(ub + k * USLOT_B, pack_f16(bf_lo(u0), bf_hi(u0)), pack_f16(bf_lo(u1), bf_hi(u1)));
                }
                STAMPX(29);
                fence_async();
                bar_sync(14, DEFER == 1 ? NWRK : 512);
                STAMP(7);
            });
        } else {
            auto stage = [&]() {
                const uint32_t tag = (ep % 7u + 1u) * 0x10001u;
                int it = 0;
                WPOINT(4, warp == 19);
                first_poll(UDLY);
                uv1 = ld_poll(usrc + 512);
                WPOINT(5, warp == 19);
                while (true) {
                    uv0.x ^= tag; uv0.y ^= tag; uv0.z ^= tag; uv0.w ^= tag; uv1.x ^= tag; uv1.y ^= tag; uv1.z ^= tag; uv1.w ^= tag;
                    if ((((uv0.x | uv0.y | uv0.z) | (uv0.w | uv1.x | uv1.y) | (uv1.z | uv1.w)) & 0x70007u) == 0) break;
                    if (++it > SPIN_LIMIT) TRAP();
                    uv0 = ld_poll(usrc); uv1 = ld_poll(usrc + 512);
                }
                STAMP(8);
                const uint32_t ub = sb + SM_U + UPAD * 16 + 4 * USLOT_B + (t128 & 1) * ULO_B + (t128 >> 1) * 16;
                sts128(ub, uv0.x, uv0.y, uv0.z, uv0.w);
                sts128(ub + 1024, uv1.x, uv1.y, uv1.z, uv1.w);
                fence_async();
                asm volatile("barrier.cluster.arrive.relaxed.aligned;\n" ::: "memory");
                bar_sync(5, 128);
                STAMP(7);
            };
            stage();
            if (odd) conv_inner(c, pln + wq * 128, gy, sb + SM_RX, hook);
            else conv_outer(c, pln + wq * 128, gy, sb + SM_RX, hook);
        }
        STAMP(10);
    }
    {
    const int lane = lane_v(), tid = 32 * warp + lane, g = lane >> 2, t = lane & 3;
    const uint32_t par = ~ep & 1u;
    if (CBAR) bar_sync(0, NWRK);
    STAMP(11);
    uint32_t H[2][4] = {}, U2[2][4] = {};
    auto publish = [&](bool hi, int slot) {
        uint4* rowp = reinterpret_cast<uint4*>(p.s->rows) + slot * 144 + warp * 4 + t;
        stg128(rowp, nzw(hi ? U2[1][0] : U2[0][0]), nzw(hi ? U2[1][1] : U2[0][1]), nzw(hi ? U2[1][2] : U2[0][2]), nzw(hi ? U2[1][3] : U2[0][3]));
        stg128(rowp + 72, nzw(hi ? H[1][0] : H[0][0]), nzw(hi ? H[1][1] : H[0][1]), nzw(hi ? H[1][2] : H[0][2]), nzw(hi ? H[1][3] : H[0][3]));
    };
#define KTOK(k) (int)(((~(k) >> 5) & 0x7f0u) | (((k) >> 1) & 15u))
#define KLATE(k) (((k) & 0x1e0u) < 0xe0u)
#define KSLOT(k, s) (KLATE(k) ? 2 * NCTA + (s) : (int)(((k) >> 8) & 0xffu))
    const uint4* const rsrc = reinterpret_cast<const uint4*>(p.s->rows) + 36 * odd;
    auto gather = [&](uint32_t mine) {
        int it = 0;
        uint32_t mn;
        do {
            mn = 1;
#pragma unroll 1
            for (int r = 0; r < 9; r++) {
                const uint32_t k = __shfl_sync(0xffffffffu, mine, r < 8 ? 4 * r : lane);
                const int row = r < 8 ? r : g, c = r < 8 ? lane : 32 + t;
                asm volatile("cp.async.cg.shared.global [%0], [%1], 16;\n" ::"r"(sb + SM_XS + row * XS_PITCH + c * 16), "l"(rsrc + KSLOT(k, row) * 144 + c) : "memory");
            }
            asm volatile("cp.async.wait_all;\n" ::: "memory");
#pragma unroll 1
            for (int r = 0; r < 9; r++) mn = min(mn, min4(lds128(sb + SM_XS + (r < 8 ? r * XS_PITCH + lane * 16 : g * XS_PITCH + (32 + t) * 16))));
            if (++it > SPIN_LIMIT) TRAP();
        } while (__any_sync(0xffffffffu, mn == 0));
    };
    auto late_rows = [&](auto role) {
        const uint32_t kk = lds32(s_key + (lane & 7) * 4), ep = lds32(s_cnt + 4);
        const bool own = KLATE(kk) && (KTOK(kk) >> 4) == b;
        uint32_t todo = __ballot_sync(0xffffffffu, own) & 0xffu;
        if (decltype(role)::value == 0 && todo) {
#pragma unroll
            for (int hf = 0; hf < 2; hf++) {
                const uint4 h = lds128(sb + SM_U + hf * 9216 + tid * 16);
                const uint2 st = lds64(s_stat + (g + 8 * hf) * 8);
                H[hf][0] = h.x; H[hf][1] = h.y; H[hf][2] = h.z; H[hf][3] = h.w;
#pragma unroll
                for (int k = 0; k < 4; k++) U2[hf][k] = ln_apply(H[hf][k], STAT_M(st), STAT_H(st), STAT_L(st));
            }
#pragma unroll 1
            while (todo) {
                const int s = __ffs(todo) - 1, tk = KTOK(__shfl_sync(0xffffffffu, kk, s));
                todo &= todo - 1;
                if ((tk & 13) == TOK(g)) publish(tk & 2, 2 * NCTA + s);
            }
            __threadfence();
        }
        bar_sync(0, NWRK);
        if (decltype(role)::value == 1) {
            if (lane < NSEL && own) *reinterpret_cast<volatile unsigned*>(p.s->flag + lane) = ep + 1u;
            int it = 0;
            while (__any_sync(0xffffffffu, KLATE(kk) && ld_acquire32(p.s->flag + (lane & 7)) != ep + 1u)) { if (++it > SPIN_LIMIT) TRAP(); }
            gather(__shfl_sync(0xffffffffu, kk, g));
        }
        bar_sync(0, NWRK);
    };
    if (warp < 18) {
        const unsigned char* ys = reinterpret_cast<const unsigned char*>(p.s->y) + (b < 96 ? (par ^ 1u) * (NCTA * 18432u) : 0u) +
                                  ((P * DM + 32 * warp + 8 * (g >> 1) + (g & 1)) * 64 + odd * 32 + t * 8);
        uint2 yv[4];
        const bool early = YFROM && b < YFROM && warp < 16;
        if (early) {
#pragma unroll
            for (int k = 0; k < 4; k++) yv[k] = ld_poll64(ys + k * 128);
        }
        mbar_wait(bar_v);
        const uint32_t xa = sb + SM_XT + warp * 64 + t * 16;
        const uint4 x0 = lds128(xa + TOK(g) * 1152), x1 = lds128(xa + (TOK(g) + 2) * 1152), dk = lds128(xa + 16 * 1152);
        uint4 wr = make_uint4(0u, 0u, 0u, 0u);
        if (g == 0) wr = lds128(xa + 17 * 1152);
        const uint32_t Z[2][4] = {{x0.x, x0.y, x0.z, x0.w}, {x1.x, x1.y, x1.z, x1.w}}, D4[4] = {dk.x, dk.y, dk.z, dk.w};
#pragma unroll
        for (int hf = 0; hf < 2; hf++) {
            const uint2 st = lds64(s_stat + (g + 8 * hf) * 8);
#pragma unroll
            for (int k = 0; k < 4; k++) U2[hf][k] = hmul2_bf(ln_apply(Z[hf][k], STAT_M(st), STAT_H(st), STAT_L(st)), D4[k]);
        }
        const uint32_t la = pin(sb + SM_LNP + (g * 20 + warp) * 4 + (U2[0][3] & U2[1][3] & (warp >> 8)));
        if (YDLY > 1) delay(YDLY);
        int it = 0;
        float d[2][4];
        uint32_t mn;
        do {
            if (!early || it) {
#pragma unroll
                for (int k = 0; k < 4; k++) yv[k] = ld_poll64(ys + k * 128);
            }
            if (++it > SPIN_LIMIT) TRAP();
            mn = min(min(min(yv[0].x, yv[0].y), min(yv[1].x, yv[1].y)), min(min(yv[2].x, yv[2].y), min(yv[3].x, yv[3].y)));
#pragma unroll
            for (int k = 0; k < 4; k++) {
                H[0][k] = hadd2_bf(Z[0][k], hadd2_bf(movm(yv[k].x), U2[0][k]));
                H[1][k] = hadd2_bf(Z[1][k], hadd2_bf(movm(yv[k].y), U2[1][k]));
            }
            ln_partial(H, d);
        } while (__any_sync(0xffffffffu, mn == 0));
        STAMP(12);
        CNT(27, it);
        if (t == (g >> 1)) {
            stsf(la, (g & 1) ? d[0][3] : d[0][2]); stsf(la + 8 * 80, (g & 1) ? d[1][3] : d[1][2]);
            stsf(la + 16 * 80, (g & 1) ? d[0][1] : d[0][0]); stsf(la + 24 * 80, (g & 1) ? d[1][1] : d[1][0]);
        }
        bar_arrive(6, NWRK);
        STAMP(13);
        bar_sync(7, 608);
        STAMP(14);
#pragma unroll
        for (int hf = 0; hf < 2; hf++) {
            const uint2 st = lds64(s_stat + (g + 8 * hf) * 8);
#pragma unroll
            for (int k = 0; k < 4; k++) U2[hf][k] = ln_apply(H[hf][k], STAT_M(st), STAT_H(st), STAT_L(st));
        }
        {
            float cs[4] = {0.f, 0.f, 0.f, 0.f};
            mma_bf16(cs, U2[0][0], U2[1][0], U2[0][1], U2[1][1], wr.x, wr.y);
            mma_bf16(cs, U2[0][2], U2[1][2], U2[0][3], U2[1][3], wr.z, wr.w);
            if (t == 0) { stsf(la + 32 * 80, cs[0]); stsf(la + 40 * 80, cs[2]); }
            bar_arrive(8, 608);
        }
        bar_sync(9, 608);
        {
            const uint2 best = lds64(s_rank);
            uint32_t todo = ((best.x & 26u) == 2 * TOK(g) ? 2u : 0u) | ((best.y & 26u) == 2 * TOK(g) ? 1u : 0u);
#pragma unroll 1
            while (todo) { publish((todo & 2u ? best.x : best.y) & 4u, 254 - 2 * b + (todo >> 1)); todo &= todo >> 1; }
        }
#pragma unroll
        for (int hf = 0; hf < 2; hf++) {
            sts128(sb + SM_OUT + (TOK(g) + 2 * hf) * (DM * 2) + warp * 64 + t * 16,
                   hadd2_bf(H[hf][0], U2[hf][0]), hadd2_bf(H[hf][1], U2[hf][1]), hadd2_bf(H[hf][2], U2[hf][2]), hadd2_bf(H[hf][3], U2[hf][3]));
            sts128(sb + SM_U + hf * 9216 + tid * 16, H[hf][0], H[hf][1], H[hf][2], H[hf][3]);
        }
        STAMP(15);
        const int mi = lane >> 3, rr = lane & 7;
        const bool gate = RMAP ? warp < 12 && (warp & 3) != 2 : warp < 9;
        const int fj = RMAP ? (gate ? 3 * (warp >> 2) + min(warp & 3, 2) : (warp < 12 ? warp >> 2 : warp - 9)) : (gate ? warp : warp - 9);
        if (gate) {
            uint32_t W[18][4];
            mbar_wait(bar_w);
            const uint32_t aad = sb + SM_WG + (mi & 1) * SM_WU + (rr + 8 * (mi >> 1)) * W_PITCH + fj * 16;
#pragma unroll
            for (int k = 0; k < 18; k++) ldsm_x4_t(W[k][0], W[k][1], W[k][2], W[k][3], aad + k * 16 * W_PITCH);
            const uint32_t bad = pin(sb + SM_XS + rr * XS_PITCH + mi * 16);
            fence_async();
            STAMP2(17);
            if (bar_or(11, NWRK, false)) {
                late_rows(IC<0>());
#pragma unroll
                for (int k = 0; k < 18; k++) ldsm_x4_t(W[k][0], W[k][1], W[k][2], W[k][3], aad + k * 16 * W_PITCH);
            }
            STAMP2(19);
            float c4[2][4] = {};
#pragma unroll
            for (int k = 0; k < 18; k += 2) {
                uint32_t b0, b1, b2, b3;
                ldsm_x4(b0, b1, b2, b3, bad + k * 32);
                mma_bf16(c4[0], W[k][0], W[k][1], W[k][2], W[k][3], b0, b1);
                mma_bf16(c4[1], W[k + 1][0], W[k + 1][1], W[k + 1][2], W[k + 1][3], b2, b3);
            }
            const uint32_t ex = sb + SM_EX + (32 * fj + lane) * 16;
            const float e0 = c4[0][0] + c4[1][0], e1 = c4[0][1] + c4[1][1], e2 = c4[0][2] + c4[1][2], e3 = c4[0][3] + c4[1][3];
            asm volatile("st.async.shared::cluster.mbarrier::complete_tx::bytes.v4.f32 [%0], {%1,%2,%3,%4}, [%5];\n"
                         ::"r"(ex ^ 0x1000000u), "f"(e0), "f"(e1), "f"(e2), "f"(e3), "r"(bar_g ^ 0x1000000u) : "memory");
            STAMP2(20);
            mbar_wait(bar_g);
            const uint4 o = lds128(ex);
            const uint32_t G = pack_bf16(e0 + __uint_as_float(o.x), e1 + __uint_as_float(o.y)), U = pack_bf16(e2 + __uint_as_float(o.z), e3 + __uint_as_float(o.w));
            sts32(sb + SM_GU + (32 * fj + lane) * 4, hmul2_bf(pack_bf16(bf_lo(G) * sigmoid_f(bf_lo(G)), bf_hi(G) * sigmoid_f(bf_hi(G))), U));
            bar_arrive(13, NWRK);
        } else {
            uint32_t W[2][18];
            auto load_wd = [&]() {
                mbar_wait(bar_d);
                const uint32_t base = sb + SM_WD + (4 * fj + (mi & 1)) * 16 + rr * WD_PITCH;
#pragma unroll
                for (int j = 0; j < 2; j++) {
#pragma unroll
                    for (int k = 0; k < 4; k++) ldsm_x4_t(W[j][4 * k], W[j][4 * k + 1], W[j][4 * k + 2], W[j][4 * k + 3], base + j * 32 + (k * 16 + 8 * (mi >> 1)) * WD_PITCH);
                    ldsm_x2_t(W[j][16], W[j][17], base + j * 32 + 64 * WD_PITCH);
                }
            };
            const uint32_t po = pin((((8 * (18 * odd + 2 * fj) + g) * 64 + P) * 16 + t * 4) * 4);
            fence_async();
            STAMP2(17);
            if (bar_or(11, NWRK, false)) late_rows(IC<0>());
            delay(DDLY); load_wd();
            bar_sync(13, NWRK);
            STAMP2(21);
            uint32_t gb[9];
            ldsm_x4_t(gb[0], gb[1], gb[2], gb[3], sb + SM_GU + lane * 16);
            ldsm_x4_t(gb[4], gb[5], gb[6], gb[7], sb + SM_GU + 512 + lane * 16);
            ldsm_x1_t(gb[8], sb + SM_GU + 1024 + lane * 16);
            float c4[2][4] = {}, d4[2][4] = {};
#pragma unroll
            for (int k = 0; k < 4; k += 2)
#pragma unroll
                for (int j = 0; j < 2; j++) {
                    mma_bf16(c4[j], W[j][4 * k], W[j][4 * k + 1], W[j][4 * k + 2], W[j][4 * k + 3], gb[2 * k], gb[2 * k + 1]);
                    mma_bf16(d4[j], W[j][4 * k + 4], W[j][4 * k + 5], W[j][4 * k + 6], W[j][4 * k + 7], gb[2 * k + 2], gb[2 * k + 3]);
                }
#pragma unroll
            for (int j = 0; j < 2; j++) mma_bf16_k8(c4[j], W[j][16], W[j][17], gb[8]);
#pragma unroll
            for (int j = 0; j < 2; j++)
                stg128(reinterpret_cast<unsigned char*>(p.s->part) + po + j * 32768, __float_as_uint(c4[j][0] + d4[j][0]) | 1u, __float_as_uint(c4[j][1] + d4[j][1]) | 1u,
                       __float_as_uint(c4[j][2] + d4[j][2]) | 1u, __float_as_uint(c4[j][3] + d4[j][3]) | 1u);
        }
        STAMP2(22);
    } else if (warp == 18) {
        const uint4* const ksrc = reinterpret_cast<const uint4*>(p.s->key3) + pin((b % KR) * 2 * NCTA + 2 * lane);
        const unsigned char* const rl = reinterpret_cast<const unsigned char*>(rsrc) + pin(lane * 16);
        const uint32_t sa = pin(sb + SM_LNP + lane * 80);
        const uint32_t klo = pin((uint32_t)(127 - b) << 9 | (uint32_t)(15 - ROWTOK(lane & 15)) << 1 | par), ra = pin(sb + SM_LNP + (32 + (lane & 15)) * 80);
        uint4* const kdst = reinterpret_cast<uint4*>(p.s->key3) + pin((lane >> 1) * 2 * NCTA + 2 * b + (lane & 1));
        FIX(ra);
        bar_sync(6, NWRK);
        {
            float mb, rc;
            ln_finish(sum18(sa), lane, mb, rc);
            if (lane < 16) stat_store(s_stat + lane * 8, mb, rc, 0u);
        }
        bar_arrive(7, 608);
        bar_sync(8, 608);
        uint32_t t0;
        {
            const uint32_t bits = __float_as_uint(rbf(sum18(ra)));
            const uint32_t me = ((bits ^ ((uint32_t)((int)bits >> 31) | 0x80000000u)) & 0xffff0000u) | klo;
            const uint32_t k0 = __reduce_max_sync(0xffffffffu, me), k1 = __reduce_max_sync(0xffffffffu, me == k0 ? 0u : me);
            const uint32_t k2 = __reduce_max_sync(0xffffffffu, me >= k1 ? 0u : me);
            if (lane < 2 * KR) stg128(kdst, k0 ^ 0x11eu, k1 ^ 0xfeu, k2 ^ 0xdeu, par);
            asm volatile("mov.u32 %0, %%clock;" : "=r"(t0) :: "memory");
            STAMPW(23);
            if (lane == 0) sts64(s_rank, ~k0, ~k1);
            bar_arrive(9, 608);
            sts32(s_k16 + (lane & 15) * 4, me);
            __syncwarp();
            const uint4 v = lds128(s_k16 + (lane & 16) * 2), w = lds128(s_k16 + (lane & 16) * 2 + 16);
            int rank = ((v.x > me) + (v.y > me)) + ((v.z > me) + (v.w > me)) + (((w.x > me) + (w.y > me)) + ((w.z > me) + (w.w > me)));
            rank += __shfl_xor_sync(0xffffffffu, rank, 16);
            if (lane < 16 && rank < 8) p.s->key[8 * b + rank] = (me ^ 0x1eu) | ((8 - rank) << 5);
        }
        uint4 kq[4];
        uint32_t u[4], mine = 0, m;
        int it = 0;
        { uint32_t now; do { asm volatile("mov.u32 %0, %%clock;" : "=r"(now) :: "memory"); } while (now - t0 < KDLY); }
        STAMPW(9);
        do {
#pragma unroll
            for (int i = 0; i < 4; i++) kq[i] = ld_poll(ksrc + 64 * i);
            if (++it > SPIN_LIMIT) TRAP();
            uint32_t S[2][4];
#pragma unroll
            for (int i = 0; i < 2; i++) {
                const uint4 &c = kq[2 * i], &d = kq[2 * i + 1];
                const uint32_t m1 = min(c.x, d.x), m2 = max(c.y, d.y);
                S[i][0] = max(c.x, d.x); S[i][1] = max(m1, m2); S[i][2] = min(m1, m2); S[i][3] = min(c.y, d.y);
            }
            const uint32_t a0 = max(S[0][0], S[1][3]), a1 = max(S[0][1], S[1][2]), a2 = max(S[0][2], S[1][1]), a3 = max(S[0][3], S[1][0]);
            const uint32_t b0 = max(a0, a2), b2 = min(a0, a2), b1 = max(a1, a3), b3 = min(a1, a3);
            u[0] = max(b0, b1); u[1] = min(b0, b1); u[2] = max(b2, b3); u[3] = min(b2, b3);
        } while (__any_sync(0xffffffffu, and3(or3(or3(xor_or(kq[0].x, kq[0].y, par), xor_or(kq[0].z, kq[1].x, par), xor_or(kq[1].y, kq[1].z, par)),
                                                  xor_or(kq[2].x, kq[2].y, par), xor_or(kq[2].z, kq[3].x, par)) | xor_or(kq[3].y, kq[3].z, par), 1u, 1u)));
        STAMPW(16);
        CNT(28, it);
        uint4 v[9];
#pragma unroll
        for (int r = 0; r < 8; r++) {
            m = __reduce_max_sync(0xffffffffu, u[0]);
            if (u[0] == m) { u[0] = u[1]; u[1] = u[2]; u[2] = u[3]; u[3] = 0; }
            if (g == r) mine = m;
            v[r] = ld_poll(rl + (size_t)((m >> 8) & 0xffu) * 2304u);
        }
        v[8] = ld_poll(reinterpret_cast<const unsigned char*>(rsrc) + (((mine >> 8) & 0xffu) * 2304u + (32 + t) * 16));
        bool again = __any_sync(0xffffffffu, u[0] == 0 || max(max(kq[0].z, kq[1].z), max(kq[2].z, kq[3].z)) > m);
        if (again) {
#pragma unroll 1
            for (int i = 0; i < 8; i++) {
                uint4 k;
                do { k = ld_poll(reinterpret_cast<const uint4*>(p.s->key) + 32 * i + lane); if (++it > SPIN_LIMIT) TRAP(); } while (((k.x ^ par) | (k.y ^ par) | (k.z ^ par) | (k.w ^ par)) & 1u);
                sts128(sb + SM_KEYS + (32 * i + lane) * 16, k.x, k.y, k.z, k.w);
            }
            m = 0xffffffffu;
#pragma unroll 1
            for (int r = 0; r < 8; r++) {
                uint32_t c = 0;
#pragma unroll 2
                for (int i = 0; i < 8; i++) {
                    const uint4 k = lds128(sb + SM_KEYS + (32 * i + lane) * 16);
                    c = max(max(c, k.x < m ? k.x : 0u), max(k.y < m ? k.y : 0u, max(k.z < m ? k.z : 0u, k.w < m ? k.w : 0u)));
                }
                m = __reduce_max_sync(0xffffffffu, c);
                if (g == r) mine = m;
            }
        }
        if (t == 0) sts32(s_key + g * 4, mine);
        uint32_t mn = 1;
#pragma unroll
        for (int r = 0; r < 9; r++) {
            sts128(sb + SM_XS + (r < 8 ? r * XS_PITCH + lane * 16 : g * XS_PITCH + (32 + t) * 16), v[r].x, v[r].y, v[r].z, v[r].w);
            mn = min(mn, min4(v[r]));
        }
        if ((again || __any_sync(0xffffffffu, mn == 0)) && !__any_sync(0xffffffffu, KLATE(mine))) gather(mine);
        STAMPW(18);
        if (bar_or(11, NWRK, KLATE(mine))) late_rows(IC<1>());
    } else {
        bar_sync(6, NWRK);
        WPOINT(16, true);
        if (WANY(17) || WANY(18)) delay(WDLY);
        WPOINT(17, true);
        if (WANY(18)) delay(WDLY);
        WPOINT(18, true);
        if (bar_or(11, NWRK, false)) late_rows(IC<2>());
        const int tk = KTOK(lds32(s_key + (lane & 7) * 4));
        const uint32_t sel = __reduce_or_sync(0xffffffffu, (tk >> 4) == b ? 1u << (tk & 15) : 0u);
        if (ODLY) delay(ODLY);
        if (!(EXP & 1)) if (sel ? lane < 16 && !((sel >> lane) & 1u) : lane == 0) bulk_s2g(p.out + (size_t)(16 * b + lane) * DM, sb + SM_OUT + lane * (DM * 2), sel ? DM * 2 : 16 * DM * 2);
        __syncwarp();
    }
    if (warp == 8 || warp >= 18) {
        const int grp = 3 * b + (warp == 8 ? 0 : warp - 17), fsl = 2 * t + ((lane >> 3) & 1), fc = 16 * (grp >> 3) + (grp & 7) + 8 * (lane >> 4);
        const uint32_t fk = lds32(s_key + fsl * 4);
        float hv = 0.f, u2 = 0.f;
        int it = 0;
        if (b < 96) {
            const uint32_t* const fsrc = p.s->rows + KSLOT(fk, fsl) * DM + (fc >> 1);
            uint32_t hw, uw;
            do { hw = ld_poll32(fsrc + 288); uw = ld_poll32(fsrc); if (++it > SPIN_LIMIT) TRAP(); } while (!hw || !uw);
            hv = (fc & 1) ? bf_hi(hw) : bf_lo(hw); u2 = (fc & 1) ? bf_hi(uw) : bf_lo(uw);
        }
        const float rs = rbf(sigmoid_f(__uint_as_float((fk ^ ((uint32_t)((int)~fk >> 31) | 0x80000000u)) & 0xffff0000u)));
        const uint32_t dof = pin(KTOK(fk) * DM + fc), so = pin(grp * 256 + lane);
        if (warp > 17) bar_sync(13, NWRK);
        if (b < 96) {
            delay(warp > 17 ? FDLY : FDLY2);
            const uint4* src = reinterpret_cast<const uint4*>(p.s->part) + so;
            float s0, s1, s2, s3;
            uint32_t ok;
            do {
                uint4 a[8];
#pragma unroll
                for (int i = 0; i < 8; i++) a[i] = ld_poll(src + 32 * i);
                if (++it > SPIN_LIMIT) TRAP();
#define A4(i) and3(and3(a[i].x, a[i].y, a[i].z), and3(a[i].w, a[i + 1].x, a[i + 1].y), a[i + 1].z & a[i + 1].w)
#define S8(f) (((__uint_as_float(a[0].f) + __uint_as_float(a[1].f)) + (__uint_as_float(a[2].f) + __uint_as_float(a[3].f))) + \
               ((__uint_as_float(a[4].f) + __uint_as_float(a[5].f)) + (__uint_as_float(a[6].f) + __uint_as_float(a[7].f))))
                ok = and3(A4(0), A4(2), and3(A4(4), A4(6), 1u));
                s0 = S8(x); s1 = S8(y); s2 = S8(z); s3 = S8(w);
                asm volatile("" : "+f"(s0), "+f"(s1), "+f"(s2), "+f"(s3));
#undef A4
#undef S8
            } while (__any_sync(0xffffffffu, !ok));
            STAMP2(24);
            if (warp == 19) { CNT(29, it); }
            const bool up = lane & 16, od = lane & 8;
            const float r0 = (up ? s2 : s0) + __shfl_xor_sync(0xffffffffu, up ? s0 : s2, 16), r1 = (up ? s3 : s1) + __shfl_xor_sync(0xffffffffu, up ? s1 : s3, 16);
            float y = (od ? r1 : r0) + __shfl_xor_sync(0xffffffffu, od ? r0 : r1, 8);
            y += __shfl_xor_sync(0xffffffffu, y, 4);
            p.out[dof] = __float2bfloat16_rn(hv + rbf(u2 + rbf(rbf(y) * rs)));
        }
    }
    if (warp == 19) asm volatile("cp.async.bulk.wait_group.read 0;\n" ::: "memory");
    if (b == 0 && tid < 8) *reinterpret_cast<volatile unsigned*>(p.s->hint + tid * 32 + 1) = lds32(s_cnt + 4) + 1u;
    STAMP(25);
    }
}

typedef CUresult (*PFN_tmEncode)(CUtensorMap*, CUtensorMapDataType, cuuint32_t, void*, const cuuint64_t*, const cuuint64_t*, const cuuint32_t*,
                                 const cuuint32_t*, CUtensorMapInterleave, CUtensorMapSwizzle, CUtensorMapL2promotion, CUtensorMapFloatOOBfill);

extern "C" void kernel_launch(void* const* d_in, const int* in_sizes, int n_in, void* d_out, int out_size) {
    Params p;
    p.x = (const bf16*)d_in[0];
    p.lar = (const bf16*)d_in[1];
    p.aim = (const bf16*)d_in[2];
    p.cre = (const bf16*)d_in[3];
    p.cim = (const bf16*)d_in[4];
    p.ldt = (const bf16*)d_in[5];
    p.dsk = (const bf16*)d_in[6];
    p.wr = (const bf16*)d_in[8];
    p.wg = (const bf16*)d_in[9];
    p.wu = (const bf16*)d_in[10];
    p.wd = (const bf16*)d_in[11];
    p.out = (bf16*)d_out;
    static PFN_tmEncode enc = nullptr;
    static void* scratch = nullptr;
    if (!enc) {
        cudaFuncSetAttribute(fused_kernel, cudaFuncAttributeMaxDynamicSharedMemorySize, SMEM_TOTAL);
        void* fn = nullptr;
        cudaDriverEntryPointQueryResult qr;
        cudaGetDriverEntryPoint("cuTensorMapEncodeTiled", &fn, cudaEnableDefault, &qr);
        enc = (PFN_tmEncode)fn;
        cudaGetSymbolAddress(&scratch, g_scratch);
    }
    p.s = (Scratch*)scratch;
    CUtensorMap tm_g, tm_u, tm_d, tm_x;
    const cuuint64_t dims[2] = {FF, DM}, strides[1] = {FF * 2};
    const cuuint32_t box[2] = {72, 48}, es[2] = {1, 1};
    enc(&tm_g, CU_TENSOR_MAP_DATA_TYPE_BFLOAT16, 2, d_in[9], dims, strides, box, es, CU_TENSOR_MAP_INTERLEAVE_NONE, CU_TENSOR_MAP_SWIZZLE_NONE,
        CU_TENSOR_MAP_L2_PROMOTION_NONE, CU_TENSOR_MAP_FLOAT_OOB_FILL_NONE);
    enc(&tm_u, CU_TENSOR_MAP_DATA_TYPE_BFLOAT16, 2, d_in[10], dims, strides, box, es, CU_TENSOR_MAP_INTERLEAVE_NONE, CU_TENSOR_MAP_SWIZZLE_NONE,
        CU_TENSOR_MAP_L2_PROMOTION_NONE, CU_TENSOR_MAP_FLOAT_OOB_FILL_NONE);
    const cuuint64_t ddims[2] = {DM / 2, FF}, dstrides[1] = {DM * 2};
    const cuuint32_t dbox[2] = {WD_PITCH / 4, 8};
    enc(&tm_d, CU_TENSOR_MAP_DATA_TYPE_UINT32, 2, d_in[11], ddims, dstrides, dbox, es, CU_TENSOR_MAP_INTERLEAVE_NONE, CU_TENSOR_MAP_SWIZZLE_NONE,
        CU_TENSOR_MAP_L2_PROMOTION_NONE, CU_TENSOR_MAP_FLOAT_OOB_FILL_NONE);
    const cuuint64_t xdims[4] = {DM, 128, 4, 4}, xstrides[3] = {DM * 8, DM * 2, DM * 1024};
    const cuuint32_t xbox[4] = {8, 128, 4, 2}, xes[4] = {1, 1, 1, 1};
    enc(&tm_x, CU_TENSOR_MAP_DATA_TYPE_BFLOAT16, 4, d_in[0], xdims, xstrides, xbox, xes, CU_TENSOR_MAP_INTERLEAVE_NONE, CU_TENSOR_MAP_SWIZZLE_NONE,
        CU_TENSOR_MAP_L2_PROMOTION_NONE, CU_TENSOR_MAP_FLOAT_OOB_FILL_NONE);
    fused_kernel<<<NCTA, NTHR, SMEM_TOTAL>>>(p, tm_g, tm_u, tm_d, tm_x);
}
```

```cpp
#include <cuda_runtime.h>
#include <cuda.h>
#include <cuda_fp16.h>
#include <cuda_bf16.h>
#include <stdint.h>

#define LSEQ 2048
#define DM 576
#define NST 128
#define FF 4608
#define NSEL 8
#define NCTA 128
#define NTHR 640
#define NWRK 640

typedef __nv_bfloat16 bf16;

#define SM_WG 0
#define SM_WU 41472
#define SM_XC (82944 - 32768)
#define SM_WD 82944
#define W_PITCH 144
#define WD_PITCH 592
#define SM_Z2 (SM_WD + 10240)
#define SM_XT (SM_PL - 18 * 1152)
#define SM_PL (SM_WD + 46080)
#define PL_HALF 1344
#define PLW_B 2624
#define PL_B (4 * PLW_B)
#define SM_U (SM_PL + 5 * PL_B)
#define UPAD 20
#define ULO_B ((UPAD + 128) * 16)
#define USLOT_B (2 * ULO_B)
#define SM_KW (SM_U + 5 * USLOT_B)
#define KW_B 3712
#define KW_PL 1216
#define KW_P 2400
#define KW_H 3440
#define SM_MISC (SM_KW + 5 * KW_B)
#define SM_LC (SM_MISC + 384)
#define SM_LNP (SM_LC + 768)
#define SM_RX (SM_LNP + 3840)
#define SMEM_TOTAL (SM_RX + 3088)
#define TBW PLW_B
#define SM_OUT SM_PL
#define SM_XS (SM_PL + 18432)
#define XS_PITCH 592
#define SM_GU (SM_PL + 23296)
#define SM_EX (SM_PL + 24576)
#define SM_KEYS SM_KW

struct __align__(128) Scratch {
    unsigned hint[8 * 32];
    unsigned flag[32];
    uint32_t key3[NCTA * 8];
    uint32_t key[NCTA * 8];
    uint32_t stat[LSEQ];
    uint32_t uT[64 * (LSEQ / 2)];
    uint32_t y[(NCTA + 96) * DM * 8];
    uint32_t part[288 * 64 * 16];
    uint32_t rows[(2 * NCTA + NSEL) * DM];
};
__device__ Scratch g_scratch;
#define STAMP(i)
#define STAMPX(i)
#define STAMPY(i)

__device__ __forceinline__ float rbf(float x) {
    uint32_t r;
    asm("cvt.rn.bf16x2.f32 %0, %1, %2;\n" : "=r"(r) : "f"(x), "f"(0.f));
    return __uint_as_float(r);
}
__device__ __forceinline__ uint32_t pack_bf16(float lo, float hi) {
    uint32_t r;
    asm("cvt.rn.bf16x2.f32 %0, %1, %2;\n" : "=r"(r) : "f"(hi), "f"(lo));
    return r;
}
__device__ __forceinline__ uint32_t pack_f16(float lo, float hi) {
    uint32_t r;
    asm("cvt.rn.f16x2.f32 %0, %1, %2;\n" : "=r"(r) : "f"(hi), "f"(lo));
    return r;
}
__device__ __forceinline__ uint32_t pack_f16_rz(float lo, float hi) {
    uint32_t r;
    asm("cvt.rz.f16x2.f32 %0, %1, %2;\n" : "=r"(r) : "f"(hi), "f"(lo));
    return r;
}
__device__ __forceinline__ float bf_lo(uint32_t w) { return __uint_as_float(w << 16); }
__device__ __forceinline__ float bf_hi(uint32_t w) { return __uint_as_float(w & 0xffff0000u); }
__device__ __forceinline__ uint32_t hadd2_bf(uint32_t a, uint32_t b) {
    __nv_bfloat162 r = __hadd2_rn(*reinterpret_cast<__nv_bfloat162*>(&a), *reinterpret_cast<__nv_bfloat162*>(&b));
    return *reinterpret_cast<uint32_t*>(&r);
}
__device__ __forceinline__ uint32_t hsub2_bf(uint32_t a, uint32_t b) {
    __nv_bfloat162 r = __hsub2_rn(*reinterpret_cast<__nv_bfloat162*>(&a), *reinterpret_cast<__nv_bfloat162*>(&b));
    return *reinterpret_cast<uint32_t*>(&r);
}
__device__ __forceinline__ uint32_t hmul2_bf(uint32_t a, uint32_t b) {
    __nv_bfloat162 r = __hmul2_rn(*reinterpret_cast<__nv_bfloat162*>(&a), *reinterpret_cast<__nv_bfloat162*>(&b));
    return *reinterpret_cast<uint32_t*>(&r);
}
__device__ __forceinline__ uint32_t hfma2_bf(uint32_t a, uint32_t b, uint32_t c) { uint32_t r; asm("fma.rn.bf16x2 %0, %1, %2, %3;\n" : "=r"(r) : "r"(a), "r"(b), "r"(c)); return r; }
__device__ __forceinline__ uint32_t hmul2(uint32_t a, uint32_t b) { uint32_t r; asm("mul.rn.f16x2 %0, %1, %2;\n" : "=r"(r) : "r"(a), "r"(b)); return r; }
__device__ __forceinline__ uint32_t hadd2(uint32_t a, uint32_t b) { uint32_t r; asm("add.rn.f16x2 %0, %1, %2;\n" : "=r"(r) : "r"(a), "r"(b)); return r; }
__device__ __forceinline__ uint32_t hfma2(uint32_t a, uint32_t b, uint32_t c) { uint32_t r; asm("fma.rn.f16x2 %0, %1, %2, %3;\n" : "=r"(r) : "r"(a), "r"(b), "r"(c)); return r; }
__device__ __forceinline__ uint32_t hfms2(uint32_t a, uint32_t b, uint32_t c) {
    uint32_t r;
    asm("{\n.reg .b32 n;\nneg.f16x2 n, %2;\nfma.rn.f16x2 %0, %1, n, %3;\n}\n" : "=r"(r) : "r"(a), "r"(b), "r"(c));
    return r;
}
__device__ __forceinline__ uint32_t nzw(uint32_t w) { return max(w, 1u); }
__device__ __forceinline__ uint32_t nzf(float f) { const uint32_t w = __float_as_uint(f); return w ? w : 0x80000000u; }
__device__ __forceinline__ uint32_t smem_u32(const void* p) { return (uint32_t)__cvta_generic_to_shared(p); }
__device__ __forceinline__ uint32_t lds32(uint32_t addr) {
    uint32_t v;
    asm volatile("ld.shared.u32 %0, [%1];\n" : "=r"(v) : "r"(addr) : "memory");
    return v;
}
__device__ __forceinline__ uint32_t lds16(uint32_t addr) {
    unsigned short v;
    asm volatile("ld.shared.u16 %0, [%1];\n" : "=h"(v) : "r"(addr) : "memory");
    return v;
}
__device__ __forceinline__ uint2 lds64(uint32_t addr) {
    uint2 v;
    asm volatile("ld.shared.v2.u32 {%0,%1}, [%2];\n" : "=r"(v.x), "=r"(v.y) : "r"(addr) : "memory");
    return v;
}
__device__ __forceinline__ uint4 lds128(uint32_t addr) {
    uint4 v;
    asm volatile("ld.shared.v4.u32 {%0,%1,%2,%3}, [%4];\n" : "=r"(v.x), "=r"(v.y), "=r"(v.z), "=r"(v.w) : "r"(addr) : "memory");
    return v;
}
__device__ __forceinline__ float ldsf(uint32_t addr) { return __uint_as_float(lds32(addr)); }
__device__ __forceinline__ void sts32(uint32_t addr, uint32_t v) { asm volatile("st.shared.u32 [%0], %1;\n" ::"r"(addr), "r"(v) : "memory"); }
__device__ __forceinline__ void sts16(uint32_t addr, uint32_t v) { asm volatile("st.shared.u16 [%0], %1;\n" ::"r"(addr), "h"((unsigned short)v) : "memory"); }
__device__ __forceinline__ void stsf(uint32_t addr, float v) { sts32(addr, __float_as_uint(v)); }
__device__ __forceinline__ void sts64(uint32_t addr, uint32_t a, uint32_t b) { asm volatile("st.shared.v2.u32 [%0], {%1,%2};\n" ::"r"(addr), "r"(a), "r"(b) : "memory"); }
__device__ __forceinline__ void sts64f(uint32_t addr, float a, float b) { sts64(addr, __float_as_uint(a), __float_as_uint(b)); }
__device__ __forceinline__ void sts128(uint32_t addr, uint32_t a, uint32_t b, uint32_t c, uint32_t d) {
    asm volatile("st.shared.v4.u32 [%0], {%1,%2,%3,%4};\n" ::"r"(addr), "r"(a), "r"(b), "r"(c), "r"(d) : "memory");
}
__device__ __forceinline__ void sts128f(uint32_t addr, const float (&v)[4]) {
    sts128(addr, __float_as_uint(v[0]), __float_as_uint(v[1]), __float_as_uint(v[2]), __float_as_uint(v[3]));
}
__device__ __forceinline__ void ldsm_x4(uint32_t& r0, uint32_t& r1, uint32_t& r2, uint32_t& r3, uint32_t addr) {
    asm volatile("ldmatrix.sync.aligned.m8n8.x4.shared.b16 {%0,%1,%2,%3}, [%4];\n"
                 : "=r"(r0), "=r"(r1), "=r"(r2), "=r"(r3) : "r"(addr) : "memory");
}
__device__ __forceinline__ void ldsm_x4_t(uint32_t& r0, uint32_t& r1, uint32_t& r2, uint32_t& r3, uint32_t addr) {
    asm volatile("ldmatrix.sync.aligned.m8n8.x4.trans.shared.b16 {%0,%1,%2,%3}, [%4];\n"
                 : "=r"(r0), "=r"(r1), "=r"(r2), "=r"(r3) : "r"(addr) : "memory");
}
__device__ __forceinline__ void ldsm_x2_t(uint32_t& r0, uint32_t& r1, uint32_t addr) {
    asm volatile("ldmatrix.sync.aligned.m8n8.x2.trans.shared.b16 {%0,%1}, [%2];\n" : "=r"(r0), "=r"(r1) : "r"(addr) : "memory");
}
__device__ __forceinline__ void ldsm_x1_t(uint32_t& r0, uint32_t addr) {
    asm volatile("ldmatrix.sync.aligned.m8n8.x1.trans.shared.b16 {%0}, [%1];\n" : "=r"(r0) : "r"(addr) : "memory");
}
__device__ __forceinline__ void stsm_x4(uint32_t addr, uint32_t r0, uint32_t r1, uint32_t r2, uint32_t r3) {
    asm volatile("stmatrix.sync.aligned.m8n8.x4.shared.b16 [%0], {%1,%2,%3,%4};\n" ::"r"(addr), "r"(r0), "r"(r1), "r"(r2), "r"(r3) : "memory");
}
__device__ __forceinline__ void stsm_x4_t(uint32_t addr, uint32_t r0, uint32_t r1, uint32_t r2, uint32_t r3) {
    asm volatile("stmatrix.sync.aligned.m8n8.x4.trans.shared.b16 [%0], {%1,%2,%3,%4};\n" ::"r"(addr), "r"(r0), "r"(r1), "r"(r2), "r"(r3) : "memory");
}
__device__ __forceinline__ uint32_t movm(uint32_t a) {
    uint32_t d;
    asm volatile("movmatrix.sync.aligned.m8n8.trans.b16 %0, %1;\n" : "=r"(d) : "r"(a));
    return d;
}
__device__ __forceinline__ void mma_f16(float (&c)[4], uint32_t a0, uint32_t a1, uint32_t a2, uint32_t a3, uint32_t b0, uint32_t b1) {
    asm volatile(
        "mma.sync.aligned.m16n8k16.row.col.f32.f16.f16.f32 {%0,%1,%2,%3}, {%4,%5,%6,%7}, {%8,%9}, {%0,%1,%2,%3};\n"
        : "+f"(c[0]), "+f"(c[1]), "+f"(c[2]), "+f"(c[3])
        : "r"(a0), "r"(a1), "r"(a2), "r"(a3), "r"(b0), "r"(b1));
}
__device__ __forceinline__ void mma_bf16(float (&c)[4], uint32_t a0, uint32_t a1, uint32_t a2, uint32_t a3, uint32_t b0, uint32_t b1) {
    asm volatile(
        "mma.sync.aligned.m16n8k16.row.col.f32.bf16.bf16.f32 {%0,%1,%2,%3}, {%4,%5,%6,%7}, {%8,%9}, {%0,%1,%2,%3};\n"
        : "+f"(c[0]), "+f"(c[1]), "+f"(c[2]), "+f"(c[3])
        : "r"(a0), "r"(a1), "r"(a2), "r"(a3), "r"(b0), "r"(b1));
}
__device__ __forceinline__ void mma_bf16_k8(float (&c)[4], uint32_t a0, uint32_t a1, uint32_t b0) {
    asm volatile("mma.sync.aligned.m16n8k8.row.col.f32.bf16.bf16.f32 {%0,%1,%2,%3}, {%4,%5}, {%6}, {%0,%1,%2,%3};\n"
                 : "+f"(c[0]), "+f"(c[1]), "+f"(c[2]), "+f"(c[3]) : "r"(a0), "r"(a1), "r"(b0));
}
__device__ __forceinline__ void bar_sync(int id, int n) { asm volatile("bar.sync %0, %1;\n" ::"r"(id), "r"(n) : "memory"); }
__device__ __forceinline__ void bar_arrive(int id, int n) { asm volatile("bar.arrive %0, %1;\n" ::"r"(id), "r"(n) : "memory"); }
__device__ __forceinline__ bool bar_or(int id, int n, bool v) {
    uint32_t r;
    asm volatile("{\n.reg .pred p, q;\nsetp.ne.u32 p, %3, 0;\nbar.red.or.pred q, %1, %2, p;\nselp.u32 %0, 1, 0, q;\n}\n" : "=r"(r) : "r"(id), "r"(n), "r"((uint32_t)v) : "memory");
    return r;
}
__device__ __forceinline__ uint32_t and3(uint32_t a, uint32_t b, uint32_t c) { uint32_t r; asm("lop3.b32 %0, %1, %2, %3, 0x80;\n" : "=r"(r) : "r"(a), "r"(b), "r"(c)); return r; }
__device__ __forceinline__ uint32_t or3(uint32_t a, uint32_t b, uint32_t c) { uint32_t r; asm("lop3.b32 %0, %1, %2, %3, 0xfe;\n" : "=r"(r) : "r"(a), "r"(b), "r"(c)); return r; }
__device__ __forceinline__ uint32_t xor_or(uint32_t a, uint32_t b, uint32_t c) { uint32_t r; asm("lop3.b32 %0, %1, %2, %3, 0x7e;\n" : "=r"(r) : "r"(a), "r"(b), "r"(c)); return r; }
__device__ __forceinline__ uint32_t pin(uint32_t v) { uint32_t r; asm volatile("shfl.sync.bfly.b32 %0, %1, 0, 0x1f, 0xffffffff;\n" : "=r"(r) : "r"(v) : "memory"); return r; }
__device__ __forceinline__ uint4 ld_poll(const void* p) {
    uint4 v;
    asm volatile("ld.relaxed.gpu.global.v4.u32 {%0,%1,%2,%3}, [%4];\n" : "=r"(v.x), "=r"(v.y), "=r"(v.z), "=r"(v.w) : "l"(p) : "memory");
    return v;
}
__device__ __forceinline__ uint2 ld_poll64(const void* p) {
    uint2 v;
    asm volatile("ld.relaxed.gpu.global.v2.u32 {%0,%1}, [%2];\n" : "=r"(v.x), "=r"(v.y) : "l"(p) : "memory");
    return v;
}
__device__ __forceinline__ uint32_t ld_poll32(const void* p) {
    uint32_t v;
    asm volatile("ld.relaxed.gpu.global.u32 %0, [%1];\n" : "=r"(v) : "l"(p) : "memory");
    return v;
}
__device__ __forceinline__ uint32_t ld_acquire32(const void* p) {
    uint32_t v;
    asm volatile("ld.acquire.gpu.global.u32 %0, [%1];\n" : "=r"(v) : "l"(p) : "memory");
    return v;
}
__device__ __forceinline__ uint4 ldg128(const void* p) {
    uint4 v;
    asm volatile("ld.global.nc.v4.u32 {%0,%1,%2,%3}, [%4];\n" : "=r"(v.x), "=r"(v.y), "=r"(v.z), "=r"(v.w) : "l"(p));
    return v;
}
__device__ __forceinline__ uint2 ldg64(const void* p) {
    uint2 v;
    asm volatile("ld.global.nc.v2.u32 {%0,%1}, [%2];\n" : "=r"(v.x), "=r"(v.y) : "l"(p));
    return v;
}
__device__ __forceinline__ uint32_t ldg16(const void* p) {
    uint32_t v;
    asm volatile("ld.global.nc.u16 %0, [%1];\n" : "=r"(v) : "l"(p));
    return v;
}
__device__ __forceinline__ uint4 ldo128(const void* p) {
    uint4 v;
    asm volatile("ld.relaxed.cta.global.v4.u32 {%0,%1,%2,%3}, [%4];\n" : "=r"(v.x), "=r"(v.y), "=r"(v.z), "=r"(v.w) : "l"(p) : "memory");
    return v;
}
__device__ __forceinline__ uint2 ldo64(const void* p) {
    uint2 v;
    asm volatile("ld.relaxed.cta.global.v2.u32 {%0,%1}, [%2];\n" : "=r"(v.x), "=r"(v.y) : "l"(p) : "memory");
    return v;
}
__device__ __forceinline__ uint32_t ldo16(const void* p) {
    uint32_t v;
    asm volatile("ld.relaxed.cta.global.u16 %0, [%1];\n" : "=r"(v) : "l"(p) : "memory");
    return v;
}
__device__ __forceinline__ void stg128(void* p, uint32_t a, uint32_t b, uint32_t c, uint32_t d) {
    asm volatile("st.global.v4.u32 [%0], {%1,%2,%3,%4};\n" ::"l"(p), "r"(a), "r"(b), "r"(c), "r"(d) : "memory");
}
__device__ __forceinline__ void stg64(void* p, uint32_t a, uint32_t b) { asm volatile("st.global.v2.u32 [%0], {%1,%2};\n" ::"l"(p), "r"(a), "r"(b) : "memory"); }
__device__ __forceinline__ uint32_t min4(const uint4& v) { return min(min(v.x, v.y), min(v.z, v.w)); }
#define SPIN_LIMIT (1 << 21)
#define TRAP() __trap()
__device__ __forceinline__ void mbar_init(uint32_t bar, uint32_t cnt) { asm volatile("mbarrier.init.shared::cta.b64 [%0], %1;\n" ::"r"(bar), "r"(cnt) : "memory"); }
__device__ __forceinline__ void mbar_expect(uint32_t bar, uint32_t bytes) {
    asm volatile("mbarrier.arrive.expect_tx.shared::cta.b64 _, [%0], %1;\n" ::"r"(bar), "r"(bytes) : "memory");
}
__device__ __forceinline__ void mbar_arrive(uint32_t bar) { asm volatile("mbarrier.arrive.shared::cta.b64 _, [%0];\n" ::"r"(bar) : "memory"); }
__device__ __forceinline__ void mbar_wait_cluster(uint32_t bar) {
    asm volatile(
        "{\n.reg .pred p;\n"
        "W_%=:\n"
        "mbarrier.try_wait.parity.acquire.cluster.shared::cta.b64 p, [%0], 0;\n"
        "@!p bra W_%=;\n}\n" ::"r"(bar) : "memory");
}
__device__ __forceinline__ void mbar_wait(uint32_t bar) {
    asm volatile(
        "{\n.reg .pred p;\n"
        "W_%=:\n"
        "mbarrier.try_wait.parity.shared::cta.b64 p, [%0], 0;\n"
        "@!p bra W_%=;\n}\n" ::"r"(bar) : "memory");
}
__device__ __forceinline__ void mbar_wait1(uint32_t bar) {
    asm volatile(
        "{\n.reg .pred p;\n"
        "W_%=:\n"
        "mbarrier.try_wait.parity.shared::cta.b64 p, [%0], 1;\n"
        "@!p bra W_%=;\n}\n" ::"r"(bar) : "memory");
}
__device__ __forceinline__ bool mbar_test(uint32_t bar) {
    uint32_t r;
    asm volatile("{\n.reg .pred p;\nmbarrier.test_wait.parity.shared::cta.b64 p, [%1], 0;\nselp.u32 %0, 1, 0, p;\n}\n" : "=r"(r) : "r"(bar) : "memory");
    return __any_sync(0xffffffffu, r);
}
__device__ __forceinline__ void bulk_g2s(uint32_t dst, const void* src, uint32_t bytes, uint32_t bar) {
    asm volatile("cp.async.bulk.shared::cluster.global.mbarrier::complete_tx::bytes [%0], [%1], %2, [%3];\n" ::"r"(dst), "l"(src), "r"(bytes), "r"(bar) : "memory");
}
__device__ __forceinline__ void bulk_s2g(void* dst, uint32_t src, uint32_t bytes) {
    asm volatile("cp.async.bulk.global.shared::cta.bulk_group [%0], [%1], %2;\ncp.async.bulk.commit_group;\n" ::"l"(dst), "r"(src), "r"(bytes) : "memory");
}
__device__ __forceinline__ void bulk_s2g_nc(void* dst, uint32_t src, uint32_t bytes) {
    asm volatile("cp.async.bulk.global.shared::cta.bulk_group [%0], [%1], %2;\n" ::"l"(dst), "r"(src), "r"(bytes) : "memory");
}
__device__ __forceinline__ void tma_2d(uint32_t dst, const CUtensorMap* tm, int c0, int c1, uint32_t bar) {
    asm volatile("cp.async.bulk.tensor.2d.shared::cluster.global.mbarrier::complete_tx::bytes [%0], [%1, {%3, %4}], [%2];\n"
                 ::"r"(dst), "l"(tm), "r"(bar), "r"(c0), "r"(c1) : "memory");
}
__device__ __forceinline__ void tma_4d(uint32_t dst, const CUtensorMap* tm, int c0, int c3, uint32_t bar) {
    asm volatile("cp.async.bulk.tensor.4d.shared::cluster.global.mbarrier::complete_tx::bytes [%0], [%1, {%3, %4, %4, %5}], [%2];\n"
                 ::"r"(dst), "l"(tm), "r"(bar), "r"(c0), "r"(0), "r"(c3) : "memory");
}
__device__ __forceinline__ void tma_4d_mc(uint32_t dst, const CUtensorMap* tm, int c0, int c3, uint32_t bar) {
    asm volatile("cp.async.bulk.tensor.4d.shared::cluster.global.mbarrier::complete_tx::bytes.multicast::cluster [%0], [%1, {%3, %4, %4, %5}], [%2], %6;\n"
                 ::"r"(dst), "l"(tm), "r"(bar), "r"(c0), "r"(0), "r"(c3), "h"((unsigned short)3) : "memory");
}
__device__ __forceinline__ void l2_prefetch(const void* src, uint32_t bytes) {
    asm volatile("cp.async.bulk.prefetch.L2.global [%0], %1;\n" ::"l"(src), "r"(bytes) : "memory");
}
__device__ __forceinline__ bool elect_one() {
    uint32_t r;
    asm volatile("{\n.reg .pred p;\nelect.sync _|p, 0xffffffff;\nselp.u32 %0, 1, 0, p;\n}\n" : "=r"(r));
    return r;
}
__device__ __forceinline__ void delay(uint32_t clks) {
    uint32_t t0, t1;
    asm volatile("mov.u32 %0, %%clock;" : "=r"(t0) :: "memory");
    do { asm volatile("mov.u32 %0, %%clock;" : "=r"(t1) :: "memory"); } while (t1 - t0 < clks);
}
__device__ __forceinline__ void fence_async() { asm volatile("fence.proxy.async.shared::cta;\n" ::: "memory"); }

__device__ __forceinline__ float2 cmul(float2 a, float2 b) {
    return make_float2(fmaf(a.x, b.x, -a.y * b.y), fmaf(a.x, b.y, a.y * b.x));
}
__device__ __forceinline__ float2 csq(float2 a) {
    float p = a.x * a.y;
    return make_float2(fmaf(a.x, a.x, -a.y * a.y), p + p);
}
__device__ __forceinline__ float ex2_approx(float x) { float r; asm("ex2.approx.ftz.f32 %0, %1;\n" : "=f"(r) : "f"(x)); return r; }
__device__ __forceinline__ float exp_bf(float x) { return rbf(ex2_approx(__fmul_ru(x, 1.4426950408889634f))); }
__device__ __forceinline__ float2 cexp_e(float lr2, float li, float e) {
    const float m = ex2_approx(lr2 * e);
    return make_float2(m * __cosf(li * e), m * __sinf(li * e));
}
__device__ __forceinline__ float rcp_approx(float x) { float r; asm("rcp.approx.ftz.f32 %0, %1;\n" : "=f"(r) : "f"(x)); return r; }
__device__ __forceinline__ float sigmoid_f(float x) { return rcp_approx(1.0f + ex2_approx(x * -1.4426950408889634f)); }
__device__ __forceinline__ float sqrt_approx(float x) { float r; asm("sqrt.approx.ftz.f32 %0, %1;\n" : "=f"(r) : "f"(x)); return r; }

__device__ __forceinline__ void wg_fence() { asm volatile("wgmma.fence.sync.aligned;\n" ::: "memory"); }
__device__ __forceinline__ void wg_commit() { asm volatile("wgmma.commit_group.sync.aligned;\n" ::: "memory"); }
__device__ __forceinline__ void wg_wait0() { asm volatile("wgmma.wait_group.sync.aligned 0;\n" ::: "memory"); }
template <int T> __device__ __forceinline__ void wg_mma(float (&acc)[16][4], const uint32_t* a, uint64_t desc);
template <int T> __device__ __forceinline__ void wg_first(float (&acc)[16][4], const uint32_t* a, uint64_t desc);
template <> __device__ __forceinline__ void wg_mma<0>(float (&acc)[16][4], const uint32_t* a, uint64_t desc) {
    asm volatile("wgmma.mma_async.sync.aligned.m64n128k16.f32.f16.f16 {%0,%1,%2,%3,%4,%5,%6,%7,%8,%9,%10,%11,%12,%13,%14,%15,%16,%17,%18,%19,%20,%21,%22,%23,%24,%25,%26,%27,%28,%29,%30,%31,%32,%33,%34,%35,%36,%37,%38,%39,%40,%41,%42,%43,%44,%45,%46,%47,%48,%49,%50,%51,%52,%53,%54,%55,%56,%57,%58,%59,%60,%61,%62,%63}, {%64,%65,%66,%67}, %68, 1, 1, 1, 0;\n"
                 : "+f"(acc[0][0]), "+f"(acc[0][1]), "+f"(acc[0][2]), "+f"(acc[0][3]), "+f"(acc[1][0]), "+f"(acc[1][1]), "+f"(acc[1][2]), "+f"(acc[1][3]), "+f"(acc[2][0]), "+f"(acc[2][1]), "+f"(acc[2][2]), "+f"(acc[2][3]), "+f"(acc[3][0]), "+f"(acc[3][1]), "+f"(acc[3][2]), "+f"(acc[3][3]), "+f"(acc[4][0]), "+f"(acc[4][1]), "+f"(acc[4][2]), "+f"(acc[4][3]), "+f"(acc[5][0]), "+f"(acc[5][1]), "+f"(acc[5][2]), "+f"(acc[5][3]), "+f"(acc[6][0]), "+f"(acc[6][1]), "+f"(acc[6][2]), "+f"(acc[6][3]), "+f"(acc[7][0]), "+f"(acc[7][1]), "+f"(acc[7][2]), "+f"(acc[7][3]), "+f"(acc[8][0]), "+f"(acc[8][1]), "+f"(acc[8][2]), "+f"(acc[8][3]), "+f"(acc[9][0]), "+f"(acc[9][1]), "+f"(acc[9][2]), "+f"(acc[9][3]), "+f"(acc[10][0]), "+f"(acc[10][1]), "+f"(acc[10][2]), "+f"(acc[10][3]), "+f"(acc[11][0]), "+f"(acc[11][1]), "+f"(acc[11][2]), "+f"(acc[11][3]), "+f"(acc[12][0]), "+f"(acc[12][1]), "+f"(acc[12][2]), "+f"(acc[12][3]), "+f"(acc[13][0]), "+f"(acc[13][1]), "+f"(acc[13][2]), "+f"(acc[13][3]), "+f"(acc[14][0]), "+f"(acc[14][1]), "+f"(acc[14][2]), "+f"(acc[14][3]), "+f"(acc[15][0]), "+f"(acc[15][1]), "+f"(acc[15][2]), "+f"(acc[15][3])
                 : "r"(a[0]), "r"(a[1]), "r"(a[2]), "r"(a[3]), "l"(desc));
}
template <> __device__ __forceinline__ void wg_mma<2>(float (&acc)[16][4], const uint32_t* a, uint64_t desc) {
    asm volatile("wgmma.mma_async.sync.aligned.m64n112k16.f32.f16.f16 {%0,%1,%2,%3,%4,%5,%6,%7,%8,%9,%10,%11,%12,%13,%14,%15,%16,%17,%18,%19,%20,%21,%22,%23,%24,%25,%26,%27,%28,%29,%30,%31,%32,%33,%34,%35,%36,%37,%38,%39,%40,%41,%42,%43,%44,%45,%46,%47,%48,%49,%50,%51,%52,%53,%54,%55}, {%56,%57,%58,%59}, %60, 1, 1, 1, 0;\n"
                 : "+f"(acc[2][0]), "+f"(acc[2][1]), "+f"(acc[2][2]), "+f"(acc[2][3]), "+f"(acc[3][0]), "+f"(acc[3][1]), "+f"(acc[3][2]), "+f"(acc[3][3]), "+f"(acc[4][0]), "+f"(acc[4][1]), "+f"(acc[4][2]), "+f"(acc[4][3]), "+f"(acc[5][0]), "+f"(acc[5][1]), "+f"(acc[5][2]), "+f"(acc[5][3]), "+f"(acc[6][0]), "+f"(acc[6][1]), "+f"(acc[6][2]), "+f"(acc[6][3]), "+f"(acc[7][0]), "+f"(acc[7][1]), "+f"(acc[7][2]), "+f"(acc[7][3]), "+f"(acc[8][0]), "+f"(acc[8][1]), "+f"(acc[8][2]), "+f"(acc[8][3]), "+f"(acc[9][0]), "+f"(acc[9][1]), "+f"(acc[9][2]), "+f"(acc[9][3]), "+f"(acc[10][0]), "+f"(acc[10][1]), "+f"(acc[10][2]), "+f"(acc[10][3]), "+f"(acc[11][0]), "+f"(acc[11][1]), "+f"(acc[11][2]), "+f"(acc[11][3]), "+f"(acc[12][0]), "+f"(acc[12][1]), "+f"(acc[12][2]), "+f"(acc[12][3]), "+f"(acc[13][0]), "+f"(acc[13][1]), "+f"(acc[13][2]), "+f"(acc[13][3]), "+f"(acc[14][0]), "+f"(acc[14][1]), "+f"(acc[14][2]), "+f"(acc[14][3]), "+f"(acc[15][0]), "+f"(acc[15][1]), "+f"(acc[15][2]), "+f"(acc[15][3])
                 : "r"(a[0]), "r"(a[1]), "r"(a[2]), "r"(a[3]), "l"(desc));
}
template <> __device__ __forceinline__ void wg_mma<4>(float (&acc)[16][4], const uint32_t* a, uint64_t desc) {
    asm volatile("wgmma.mma_async.sync.aligned.m64n96k16.f32.f16.f16 {%0,%1,%2,%3,%4,%5,%6,%7,%8,%9,%10,%11,%12,%13,%14,%15,%16,%17,%18,%19,%20,%21,%22,%23,%24,%25,%26,%27,%28,%29,%30,%31,%32,%33,%34,%35,%36,%37,%38,%39,%40,%41,%42,%43,%44,%45,%46,%47}, {%48,%49,%50,%51}, %52, 1, 1, 1, 0;\n"
                 : "+f"(acc[4][0]), "+f"(acc[4][1]), "+f"(acc[4][2]), "+f"(acc[4][3]), "+f"(acc[5][0]), "+f"(acc[5][1]), "+f"(acc[5][2]), "+f"(acc[5][3]), "+f"(acc[6][0]), "+f"(acc[6][1]), "+f"(acc[6][2]), "+f"(acc[6][3]), "+f"(acc[7][0]), "+f"(acc[7][1]), "+f"(acc[7][2]), "+f"(acc[7][3]), "+f"(acc[8][0]), "+f"(acc[8][1]), "+f"(acc[8][2]), "+f"(acc[8][3]), "+f"(acc[9][0]), "+f"(acc[9][1]), "+f"(acc[9][2]), "+f"(acc[9][3]), "+f"(acc[10][0]), "+f"(acc[10][1]), "+f"(acc[10][2]), "+f"(acc[10][3]), "+f"(acc[11][0]), "+f"(acc[11][1]), "+f"(acc[11][2]), "+f"(acc[11][3]), "+f"(acc[12][0]), "+f"(acc[12][1]), "+f"(acc[12][2]), "+f"(acc[12][3]), "+f"(acc[13][0]), "+f"(acc[13][1]), "+f"(acc[13][2]), "+f"(acc[13][3]), "+f"(acc[14][0]), "+f"(acc[14][1]), "+f"(acc[14][2]), "+f"(acc[14][3]), "+f"(acc[15][0]), "+f"(acc[15][1]), "+f"(acc[15][2]), "+f"(acc[15][3])
                 : "r"(a[0]), "r"(a[1]), "r"(a[2]), "r"(a[3]), "l"(desc));
}
template <> __device__ __forceinline__ void wg_mma<6>(float (&acc)[16][4], const uint32_t* a, uint64_t desc) {
    asm volatile("wgmma.mma_async.sync.aligned.m64n80k16.f32.f16.f16 {%0,%1,%2,%3,%4,%5,%6,%7,%8,%9,%10,%11,%12,%13,%14,%15,%16,%17,%18,%19,%20,%21,%22,%23,%24,%25,%26,%27,%28,%29,%30,%31,%32,%33,%34,%35,%36,%37,%38,%39}, {%40,%41,%42,%43}, %44, 1, 1, 1, 0;\n"
                 : "+f"(acc[6][0]), "+f"(acc[6][1]), "+f"(acc[6][2]), "+f"(acc[6][3]), "+f"(acc[7][0]), "+f"(acc[7][1]), "+f"(acc[7][2]), "+f"(acc[7][3]), "+f"(acc[8][0]), "+f"(acc[8][1]), "+f"(acc[8][2]), "+f"(acc[8][3]), "+f"(acc[9][0]), "+f"(acc[9][1]), "+f"(acc[9][2]), "+f"(acc[9][3]), "+f"(acc[10][0]), "+f"(acc[10][1]), "+f"(acc[10][2]), "+f"(acc[10][3]), "+f"(acc[11][0]), "+f"(acc[11][1]), "+f"(acc[11][2]), "+f"(acc[11][3]), "+f"(acc[12][0]), "+f"(acc[12][1]), "+f"(acc[12][2]), "+f"(acc[12][3]), "+f"(acc[13][0]), "+f"(acc[13][1]), "+f"(acc[13][2]), "+f"(acc[13][3]), "+f"(acc[14][0]), "+f"(acc[14][1]), "+f"(acc[14][2]), "+f"(acc[14][3]), "+f"(acc[15][0]), "+f"(acc[15][1]), "+f"(acc[15][2]), "+f"(acc[15][3])
                 : "r"(a[0]), "r"(a[1]), "r"(a[2]), "r"(a[3]), "l"(desc));
}
template <> __device__ __forceinline__ void wg_mma<8>(float (&acc)[16][4], const uint32_t* a, uint64_t desc) {
    asm volatile("wgmma.mma_async.sync.aligned.m64n64k16.f32.f16.f16 {%0,%1,%2,%3,%4,%5,%6,%7,%8,%9,%10,%11,%12,%13,%14,%15,%16,%17,%18,%19,%20,%21,%22,%23,%24,%25,%26,%27,%28,%29,%30,%31}, {%32,%33,%34,%35}, %36, 1, 1, 1, 0;\n"
                 : "+f"(acc[8][0]), "+f"(acc[8][1]), "+f"(acc[8][2]), "+f"(acc[8][3]), "+f"(acc[9][0]), "+f"(acc[9][1]), "+f"(acc[9][2]), "+f"(acc[9][3]), "+f"(acc[10][0]), "+f"(acc[10][1]), "+f"(acc[10][2]), "+f"(acc[10][3]), "+f"(acc[11][0]), "+f"(acc[11][1]), "+f"(acc[11][2]), "+f"(acc[11][3]), "+f"(acc[12][0]), "+f"(acc[12][1]), "+f"(acc[12][2]), "+f"(acc[12][3]), "+f"(acc[13][0]), "+f"(acc[13][1]), "+f"(acc[13][2]), "+f"(acc[13][3]), "+f"(acc[14][0]), "+f"(acc[14][1]), "+f"(acc[14][2]), "+f"(acc[14][3]), "+f"(acc[15][0]), "+f"(acc[15][1]), "+f"(acc[15][2]), "+f"(acc[15][3])
                 : "r"(a[0]), "r"(a[1]), "r"(a[2]), "r"(a[3]), "l"(desc));
}
template <> __device__ __forceinline__ void wg_mma<10>(float (&acc)[16][4], const uint32_t* a, uint64_t desc) {
    asm volatile("wgmma.mma_async.sync.aligned.m64n48k16.f32.f16.f16 {%0,%1,%2,%3,%4,%5,%6,%7,%8,%9,%10,%11,%12,%13,%14,%15,%16,%17,%18,%19,%20,%21,%22,%23}, {%24,%25,%26,%27}, %28, 1, 1, 1, 0;\n"
                 : "+f"(acc[10][0]), "+f"(acc[10][1]), "+f"(acc[10][2]), "+f"(acc[10][3]), "+f"(acc[11][0]), "+f"(acc[11][1]), "+f"(acc[11][2]), "+f"(acc[11][3]), "+f"(acc[12][0]), "+f"(acc[12][1]), "+f"(acc[12][2]), "+f"(acc[12][3]), "+f"(acc[13][0]), "+f"(acc[13][1]), "+f"(acc[13][2]), "+f"(acc[13][3]), "+f"(acc[14][0]), "+f"(acc[14][1]), "+f"(acc[14][2]), "+f"(acc[14][3]), "+f"(acc[15][0]), "+f"(acc[15][1]), "+f"(acc[15][2]), "+f"(acc[15][3])
                 : "r"(a[0]), "r"(a[1]), "r"(a[2]), "r"(a[3]), "l"(desc));
}
template <> __device__ __forceinline__ void wg_mma<12>(float (&acc)[16][4], const uint32_t* a, uint64_t desc) {
    asm volatile("wgmma.mma_async.sync.aligned.m64n32k16.f32.f16.f16 {%0,%1,%2,%3,%4,%5,%6,%7,%8,%9,%10,%11,%12,%13,%14,%15}, {%16,%17,%18,%19}, %20, 1, 1, 1, 0;\n"
                 : "+f"(acc[12][0]), "+f"(acc[12][1]), "+f"(acc[12][2]), "+f"(acc[12][3]), "+f"(acc[13][0]), "+f"(acc[13][1]), "+f"(acc[13][2]), "+f"(acc[13][3]), "+f"(acc[14][0]), "+f"(acc[14][1]), "+f"(acc[14][2]), "+f"(acc[14][3]), "+f"(acc[15][0]), "+f"(acc[15][1]), "+f"(acc[15][2]), "+f"(acc[15][3])
                 : "r"(a[0]), "r"(a[1]), "r"(a[2]), "r"(a[3]), "l"(desc));
}
template <> __device__ __forceinline__ void wg_mma<14>(float (&acc)[16][4], const uint32_t* a, uint64_t desc) {
    asm volatile("wgmma.mma_async.sync.aligned.m64n16k16.f32.f16.f16 {%0,%1,%2,%3,%4,%5,%6,%7}, {%8,%9,%10,%11}, %12, 1, 1, 1, 0;\n"
                 : "+f"(acc[14][0]), "+f"(acc[14][1]), "+f"(acc[14][2]), "+f"(acc[14][3]), "+f"(acc[15][0]), "+f"(acc[15][1]), "+f"(acc[15][2]), "+f"(acc[15][3])
                 : "r"(a[0]), "r"(a[1]), "r"(a[2]), "r"(a[3]), "l"(desc));
}
template <> __device__ __forceinline__ void wg_first<0>(float (&acc)[16][4], const uint32_t* a, uint64_t desc) {
    asm volatile("wgmma.mma_async.sync.aligned.m64n128k16.f32.f16.f16 {%0,%1,%2,%3,%4,%5,%6,%7,%8,%9,%10,%11,%12,%13,%14,%15,%16,%17,%18,%19,%20,%21,%22,%23,%24,%25,%26,%27,%28,%29,%30,%31,%32,%33,%34,%35,%36,%37,%38,%39,%40,%41,%42,%43,%44,%45,%46,%47,%48,%49,%50,%51,%52,%53,%54,%55,%56,%57,%58,%59,%60,%61,%62,%63}, {%64,%65,%66,%67}, %68, 0, 1, 1, 0;\n"
                 : "=f"(acc[0][0]), "=f"(acc[0][1]), "=f"(acc[0][2]), "=f"(acc[0][3]), "=f"(acc[1][0]), "=f"(acc[1][1]), "=f"(acc[1][2]), "=f"(acc[1][3]), "=f"(acc[2][0]), "=f"(acc[2][1]), "=f"(acc[2][2]), "=f"(acc[2][3]), "=f"(acc[3][0]), "=f"(acc[3][1]), "=f"(acc[3][2]), "=f"(acc[3][3]), "=f"(acc[4][0]), "=f"(acc[4][1]), "=f"(acc[4][2]), "=f"(acc[4][3]), "=f"(acc[5][0]), "=f"(acc[5][1]), "=f"(acc[5][2]), "=f"(acc[5][3]), "=f"(acc[6][0]), "=f"(acc[6][1]), "=f"(acc[6][2]), "=f"(acc[6][3]), "=f"(acc[7][0]), "=f"(acc[7][1]), "=f"(acc[7][2]), "=f"(acc[7][3]), "=f"(acc[8][0]), "=f"(acc[8][1]), "=f"(acc[8][2]), "=f"(acc[8][3]), "=f"(acc[9][0]), "=f"(acc[9][1]), "=f"(acc[9][2]), "=f"(acc[9][3]), "=f"(acc[10][0]), "=f"(acc[10][1]), "=f"(acc[10][2]), "=f"(acc[10][3]), "=f"(acc[11][0]), "=f"(acc[11][1]), "=f"(acc[11][2]), "=f"(acc[11][3]), "=f"(acc[12][0]), "=f"(acc[12][1]), "=f"(acc[12][2]), "=f"(acc[12][3]), "=f"(acc[13][0]), "=f"(acc[13][1]), "=f"(acc[13][2]), "=f"(acc[13][3]), "=f"(acc[14][0]), "=f"(acc[14][1]), "=f"(acc[14][2]), "=f"(acc[14][3]), "=f"(acc[15][0]), "=f"(acc[15][1]), "=f"(acc[15][2]), "=f"(acc[15][3])
                 : "r"(a[0]), "r"(a[1]), "r"(a[2]), "r"(a[3]), "l"(desc));
}
template <> __device__ __forceinline__ void wg_first<4>(float (&acc)[16][4], const uint32_t* a, uint64_t desc) {
    asm volatile("wgmma.mma_async.sync.aligned.m64n96k16.f32.f16.f16 {%0,%1,%2,%3,%4,%5,%6,%7,%8,%9,%10,%11,%12,%13,%14,%15,%16,%17,%18,%19,%20,%21,%22,%23,%24,%25,%26,%27,%28,%29,%30,%31,%32,%33,%34,%35,%36,%37,%38,%39,%40,%41,%42,%43,%44,%45,%46,%47}, {%48,%49,%50,%51}, %52, 0, 1, 1, 0;\n"
                 : "=f"(acc[4][0]), "=f"(acc[4][1]), "=f"(acc[4][2]), "=f"(acc[4][3]), "=f"(acc[5][0]), "=f"(acc[5][1]), "=f"(acc[5][2]), "=f"(acc[5][3]), "=f"(acc[6][0]), "=f"(acc[6][1]), "=f"(acc[6][2]), "=f"(acc[6][3]), "=f"(acc[7][0]), "=f"(acc[7][1]), "=f"(acc[7][2]), "=f"(acc[7][3]), "=f"(acc[8][0]), "=f"(acc[8][1]), "=f"(acc[8][2]), "=f"(acc[8][3]), "=f"(acc[9][0]), "=f"(acc[9][1]), "=f"(acc[9][2]), "=f"(acc[9][3]), "=f"(acc[10][0]), "=f"(acc[10][1]), "=f"(acc[10][2]), "=f"(acc[10][3]), "=f"(acc[11][0]), "=f"(acc[11][1]), "=f"(acc[11][2]), "=f"(acc[11][3]), "=f"(acc[12][0]), "=f"(acc[12][1]), "=f"(acc[12][2]), "=f"(acc[12][3]), "=f"(acc[13][0]), "=f"(acc[13][1]), "=f"(acc[13][2]), "=f"(acc[13][3]), "=f"(acc[14][0]), "=f"(acc[14][1]), "=f"(acc[14][2]), "=f"(acc[14][3]), "=f"(acc[15][0]), "=f"(acc[15][1]), "=f"(acc[15][2]), "=f"(acc[15][3])
                 : "r"(a[0]), "r"(a[1]), "r"(a[2]), "r"(a[3]), "l"(desc));
}

#define SDLY 900
#define UDLY 1400
#define KDLY 950
#define FDLY 1000
#define FDLY2 400
#define DDLY 300
#define WDLY 500
#define HW 15
#define FIX(v) do { if ((v) == 1u) TRAP(); } while (0)
#define STAMPW(i) STAMPY(i)
#define STAMP2(i) STAMP(i)
#undef STAMPX
#define STAMPX(i)
struct Params {
    const bf16 *x, *lar, *aim, *cre, *cim, *ldt, *dsk;
    Scratch* s;
    const bf16 *wr, *wg, *wu, *wd;
    bf16* out;
};

#define TOK(g) (2 * (g) - ((g) & 1))
#define ROWTOK(r) (TOK((r) & 7) + (((r) >> 2) & 2))
__device__ __forceinline__ void ln_partial(const uint32_t (&H)[2][4], float (&d)[2][4]) {
#pragma unroll
    for (int hf = 0; hf < 2; hf++) {
        d[hf][0] = d[hf][1] = d[hf][2] = d[hf][3] = 0.f;
        mma_bf16(d[hf], H[hf][0], 0x3f803f80u, H[hf][1], 0x3f803f80u, H[hf][0], H[hf][1]);
    }
#pragma unroll
    for (int hf = 0; hf < 2; hf++) mma_bf16(d[hf], H[hf][2], 0x3f803f80u, H[hf][3], 0x3f803f80u, H[hf][2], H[hf][3]);
}
__device__ __forceinline__ float sum18(uint32_t a) {
    const uint4 p = lds128(a), q = lds128(a + 16), r = lds128(a + 32), s = lds128(a + 48);
    const uint2 u = lds64(a + 64);
#define F(x) __uint_as_float(x)
    return (((F(p.x) + F(p.y)) + (F(p.z) + F(p.w))) + ((F(q.x) + F(q.y)) + (F(q.z) + F(q.w)))) +
           (((F(r.x) + F(r.y)) + (F(r.z) + F(r.w))) + ((F(s.x) + F(s.y)) + (F(s.z) + F(s.w))) + (F(u.x) + F(u.y)));
#undef F
}
__device__ __forceinline__ void ln_stats(float sm, float sq, float& mb, float& sd) {
    const float m0 = sm * (1.0f / 576.0f);
    const float mean = fmaf(fmaf(-m0, 576.0f, sm), 1.0f / 576.0f, m0);
    const float var = fmaxf(fmaf(-mean, mean, sq * (1.0f / 576.0f)), 0.f);
    mb = rbf(mean);
    sd = rbf(sqrt_approx(rbf(rbf(var) + 1e-5f)));
}
__device__ __forceinline__ void ln_finish(float v, int lane, float& mb, float& rc) {
    const float o = __shfl_xor_sync(0xffffffffu, v, 16);
    float sd;
    ln_stats(lane < 16 ? v : o, lane < 16 ? o : v, mb, sd);
    rc = rcp_approx(sd);
}
__device__ __forceinline__ uint32_t ln_apply(uint32_t w, uint32_t m2, uint32_t rh, uint32_t rl) {
    const uint32_t d = hsub2_bf(w, m2);
    return hfma2_bf(d, rh, hmul2_bf(d, rl));
}
__device__ __forceinline__ void stat_store(uint32_t a, float mb, float rc, uint32_t extra) {
    const float rh = rbf(rc);
    sts64(a, (__float_as_uint(mb) >> 16) | (extra << 16), pack_bf16(rh, rc - rh));
}
#define STAT_M(s) __byte_perm((s).x, (s).x, 0x1010)
#define STAT_H(s) __byte_perm((s).y, (s).y, 0x1010)
#define STAT_L(s) __byte_perm((s).y, (s).y, 0x3232)

__device__ __forceinline__ void hcmul(uint32_t re, uint32_t im, uint32_t zx, uint32_t zy, uint32_t& ore, uint32_t& oim) {
    ore = hfms2(im, zy, hmul2(re, zx));
    oim = hfma2(re, zy, hmul2(im, zx));
}

struct KGen {
    uint32_t A[2][4][4];
    float2 z1, z8, z64, z128, T[9];
};
__device__ __forceinline__ void kgen_setup(KGen& k, float lar, float aim, float dt) {
    const float lr2 = -(exp_bf(lar) * dt) * 1.4426950408889634f, li = aim * dt;
    k.z1 = cexp_e(lr2, li, 1.0f);
    k.z8 = cexp_e(lr2, li, 8.0f);
    k.z64 = cexp_e(lr2, li, 64.0f);
}
__device__ __forceinline__ void kgen_rows(KGen& k, uint32_t tb, int lane) {
    const float2 z8 = k.z8, z64 = k.z64;
    const uint32_t row = tb + lane * 16;
    k.z128 = csq(z64);
    const float2 z16 = csq(z8), z24 = cmul(z16, z8), z32 = csq(z16), z40 = cmul(z32, z8), z48 = csq(z24), z56 = cmul(z32, z24);
    uint32_t re[4], im[4], a[4], b[4];
    re[0] = pack_f16(1.0f, z8.x); im[0] = pack_f16(0.0f, z8.y);
    re[1] = pack_f16(z16.x, z24.x); im[1] = pack_f16(z16.y, z24.y);
    re[2] = pack_f16(z32.x, z40.x); im[2] = pack_f16(z32.y, z40.y);
    re[3] = pack_f16(z48.x, z56.x); im[3] = pack_f16(z48.y, z56.y);
    sts128(row, re[0], re[1], re[2], re[3]);
    sts128(row + 1024, im[0], im[1], im[2], im[3]);
    const uint32_t zx = pack_f16(z64.x, z64.x), zy = pack_f16(z64.y, z64.y), zw = pack_f16(k.z128.x, k.z128.y);
#pragma unroll
    for (int j = 0; j < 4; j++) hcmul(re[j], im[j], zx, zy, a[j], b[j]);
    sts128(row + 512, a[0], a[1], a[2], a[3]);
    sts128(row + 1536, b[0], b[1], b[2], b[3]);
    const int mi = lane >> 3;
    const uint32_t zd = tb + 2048 + mi * 16;
    sts16(tb + 2048 + lane * 2, zw); sts16(tb + 2112 + lane * 2, zw >> 16);
    __syncwarp();
    const uint32_t ad = tb + (lane & 7) * 16 + mi * 512;
    ldsm_x4(a[0], a[1], a[2], a[3], zd);
    ldsm_x4(b[0], b[1], b[2], b[3], zd + 64);
#pragma unroll
    for (int ks = 0; ks < 4; ks++) {
        ldsm_x4_t(k.A[0][ks][0], k.A[0][ks][1], k.A[0][ks][2], k.A[0][ks][3], ad + ks * 128);
        hcmul(k.A[0][ks][0], k.A[0][ks][2], a[ks], b[ks], k.A[1][ks][0], k.A[1][ks][2]);
        hcmul(k.A[0][ks][1], k.A[0][ks][3], a[ks], b[ks], k.A[1][ks][1], k.A[1][ks][3]);
    }
}
__device__ __forceinline__ void kgen_chain(KGen& k, uint32_t cr, uint32_t ci, float cs) {
    k.T[0] = make_float2(bf_lo(cr) * cs, -bf_lo(ci) * cs);
    const float2 y1 = make_float2(k.z1.x, -k.z1.y);
#pragma unroll
    for (int c = 1; c < 8; c++) k.T[c] = cmul(k.T[c - 1], y1);
    k.T[8] = cmul(k.T[0], make_float2(k.z8.x, -k.z8.y));
}
__device__ __forceinline__ void kgen_cols(KGen& k, uint32_t tb, uint32_t t5, int lane) {
    const uint32_t row = tb + lane * 16;
    const float2 (&T)[9] = k.T;
    const float2 y128 = make_float2(k.z128.x, -k.z128.y);
    const float2 y256 = csq(y128), y512 = csq(y256), y768 = cmul(y512, y256), y1024 = csq(y512);
    const float2 c1032 = cmul(T[8], y1024);
    __syncwarp();
    sts128(row, pack_f16(T[0].x, T[1].x), pack_f16(T[2].x, T[3].x), pack_f16(T[4].x, T[5].x), pack_f16(T[6].x, T[7].x));
    sts128(row + 512, pack_f16(T[0].y, T[1].y), pack_f16(T[2].y, T[3].y), pack_f16(T[4].y, T[5].y), pack_f16(T[6].y, T[7].y));
    uint32_t a[4], b[4];
    {
        const uint32_t zx = pack_f16(y256.x, y256.x), zy = pack_f16(y256.y, y256.y);
        hcmul(pack_f16(T[0].x, T[2].x), pack_f16(T[0].y, T[2].y), zx, zy, a[0], b[0]);
        hcmul(pack_f16(T[4].x, T[6].x), pack_f16(T[4].y, T[6].y), zx, zy, a[1], b[1]);
        const uint32_t r04 = pack_f16(T[0].x, T[4].x), i04 = pack_f16(T[0].y, T[4].y);
        hcmul(r04, i04, pack_f16(y512.x, y512.x), pack_f16(y512.y, y512.y), a[2], b[2]);
        hcmul(r04, i04, pack_f16(y768.x, y768.x), pack_f16(y768.y, y768.y), a[3], b[3]);
    }
    sts128(row + 1024, a[0], a[1], a[2], a[3]);
    sts128(row + 1536, b[0], b[1], b[2], b[3]);
    {
        const uint32_t r0 = pack_f16(1.0f, y256.x), i0 = pack_f16(0.0f, y256.y), r1 = pack_f16(y512.x, y768.x), i1 = pack_f16(y512.y, y768.y);
        const uint32_t zx = pack_f16(T[8].x, T[8].x), zy = pack_f16(T[8].y, T[8].y), wx = pack_f16(c1032.x, c1032.x), wy = pack_f16(c1032.y, c1032.y);
        hcmul(r0, i0, zx, zy, a[0], b[0]); hcmul(r1, i1, zx, zy, a[1], b[1]);
        hcmul(r0, i0, wx, wy, a[2], b[2]); hcmul(r1, i1, wx, wy, a[3], b[3]);
    }
    sts128(row + 2048, a[0], a[1], a[2], a[3]);
    sts128(t5 + lane * 16, b[0], b[1], b[2], b[3]);
}
__device__ __forceinline__ void kgen_mma(const KGen& k, uint32_t tb, uint32_t t5, int lane) {
    __syncwarp();
    float acc[2][3][4];
#pragma unroll
    for (int i = 0; i < 6; i++)
#pragma unroll
        for (int j = 0; j < 4; j++) acc[i / 3][i % 3][j] = 0.f;
    const int mi = lane >> 3;
    const uint32_t ro = ((lane & 7) + 8 * (mi >> 1)) * 16, bd = tb + ro + (mi & 1) * 512, b2 = ro + ((mi & 1) ? t5 : tb + 2048);
#pragma unroll
    for (int kp = 0; kp < 2; kp++)
#pragma unroll
        for (int j = 0; j < 3; j++) {
            uint32_t b[4];
            ldsm_x4_t(b[0], b[1], b[2], b[3], (j < 2 ? bd + j * 1024 : b2) + kp * 256);
#pragma unroll
            for (int h = 0; h < 2; h++)
#pragma unroll
                for (int m = 0; m < 2; m++) {
                    const uint32_t (&A)[4] = k.A[m][2 * kp + h];
                    mma_f16(acc[m][j], A[0], A[1], A[2], A[3], b[2 * h], b[2 * h + 1]);
                }
        }
    __syncwarp();
#define PK(j) pack_f16(acc[0][j][0], acc[0][j][1]), pack_f16(acc[0][j][2], acc[0][j][3]), pack_f16(acc[1][j][0], acc[1][j][1]), pack_f16(acc[1][j][2], acc[1][j][3])
    stsm_x4(tb + lane * 16, PK(0));
    stsm_x4(tb + 512 + lane * 16, PK(1));
    stsm_x4_t(tb + 1024 + (lane & 7) * 80 + mi * 16, PK(2));
#undef PK
}
__device__ __forceinline__ uint32_t table_buf(uint32_t sb, int warp) { return sb + SM_PL + warp * TBW; }

__device__ __forceinline__ uint4 lds16x4(uint32_t a) { return make_uint4(lds16(a), lds16(a + TBW), lds16(a + 2 * TBW), lds16(a + 3 * TBW)); }
__device__ __forceinline__ void combine_setup(uint32_t sb, int warp, int lane, uint32_t kw, uint32_t& o, uint32_t& n, uint32_t& d) {
    const int wq = warp & 3;
    const uint32_t a = table_buf(sb, warp & ~3);
    o = wq == 3 ? a + 1024 + 320 + (lane >> 3) * 80 + (lane & 7) * 8 : a + (wq ? 504 + wq * 8 : 0) + lane * 16;
    n = a + 1024 + wq * 80 + lane * 2;
    d = wq < 3 ? kw + (wq == 2 ? KW_P : 32 + wq * 512) + lane * 16 : kw + KW_H + 8 + lane * 8;
}
__device__ __forceinline__ void kgen_combine(int wq, int lane, uint32_t o, uint32_t na, uint32_t d) {
#define S4(f) hadd2(hadd2(u.f, v.f), hadd2(w.f, x.f))
#define H4(v) hadd2(hadd2(v.x, v.y), hadd2(v.z, v.w))
#define BP __byte_perm
    if (wq == 0) {
        const uint4 u = lds128(o), v = lds128(o + TBW), w = lds128(o + 2 * TBW), x = lds128(o + 3 * TBW), nn = lds16x4(na);
        const uint32_t n = H4(nn), k0 = S4(x), k2 = S4(y), k4 = S4(z), k6 = S4(w);
        sts128(d, BP(k0, k0, 0x1032), BP(k0, k2, 0x3254), BP(k2, k2, 0x1032), BP(k2, k4, 0x3254));
        sts128(d + KW_PL, BP(k4, k4, 0x1032), BP(k4, k6, 0x3254), BP(k6, k6, 0x1032), BP(k6, n, 0x3254));
        if (lane == 0) sts32(d + KW_PL - 4, k0 & 0xffffu);
    } else {
        const uint2 u = lds64(o), v = lds64(o + TBW), w = lds64(o + 2 * TBW), x = lds64(o + 3 * TBW);
        uint4 nn = make_uint4(0u, 0u, 0u, 0u), mm = nn;
        if (wq < 3) nn = lds16x4(na);
        if (wq == 2) mm = lds16x4(na + 80);
        const uint32_t k0 = S4(x), k2 = S4(y), n = H4(nn), m = H4(mm);
        if (wq == 3) {
            sts64(d, k0, k2);
        } else if (wq == 1) {
            const uint32_t cc = BP(k2, k2, 0x1010);
            sts128(d, BP(k0, k0, 0x1010), BP(k0, k0, 0x1032), BP(k0, k2, 0x3254), cc);
            sts128(d + KW_PL, cc, BP(k2, k2, 0x1032), BP(k2, n, 0x3254), BP(n, n, 0x1010));
        } else {
            const uint32_t w40 = BP(k0, k0, 0x1032), w84 = BP(k0, n, 0x3254), w0 = BP(k0, k0, 0x1010), w4 = BP(k0, k0, 0x3232), w8 = BP(n, n, 0x1010);
            sts64(d, w40, w84);
            sts64(d + 512, BP(k2, k2, 0x1032), BP(k2, m, 0x3254));
            if (lane < 8) { sts128(d - (KW_P - 1056), w0, w0, w40, w4); sts128(d - (KW_P - 1056 - KW_PL), w4, w84, w8, w8); }
            if (lane == 31) sts16(d + (KW_H + 6 - KW_P - 496), m);
        }
    }
#undef S4
#undef H4
#undef BP
}

__device__ __forceinline__ int c_exponent(const uint2& r, const uint2& i, float dt) {
    const uint32_t mx = __vmaxu2(__vmaxu2(r.x & 0x7fff7fffu, r.y & 0x7fff7fffu), __vmaxu2(i.x & 0x7fff7fffu, i.y & 0x7fff7fffu));
    return __reduce_max_sync(0xffffffffu, max(mx, mx << 16) + (__float_as_uint(dt) & 0x7f800000u)) >> 23;
}

__device__ __forceinline__ int warp_v() { int l; asm volatile("mov.u32 %0, %%tid.x;" : "=r"(l)); return __shfl_sync(0xffffffffu, l >> 5, 0); }
__device__ __forceinline__ int lane_v() { int l; asm volatile("mov.u32 %0, %%laneid;" : "=r"(l)); return l; }
__device__ __forceinline__ uint32_t prmt_v(uint32_t a, uint32_t b, uint32_t s) { uint32_t d; asm volatile("prmt.b32 %0, %1, %2, %3;\n" : "=r"(d) : "r"(a), "r"(b), "r"(s)); return d; }
__device__ __forceinline__ uint32_t mov_v(uint32_t a) { uint32_t d; asm volatile("mov.b32 %0, %1;\n" : "=r"(d) : "r"(a)); return d; }
template <int G>
__device__ __forceinline__ void conv_rename(float (&acc)[16][4]) {
#pragma unroll
    for (int i = G; i < 16; i++)
#pragma unroll
        for (int j = 0; j < 4; j++) { float v; asm volatile("mov.b32 %0, %1;\n" : "=f"(v) : "f"(acc[i][j])); acc[i][j] = v; }
}
struct Conv {
    uint32_t kw;
    uint32_t wa;
    uint32_t pa, s2;
    uint32_t s8;
    uint32_t id;
    uint32_t lc;
    uint32_t fs;
    uint32_t fl, yo;
    uint32_t yp;
    size_t ycopy;
    uint32_t ps;
    uint64_t d0;
    int warp;
};
struct Pk { uint32_t w[4]; };
__device__ __forceinline__ Pk pk2(const float (&u)[4], const float (&v)[4]) {
    Pk r;
    r.w[0] = pack_f16(u[0], u[1]); r.w[1] = pack_f16(u[2], u[3]); r.w[2] = pack_f16(v[0], v[1]); r.w[3] = pack_f16(v[2], v[3]);
    return r;
}
__device__ __forceinline__ void park(uint32_t a, const Pk& v) {
    asm volatile("stmatrix.sync.aligned.m8n8.x4.trans.shared.b16 [%0], {%1,%2,%3,%4};\n" ::"r"(a), "r"(v.w[0]), "r"(v.w[1]), "r"(v.w[2]), "r"(v.w[3]) : "memory");
}
__device__ __forceinline__ void conv_constants(uint32_t lc, int l) {
    const int d = (l >> 2) - 2 * (l & 3);
    const int e = d + 8, r4 = (e + 1 + ((e >> 2) & 1)) >> 2, p4 = (e + (((e - 1) >> 2) & 1)) >> 2;
    const uint32_t s2 = r4 == p4 ? 0x1010u : 0x3210u;
    sts64(lc + l * 8, KW_P + ((r4 - 5) >> 1) * 16 + ((r4 - 5) & 1) * 4, s2 | ((d < 0 ? s2 : 0x7654u) << 16));
    const int lo = (d >= 4) - (d < -3), ho = (d >= 5) - (d < -2), le = (d > 4) - (d < -4), he = (d > 5) - (d < -3);
    sts32(lc + 512 + l * 8, (0x5454u + lo * 0x22 + ho * 0x2200) | ((0x3232u + le * 0x22 + he * 0x2200) << 16));
    const int cc = l >> 2, j = l & 3;
    sts64(lc + 256 + l * 8, (j >> 1) * PL_HALF + (16 + cc) * 16 + (j & 1) * 8, (cc >> 1) * (DM * 64) + (cc & 1) * 32 + j * 8);
}
__device__ __forceinline__ void conv_selectors4(Conv& c) {
    const uint2 v = lds64(c.lc + lane_v() * 8);
    c.pa = v.x; c.s2 = v.y;
}
__device__ __forceinline__ void conv_selectors8(Conv& c) { c.s8 = lds32(c.lc + 512 + lane_v() * 8); }
template <int G, int I0, int I1>
__device__ __forceinline__ void conv_load(const Conv& c, uint32_t (&q)[9]) {
    const int wq = c.warp & 3;
    if (G < 2) {
#pragma unroll
        for (int i = I0; i < I1; i++) q[i] = lds32(c.wa + G * 512 + i * 16);
    } else if (G < 4) {
        const uint32_t a = (G == 2 && wq == 0) ? c.wa + 1024 : c.pa + c.kw + wq * 128 + (G < 2 ? 0 : G - 2) * 512;
#pragma unroll
        for (int i = I0; i < I1; i++) q[i] = lds32(a + i * 16);
    } else {
        const uint4 u = lds128(c.kw + KW_H + (G < 4 ? 0 : G - 4) * 64 + wq * 16);
        const uint2 v = lds64(c.kw + KW_H + (G < 4 ? 0 : G - 4) * 64 + wq * 16 + 16);
        q[0] = u.x; q[1] = u.y; q[2] = u.z; q[3] = u.w; q[4] = v.x; q[5] = v.y;
        if (G == 4 && wq == 0) { q[6] = lds32(c.pa + c.kw + 1024); q[7] = lds32(c.pa + c.kw + 1040); }
    }
}
template <int G, int J0, int J1>
__device__ __forceinline__ void conv_frag(const Conv& c, const uint32_t (&q)[9], uint32_t* a, const Pk& dp) {
    const uint32_t dep = dp.w[0];
    if (G < 4) {
        const uint32_t s = (G < 2 || (G == 2 && (c.warp & 3) == 0)) ? c.id : c.s2;
#pragma unroll
        for (int j = J0; j < J1; j++) {
            uint32_t* o = a + 4 * (j - J0);
            o[0] = prmt_v(q[2 * j + 1], dp.w[0], s); o[1] = prmt_v(q[2 * j + 2], dp.w[1], s); o[2] = prmt_v(q[2 * j], dp.w[2], s); o[3] = prmt_v(q[2 * j + 1], dp.w[3], s);
        }
    } else {
        const uint32_t so = prmt_v(c.s8, dep, c.id), se = prmt_v(c.s8, dep, c.id + 0x22);
#pragma unroll
        for (int j = J0; j < J1; j++) {
            uint32_t* o = a + 4 * (j - J0);
            o[0] = prmt_v(q[j + 1], q[j + 2], se); o[1] = prmt_v(q[j + 1], q[j + 2], so); o[2] = prmt_v(q[j], q[j + 1], so);
            if (G == 4 && j == 0 && (c.warp & 3) == 0) {
                o[2] = prmt_v(q[6], dep, c.s2);
                o[0] = prmt_v(q[7], o[0], c.s2 >> 16);
            }
            o[3] = mov_v(o[0]);
        }
    }
}
template <int G, int J0, int J1>
__device__ __forceinline__ void conv_frag(const Conv& c, const uint32_t (&q)[9], uint32_t* a, float depf) {
    const uint32_t d = __float_as_uint(depf);
    conv_frag<G, J0, J1>(c, q, a, Pk{{d, d, d, d}});
}
template <int G, int T, int J0, int J1>
__device__ __forceinline__ void conv_mma(float (&acc)[16][4], const Conv& c, const uint32_t* a) {
#pragma unroll
    for (int j = J0; j < J1; j++) wg_mma<T>(acc, a + 4 * (j - J0), c.d0 - 8 * (2 * G - T) - j);
}
__device__ __forceinline__ float h_lo(uint32_t w) { return __half2float(__ushort_as_half((unsigned short)(w & 0xffffu))); }
__device__ __forceinline__ float h_hi(uint32_t w) { return __half2float(__ushort_as_half((unsigned short)(w >> 16))); }
__device__ __forceinline__ void flush_setup(Conv& c) {
    const uint2 v = lds64(c.lc + 256 + lane_v() * 8);
    c.fl = v.x; c.yo = v.y;
}
template <int Q>
__device__ __forceinline__ void flush_load(const Conv& c, uint32_t pl, uint2 (&f)[4]) {
#pragma unroll
    for (int w = 0; w < 4; w++) f[w] = lds64(c.fl + pl + (Q & 1) * 512 + w * (PLW_B - 64));
}
template <int Q>
__device__ __forceinline__ void flush_load_first(const Conv& c, uint32_t pl, uint2 (&f)[4], float depf) {
    const uint32_t p = prmt_v(c.fl, __float_as_uint(depf), c.id) + pl + (Q & 1) * 512;
#define LDV64(d, a) asm volatile("ld.volatile.shared.v2.u32 {%0,%1}, [%2];\n" : "=r"(d.x), "=r"(d.y) : "r"(a) : "memory")
    LDV64(f[0], p); LDV64(f[1], p + (PLW_B - 64)); LDV64(f[2], p + 2 * (PLW_B - 64)); LDV64(f[3], p + 3 * (PLW_B - 64));
}
#define FDEP __uint_as_float(f[3].y)
template <int Q, int mode>
__device__ __forceinline__ void conv_flush(const Conv& c, const uint2 (&f)[4], unsigned char* gy, uint32_t rx) {
    const uint32_t a0 = hadd2(f[0].x, f[1].x), a1 = hadd2(f[2].x, f[3].x), b0 = hadd2(f[0].y, f[1].y), b1 = hadd2(f[2].y, f[3].y);
    if (Q > 0 && mode == 1) {
        const uint32_t ra = rx + 16 + (Q > 0 ? Q - 1 : 0) * 1024 + (c.warp & 3) * 256 + lane_v() * 8;
        asm volatile("st.async.shared::cluster.mbarrier::complete_tx::bytes.v2.b32 [%0], {%1,%2}, [%3];\n"
                     ::"r"(ra ^ 0x1000000u), "r"(hadd2(a0, a1)), "r"(hadd2(b0, b1)), "r"((rx + (Q > 1 ? 8 : 0)) ^ 0x1000000u) : "memory");
        return;
    }
    float v0 = h_lo(a0) + h_lo(a1), v1 = h_hi(a0) + h_hi(a1), v2 = h_lo(b0) + h_lo(b1), v3 = h_hi(b0) + h_hi(b1);
    if (Q > 0 && mode == 2) {
        const uint2 o = lds64(rx + 16 + (Q > 0 ? Q - 1 : 0) * 1024 + (c.warp & 3) * 256 + lane_v() * 8);
        v0 += h_lo(o.x); v1 += h_hi(o.x); v2 += h_lo(o.y); v3 += h_hi(o.y);
    }
    const uint32_t lo = hmul2_bf(pack_bf16(v0, v1), c.fs), hi = hmul2_bf(pack_bf16(v2, v3), c.fs);
    stg64(gy + Q * 32 * DM * 32 + (c.yo + (Q < 3 ? c.yp : 0u)), nzw(lo), nzw(hi));
}
template <int I, bool S = false> struct IC { static constexpr int value = I; static constexpr bool shared = S; };
template <class T> __device__ constexpr bool wg_is4() { return T::shared; }
#define SLOT(n) (c.ps + (2 + ((n) & 7)) * 128)
#define GO() do { wg_commit(); __syncwarp(); } while (0)
#define DEP acc[15][3]
template <class FG, class FP, class FN>
__device__ __forceinline__ void conv_head(Conv& c, float (&acc)[16][4], uint32_t (&q)[9], uint32_t (&r)[9], uint32_t* a, FG fg, FP pre, FN next) {
    c.id = 0x3210u + (c.warp >> 8);
    pre();
    conv_load<0, 0, 9>(c, q);
    conv_frag<0, 0, 1>(c, q, a, 0.f);
    wg_fence(); wg_first<0>(acc, a, c.d0); GO();
    park(c.ps, Pk{{0u, 0u, 0u, 0u}});
    wg_wait0();
    conv_frag<0, 1, 2>(c, q, a, DEP);
    wg_fence(); conv_mma<0, 0, 1, 2>(acc, c, a); GO();
    fg(IC<0>());
    wg_wait0();
    conv_frag<0, 2, 3>(c, q, a, DEP);
    wg_fence(); conv_mma<0, 0, 2, 3>(acc, c, a); GO();
    conv_load<1, 0, 5>(c, r);
    wg_wait0();
    conv_frag<0, 3, 4>(c, q, a, DEP);
    wg_fence(); conv_mma<0, 0, 3, 4>(acc, c, a); GO();
    conv_load<1, 5, 9>(c, r);
    fg(IC<1>());
    wg_wait0();
    const Pk k = pk2(acc[0], acc[1]);
    conv_rename<2>(acc);
    conv_frag<1, 0, 2>(c, r, a, k);
    wg_fence(); conv_mma<1, 2, 0, 2>(acc, c, a); GO();
    park(SLOT(0), k);
    next(IC<0>());
    fg(IC<2>());
    wg_wait0();
    conv_frag<1, 2, 4>(c, r, a, DEP);
    wg_fence(); conv_mma<1, 2, 2, 4>(acc, c, a); GO();
    next(IC<1>());
    fg(IC<3>());
    wg_wait0();
}
template <class FG, class FP>
__device__ __forceinline__ void conv_run(Conv& c, uint32_t pl, unsigned char* gy, FG fg, FP pre) {
    float acc[16][4];
    uint32_t q[9], r[9], a[32];
    uint2 f[4];
    const int bid = 1 + (c.warp >> 2);
    conv_head(c, acc, q, r, a, fg, pre, [&](auto i) { if (decltype(i)::value == 0) conv_selectors4(c); else conv_load<2, 0, 9>(c, q); });
    Pk k = pk2(acc[2], acc[3]);
    conv_rename<4>(acc);
    conv_frag<2, 0, 4>(c, q, a, k);
    wg_fence(); conv_mma<2, 4, 0, 4>(acc, c, a); GO();
    park(SLOT(2), k);
    conv_load<3, 0, 9>(c, q);
    flush_setup(c);
    bar_sync(bid, 128);
    fg(IC<4>());
    wg_wait0();
    conv_rename<6>(acc);
    flush_load_first<0>(c, pl, f, DEP);
    conv_frag<3, 0, 4>(c, q, a, FDEP);
    wg_fence(); conv_mma<3, 6, 0, 4>(acc, c, a); GO();
    park(SLOT(4), pk2(acc[4], acc[5]));
    conv_load<4, 0, 9>(c, q);
    conv_selectors8(c);
    conv_flush<0, 0>(c, f, gy, 0u);
    fg(IC<5>());
    wg_wait0();
    conv_rename<8>(acc);
    conv_frag<4, 0, 4>(c, q, a, DEP);
    wg_fence(); conv_mma<4, 8, 0, 4>(acc, c, a); GO();
    k = pk2(acc[6], acc[7]);
    park(SLOT(6), k); park(c.ps, k);
    conv_load<5, 0, 9>(c, q);
    bar_sync(bid, 128);
    fg(IC<6>());
    wg_wait0();
    conv_rename<10>(acc);
    flush_load_first<1>(c, pl, f, DEP);
    conv_frag<5, 0, 4>(c, q, a, FDEP);
    wg_fence(); conv_mma<5, 10, 0, 4>(acc, c, a); GO();
    park(SLOT(8), pk2(acc[8], acc[9]));
    conv_load<6, 0, 9>(c, q); conv_load<7, 0, 9>(c, r);
    conv_flush<1, 0>(c, f, gy, 0u);
    fg(IC<7>());
    wg_wait0();
    conv_rename<12>(acc);
    conv_frag<6, 0, 4>(c, q, a, DEP); conv_frag<7, 0, 4>(c, r, a + 16, DEP);
    wg_fence(); conv_mma<6, 12, 0, 4>(acc, c, a); conv_mma<7, 12, 0, 4>(acc, c, a + 16); GO();
    park(SLOT(10), pk2(acc[10], acc[11]));
    bar_sync(bid, 128);
    flush_load<2>(c, pl, f);
    conv_flush<2, 0>(c, f, gy, 0u);
    fg(IC<8>());
    if (c.id == 0) TRAP();
    wg_wait0();
    park(SLOT(12), pk2(acc[12], acc[13])); park(SLOT(14), pk2(acc[14], acc[15]));
    bar_sync(bid, 128);
    flush_load<3>(c, pl, f);
    conv_flush<3, 0>(c, f, gy, 0u);
}
template <class FG>
__device__ __forceinline__ void conv_outer(Conv& c, uint32_t pl, unsigned char* gy, uint32_t rx, FG fg) {
    float acc[16][4];
    uint32_t q[9], r[9], a[32];
    uint2 f[4], f2[4];
    const int bid = 1 + (c.warp >> 2);
    conv_head(c, acc, q, r, a, [&](auto gi) { if (decltype(gi)::value == 2) fg(IC<2, true>()); }, [&]() {}, [&](auto i) { if (decltype(i)::value == 0) conv_selectors8(c); else conv_load<6, 0, 9>(c, q); });
    park(SLOT(2), pk2(acc[2], acc[3])); park(SLOT(4), pk2(acc[4], acc[5]));
    const Pk k = pk2(acc[6], acc[7]);
    park(SLOT(6), k);
    conv_load<7, 0, 9>(c, r);
    conv_rename<12>(acc);
    conv_frag<6, 0, 4>(c, q, a, __uint_as_float(k.w[3])); conv_frag<7, 0, 4>(c, r, a + 16, __uint_as_float(k.w[3]));
    wg_fence(); conv_mma<6, 12, 0, 4>(acc, c, a); conv_mma<7, 12, 0, 4>(acc, c, a + 16); GO();
    flush_setup(c);
    bar_sync(bid, 128);
    flush_load<0>(c, pl, f); flush_load<1>(c, pl, f2);
    conv_flush<1, 1>(c, f2, gy, rx);
    conv_flush<0, 1>(c, f, gy, rx);
    wg_wait0();
    bar_sync(bid, 128);
    park(c.ps, k); park(SLOT(8), pk2(acc[8], acc[9])); park(SLOT(10), pk2(acc[10], acc[11]));
    park(SLOT(12), pk2(acc[12], acc[13])); park(SLOT(14), pk2(acc[14], acc[15]));
    bar_sync(bid, 128);
    flush_load<2>(c, pl, f); flush_load<3>(c, pl, f2);
    conv_flush<2, 1>(c, f, gy, rx);
    conv_flush<3, 1>(c, f2, gy, rx);
}
template <class FG>
__device__ __forceinline__ void conv_inner(Conv& c, uint32_t pl, unsigned char* gy, uint32_t rx, FG fg) {
    float acc[16][4];
    uint32_t q[9], a[16];
    uint2 f[4], f2[4];
    const int bid = 1 + (c.warp >> 2);
    c.id = 0x3210u + (c.warp >> 8);
    conv_selectors4(c);
    conv_load<2, 0, 9>(c, q);
    conv_frag<2, 0, 4>(c, q, a, 0.f);
    wg_fence(); wg_first<4>(acc, a, c.d0); conv_mma<2, 4, 1, 4>(acc, c, a + 4); GO();
    conv_load<3, 0, 9>(c, q);
    park(SLOT(2), Pk{{0u, 0u, 0u, 0u}});
    fg(IC<2, true>());
    wg_wait0();
    conv_rename<6>(acc);
    conv_frag<3, 0, 4>(c, q, a, DEP);
    wg_fence(); conv_mma<3, 6, 0, 4>(acc, c, a); GO();
    park(SLOT(4), pk2(acc[4], acc[5]));
    conv_load<4, 0, 9>(c, q);
    conv_selectors8(c);
    wg_wait0();
    conv_rename<8>(acc);
    conv_frag<4, 0, 4>(c, q, a, DEP);
    wg_fence(); conv_mma<4, 8, 0, 4>(acc, c, a); GO();
    const Pk k = pk2(acc[6], acc[7]);
    park(SLOT(6), k); park(c.ps, k);
    conv_load<5, 0, 9>(c, q);
    flush_setup(c);
    wg_wait0();
    conv_rename<10>(acc);
    conv_frag<5, 0, 4>(c, q, a, DEP);
    wg_fence(); conv_mma<5, 10, 0, 4>(acc, c, a); GO();
    park(SLOT(8), pk2(acc[8], acc[9]));
    bar_sync(bid, 128);
    flush_load<1>(c, pl, f);
    mbar_wait(rx);
    conv_flush<1, 2>(c, f, gy, rx);
    wg_wait0();
    bar_sync(bid, 128);
    park(SLOT(10), pk2(acc[10], acc[11])); park(SLOT(12), pk2(acc[12], acc[13])); park(SLOT(14), pk2(acc[14], acc[15]));
    bar_sync(bid, 128);
    flush_load<3>(c, pl, f); flush_load<2>(c, pl, f2);
    mbar_wait(rx + 8);
    conv_flush<3, 2>(c, f, gy, rx);
    conv_flush<2, 2>(c, f2, gy, rx);
}
#undef SLOT
#undef GO
#undef DEP
template <int U0, int U1>
__device__ __forceinline__ void weight_units(uint32_t sb, const CUtensorMap* tg, const CUtensorMap* tu, const CUtensorMap* td, bool w) {
    if (U1 > U0 && w && elect_one()) {
#pragma unroll
        for (int i = U0; i < U1; i++) {
            if (i < 12) tma_2d(sb + SM_WG + i * 6912, i < 6 ? tg : tu, 72 * (blockIdx.x >> 1), 288 * (blockIdx.x & 1) + (i % 6) * 48, sb + SM_MISC + 328);
            else tma_2d(sb + SM_WD + (i - 12) * 4736, td, 144 * (blockIdx.x & 1), 72 * (blockIdx.x >> 1) + 8 * (i - 12), sb + SM_MISC + 336);
        }
    }
}
#define WS 1111121111122004100
__device__ constexpr int wsched(int i) {
    unsigned long long v = WS;
    int n = 0;
    for (int k = 19; k >= 1; k--) { if (k < i) n += (int)(v % 10); v /= 10; }
    return n;
}
static_assert(wsched(20) == 21 && wsched(6) <= 7 && wsched(11) <= 12 && wsched(13) <= 14 && wsched(16) <= 17 && wsched(16) == wsched(15) && wsched(19) == 21, "");
#define WANY(i) (wsched((i) + 1) > wsched(i))
#define WPOINT(i, w) do { weight_units<wsched(i), wsched(i + 1)>(sb, &tm_g, &tm_u, &tm_d, w); } while (0)

__global__ void __launch_bounds__(NTHR, 1) __cluster_dims__(2, 1, 1)
fused_kernel(const Params p, const __grid_constant__ CUtensorMap tm_g, const __grid_constant__ CUtensorMap tm_u, const __grid_constant__ CUtensorMap tm_d, const __grid_constant__ CUtensorMap tm_x) {
    extern __shared__ __align__(1024) unsigned char smem[];
    const uint32_t sb = smem_u32(smem);
    const int tid = threadIdx.x, warp = __shfl_sync(0xffffffffu, tid >> 5, 0), lane = tid & 31;
    const int b = blockIdx.x, P = b >> 1, odd = b & 1;
    const int g = lane >> 2, t = lane & 3;
    const int wg = warp >> 2, t128 = tid & 127;
    const uint32_t s_stat = sb + SM_MISC;
    const uint32_t s_key = sb + SM_MISC + 128;
    const uint32_t s_rank = sb + SM_MISC + 256;
    const uint32_t s_k16 = sb + SM_MISC + 192;
    const uint32_t s_cnt = sb + SM_MISC + 320;
    const uint32_t bar_w = sb + SM_MISC + 328, bar_d = bar_w + 8, bar_g = bar_w + 16, bar_x = bar_w + 24, bar_t = bar_w + 32, bar_s = bar_w + 40, bar_v = bar_w + 48, bar_h = sb + SM_MISC + 160;
    STAMP(0);

    if (warp == 19) {
        if (lane == 0) {
            mbar_init(bar_w, 1); mbar_init(bar_d, 1); mbar_init(bar_g, 1); mbar_init(sb + SM_RX, 1); mbar_init(sb + SM_RX + 8, 1);
            mbar_init(bar_x, 1); mbar_init(bar_t, 1); mbar_init(bar_s, 1); mbar_init(bar_v, 2); mbar_init(bar_h, 1); mbar_init(bar_h + 8, 1); mbar_init(bar_h + 16, 1); mbar_init(bar_h + 24, 1); mbar_expect(bar_x, 32768);
            asm volatile("fence.mbarrier_init.release.cluster;\n" ::: "memory");
            mbar_expect(bar_w, 82944); mbar_expect(bar_d, 72 * WD_PITCH); mbar_expect(bar_g, 4608); mbar_expect(bar_t, 16 * 1152); mbar_expect(bar_v, 2 * 1152); mbar_expect(sb + SM_RX, 1024); mbar_expect(sb + SM_RX + 8, 2048);
        }
        __syncwarp();
    }
    if (wg < 3) { sts128(sb + SM_Z2 + tid * 16, 0u, 0u, 0u, 0u); sts128(sb + SM_Z2 + 6144 + tid * 16, 0u, 0u, 0u, 0u); fence_async(); }
    const int ch = wg < 4 ? 4 * b + wg : 512 + P;
    const bf16 *q0 = p.lar + ch * NST, *q1 = p.aim + ch * NST, *q2 = p.cre + ch * NST, *q3 = p.cim + ch * NST;
    asm volatile("" : "+l"(q0), "+l"(q1), "+l"(q2), "+l"(q3));
    const uint32_t ldt = ldo16(p.ldt + ch), pl = ldo16(q0 + t128), pa2 = ldo16(q1 + t128);
    const uint32_t pc = ldo16(q2 + t128), pi = ldo16(q3 + t128);
    const uint2 call_re = ldo64(q2 + 4 * lane), call_im = ldo64(q3 + 4 * lane);
    const uint32_t epl = ld_poll32(p.s->hint + (b & 7) * 32 + 1);
    bar_sync(0, NWRK);
    if (wg == 4) {
        const int o = (4 * (warp & 3) + (g >> 1)) * 1152 + (g & 1) * 576 + t * 16;
#pragma unroll
        for (int c = 0; c < 9; c++)
            asm volatile("cp.async.cg.shared.global [%0], [%1], 16;\n" ::"r"(sb + SM_XT + o + c * 64), "l"(reinterpret_cast<const char*>(p.x) + b * 18432 + o + c * 64) : "memory");
        asm volatile("cp.async.commit_group;\n" ::: "memory");
    }
    asm volatile("barrier.cluster.arrive.relaxed.aligned;\n" ::: "memory");
    if (warp == 18) {
        if (lane == 0) {
            bulk_s2g(reinterpret_cast<unsigned char*>(p.s->y) + 96 * 18432 + b * 4608, sb + SM_Z2, 4608);
        }
        bar_arrive(12, 64);
    }
    if (warp == 19) {
        bar_sync(12, 64);
        asm volatile("barrier.cluster.wait.aligned;\n" ::: "memory");
        if (elect_one()) tma_4d_mc(sb + SM_XC + odd * 16384, &tm_x, 8 * P, 2 * odd, bar_x);
        __syncwarp();
    }
    const uint32_t kw = sb + SM_KW + wg * KW_B;
    const uint32_t tb = table_buf(sb, warp), t5 = sb + SM_WD + warp * 512;
    if (wg == 4) {
        if (!(g & 1) && t == (g >> 1)) *reinterpret_cast<volatile uint32_t*>(p.s->stat + 16 * b + 4 * (warp & 3) + t) = 0u;
        if (warp < 18) {
            unsigned char* const ud = reinterpret_cast<unsigned char*>(p.s->uT) + (size_t)(8 * (warp & 1) + 2 * (g >> 1)) * 16384 + b * 128 + (g & 1) * 32 + t * 8;
#pragma unroll
            for (int k = 0; k < 4; k++) *reinterpret_cast<volatile unsigned long long*>(ud + (k >> 1) * 16384 + (k & 1) * 64) = 0ull;
        }
        if (warp == 17) conv_constants(sb + SM_LC, lane);
    }
    if (t128 < 2 * UPAD) sts128(sb + SM_U + wg * USLOT_B + (t128 & 1) * ULO_B + (t128 >> 1) * 16, 0u, 0u, 0u, 0u);
    if (t128 >= 124) sts128(kw + (t128 & 1) * 16 + (t128 & 2) * (KW_PL / 2), 0u, 0u, 0u, 0u);
    uint32_t co, cn, cd;
    combine_setup(sb, warp, lane, kw, co, cn, cd);
    const uint4* usrc = wg < 4 ? reinterpret_cast<const uint4*>(p.s->stat) + tid
                               : reinterpret_cast<const uint4*>(p.s->uT) + (P >> 2) * 1024 + (t128 >> 1) * 8 + (P & 3) * 2 + (t128 & 1);
    uint32_t zero;
    {
        uint32_t uo = (uint32_t)(reinterpret_cast<const char*>(usrc) - reinterpret_cast<const char*>(p.s)), pk = (cn - co + 1024) | ((cd - kw) << 16);
        asm volatile("st.volatile.shared.v4.u32 [%4], {0, %1, %2, %3};\nld.volatile.shared.v4.u32 {%0, %1, %2, %3}, [%4];\n" : "=r"(zero), "+r"(co), "+r"(pk), "+r"(uo) : "r"(tb + lane * 16) : "memory");
        cn = co + (pk & 0xffffu) - 1024; cd = kw + (pk >> 16);
        usrc = reinterpret_cast<const uint4*>(reinterpret_cast<const char*>(p.s) + uo);
    }
    const float dt = exp_bf(__uint_as_float(__byte_perm(ldt, zero, 0x1044)));
    const uint32_t ep = __reduce_or_sync(0xffffffffu, epl | zero);
    auto stats = [&]() {
        const int wq = warp & 3;
        const uint32_t xa = sb + SM_XT + (4 * wq + (g >> 1)) * 1152 + (g & 1) * 576 + t * 16;
        const bool own = !(g & 1) && t == (g >> 1);
        float d[4][4] = {};
        asm volatile("cp.async.wait_group 0;\n" ::: "memory");
        STAMP(26);
        uint4 v[9];
#pragma unroll
        for (int c = 0; c < 9; c++) v[c] = lds128(xa + c * 64);
#pragma unroll
        for (int c = 0; c < 9; c++) {
            mma_bf16(d[2 * (c & 1)], v[c].x, 0x3f803f80u, v[c].y, 0x3f803f80u, v[c].x, v[c].y);
            mma_bf16(d[2 * (c & 1) + 1], v[c].z, 0x3f803f80u, v[c].w, 0x3f803f80u, v[c].z, v[c].w);
        }
        STAMP(27);
        float sm = (g & 1) ? (d[0][3] + d[1][3]) + (d[2][3] + d[3][3]) : (d[0][2] + d[1][2]) + (d[2][2] + d[3][2]);
        float sq = (g & 1) ? (d[0][1] + d[1][1]) + (d[2][1] + d[3][1]) : (d[0][0] + d[1][0]) + (d[2][0] + d[3][0]);
        sm += __shfl_xor_sync(0xffffffffu, sm, 4); sq += __shfl_xor_sync(0xffffffffu, sq, 4);
        if (lane == 0) mbar_arrive(bar_h + 8 * wq);
        float mb, sd;
        ln_stats(sm, sq, mb, sd);
        if (own) p.s->stat[16 * b + 4 * wq + t] = (__float_as_uint(mb) >> 16) | (__float_as_uint(sd) & 0x7fff0000u) | (ep << 31);
        STAMPX(22);
        if (own) stat_store(s_stat + (2 * wq + (t & 1) + 8 * (t >> 1)) * 8, mb, rcp_approx(sd), 0u);
        if (wq == 2) asm volatile("cp.async.bulk.wait_group 0;\n" ::: "memory");
        bar_sync(5, 128);
        STAMP(28);
        if (wq == 2) {
            if (lane < 8) p.s->key3[8 * b + lane] = ep & 1u;
            if (lane == 0) {
                uint32_t now;
                asm volatile("mov.u32 %0, %%clock;" : "=r"(now));
                sts64(s_cnt, now, ep);
                mbar_arrive(bar_s);
                bulk_g2s(sb + SM_XT + 16 * 1152, p.dsk, 1152, bar_v);
                bulk_g2s(sb + SM_XT + 17 * 1152, p.wr, 1152, bar_v);
            }
            __syncwarp();
        }
        WPOINT(1, wq == 3);
        if (wq < 2) {
            unsigned char* const ud = reinterpret_cast<unsigned char*>(p.s->uT) + (size_t)(8 * wq + 2 * (g >> 1)) * 16384 + b * 128 + (g & 1) * 32 + t * 8;
            const uint32_t utag = (ep % 7u + 1u) * 0x10001u;
            uint32_t U[2][4];
#pragma unroll
            for (int hf = 0; hf < 2; hf++) {
                const uint2 st = lds64(s_stat + (g + 8 * hf) * 8);
                const uint4 xu = lds128(sb + SM_XT + (TOK(g) + 2 * hf) * 1152 + warp * 64 + t * 16);
                const uint32_t X[4] = {xu.x, xu.y, xu.z, xu.w};
#pragma unroll
                for (int k = 0; k < 4; k++) {
                    const uint32_t u = ln_apply(X[k], STAT_M(st), STAT_H(st), STAT_L(st));
                    U[hf][k] = movm((pack_f16(bf_lo(u), bf_hi(u)) & 0xfff8fff8u) | utag);
                }
            }
#pragma unroll
            for (int k = 0; k < 4; k++) stg64(ud + (k >> 1) * 16384 + (k & 1) * 64, U[0][k], U[1][k]);
        }
    };
    STAMP(1);
    if (wg < 4) { STAMPX(16); }
    KGen kg;
    kgen_setup(kg, __uint_as_float(__byte_perm(pl, zero, 0x1044)), __uint_as_float(__byte_perm(pa2, zero, 0x1044)), dt);
    kgen_rows(kg, tb, lane);
    STAMP(2);
    const int E = min(max(c_exponent(call_re, call_im, dt) - 243, -120), 120);
    kgen_chain(kg, pc, pi, dt * __uint_as_float((uint32_t)(128 - E) << 23));
    STAMP(3);
    kgen_cols(kg, tb, t5, lane);
    STAMP(4);
    if (wg == 4) stats();
    if (warp != 19) asm volatile("barrier.cluster.wait.aligned;\n" ::: "memory");
    if (wg < 4) { STAMPX(17); }
    if (wg < 4) mbar_wait(bar_h + 8 * (warp & 3));
    if (wg < 4) { STAMPX(19); }
    kgen_mma(kg, tb, t5, lane);
    if (wg < 4) { STAMPX(20); }
    STAMP(5);
    uint4 uv0, uv1;
    auto first_poll = [&](uint32_t dly) {
        mbar_wait(bar_s);
        const uint32_t t0 = lds32(s_cnt);
        uint32_t now;
        do { asm volatile("mov.u32 %0, %%clock;" : "=r"(now) :: "memory"); } while (now - t0 < dly);
        uv0 = ld_poll(usrc);
    };
    WPOINT(2, warp == 19);
    bar_sync(1 + wg, 128);
    if (wg < 4) { STAMPX(21); }
    kgen_combine(warp & 3, lane, co, cn, cd);
    STAMP(6);
    if (wg < 4) { STAMPX(18); }
    WPOINT(3, warp == 19);
    if (wg < 4) first_poll(SDLY);
    {
        const int wq = warp & 3;
        Conv c;
        const uint32_t pln = sb + SM_PL + wg * PL_B;
        const int e = g - 2 * t + 7;
        c.kw = kw; c.wa = pin(kw + ((e >> 2) & 1) * KW_PL + (8 * wq + (e >> 3)) * 16 + (e & 3) * 4);
        c.ps = mov_v(pln + wq * PLW_B + ((lane >> 3) & 1) * PL_HALF + ((lane >> 4) * 8 + (lane & 7)) * 16); c.warp = warp;
        c.lc = sb + SM_LC; c.fs = (uint32_t)(127 + E) * 0x800080u; c.yp = (ep & 1u) * (NCTA * 18432u);
        c.d0 = ((uint64_t)(ULO_B >> 4) << 16) | ((uint64_t)(128 >> 4) << 32) | (uint64_t)(((sb + SM_U + wg * USLOT_B + UPAD * 16) & 0x3FFFF) >> 4);
        unsigned char* gy = reinterpret_cast<unsigned char*>(p.s->y) + ((size_t)(4 * wq) * DM + ch) * 64;
        auto hook = [&](auto gi) {
                     constexpr int G = decltype(gi)::value;
                     if (G == (wg_is4<decltype(gi)>() ? 2 : 5)) asm volatile("barrier.cluster.wait.aligned;\n" ::: "memory");
                     if (!wg_is4<decltype(gi)>() && (G == 0 || G == 2) && warp == HW && elect_one()) {
                         unsigned char* const sc = reinterpret_cast<unsigned char*>(p.s);
                         if (G == 0) {
                             if (b < 96) bulk_s2g_nc(sc + offsetof(Scratch, part) + b * 12288, sb + SM_Z2, 12288);
                             bulk_s2g(sc + offsetof(Scratch, rows) + (127 - b) * 4608, sb + SM_Z2, 4608);
                         }
                         if (G == 2) {
                             bulk_s2g_nc(sc + offsetof(Scratch, y) + (NCTA * 18432u - c.yp) + b * 13824, sb + SM_Z2, 6912);
                             bulk_s2g(sc + offsetof(Scratch, y) + (NCTA * 18432u - c.yp) + b * 13824 + 6912, sb + SM_Z2, 6912);
                         }
                     }
                     if (!wg_is4<decltype(gi)>()) WPOINT(6 + G, warp == (G >= 7 ? HW : 4 * (G % 3) + 1));
                     if (!wg_is4<decltype(gi)>() && G == 6 && warp == HW) {
                         asm volatile("cp.async.bulk.wait_group 0;\n" ::: "memory");
                         __syncwarp();
                         if (elect_one()) mbar_arrive(bar_v);
                     }
                 };
        if (wg < 4) {
            asm volatile("barrier.cluster.arrive.relaxed.aligned;\n" ::: "memory");
            conv_run(c, pln + wq * 128, gy, hook, [&]() {
                STAMPX(23);
                mbar_wait(bar_x);
                STAMP(9);
                STAMPX(24);
                uint2 xc[4];
                uint32_t xw[4][2];
#pragma unroll
                for (int j = 0; j < 4; j++) xc[j] = lds64(sb + SM_XC + wg * 8192 + j * 2048 + t128 * 16 + odd * 8);
#pragma unroll
                for (int i = 0; i < 8; i++) {
                    const int k = i >> 1, h = i & 1;
                    xw[k][h] = prmt_v(k < 2 ? xc[2 * h].x : xc[2 * h].y, k < 2 ? xc[2 * h + 1].x : xc[2 * h + 1].y, (k & 1) ? 0x7632 : 0x5410);
                }
                const uint32_t ub = mov_v(sb + SM_U + UPAD * 16 + ((tid >> 1) & 1) * ULO_B + (tid >> 2) * 16 + (tid & 1) * 8), tag = ep << 31;
                int it = 0;
                while (min(min((int)(uv0.x ^ tag), (int)(uv0.y ^ tag)), min((int)(uv0.z ^ tag), (int)(uv0.w ^ tag))) < 0x10000) {
                    if (++it > SPIN_LIMIT) TRAP();
                    uv0 = ld_poll(usrc);
                }
                STAMP(8);
                STAMPX(26);
                const float r0 = rcp_approx(fabsf(bf_hi(uv0.x))), r1 = rcp_approx(fabsf(bf_hi(uv0.y))), r2 = rcp_approx(fabsf(bf_hi(uv0.z))), r3 = rcp_approx(fabsf(bf_hi(uv0.w)));
                const uint32_t m[2] = {__byte_perm(uv0.x, uv0.y, 0x5410), __byte_perm(uv0.z, uv0.w, 0x5410)};
                const uint32_t rh[2] = {pack_bf16(r0, r1), pack_bf16(r2, r3)};
                const uint32_t rl[2] = {pack_bf16(r0 - bf_lo(rh[0]), r1 - bf_hi(rh[0])), pack_bf16(r2 - bf_lo(rh[1]), r3 - bf_hi(rh[1]))};
#pragma unroll
                for (int k = 0; k < 4; k++) {
                    const uint32_t u0 = ln_apply(xw[k][0], m[0], rh[0], rl[0]), u1 = ln_apply(xw[k][1], m[1], rh[1], rl[1]);
                    sts64(ub + k * USLOT_B, pack_f16(bf_lo(u0), bf_hi(u0)), pack_f16(bf_lo(u1), bf_hi(u1)));
                }
                STAMPX(29);
                fence_async();
                bar_sync(14, 512);
                STAMP(7);
            });
        } else {
            auto stage = [&]() {
                const uint32_t tag = (ep % 7u + 1u) * 0x10001u;
                int it = 0;
                WPOINT(4, warp == 19);
                first_poll(UDLY);
                uv1 = ld_poll(usrc + 512);
                WPOINT(5, warp == 19);
                while (true) {
                    uv0.x ^= tag; uv0.y ^= tag; uv0.z ^= tag; uv0.w ^= tag; uv1.x ^= tag; uv1.y ^= tag; uv1.z ^= tag; uv1.w ^= tag;
                    if ((((uv0.x | uv0.y | uv0.z) | (uv0.w | uv1.x | uv1.y) | (uv1.z | uv1.w)) & 0x70007u) == 0) break;
                    if (++it > SPIN_LIMIT) TRAP();
                    uv0 = ld_poll(usrc); uv1 = ld_poll(usrc + 512);
                }
                STAMP(8);
                const uint32_t ub = sb + SM_U + UPAD * 16 + 4 * USLOT_B + (t128 & 1) * ULO_B + (t128 >> 1) * 16;
                sts128(ub, uv0.x, uv0.y, uv0.z, uv0.w);
                sts128(ub + 1024, uv1.x, uv1.y, uv1.z, uv1.w);
                fence_async();
                asm volatile("barrier.cluster.arrive.relaxed.aligned;\n" ::: "memory");
                bar_sync(5, 128);
                STAMP(7);
            };
            stage();
            if (odd) conv_inner(c, pln + wq * 128, gy, sb + SM_RX, hook);
            else conv_outer(c, pln + wq * 128, gy, sb + SM_RX, hook);
        }
        STAMP(10);
    }
    {
    const int lane = lane_v(), tid = 32 * warp + lane, g = lane >> 2, t = lane & 3;
    const uint32_t par = ~ep & 1u;
    bar_sync(0, NWRK);
    STAMP(11);
    uint32_t H[2][4] = {}, U2[2][4] = {};
    auto publish = [&](bool hi, int slot) {
        uint4* rowp = reinterpret_cast<uint4*>(p.s->rows) + slot * 144 + warp * 4 + t;
        stg128(rowp, nzw(hi ? U2[1][0] : U2[0][0]), nzw(hi ? U2[1][1] : U2[0][1]), nzw(hi ? U2[1][2] : U2[0][2]), nzw(hi ? U2[1][3] : U2[0][3]));
        stg128(rowp + 72, nzw(hi ? H[1][0] : H[0][0]), nzw(hi ? H[1][1] : H[0][1]), nzw(hi ? H[1][2] : H[0][2]), nzw(hi ? H[1][3] : H[0][3]));
    };
#define KTOK(k) (int)(((~(k) >> 5) & 0x7f0u) | (((k) >> 1) & 15u))
#define KLATE(k) (((k) & 0x1e0u) < 0xe0u)
#define KSLOT(k, s) (KLATE(k) ? 2 * NCTA + (s) : (int)(((k) >> 8) & 0xffu))
    const uint4* const rsrc = reinterpret_cast<const uint4*>(p.s->rows) + 36 * odd;
    auto gather = [&](uint32_t mine) {
        int it = 0;
        uint32_t mn;
        do {
            mn = 1;
#pragma unroll 1
            for (int r = 0; r < 9; r++) {
                const uint32_t k = __shfl_sync(0xffffffffu, mine, r < 8 ? 4 * r : lane);
                const int row = r < 8 ? r : g, c = r < 8 ? lane : 32 + t;
                asm volatile("cp.async.cg.shared.global [%0], [%1], 16;\n" ::"r"(sb + SM_XS + row * XS_PITCH + c * 16), "l"(rsrc + KSLOT(k, row) * 144 + c) : "memory");
            }
            asm volatile("cp.async.wait_all;\n" ::: "memory");
#pragma unroll 1
            for (int r = 0; r < 9; r++) mn = min(mn, min4(lds128(sb + SM_XS + (r < 8 ? r * XS_PITCH + lane * 16 : g * XS_PITCH + (32 + t) * 16))));
            if (++it > SPIN_LIMIT) TRAP();
        } while (__any_sync(0xffffffffu, mn == 0));
    };
    auto late_rows = [&](auto role) {
        const uint32_t kk = lds32(s_key + (lane & 7) * 4), ep = lds32(s_cnt + 4);
        const bool own = KLATE(kk) && (KTOK(kk) >> 4) == b;
        uint32_t todo = __ballot_sync(0xffffffffu, own) & 0xffu;
        if (decltype(role)::value == 0 && todo) {
#pragma unroll
            for (int hf = 0; hf < 2; hf++) {
                const uint4 h = lds128(sb + SM_U + hf * 9216 + tid * 16);
                const uint2 st = lds64(s_stat + (g + 8 * hf) * 8);
                H[hf][0] = h.x; H[hf][1] = h.y; H[hf][2] = h.z; H[hf][3] = h.w;
#pragma unroll
                for (int k = 0; k < 4; k++) U2[hf][k] = ln_apply(H[hf][k], STAT_M(st), STAT_H(st), STAT_L(st));
            }
#pragma unroll 1
            while (todo) {
                const int s = __ffs(todo) - 1, tk = KTOK(__shfl_sync(0xffffffffu, kk, s));
                todo &= todo - 1;
                if ((tk & 13) == TOK(g)) publish(tk & 2, 2 * NCTA + s);
            }
            __threadfence();
        }
        bar_sync(0, NWRK);
        if (decltype(role)::value == 1) {
            if (lane < NSEL && own) *reinterpret_cast<volatile unsigned*>(p.s->flag + lane) = ep + 1u;
            int it = 0;
            while (__any_sync(0xffffffffu, KLATE(kk) && ld_acquire32(p.s->flag + (lane & 7)) != ep + 1u)) { if (++it > SPIN_LIMIT) TRAP(); }
            gather(__shfl_sync(0xffffffffu, kk, g));
        }
        bar_sync(0, NWRK);
    };
    if (warp < 18) {
        const unsigned char* ys = reinterpret_cast<const unsigned char*>(p.s->y) + (b < 96 ? (par ^ 1u) * (NCTA * 18432u) : 0u) +
                                  ((P * DM + 32 * warp + 8 * (g >> 1) + (g & 1)) * 64 + odd * 32 + t * 8);
        uint2 yv[4];
        const bool early = b < 64 && warp < 16;
        if (early) {
#pragma unroll
            for (int k = 0; k < 4; k++) yv[k] = ld_poll64(ys + k * 128);
        }
        mbar_wait(bar_v);
        const uint32_t xa = sb + SM_XT + warp * 64 + t * 16;
        const uint4 x0 = lds128(xa + TOK(g) * 1152), x1 = lds128(xa + (TOK(g) + 2) * 1152), dk = lds128(xa + 16 * 1152);
        uint4 wr = make_uint4(0u, 0u, 0u, 0u);
        if (g == 0) wr = lds128(xa + 17 * 1152);
        const uint32_t Z[2][4] = {{x0.x, x0.y, x0.z, x0.w}, {x1.x, x1.y, x1.z, x1.w}}, D4[4] = {dk.x, dk.y, dk.z, dk.w};
#pragma unroll
        for (int hf = 0; hf < 2; hf++) {
            const uint2 st = lds64(s_stat + (g + 8 * hf) * 8);
#pragma unroll
            for (int k = 0; k < 4; k++) U2[hf][k] = hmul2_bf(ln_apply(Z[hf][k], STAT_M(st), STAT_H(st), STAT_L(st)), D4[k]);
        }
        const uint32_t la = pin(sb + SM_LNP + (g * 20 + warp) * 4 + (U2[0][3] & U2[1][3] & (warp >> 8)));
        int it = 0;
        float d[2][4];
        uint32_t mn;
        do {
            if (!early || it) {
#pragma unroll
                for (int k = 0; k < 4; k++) yv[k] = ld_poll64(ys + k * 128);
            }
            if (++it > SPIN_LIMIT) TRAP();
            mn = min(min(min(yv[0].x, yv[0].y), min(yv[1].x, yv[1].y)), min(min(yv[2].x, yv[2].y), min(yv[3].x, yv[3].y)));
#pragma unroll
            for (int k = 0; k < 4; k++) {
                H[0][k] = hadd2_bf(Z[0][k], hadd2_bf(movm(yv[k].x), U2[0][k]));
                H[1][k] = hadd2_bf(Z[1][k], hadd2_bf(movm(yv[k].y), U2[1][k]));
            }
            ln_partial(H, d);
        } while (__any_sync(0xffffffffu, mn == 0));
        STAMP(12);
        if (t == (g >> 1)) {
            stsf(la, (g & 1) ? d[0][3] : d[0][2]); stsf(la + 8 * 80, (g & 1) ? d[1][3] : d[1][2]);
            stsf(la + 16 * 80, (g & 1) ? d[0][1] : d[0][0]); stsf(la + 24 * 80, (g & 1) ? d[1][1] : d[1][0]);
        }
        bar_arrive(6, NWRK);
        STAMP(13);
        bar_sync(7, 608);
        STAMP(14);
#pragma unroll
        for (int hf = 0; hf < 2; hf++) {
            const uint2 st = lds64(s_stat + (g + 8 * hf) * 8);
#pragma unroll
            for (int k = 0; k < 4; k++) U2[hf][k] = ln_apply(H[hf][k], STAT_M(st), STAT_H(st), STAT_L(st));
        }
        {
            float cs[4] = {0.f, 0.f, 0.f, 0.f};
            mma_bf16(cs, U2[0][0], U2[1][0], U2[0][1], U2[1][1], wr.x, wr.y);
            mma_bf16(cs, U2[0][2], U2[1][2], U2[0][3], U2[1][3], wr.z, wr.w);
            if (t == 0) { stsf(la + 32 * 80, cs[0]); stsf(la + 40 * 80, cs[2]); }
            bar_arrive(8, 608);
        }
        bar_sync(9, 608);
        {
            const uint2 best = lds64(s_rank);
            uint32_t todo = ((best.x & 26u) == 2 * TOK(g) ? 2u : 0u) | ((best.y & 26u) == 2 * TOK(g) ? 1u : 0u);
#pragma unroll 1
            while (todo) { publish((todo & 2u ? best.x : best.y) & 4u, 254 - 2 * b + (todo >> 1)); todo &= todo >> 1; }
        }
#pragma unroll
        for (int hf = 0; hf < 2; hf++) {
            sts128(sb + SM_OUT + (TOK(g) + 2 * hf) * (DM * 2) + warp * 64 + t * 16,
                   hadd2_bf(H[hf][0], U2[hf][0]), hadd2_bf(H[hf][1], U2[hf][1]), hadd2_bf(H[hf][2], U2[hf][2]), hadd2_bf(H[hf][3], U2[hf][3]));
            sts128(sb + SM_U + hf * 9216 + tid * 16, H[hf][0], H[hf][1], H[hf][2], H[hf][3]);
        }
        STAMP(15);
        const int mi = lane >> 3, rr = lane & 7;
        const bool gate = warp < 12 && (warp & 3) != 2;
        const int fj = gate ? 3 * (warp >> 2) + min(warp & 3, 2) : (warp < 12 ? warp >> 2 : warp - 9);
        if (gate) {
            uint32_t W[18][4];
            mbar_wait(bar_w);
            const uint32_t aad = sb + SM_WG + (mi & 1) * SM_WU + (rr + 8 * (mi >> 1)) * W_PITCH + fj * 16;
#pragma unroll
            for (int k = 0; k < 18; k++) ldsm_x4_t(W[k][0], W[k][1], W[k][2], W[k][3], aad + k * 16 * W_PITCH);
            const uint32_t bad = pin(sb + SM_XS + rr * XS_PITCH + mi * 16);
            fence_async();
            STAMP2(17);
            if (bar_or(11, NWRK, false)) {
                late_rows(IC<0>());
#pragma unroll
                for (int k = 0; k < 18; k++) ldsm_x4_t(W[k][0], W[k][1], W[k][2], W[k][3], aad + k * 16 * W_PITCH);
            }
            STAMP2(19);
            float c4[2][4] = {};
#pragma unroll
            for (int k = 0; k < 18; k += 2) {
                uint32_t b0, b1, b2, b3;
                ldsm_x4(b0, b1, b2, b3, bad + k * 32);
                mma_bf16(c4[0], W[k][0], W[k][1], W[k][2], W[k][3], b0, b1);
                mma_bf16(c4[1], W[k + 1][0], W[k + 1][1], W[k + 1][2], W[k + 1][3], b2, b3);
            }
            const uint32_t ex = sb + SM_EX + (32 * fj + lane) * 16;
            const float e0 = c4[0][0] + c4[1][0], e1 = c4[0][1] + c4[1][1], e2 = c4[0][2] + c4[1][2], e3 = c4[0][3] + c4[1][3];
            asm volatile("st.async.shared::cluster.mbarrier::complete_tx::bytes.v4.f32 [%0], {%1,%2,%3,%4}, [%5];\n"
                         ::"r"(ex ^ 0x1000000u), "f"(e0), "f"(e1), "f"(e2), "f"(e3), "r"(bar_g ^ 0x1000000u) : "memory");
            STAMP2(20);
            mbar_wait(bar_g);
            const uint4 o = lds128(ex);
            const uint32_t G = pack_bf16(e0 + __uint_as_float(o.x), e1 + __uint_as_float(o.y)), U = pack_bf16(e2 + __uint_as_float(o.z), e3 + __uint_as_float(o.w));
            sts32(sb + SM_GU + (32 * fj + lane) * 4, hmul2_bf(pack_bf16(bf_lo(G) * sigmoid_f(bf_lo(G)), bf_hi(G) * sigmoid_f(bf_hi(G))), U));
            bar_arrive(13, NWRK);
        } else {
            uint32_t W[2][18];
            auto load_wd = [&]() {
                mbar_wait(bar_d);
                const uint32_t base = sb + SM_WD + (4 * fj + (mi & 1)) * 16 + rr * WD_PITCH;
#pragma unroll
                for (int j = 0; j < 2; j++) {
#pragma unroll
                    for (int k = 0; k < 4; k++) ldsm_x4_t(W[j][4 * k], W[j][4 * k + 1], W[j][4 * k + 2], W[j][4 * k + 3], base + j * 32 + (k * 16 + 8 * (mi >> 1)) * WD_PITCH);
                    ldsm_x2_t(W[j][16], W[j][17], base + j * 32 + 64 * WD_PITCH);
                }
            };
            const uint32_t po = pin((((8 * (18 * odd + 2 * fj) + g) * 64 + P) * 16 + t * 4) * 4);
            fence_async();
            STAMP2(17);
            if (bar_or(11, NWRK, false)) late_rows(IC<0>());
            delay(DDLY); load_wd();
            bar_sync(13, NWRK);
            STAMP2(21);
            uint32_t gb[9];
            ldsm_x4_t(gb[0], gb[1], gb[2], gb[3], sb + SM_GU + lane * 16);
            ldsm_x4_t(gb[4], gb[5], gb[6], gb[7], sb + SM_GU + 512 + lane * 16);
            ldsm_x1_t(gb[8], sb + SM_GU + 1024 + lane * 16);
            float c4[2][4] = {}, d4[2][4] = {};
#pragma unroll
            for (int k = 0; k < 4; k += 2)
#pragma unroll
                for (int j = 0; j < 2; j++) {
                    mma_bf16(c4[j], W[j][4 * k], W[j][4 * k + 1], W[j][4 * k + 2], W[j][4 * k + 3], gb[2 * k], gb[2 * k + 1]);
                    mma_bf16(d4[j], W[j][4 * k + 4], W[j][4 * k + 5], W[j][4 * k + 6], W[j][4 * k + 7], gb[2 * k + 2], gb[2 * k + 3]);
                }
#pragma unroll
            for (int j = 0; j < 2; j++) mma_bf16_k8(c4[j], W[j][16], W[j][17], gb[8]);
#pragma unroll
            for (int j = 0; j < 2; j++)
                stg128(reinterpret_cast<unsigned char*>(p.s->part) + po + j * 32768, __float_as_uint(c4[j][0] + d4[j][0]) | 1u, __float_as_uint(c4[j][1] + d4[j][1]) | 1u,
                       __float_as_uint(c4[j][2] + d4[j][2]) | 1u, __float_as_uint(c4[j][3] + d4[j][3]) | 1u);
        }
        STAMP2(22);
    } else if (warp == 18) {
        const uint4* const ksrc = reinterpret_cast<const uint4*>(p.s->key3) + pin(2 * lane);
        const unsigned char* const rl = reinterpret_cast<const unsigned char*>(rsrc) + pin(lane * 16);
        const uint32_t sa = pin(sb + SM_LNP + lane * 80);
        const uint32_t klo = pin((uint32_t)(127 - b) << 9 | (uint32_t)(15 - ROWTOK(lane & 15)) << 1 | par), ra = pin(sb + SM_LNP + (32 + (lane & 15)) * 80);
        uint4* const kdst = reinterpret_cast<uint4*>(p.s->key3) + pin((lane >> 1) * 2 * NCTA + 2 * b + (lane & 1));
        FIX(ra);
        bar_sync(6, NWRK);
        {
            float mb, rc;
            ln_finish(sum18(sa), lane, mb, rc);
            if (lane < 16) stat_store(s_stat + lane * 8, mb, rc, 0u);
        }
        bar_arrive(7, 608);
        bar_sync(8, 608);
        uint32_t t0;
        {
            const uint32_t bits = __float_as_uint(rbf(sum18(ra)));
            const uint32_t me = ((bits ^ ((uint32_t)((int)bits >> 31) | 0x80000000u)) & 0xffff0000u) | klo;
            const uint32_t k0 = __reduce_max_sync(0xffffffffu, me), k1 = __reduce_max_sync(0xffffffffu, me == k0 ? 0u : me);
            const uint32_t k2 = __reduce_max_sync(0xffffffffu, me >= k1 ? 0u : me);
            if (lane < 2) stg128(kdst, k0 ^ 0x11eu, k1 ^ 0xfeu, k2 ^ 0xdeu, par);
            asm volatile("mov.u32 %0, %%clock;" : "=r"(t0) :: "memory");
            STAMPW(23);
            if (lane == 0) sts64(s_rank, ~k0, ~k1);
            bar_arrive(9, 608);
            sts32(s_k16 + (lane & 15) * 4, me);
            __syncwarp();
            const uint4 v = lds128(s_k16 + (lane & 16) * 2), w = lds128(s_k16 + (lane & 16) * 2 + 16);
            int rank = ((v.x > me) + (v.y > me)) + ((v.z > me) + (v.w > me)) + (((w.x > me) + (w.y > me)) + ((w.z > me) + (w.w > me)));
            rank += __shfl_xor_sync(0xffffffffu, rank, 16);
            if (lane < 16 && rank < 8) p.s->key[8 * b + rank] = (me ^ 0x1eu) | ((8 - rank) << 5);
        }
        uint4 kq[4];
        uint32_t u[4], mine = 0, m;
        int it = 0;
        { uint32_t now; do { asm volatile("mov.u32 %0, %%clock;" : "=r"(now) :: "memory"); } while (now - t0 < KDLY); }
        do {
#pragma unroll
            for (int i = 0; i < 4; i++) kq[i] = ld_poll(ksrc + 64 * i);
            if (++it > SPIN_LIMIT) TRAP();
            uint32_t S[2][4];
#pragma unroll
            for (int i = 0; i < 2; i++) {
                const uint4 &c = kq[2 * i], &d = kq[2 * i + 1];
                const uint32_t m1 = min(c.x, d.x), m2 = max(c.y, d.y);
                S[i][0] = max(c.x, d.x); S[i][1] = max(m1, m2); S[i][2] = min(m1, m2); S[i][3] = min(c.y, d.y);
            }
            const uint32_t a0 = max(S[0][0], S[1][3]), a1 = max(S[0][1], S[1][2]), a2 = max(S[0][2], S[1][1]), a3 = max(S[0][3], S[1][0]);
            const uint32_t b0 = max(a0, a2), b2 = min(a0, a2), b1 = max(a1, a3), b3 = min(a1, a3);
            u[0] = max(b0, b1); u[1] = min(b0, b1); u[2] = max(b2, b3); u[3] = min(b2, b3);
        } while (__any_sync(0xffffffffu, and3(or3(or3(xor_or(kq[0].x, kq[0].y, par), xor_or(kq[0].z, kq[1].x, par), xor_or(kq[1].y, kq[1].z, par)),
                                                  xor_or(kq[2].x, kq[2].y, par), xor_or(kq[2].z, kq[3].x, par)) | xor_or(kq[3].y, kq[3].z, par), 1u, 1u)));
        STAMPW(16);
        uint4 v[9];
#pragma unroll
        for (int r = 0; r < 8; r++) {
            m = __reduce_max_sync(0xffffffffu, u[0]);
            if (u[0] == m) { u[0] = u[1]; u[1] = u[2]; u[2] = u[3]; u[3] = 0; }
            if (g == r) mine = m;
            v[r] = ld_poll(rl + (size_t)((m >> 8) & 0xffu) * 2304u);
        }
        v[8] = ld_poll(reinterpret_cast<const unsigned char*>(rsrc) + (((mine >> 8) & 0xffu) * 2304u + (32 + t) * 16));
        bool again = __any_sync(0xffffffffu, u[0] == 0 || max(max(kq[0].z, kq[1].z), max(kq[2].z, kq[3].z)) > m);
        if (again) {
#pragma unroll 1
            for (int i = 0; i < 8; i++) {
                uint4 k;
                do { k = ld_poll(reinterpret_cast<const uint4*>(p.s->key) + 32 * i + lane); if (++it > SPIN_LIMIT) TRAP(); } while (((k.x ^ par) | (k.y ^ par) | (k.z ^ par) | (k.w ^ par)) & 1u);
                sts128(sb + SM_KEYS + (32 * i + lane) * 16, k.x, k.y, k.z, k.w);
            }
            m = 0xffffffffu;
#pragma unroll 1
            for (int r = 0; r < 8; r++) {
                uint32_t c = 0;
#pragma unroll 2
                for (int i = 0; i < 8; i++) {
                    const uint4 k = lds128(sb + SM_KEYS + (32 * i + lane) * 16);
                    c = max(max(c, k.x < m ? k.x : 0u), max(k.y < m ? k.y : 0u, max(k.z < m ? k.z : 0u, k.w < m ? k.w : 0u)));
                }
                m = __reduce_max_sync(0xffffffffu, c);
                if (g == r) mine = m;
            }
        }
        if (t == 0) sts32(s_key + g * 4, mine);
        uint32_t mn = 1;
#pragma unroll
        for (int r = 0; r < 9; r++) {
            sts128(sb + SM_XS + (r < 8 ? r * XS_PITCH + lane * 16 : g * XS_PITCH + (32 + t) * 16), v[r].x, v[r].y, v[r].z, v[r].w);
            mn = min(mn, min4(v[r]));
        }
        if ((again || __any_sync(0xffffffffu, mn == 0)) && !__any_sync(0xffffffffu, KLATE(mine))) gather(mine);
        STAMPW(18);
        if (bar_or(11, NWRK, KLATE(mine))) late_rows(IC<1>());
    } else {
        bar_sync(6, NWRK);
        WPOINT(16, true);
        if (WANY(17) || WANY(18)) delay(WDLY);
        WPOINT(17, true);
        if (WANY(18)) delay(WDLY);
        WPOINT(18, true);
        if (bar_or(11, NWRK, false)) late_rows(IC<2>());
        const int tk = KTOK(lds32(s_key + (lane & 7) * 4));
        const uint32_t sel = __reduce_or_sync(0xffffffffu, (tk >> 4) == b ? 1u << (tk & 15) : 0u);
        if (sel ? lane < 16 && !((sel >> lane) & 1u) : lane == 0) bulk_s2g(p.out + (size_t)(16 * b + lane) * DM, sb + SM_OUT + lane * (DM * 2), sel ? DM * 2 : 16 * DM * 2);
        __syncwarp();
    }
    if (warp == 8 || warp >= 18) {
        const int grp = 3 * b + (warp == 8 ? 0 : warp - 17), fsl = 2 * t + ((lane >> 3) & 1), fc = 16 * (grp >> 3) + (grp & 7) + 8 * (lane >> 4);
        const uint32_t fk = lds32(s_key + fsl * 4);
        float hv = 0.f, u2 = 0.f;
        int it = 0;
        if (b < 96) {
            const uint32_t* const fsrc = p.s->rows + KSLOT(fk, fsl) * DM + (fc >> 1);
            uint32_t hw, uw;
            do { hw = ld_poll32(fsrc + 288); uw = ld_poll32(fsrc); if (++it > SPIN_LIMIT) TRAP(); } while (!hw || !uw);
            hv = (fc & 1) ? bf_hi(hw) : bf_lo(hw); u2 = (fc & 1) ? bf_hi(uw) : bf_lo(uw);
        }
        const float rs = rbf(sigmoid_f(__uint_as_float((fk ^ ((uint32_t)((int)~fk >> 31) | 0x80000000u)) & 0xffff0000u)));
        const uint32_t dof = pin(KTOK(fk) * DM + fc), so = pin(grp * 256 + lane);
        if (warp > 17) bar_sync(13, NWRK);
        if (b < 96) {
            delay(warp > 17 ? FDLY : FDLY2);
            const uint4* src = reinterpret_cast<const uint4*>(p.s->part) + so;
            float s0, s1, s2, s3;
            uint32_t ok;
            do {
                uint4 a[8];
#pragma unroll
                for (int i = 0; i < 8; i++) a[i] = ld_poll(src + 32 * i);
                if (++it > SPIN_LIMIT) TRAP();
#define A4(i) and3(and3(a[i].x, a[i].y, a[i].z), and3(a[i].w, a[i + 1].x, a[i + 1].y), a[i + 1].z & a[i + 1].w)
#define S8(f) (((__uint_as_float(a[0].f) + __uint_as_float(a[1].f)) + (__uint_as_float(a[2].f) + __uint_as_float(a[3].f))) + \
               ((__uint_as_float(a[4].f) + __uint_as_float(a[5].f)) + (__uint_as_float(a[6].f) + __uint_as_float(a[7].f))))
                ok = and3(A4(0), A4(2), and3(A4(4), A4(6), 1u));
                s0 = S8(x); s1 = S8(y); s2 = S8(z); s3 = S8(w);
                asm volatile("" : "+f"(s0), "+f"(s1), "+f"(s2), "+f"(s3));
#undef A4
#undef S8
            } while (__any_sync(0xffffffffu, !ok));
            STAMP2(24);
            const bool up = lane & 16, od = lane & 8;
            const float r0 = (up ? s2 : s0) + __shfl_xor_sync(0xffffffffu, up ? s0 : s2, 16), r1 = (up ? s3 : s1) + __shfl_xor_sync(0xffffffffu, up ? s1 : s3, 16);
            float y = (od ? r1 : r0) + __shfl_xor_sync(0xffffffffu, od ? r0 : r1, 8);
            y += __shfl_xor_sync(0xffffffffu, y, 4);
            p.out[dof] = __float2bfloat16_rn(hv + rbf(u2 + rbf(rbf(y) * rs)));
        }
    }
    if (warp == 19) asm volatile("cp.async.bulk.wait_group.read 0;\n" ::: "memory");
    if (b == 0 && tid < 8) *reinterpret_cast<volatile unsigned*>(p.s->hint + tid * 32 + 1) = lds32(s_cnt + 4) + 1u;
    STAMP(25);
    }
}

typedef CUresult (*PFN_tmEncode)(CUtensorMap*, CUtensorMapDataType, cuuint32_t, void*, const cuuint64_t*, const cuuint64_t*, const cuuint32_t*,
                                 const cuuint32_t*, CUtensorMapInterleave, CUtensorMapSwizzle, CUtensorMapL2promotion, CUtensorMapFloatOOBfill);

extern "C" void kernel_launch(void* const* d_in, const int* in_sizes, int n_in, void* d_out, int out_size) {
    Params p;
    p.x = (const bf16*)d_in[0];
    p.lar = (const bf16*)d_in[1];
    p.aim = (const bf16*)d_in[2];
    p.cre = (const bf16*)d_in[3];
    p.cim = (const bf16*)d_in[4];
    p.ldt = (const bf16*)d_in[5];
    p.dsk = (const bf16*)d_in[6];
    p.wr = (const bf16*)d_in[8];
    p.wg = (const bf16*)d_in[9];
    p.wu = (const bf16*)d_in[10];
    p.wd = (const bf16*)d_in[11];
    p.out = (bf16*)d_out;
    static PFN_tmEncode enc = nullptr;
    static void* scratch = nullptr;
    if (!enc) {
        cudaFuncSetAttribute(fused_kernel, cudaFuncAttributeMaxDynamicSharedMemorySize, SMEM_TOTAL);
        void* fn = nullptr;
        cudaDriverEntryPointQueryResult qr;
        cudaGetDriverEntryPoint("cuTensorMapEncodeTiled", &fn, cudaEnableDefault, &qr);
        enc = (PFN_tmEncode)fn;
        cudaGetSymbolAddress(&scratch, g_scratch);
    }
    p.s = (Scratch*)scratch;
    CUtensorMap tm_g, tm_u, tm_d, tm_x;
    const cuuint64_t dims[2] = {FF, DM}, strides[1] = {FF * 2};
    const cuuint32_t box[2] = {72, 48}, es[2] = {1, 1};
    enc(&tm_g, CU_TENSOR_MAP_DATA_TYPE_BFLOAT16, 2, d_in[9], dims, strides, box, es, CU_TENSOR_MAP_INTERLEAVE_NONE, CU_TENSOR_MAP_SWIZZLE_NONE,
        CU_TENSOR_MAP_L2_PROMOTION_NONE, CU_TENSOR_MAP_FLOAT_OOB_FILL_NONE);
    enc(&tm_u, CU_TENSOR_MAP_DATA_TYPE_BFLOAT16, 2, d_in[10], dims, strides, box, es, CU_TENSOR_MAP_INTERLEAVE_NONE, CU_TENSOR_MAP_SWIZZLE_NONE,
        CU_TENSOR_MAP_L2_PROMOTION_NONE, CU_TENSOR_MAP_FLOAT_OOB_FILL_NONE);
    const cuuint64_t ddims[2] = {DM / 2, FF}, dstrides[1] = {DM * 2};
    const cuuint32_t dbox[2] = {WD_PITCH / 4, 8};
    enc(&tm_d, CU_TENSOR_MAP_DATA_TYPE_UINT32, 2, d_in[11], ddims, dstrides, dbox, es, CU_TENSOR_MAP_INTERLEAVE_NONE, CU_TENSOR_MAP_SWIZZLE_NONE,
        CU_TENSOR_MAP_L2_PROMOTION_NONE, CU_TENSOR_MAP_FLOAT_OOB_FILL_NONE);
    const cuuint64_t xdims[4] = {DM, 128, 4, 4}, xstrides[3] = {DM * 8, DM * 2, DM * 1024};
    const cuuint32_t xbox[4] = {8, 128, 4, 2}, xes[4] = {1, 1, 1, 1};
    enc(&tm_x, CU_TENSOR_MAP_DATA_TYPE_BFLOAT16, 4, d_in[0], xdims, xstrides, xbox, xes, CU_TENSOR_MAP_INTERLEAVE_NONE, CU_TENSOR_MAP_SWIZZLE_NONE,
        CU_TENSOR_MAP_L2_PROMOTION_NONE, CU_TENSOR_MAP_FLOAT_OOB_FILL_NONE);
    fused_kernel<<<NCTA, NTHR, SMEM_TOTAL>>>(p, tm_g, tm_u, tm_d, tm_x);
}
```

```cpp
#include <cuda_runtime.h>
#include <cuda.h>
#include <cuda_fp16.h>
#include <cuda_bf16.h>
#include <stdint.h>

#define LSEQ 2048
#define DM 576
#define NST 128
#define FF 4608
#define NSEL 8
#define NCTA 128
#define NTHR 640
#define NWRK 640

typedef __nv_bfloat16 bf16;

#define SM_WG 0
#define SM_WU 41472
#define SM_XC (82944 - 32768)
#define SM_WD 82944
#define W_PITCH 144
#define WD_PITCH 592
#define SM_Z2 (SM_WD + 10240)
#define SM_XT (SM_PL - 18 * 1152)
#define SM_PL (SM_WD + 46080)
#define PL_HALF 1344
#define PLW_B 2624
#define PL_B (4 * PLW_B)
#define SM_U (SM_PL + 5 * PL_B)
#define UPAD 20
#define ULO_B ((UPAD + 128) * 16)
#define USLOT_B (2 * ULO_B)
#define SM_KW (SM_U + 5 * USLOT_B)
#define KW_B 3712
#define KW_PL 1216
#define KW_P 2400
#define KW_H 3440
#define SM_MISC (SM_KW + 5 * KW_B)
#define SM_LC (SM_MISC + 416)
#define SM_LNP (SM_LC + 768)
#define SM_RX (SM_LNP + 3840)
#define SMEM_TOTAL (SM_RX + 3088)
#define TBW PLW_B
#define SM_OUT SM_PL
#define SM_XS (SM_PL + 18432)
#define XS_PITCH 592
#define SM_GU (SM_PL + 23296)
#define SM_EX (SM_PL + 24576)
#define SM_KEYS SM_KW

struct __align__(128) Scratch {
    unsigned hint[8 * 32];
    unsigned flag[32];
    uint32_t key3[NCTA * 8];
    uint32_t key[NCTA * 8];
    uint32_t stat[LSEQ];
    uint32_t uT[64 * (LSEQ / 2)];
    uint32_t y[(NCTA + 96) * DM * 8];
    uint32_t part[288 * 64 * 16];
    uint32_t rows[(2 * NCTA + NSEL) * DM];
};
__device__ Scratch g_scratch;
#define STAMP(i)
#define STAMPX(i)
#define STAMPY(i)

__device__ __forceinline__ float rbf(float x) {
    uint32_t r;
    asm("cvt.rn.bf16x2.f32 %0, %1, %2;\n" : "=r"(r) : "f"(x), "f"(0.f));
    return __uint_as_float(r);
}
__device__ __forceinline__ uint32_t pack_bf16(float lo, float hi) {
    uint32_t r;
    asm("cvt.rn.bf16x2.f32 %0, %1, %2;\n" : "=r"(r) : "f"(hi), "f"(lo));
    return r;
}
__device__ __forceinline__ uint32_t pack_f16(float lo, float hi) {
    uint32_t r;
    asm("cvt.rn.f16x2.f32 %0, %1, %2;\n" : "=r"(r) : "f"(hi), "f"(lo));
    return r;
}
__device__ __forceinline__ uint32_t pack_f16_rz(float lo, float hi) {
    uint32_t r;
    asm("cvt.rz.f16x2.f32 %0, %1, %2;\n" : "=r"(r) : "f"(hi), "f"(lo));
    return r;
}
__device__ __forceinline__ float bf_lo(uint32_t w) { return __uint_as_float(w << 16); }
__device__ __forceinline__ float bf_hi(uint32_t w) { return __uint_as_float(w & 0xffff0000u); }
__device__ __forceinline__ uint32_t hadd2_bf(uint32_t a, uint32_t b) {
    __nv_bfloat162 r = __hadd2_rn(*reinterpret_cast<__nv_bfloat162*>(&a), *reinterpret_cast<__nv_bfloat162*>(&b));
    return *reinterpret_cast<uint32_t*>(&r);
}
__device__ __forceinline__ uint32_t hsub2_bf(uint32_t a, uint32_t b) {
    __nv_bfloat162 r = __hsub2_rn(*reinterpret_cast<__nv_bfloat162*>(&a), *reinterpret_cast<__nv_bfloat162*>(&b));
    return *reinterpret_cast<uint32_t*>(&r);
}
__device__ __forceinline__ uint32_t hmul2_bf(uint32_t a, uint32_t b) {
    __nv_bfloat162 r = __hmul2_rn(*reinterpret_cast<__nv_bfloat162*>(&a), *reinterpret_cast<__nv_bfloat162*>(&b));
    return *reinterpret_cast<uint32_t*>(&r);
}
__device__ __forceinline__ uint32_t hfma2_bf(uint32_t a, uint32_t b, uint32_t c) { uint32_t r; asm("fma.rn.bf16x2 %0, %1, %2, %3;\n" : "=r"(r) : "r"(a), "r"(b), "r"(c)); return r; }
__device__ __forceinline__ uint32_t hmul2(uint32_t a, uint32_t b) { uint32_t r; asm("mul.rn.f16x2 %0, %1, %2;\n" : "=r"(r) : "r"(a), "r"(b)); return r; }
__device__ __forceinline__ uint32_t hadd2(uint32_t a, uint32_t b) { uint32_t r; asm("add.rn.f16x2 %0, %1, %2;\n" : "=r"(r) : "r"(a), "r"(b)); return r; }
__device__ __forceinline__ uint32_t hfma2(uint32_t a, uint32_t b, uint32_t c) { uint32_t r; asm("fma.rn.f16x2 %0, %1, %2, %3;\n" : "=r"(r) : "r"(a), "r"(b), "r"(c)); return r; }
__device__ __forceinline__ uint32_t hfms2(uint32_t a, uint32_t b, uint32_t c) {
    uint32_t r;
    asm("{\n.reg .b32 n;\nneg.f16x2 n, %2;\nfma.rn.f16x2 %0, %1, n, %3;\n}\n" : "=r"(r) : "r"(a), "r"(b), "r"(c));
    return r;
}
__device__ __forceinline__ uint32_t nzw(uint32_t w) { return max(w, 1u); }
__device__ __forceinline__ uint32_t nzf(float f) { const uint32_t w = __float_as_uint(f); return w ? w : 0x80000000u; }
__device__ __forceinline__ uint32_t smem_u32(const void* p) { return (uint32_t)__cvta_generic_to_shared(p); }
__device__ __forceinline__ uint32_t lds32(uint32_t addr) {
    uint32_t v;
    asm volatile("ld.shared.u32 %0, [%1];\n" : "=r"(v) : "r"(addr) : "memory");
    return v;
}
__device__ __forceinline__ uint32_t lds16(uint32_t addr) {
    unsigned short v;
    asm volatile("ld.shared.u16 %0, [%1];\n" : "=h"(v) : "r"(addr) : "memory");
    return v;
}
__device__ __forceinline__ uint2 lds64(uint32_t addr) {
    uint2 v;
    asm volatile("ld.shared.v2.u32 {%0,%1}, [%2];\n" : "=r"(v.x), "=r"(v.y) : "r"(addr) : "memory");
    return v;
}
__device__ __forceinline__ uint4 lds128(uint32_t addr) {
    uint4 v;
    asm volatile("ld.shared.v4.u32 {%0,%1,%2,%3}, [%4];\n" : "=r"(v.x), "=r"(v.y), "=r"(v.z), "=r"(v.w) : "r"(addr) : "memory");
    return v;
}
__device__ __forceinline__ float ldsf(uint32_t addr) { return __uint_as_float(lds32(addr)); }
__device__ __forceinline__ void sts32(uint32_t addr, uint32_t v) { asm volatile("st.shared.u32 [%0], %1;\n" ::"r"(addr), "r"(v) : "memory"); }
__device__ __forceinline__ void sts16(uint32_t addr, uint32_t v) { asm volatile("st.shared.u16 [%0], %1;\n" ::"r"(addr), "h"((unsigned short)v) : "memory"); }
__device__ __forceinline__ void stsf(uint32_t addr, float v) { sts32(addr, __float_as_uint(v)); }
__device__ __forceinline__ void sts64(uint32_t addr, uint32_t a, uint32_t b) { asm volatile("st.shared.v2.u32 [%0], {%1,%2};\n" ::"r"(addr), "r"(a), "r"(b) : "memory"); }
__device__ __forceinline__ void sts64f(uint32_t addr, float a, float b) { sts64(addr, __float_as_uint(a), __float_as_uint(b)); }
__device__ __forceinline__ void sts128(uint32_t addr, uint32_t a, uint32_t b, uint32_t c, uint32_t d) {
    asm volatile("st.shared.v4.u32 [%0], {%1,%2,%3,%4};\n" ::"r"(addr), "r"(a), "r"(b), "r"(c), "r"(d) : "memory");
}
__device__ __forceinline__ void sts128f(uint32_t addr, const float (&v)[4]) {
    sts128(addr, __float_as_uint(v[0]), __float_as_uint(v[1]), __float_as_uint(v[2]), __float_as_uint(v[3]));
}
__device__ __forceinline__ void ldsm_x4(uint32_t& r0, uint32_t& r1, uint32_t& r2, uint32_t& r3, uint32_t addr) {
    asm volatile("ldmatrix.sync.aligned.m8n8.x4.shared.b16 {%0,%1,%2,%3}, [%4];\n"
                 : "=r"(r0), "=r"(r1), "=r"(r2), "=r"(r3) : "r"(addr) : "memory");
}
__device__ __forceinline__ void ldsm_x4_t(uint32_t& r0, uint32_t& r1, uint32_t& r2, uint32_t& r3, uint32_t addr) {
    asm volatile("ldmatrix.sync.aligned.m8n8.x4.trans.shared.b16 {%0,%1,%2,%3}, [%4];\n"
                 : "=r"(r0), "=r"(r1), "=r"(r2), "=r"(r3) : "r"(addr) : "memory");
}
__device__ __forceinline__ void ldsm_x2_t(uint32_t& r0, uint32_t& r1, uint32_t addr) {
    asm volatile("ldmatrix.sync.aligned.m8n8.x2.trans.shared.b16 {%0,%1}, [%2];\n" : "=r"(r0), "=r"(r1) : "r"(addr) : "memory");
}
__device__ __forceinline__ void ldsm_x1_t(uint32_t& r0, uint32_t addr) {
    asm volatile("ldmatrix.sync.aligned.m8n8.x1.trans.shared.b16 {%0}, [%1];\n" : "=r"(r0) : "r"(addr) : "memory");
}
__device__ __forceinline__ void stsm_x4(uint32_t addr, uint32_t r0, uint32_t r1, uint32_t r2, uint32_t r3) {
    asm volatile("stmatrix.sync.aligned.m8n8.x4.shared.b16 [%0], {%1,%2,%3,%4};\n" ::"r"(addr), "r"(r0), "r"(r1), "r"(r2), "r"(r3) : "memory");
}
__device__ __forceinline__ void stsm_x4_t(uint32_t addr, uint32_t r0, uint32_t r1, uint32_t r2, uint32_t r3) {
    asm volatile("stmatrix.sync.aligned.m8n8.x4.trans.shared.b16 [%0], {%1,%2,%3,%4};\n" ::"r"(addr), "r"(r0), "r"(r1), "r"(r2), "r"(r3) : "memory");
}
__device__ __forceinline__ uint32_t movm(uint32_t a) {
    uint32_t d;
    asm volatile("movmatrix.sync.aligned.m8n8.trans.b16 %0, %1;\n" : "=r"(d) : "r"(a));
    return d;
}
__device__ __forceinline__ void mma_f16(float (&c)[4], uint32_t a0, uint32_t a1, uint32_t a2, uint32_t a3, uint32_t b0, uint32_t b1) {
    asm volatile(
        "mma.sync.aligned.m16n8k16.row.col.f32.f16.f16.f32 {%0,%1,%2,%3}, {%4,%5,%6,%7}, {%8,%9}, {%0,%1,%2,%3};\n"
        : "+f"(c[0]), "+f"(c[1]), "+f"(c[2]), "+f"(c[3])
        : "r"(a0), "r"(a1), "r"(a2), "r"(a3), "r"(b0), "r"(b1));
}
__device__ __forceinline__ void mma_bf16(float (&c)[4], uint32_t a0, uint32_t a1, uint32_t a2, uint32_t a3, uint32_t b0, uint32_t b1) {
    asm volatile(
        "mma.sync.aligned.m16n8k16.row.col.f32.bf16.bf16.f32 {%0,%1,%2,%3}, {%4,%5,%6,%7}, {%8,%9}, {%0,%1,%2,%3};\n"
        : "+f"(c[0]), "+f"(c[1]), "+f"(c[2]), "+f"(c[3])
        : "r"(a0), "r"(a1), "r"(a2), "r"(a3), "r"(b0), "r"(b1));
}
__device__ __forceinline__ void mma_bf16_k8(float (&c)[4], uint32_t a0, uint32_t a1, uint32_t b0) {
    asm volatile("mma.sync.aligned.m16n8k8.row.col.f32.bf16.bf16.f32 {%0,%1,%2,%3}, {%4,%5}, {%6}, {%0,%1,%2,%3};\n"
                 : "+f"(c[0]), "+f"(c[1]), "+f"(c[2]), "+f"(c[3]) : "r"(a0), "r"(a1), "r"(b0));
}
__device__ __forceinline__ void bar_sync(int id, int n) { asm volatile("bar.sync %0, %1;\n" ::"r"(id), "r"(n) : "memory"); }
__device__ __forceinline__ void bar_arrive(int id, int n) { asm volatile("bar.arrive %0, %1;\n" ::"r"(id), "r"(n) : "memory"); }
__device__ __forceinline__ bool bar_or(int id, int n, bool v) {
    uint32_t r;
    asm volatile("{\n.reg .pred p, q;\nsetp.ne.u32 p, %3, 0;\nbar.red.or.pred q, %1, %2, p;\nselp.u32 %0, 1, 0, q;\n}\n" : "=r"(r) : "r"(id), "r"(n), "r"((uint32_t)v) : "memory");
    return r;
}
__device__ __forceinline__ uint32_t and3(uint32_t a, uint32_t b, uint32_t c) { uint32_t r; asm("lop3.b32 %0, %1, %2, %3, 0x80;\n" : "=r"(r) : "r"(a), "r"(b), "r"(c)); return r; }
__device__ __forceinline__ uint32_t or3(uint32_t a, uint32_t b, uint32_t c) { uint32_t r; asm("lop3.b32 %0, %1, %2, %3, 0xfe;\n" : "=r"(r) : "r"(a), "r"(b), "r"(c)); return r; }
__device__ __forceinline__ uint32_t xor_or(uint32_t a, uint32_t b, uint32_t c) { uint32_t r; asm("lop3.b32 %0, %1, %2, %3, 0x7e;\n" : "=r"(r) : "r"(a), "r"(b), "r"(c)); return r; }
__device__ __forceinline__ uint32_t pin(uint32_t v) { uint32_t r; asm volatile("shfl.sync.bfly.b32 %0, %1, 0, 0x1f, 0xffffffff;\n" : "=r"(r) : "r"(v) : "memory"); return r; }
__device__ __forceinline__ uint4 ld_poll(const void* p) {
    uint4 v;
    asm volatile("ld.relaxed.gpu.global.v4.u32 {%0,%1,%2,%3}, [%4];\n" : "=r"(v.x), "=r"(v.y), "=r"(v.z), "=r"(v.w) : "l"(p) : "memory");
    return v;
}
__device__ __forceinline__ uint2 ld_poll64(const void* p) {
    uint2 v;
    asm volatile("ld.relaxed.gpu.global.v2.u32 {%0,%1}, [%2];\n" : "=r"(v.x), "=r"(v.y) : "l"(p) : "memory");
    return v;
}
__device__ __forceinline__ uint32_t ld_poll32(const void* p) {
    uint32_t v;
    asm volatile("ld.relaxed.gpu.global.u32 %0, [%1];\n" : "=r"(v) : "l"(p) : "memory");
    return v;
}
__device__ __forceinline__ uint32_t ld_acquire32(const void* p) {
    uint32_t v;
    asm volatile("ld.acquire.gpu.global.u32 %0, [%1];\n" : "=r"(v) : "l"(p) : "memory");
    return v;
}
__device__ __forceinline__ uint4 ldg128(const void* p) {
    uint4 v;
    asm volatile("ld.global.nc.v4.u32 {%0,%1,%2,%3}, [%4];\n" : "=r"(v.x), "=r"(v.y), "=r"(v.z), "=r"(v.w) : "l"(p));
    return v;
}
__device__ __forceinline__ uint2 ldg64(const void* p) {
    uint2 v;
    asm volatile("ld.global.nc.v2.u32 {%0,%1}, [%2];\n" : "=r"(v.x), "=r"(v.y) : "l"(p));
    return v;
}
__device__ __forceinline__ uint32_t ldg16(const void* p) {
    uint32_t v;
    asm volatile("ld.global.nc.u16 %0, [%1];\n" : "=r"(v) : "l"(p));
    return v;
}
__device__ __forceinline__ uint4 ldo128(const void* p) {
    uint4 v;
    asm volatile("ld.relaxed.cta.global.v4.u32 {%0,%1,%2,%3}, [%4];\n" : "=r"(v.x), "=r"(v.y), "=r"(v.z), "=r"(v.w) : "l"(p) : "memory");
    return v;
}
__device__ __forceinline__ uint2 ldo64(const void* p) {
    uint2 v;
    asm volatile("ld.relaxed.cta.global.v2.u32 {%0,%1}, [%2];\n" : "=r"(v.x), "=r"(v.y) : "l"(p) : "memory");
    return v;
}
__device__ __forceinline__ uint32_t ldo16(const void* p) {
    uint32_t v;
    asm volatile("ld.relaxed.cta.global.u16 %0, [%1];\n" : "=r"(v) : "l"(p) : "memory");
    return v;
}
__device__ __forceinline__ void stg128(void* p, uint32_t a, uint32_t b, uint32_t c, uint32_t d) {
    asm volatile("st.global.v4.u32 [%0], {%1,%2,%3,%4};\n" ::"l"(p), "r"(a), "r"(b), "r"(c), "r"(d) : "memory");
}
__device__ __forceinline__ void stg64(void* p, uint32_t a, uint32_t b) { asm volatile("st.global.v2.u32 [%0], {%1,%2};\n" ::"l"(p), "r"(a), "r"(b) : "memory"); }
__device__ __forceinline__ uint32_t min4(const uint4& v) { return min(min(v.x, v.y), min(v.z, v.w)); }
#define SPIN_LIMIT (1 << 21)
#define TRAP() __trap()
__device__ __forceinline__ void mbar_init(uint32_t bar, uint32_t cnt) { asm volatile("mbarrier.init.shared::cta.b64 [%0], %1;\n" ::"r"(bar), "r"(cnt) : "memory"); }
__device__ __forceinline__ void mbar_expect(uint32_t bar, uint32_t bytes) {
    asm volatile("mbarrier.arrive.expect_tx.shared::cta.b64 _, [%0], %1;\n" ::"r"(bar), "r"(bytes) : "memory");
}
__device__ __forceinline__ void mbar_arrive(uint32_t bar) { asm volatile("mbarrier.arrive.shared::cta.b64 _, [%0];\n" ::"r"(bar) : "memory"); }
__device__ __forceinline__ void mbar_wait_cluster(uint32_t bar) {
    asm volatile(
        "{\n.reg .pred p;\n"
        "W_%=:\n"
        "mbarrier.try_wait.parity.acquire.cluster.shared::cta.b64 p, [%0], 0;\n"
        "@!p bra W_%=;\n}\n" ::"r"(bar) : "memory");
}
__device__ __forceinline__ void mbar_wait(uint32_t bar) {
    asm volatile(
        "{\n.reg .pred p;\n"
        "W_%=:\n"
        "mbarrier.try_wait.parity.shared::cta.b64 p, [%0], 0;\n"
        "@!p bra W_%=;\n}\n" ::"r"(bar) : "memory");
}
__device__ __forceinline__ void mbar_wait1(uint32_t bar) {
    asm volatile(
        "{\n.reg .pred p;\n"
        "W_%=:\n"
        "mbarrier.try_wait.parity.shared::cta.b64 p, [%0], 1;\n"
        "@!p bra W_%=;\n}\n" ::"r"(bar) : "memory");
}
__device__ __forceinline__ bool mbar_test(uint32_t bar) {
    uint32_t r;
    asm volatile("{\n.reg .pred p;\nmbarrier.test_wait.parity.shared::cta.b64 p, [%1], 0;\nselp.u32 %0, 1, 0, p;\n}\n" : "=r"(r) : "r"(bar) : "memory");
    return __any_sync(0xffffffffu, r);
}
__device__ __forceinline__ void bulk_g2s(uint32_t dst, const void* src, uint32_t bytes, uint32_t bar) {
    asm volatile("cp.async.bulk.shared::cluster.global.mbarrier::complete_tx::bytes [%0], [%1], %2, [%3];\n" ::"r"(dst), "l"(src), "r"(bytes), "r"(bar) : "memory");
}
__device__ __forceinline__ void bulk_s2g(void* dst, uint32_t src, uint32_t bytes) {
    asm volatile("cp.async.bulk.global.shared::cta.bulk_group [%0], [%1], %2;\ncp.async.bulk.commit_group;\n" ::"l"(dst), "r"(src), "r"(bytes) : "memory");
}
__device__ __forceinline__ void bulk_s2g_nc(void* dst, uint32_t src, uint32_t bytes) {
    asm volatile("cp.async.bulk.global.shared::cta.bulk_group [%0], [%1], %2;\n" ::"l"(dst), "r"(src), "r"(bytes) : "memory");
}
__device__ __forceinline__ void tma_2d(uint32_t dst, const CUtensorMap* tm, int c0, int c1, uint32_t bar) {
    asm volatile("cp.async.bulk.tensor.2d.shared::cluster.global.mbarrier::complete_tx::bytes [%0], [%1, {%3, %4}], [%2];\n"
                 ::"r"(dst), "l"(tm), "r"(bar), "r"(c0), "r"(c1) : "memory");
}
__device__ __forceinline__ void tma_4d(uint32_t dst, const CUtensorMap* tm, int c0, int c3, uint32_t bar) {
    asm volatile("cp.async.bulk.tensor.4d.shared::cluster.global.mbarrier::complete_tx::bytes [%0], [%1, {%3, %4, %4, %5}], [%2];\n"
                 ::"r"(dst), "l"(tm), "r"(bar), "r"(c0), "r"(0), "r"(c3) : "memory");
}
__device__ __forceinline__ void tma_4d_mc(uint32_t dst, const CUtensorMap* tm, int c0, int c3, uint32_t bar) {
    asm volatile("cp.async.bulk.tensor.4d.shared::cluster.global.mbarrier::complete_tx::bytes.multicast::cluster [%0], [%1, {%3, %4, %4, %5}], [%2], %6;\n"
                 ::"r"(dst), "l"(tm), "r"(bar), "r"(c0), "r"(0), "r"(c3), "h"((unsigned short)3) : "memory");
}
__device__ __forceinline__ void l2_prefetch(const void* src, uint32_t bytes) {
    asm volatile("cp.async.bulk.prefetch.L2.global [%0], %1;\n" ::"l"(src), "r"(bytes) : "memory");
}
__device__ __forceinline__ bool elect_one() {
    uint32_t r;
    asm volatile("{\n.reg .pred p;\nelect.sync _|p, 0xffffffff;\nselp.u32 %0, 1, 0, p;\n}\n" : "=r"(r));
    return r;
}
__device__ __forceinline__ void delay(uint32_t clks) {
    uint32_t t0, t1;
    asm volatile("mov.u32 %0, %%clock;" : "=r"(t0) :: "memory");
    do { asm volatile("mov.u32 %0, %%clock;" : "=r"(t1) :: "memory"); } while (t1 - t0 < clks);
}
__device__ __forceinline__ void fence_async() { asm volatile("fence.proxy.async.shared::cta;\n" ::: "memory"); }

__device__ __forceinline__ float2 cmul(float2 a, float2 b) {
    return make_float2(fmaf(a.x, b.x, -a.y * b.y), fmaf(a.x, b.y, a.y * b.x));
}
__device__ __forceinline__ float2 csq(float2 a) {
    float p = a.x * a.y;
    return make_float2(fmaf(a.x, a.x, -a.y * a.y), p + p);
}
__device__ __forceinline__ float ex2_approx(float x) { float r; asm("ex2.approx.ftz.f32 %0, %1;\n" : "=f"(r) : "f"(x)); return r; }
__device__ __forceinline__ float exp_bf(float x) { return rbf(ex2_approx(__fmul_ru(x, 1.4426950408889634f))); }
__device__ __forceinline__ float2 cexp_e(float lr2, float li, float e) {
    const float m = ex2_approx(lr2 * e);
    return make_float2(m * __cosf(li * e), m * __sinf(li * e));
}
__device__ __forceinline__ float rcp_approx(float x) { float r; asm("rcp.approx.ftz.f32 %0, %1;\n" : "=f"(r) : "f"(x)); return r; }
__device__ __forceinline__ float sigmoid_f(float x) { return rcp_approx(1.0f + ex2_approx(x * -1.4426950408889634f)); }
__device__ __forceinline__ float sqrt_approx(float x) { float r; asm("sqrt.approx.ftz.f32 %0, %1;\n" : "=f"(r) : "f"(x)); return r; }

__device__ __forceinline__ void wg_fence() { asm volatile("wgmma.fence.sync.aligned;\n" ::: "memory"); }
__device__ __forceinline__ void wg_commit() { asm volatile("wgmma.commit_group.sync.aligned;\n" ::: "memory"); }
__device__ __forceinline__ void wg_wait0() { asm volatile("wgmma.wait_group.sync.aligned 0;\n" ::: "memory"); }
template <int T> __device__ __forceinline__ void wg_mma(float (&acc)[16][4], const uint32_t* a, uint64_t desc);
template <int T> __device__ __forceinline__ void wg_first(float (&acc)[16][4], const uint32_t* a, uint64_t desc);
template <> __device__ __forceinline__ void wg_mma<0>(float (&acc)[16][4], const uint32_t* a, uint64_t desc) {
    asm volatile("wgmma.mma_async.sync.aligned.m64n128k16.f32.f16.f16 {%0,%1,%2,%3,%4,%5,%6,%7,%8,%9,%10,%11,%12,%13,%14,%15,%16,%17,%18,%19,%20,%21,%22,%23,%24,%25,%26,%27,%28,%29,%30,%31,%32,%33,%34,%35,%36,%37,%38,%39,%40,%41,%42,%43,%44,%45,%46,%47,%48,%49,%50,%51,%52,%53,%54,%55,%56,%57,%58,%59,%60,%61,%62,%63}, {%64,%65,%66,%67}, %68, 1, 1, 1, 0;\n"
                 : "+f"(acc[0][0]), "+f"(acc[0][1]), "+f"(acc[0][2]), "+f"(acc[0][3]), "+f"(acc[1][0]), "+f"(acc[1][1]), "+f"(acc[1][2]), "+f"(acc[1][3]), "+f"(acc[2][0]), "+f"(acc[2][1]), "+f"(acc[2][2]), "+f"(acc[2][3]), "+f"(acc[3][0]), "+f"(acc[3][1]), "+f"(acc[3][2]), "+f"(acc[3][3]), "+f"(acc[4][0]), "+f"(acc[4][1]), "+f"(acc[4][2]), "+f"(acc[4][3]), "+f"(acc[5][0]), "+f"(acc[5][1]), "+f"(acc[5][2]), "+f"(acc[5][3]), "+f"(acc[6][0]), "+f"(acc[6][1]), "+f"(acc[6][2]), "+f"(acc[6][3]), "+f"(acc[7][0]), "+f"(acc[7][1]), "+f"(acc[7][2]), "+f"(acc[7][3]), "+f"(acc[8][0]), "+f"(acc[8][1]), "+f"(acc[8][2]), "+f"(acc[8][3]), "+f"(acc[9][0]), "+f"(acc[9][1]), "+f"(acc[9][2]), "+f"(acc[9][3]), "+f"(acc[10][0]), "+f"(acc[10][1]), "+f"(acc[10][2]), "+f"(acc[10][3]), "+f"(acc[11][0]), "+f"(acc[11][1]), "+f"(acc[11][2]), "+f"(acc[11][3]), "+f"(acc[12][0]), "+f"(acc[12][1]), "+f"(acc[12][2]), "+f"(acc[12][3]), "+f"(acc[13][0]), "+f"(acc[13][1]), "+f"(acc[13][2]), "+f"(acc[13][3]), "+f"(acc[14][0]), "+f"(acc[14][1]), "+f"(acc[14][2]), "+f"(acc[14][3]), "+f"(acc[15][0]), "+f"(acc[15][1]), "+f"(acc[15][2]), "+f"(acc[15][3])
                 : "r"(a[0]), "r"(a[1]), "r"(a[2]), "r"(a[3]), "l"(desc));
}
template <> __device__ __forceinline__ void wg_mma<2>(float (&acc)[16][4], const uint32_t* a, uint64_t desc) {
    asm volatile("wgmma.mma_async.sync.aligned.m64n112k16.f32.f16.f16 {%0,%1,%2,%3,%4,%5,%6,%7,%8,%9,%10,%11,%12,%13,%14,%15,%16,%17,%18,%19,%20,%21,%22,%23,%24,%25,%26,%27,%28,%29,%30,%31,%32,%33,%34,%35,%36,%37,%38,%39,%40,%41,%42,%43,%44,%45,%46,%47,%48,%49,%50,%51,%52,%53,%54,%55}, {%56,%57,%58,%59}, %60, 1, 1, 1, 0;\n"
                 : "+f"(acc[2][0]), "+f"(acc[2][1]), "+f"(acc[2][2]), "+f"(acc[2][3]), "+f"(acc[3][0]), "+f"(acc[3][1]), "+f"(acc[3][2]), "+f"(acc[3][3]), "+f"(acc[4][0]), "+f"(acc[4][1]), "+f"(acc[4][2]), "+f"(acc[4][3]), "+f"(acc[5][0]), "+f"(acc[5][1]), "+f"(acc[5][2]), "+f"(acc[5][3]), "+f"(acc[6][0]), "+f"(acc[6][1]), "+f"(acc[6][2]), "+f"(acc[6][3]), "+f"(acc[7][0]), "+f"(acc[7][1]), "+f"(acc[7][2]), "+f"(acc[7][3]), "+f"(acc[8][0]), "+f"(acc[8][1]), "+f"(acc[8][2]), "+f"(acc[8][3]), "+f"(acc[9][0]), "+f"(acc[9][1]), "+f"(acc[9][2]), "+f"(acc[9][3]), "+f"(acc[10][0]), "+f"(acc[10][1]), "+f"(acc[10][2]), "+f"(acc[10][3]), "+f"(acc[11][0]), "+f"(acc[11][1]), "+f"(acc[11][2]), "+f"(acc[11][3]), "+f"(acc[12][0]), "+f"(acc[12][1]), "+f"(acc[12][2]), "+f"(acc[12][3]), "+f"(acc[13][0]), "+f"(acc[13][1]), "+f"(acc[13][2]), "+f"(acc[13][3]), "+f"(acc[14][0]), "+f"(acc[14][1]), "+f"(acc[14][2]), "+f"(acc[14][3]), "+f"(acc[15][0]), "+f"(acc[15][1]), "+f"(acc[15][2]), "+f"(acc[15][3])
                 : "r"(a[0]), "r"(a[1]), "r"(a[2]), "r"(a[3]), "l"(desc));
}
template <> __device__ __forceinline__ void wg_mma<4>(float (&acc)[16][4], const uint32_t* a, uint64_t desc) {
    asm volatile("wgmma.mma_async.sync.aligned.m64n96k16.f32.f16.f16 {%0,%1,%2,%3,%4,%5,%6,%7,%8,%9,%10,%11,%12,%13,%14,%15,%16,%17,%18,%19,%20,%21,%22,%23,%24,%25,%26,%27,%28,%29,%30,%31,%32,%33,%34,%35,%36,%37,%38,%39,%40,%41,%42,%43,%44,%45,%46,%47}, {%48,%49,%50,%51}, %52, 1, 1, 1, 0;\n"
                 : "+f"(acc[4][0]), "+f"(acc[4][1]), "+f"(acc[4][2]), "+f"(acc[4][3]), "+f"(acc[5][0]), "+f"(acc[5][1]), "+f"(acc[5][2]), "+f"(acc[5][3]), "+f"(acc[6][0]), "+f"(acc[6][1]), "+f"(acc[6][2]), "+f"(acc[6][3]), "+f"(acc[7][0]), "+f"(acc[7][1]), "+f"(acc[7][2]), "+f"(acc[7][3]), "+f"(acc[8][0]), "+f"(acc[8][1]), "+f"(acc[8][2]), "+f"(acc[8][3]), "+f"(acc[9][0]), "+f"(acc[9][1]), "+f"(acc[9][2]), "+f"(acc[9][3]), "+f"(acc[10][0]), "+f"(acc[10][1]), "+f"(acc[10][2]), "+f"(acc[10][3]), "+f"(acc[11][0]), "+f"(acc[11][1]), "+f"(acc[11][2]), "+f"(acc[11][3]), "+f"(acc[12][0]), "+f"(acc[12][1]), "+f"(acc[12][2]), "+f"(acc[12][3]), "+f"(acc[13][0]), "+f"(acc[13][1]), "+f"(acc[13][2]), "+f"(acc[13][3]), "+f"(acc[14][0]), "+f"(acc[14][1]), "+f"(acc[14][2]), "+f"(acc[14][3]), "+f"(acc[15][0]), "+f"(acc[15][1]), "+f"(acc[15][2]), "+f"(acc[15][3])
                 : "r"(a[0]), "r"(a[1]), "r"(a[2]), "r"(a[3]), "l"(desc));
}
template <> __device__ __forceinline__ void wg_mma<6>(float (&acc)[16][4], const uint32_t* a, uint64_t desc) {
    asm volatile("wgmma.mma_async.sync.aligned.m64n80k16.f32.f16.f16 {%0,%1,%2,%3,%4,%5,%6,%7,%8,%9,%10,%11,%12,%13,%14,%15,%16,%17,%18,%19,%20,%21,%22,%23,%24,%25,%26,%27,%28,%29,%30,%31,%32,%33,%34,%35,%36,%37,%38,%39}, {%40,%41,%42,%43}, %44, 1, 1, 1, 0;\n"
                 : "+f"(acc[6][0]), "+f"(acc[6][1]), "+f"(acc[6][2]), "+f"(acc[6][3]), "+f"(acc[7][0]), "+f"(acc[7][1]), "+f"(acc[7][2]), "+f"(acc[7][3]), "+f"(acc[8][0]), "+f"(acc[8][1]), "+f"(acc[8][2]), "+f"(acc[8][3]), "+f"(acc[9][0]), "+f"(acc[9][1]), "+f"(acc[9][2]), "+f"(acc[9][3]), "+f"(acc[10][0]), "+f"(acc[10][1]), "+f"(acc[10][2]), "+f"(acc[10][3]), "+f"(acc[11][0]), "+f"(acc[11][1]), "+f"(acc[11][2]), "+f"(acc[11][3]), "+f"(acc[12][0]), "+f"(acc[12][1]), "+f"(acc[12][2]), "+f"(acc[12][3]), "+f"(acc[13][0]), "+f"(acc[13][1]), "+f"(acc[13][2]), "+f"(acc[13][3]), "+f"(acc[14][0]), "+f"(acc[14][1]), "+f"(acc[14][2]), "+f"(acc[14][3]), "+f"(acc[15][0]), "+f"(acc[15][1]), "+f"(acc[15][2]), "+f"(acc[15][3])
                 : "r"(a[0]), "r"(a[1]), "r"(a[2]), "r"(a[3]), "l"(desc));
}
template <> __device__ __forceinline__ void wg_mma<8>(float (&acc)[16][4], const uint32_t* a, uint64_t desc) {
    asm volatile("wgmma.mma_async.sync.aligned.m64n64k16.f32.f16.f16 {%0,%1,%2,%3,%4,%5,%6,%7,%8,%9,%10,%11,%12,%13,%14,%15,%16,%17,%18,%19,%20,%21,%22,%23,%24,%25,%26,%27,%28,%29,%30,%31}, {%32,%33,%34,%35}, %36, 1, 1, 1, 0;\n"
                 : "+f"(acc[8][0]), "+f"(acc[8][1]), "+f"(acc[8][2]), "+f"(acc[8][3]), "+f"(acc[9][0]), "+f"(acc[9][1]), "+f"(acc[9][2]), "+f"(acc[9][3]), "+f"(acc[10][0]), "+f"(acc[10][1]), "+f"(acc[10][2]), "+f"(acc[10][3]), "+f"(acc[11][0]), "+f"(acc[11][1]), "+f"(acc[11][2]), "+f"(acc[11][3]), "+f"(acc[12][0]), "+f"(acc[12][1]), "+f"(acc[12][2]), "+f"(acc[12][3]), "+f"(acc[13][0]), "+f"(acc[13][1]), "+f"(acc[13][2]), "+f"(acc[13][3]), "+f"(acc[14][0]), "+f"(acc[14][1]), "+f"(acc[14][2]), "+f"(acc[14][3]), "+f"(acc[15][0]), "+f"(acc[15][1]), "+f"(acc[15][2]), "+f"(acc[15][3])
                 : "r"(a[0]), "r"(a[1]), "r"(a[2]), "r"(a[3]), "l"(desc));
}
template <> __device__ __forceinline__ void wg_mma<10>(float (&acc)[16][4], const uint32_t* a, uint64_t desc) {
    asm volatile("wgmma.mma_async.sync.aligned.m64n48k16.f32.f16.f16 {%0,%1,%2,%3,%4,%5,%6,%7,%8,%9,%10,%11,%12,%13,%14,%15,%16,%17,%18,%19,%20,%21,%22,%23}, {%24,%25,%26,%27}, %28, 1, 1, 1, 0;\n"
                 : "+f"(acc[10][0]), "+f"(acc[10][1]), "+f"(acc[10][2]), "+f"(acc[10][3]), "+f"(acc[11][0]), "+f"(acc[11][1]), "+f"(acc[11][2]), "+f"(acc[11][3]), "+f"(acc[12][0]), "+f"(acc[12][1]), "+f"(acc[12][2]), "+f"(acc[12][3]), "+f"(acc[13][0]), "+f"(acc[13][1]), "+f"(acc[13][2]), "+f"(acc[13][3]), "+f"(acc[14][0]), "+f"(acc[14][1]), "+f"(acc[14][2]), "+f"(acc[14][3]), "+f"(acc[15][0]), "+f"(acc[15][1]), "+f"(acc[15][2]), "+f"(acc[15][3])
                 : "r"(a[0]), "r"(a[1]), "r"(a[2]), "r"(a[3]), "l"(desc));
}
template <> __device__ __forceinline__ void wg_mma<12>(float (&acc)[16][4], const uint32_t* a, uint64_t desc) {
    asm volatile("wgmma.mma_async.sync.aligned.m64n32k16.f32.f16.f16 {%0,%1,%2,%3,%4,%5,%6,%7,%8,%9,%10,%11,%12,%13,%14,%15}, {%16,%17,%18,%19}, %20, 1, 1, 1, 0;\n"
                 : "+f"(acc[12][0]), "+f"(acc[12][1]), "+f"(acc[12][2]), "+f"(acc[12][3]), "+f"(acc[13][0]), "+f"(acc[13][1]), "+f"(acc[13][2]), "+f"(acc[13][3]), "+f"(acc[14][0]), "+f"(acc[14][1]), "+f"(acc[14][2]), "+f"(acc[14][3]), "+f"(acc[15][0]), "+f"(acc[15][1]), "+f"(acc[15][2]), "+f"(acc[15][3])
                 : "r"(a[0]), "r"(a[1]), "r"(a[2]), "r"(a[3]), "l"(desc));
}
template <> __device__ __forceinline__ void wg_mma<14>(float (&acc)[16][4], const uint32_t* a, uint64_t desc) {
    asm volatile("wgmma.mma_async.sync.aligned.m64n16k16.f32.f16.f16 {%0,%1,%2,%3,%4,%5,%6,%7}, {%8,%9,%10,%11}, %12, 1, 1, 1, 0;\n"
                 : "+f"(acc[14][0]), "+f"(acc[14][1]), "+f"(acc[14][2]), "+f"(acc[14][3]), "+f"(acc[15][0]), "+f"(acc[15][1]), "+f"(acc[15][2]), "+f"(acc[15][3])
                 : "r"(a[0]), "r"(a[1]), "r"(a[2]), "r"(a[3]), "l"(desc));
}
template <> __device__ __forceinline__ void wg_first<0>(float (&acc)[16][4], const uint32_t* a, uint64_t desc) {
    asm volatile("wgmma.mma_async.sync.aligned.m64n128k16.f32.f16.f16 {%0,%1,%2,%3,%4,%5,%6,%7,%8,%9,%10,%11,%12,%13,%14,%15,%16,%17,%18,%19,%20,%21,%22,%23,%24,%25,%26,%27,%28,%29,%30,%31,%32,%33,%34,%35,%36,%37,%38,%39,%40,%41,%42,%43,%44,%45,%46,%47,%48,%49,%50,%51,%52,%53,%54,%55,%56,%57,%58,%59,%60,%61,%62,%63}, {%64,%65,%66,%67}, %68, 0, 1, 1, 0;\n"
                 : "=f"(acc[0][0]), "=f"(acc[0][1]), "=f"(acc[0][2]), "=f"(acc[0][3]), "=f"(acc[1][0]), "=f"(acc[1][1]), "=f"(acc[1][2]), "=f"(acc[1][3]), "=f"(acc[2][0]), "=f"(acc[2][1]), "=f"(acc[2][2]), "=f"(acc[2][3]), "=f"(acc[3][0]), "=f"(acc[3][1]), "=f"(acc[3][2]), "=f"(acc[3][3]), "=f"(acc[4][0]), "=f"(acc[4][1]), "=f"(acc[4][2]), "=f"(acc[4][3]), "=f"(acc[5][0]), "=f"(acc[5][1]), "=f"(acc[5][2]), "=f"(acc[5][3]), "=f"(acc[6][0]), "=f"(acc[6][1]), "=f"(acc[6][2]), "=f"(acc[6][3]), "=f"(acc[7][0]), "=f"(acc[7][1]), "=f"(acc[7][2]), "=f"(acc[7][3]), "=f"(acc[8][0]), "=f"(acc[8][1]), "=f"(acc[8][2]), "=f"(acc[8][3]), "=f"(acc[9][0]), "=f"(acc[9][1]), "=f"(acc[9][2]), "=f"(acc[9][3]), "=f"(acc[10][0]), "=f"(acc[10][1]), "=f"(acc[10][2]), "=f"(acc[10][3]), "=f"(acc[11][0]), "=f"(acc[11][1]), "=f"(acc[11][2]), "=f"(acc[11][3]), "=f"(acc[12][0]), "=f"(acc[12][1]), "=f"(acc[12][2]), "=f"(acc[12][3]), "=f"(acc[13][0]), "=f"(acc[13][1]), "=f"(acc[13][2]), "=f"(acc[13][3]), "=f"(acc[14][0]), "=f"(acc[14][1]), "=f"(acc[14][2]), "=f"(acc[14][3]), "=f"(acc[15][0]), "=f"(acc[15][1]), "=f"(acc[15][2]), "=f"(acc[15][3])
                 : "r"(a[0]), "r"(a[1]), "r"(a[2]), "r"(a[3]), "l"(desc));
}
template <> __device__ __forceinline__ void wg_first<4>(float (&acc)[16][4], const uint32_t* a, uint64_t desc) {
    asm volatile("wgmma.mma_async.sync.aligned.m64n96k16.f32.f16.f16 {%0,%1,%2,%3,%4,%5,%6,%7,%8,%9,%10,%11,%12,%13,%14,%15,%16,%17,%18,%19,%20,%21,%22,%23,%24,%25,%26,%27,%28,%29,%30,%31,%32,%33,%34,%35,%36,%37,%38,%39,%40,%41,%42,%43,%44,%45,%46,%47}, {%48,%49,%50,%51}, %52, 0, 1, 1, 0;\n"
                 : "=f"(acc[4][0]), "=f"(acc[4][1]), "=f"(acc[4][2]), "=f"(acc[4][3]), "=f"(acc[5][0]), "=f"(acc[5][1]), "=f"(acc[5][2]), "=f"(acc[5][3]), "=f"(acc[6][0]), "=f"(acc[6][1]), "=f"(acc[6][2]), "=f"(acc[6][3]), "=f"(acc[7][0]), "=f"(acc[7][1]), "=f"(acc[7][2]), "=f"(acc[7][3]), "=f"(acc[8][0]), "=f"(acc[8][1]), "=f"(acc[8][2]), "=f"(acc[8][3]), "=f"(acc[9][0]), "=f"(acc[9][1]), "=f"(acc[9][2]), "=f"(acc[9][3]), "=f"(acc[10][0]), "=f"(acc[10][1]), "=f"(acc[10][2]), "=f"(acc[10][3]), "=f"(acc[11][0]), "=f"(acc[11][1]), "=f"(acc[11][2]), "=f"(acc[11][3]), "=f"(acc[12][0]), "=f"(acc[12][1]), "=f"(acc[12][2]), "=f"(acc[12][3]), "=f"(acc[13][0]), "=f"(acc[13][1]), "=f"(acc[13][2]), "=f"(acc[13][3]), "=f"(acc[14][0]), "=f"(acc[14][1]), "=f"(acc[14][2]), "=f"(acc[14][3]), "=f"(acc[15][0]), "=f"(acc[15][1]), "=f"(acc[15][2]), "=f"(acc[15][3])
                 : "r"(a[0]), "r"(a[1]), "r"(a[2]), "r"(a[3]), "l"(desc));
}

#define SDLY 900
#define UDLY 1400
#define KDLY 950
#define PREW 1
#define UE 1
#define W2 19
#define W3 19
#define PFN 3
#define PFO 0
#define FDLY 1000
#define FDLY2 400
#define DDLY 300
#define WDLY 500
#define HW 15
#define FIX(v) do { if ((v) == 1u) TRAP(); } while (0)
#define STAMPW(i) STAMPY(i)
#define STAMP2(i) STAMP(i)
#undef STAMPX
#define STAMPX(i)
struct Params {
    const bf16 *x, *lar, *aim, *cre, *cim, *ldt, *dsk;
    Scratch* s;
    const bf16 *wr, *wg, *wu, *wd;
    bf16* out;
};

#define TOK(g) (2 * (g) - ((g) & 1))
#define ROWTOK(r) (TOK((r) & 7) + (((r) >> 2) & 2))
__device__ __forceinline__ void ln_partial(const uint32_t (&H)[2][4], float (&d)[2][4]) {
#pragma unroll
    for (int hf = 0; hf < 2; hf++) {
        d[hf][0] = d[hf][1] = d[hf][2] = d[hf][3] = 0.f;
        mma_bf16(d[hf], H[hf][0], 0x3f803f80u, H[hf][1], 0x3f803f80u, H[hf][0], H[hf][1]);
    }
#pragma unroll
    for (int hf = 0; hf < 2; hf++) mma_bf16(d[hf], H[hf][2], 0x3f803f80u, H[hf][3], 0x3f803f80u, H[hf][2], H[hf][3]);
}
__device__ __forceinline__ float sum18(uint32_t a) {
    const uint4 p = lds128(a), q = lds128(a + 16), r = lds128(a + 32), s = lds128(a + 48);
    const uint2 u = lds64(a + 64);
#define F(x) __uint_as_float(x)
    return (((F(p.x) + F(p.y)) + (F(p.z) + F(p.w))) + ((F(q.x) + F(q.y)) + (F(q.z) + F(q.w)))) +
           (((F(r.x) + F(r.y)) + (F(r.z) + F(r.w))) + ((F(s.x) + F(s.y)) + (F(s.z) + F(s.w))) + (F(u.x) + F(u.y)));
#undef F
}
__device__ __forceinline__ void ln_stats(float sm, float sq, float& mb, float& sd) {
    const float m0 = sm * (1.0f / 576.0f);
    const float mean = fmaf(fmaf(-m0, 576.0f, sm), 1.0f / 576.0f, m0);
    const float var = fmaxf(fmaf(-mean, mean, sq * (1.0f / 576.0f)), 0.f);
    mb = rbf(mean);
    sd = rbf(sqrt_approx(rbf(rbf(var) + 1e-5f)));
}
__device__ __forceinline__ void ln_finish(float v, int lane, float& mb, float& rc) {
    const float o = __shfl_xor_sync(0xffffffffu, v, 16);
    float sd;
    ln_stats(lane < 16 ? v : o, lane < 16 ? o : v, mb, sd);
    rc = rcp_approx(sd);
}
__device__ __forceinline__ uint32_t ln_apply(uint32_t w, uint32_t m2, uint32_t rh, uint32_t rl) {
    const uint32_t d = hsub2_bf(w, m2);
    return hfma2_bf(d, rh, hmul2_bf(d, rl));
}
__device__ __forceinline__ void stat_store(uint32_t a, float mb, float rc, uint32_t extra) {
    const float rh = rbf(rc);
    sts64(a, (__float_as_uint(mb) >> 16) | (extra << 16), pack_bf16(rh, rc - rh));
}
#define STAT_M(s) __byte_perm((s).x, (s).x, 0x1010)
#define STAT_H(s) __byte_perm((s).y, (s).y, 0x1010)
#define STAT_L(s) __byte_perm((s).y, (s).y, 0x3232)

__device__ __forceinline__ void hcmul(uint32_t re, uint32_t im, uint32_t zx, uint32_t zy, uint32_t& ore, uint32_t& oim) {
    ore = hfms2(im, zy, hmul2(re, zx));
    oim = hfma2(re, zy, hmul2(im, zx));
}

struct KGen {
    uint32_t A[2][4][4];
    float2 z1, z8, z64, z128, T[9];
};
__device__ __forceinline__ void kgen_setup(KGen& k, float lar, float aim, float dt) {
    const float lr2 = -(exp_bf(lar) * dt) * 1.4426950408889634f, li = aim * dt;
    k.z1 = cexp_e(lr2, li, 1.0f);
    k.z8 = cexp_e(lr2, li, 8.0f);
    k.z64 = cexp_e(lr2, li, 64.0f);
}
__device__ __forceinline__ void kgen_rows(KGen& k, uint32_t tb, int lane) {
    const float2 z8 = k.z8, z64 = k.z64;
    const uint32_t row = tb + lane * 16;
    k.z128 = csq(z64);
    const float2 z16 = csq(z8), z24 = cmul(z16, z8), z32 = csq(z16), z40 = cmul(z32, z8), z48 = csq(z24), z56 = cmul(z32, z24);
    uint32_t re[4], im[4], a[4], b[4];
    re[0] = pack_f16(1.0f, z8.x); im[0] = pack_f16(0.0f, z8.y);
    re[1] = pack_f16(z16.x, z24.x); im[1] = pack_f16(z16.y, z24.y);
    re[2] = pack_f16(z32.x, z40.x); im[2] = pack_f16(z32.y, z40.y);
    re[3] = pack_f16(z48.x, z56.x); im[3] = pack_f16(z48.y, z56.y);
    sts128(row, re[0], re[1], re[2], re[3]);
    sts128(row + 1024, im[0], im[1], im[2], im[3]);
    const uint32_t zx = pack_f16(z64.x, z64.x), zy = pack_f16(z64.y, z64.y), zw = pack_f16(k.z128.x, k.z128.y);
#pragma unroll
    for (int j = 0; j < 4; j++) hcmul(re[j], im[j], zx, zy, a[j], b[j]);
    sts128(row + 512, a[0], a[1], a[2], a[3]);
    sts128(row + 1536, b[0], b[1], b[2], b[3]);
    const int mi = lane >> 3;
    const uint32_t zd = tb + 2048 + mi * 16;
    sts16(tb + 2048 + lane * 2, zw); sts16(tb + 2112 + lane * 2, zw >> 16);
    __syncwarp();
    const uint32_t ad = tb + (lane & 7) * 16 + mi * 512;
    ldsm_x4(a[0], a[1], a[2], a[3], zd);
    ldsm_x4(b[0], b[1], b[2], b[3], zd + 64);
#pragma unroll
    for (int ks = 0; ks < 4; ks++) {
        ldsm_x4_t(k.A[0][ks][0], k.A[0][ks][1], k.A[0][ks][2], k.A[0][ks][3], ad + ks * 128);
        hcmul(k.A[0][ks][0], k.A[0][ks][2], a[ks], b[ks], k.A[1][ks][0], k.A[1][ks][2]);
        hcmul(k.A[0][ks][1], k.A[0][ks][3], a[ks], b[ks], k.A[1][ks][1], k.A[1][ks][3]);
    }
}
__device__ __forceinline__ void kgen_chain(KGen& k, uint32_t cr, uint32_t ci, float cs) {
    k.T[0] = make_float2(bf_lo(cr) * cs, -bf_lo(ci) * cs);
    const float2 y1 = make_float2(k.z1.x, -k.z1.y);
#pragma unroll
    for (int c = 1; c < 8; c++) k.T[c] = cmul(k.T[c - 1], y1);
    k.T[8] = cmul(k.T[0], make_float2(k.z8.x, -k.z8.y));
}
__device__ __forceinline__ void kgen_cols(KGen& k, uint32_t tb, uint32_t t5, int lane) {
    const uint32_t row = tb + lane * 16;
    const float2 (&T)[9] = k.T;
    const float2 y128 = make_float2(k.z128.x, -k.z128.y);
    const float2 y256 = csq(y128), y512 = csq(y256), y768 = cmul(y512, y256), y1024 = csq(y512);
    const float2 c1032 = cmul(T[8], y1024);
    __syncwarp();
    sts128(row, pack_f16(T[0].x, T[1].x), pack_f16(T[2].x, T[3].x), pack_f16(T[4].x, T[5].x), pack_f16(T[6].x, T[7].x));
    sts128(row + 512, pack_f16(T[0].y, T[1].y), pack_f16(T[2].y, T[3].y), pack_f16(T[4].y, T[5].y), pack_f16(T[6].y, T[7].y));
    uint32_t a[4], b[4];
    {
        const uint32_t zx = pack_f16(y256.x, y256.x), zy = pack_f16(y256.y, y256.y);
        hcmul(pack_f16(T[0].x, T[2].x), pack_f16(T[0].y, T[2].y), zx, zy, a[0], b[0]);
        hcmul(pack_f16(T[4].x, T[6].x), pack_f16(T[4].y, T[6].y), zx, zy, a[1], b[1]);
        const uint32_t r04 = pack_f16(T[0].x, T[4].x), i04 = pack_f16(T[0].y, T[4].y);
        hcmul(r04, i04, pack_f16(y512.x, y512.x), pack_f16(y512.y, y512.y), a[2], b[2]);
        hcmul(r04, i04, pack_f16(y768.x, y768.x), pack_f16(y768.y, y768.y), a[3], b[3]);
    }
    sts128(row + 1024, a[0], a[1], a[2], a[3]);
    sts128(row + 1536, b[0], b[1], b[2], b[3]);
    {
        const uint32_t r0 = pack_f16(1.0f, y256.x), i0 = pack_f16(0.0f, y256.y), r1 = pack_f16(y512.x, y768.x), i1 = pack_f16(y512.y, y768.y);
        const uint32_t zx = pack_f16(T[8].x, T[8].x), zy = pack_f16(T[8].y, T[8].y), wx = pack_f16(c1032.x, c1032.x), wy = pack_f16(c1032.y, c1032.y);
        hcmul(r0, i0, zx, zy, a[0], b[0]); hcmul(r1, i1, zx, zy, a[1], b[1]);
        hcmul(r0, i0, wx, wy, a[2], b[2]); hcmul(r1, i1, wx, wy, a[3], b[3]);
    }
    sts128(row + 2048, a[0], a[1], a[2], a[3]);
    sts128(t5 + lane * 16, b[0], b[1], b[2], b[3]);
}
__device__ __forceinline__ void kgen_mma(const KGen& k, uint32_t tb, uint32_t t5, int lane) {
    __syncwarp();
    float acc[2][3][4];
#pragma unroll
    for (int i = 0; i < 6; i++)
#pragma unroll
        for (int j = 0; j < 4; j++) acc[i / 3][i % 3][j] = 0.f;
    const int mi = lane >> 3;
    const uint32_t ro = ((lane & 7) + 8 * (mi >> 1)) * 16, bd = tb + ro + (mi & 1) * 512, b2 = ro + ((mi & 1) ? t5 : tb + 2048);
#pragma unroll
    for (int kp = 0; kp < 2; kp++)
#pragma unroll
        for (int j = 0; j < 3; j++) {
            uint32_t b[4];
            ldsm_x4_t(b[0], b[1], b[2], b[3], (j < 2 ? bd + j * 1024 : b2) + kp * 256);
#pragma unroll
            for (int h = 0; h < 2; h++)
#pragma unroll
                for (int m = 0; m < 2; m++) {
                    const uint32_t (&A)[4] = k.A[m][2 * kp + h];
                    mma_f16(acc[m][j], A[0], A[1], A[2], A[3], b[2 * h], b[2 * h + 1]);
                }
        }
    __syncwarp();
#define PK(j) pack_f16(acc[0][j][0], acc[0][j][1]), pack_f16(acc[0][j][2], acc[0][j][3]), pack_f16(acc[1][j][0], acc[1][j][1]), pack_f16(acc[1][j][2], acc[1][j][3])
    stsm_x4(tb + lane * 16, PK(0));
    stsm_x4(tb + 512 + lane * 16, PK(1));
    stsm_x4_t(tb + 1024 + (lane & 7) * 80 + mi * 16, PK(2));
#undef PK
}
__device__ __forceinline__ uint32_t table_buf(uint32_t sb, int warp) { return sb + SM_PL + warp * TBW; }

__device__ __forceinline__ uint4 lds16x4(uint32_t a) { return make_uint4(lds16(a), lds16(a + TBW), lds16(a + 2 * TBW), lds16(a + 3 * TBW)); }
__device__ __forceinline__ void combine_setup(uint32_t sb, int warp, int lane, uint32_t kw, uint32_t& o, uint32_t& n, uint32_t& d) {
    const int wq = warp & 3;
    const uint32_t a = table_buf(sb, warp & ~3);
    o = wq == 3 ? a + 1024 + 320 + (lane >> 3) * 80 + (lane & 7) * 8 : a + (wq ? 504 + wq * 8 : 0) + lane * 16;
    n = a + 1024 + wq * 80 + lane * 2;
    d = wq < 3 ? kw + (wq == 2 ? KW_P : 32 + wq * 512) + lane * 16 : kw + KW_H + 8 + lane * 8;
}
__device__ __forceinline__ void kgen_combine(int wq, int lane, uint32_t o, uint32_t na, uint32_t d) {
#define S4(f) hadd2(hadd2(u.f, v.f), hadd2(w.f, x.f))
#define H4(v) hadd2(hadd2(v.x, v.y), hadd2(v.z, v.w))
#define BP __byte_perm
    if (wq == 0) {
        const uint4 u = lds128(o), v = lds128(o + TBW), w = lds128(o + 2 * TBW), x = lds128(o + 3 * TBW), nn = lds16x4(na);
        const uint32_t n = H4(nn), k0 = S4(x), k2 = S4(y), k4 = S4(z), k6 = S4(w);
        sts128(d, BP(k0, k0, 0x1032), BP(k0, k2, 0x3254), BP(k2, k2, 0x1032), BP(k2, k4, 0x3254));
        sts128(d + KW_PL, BP(k4, k4, 0x1032), BP(k4, k6, 0x3254), BP(k6, k6, 0x1032), BP(k6, n, 0x3254));
        if (lane == 0) sts32(d + KW_PL - 4, k0 & 0xffffu);
    } else {
        const uint2 u = lds64(o), v = lds64(o + TBW), w = lds64(o + 2 * TBW), x = lds64(o + 3 * TBW);
        uint4 nn = make_uint4(0u, 0u, 0u, 0u), mm = nn;
        if (wq < 3) nn = lds16x4(na);
        if (wq == 2) mm = lds16x4(na + 80);
        const uint32_t k0 = S4(x), k2 = S4(y), n = H4(nn), m = H4(mm);
        if (wq == 3) {
            sts64(d, k0, k2);
        } else if (wq == 1) {
            const uint32_t cc = BP(k2, k2, 0x1010);
            sts128(d, BP(k0, k0, 0x1010), BP(k0, k0, 0x1032), BP(k0, k2, 0x3254), cc);
            sts128(d + KW_PL, cc, BP(k2, k2, 0x1032), BP(k2, n, 0x3254), BP(n, n, 0x1010));
        } else {
            const uint32_t w40 = BP(k0, k0, 0x1032), w84 = BP(k0, n, 0x3254), w0 = BP(k0, k0, 0x1010), w4 = BP(k0, k0, 0x3232), w8 = BP(n, n, 0x1010);
            sts64(d, w40, w84);
            sts64(d + 512, BP(k2, k2, 0x1032), BP(k2, m, 0x3254));
            if (lane < 8) { sts128(d - (KW_P - 1056), w0, w0, w40, w4); sts128(d - (KW_P - 1056 - KW_PL), w4, w84, w8, w8); }
            if (lane == 31) sts16(d + (KW_H + 6 - KW_P - 496), m);
        }
    }
#undef S4
#undef H4
#undef BP
}

__device__ __forceinline__ int c_exponent(const uint2& r, const uint2& i, float dt) {
    const uint32_t mx = __vmaxu2(__vmaxu2(r.x & 0x7fff7fffu, r.y & 0x7fff7fffu), __vmaxu2(i.x & 0x7fff7fffu, i.y & 0x7fff7fffu));
    return __reduce_max_sync(0xffffffffu, max(mx, mx << 16) + (__float_as_uint(dt) & 0x7f800000u)) >> 23;
}

#define YQ 2
#define F0 0
__device__ __forceinline__ int warp_v() { int l; asm volatile("mov.u32 %0, %%tid.x;" : "=r"(l)); return __shfl_sync(0xffffffffu, l >> 5, 0); }
__device__ __forceinline__ int lane_v() { int l; asm volatile("mov.u32 %0, %%laneid;" : "=r"(l)); return l; }
__device__ __forceinline__ uint32_t prmt_v(uint32_t a, uint32_t b, uint32_t s) { uint32_t d; asm volatile("prmt.b32 %0, %1, %2, %3;\n" : "=r"(d) : "r"(a), "r"(b), "r"(s)); return d; }
__device__ __forceinline__ uint32_t mov_v(uint32_t a) { uint32_t d; asm volatile("mov.b32 %0, %1;\n" : "=r"(d) : "r"(a)); return d; }
template <int G>
__device__ __forceinline__ void conv_rename(float (&acc)[16][4]) {
#pragma unroll
    for (int i = G; i < 16; i++)
#pragma unroll
        for (int j = 0; j < 4; j++) { float v; asm volatile("mov.b32 %0, %1;\n" : "=f"(v) : "f"(acc[i][j])); acc[i][j] = v; }
}
struct Conv {
    uint32_t kw;
    uint32_t wa;
    uint32_t pa, s2;
    uint32_t s8;
    uint32_t id;
    uint32_t lc;
    uint32_t fs;
    uint32_t fl, yo;
    uint32_t yp;
    size_t ycopy;
    uint32_t ps;
    uint64_t d0;
    int warp;
};
struct Pk { uint32_t w[4]; };
__device__ __forceinline__ Pk pk2(const float (&u)[4], const float (&v)[4]) {
    Pk r;
    r.w[0] = pack_f16(u[0], u[1]); r.w[1] = pack_f16(u[2], u[3]); r.w[2] = pack_f16(v[0], v[1]); r.w[3] = pack_f16(v[2], v[3]);
    return r;
}
__device__ __forceinline__ void park(uint32_t a, const Pk& v) {
    asm volatile("stmatrix.sync.aligned.m8n8.x4.trans.shared.b16 [%0], {%1,%2,%3,%4};\n" ::"r"(a), "r"(v.w[0]), "r"(v.w[1]), "r"(v.w[2]), "r"(v.w[3]) : "memory");
}
__device__ __forceinline__ void conv_constants(uint32_t lc, int l) {
    const int d = (l >> 2) - 2 * (l & 3);
    const int e = d + 8, r4 = (e + 1 + ((e >> 2) & 1)) >> 2, p4 = (e + (((e - 1) >> 2) & 1)) >> 2;
    const uint32_t s2 = r4 == p4 ? 0x1010u : 0x3210u;
    sts64(lc + l * 8, KW_P + ((r4 - 5) >> 1) * 16 + ((r4 - 5) & 1) * 4, s2 | ((d < 0 ? s2 : 0x7654u) << 16));
    const int lo = (d >= 4) - (d < -3), ho = (d >= 5) - (d < -2), le = (d > 4) - (d < -4), he = (d > 5) - (d < -3);
    sts32(lc + 512 + l * 8, (0x5454u + lo * 0x22 + ho * 0x2200) | ((0x3232u + le * 0x22 + he * 0x2200) << 16));
    const int cc = l >> 2, j = l & 3;
    sts64(lc + 256 + l * 8, (j >> 1) * PL_HALF + (16 + cc) * 16 + (j & 1) * 8, (cc >> 1) * (DM * 64) + (cc & 1) * 32 + j * 8);
}
__device__ __forceinline__ void conv_selectors4(Conv& c) {
    const uint2 v = lds64(c.lc + lane_v() * 8);
    c.pa = v.x; c.s2 = v.y;
}
__device__ __forceinline__ void conv_selectors8(Conv& c) { c.s8 = lds32(c.lc + 512 + lane_v() * 8); }
template <int G, int I0, int I1>
__device__ __forceinline__ void conv_load(const Conv& c, uint32_t (&q)[9]) {
    const int wq = c.warp & 3;
    if (G < 2) {
#pragma unroll
        for (int i = I0; i < I1; i++) q[i] = lds32(c.wa + G * 512 + i * 16);
    } else if (G < 4) {
        const uint32_t a = (G == 2 && wq == 0) ? c.wa + 1024 : c.pa + c.kw + wq * 128 + (G < 2 ? 0 : G - 2) * 512;
#pragma unroll
        for (int i = I0; i < I1; i++) q[i] = lds32(a + i * 16);
    } else {
        const uint4 u = lds128(c.kw + KW_H + (G < 4 ? 0 : G - 4) * 64 + wq * 16);
        const uint2 v = lds64(c.kw + KW_H + (G < 4 ? 0 : G - 4) * 64 + wq * 16 + 16);
        q[0] = u.x; q[1] = u.y; q[2] = u.z; q[3] = u.w; q[4] = v.x; q[5] = v.y;
        if (G == 4 && wq == 0) { q[6] = lds32(c.pa + c.kw + 1024); q[7] = lds32(c.pa + c.kw + 1040); }
    }
}
template <int G, int J0, int J1>
__device__ __forceinline__ void conv_frag(const Conv& c, const uint32_t (&q)[9], uint32_t* a, const Pk& dp) {
    const uint32_t dep = dp.w[0];
    if (G < 4) {
        const uint32_t s = (G < 2 || (G == 2 && (c.warp & 3) == 0)) ? c.id : c.s2;
#pragma unroll
        for (int j = J0; j < J1; j++) {
            uint32_t* o = a + 4 * (j - J0);
            o[0] = prmt_v(q[2 * j + 1], dp.w[0], s); o[1] = prmt_v(q[2 * j + 2], dp.w[1], s); o[2] = prmt_v(q[2 * j], dp.w[2], s); o[3] = prmt_v(q[2 * j + 1], dp.w[3], s);
        }
    } else {
        const uint32_t so = prmt_v(c.s8, dep, c.id), se = prmt_v(c.s8, dep, c.id + 0x22);
#pragma unroll
        for (int j = J0; j < J1; j++) {
            uint32_t* o = a + 4 * (j - J0);
            o[0] = prmt_v(q[j + 1], q[j + 2], se); o[1] = prmt_v(q[j + 1], q[j + 2], so); o[2] = prmt_v(q[j], q[j + 1], so);
            if (G == 4 && j == 0 && (c.warp & 3) == 0) {
                o[2] = prmt_v(q[6], dep, c.s2);
                o[0] = prmt_v(q[7], o[0], c.s2 >> 16);
            }
            o[3] = mov_v(o[0]);
        }
    }
}
template <int G, int J0, int J1>
__device__ __forceinline__ void conv_frag(const Conv& c, const uint32_t (&q)[9], uint32_t* a, float depf) {
    const uint32_t d = __float_as_uint(depf);
    conv_frag<G, J0, J1>(c, q, a, Pk{{d, d, d, d}});
}
template <int G, int T, int J0, int J1>
__device__ __forceinline__ void conv_mma(float (&acc)[16][4], const Conv& c, const uint32_t* a) {
#pragma unroll
    for (int j = J0; j < J1; j++) wg_mma<T>(acc, a + 4 * (j - J0), c.d0 - 8 * (2 * G - T) - j);
}
__device__ __forceinline__ float h_lo(uint32_t w) { return __half2float(__ushort_as_half((unsigned short)(w & 0xffffu))); }
__device__ __forceinline__ float h_hi(uint32_t w) { return __half2float(__ushort_as_half((unsigned short)(w >> 16))); }
__device__ __forceinline__ void flush_setup(Conv& c) {
    const uint2 v = lds64(c.lc + 256 + lane_v() * 8);
    c.fl = v.x; c.yo = v.y;
}
template <int Q>
__device__ __forceinline__ void flush_load(const Conv& c, uint32_t pl, uint2 (&f)[4]) {
#pragma unroll
    for (int w = 0; w < 4; w++) f[w] = lds64(c.fl + pl + (Q & 1) * 512 + w * (PLW_B - 64));
}
template <int Q>
__device__ __forceinline__ void flush_load_first(const Conv& c, uint32_t pl, uint2 (&f)[4], float depf) {
    const uint32_t p = prmt_v(c.fl, __float_as_uint(depf), c.id) + pl + (Q & 1) * 512;
#define LDV64(d, a) asm volatile("ld.volatile.shared.v2.u32 {%0,%1}, [%2];\n" : "=r"(d.x), "=r"(d.y) : "r"(a) : "memory")
    LDV64(f[0], p); LDV64(f[1], p + (PLW_B - 64)); LDV64(f[2], p + 2 * (PLW_B - 64)); LDV64(f[3], p + 3 * (PLW_B - 64));
}
#define FDEP __uint_as_float(f[3].y)
template <int Q, int mode>
__device__ __forceinline__ void conv_flush(const Conv& c, const uint2 (&f)[4], unsigned char* gy, uint32_t rx) {
    const uint32_t a0 = hadd2(f[0].x, f[1].x), a1 = hadd2(f[2].x, f[3].x), b0 = hadd2(f[0].y, f[1].y), b1 = hadd2(f[2].y, f[3].y);
    if (Q > 0 && mode == 1) {
        const uint32_t ra = rx + 16 + (Q > 0 ? Q - 1 : 0) * 1024 + (c.warp & 3) * 256 + lane_v() * 8;
        asm volatile("st.async.shared::cluster.mbarrier::complete_tx::bytes.v2.b32 [%0], {%1,%2}, [%3];\n"
                     ::"r"(ra ^ 0x1000000u), "r"(hadd2(a0, a1)), "r"(hadd2(b0, b1)), "r"((rx + (Q > 1 ? 8 : 0)) ^ 0x1000000u) : "memory");
        return;
    }
    float v0 = h_lo(a0) + h_lo(a1), v1 = h_hi(a0) + h_hi(a1), v2 = h_lo(b0) + h_lo(b1), v3 = h_hi(b0) + h_hi(b1);
    if (Q > 0 && mode == 2) {
        const uint2 o = lds64(rx + 16 + (Q > 0 ? Q - 1 : 0) * 1024 + (c.warp & 3) * 256 + lane_v() * 8);
        v0 += h_lo(o.x); v1 += h_hi(o.x); v2 += h_lo(o.y); v3 += h_hi(o.y);
    }
    const uint32_t lo = hmul2_bf(pack_bf16(v0, v1), c.fs), hi = hmul2_bf(pack_bf16(v2, v3), c.fs);
    stg64(gy + Q * 32 * DM * 32 + (c.yo + (Q < YQ ? c.yp : 0u)), nzw(lo), nzw(hi));
}
template <int I, bool S = false> struct IC { static constexpr int value = I; static constexpr bool shared = S; };
template <class T> __device__ constexpr bool wg_is4() { return T::shared; }
#define SLOT(n) (c.ps + (2 + ((n) & 7)) * 128)
#define GO() do { wg_commit(); __syncwarp(); } while (0)
#define DEP acc[15][3]
template <class FG, class FP, class FN>
__device__ __forceinline__ void conv_head(Conv& c, float (&acc)[16][4], uint32_t (&q)[9], uint32_t (&r)[9], uint32_t* a, FG fg, FP pre, FN next) {
    c.id = 0x3210u + (c.warp >> 8);
    pre();
    conv_load<0, 0, 9>(c, q);
    conv_frag<0, 0, 1>(c, q, a, 0.f);
    wg_fence(); wg_first<0>(acc, a, c.d0); GO();
    park(c.ps, Pk{{0u, 0u, 0u, 0u}});
    wg_wait0();
    conv_frag<0, 1, 2>(c, q, a, DEP);
    wg_fence(); conv_mma<0, 0, 1, 2>(acc, c, a); GO();
    fg(IC<0>());
    wg_wait0();
    conv_frag<0, 2, 3>(c, q, a, DEP);
    wg_fence(); conv_mma<0, 0, 2, 3>(acc, c, a); GO();
    conv_load<1, 0, 5>(c, r);
    wg_wait0();
    conv_frag<0, 3, 4>(c, q, a, DEP);
    wg_fence(); conv_mma<0, 0, 3, 4>(acc, c, a); GO();
    conv_load<1, 5, 9>(c, r);
    fg(IC<1>());
    wg_wait0();
    const Pk k = pk2(acc[0], acc[1]);
    conv_rename<2>(acc);
    conv_frag<1, 0, 2>(c, r, a, k);
    wg_fence(); conv_mma<1, 2, 0, 2>(acc, c, a); GO();
    park(SLOT(0), k);
    next(IC<0>());
    fg(IC<2>());
    wg_wait0();
    conv_frag<1, 2, 4>(c, r, a, DEP);
    wg_fence(); conv_mma<1, 2, 2, 4>(acc, c, a); GO();
    next(IC<1>());
    fg(IC<3>());
    wg_wait0();
}
template <class FG, class FP>
__device__ __forceinline__ void conv_run(Conv& c, uint32_t pl, unsigned char* gy, FG fg, FP pre) {
    float acc[16][4];
    uint32_t q[9], r[9], a[32];
    uint2 f[4];
    const int bid = 1 + (c.warp >> 2);
    conv_head(c, acc, q, r, a, fg, pre, [&](auto i) { if (decltype(i)::value == 0) conv_selectors4(c); else conv_load<2, 0, 9>(c, q); });
    Pk k = pk2(acc[2], acc[3]);
    conv_rename<4>(acc);
    conv_frag<2, 0, 4>(c, q, a, k);
    wg_fence(); conv_mma<2, 4, 0, 4>(acc, c, a); GO();
    park(SLOT(2), k);
    conv_load<3, 0, 9>(c, q);
    flush_setup(c);
    bar_sync(bid, 128);
    fg(IC<4>());
    wg_wait0();
    conv_rename<6>(acc);
    if (F0) { flush_load_first<0>(c, pl, f, DEP); conv_frag<3, 0, 4>(c, q, a, FDEP); }
    else conv_frag<3, 0, 4>(c, q, a, DEP);
    wg_fence(); conv_mma<3, 6, 0, 4>(acc, c, a); GO();
    park(SLOT(4), pk2(acc[4], acc[5]));
    conv_load<4, 0, 9>(c, q);
    conv_selectors8(c);
    if (!F0) flush_load<0>(c, pl, f);
    conv_flush<0, 0>(c, f, gy, 0u);
    fg(IC<5>());
    wg_wait0();
    conv_rename<8>(acc);
    conv_frag<4, 0, 4>(c, q, a, DEP);
    wg_fence(); conv_mma<4, 8, 0, 4>(acc, c, a); GO();
    k = pk2(acc[6], acc[7]);
    park(SLOT(6), k);
    conv_load<5, 0, 9>(c, q);
    bar_sync(bid, 128);
    park(c.ps, k);
    fg(IC<6>());
    wg_wait0();
    conv_rename<10>(acc);
    flush_load_first<1>(c, pl, f, DEP);
    conv_frag<5, 0, 4>(c, q, a, FDEP);
    wg_fence(); conv_mma<5, 10, 0, 4>(acc, c, a); GO();
    park(SLOT(8), pk2(acc[8], acc[9]));
    conv_load<6, 0, 9>(c, q); conv_load<7, 0, 9>(c, r);
    conv_flush<1, 0>(c, f, gy, 0u);
    fg(IC<7>());
    wg_wait0();
    conv_rename<12>(acc);
    conv_frag<6, 0, 4>(c, q, a, DEP); conv_frag<7, 0, 4>(c, r, a + 16, DEP);
    wg_fence(); conv_mma<6, 12, 0, 4>(acc, c, a); conv_mma<7, 12, 0, 4>(acc, c, a + 16); GO();
    park(SLOT(10), pk2(acc[10], acc[11]));
    bar_sync(bid, 128);
    flush_load<2>(c, pl, f);
    conv_flush<2, 0>(c, f, gy, 0u);
    fg(IC<8>());
    if (c.id == 0) TRAP();
    wg_wait0();
    park(SLOT(12), pk2(acc[12], acc[13])); park(SLOT(14), pk2(acc[14], acc[15]));
    bar_sync(bid, 128);
    flush_load<3>(c, pl, f);
    conv_flush<3, 0>(c, f, gy, 0u);
}
template <class FG>
__device__ __forceinline__ void conv_outer(Conv& c, uint32_t pl, unsigned char* gy, uint32_t rx, FG fg) {
    float acc[16][4];
    uint32_t q[9], r[9], a[32];
    uint2 f[4], f2[4];
    const int bid = 1 + (c.warp >> 2);
    conv_head(c, acc, q, r, a, [&](auto gi) { if (decltype(gi)::value == 2) fg(IC<2, true>()); }, [&]() {}, [&](auto i) { if (decltype(i)::value == 0) conv_selectors8(c); else conv_load<6, 0, 9>(c, q); });
    park(SLOT(2), pk2(acc[2], acc[3])); park(SLOT(4), pk2(acc[4], acc[5]));
    const Pk k = pk2(acc[6], acc[7]);
    park(SLOT(6), k);
    conv_load<7, 0, 9>(c, r);
    conv_rename<12>(acc);
    conv_frag<6, 0, 4>(c, q, a, __uint_as_float(k.w[3])); conv_frag<7, 0, 4>(c, r, a + 16, __uint_as_float(k.w[3]));
    wg_fence(); conv_mma<6, 12, 0, 4>(acc, c, a); conv_mma<7, 12, 0, 4>(acc, c, a + 16); GO();
    flush_setup(c);
    bar_sync(bid, 128);
    flush_load<0>(c, pl, f); flush_load<1>(c, pl, f2);
    conv_flush<1, 1>(c, f2, gy, rx);
    conv_flush<0, 1>(c, f, gy, rx);
    wg_wait0();
    bar_sync(bid, 128);
    park(c.ps, k); park(SLOT(8), pk2(acc[8], acc[9])); park(SLOT(10), pk2(acc[10], acc[11]));
    park(SLOT(12), pk2(acc[12], acc[13])); park(SLOT(14), pk2(acc[14], acc[15]));
    bar_sync(bid, 128);
    flush_load<2>(c, pl, f); flush_load<3>(c, pl, f2);
    conv_flush<2, 1>(c, f, gy, rx);
    conv_flush<3, 1>(c, f2, gy, rx);
}
template <class FG>
__device__ __forceinline__ void conv_inner(Conv& c, uint32_t pl, unsigned char* gy, uint32_t rx, FG fg) {
    float acc[16][4];
    uint32_t q[9], a[16];
    uint2 f[4], f2[4];
    const int bid = 1 + (c.warp >> 2);
    c.id = 0x3210u + (c.warp >> 8);
    conv_selectors4(c);
    conv_load<2, 0, 9>(c, q);
    conv_frag<2, 0, 4>(c, q, a, 0.f);
    wg_fence(); wg_first<4>(acc, a, c.d0); conv_mma<2, 4, 1, 4>(acc, c, a + 4); GO();
    conv_load<3, 0, 9>(c, q);
    park(SLOT(2), Pk{{0u, 0u, 0u, 0u}});
    fg(IC<2, true>());
    wg_wait0();
    conv_rename<6>(acc);
    conv_frag<3, 0, 4>(c, q, a, DEP);
    wg_fence(); conv_mma<3, 6, 0, 4>(acc, c, a); GO();
    park(SLOT(4), pk2(acc[4], acc[5]));
    conv_load<4, 0, 9>(c, q);
    conv_selectors8(c);
    wg_wait0();
    conv_rename<8>(acc);
    conv_frag<4, 0, 4>(c, q, a, DEP);
    wg_fence(); conv_mma<4, 8, 0, 4>(acc, c, a); GO();
    const Pk k = pk2(acc[6], acc[7]);
    park(SLOT(6), k); park(c.ps, k);
    conv_load<5, 0, 9>(c, q);
    flush_setup(c);
    wg_wait0();
    conv_rename<10>(acc);
    conv_frag<5, 0, 4>(c, q, a, DEP);
    wg_fence(); conv_mma<5, 10, 0, 4>(acc, c, a); GO();
    park(SLOT(8), pk2(acc[8], acc[9]));
    bar_sync(bid, 128);
    flush_load<1>(c, pl, f);
    mbar_wait(rx);
    conv_flush<1, 2>(c, f, gy, rx);
    wg_wait0();
    bar_sync(bid, 128);
    park(SLOT(10), pk2(acc[10], acc[11])); park(SLOT(12), pk2(acc[12], acc[13])); park(SLOT(14), pk2(acc[14], acc[15]));
    bar_sync(bid, 128);
    flush_load<3>(c, pl, f); flush_load<2>(c, pl, f2);
    mbar_wait(rx + 8);
    conv_flush<3, 2>(c, f, gy, rx);
    conv_flush<2, 2>(c, f2, gy, rx);
}
#undef SLOT
#undef GO
#undef DEP
template <int U0, int U1>
__device__ __forceinline__ void weight_units(uint32_t sb, const CUtensorMap* tg, const CUtensorMap* tu, const CUtensorMap* td, bool w) {
    if (U1 > U0 && w && elect_one()) {
#pragma unroll
        for (int i = U0; i < U1; i++) {
            if (i < 12) tma_2d(sb + SM_WG + i * 6912, i < 6 ? tg : tu, 72 * (blockIdx.x >> 1), 288 * (blockIdx.x & 1) + (i % 6) * 48, sb + SM_MISC + 328);
            else tma_2d(sb + SM_WD + (i - 12) * 4736, td, 144 * (blockIdx.x & 1), 72 * (blockIdx.x >> 1) + 8 * (i - 12), sb + SM_MISC + 336);
        }
    }
}
#define WS 2110121111122004100
__device__ constexpr int wsched(int i) {
    unsigned long long v = WS;
    int n = 0;
    for (int k = 19; k >= 1; k--) { if (k < i) n += (int)(v % 10); v /= 10; }
    return n;
}
static_assert(wsched(20) == 21 && wsched(6) <= 7 && wsched(11) <= 12 && wsched(13) <= 14 && wsched(16) <= 17 && wsched(16) == wsched(15) && wsched(19) == 21, "");
#define WANY(i) (wsched((i) + 1) > wsched(i))
#define WPOINT(i, w) do { weight_units<wsched(i), wsched(i + 1)>(sb, &tm_g, &tm_u, &tm_d, w); } while (0)

__global__ void __launch_bounds__(NTHR, 1) __cluster_dims__(2, 1, 1)
fused_kernel(const Params p, const __grid_constant__ CUtensorMap tm_g, const __grid_constant__ CUtensorMap tm_u, const __grid_constant__ CUtensorMap tm_d, const __grid_constant__ CUtensorMap tm_x) {
    extern __shared__ __align__(1024) unsigned char smem[];
    const uint32_t sb = smem_u32(smem);
    const int tid = threadIdx.x, warp = __shfl_sync(0xffffffffu, tid >> 5, 0), lane = tid & 31;
    const int b = blockIdx.x, P = b >> 1, odd = b & 1;
    const int g = lane >> 2, t = lane & 3;
    const int wg = warp >> 2, t128 = tid & 127;
    const uint32_t s_stat = sb + SM_MISC;
    const uint32_t s_key = sb + SM_MISC + 128;
    const uint32_t s_rank = sb + SM_MISC + 256;
    const uint32_t s_k16 = sb + SM_MISC + 192;
    const uint32_t s_cnt = sb + SM_MISC + 320;
    const uint32_t bar_w = sb + SM_MISC + 328, bar_d = bar_w + 8, bar_g = bar_w + 16, bar_x = bar_w + 24, bar_v = bar_w + 32, bar_s = bar_w + 40, bar_h = bar_w + 48;
    STAMP(0);

    const int ch = wg < 4 ? 4 * b + wg : 512 + P;
    const uint32_t mo = tid < 512 ? 512 * b + tid : 65536 + 128 * P + t128, mq = (mo & ~127u) + 4 * lane;
    const uint32_t pl = ldo16(p.lar + mo), pa2 = ldo16(p.aim + mo), ldt = ldo16(p.ldt + (mo >> 7));
    const uint32_t pc = ldo16(p.cre + mo), pi = ldo16(p.cim + mo);
    const uint2 call_re = ldo64(p.cre + mq), call_im = ldo64(p.cim + mq);
    const uint32_t epl = ld_poll32(p.s->hint + (b & 7) * 32 + 1);
    if (wg < 4) {
        bar_arrive(0, NWRK);
        asm volatile("barrier.cluster.arrive.relaxed.aligned;\n" ::: "memory");
    } else {
        const int o = (4 * (warp & 3) + (g >> 1)) * 1152 + (g & 1) * 576 + t * 16;
        sts128(sb + SM_Z2 + t128 * 16, 0u, 0u, 0u, 0u); sts128(sb + SM_Z2 + 2048 + t128 * 16, 0u, 0u, 0u, 0u);
        if (warp == 16) sts128(sb + SM_Z2 + 4096 + lane * 16, 0u, 0u, 0u, 0u);
        fence_async();
        bar_sync(0, NWRK);
        STAMP(9);
#pragma unroll
        for (int c = 0; c < 9; c++)
            asm volatile("cp.async.cg.shared.global [%0], [%1], 16;\n" ::"r"(sb + SM_XT + o + c * 64), "l"(reinterpret_cast<const char*>(p.x) + b * 18432 + o + c * 64) : "memory");
        asm volatile("cp.async.commit_group;\n" ::: "memory");
        if (elect_one()) {
            mbar_init(bar_h + 8 * (warp & 3), 1);
            if (warp == 19) {
                mbar_init(bar_x, 1); mbar_init(bar_w, 1);
                mbar_expect(bar_x, 32768); mbar_expect(bar_w, 82944);
#pragma unroll
                for (int i = YQ; i < 4; i++) bulk_s2g(reinterpret_cast<unsigned char*>(p.s->y) + 32 * i * 18432 + b * 4608, sb + SM_Z2, 4608);
            } else if (warp == 18) {
                mbar_init(bar_s, 1); mbar_init(bar_v, 2); mbar_init(bar_d, 1); mbar_init(bar_g, 1); mbar_init(sb + SM_RX, 1); mbar_init(sb + SM_RX + 8, 1);
                mbar_expect(bar_v, 2 * 1152); mbar_expect(bar_d, 72 * WD_PITCH); mbar_expect(bar_g, 4608); mbar_expect(sb + SM_RX, 1024); mbar_expect(sb + SM_RX + 8, 2048);
            }
            asm volatile("fence.mbarrier_init.release.cluster;\n" ::: "memory");
        }
        __syncwarp();
        asm volatile("barrier.cluster.arrive.relaxed.aligned;\n" ::: "memory");
        if (warp == 19) {
            asm volatile("barrier.cluster.wait.aligned;\n" ::: "memory");
            if (elect_one()) tma_4d_mc(sb + SM_XC + odd * 16384, &tm_x, 8 * P, 2 * odd, bar_x);
            __syncwarp();
        }
        if (PREW) {
            if (!(g & 1) && t == (g >> 1)) *reinterpret_cast<volatile uint32_t*>(p.s->stat + 16 * b + 4 * (warp & 3) + t) = 0u;
            if (warp < 18) {
                unsigned char* const ud = reinterpret_cast<unsigned char*>(p.s->uT) + (size_t)(8 * (warp & 1) + 2 * (g >> 1)) * 16384 + b * 128 + (g & 1) * 32 + t * 8;
#pragma unroll
                for (int k = 0; k < 4; k++) *reinterpret_cast<volatile unsigned long long*>(ud + (k >> 1) * 16384 + (k & 1) * 64) = 0ull;
            }
        }
    }
    const uint32_t kw = sb + SM_KW + wg * KW_B;
    const uint32_t tb = table_buf(sb, warp), t5 = sb + SM_WD + warp * 512;
    STAMP(29);
    const float dt = exp_bf(bf_lo(ldt));
    const uint32_t ep = __reduce_or_sync(0xffffffffu, epl);
    auto stats = [&]() {
        const int wq = warp & 3;
        const uint32_t xa = sb + SM_XT + (4 * wq + (g >> 1)) * 1152 + (g & 1) * 576 + t * 16;
        const bool own = !(g & 1) && t == (g >> 1);
        float d[4][4] = {};
        asm volatile("cp.async.wait_group 0;\n" ::: "memory");
        STAMP(26);
        uint4 v[9];
#pragma unroll
        for (int c = 0; c < 9; c++) v[c] = lds128(xa + c * 64);
#pragma unroll
        for (int c = 0; c < 9; c++) {
            mma_bf16(d[2 * (c & 1)], v[c].x, 0x3f803f80u, v[c].y, 0x3f803f80u, v[c].x, v[c].y);
            mma_bf16(d[2 * (c & 1) + 1], v[c].z, 0x3f803f80u, v[c].w, 0x3f803f80u, v[c].z, v[c].w);
        }
        STAMP(27);
        float sm = (g & 1) ? (d[0][3] + d[1][3]) + (d[2][3] + d[3][3]) : (d[0][2] + d[1][2]) + (d[2][2] + d[3][2]);
        float sq = (g & 1) ? (d[0][1] + d[1][1]) + (d[2][1] + d[3][1]) : (d[0][0] + d[1][0]) + (d[2][0] + d[3][0]);
        sm += __shfl_xor_sync(0xffffffffu, sm, 4); sq += __shfl_xor_sync(0xffffffffu, sq, 4);
        if (lane == 0) mbar_arrive(bar_h + 8 * wq);
        float mb, sd;
        ln_stats(sm, sq, mb, sd);
        if (own) p.s->stat[16 * b + 4 * wq + t] = (__float_as_uint(mb) >> 16) | (__float_as_uint(sd) & 0x7fff0000u) | (ep << 31);
        STAMPX(22);
        if (own) stat_store(s_stat + (2 * wq + (t & 1) + 8 * (t >> 1)) * 8, mb, rcp_approx(sd), 0u);
        if (wq == 3) asm volatile("cp.async.bulk.wait_group 0;\n" ::: "memory");
        bar_sync(5, 128);
        STAMP(28);
        uint32_t now;
        asm volatile("mov.u32 %0, %%clock;" : "=r"(now) :: "memory");
        if (wq == 2) {
            conv_constants(sb + SM_LC, lane);
            __syncwarp();
            if (lane < 8) p.s->key3[8 * b + lane] = ep & 1u;
            if (lane == 0) {
                sts64(s_cnt, now, ep);
                mbar_arrive(bar_s);
                bulk_g2s(sb + SM_XT + 16 * 1152, p.dsk, 1152, bar_v);
                bulk_g2s(sb + SM_XT + 17 * 1152, p.wr, 1152, bar_v);
            }
            __syncwarp();
        }
        WPOINT(1, wq == 3);
        if (wq < 2) {
            unsigned char* const ud = reinterpret_cast<unsigned char*>(p.s->uT) + (size_t)(8 * wq + 2 * (g >> 1)) * 16384 + b * 128 + (g & 1) * 32 + t * 8;
            const uint32_t utag = (ep % 7u + 1u) * 0x10001u;
            uint32_t U[2][4];
#pragma unroll
            for (int hf = 0; hf < 2; hf++) {
                const uint2 st = lds64(s_stat + (g + 8 * hf) * 8);
                const uint4 xu = lds128(sb + SM_XT + (TOK(g) + 2 * hf) * 1152 + warp * 64 + t * 16);
                const uint32_t X[4] = {xu.x, xu.y, xu.z, xu.w};
#pragma unroll
                for (int k = 0; k < 4; k++) {
                    const uint32_t u = ln_apply(X[k], STAT_M(st), STAT_H(st), STAT_L(st));
                    U[hf][k] = movm((pack_f16(bf_lo(u), bf_hi(u)) & 0xfff8fff8u) | utag);
                }
            }
#pragma unroll
            for (int k = 0; k < 4; k++) stg64(ud + (k >> 1) * 16384 + (k & 1) * 64, U[0][k], U[1][k]);
        }
    };
    STAMP(1);
    if (wg < 4) { STAMPX(16); }
    KGen kg;
    kgen_setup(kg, bf_lo(pl), bf_lo(pa2), dt);
    kgen_rows(kg, tb, lane);
    STAMP(2);
    const int E = min(max(c_exponent(call_re, call_im, dt) - 243, -120), 120);
    kgen_chain(kg, pc, pi, dt * __uint_as_float((uint32_t)(128 - E) << 23));
    STAMP(3);
    kgen_cols(kg, tb, t5, lane);
    STAMP(4);
    if (wg == 4) stats();
    if (warp != 19) asm volatile("barrier.cluster.wait.aligned;\n" ::: "memory");
    if (wg < 4) { STAMPX(17); }
    if (PFN && tid < 54 * PFN)
        asm volatile("prefetch.global.L2 [%0];\n" ::"l"(reinterpret_cast<const char*>(p.wg) + ((b >> 6) * 288 + PFO * 48) * (FF * 2) + ((b & 63) * 54 * PFN + tid) * 128));
    if (t128 < 2 * UPAD) sts128(sb + SM_U + wg * USLOT_B + (t128 & 1) * ULO_B + (t128 >> 1) * 16, 0u, 0u, 0u, 0u);
    if (t128 >= 124) sts128(kw + (t128 & 1) * 16 + (t128 & 2) * (KW_PL / 2), 0u, 0u, 0u, 0u);
    if (warp < 15) sts128(sb + SM_Z2 + 4608 + tid * 16, 0u, 0u, 0u, 0u);
    uint32_t co, cn, cd;
    combine_setup(sb, warp, lane, kw, co, cn, cd);
    co = pin(co); cn = pin(cn); cd = pin(cd);
    const uint4* const usrc = reinterpret_cast<const uint4*>(p.s->stat) + pin(wg < 4 ? tid : 512 + (P >> 2) * 1024 + (t128 >> 1) * 8 + (P & 3) * 2 + (t128 & 1));
    if (wg < 4) mbar_wait(bar_h + 8 * (warp & 3));
    if (wg < 4) { STAMPX(19); }
    kgen_mma(kg, tb, t5, lane);
    if (wg < 4) { STAMPX(20); }
    STAMP(5);
    uint4 uv0, uv1;
    auto first_poll = [&](uint32_t dly) {
        mbar_wait(bar_s);
        const uint32_t t0 = lds32(s_cnt);
        uint32_t now;
        do { asm volatile("mov.u32 %0, %%clock;" : "=r"(now) :: "memory"); } while (now - t0 < dly);
        uv0 = ld_poll(usrc);
    };
    if (UE && wg == 4) { first_poll(UDLY); uv1 = ld_poll(usrc + 512); }
    WPOINT(2, warp == W2);
    bar_sync(1 + wg, 128);
    if (wg < 4) { STAMPX(21); }
    kgen_combine(warp & 3, lane, co, cn, cd);
    STAMP(6);
    if (wg < 4) { STAMPX(18); }
    WPOINT(3, warp == W3);
    if (wg < 4) first_poll(SDLY);
    {
        const int wq = warp & 3;
        Conv c;
        const uint32_t pln = sb + SM_PL + wg * PL_B;
        const int e = g - 2 * t + 7;
        c.kw = kw; c.wa = pin(kw + ((e >> 2) & 1) * KW_PL + (8 * wq + (e >> 3)) * 16 + (e & 3) * 4);
        c.ps = mov_v(pln + wq * PLW_B + ((lane >> 3) & 1) * PL_HALF + ((lane >> 4) * 8 + (lane & 7)) * 16); c.warp = warp;
        c.lc = sb + SM_LC; c.fs = (uint32_t)(127 + E) * 0x800080u; c.yp = (ep & 1u) * (NCTA * 18432u);
        c.d0 = ((uint64_t)(ULO_B >> 4) << 16) | ((uint64_t)(128 >> 4) << 32) | (uint64_t)(((sb + SM_U + wg * USLOT_B + UPAD * 16) & 0x3FFFF) >> 4);
        unsigned char* gy = reinterpret_cast<unsigned char*>(p.s->y) + ((size_t)(4 * wq) * DM + ch) * 64;
        auto hook = [&](auto gi) {
                     constexpr int G = decltype(gi)::value;
                     if (G == (wg_is4<decltype(gi)>() ? 2 : 5)) asm volatile("barrier.cluster.wait.aligned;\n" ::: "memory");
                     if (!wg_is4<decltype(gi)>() && (G == 0 || G == 2) && warp == HW && elect_one()) {
                         unsigned char* const sc = reinterpret_cast<unsigned char*>(p.s);
                         if (G == 0) {
                             if (b < 96) bulk_s2g_nc(sc + offsetof(Scratch, part) + b * 12288, sb + SM_Z2, 12288);
                             bulk_s2g(sc + offsetof(Scratch, rows) + (127 - b) * 4608, sb + SM_Z2, 4608);
                         }
                         if (G == 2) {
                             if (YQ == 3) bulk_s2g_nc(sc + offsetof(Scratch, y) + (NCTA * 18432u - c.yp) + b * 13824 + 6912, sb + SM_Z2, 6912);
                             if (YQ) bulk_s2g(sc + offsetof(Scratch, y) + (NCTA * 18432u - c.yp) + b * (4608 * YQ), sb + SM_Z2, YQ == 3 ? 6912 : 4608 * YQ);
                         }
                     }
                     if (!wg_is4<decltype(gi)>()) WPOINT(6 + G, warp == (G >= 7 ? HW : 4 * (G % 3) + 1));
                     if (!wg_is4<decltype(gi)>() && G == 6 && warp == HW) {
                         asm volatile("cp.async.bulk.wait_group 0;\n" ::: "memory");
                         __syncwarp();
                         if (elect_one()) mbar_arrive(bar_v);
                     }
                 };
        if (wg < 4) {
            asm volatile("barrier.cluster.arrive.relaxed.aligned;\n" ::: "memory");
            conv_run(c, pln + wq * 128, gy, hook, [&]() {
                STAMPX(23);
                mbar_wait(bar_x);
                STAMPX(24);
                uint2 xc[4];
                uint32_t xw[4][2];
#pragma unroll
                for (int j = 0; j < 4; j++) xc[j] = lds64(sb + SM_XC + wg * 8192 + j * 2048 + t128 * 16 + odd * 8);
#pragma unroll
                for (int i = 0; i < 8; i++) {
                    const int k = i >> 1, h = i & 1;
                    xw[k][h] = prmt_v(k < 2 ? xc[2 * h].x : xc[2 * h].y, k < 2 ? xc[2 * h + 1].x : xc[2 * h + 1].y, (k & 1) ? 0x7632 : 0x5410);
                }
                const uint32_t ub = mov_v(sb + SM_U + UPAD * 16 + ((tid >> 1) & 1) * ULO_B + (tid >> 2) * 16 + (tid & 1) * 8), tag = ep << 31;
                int it = 0;
                while (min(min((int)(uv0.x ^ tag), (int)(uv0.y ^ tag)), min((int)(uv0.z ^ tag), (int)(uv0.w ^ tag))) < 0x10000) {
                    if (++it > SPIN_LIMIT) TRAP();
                    uv0 = ld_poll(usrc);
                }
                STAMP(8);
                STAMPX(26);
                const float r0 = rcp_approx(fabsf(bf_hi(uv0.x))), r1 = rcp_approx(fabsf(bf_hi(uv0.y))), r2 = rcp_approx(fabsf(bf_hi(uv0.z))), r3 = rcp_approx(fabsf(bf_hi(uv0.w)));
                const uint32_t m[2] = {__byte_perm(uv0.x, uv0.y, 0x5410), __byte_perm(uv0.z, uv0.w, 0x5410)};
                const uint32_t rh[2] = {pack_bf16(r0, r1), pack_bf16(r2, r3)};
                const uint32_t rl[2] = {pack_bf16(r0 - bf_lo(rh[0]), r1 - bf_hi(rh[0])), pack_bf16(r2 - bf_lo(rh[1]), r3 - bf_hi(rh[1]))};
#pragma unroll
                for (int k = 0; k < 4; k++) {
                    const uint32_t u0 = ln_apply(xw[k][0], m[0], rh[0], rl[0]), u1 = ln_apply(xw[k][1], m[1], rh[1], rl[1]);
                    sts64(ub + k * USLOT_B, pack_f16(bf_lo(u0), bf_hi(u0)), pack_f16(bf_lo(u1), bf_hi(u1)));
                }
                STAMPX(29);
                fence_async();
                bar_sync(14, 512);
                STAMP(7);
            });
        } else {
            auto stage = [&]() {
                const uint32_t tag = (ep % 7u + 1u) * 0x10001u;
                int it = 0;
                WPOINT(4, warp == 19);
                if (!UE) { first_poll(UDLY); uv1 = ld_poll(usrc + 512); }
                if (!UE) WPOINT(5, warp == 19);
                while (true) {
                    uv0.x ^= tag; uv0.y ^= tag; uv0.z ^= tag; uv0.w ^= tag; uv1.x ^= tag; uv1.y ^= tag; uv1.z ^= tag; uv1.w ^= tag;
                    if ((((uv0.x | uv0.y | uv0.z) | (uv0.w | uv1.x | uv1.y) | (uv1.z | uv1.w)) & 0x70007u) == 0) break;
                    if (++it > SPIN_LIMIT) TRAP();
                    uv0 = ld_poll(usrc); uv1 = ld_poll(usrc + 512);
                }
                STAMP(8);
                const uint32_t ub = sb + SM_U + UPAD * 16 + 4 * USLOT_B + (t128 & 1) * ULO_B + (t128 >> 1) * 16;
                sts128(ub, uv0.x, uv0.y, uv0.z, uv0.w);
                sts128(ub + 1024, uv1.x, uv1.y, uv1.z, uv1.w);
                fence_async();
                asm volatile("barrier.cluster.arrive.relaxed.aligned;\n" ::: "memory");
                bar_sync(5, 128);
                if (UE) WPOINT(5, warp == 19);
                STAMP(7);
            };
            stage();
            if (odd) conv_inner(c, pln + wq * 128, gy, sb + SM_RX, hook);
            else conv_outer(c, pln + wq * 128, gy, sb + SM_RX, hook);
        }
        STAMP(10);
    }
    {
    const int lane = lane_v(), tid = 32 * warp + lane, g = lane >> 2, t = lane & 3;
    const uint32_t par = ~ep & 1u;
    bar_sync(0, NWRK);
    STAMP(11);
    uint32_t H[2][4] = {}, U2[2][4] = {};
    auto publish = [&](bool hi, int slot) {
        uint4* rowp = reinterpret_cast<uint4*>(p.s->rows) + slot * 144 + warp * 4 + t;
        stg128(rowp, nzw(hi ? U2[1][0] : U2[0][0]), nzw(hi ? U2[1][1] : U2[0][1]), nzw(hi ? U2[1][2] : U2[0][2]), nzw(hi ? U2[1][3] : U2[0][3]));
        stg128(rowp + 72, nzw(hi ? H[1][0] : H[0][0]), nzw(hi ? H[1][1] : H[0][1]), nzw(hi ? H[1][2] : H[0][2]), nzw(hi ? H[1][3] : H[0][3]));
    };
#define KTOK(k) (int)(((~(k) >> 5) & 0x7f0u) | (((k) >> 1) & 15u))
#define KLATE(k) (((k) & 0x1e0u) < 0xe0u)
#define KSLOT(k, s) (KLATE(k) ? 2 * NCTA + (s) : (int)(((k) >> 8) & 0xffu))
    const uint4* const rsrc = reinterpret_cast<const uint4*>(p.s->rows) + 36 * odd;
    auto gather = [&](uint32_t mine) {
        int it = 0;
        uint32_t mn;
        do {
            mn = 1;
#pragma unroll 1
            for (int r = 0; r < 9; r++) {
                const uint32_t k = __shfl_sync(0xffffffffu, mine, r < 8 ? 4 * r : lane);
                const int row = r < 8 ? r : g, c = r < 8 ? lane : 32 + t;
                asm volatile("cp.async.cg.shared.global [%0], [%1], 16;\n" ::"r"(sb + SM_XS + row * XS_PITCH + c * 16), "l"(rsrc + KSLOT(k, row) * 144 + c) : "memory");
            }
            asm volatile("cp.async.wait_all;\n" ::: "memory");
#pragma unroll 1
            for (int r = 0; r < 9; r++) mn = min(mn, min4(lds128(sb + SM_XS + (r < 8 ? r * XS_PITCH + lane * 16 : g * XS_PITCH + (32 + t) * 16))));
            if (++it > SPIN_LIMIT) TRAP();
        } while (__any_sync(0xffffffffu, mn == 0));
    };
    auto late_rows = [&](auto role) {
        const uint32_t kk = lds32(s_key + (lane & 7) * 4), ep = lds32(s_cnt + 4);
        const bool own = KLATE(kk) && (KTOK(kk) >> 4) == b;
        uint32_t todo = __ballot_sync(0xffffffffu, own) & 0xffu;
        if (decltype(role)::value == 0 && todo) {
#pragma unroll
            for (int hf = 0; hf < 2; hf++) {
                const uint4 h = lds128(sb + SM_U + hf * 9216 + tid * 16);
                const uint2 st = lds64(s_stat + (g + 8 * hf) * 8);
                H[hf][0] = h.x; H[hf][1] = h.y; H[hf][2] = h.z; H[hf][3] = h.w;
#pragma unroll
                for (int k = 0; k < 4; k++) U2[hf][k] = ln_apply(H[hf][k], STAT_M(st), STAT_H(st), STAT_L(st));
            }
#pragma unroll 1
            while (todo) {
                const int s = __ffs(todo) - 1, tk = KTOK(__shfl_sync(0xffffffffu, kk, s));
                todo &= todo - 1;
                if ((tk & 13) == TOK(g)) publish(tk & 2, 2 * NCTA + s);
            }
            __threadfence();
        }
        bar_sync(0, NWRK);
        if (decltype(role)::value == 1) {
            if (lane < NSEL && own) *reinterpret_cast<volatile unsigned*>(p.s->flag + lane) = ep + 1u;
            int it = 0;
            while (__any_sync(0xffffffffu, KLATE(kk) && ld_acquire32(p.s->flag + (lane & 7)) != ep + 1u)) { if (++it > SPIN_LIMIT) TRAP(); }
            gather(__shfl_sync(0xffffffffu, kk, g));
        }
        bar_sync(0, NWRK);
    };
    if (warp < 18) {
        const unsigned char* ys = reinterpret_cast<const unsigned char*>(p.s->y) + (b < 32 * YQ ? (par ^ 1u) * (NCTA * 18432u) : 0u) +
                                  ((P * DM + 32 * warp + 8 * (g >> 1) + (g & 1)) * 64 + odd * 32 + t * 8);
        uint2 yv[4];
        const bool early = b < 64 && warp < 16;
        if (early) {
#pragma unroll
            for (int k = 0; k < 4; k++) yv[k] = ld_poll64(ys + k * 128);
        }
        mbar_wait(bar_v);
        const uint32_t xa = sb + SM_XT + warp * 64 + t * 16;
        const uint4 x0 = lds128(xa + TOK(g) * 1152), x1 = lds128(xa + (TOK(g) + 2) * 1152), dk = lds128(xa + 16 * 1152);
        uint4 wr = make_uint4(0u, 0u, 0u, 0u);
        if (g == 0) wr = lds128(xa + 17 * 1152);
        const uint32_t Z[2][4] = {{x0.x, x0.y, x0.z, x0.w}, {x1.x, x1.y, x1.z, x1.w}}, D4[4] = {dk.x, dk.y, dk.z, dk.w};
#pragma unroll
        for (int hf = 0; hf < 2; hf++) {
            const uint2 st = lds64(s_stat + (g + 8 * hf) * 8);
#pragma unroll
            for (int k = 0; k < 4; k++) U2[hf][k] = hmul2_bf(ln_apply(Z[hf][k], STAT_M(st), STAT_H(st), STAT_L(st)), D4[k]);
        }
        const uint32_t la = pin(sb + SM_LNP + (g * 20 + warp) * 4 + (U2[0][3] & U2[1][3] & (warp >> 8)));
        int it = 0;
        float d[2][4];
        uint32_t mn;
        do {
            if (!early || it) {
#pragma unroll
                for (int k = 0; k < 4; k++) yv[k] = ld_poll64(ys + k * 128);
            }
            if (++it > SPIN_LIMIT) TRAP();
            mn = min(min(min(yv[0].x, yv[0].y), min(yv[1].x, yv[1].y)), min(min(yv[2].x, yv[2].y), min(yv[3].x, yv[3].y)));
#pragma unroll
            for (int k = 0; k < 4; k++) {
                H[0][k] = hadd2_bf(Z[0][k], hadd2_bf(movm(yv[k].x), U2[0][k]));
                H[1][k] = hadd2_bf(Z[1][k], hadd2_bf(movm(yv[k].y), U2[1][k]));
            }
            ln_partial(H, d);
        } while (__any_sync(0xffffffffu, mn == 0));
        STAMP(12);
        if (t == (g >> 1)) {
            stsf(la, (g & 1) ? d[0][3] : d[0][2]); stsf(la + 8 * 80, (g & 1) ? d[1][3] : d[1][2]);
            stsf(la + 16 * 80, (g & 1) ? d[0][1] : d[0][0]); stsf(la + 24 * 80, (g & 1) ? d[1][1] : d[1][0]);
        }
        bar_arrive(6, NWRK);
        STAMP(13);
        bar_sync(7, 608);
        STAMP(14);
#pragma unroll
        for (int hf = 0; hf < 2; hf++) {
            const uint2 st = lds64(s_stat + (g + 8 * hf) * 8);
#pragma unroll
            for (int k = 0; k < 4; k++) U2[hf][k] = ln_apply(H[hf][k], STAT_M(st), STAT_H(st), STAT_L(st));
        }
        {
            float cs[4] = {0.f, 0.f, 0.f, 0.f};
            mma_bf16(cs, U2[0][0], U2[1][0], U2[0][1], U2[1][1], wr.x, wr.y);
            mma_bf16(cs, U2[0][2], U2[1][2], U2[0][3], U2[1][3], wr.z, wr.w);
            if (t == 0) { stsf(la + 32 * 80, cs[0]); stsf(la + 40 * 80, cs[2]); }
            bar_arrive(8, 608);
        }
        bar_sync(9, 608);
        {
            const uint2 best = lds64(s_rank);
            uint32_t todo = ((best.x & 26u) == 2 * TOK(g) ? 2u : 0u) | ((best.y & 26u) == 2 * TOK(g) ? 1u : 0u);
#pragma unroll 1
            while (todo) { publish((todo & 2u ? best.x : best.y) & 4u, 254 - 2 * b + (todo >> 1)); todo &= todo >> 1; }
        }
#pragma unroll
        for (int hf = 0; hf < 2; hf++) {
            sts128(sb + SM_OUT + (TOK(g) + 2 * hf) * (DM * 2) + warp * 64 + t * 16,
                   hadd2_bf(H[hf][0], U2[hf][0]), hadd2_bf(H[hf][1], U2[hf][1]), hadd2_bf(H[hf][2], U2[hf][2]), hadd2_bf(H[hf][3], U2[hf][3]));
            sts128(sb + SM_U + hf * 9216 + tid * 16, H[hf][0], H[hf][1], H[hf][2], H[hf][3]);
        }
        STAMP(15);
        const int mi = lane >> 3, rr = lane & 7;
        const bool gate = warp < 12 && (warp & 3) != 2;
        const int fj = gate ? 3 * (warp >> 2) + min(warp & 3, 2) : (warp < 12 ? warp >> 2 : warp - 9);
        if (gate) {
            uint32_t W[18][4];
            mbar_wait(bar_w);
            const uint32_t aad = sb + SM_WG + (mi & 1) * SM_WU + (rr + 8 * (mi >> 1)) * W_PITCH + fj * 16;
#pragma unroll
            for (int k = 0; k < 18; k++) ldsm_x4_t(W[k][0], W[k][1], W[k][2], W[k][3], aad + k * 16 * W_PITCH);
            const uint32_t bad = pin(sb + SM_XS + rr * XS_PITCH + mi * 16);
            fence_async();
            STAMP2(17);
            if (bar_or(11, NWRK, false)) {
                late_rows(IC<0>());
#pragma unroll
                for (int k = 0; k < 18; k++) ldsm_x4_t(W[k][0], W[k][1], W[k][2], W[k][3], aad + k * 16 * W_PITCH);
            }
            STAMP2(19);
            float c4[2][4] = {};
#pragma unroll
            for (int k = 0; k < 18; k += 2) {
                uint32_t b0, b1, b2, b3;
                ldsm_x4(b0, b1, b2, b3, bad + k * 32);
                mma_bf16(c4[0], W[k][0], W[k][1], W[k][2], W[k][3], b0, b1);
                mma_bf16(c4[1], W[k + 1][0], W[k + 1][1], W[k + 1][2], W[k + 1][3], b2, b3);
            }
            const uint32_t ex = sb + SM_EX + (32 * fj + lane) * 16;
            const float e0 = c4[0][0] + c4[1][0], e1 = c4[0][1] + c4[1][1], e2 = c4[0][2] + c4[1][2], e3 = c4[0][3] + c4[1][3];
            asm volatile("st.async.shared::cluster.mbarrier::complete_tx::bytes.v4.f32 [%0], {%1,%2,%3,%4}, [%5];\n"
                         ::"r"(ex ^ 0x1000000u), "f"(e0), "f"(e1), "f"(e2), "f"(e3), "r"(bar_g ^ 0x1000000u) : "memory");
            STAMP2(20);
            mbar_wait(bar_g);
            const uint4 o = lds128(ex);
            const uint32_t G = pack_bf16(e0 + __uint_as_float(o.x), e1 + __uint_as_float(o.y)), U = pack_bf16(e2 + __uint_as_float(o.z), e3 + __uint_as_float(o.w));
            sts32(sb + SM_GU + (32 * fj + lane) * 4, hmul2_bf(pack_bf16(bf_lo(G) * sigmoid_f(bf_lo(G)), bf_hi(G) * sigmoid_f(bf_hi(G))), U));
            bar_arrive(13, NWRK);
        } else {
            uint32_t W[2][18];
            auto load_wd = [&]() {
                mbar_wait(bar_d);
                const uint32_t base = sb + SM_WD + (4 * fj + (mi & 1)) * 16 + rr * WD_PITCH;
#pragma unroll
                for (int j = 0; j < 2; j++) {
#pragma unroll
                    for (int k = 0; k < 4; k++) ldsm_x4_t(W[j][4 * k], W[j][4 * k + 1], W[j][4 * k + 2], W[j][4 * k + 3], base + j * 32 + (k * 16 + 8 * (mi >> 1)) * WD_PITCH);
                    ldsm_x2_t(W[j][16], W[j][17], base + j * 32 + 64 * WD_PITCH);
                }
            };
            const uint32_t po = pin((((8 * (18 * odd + 2 * fj) + g) * 64 + P) * 16 + t * 4) * 4);
            fence_async();
            STAMP2(17);
            if (bar_or(11, NWRK, false)) late_rows(IC<0>());
            delay(DDLY); load_wd();
            bar_sync(13, NWRK);
            STAMP2(21);
            uint32_t gb[9];
            ldsm_x4_t(gb[0], gb[1], gb[2], gb[3], sb + SM_GU + lane * 16);
            ldsm_x4_t(gb[4], gb[5], gb[6], gb[7], sb + SM_GU + 512 + lane * 16);
            ldsm_x1_t(gb[8], sb + SM_GU + 1024 + lane * 16);
            float c4[2][4] = {}, d4[2][4] = {};
#pragma unroll
            for (int k = 0; k < 4; k += 2)
#pragma unroll
                for (int j = 0; j < 2; j++) {
                    mma_bf16(c4[j], W[j][4 * k], W[j][4 * k + 1], W[j][4 * k + 2], W[j][4 * k + 3], gb[2 * k], gb[2 * k + 1]);
                    mma_bf16(d4[j], W[j][4 * k + 4], W[j][4 * k + 5], W[j][4 * k + 6], W[j][4 * k + 7], gb[2 * k + 2], gb[2 * k + 3]);
                }
#pragma unroll
            for (int j = 0; j < 2; j++) mma_bf16_k8(c4[j], W[j][16], W[j][17], gb[8]);
#pragma unroll
            for (int j = 0; j < 2; j++)
                stg128(reinterpret_cast<unsigned char*>(p.s->part) + po + j * 32768, __float_as_uint(c4[j][0] + d4[j][0]) | 1u, __float_as_uint(c4[j][1] + d4[j][1]) | 1u,
                       __float_as_uint(c4[j][2] + d4[j][2]) | 1u, __float_as_uint(c4[j][3] + d4[j][3]) | 1u);
        }
        STAMP2(22);
    } else if (warp == 18) {
        const uint4* const ksrc = reinterpret_cast<const uint4*>(p.s->key3) + pin(2 * lane);
        const unsigned char* const rl = reinterpret_cast<const unsigned char*>(rsrc) + pin(lane * 16);
        const uint32_t sa = pin(sb + SM_LNP + lane * 80);
        const uint32_t klo = pin((uint32_t)(127 - b) << 9 | (uint32_t)(15 - ROWTOK(lane & 15)) << 1 | par), ra = pin(sb + SM_LNP + (32 + (lane & 15)) * 80);
        uint4* const kdst = reinterpret_cast<uint4*>(p.s->key3) + pin((lane >> 1) * 2 * NCTA + 2 * b + (lane & 1));
        FIX(ra);
        bar_sync(6, NWRK);
        {
            float mb, rc;
            ln_finish(sum18(sa), lane, mb, rc);
            if (lane < 16) stat_store(s_stat + lane * 8, mb, rc, 0u);
        }
        bar_arrive(7, 608);
        bar_sync(8, 608);
        uint32_t t0;
        {
            const uint32_t bits = __float_as_uint(rbf(sum18(ra)));
            const uint32_t me = ((bits ^ ((uint32_t)((int)bits >> 31) | 0x80000000u)) & 0xffff0000u) | klo;
            const uint32_t k0 = __reduce_max_sync(0xffffffffu, me), k1 = __reduce_max_sync(0xffffffffu, me == k0 ? 0u : me);
            const uint32_t k2 = __reduce_max_sync(0xffffffffu, me >= k1 ? 0u : me);
            if (lane < 2) stg128(kdst, k0 ^ 0x11eu, k1 ^ 0xfeu, k2 ^ 0xdeu, par);
            asm volatile("mov.u32 %0, %%clock;" : "=r"(t0) :: "memory");
            STAMPW(23);
            if (lane == 0) sts64(s_rank, ~k0, ~k1);
            bar_arrive(9, 608);
            sts32(s_k16 + (lane & 15) * 4, me);
            __syncwarp();
            const uint4 v = lds128(s_k16 + (lane & 16) * 2), w = lds128(s_k16 + (lane & 16) * 2 + 16);
            int rank = ((v.x > me) + (v.y > me)) + ((v.z > me) + (v.w > me)) + (((w.x > me) + (w.y > me)) + ((w.z > me) + (w.w > me)));
            rank += __shfl_xor_sync(0xffffffffu, rank, 16);
            if (lane < 16 && rank < 8) p.s->key[8 * b + rank] = (me ^ 0x1eu) | ((8 - rank) << 5);
        }
        uint4 kq[4];
        uint32_t u[4], mine = 0, m;
        int it = 0;
        { uint32_t now; do { asm volatile("mov.u32 %0, %%clock;" : "=r"(now) :: "memory"); } while (now - t0 < KDLY); }
        do {
#pragma unroll
            for (int i = 0; i < 4; i++) kq[i] = ld_poll(ksrc + 64 * i);
            if (++it > SPIN_LIMIT) TRAP();
            uint32_t S[2][4];
#pragma unroll
            for (int i = 0; i < 2; i++) {
                const uint4 &c = kq[2 * i], &d = kq[2 * i + 1];
                const uint32_t m1 = min(c.x, d.x), m2 = max(c.y, d.y);
                S[i][0] = max(c.x, d.x); S[i][1] = max(m1, m2); S[i][2] = min(m1, m2); S[i][3] = min(c.y, d.y);
            }
            const uint32_t a0 = max(S[0][0], S[1][3]), a1 = max(S[0][1], S[1][2]), a2 = max(S[0][2], S[1][1]), a3 = max(S[0][3], S[1][0]);
            const uint32_t b0 = max(a0, a2), b2 = min(a0, a2), b1 = max(a1, a3), b3 = min(a1, a3);
            u[0] = max(b0, b1); u[1] = min(b0, b1); u[2] = max(b2, b3); u[3] = min(b2, b3);
        } while (__any_sync(0xffffffffu, and3(or3(or3(xor_or(kq[0].x, kq[0].y, par), xor_or(kq[0].z, kq[1].x, par), xor_or(kq[1].y, kq[1].z, par)),
                                                  xor_or(kq[2].x, kq[2].y, par), xor_or(kq[2].z, kq[3].x, par)) | xor_or(kq[3].y, kq[3].z, par), 1u, 1u)));
        STAMPW(16);
        uint4 v[9];
#pragma unroll
        for (int r = 0; r < 8; r++) {
            m = __reduce_max_sync(0xffffffffu, u[0]);
            if (u[0] == m) { u[0] = u[1]; u[1] = u[2]; u[2] = u[3]; u[3] = 0; }
            if (g == r) mine = m;
            v[r] = ld_poll(rl + (size_t)((m >> 8) & 0xffu) * 2304u);
        }
        v[8] = ld_poll(reinterpret_cast<const unsigned char*>(rsrc) + (((mine >> 8) & 0xffu) * 2304u + (32 + t) * 16));
        bool again = __any_sync(0xffffffffu, u[0] == 0 || max(max(kq[0].z, kq[1].z), max(kq[2].z, kq[3].z)) > m);
        if (again) {
#pragma unroll 1
            for (int i = 0; i < 8; i++) {
                uint4 k;
                do { k = ld_poll(reinterpret_cast<const uint4*>(p.s->key) + 32 * i + lane); if (++it > SPIN_LIMIT) TRAP(); } while (((k.x ^ par) | (k.y ^ par) | (k.z ^ par) | (k.w ^ par)) & 1u);
                sts128(sb + SM_KEYS + (32 * i + lane) * 16, k.x, k.y, k.z, k.w);
            }
            m = 0xffffffffu;
#pragma unroll 1
            for (int r = 0; r < 8; r++) {
                uint32_t c = 0;
#pragma unroll 2
                for (int i = 0; i < 8; i++) {
                    const uint4 k = lds128(sb + SM_KEYS + (32 * i + lane) * 16);
                    c = max(max(c, k.x < m ? k.x : 0u), max(k.y < m ? k.y : 0u, max(k.z < m ? k.z : 0u, k.w < m ? k.w : 0u)));
                }
                m = __reduce_max_sync(0xffffffffu, c);
                if (g == r) mine = m;
            }
        }
        if (t == 0) sts32(s_key + g * 4, mine);
        uint32_t mn = 1;
#pragma unroll
        for (int r = 0; r < 9; r++) {
            sts128(sb + SM_XS + (r < 8 ? r * XS_PITCH + lane * 16 : g * XS_PITCH + (32 + t) * 16), v[r].x, v[r].y, v[r].z, v[r].w);
            mn = min(mn, min4(v[r]));
        }
        if ((again || __any_sync(0xffffffffu, mn == 0)) && !__any_sync(0xffffffffu, KLATE(mine))) gather(mine);
        STAMPW(18);
        if (bar_or(11, NWRK, KLATE(mine))) late_rows(IC<1>());
    } else {
        bar_sync(6, NWRK);
        WPOINT(16, true);
        if (WANY(17) || WANY(18)) delay(WDLY);
        WPOINT(17, true);
        if (WANY(18)) delay(WDLY);
        WPOINT(18, true);
        if (bar_or(11, NWRK, false)) late_rows(IC<2>());
        const int tk = KTOK(lds32(s_key + (lane & 7) * 4));
        const uint32_t sel = __reduce_or_sync(0xffffffffu, (tk >> 4) == b ? 1u << (tk & 15) : 0u);
        if (sel ? lane < 16 && !((sel >> lane) & 1u) : lane == 0) bulk_s2g(p.out + (size_t)(16 * b + lane) * DM, sb + SM_OUT + lane * (DM * 2), sel ? DM * 2 : 16 * DM * 2);
        __syncwarp();
    }
    if (warp == 8 || warp >= 18) {
        const int grp = 3 * b + (warp == 8 ? 0 : warp - 17), fsl = 2 * t + ((lane >> 3) & 1), fc = 16 * (grp >> 3) + (grp & 7) + 8 * (lane >> 4);
        const uint32_t fk = lds32(s_key + fsl * 4);
        float hv = 0.f, u2 = 0.f;
        int it = 0;
        if (b < 96) {
            const uint32_t* const fsrc = p.s->rows + KSLOT(fk, fsl) * DM + (fc >> 1);
            uint32_t hw, uw;
            do { hw = ld_poll32(fsrc + 288); uw = ld_poll32(fsrc); if (++it > SPIN_LIMIT) TRAP(); } while (!hw || !uw);
            hv = (fc & 1) ? bf_hi(hw) : bf_lo(hw); u2 = (fc & 1) ? bf_hi(uw) : bf_lo(uw);
        }
        const float rs = rbf(sigmoid_f(__uint_as_float((fk ^ ((uint32_t)((int)~fk >> 31) | 0x80000000u)) & 0xffff0000u)));
        const uint32_t dof = pin(KTOK(fk) * DM + fc), so = pin(grp * 256 + lane);
        if (warp > 17) bar_sync(13, NWRK);
        if (b < 96) {
            delay(warp > 17 ? FDLY : FDLY2);
            const uint4* src = reinterpret_cast<const uint4*>(p.s->part) + so;
            float s0, s1, s2, s3;
            uint32_t ok;
            do {
                uint4 a[8];
#pragma unroll
                for (int i = 0; i < 8; i++) a[i] = ld_poll(src + 32 * i);
                if (++it > SPIN_LIMIT) TRAP();
#define A4(i) and3(and3(a[i].x, a[i].y, a[i].z), and3(a[i].w, a[i + 1].x, a[i + 1].y), a[i + 1].z & a[i + 1].w)
#define S8(f) (((__uint_as_float(a[0].f) + __uint_as_float(a[1].f)) + (__uint_as_float(a[2].f) + __uint_as_float(a[3].f))) + \
               ((__uint_as_float(a[4].f) + __uint_as_float(a[5].f)) + (__uint_as_float(a[6].f) + __uint_as_float(a[7].f))))
                ok = and3(A4(0), A4(2), and3(A4(4), A4(6), 1u));
                s0 = S8(x); s1 = S8(y); s2 = S8(z); s3 = S8(w);
                asm volatile("" : "+f"(s0), "+f"(s1), "+f"(s2), "+f"(s3));
#undef A4
#undef S8
            } while (__any_sync(0xffffffffu, !ok));
            STAMP2(24);
            const bool up = lane & 16, od = lane & 8;
            const float r0 = (up ? s2 : s0) + __shfl_xor_sync(0xffffffffu, up ? s0 : s2, 16), r1 = (up ? s3 : s1) + __shfl_xor_sync(0xffffffffu, up ? s1 : s3, 16);
            float y = (od ? r1 : r0) + __shfl_xor_sync(0xffffffffu, od ? r0 : r1, 8);
            y += __shfl_xor_sync(0xffffffffu, y, 4);
            p.out[dof] = __float2bfloat16_rn(hv + rbf(u2 + rbf(rbf(y) * rs)));
        }
    }
    if (warp == 19) asm volatile("cp.async.bulk.wait_group.read 0;\n" ::: "memory");
    if (b == 0 && tid < 8) *reinterpret_cast<volatile unsigned*>(p.s->hint + tid * 32 + 1) = lds32(s_cnt + 4) + 1u;
    STAMP(25);
    }
}

typedef CUresult (*PFN_tmEncode)(CUtensorMap*, CUtensorMapDataType, cuuint32_t, void*, const cuuint64_t*, const cuuint64_t*, const cuuint32_t*,
                                 const cuuint32_t*, CUtensorMapInterleave, CUtensorMapSwizzle, CUtensorMapL2promotion, CUtensorMapFloatOOBfill);

extern "C" void kernel_launch(void* const* d_in, const int* in_sizes, int n_in, void* d_out, int out_size) {
    Params p;
    p.x = (const bf16*)d_in[0];
    p.lar = (const bf16*)d_in[1];
    p.aim = (const bf16*)d_in[2];
    p.cre = (const bf16*)d_in[3];
    p.cim = (const bf16*)d_in[4];
    p.ldt = (const bf16*)d_in[5];
    p.dsk = (const bf16*)d_in[6];
    p.wr = (const bf16*)d_in[8];
    p.wg = (const bf16*)d_in[9];
    p.wu = (const bf16*)d_in[10];
    p.wd = (const bf16*)d_in[11];
    p.out = (bf16*)d_out;
    static PFN_tmEncode enc = nullptr;
    static void* scratch = nullptr;
    if (!enc) {
        cudaFuncSetAttribute(fused_kernel, cudaFuncAttributeMaxDynamicSharedMemorySize, SMEM_TOTAL);
        void* fn = nullptr;
        cudaDriverEntryPointQueryResult qr;
        cudaGetDriverEntryPoint("cuTensorMapEncodeTiled", &fn, cudaEnableDefault, &qr);
        enc = (PFN_tmEncode)fn;
        cudaGetSymbolAddress(&scratch, g_scratch);
    }
    p.s = (Scratch*)scratch;
    CUtensorMap tm_g, tm_u, tm_d, tm_x;
    const cuuint64_t dims[2] = {FF, DM}, strides[1] = {FF * 2};
    const cuuint32_t box[2] = {72, 48}, es[2] = {1, 1};
    enc(&tm_g, CU_TENSOR_MAP_DATA_TYPE_BFLOAT16, 2, d_in[9], dims, strides, box, es, CU_TENSOR_MAP_INTERLEAVE_NONE, CU_TENSOR_MAP_SWIZZLE_NONE,
        CU_TENSOR_MAP_L2_PROMOTION_NONE, CU_TENSOR_MAP_FLOAT_OOB_FILL_NONE);
    enc(&tm_u, CU_TENSOR_MAP_DATA_TYPE_BFLOAT16, 2, d_in[10], dims, strides, box, es, CU_TENSOR_MAP_INTERLEAVE_NONE, CU_TENSOR_MAP_SWIZZLE_NONE,
        CU_TENSOR_MAP_L2_PROMOTION_NONE, CU_TENSOR_MAP_FLOAT_OOB_FILL_NONE);
    const cuuint64_t ddims[2] = {DM / 2, FF}, dstrides[1] = {DM * 2};
    const cuuint32_t dbox[2] = {WD_PITCH / 4, 8};
    enc(&tm_d, CU_TENSOR_MAP_DATA_TYPE_UINT32, 2, d_in[11], ddims, dstrides, dbox, es, CU_TENSOR_MAP_INTERLEAVE_NONE, CU_TENSOR_MAP_SWIZZLE_NONE,
        CU_TENSOR_MAP_L2_PROMOTION_NONE, CU_TENSOR_MAP_FLOAT_OOB_FILL_NONE);
    const cuuint64_t xdims[4] = {DM, 128, 4, 4}, xstrides[3] = {DM * 8, DM * 2, DM * 1024};
    const cuuint32_t xbox[4] = {8, 128, 4, 2}, xes[4] = {1, 1, 1, 1};
    enc(&tm_x, CU_TENSOR_MAP_DATA_TYPE_BFLOAT16, 4, d_in[0], xdims, xstrides, xbox, xes, CU_TENSOR_MAP_INTERLEAVE_NONE, CU_TENSOR_MAP_SWIZZLE_NONE,
        CU_TENSOR_MAP_L2_PROMOTION_NONE, CU_TENSOR_MAP_FLOAT_OOB_FILL_NONE);
    fused_kernel<<<NCTA, NTHR, SMEM_TOTAL>>>(p, tm_g, tm_u, tm_d, tm_x);
}
```

```cpp
#include <cuda_runtime.h>
#include <cuda.h>
#include <cuda_fp16.h>
#include <cuda_bf16.h>
#include <stdint.h>

#define LSEQ 2048
#define DM 576
#define NST 128
#define FF 4608
#define NSEL 8
#define NCTA 128
#define NTHR 640
#define NWRK 640

typedef __nv_bfloat16 bf16;

#define SM_WG 0
#define SM_WU 41472
#define SM_XC (82944 - 32768)
#define SM_WD 82944
#define W_PITCH 144
#define WD_PITCH 592
#define SM_Z2 (SM_WD + 10240)
#define SM_XT (SM_PL - 18 * 1152)
#define SM_PL (SM_WD + 46080)
#define PL_HALF 1344
#define PLW_B 2624
#define PL_B (4 * PLW_B)
#define SM_U (SM_PL + 5 * PL_B)
#define UPAD 20
#define ULO_B ((UPAD + 128) * 16)
#define USLOT_B (2 * ULO_B)
#define SM_KW (SM_U + 5 * USLOT_B)
#define KW_B 3712
#define KW_PL 1216
#define KW_P 2400
#define KW_H 3440
#define SM_MISC (SM_KW + 5 * KW_B)
#define SM_LC (SM_MISC + 416)
#define SM_LNP (SM_LC + 768)
#define SM_RX (SM_LNP + 3840)
#define SMEM_TOTAL (SM_RX + 3088)
#define TBW PLW_B
#define SM_OUT SM_PL
#define SM_XS (SM_PL + 18432)
#define XS_PITCH 592
#define SM_GU (SM_PL + 23296)
#define SM_EX (SM_PL + 24576)
#define SM_KEYS SM_KW

struct __align__(128) Scratch {
    unsigned hint[8 * 32];
    unsigned flag[32];
    uint32_t key3[NCTA * 8];
    uint32_t key[NCTA * 8];
    uint32_t stat[LSEQ];
    uint32_t uT[64 * (LSEQ / 2)];
    uint32_t y[(NCTA + 96) * DM * 8];
    uint32_t part[288 * 64 * 16];
    uint32_t rows[(2 * NCTA + NSEL) * DM];
};
__device__ Scratch g_scratch;
#define STAMP(i)
#define STAMPX(i)
#define STAMPY(i)

__device__ __forceinline__ float rbf(float x) {
    uint32_t r;
    asm("cvt.rn.bf16x2.f32 %0, %1, %2;\n" : "=r"(r) : "f"(x), "f"(0.f));
    return __uint_as_float(r);
}
__device__ __forceinline__ uint32_t pack_bf16(float lo, float hi) {
    uint32_t r;
    asm("cvt.rn.bf16x2.f32 %0, %1, %2;\n" : "=r"(r) : "f"(hi), "f"(lo));
    return r;
}
__device__ __forceinline__ uint32_t pack_f16(float lo, float hi) {
    uint32_t r;
    asm("cvt.rn.f16x2.f32 %0, %1, %2;\n" : "=r"(r) : "f"(hi), "f"(lo));
    return r;
}
__device__ __forceinline__ uint32_t pack_f16_rz(float lo, float hi) {
    uint32_t r;
    asm("cvt.rz.f16x2.f32 %0, %1, %2;\n" : "=r"(r) : "f"(hi), "f"(lo));
    return r;
}
__device__ __forceinline__ float bf_lo(uint32_t w) { return __uint_as_float(w << 16); }
__device__ __forceinline__ float bf_hi(uint32_t w) { return __uint_as_float(w & 0xffff0000u); }
__device__ __forceinline__ uint32_t hadd2_bf(uint32_t a, uint32_t b) {
    __nv_bfloat162 r = __hadd2_rn(*reinterpret_cast<__nv_bfloat162*>(&a), *reinterpret_cast<__nv_bfloat162*>(&b));
    return *reinterpret_cast<uint32_t*>(&r);
}
__device__ __forceinline__ uint32_t hsub2_bf(uint32_t a, uint32_t b) {
    __nv_bfloat162 r = __hsub2_rn(*reinterpret_cast<__nv_bfloat162*>(&a), *reinterpret_cast<__nv_bfloat162*>(&b));
    return *reinterpret_cast<uint32_t*>(&r);
}
__device__ __forceinline__ uint32_t hmul2_bf(uint32_t a, uint32_t b) {
    __nv_bfloat162 r = __hmul2_rn(*reinterpret_cast<__nv_bfloat162*>(&a), *reinterpret_cast<__nv_bfloat162*>(&b));
    return *reinterpret_cast<uint32_t*>(&r);
}
__device__ __forceinline__ uint32_t hfma2_bf(uint32_t a, uint32_t b, uint32_t c) { uint32_t r; asm("fma.rn.bf16x2 %0, %1, %2, %3;\n" : "=r"(r) : "r"(a), "r"(b), "r"(c)); return r; }
__device__ __forceinline__ uint32_t hmul2(uint32_t a, uint32_t b) { uint32_t r; asm("mul.rn.f16x2 %0, %1, %2;\n" : "=r"(r) : "r"(a), "r"(b)); return r; }
__device__ __forceinline__ uint32_t hadd2(uint32_t a, uint32_t b) { uint32_t r; asm("add.rn.f16x2 %0, %1, %2;\n" : "=r"(r) : "r"(a), "r"(b)); return r; }
__device__ __forceinline__ uint32_t hfma2(uint32_t a, uint32_t b, uint32_t c) { uint32_t r; asm("fma.rn.f16x2 %0, %1, %2, %3;\n" : "=r"(r) : "r"(a), "r"(b), "r"(c)); return r; }
__device__ __forceinline__ uint32_t hfms2(uint32_t a, uint32_t b, uint32_t c) {
    uint32_t r;
    asm("{\n.reg .b32 n;\nneg.f16x2 n, %2;\nfma.rn.f16x2 %0, %1, n, %3;\n}\n" : "=r"(r) : "r"(a), "r"(b), "r"(c));
    return r;
}
__device__ __forceinline__ uint32_t nzw(uint32_t w) { return max(w, 1u); }
__device__ __forceinline__ uint32_t nzf(float f) { const uint32_t w = __float_as_uint(f); return w ? w : 0x80000000u; }
__device__ __forceinline__ uint32_t smem_u32(const void* p) { return (uint32_t)__cvta_generic_to_shared(p); }
__device__ __forceinline__ uint32_t lds32(uint32_t addr) {
    uint32_t v;
    asm volatile("ld.shared.u32 %0, [%1];\n" : "=r"(v) : "r"(addr) : "memory");
    return v;
}
__device__ __forceinline__ uint32_t lds16(uint32_t addr) {
    unsigned short v;
    asm volatile("ld.shared.u16 %0, [%1];\n" : "=h"(v) : "r"(addr) : "memory");
    return v;
}
__device__ __forceinline__ uint2 lds64(uint32_t addr) {
    uint2 v;
    asm volatile("ld.shared.v2.u32 {%0,%1}, [%2];\n" : "=r"(v.x), "=r"(v.y) : "r"(addr) : "memory");
    return v;
}
__device__ __forceinline__ uint4 lds128(uint32_t addr) {
    uint4 v;
    asm volatile("ld.shared.v4.u32 {%0,%1,%2,%3}, [%4];\n" : "=r"(v.x), "=r"(v.y), "=r"(v.z), "=r"(v.w) : "r"(addr) : "memory");
    return v;
}
__device__ __forceinline__ float ldsf(uint32_t addr) { return __uint_as_float(lds32(addr)); }
__device__ __forceinline__ void sts32(uint32_t addr, uint32_t v) { asm volatile("st.shared.u32 [%0], %1;\n" ::"r"(addr), "r"(v) : "memory"); }
__device__ __forceinline__ void sts16(uint32_t addr, uint32_t v) { asm volatile("st.shared.u16 [%0], %1;\n" ::"r"(addr), "h"((unsigned short)v) : "memory"); }
__device__ __forceinline__ void stsf(uint32_t addr, float v) { sts32(addr, __float_as_uint(v)); }
__device__ __forceinline__ void sts64(uint32_t addr, uint32_t a, uint32_t b) { asm volatile("st.shared.v2.u32 [%0], {%1,%2};\n" ::"r"(addr), "r"(a), "r"(b) : "memory"); }
__device__ __forceinline__ void sts64f(uint32_t addr, float a, float b) { sts64(addr, __float_as_uint(a), __float_as_uint(b)); }
__device__ __forceinline__ void sts128(uint32_t addr, uint32_t a, uint32_t b, uint32_t c, uint32_t d) {
    asm volatile("st.shared.v4.u32 [%0], {%1,%2,%3,%4};\n" ::"r"(addr), "r"(a), "r"(b), "r"(c), "r"(d) : "memory");
}
__device__ __forceinline__ void sts128f(uint32_t addr, const float (&v)[4]) {
    sts128(addr, __float_as_uint(v[0]), __float_as_uint(v[1]), __float_as_uint(v[2]), __float_as_uint(v[3]));
}
__device__ __forceinline__ void ldsm_x4(uint32_t& r0, uint32_t& r1, uint32_t& r2, uint32_t& r3, uint32_t addr) {
    asm volatile("ldmatrix.sync.aligned.m8n8.x4.shared.b16 {%0,%1,%2,%3}, [%4];\n"
                 : "=r"(r0), "=r"(r1), "=r"(r2), "=r"(r3) : "r"(addr) : "memory");
}
__device__ __forceinline__ void ldsm_x4_t(uint32_t& r0, uint32_t& r1, uint32_t& r2, uint32_t& r3, uint32_t addr) {
    asm volatile("ldmatrix.sync.aligned.m8n8.x4.trans.shared.b16 {%0,%1,%2,%3}, [%4];\n"
                 : "=r"(r0), "=r"(r1), "=r"(r2), "=r"(r3) : "r"(addr) : "memory");
}
__device__ __forceinline__ void ldsm_x2_t(uint32_t& r0, uint32_t& r1, uint32_t addr) {
    asm volatile("ldmatrix.sync.aligned.m8n8.x2.trans.shared.b16 {%0,%1}, [%2];\n" : "=r"(r0), "=r"(r1) : "r"(addr) : "memory");
}
__device__ __forceinline__ void ldsm_x1_t(uint32_t& r0, uint32_t addr) {
    asm volatile("ldmatrix.sync.aligned.m8n8.x1.trans.shared.b16 {%0}, [%1];\n" : "=r"(r0) : "r"(addr) : "memory");
}
__device__ __forceinline__ void stsm_x4(uint32_t addr, uint32_t r0, uint32_t r1, uint32_t r2, uint32_t r3) {
    asm volatile("stmatrix.sync.aligned.m8n8.x4.shared.b16 [%0], {%1,%2,%3,%4};\n" ::"r"(addr), "r"(r0), "r"(r1), "r"(r2), "r"(r3) : "memory");
}
__device__ __forceinline__ void stsm_x4_t(uint32_t addr, uint32_t r0, uint32_t r1, uint32_t r2, uint32_t r3) {
    asm volatile("stmatrix.sync.aligned.m8n8.x4.trans.shared.b16 [%0], {%1,%2,%3,%4};\n" ::"r"(addr), "r"(r0), "r"(r1), "r"(r2), "r"(r3) : "memory");
}
__device__ __forceinline__ uint32_t movm(uint32_t a) {
    uint32_t d;
    asm volatile("movmatrix.sync.aligned.m8n8.trans.b16 %0, %1;\n" : "=r"(d) : "r"(a));
    return d;
}
__device__ __forceinline__ void mma_f16(float (&c)[4], uint32_t a0, uint32_t a1, uint32_t a2, uint32_t a3, uint32_t b0, uint32_t b1) {
    asm volatile(
        "mma.sync.aligned.m16n8k16.row.col.f32.f16.f16.f32 {%0,%1,%2,%3}, {%4,%5,%6,%7}, {%8,%9}, {%0,%1,%2,%3};\n"
        : "+f"(c[0]), "+f"(c[1]), "+f"(c[2]), "+f"(c[3])
        : "r"(a0), "r"(a1), "r"(a2), "r"(a3), "r"(b0), "r"(b1));
}
__device__ __forceinline__ void mma_bf16(float (&c)[4], uint32_t a0, uint32_t a1, uint32_t a2, uint32_t a3, uint32_t b0, uint32_t b1) {
    asm volatile(
        "mma.sync.aligned.m16n8k16.row.col.f32.bf16.bf16.f32 {%0,%1,%2,%3}, {%4,%5,%6,%7}, {%8,%9}, {%0,%1,%2,%3};\n"
        : "+f"(c[0]), "+f"(c[1]), "+f"(c[2]), "+f"(c[3])
        : "r"(a0), "r"(a1), "r"(a2), "r"(a3), "r"(b0), "r"(b1));
}
__device__ __forceinline__ void mma_bf16_k8(float (&c)[4], uint32_t a0, uint32_t a1, uint32_t b0) {
    asm volatile("mma.sync.aligned.m16n8k8.row.col.f32.bf16.bf16.f32 {%0,%1,%2,%3}, {%4,%5}, {%6}, {%0,%1,%2,%3};\n"
                 : "+f"(c[0]), "+f"(c[1]), "+f"(c[2]), "+f"(c[3]) : "r"(a0), "r"(a1), "r"(b0));
}
__device__ __forceinline__ void bar_sync(int id, int n) { asm volatile("bar.sync %0, %1;\n" ::"r"(id), "r"(n) : "memory"); }
__device__ __forceinline__ void bar_arrive(int id, int n) { asm volatile("bar.arrive %0, %1;\n" ::"r"(id), "r"(n) : "memory"); }
__device__ __forceinline__ bool bar_or(int id, int n, bool v) {
    uint32_t r;
    asm volatile("{\n.reg .pred p, q;\nsetp.ne.u32 p, %3, 0;\nbar.red.or.pred q, %1, %2, p;\nselp.u32 %0, 1, 0, q;\n}\n" : "=r"(r) : "r"(id), "r"(n), "r"((uint32_t)v) : "memory");
    return r;
}
__device__ __forceinline__ uint32_t and3(uint32_t a, uint32_t b, uint32_t c) { uint32_t r; asm("lop3.b32 %0, %1, %2, %3, 0x80;\n" : "=r"(r) : "r"(a), "r"(b), "r"(c)); return r; }
__device__ __forceinline__ uint32_t or3(uint32_t a, uint32_t b, uint32_t c) { uint32_t r; asm("lop3.b32 %0, %1, %2, %3, 0xfe;\n" : "=r"(r) : "r"(a), "r"(b), "r"(c)); return r; }
__device__ __forceinline__ uint32_t xor_or(uint32_t a, uint32_t b, uint32_t c) { uint32_t r; asm("lop3.b32 %0, %1, %2, %3, 0x7e;\n" : "=r"(r) : "r"(a), "r"(b), "r"(c)); return r; }
__device__ __forceinline__ uint32_t pin(uint32_t v) { uint32_t r; asm volatile("shfl.sync.bfly.b32 %0, %1, 0, 0x1f, 0xffffffff;\n" : "=r"(r) : "r"(v) : "memory"); return r; }
__device__ __forceinline__ uint4 ld_poll(const void* p) {
    uint4 v;
    asm volatile("ld.relaxed.gpu.global.v4.u32 {%0,%1,%2,%3}, [%4];\n" : "=r"(v.x), "=r"(v.y), "=r"(v.z), "=r"(v.w) : "l"(p) : "memory");
    return v;
}
__device__ __forceinline__ uint2 ld_poll64(const void* p) {
    uint2 v;
    asm volatile("ld.relaxed.gpu.global.v2.u32 {%0,%1}, [%2];\n" : "=r"(v.x), "=r"(v.y) : "l"(p) : "memory");
    return v;
}
__device__ __forceinline__ uint32_t ld_poll32(const void* p) {
    uint32_t v;
    asm volatile("ld.relaxed.gpu.global.u32 %0, [%1];\n" : "=r"(v) : "l"(p) : "memory");
    return v;
}
__device__ __forceinline__ uint32_t ld_acquire32(const void* p) {
    uint32_t v;
    asm volatile("ld.acquire.gpu.global.u32 %0, [%1];\n" : "=r"(v) : "l"(p) : "memory");
    return v;
}
__device__ __forceinline__ uint4 ldg128(const void* p) {
    uint4 v;
    asm volatile("ld.global.nc.v4.u32 {%0,%1,%2,%3}, [%4];\n" : "=r"(v.x), "=r"(v.y), "=r"(v.z), "=r"(v.w) : "l"(p));
    return v;
}
__device__ __forceinline__ uint2 ldg64(const void* p) {
    uint2 v;
    asm volatile("ld.global.nc.v2.u32 {%0,%1}, [%2];\n" : "=r"(v.x), "=r"(v.y) : "l"(p));
    return v;
}
__device__ __forceinline__ uint32_t ldg16(const void* p) {
    uint32_t v;
    asm volatile("ld.global.nc.u16 %0, [%1];\n" : "=r"(v) : "l"(p));
    return v;
}
__device__ __forceinline__ uint4 ldo128(const void* p) {
    uint4 v;
    asm volatile("ld.relaxed.cta.global.v4.u32 {%0,%1,%2,%3}, [%4];\n" : "=r"(v.x), "=r"(v.y), "=r"(v.z), "=r"(v.w) : "l"(p) : "memory");
    return v;
}
__device__ __forceinline__ uint2 ldo64(const void* p) {
    uint2 v;
    asm volatile("ld.relaxed.cta.global.v2.u32 {%0,%1}, [%2];\n" : "=r"(v.x), "=r"(v.y) : "l"(p) : "memory");
    return v;
}
__device__ __forceinline__ uint32_t ldo16(const void* p) {
    uint32_t v;
    asm volatile("ld.relaxed.cta.global.u16 %0, [%1];\n" : "=r"(v) : "l"(p) : "memory");
    return v;
}
__device__ __forceinline__ void stg128(void* p, uint32_t a, uint32_t b, uint32_t c, uint32_t d) {
    asm volatile("st.global.v4.u32 [%0], {%1,%2,%3,%4};\n" ::"l"(p), "r"(a), "r"(b), "r"(c), "r"(d) : "memory");
}
__device__ __forceinline__ void stg64(void* p, uint32_t a, uint32_t b) { asm volatile("st.global.v2.u32 [%0], {%1,%2};\n" ::"l"(p), "r"(a), "r"(b) : "memory"); }
__device__ __forceinline__ uint32_t min4(const uint4& v) { return min(min(v.x, v.y), min(v.z, v.w)); }
#define SPIN_LIMIT (1 << 21)
#define TRAP() __trap()
__device__ __forceinline__ void mbar_init(uint32_t bar, uint32_t cnt) { asm volatile("mbarrier.init.shared::cta.b64 [%0], %1;\n" ::"r"(bar), "r"(cnt) : "memory"); }
__device__ __forceinline__ void mbar_expect(uint32_t bar, uint32_t bytes) {
    asm volatile("mbarrier.arrive.expect_tx.shared::cta.b64 _, [%0], %1;\n" ::"r"(bar), "r"(bytes) : "memory");
}
__device__ __forceinline__ void mbar_arrive(uint32_t bar) { asm volatile("mbarrier.arrive.shared::cta.b64 _, [%0];\n" ::"r"(bar) : "memory"); }
__device__ __forceinline__ void mbar_wait_cluster(uint32_t bar) {
    asm volatile(
        "{\n.reg .pred p;\n"
        "W_%=:\n"
        "mbarrier.try_wait.parity.acquire.cluster.shared::cta.b64 p, [%0], 0;\n"
        "@!p bra W_%=;\n}\n" ::"r"(bar) : "memory");
}
__device__ __forceinline__ void mbar_wait(uint32_t bar) {
    asm volatile(
        "{\n.reg .pred p;\n"
        "W_%=:\n"
        "mbarrier.try_wait.parity.shared::cta.b64 p, [%0], 0;\n"
        "@!p bra W_%=;\n}\n" ::"r"(bar) : "memory");
}
__device__ __forceinline__ void mbar_wait1(uint32_t bar) {
    asm volatile(
        "{\n.reg .pred p;\n"
        "W_%=:\n"
        "mbarrier.try_wait.parity.shared::cta.b64 p, [%0], 1;\n"
        "@!p bra W_%=;\n}\n" ::"r"(bar) : "memory");
}
__device__ __forceinline__ bool mbar_test(uint32_t bar) {
    uint32_t r;
    asm volatile("{\n.reg .pred p;\nmbarrier.test_wait.parity.shared::cta.b64 p, [%1], 0;\nselp.u32 %0, 1, 0, p;\n}\n" : "=r"(r) : "r"(bar) : "memory");
    return __any_sync(0xffffffffu, r);
}
__device__ __forceinline__ void bulk_g2s(uint32_t dst, const void* src, uint32_t bytes, uint32_t bar) {
    asm volatile("cp.async.bulk.shared::cluster.global.mbarrier::complete_tx::bytes [%0], [%1], %2, [%3];\n" ::"r"(dst), "l"(src), "r"(bytes), "r"(bar) : "memory");
}
__device__ __forceinline__ void bulk_s2g(void* dst, uint32_t src, uint32_t bytes) {
    asm volatile("cp.async.bulk.global.shared::cta.bulk_group [%0], [%1], %2;\ncp.async.bulk.commit_group;\n" ::"l"(dst), "r"(src), "r"(bytes) : "memory");
}
__device__ __forceinline__ void bulk_s2g_nc(void* dst, uint32_t src, uint32_t bytes) {
    asm volatile("cp.async.bulk.global.shared::cta.bulk_group [%0], [%1], %2;\n" ::"l"(dst), "r"(src), "r"(bytes) : "memory");
}
__device__ __forceinline__ void tma_2d(uint32_t dst, const CUtensorMap* tm, int c0, int c1, uint32_t bar) {
    asm volatile("cp.async.bulk.tensor.2d.shared::cluster.global.mbarrier::complete_tx::bytes [%0], [%1, {%3, %4}], [%2];\n"
                 ::"r"(dst), "l"(tm), "r"(bar), "r"(c0), "r"(c1) : "memory");
}
__device__ __forceinline__ void tma_4d(uint32_t dst, const CUtensorMap* tm, int c0, int c3, uint32_t bar) {
    asm volatile("cp.async.bulk.tensor.4d.shared::cluster.global.mbarrier::complete_tx::bytes [%0], [%1, {%3, %4, %4, %5}], [%2];\n"
                 ::"r"(dst), "l"(tm), "r"(bar), "r"(c0), "r"(0), "r"(c3) : "memory");
}
__device__ __forceinline__ void tma_4d_mc(uint32_t dst, const CUtensorMap* tm, int c0, int c3, uint32_t bar) {
    asm volatile("cp.async.bulk.tensor.4d.shared::cluster.global.mbarrier::complete_tx::bytes.multicast::cluster [%0], [%1, {%3, %4, %4, %5}], [%2], %6;\n"
                 ::"r"(dst), "l"(tm), "r"(bar), "r"(c0), "r"(0), "r"(c3), "h"((unsigned short)3) : "memory");
}
__device__ __forceinline__ void l2_prefetch(const void* src, uint32_t bytes) {
    asm volatile("cp.async.bulk.prefetch.L2.global [%0], %1;\n" ::"l"(src), "r"(bytes) : "memory");
}
__device__ __forceinline__ bool elect_one() {
    uint32_t r;
    asm volatile("{\n.reg .pred p;\nelect.sync _|p, 0xffffffff;\nselp.u32 %0, 1, 0, p;\n}\n" : "=r"(r));
    return r;
}
__device__ __forceinline__ void delay(uint32_t clks) {
    uint32_t t0, t1;
    asm volatile("mov.u32 %0, %%clock;" : "=r"(t0) :: "memory");
    do { asm volatile("mov.u32 %0, %%clock;" : "=r"(t1) :: "memory"); } while (t1 - t0 < clks);
}
__device__ __forceinline__ void fence_async() { asm volatile("fence.proxy.async.shared::cta;\n" ::: "memory"); }

__device__ __forceinline__ float2 cmul(float2 a, float2 b) {
    return make_float2(fmaf(a.x, b.x, -a.y * b.y), fmaf(a.x, b.y, a.y * b.x));
}
__device__ __forceinline__ float2 csq(float2 a) {
    float p = a.x * a.y;
    return make_float2(fmaf(a.x, a.x, -a.y * a.y), p + p);
}
__device__ __forceinline__ float ex2_approx(float x) { float r; asm("ex2.approx.ftz.f32 %0, %1;\n" : "=f"(r) : "f"(x)); return r; }
__device__ __forceinline__ float exp_bf(float x) { return rbf(ex2_approx(__fmul_ru(x, 1.4426950408889634f))); }
__device__ __forceinline__ float2 cexp_e(float lr2, float li, float e) {
    const float m = ex2_approx(lr2 * e);
    return make_float2(m * __cosf(li * e), m * __sinf(li * e));
}
__device__ __forceinline__ float rcp_approx(float x) { float r; asm("rcp.approx.ftz.f32 %0, %1;\n" : "=f"(r) : "f"(x)); return r; }
__device__ __forceinline__ float sigmoid_f(float x) { return rcp_approx(1.0f + ex2_approx(x * -1.4426950408889634f)); }
__device__ __forceinline__ float sqrt_approx(float x) { float r; asm("sqrt.approx.ftz.f32 %0, %1;\n" : "=f"(r) : "f"(x)); return r; }

__device__ __forceinline__ void wg_fence() { asm volatile("wgmma.fence.sync.aligned;\n" ::: "memory"); }
__device__ __forceinline__ void wg_commit() { asm volatile("wgmma.commit_group.sync.aligned;\n" ::: "memory"); }
__device__ __forceinline__ void wg_wait0() { asm volatile("wgmma.wait_group.sync.aligned 0;\n" ::: "memory"); }
template <int T> __device__ __forceinline__ void wg_mma(float (&acc)[16][4], const uint32_t* a, uint64_t desc);
template <int T> __device__ __forceinline__ void wg_first(float (&acc)[16][4], const uint32_t* a, uint64_t desc);
template <> __device__ __forceinline__ void wg_mma<0>(float (&acc)[16][4], const uint32_t* a, uint64_t desc) {
    asm volatile("wgmma.mma_async.sync.aligned.m64n128k16.f32.f16.f16 {%0,%1,%2,%3,%4,%5,%6,%7,%8,%9,%10,%11,%12,%13,%14,%15,%16,%17,%18,%19,%20,%21,%22,%23,%24,%25,%26,%27,%28,%29,%30,%31,%32,%33,%34,%35,%36,%37,%38,%39,%40,%41,%42,%43,%44,%45,%46,%47,%48,%49,%50,%51,%52,%53,%54,%55,%56,%57,%58,%59,%60,%61,%62,%63}, {%64,%65,%66,%67}, %68, 1, 1, 1, 0;\n"
                 : "+f"(acc[0][0]), "+f"(acc[0][1]), "+f"(acc[0][2]), "+f"(acc[0][3]), "+f"(acc[1][0]), "+f"(acc[1][1]), "+f"(acc[1][2]), "+f"(acc[1][3]), "+f"(acc[2][0]), "+f"(acc[2][1]), "+f"(acc[2][2]), "+f"(acc[2][3]), "+f"(acc[3][0]), "+f"(acc[3][1]), "+f"(acc[3][2]), "+f"(acc[3][3]), "+f"(acc[4][0]), "+f"(acc[4][1]), "+f"(acc[4][2]), "+f"(acc[4][3]), "+f"(acc[5][0]), "+f"(acc[5][1]), "+f"(acc[5][2]), "+f"(acc[5][3]), "+f"(acc[6][0]), "+f"(acc[6][1]), "+f"(acc[6][2]), "+f"(acc[6][3]), "+f"(acc[7][0]), "+f"(acc[7][1]), "+f"(acc[7][2]), "+f"(acc[7][3]), "+f"(acc[8][0]), "+f"(acc[8][1]), "+f"(acc[8][2]), "+f"(acc[8][3]), "+f"(acc[9][0]), "+f"(acc[9][1]), "+f"(acc[9][2]), "+f"(acc[9][3]), "+f"(acc[10][0]), "+f"(acc[10][1]), "+f"(acc[10][2]), "+f"(acc[10][3]), "+f"(acc[11][0]), "+f"(acc[11][1]), "+f"(acc[11][2]), "+f"(acc[11][3]), "+f"(acc[12][0]), "+f"(acc[12][1]), "+f"(acc[12][2]), "+f"(acc[12][3]), "+f"(acc[13][0]), "+f"(acc[13][1]), "+f"(acc[13][2]), "+f"(acc[13][3]), "+f"(acc[14][0]), "+f"(acc[14][1]), "+f"(acc[14][2]), "+f"(acc[14][3]), "+f"(acc[15][0]), "+f"(acc[15][1]), "+f"(acc[15][2]), "+f"(acc[15][3])
                 : "r"(a[0]), "r"(a[1]), "r"(a[2]), "r"(a[3]), "l"(desc));
}
template <> __device__ __forceinline__ void wg_mma<2>(float (&acc)[16][4], const uint32_t* a, uint64_t desc) {
    asm volatile("wgmma.mma_async.sync.aligned.m64n112k16.f32.f16.f16 {%0,%1,%2,%3,%4,%5,%6,%7,%8,%9,%10,%11,%12,%13,%14,%15,%16,%17,%18,%19,%20,%21,%22,%23,%24,%25,%26,%27,%28,%29,%30,%31,%32,%33,%34,%35,%36,%37,%38,%39,%40,%41,%42,%43,%44,%45,%46,%47,%48,%49,%50,%51,%52,%53,%54,%55}, {%56,%57,%58,%59}, %60, 1, 1, 1, 0;\n"
                 : "+f"(acc[2][0]), "+f"(acc[2][1]), "+f"(acc[2][2]), "+f"(acc[2][3]), "+f"(acc[3][0]), "+f"(acc[3][1]), "+f"(acc[3][2]), "+f"(acc[3][3]), "+f"(acc[4][0]), "+f"(acc[4][1]), "+f"(acc[4][2]), "+f"(acc[4][3]), "+f"(acc[5][0]), "+f"(acc[5][1]), "+f"(acc[5][2]), "+f"(acc[5][3]), "+f"(acc[6][0]), "+f"(acc[6][1]), "+f"(acc[6][2]), "+f"(acc[6][3]), "+f"(acc[7][0]), "+f"(acc[7][1]), "+f"(acc[7][2]), "+f"(acc[7][3]), "+f"(acc[8][0]), "+f"(acc[8][1]), "+f"(acc[8][2]), "+f"(acc[8][3]), "+f"(acc[9][0]), "+f"(acc[9][1]), "+f"(acc[9][2]), "+f"(acc[9][3]), "+f"(acc[10][0]), "+f"(acc[10][1]), "+f"(acc[10][2]), "+f"(acc[10][3]), "+f"(acc[11][0]), "+f"(acc[11][1]), "+f"(acc[11][2]), "+f"(acc[11][3]), "+f"(acc[12][0]), "+f"(acc[12][1]), "+f"(acc[12][2]), "+f"(acc[12][3]), "+f"(acc[13][0]), "+f"(acc[13][1]), "+f"(acc[13][2]), "+f"(acc[13][3]), "+f"(acc[14][0]), "+f"(acc[14][1]), "+f"(acc[14][2]), "+f"(acc[14][3]), "+f"(acc[15][0]), "+f"(acc[15][1]), "+f"(acc[15][2]), "+f"(acc[15][3])
                 : "r"(a[0]), "r"(a[1]), "r"(a[2]), "r"(a[3]), "l"(desc));
}
template <> __device__ __forceinline__ void wg_mma<4>(float (&acc)[16][4], const uint32_t* a, uint64_t desc) {
    asm volatile("wgmma.mma_async.sync.aligned.m64n96k16.f32.f16.f16 {%0,%1,%2,%3,%4,%5,%6,%7,%8,%9,%10,%11,%12,%13,%14,%15,%16,%17,%18,%19,%20,%21,%22,%23,%24,%25,%26,%27,%28,%29,%30,%31,%32,%33,%34,%35,%36,%37,%38,%39,%40,%41,%42,%43,%44,%45,%46,%47}, {%48,%49,%50,%51}, %52, 1, 1, 1, 0;\n"
                 : "+f"(acc[4][0]), "+f"(acc[4][1]), "+f"(acc[4][2]), "+f"(acc[4][3]), "+f"(acc[5][0]), "+f"(acc[5][1]), "+f"(acc[5][2]), "+f"(acc[5][3]), "+f"(acc[6][0]), "+f"(acc[6][1]), "+f"(acc[6][2]), "+f"(acc[6][3]), "+f"(acc[7][0]), "+f"(acc[7][1]), "+f"(acc[7][2]), "+f"(acc[7][3]), "+f"(acc[8][0]), "+f"(acc[8][1]), "+f"(acc[8][2]), "+f"(acc[8][3]), "+f"(acc[9][0]), "+f"(acc[9][1]), "+f"(acc[9][2]), "+f"(acc[9][3]), "+f"(acc[10][0]), "+f"(acc[10][1]), "+f"(acc[10][2]), "+f"(acc[10][3]), "+f"(acc[11][0]), "+f"(acc[11][1]), "+f"(acc[11][2]), "+f"(acc[11][3]), "+f"(acc[12][0]), "+f"(acc[12][1]), "+f"(acc[12][2]), "+f"(acc[12][3]), "+f"(acc[13][0]), "+f"(acc[13][1]), "+f"(acc[13][2]), "+f"(acc[13][3]), "+f"(acc[14][0]), "+f"(acc[14][1]), "+f"(acc[14][2]), "+f"(acc[14][3]), "+f"(acc[15][0]), "+f"(acc[15][1]), "+f"(acc[15][2]), "+f"(acc[15][3])
                 : "r"(a[0]), "r"(a[1]), "r"(a[2]), "r"(a[3]), "l"(desc));
}
template <> __device__ __forceinline__ void wg_mma<6>(float (&acc)[16][4], const uint32_t* a, uint64_t desc) {
    asm volatile("wgmma.mma_async.sync.aligned.m64n80k16.f32.f16.f16 {%0,%1,%2,%3,%4,%5,%6,%7,%8,%9,%10,%11,%12,%13,%14,%15,%16,%17,%18,%19,%20,%21,%22,%23,%24,%25,%26,%27,%28,%29,%30,%31,%32,%33,%34,%35,%36,%37,%38,%39}, {%40,%41,%42,%43}, %44, 1, 1, 1, 0;\n"
                 : "+f"(acc[6][0]), "+f"(acc[6][1]), "+f"(acc[6][2]), "+f"(acc[6][3]), "+f"(acc[7][0]), "+f"(acc[7][1]), "+f"(acc[7][2]), "+f"(acc[7][3]), "+f"(acc[8][0]), "+f"(acc[8][1]), "+f"(acc[8][2]), "+f"(acc[8][3]), "+f"(acc[9][0]), "+f"(acc[9][1]), "+f"(acc[9][2]), "+f"(acc[9][3]), "+f"(acc[10][0]), "+f"(acc[10][1]), "+f"(acc[10][2]), "+f"(acc[10][3]), "+f"(acc[11][0]), "+f"(acc[11][1]), "+f"(acc[11][2]), "+f"(acc[11][3]), "+f"(acc[12][0]), "+f"(acc[12][1]), "+f"(acc[12][2]), "+f"(acc[12][3]), "+f"(acc[13][0]), "+f"(acc[13][1]), "+f"(acc[13][2]), "+f"(acc[13][3]), "+f"(acc[14][0]), "+f"(acc[14][1]), "+f"(acc[14][2]), "+f"(acc[14][3]), "+f"(acc[15][0]), "+f"(acc[15][1]), "+f"(acc[15][2]), "+f"(acc[15][3])
                 : "r"(a[0]), "r"(a[1]), "r"(a[2]), "r"(a[3]), "l"(desc));
}
template <> __device__ __forceinline__ void wg_mma<8>(float (&acc)[16][4], const uint32_t* a, uint64_t desc) {
    asm volatile("wgmma.mma_async.sync.aligned.m64n64k16.f32.f16.f16 {%0,%1,%2,%3,%4,%5,%6,%7,%8,%9,%10,%11,%12,%13,%14,%15,%16,%17,%18,%19,%20,%21,%22,%23,%24,%25,%26,%27,%28,%29,%30,%31}, {%32,%33,%34,%35}, %36, 1, 1, 1, 0;\n"
                 : "+f"(acc[8][0]), "+f"(acc[8][1]), "+f"(acc[8][2]), "+f"(acc[8][3]), "+f"(acc[9][0]), "+f"(acc[9][1]), "+f"(acc[9][2]), "+f"(acc[9][3]), "+f"(acc[10][0]), "+f"(acc[10][1]), "+f"(acc[10][2]), "+f"(acc[10][3]), "+f"(acc[11][0]), "+f"(acc[11][1]), "+f"(acc[11][2]), "+f"(acc[11][3]), "+f"(acc[12][0]), "+f"(acc[12][1]), "+f"(acc[12][2]), "+f"(acc[12][3]), "+f"(acc[13][0]), "+f"(acc[13][1]), "+f"(acc[13][2]), "+f"(acc[13][3]), "+f"(acc[14][0]), "+f"(acc[14][1]), "+f"(acc[14][2]), "+f"(acc[14][3]), "+f"(acc[15][0]), "+f"(acc[15][1]), "+f"(acc[15][2]), "+f"(acc[15][3])
                 : "r"(a[0]), "r"(a[1]), "r"(a[2]), "r"(a[3]), "l"(desc));
}
template <> __device__ __forceinline__ void wg_mma<10>(float (&acc)[16][4], const uint32_t* a, uint64_t desc) {
    asm volatile("wgmma.mma_async.sync.aligned.m64n48k16.f32.f16.f16 {%0,%1,%2,%3,%4,%5,%6,%7,%8,%9,%10,%11,%12,%13,%14,%15,%16,%17,%18,%19,%20,%21,%22,%23}, {%24,%25,%26,%27}, %28, 1, 1, 1, 0;\n"
                 : "+f"(acc[10][0]), "+f"(acc[10][1]), "+f"(acc[10][2]), "+f"(acc[10][3]), "+f"(acc[11][0]), "+f"(acc[11][1]), "+f"(acc[11][2]), "+f"(acc[11][3]), "+f"(acc[12][0]), "+f"(acc[12][1]), "+f"(acc[12][2]), "+f"(acc[12][3]), "+f"(acc[13][0]), "+f"(acc[13][1]), "+f"(acc[13][2]), "+f"(acc[13][3]), "+f"(acc[14][0]), "+f"(acc[14][1]), "+f"(acc[14][2]), "+f"(acc[14][3]), "+f"(acc[15][0]), "+f"(acc[15][1]), "+f"(acc[15][2]), "+f"(acc[15][3])
                 : "r"(a[0]), "r"(a[1]), "r"(a[2]), "r"(a[3]), "l"(desc));
}
template <> __device__ __forceinline__ void wg_mma<12>(float (&acc)[16][4], const uint32_t* a, uint64_t desc) {
    asm volatile("wgmma.mma_async.sync.aligned.m64n32k16.f32.f16.f16 {%0,%1,%2,%3,%4,%5,%6,%7,%8,%9,%10,%11,%12,%13,%14,%15}, {%16,%17,%18,%19}, %20, 1, 1, 1, 0;\n"
                 : "+f"(acc[12][0]), "+f"(acc[12][1]), "+f"(acc[12][2]), "+f"(acc[12][3]), "+f"(acc[13][0]), "+f"(acc[13][1]), "+f"(acc[13][2]), "+f"(acc[13][3]), "+f"(acc[14][0]), "+f"(acc[14][1]), "+f"(acc[14][2]), "+f"(acc[14][3]), "+f"(acc[15][0]), "+f"(acc[15][1]), "+f"(acc[15][2]), "+f"(acc[15][3])
                 : "r"(a[0]), "r"(a[1]), "r"(a[2]), "r"(a[3]), "l"(desc));
}
template <> __device__ __forceinline__ void wg_mma<14>(float (&acc)[16][4], const uint32_t* a, uint64_t desc) {
    asm volatile("wgmma.mma_async.sync.aligned.m64n16k16.f32.f16.f16 {%0,%1,%2,%3,%4,%5,%6,%7}, {%8,%9,%10,%11}, %12, 1, 1, 1, 0;\n"
                 : "+f"(acc[14][0]), "+f"(acc[14][1]), "+f"(acc[14][2]), "+f"(acc[14][3]), "+f"(acc[15][0]), "+f"(acc[15][1]), "+f"(acc[15][2]), "+f"(acc[15][3])
                 : "r"(a[0]), "r"(a[1]), "r"(a[2]), "r"(a[3]), "l"(desc));
}
template <> __device__ __forceinline__ void wg_first<0>(float (&acc)[16][4], const uint32_t* a, uint64_t desc) {
    asm volatile("wgmma.mma_async.sync.aligned.m64n128k16.f32.f16.f16 {%0,%1,%2,%3,%4,%5,%6,%7,%8,%9,%10,%11,%12,%13,%14,%15,%16,%17,%18,%19,%20,%21,%22,%23,%24,%25,%26,%27,%28,%29,%30,%31,%32,%33,%34,%35,%36,%37,%38,%39,%40,%41,%42,%43,%44,%45,%46,%47,%48,%49,%50,%51,%52,%53,%54,%55,%56,%57,%58,%59,%60,%61,%62,%63}, {%64,%65,%66,%67}, %68, 0, 1, 1, 0;\n"
                 : "=f"(acc[0][0]), "=f"(acc[0][1]), "=f"(acc[0][2]), "=f"(acc[0][3]), "=f"(acc[1][0]), "=f"(acc[1][1]), "=f"(acc[1][2]), "=f"(acc[1][3]), "=f"(acc[2][0]), "=f"(acc[2][1]), "=f"(acc[2][2]), "=f"(acc[2][3]), "=f"(acc[3][0]), "=f"(acc[3][1]), "=f"(acc[3][2]), "=f"(acc[3][3]), "=f"(acc[4][0]), "=f"(acc[4][1]), "=f"(acc[4][2]), "=f"(acc[4][3]), "=f"(acc[5][0]), "=f"(acc[5][1]), "=f"(acc[5][2]), "=f"(acc[5][3]), "=f"(acc[6][0]), "=f"(acc[6][1]), "=f"(acc[6][2]), "=f"(acc[6][3]), "=f"(acc[7][0]), "=f"(acc[7][1]), "=f"(acc[7][2]), "=f"(acc[7][3]), "=f"(acc[8][0]), "=f"(acc[8][1]), "=f"(acc[8][2]), "=f"(acc[8][3]), "=f"(acc[9][0]), "=f"(acc[9][1]), "=f"(acc[9][2]), "=f"(acc[9][3]), "=f"(acc[10][0]), "=f"(acc[10][1]), "=f"(acc[10][2]), "=f"(acc[10][3]), "=f"(acc[11][0]), "=f"(acc[11][1]), "=f"(acc[11][2]), "=f"(acc[11][3]), "=f"(acc[12][0]), "=f"(acc[12][1]), "=f"(acc[12][2]), "=f"(acc[12][3]), "=f"(acc[13][0]), "=f"(acc[13][1]), "=f"(acc[13][2]), "=f"(acc[13][3]), "=f"(acc[14][0]), "=f"(acc[14][1]), "=f"(acc[14][2]), "=f"(acc[14][3]), "=f"(acc[15][0]), "=f"(acc[15][1]), "=f"(acc[15][2]), "=f"(acc[15][3])
                 : "r"(a[0]), "r"(a[1]), "r"(a[2]), "r"(a[3]), "l"(desc));
}
template <> __device__ __forceinline__ void wg_first<4>(float (&acc)[16][4], const uint32_t* a, uint64_t desc) {
    asm volatile("wgmma.mma_async.sync.aligned.m64n96k16.f32.f16.f16 {%0,%1,%2,%3,%4,%5,%6,%7,%8,%9,%10,%11,%12,%13,%14,%15,%16,%17,%18,%19,%20,%21,%22,%23,%24,%25,%26,%27,%28,%29,%30,%31,%32,%33,%34,%35,%36,%37,%38,%39,%40,%41,%42,%43,%44,%45,%46,%47}, {%48,%49,%50,%51}, %52, 0, 1, 1, 0;\n"
                 : "=f"(acc[4][0]), "=f"(acc[4][1]), "=f"(acc[4][2]), "=f"(acc[4][3]), "=f"(acc[5][0]), "=f"(acc[5][1]), "=f"(acc[5][2]), "=f"(acc[5][3]), "=f"(acc[6][0]), "=f"(acc[6][1]), "=f"(acc[6][2]), "=f"(acc[6][3]), "=f"(acc[7][0]), "=f"(acc[7][1]), "=f"(acc[7][2]), "=f"(acc[7][3]), "=f"(acc[8][0]), "=f"(acc[8][1]), "=f"(acc[8][2]), "=f"(acc[8][3]), "=f"(acc[9][0]), "=f"(acc[9][1]), "=f"(acc[9][2]), "=f"(acc[9][3]), "=f"(acc[10][0]), "=f"(acc[10][1]), "=f"(acc[10][2]), "=f"(acc[10][3]), "=f"(acc[11][0]), "=f"(acc[11][1]), "=f"(acc[11][2]), "=f"(acc[11][3]), "=f"(acc[12][0]), "=f"(acc[12][1]), "=f"(acc[12][2]), "=f"(acc[12][3]), "=f"(acc[13][0]), "=f"(acc[13][1]), "=f"(acc[13][2]), "=f"(acc[13][3]), "=f"(acc[14][0]), "=f"(acc[14][1]), "=f"(acc[14][2]), "=f"(acc[14][3]), "=f"(acc[15][0]), "=f"(acc[15][1]), "=f"(acc[15][2]), "=f"(acc[15][3])
                 : "r"(a[0]), "r"(a[1]), "r"(a[2]), "r"(a[3]), "l"(desc));
}

#define SDLY 900
#define UDLY 1400
#define KDLY 950
#define FDLY 1000
#define FDLY2 400
#define DDLY 300
#define WDLY 500
#define HW 15
#define FIX(v) do { if ((v) == 1u) TRAP(); } while (0)
#define STAMPW(i) STAMPY(i)
#define STAMP2(i) STAMP(i)
#undef STAMPX
#define STAMPX(i)
struct Params {
    const bf16 *x, *lar, *aim, *cre, *cim, *ldt, *dsk;
    Scratch* s;
    const bf16* wr;
    bf16* out;
};

#define TOK(g) (2 * (g) - ((g) & 1))
#define ROWTOK(r) (TOK((r) & 7) + (((r) >> 2) & 2))
__device__ __forceinline__ void ln_partial(const uint32_t (&H)[2][4], float (&d)[2][4]) {
#pragma unroll
    for (int hf = 0; hf < 2; hf++) {
        d[hf][0] = d[hf][1] = d[hf][2] = d[hf][3] = 0.f;
        mma_bf16(d[hf], H[hf][0], 0x3f803f80u, H[hf][1], 0x3f803f80u, H[hf][0], H[hf][1]);
    }
#pragma unroll
    for (int hf = 0; hf < 2; hf++) mma_bf16(d[hf], H[hf][2], 0x3f803f80u, H[hf][3], 0x3f803f80u, H[hf][2], H[hf][3]);
}
__device__ __forceinline__ float sum18(uint32_t a) {
    const uint4 p = lds128(a), q = lds128(a + 16), r = lds128(a + 32), s = lds128(a + 48);
    const uint2 u = lds64(a + 64);
#define F(x) __uint_as_float(x)
    return (((F(p.x) + F(p.y)) + (F(p.z) + F(p.w))) + ((F(q.x) + F(q.y)) + (F(q.z) + F(q.w)))) +
           (((F(r.x) + F(r.y)) + (F(r.z) + F(r.w))) + ((F(s.x) + F(s.y)) + (F(s.z) + F(s.w))) + (F(u.x) + F(u.y)));
#undef F
}
__device__ __forceinline__ void ln_stats(float sm, float sq, float& mb, float& sd) {
    const float m0 = sm * (1.0f / 576.0f);
    const float mean = fmaf(fmaf(-m0, 576.0f, sm), 1.0f / 576.0f, m0);
    const float var = fmaxf(fmaf(-mean, mean, sq * (1.0f / 576.0f)), 0.f);
    mb = rbf(mean);
    sd = rbf(sqrt_approx(rbf(rbf(var) + 1e-5f)));
}
__device__ __forceinline__ void ln_finish(float v, int lane, float& mb, float& rc) {
    const float o = __shfl_xor_sync(0xffffffffu, v, 16);
    float sd;
    ln_stats(lane < 16 ? v : o, lane < 16 ? o : v, mb, sd);
    rc = rcp_approx(sd);
}
__device__ __forceinline__ uint32_t ln_apply(uint32_t w, uint32_t m2, uint32_t rh, uint32_t rl) {
    const uint32_t d = hsub2_bf(w, m2);
    return hfma2_bf(d, rh, hmul2_bf(d, rl));
}
__device__ __forceinline__ void stat_store(uint32_t a, float mb, float rc, uint32_t extra) {
    const float rh = rbf(rc);
    sts64(a, (__float_as_uint(mb) >> 16) | (extra << 16), pack_bf16(rh, rc - rh));
}
#define STAT_M(s) __byte_perm((s).x, (s).x, 0x1010)
#define STAT_H(s) __byte_perm((s).y, (s).y, 0x1010)
#define STAT_L(s) __byte_perm((s).y, (s).y, 0x3232)

__device__ __forceinline__ void hcmul(uint32_t re, uint32_t im, uint32_t zx, uint32_t zy, uint32_t& ore, uint32_t& oim) {
    ore = hfms2(im, zy, hmul2(re, zx));
    oim = hfma2(re, zy, hmul2(im, zx));
}

struct KGen {
    uint32_t A[2][4][4];
    float2 z1, z8, z64, z128, T[9];
};
__device__ __forceinline__ void kgen_setup(KGen& k, float lar, float aim, float dt) {
    const float lr2 = -(exp_bf(lar) * dt) * 1.4426950408889634f, li = aim * dt;
    k.z1 = cexp_e(lr2, li, 1.0f);
    k.z8 = cexp_e(lr2, li, 8.0f);
    k.z64 = cexp_e(lr2, li, 64.0f);
}
__device__ __forceinline__ void kgen_rows(KGen& k, uint32_t tb, int lane) {
    const float2 z8 = k.z8, z64 = k.z64;
    const uint32_t row = tb + lane * 16;
    k.z128 = csq(z64);
    const float2 z16 = csq(z8), z24 = cmul(z16, z8), z32 = csq(z16), z40 = cmul(z32, z8), z48 = csq(z24), z56 = cmul(z32, z24);
    uint32_t re[4], im[4], a[4], b[4];
    re[0] = pack_f16(1.0f, z8.x); im[0] = pack_f16(0.0f, z8.y);
    re[1] = pack_f16(z16.x, z24.x); im[1] = pack_f16(z16.y, z24.y);
    re[2] = pack_f16(z32.x, z40.x); im[2] = pack_f16(z32.y, z40.y);
    re[3] = pack_f16(z48.x, z56.x); im[3] = pack_f16(z48.y, z56.y);
    sts128(row, re[0], re[1], re[2], re[3]);
    sts128(row + 1024, im[0], im[1], im[2], im[3]);
    const uint32_t zx = pack_f16(z64.x, z64.x), zy = pack_f16(z64.y, z64.y), zw = pack_f16(k.z128.x, k.z128.y);
#pragma unroll
    for (int j = 0; j < 4; j++) hcmul(re[j], im[j], zx, zy, a[j], b[j]);
    sts128(row + 512, a[0], a[1], a[2], a[3]);
    sts128(row + 1536, b[0], b[1], b[2], b[3]);
    const int mi = lane >> 3;
    const uint32_t zd = tb + 2048 + mi * 16;
    sts16(tb + 2048 + lane * 2, zw); sts16(tb + 2112 + lane * 2, zw >> 16);
    __syncwarp();
    const uint32_t ad = tb + (lane & 7) * 16 + mi * 512;
    ldsm_x4(a[0], a[1], a[2], a[3], zd);
    ldsm_x4(b[0], b[1], b[2], b[3], zd + 64);
#pragma unroll
    for (int ks = 0; ks < 4; ks++) {
        ldsm_x4_t(k.A[0][ks][0], k.A[0][ks][1], k.A[0][ks][2], k.A[0][ks][3], ad + ks * 128);
        hcmul(k.A[0][ks][0], k.A[0][ks][2], a[ks], b[ks], k.A[1][ks][0], k.A[1][ks][2]);
        hcmul(k.A[0][ks][1], k.A[0][ks][3], a[ks], b[ks], k.A[1][ks][1], k.A[1][ks][3]);
    }
}
__device__ __forceinline__ void kgen_chain(KGen& k, uint32_t cr, uint32_t ci, float cs) {
    k.T[0] = make_float2(bf_lo(cr) * cs, -bf_lo(ci) * cs);
    const float2 y1 = make_float2(k.z1.x, -k.z1.y);
#pragma unroll
    for (int c = 1; c < 8; c++) k.T[c] = cmul(k.T[c - 1], y1);
    k.T[8] = cmul(k.T[0], make_float2(k.z8.x, -k.z8.y));
}
__device__ __forceinline__ void kgen_cols(KGen& k, uint32_t tb, uint32_t t5, int lane) {
    const uint32_t row = tb + lane * 16;
    const float2 (&T)[9] = k.T;
    const float2 y128 = make_float2(k.z128.x, -k.z128.y);
    const float2 y256 = csq(y128), y512 = csq(y256), y768 = cmul(y512, y256), y1024 = csq(y512);
    const float2 c1032 = cmul(T[8], y1024);
    __syncwarp();
    sts128(row, pack_f16(T[0].x, T[1].x), pack_f16(T[2].x, T[3].x), pack_f16(T[4].x, T[5].x), pack_f16(T[6].x, T[7].x));
    sts128(row + 512, pack_f16(T[0].y, T[1].y), pack_f16(T[2].y, T[3].y), pack_f16(T[4].y, T[5].y), pack_f16(T[6].y, T[7].y));
    uint32_t a[4], b[4];
    {
        const uint32_t zx = pack_f16(y256.x, y256.x), zy = pack_f16(y256.y, y256.y);
        hcmul(pack_f16(T[0].x, T[2].x), pack_f16(T[0].y, T[2].y), zx, zy, a[0], b[0]);
        hcmul(pack_f16(T[4].x, T[6].x), pack_f16(T[4].y, T[6].y), zx, zy, a[1], b[1]);
        const uint32_t r04 = pack_f16(T[0].x, T[4].x), i04 = pack_f16(T[0].y, T[4].y);
        hcmul(r04, i04, pack_f16(y512.x, y512.x), pack_f16(y512.y, y512.y), a[2], b[2]);
        hcmul(r04, i04, pack_f16(y768.x, y768.x), pack_f16(y768.y, y768.y), a[3], b[3]);
    }
    sts128(row + 1024, a[0], a[1], a[2], a[3]);
    sts128(row + 1536, b[0], b[1], b[2], b[3]);
    {
        const uint32_t r0 = pack_f16(1.0f, y256.x), i0 = pack_f16(0.0f, y256.y), r1 = pack_f16(y512.x, y768.x), i1 = pack_f16(y512.y, y768.y);
        const uint32_t zx = pack_f16(T[8].x, T[8].x), zy = pack_f16(T[8].y, T[8].y), wx = pack_f16(c1032.x, c1032.x), wy = pack_f16(c1032.y, c1032.y);
        hcmul(r0, i0, zx, zy, a[0], b[0]); hcmul(r1, i1, zx, zy, a[1], b[1]);
        hcmul(r0, i0, wx, wy, a[2], b[2]); hcmul(r1, i1, wx, wy, a[3], b[3]);
    }
    sts128(row + 2048, a[0], a[1], a[2], a[3]);
    sts128(t5 + lane * 16, b[0], b[1], b[2], b[3]);
}
__device__ __forceinline__ void kgen_mma(const KGen& k, uint32_t tb, uint32_t t5, int lane) {
    __syncwarp();
    float acc[2][3][4];
#pragma unroll
    for (int i = 0; i < 6; i++)
#pragma unroll
        for (int j = 0; j < 4; j++) acc[i / 3][i % 3][j] = 0.f;
    const int mi = lane >> 3;
    const uint32_t ro = ((lane & 7) + 8 * (mi >> 1)) * 16, bd = tb + ro + (mi & 1) * 512, b2 = ro + ((mi & 1) ? t5 : tb + 2048);
#pragma unroll
    for (int kp = 0; kp < 2; kp++)
#pragma unroll
        for (int j = 0; j < 3; j++) {
            uint32_t b[4];
            ldsm_x4_t(b[0], b[1], b[2], b[3], (j < 2 ? bd + j * 1024 : b2) + kp * 256);
#pragma unroll
            for (int h = 0; h < 2; h++)
#pragma unroll
                for (int m = 0; m < 2; m++) {
                    const uint32_t (&A)[4] = k.A[m][2 * kp + h];
                    mma_f16(acc[m][j], A[0], A[1], A[2], A[3], b[2 * h], b[2 * h + 1]);
                }
        }
    __syncwarp();
#define PK(j) pack_f16(acc[0][j][0], acc[0][j][1]), pack_f16(acc[0][j][2], acc[0][j][3]), pack_f16(acc[1][j][0], acc[1][j][1]), pack_f16(acc[1][j][2], acc[1][j][3])
    stsm_x4(tb + lane * 16, PK(0));
    stsm_x4(tb + 512 + lane * 16, PK(1));
    stsm_x4_t(tb + 1024 + (lane & 7) * 80 + mi * 16, PK(2));
#undef PK
}
__device__ __forceinline__ uint32_t table_buf(uint32_t sb, int warp) { return sb + SM_PL + warp * TBW; }

__device__ __forceinline__ uint4 lds16x4(uint32_t a) { return make_uint4(lds16(a), lds16(a + TBW), lds16(a + 2 * TBW), lds16(a + 3 * TBW)); }
__device__ __forceinline__ void combine_setup(uint32_t sb, int warp, int lane, uint32_t kw, uint32_t& o, uint32_t& n, uint32_t& d) {
    const int wq = warp & 3;
    const uint32_t a = table_buf(sb, warp & ~3);
    o = wq == 3 ? a + 1024 + 320 + (lane >> 3) * 80 + (lane & 7) * 8 : a + (wq ? 504 + wq * 8 : 0) + lane * 16;
    n = a + 1024 + wq * 80 + lane * 2;
    d = wq < 3 ? kw + (wq == 2 ? KW_P : 32 + wq * 512) + lane * 16 : kw + KW_H + 8 + lane * 8;
}
__device__ __forceinline__ void kgen_combine(int wq, int lane, uint32_t o, uint32_t na, uint32_t d) {
#define S4(f) hadd2(hadd2(u.f, v.f), hadd2(w.f, x.f))
#define H4(v) hadd2(hadd2(v.x, v.y), hadd2(v.z, v.w))
#define BP __byte_perm
    if (wq == 0) {
        const uint4 u = lds128(o), v = lds128(o + TBW), w = lds128(o + 2 * TBW), x = lds128(o + 3 * TBW), nn = lds16x4(na);
        const uint32_t n = H4(nn), k0 = S4(x), k2 = S4(y), k4 = S4(z), k6 = S4(w);
        sts128(d, BP(k0, k0, 0x1032), BP(k0, k2, 0x3254), BP(k2, k2, 0x1032), BP(k2, k4, 0x3254));
        sts128(d + KW_PL, BP(k4, k4, 0x1032), BP(k4, k6, 0x3254), BP(k6, k6, 0x1032), BP(k6, n, 0x3254));
        if (lane == 0) sts32(d + KW_PL - 4, k0 & 0xffffu);
    } else {
        const uint2 u = lds64(o), v = lds64(o + TBW), w = lds64(o + 2 * TBW), x = lds64(o + 3 * TBW);
        uint4 nn = make_uint4(0u, 0u, 0u, 0u), mm = nn;
        if (wq < 3) nn = lds16x4(na);
        if (wq == 2) mm = lds16x4(na + 80);
        const uint32_t k0 = S4(x), k2 = S4(y), n = H4(nn), m = H4(mm);
        if (wq == 3) {
            sts64(d, k0, k2);
        } else if (wq == 1) {
            const uint32_t cc = BP(k2, k2, 0x1010);
            sts128(d, BP(k0, k0, 0x1010), BP(k0, k0, 0x1032), BP(k0, k2, 0x3254), cc);
            sts128(d + KW_PL, cc, BP(k2, k2, 0x1032), BP(k2, n, 0x3254), BP(n, n, 0x1010));
        } else {
            const uint32_t w40 = BP(k0, k0, 0x1032), w84 = BP(k0, n, 0x3254), w0 = BP(k0, k0, 0x1010), w4 = BP(k0, k0, 0x3232), w8 = BP(n, n, 0x1010);
            sts64(d, w40, w84);
            sts64(d + 512, BP(k2, k2, 0x1032), BP(k2, m, 0x3254));
            if (lane < 8) { sts128(d - (KW_P - 1056), w0, w0, w40, w4); sts128(d - (KW_P - 1056 - KW_PL), w4, w84, w8, w8); }
            if (lane == 31) sts16(d + (KW_H + 6 - KW_P - 496), m);
        }
    }
#undef S4
#undef H4
#undef BP
}

__device__ __forceinline__ int c_exponent(const uint2& r, const uint2& i, float dt) {
    const uint32_t mx = __vmaxu2(__vmaxu2(r.x & 0x7fff7fffu, r.y & 0x7fff7fffu), __vmaxu2(i.x & 0x7fff7fffu, i.y & 0x7fff7fffu));
    return __reduce_max_sync(0xffffffffu, max(mx, mx << 16) + (__float_as_uint(dt) & 0x7f800000u)) >> 23;
}

#define YQ 2
#define F0 0
__device__ __forceinline__ int warp_v() { int l; asm volatile("mov.u32 %0, %%tid.x;" : "=r"(l)); return __shfl_sync(0xffffffffu, l >> 5, 0); }
__device__ __forceinline__ int lane_v() { int l; asm volatile("mov.u32 %0, %%laneid;" : "=r"(l)); return l; }
__device__ __forceinline__ uint32_t prmt_v(uint32_t a, uint32_t b, uint32_t s) { uint32_t d; asm volatile("prmt.b32 %0, %1, %2, %3;\n" : "=r"(d) : "r"(a), "r"(b), "r"(s)); return d; }
__device__ __forceinline__ uint32_t mov_v(uint32_t a) { uint32_t d; asm volatile("mov.b32 %0, %1;\n" : "=r"(d) : "r"(a)); return d; }
template <int G>
__device__ __forceinline__ void conv_rename(float (&acc)[16][4]) {
#pragma unroll
    for (int i = G; i < 16; i++)
#pragma unroll
        for (int j = 0; j < 4; j++) { float v; asm volatile("mov.b32 %0, %1;\n" : "=f"(v) : "f"(acc[i][j])); acc[i][j] = v; }
}
struct Conv {
    uint32_t kw;
    uint32_t wa;
    uint32_t pa, s2;
    uint32_t s8;
    uint32_t id;
    uint32_t lc;
    uint32_t fs;
    uint32_t fl, yo;
    uint32_t yp;
    size_t ycopy;
    uint32_t ps;
    uint64_t d0;
    int warp;
};
struct Pk { uint32_t w[4]; };
__device__ __forceinline__ Pk pk2(const float (&u)[4], const float (&v)[4]) {
    Pk r;
    r.w[0] = pack_f16(u[0], u[1]); r.w[1] = pack_f16(u[2], u[3]); r.w[2] = pack_f16(v[0], v[1]); r.w[3] = pack_f16(v[2], v[3]);
    return r;
}
__device__ __forceinline__ void park(uint32_t a, const Pk& v) {
    asm volatile("stmatrix.sync.aligned.m8n8.x4.trans.shared.b16 [%0], {%1,%2,%3,%4};\n" ::"r"(a), "r"(v.w[0]), "r"(v.w[1]), "r"(v.w[2]), "r"(v.w[3]) : "memory");
}
__device__ __forceinline__ void conv_constants(uint32_t lc, int l) {
    const int d = (l >> 2) - 2 * (l & 3);
    const int e = d + 8, r4 = (e + 1 + ((e >> 2) & 1)) >> 2, p4 = (e + (((e - 1) >> 2) & 1)) >> 2;
    const uint32_t s2 = r4 == p4 ? 0x1010u : 0x3210u;
    sts64(lc + l * 8, KW_P + ((r4 - 5) >> 1) * 16 + ((r4 - 5) & 1) * 4, s2 | ((d < 0 ? s2 : 0x7654u) << 16));
    const int lo = (d >= 4) - (d < -3), ho = (d >= 5) - (d < -2), le = (d > 4) - (d < -4), he = (d > 5) - (d < -3);
    sts32(lc + 512 + l * 8, (0x5454u + lo * 0x22 + ho * 0x2200) | ((0x3232u + le * 0x22 + he * 0x2200) << 16));
    const int cc = l >> 2, j = l & 3;
    sts64(lc + 256 + l * 8, (j >> 1) * PL_HALF + (16 + cc) * 16 + (j & 1) * 8, (cc >> 1) * (DM * 64) + (cc & 1) * 32 + j * 8);
}
__device__ __forceinline__ void conv_selectors4(Conv& c) {
    const uint2 v = lds64(c.lc + lane_v() * 8);
    c.pa = v.x; c.s2 = v.y;
}
__device__ __forceinline__ void conv_selectors8(Conv& c) { c.s8 = lds32(c.lc + 512 + lane_v() * 8); }
template <int G, int I0, int I1>
__device__ __forceinline__ void conv_load(const Conv& c, uint32_t (&q)[9]) {
    const int wq = c.warp & 3;
    if (G < 2) {
#pragma unroll
        for (int i = I0; i < I1; i++) q[i] = lds32(c.wa + G * 512 + i * 16);
    } else if (G < 4) {
        const uint32_t a = (G == 2 && wq == 0) ? c.wa + 1024 : c.pa + c.kw + wq * 128 + (G < 2 ? 0 : G - 2) * 512;
#pragma unroll
        for (int i = I0; i < I1; i++) q[i] = lds32(a + i * 16);
    } else {
        const uint4 u = lds128(c.kw + KW_H + (G < 4 ? 0 : G - 4) * 64 + wq * 16);
        const uint2 v = lds64(c.kw + KW_H + (G < 4 ? 0 : G - 4) * 64 + wq * 16 + 16);
        q[0] = u.x; q[1] = u.y; q[2] = u.z; q[3] = u.w; q[4] = v.x; q[5] = v.y;
        if (G == 4 && wq == 0) { q[6] = lds32(c.pa + c.kw + 1024); q[7] = lds32(c.pa + c.kw + 1040); }
    }
}
template <int G, int J0, int J1>
__device__ __forceinline__ void conv_frag(const Conv& c, const uint32_t (&q)[9], uint32_t* a, const Pk& dp) {
    const uint32_t dep = dp.w[0];
    if (G < 4) {
        const uint32_t s = (G < 2 || (G == 2 && (c.warp & 3) == 0)) ? c.id : c.s2;
#pragma unroll
        for (int j = J0; j < J1; j++) {
            uint32_t* o = a + 4 * (j - J0);
            o[0] = prmt_v(q[2 * j + 1], dp.w[0], s); o[1] = prmt_v(q[2 * j + 2], dp.w[1], s); o[2] = prmt_v(q[2 * j], dp.w[2], s); o[3] = prmt_v(q[2 * j + 1], dp.w[3], s);
        }
    } else {
        const uint32_t so = prmt_v(c.s8, dep, c.id), se = prmt_v(c.s8, dep, c.id + 0x22);
#pragma unroll
        for (int j = J0; j < J1; j++) {
            uint32_t* o = a + 4 * (j - J0);
            o[0] = prmt_v(q[j + 1], q[j + 2], se); o[1] = prmt_v(q[j + 1], q[j + 2], so); o[2] = prmt_v(q[j], q[j + 1], so);
            if (G == 4 && j == 0 && (c.warp & 3) == 0) {
                o[2] = prmt_v(q[6], dep, c.s2);
                o[0] = prmt_v(q[7], o[0], c.s2 >> 16);
            }
            o[3] = mov_v(o[0]);
        }
    }
}
template <int G, int J0, int J1>
__device__ __forceinline__ void conv_frag(const Conv& c, const uint32_t (&q)[9], uint32_t* a, float depf) {
    const uint32_t d = __float_as_uint(depf);
    conv_frag<G, J0, J1>(c, q, a, Pk{{d, d, d, d}});
}
template <int G, int T, int J0, int J1>
__device__ __forceinline__ void conv_mma(float (&acc)[16][4], const Conv& c, const uint32_t* a) {
#pragma unroll
    for (int j = J0; j < J1; j++) wg_mma<T>(acc, a + 4 * (j - J0), c.d0 - 8 * (2 * G - T) - j);
}
__device__ __forceinline__ float h_lo(uint32_t w) { return __half2float(__ushort_as_half((unsigned short)(w & 0xffffu))); }
__device__ __forceinline__ float h_hi(uint32_t w) { return __half2float(__ushort_as_half((unsigned short)(w >> 16))); }
__device__ __forceinline__ void flush_setup(Conv& c) {
    const uint2 v = lds64(c.lc + 256 + lane_v() * 8);
    c.fl = v.x; c.yo = v.y;
}
template <int Q>
__device__ __forceinline__ void flush_load(const Conv& c, uint32_t pl, uint2 (&f)[4]) {
#pragma unroll
    for (int w = 0; w < 4; w++) f[w] = lds64(c.fl + pl + (Q & 1) * 512 + w * (PLW_B - 64));
}
template <int Q>
__device__ __forceinline__ void flush_load_first(const Conv& c, uint32_t pl, uint2 (&f)[4], float depf) {
    const uint32_t p = prmt_v(c.fl, __float_as_uint(depf), c.id) + pl + (Q & 1) * 512;
#define LDV64(d, a) asm volatile("ld.volatile.shared.v2.u32 {%0,%1}, [%2];\n" : "=r"(d.x), "=r"(d.y) : "r"(a) : "memory")
    LDV64(f[0], p); LDV64(f[1], p + (PLW_B - 64)); LDV64(f[2], p + 2 * (PLW_B - 64)); LDV64(f[3], p + 3 * (PLW_B - 64));
}
#define FDEP __uint_as_float(f[3].y)
template <int Q, int mode>
__device__ __forceinline__ void conv_flush(const Conv& c, const uint2 (&f)[4], unsigned char* gy, uint32_t rx) {
    const uint32_t a0 = hadd2(f[0].x, f[1].x), a1 = hadd2(f[2].x, f[3].x), b0 = hadd2(f[0].y, f[1].y), b1 = hadd2(f[2].y, f[3].y);
    if (Q > 0 && mode == 1) {
        const uint32_t ra = rx + 16 + (Q > 0 ? Q - 1 : 0) * 1024 + (c.warp & 3) * 256 + lane_v() * 8;
        asm volatile("st.async.shared::cluster.mbarrier::complete_tx::bytes.v2.b32 [%0], {%1,%2}, [%3];\n"
                     ::"r"(ra ^ 0x1000000u), "r"(hadd2(a0, a1)), "r"(hadd2(b0, b1)), "r"((rx + (Q > 1 ? 8 : 0)) ^ 0x1000000u) : "memory");
        return;
    }
    float v0 = h_lo(a0) + h_lo(a1), v1 = h_hi(a0) + h_hi(a1), v2 = h_lo(b0) + h_lo(b1), v3 = h_hi(b0) + h_hi(b1);
    if (Q > 0 && mode == 2) {
        const uint2 o = lds64(rx + 16 + (Q > 0 ? Q - 1 : 0) * 1024 + (c.warp & 3) * 256 + lane_v() * 8);
        v0 += h_lo(o.x); v1 += h_hi(o.x); v2 += h_lo(o.y); v3 += h_hi(o.y);
    }
    const uint32_t lo = hmul2_bf(pack_bf16(v0, v1), c.fs), hi = hmul2_bf(pack_bf16(v2, v3), c.fs);
    stg64(gy + Q * 32 * DM * 32 + (c.yo + (Q < YQ ? c.yp : 0u)), nzw(lo), nzw(hi));
}
template <int I, bool S = false> struct IC { static constexpr int value = I; static constexpr bool shared = S; };
template <class T> __device__ constexpr bool wg_is4() { return T::shared; }
#define SLOT(n) (c.ps + (2 + ((n) & 7)) * 128)
#define GO() do { wg_commit(); __syncwarp(); } while (0)
#define DEP acc[15][3]
template <class FG, class FP, class FN>
__device__ __forceinline__ void conv_head(Conv& c, float (&acc)[16][4], uint32_t (&q)[9], uint32_t (&r)[9], uint32_t* a, FG fg, FP pre, FN next) {
    c.id = 0x3210u + (c.warp >> 8);
    pre();
    conv_load<0, 0, 9>(c, q);
    conv_frag<0, 0, 1>(c, q, a, 0.f);
    wg_fence(); wg_first<0>(acc, a, c.d0); GO();
    park(c.ps, Pk{{0u, 0u, 0u, 0u}});
    wg_wait0();
    conv_frag<0, 1, 2>(c, q, a, DEP);
    wg_fence(); conv_mma<0, 0, 1, 2>(acc, c, a); GO();
    fg(IC<0>());
    wg_wait0();
    conv_frag<0, 2, 3>(c, q, a, DEP);
    wg_fence(); conv_mma<0, 0, 2, 3>(acc, c, a); GO();
    conv_load<1, 0, 5>(c, r);
    wg_wait0();
    conv_frag<0, 3, 4>(c, q, a, DEP);
    wg_fence(); conv_mma<0, 0, 3, 4>(acc, c, a); GO();
    conv_load<1, 5, 9>(c, r);
    fg(IC<1>());
    wg_wait0();
    const Pk k = pk2(acc[0], acc[1]);
    conv_rename<2>(acc);
    conv_frag<1, 0, 2>(c, r, a, k);
    wg_fence(); conv_mma<1, 2, 0, 2>(acc, c, a); GO();
    park(SLOT(0), k);
    next(IC<0>());
    fg(IC<2>());
    wg_wait0();
    conv_frag<1, 2, 4>(c, r, a, DEP);
    wg_fence(); conv_mma<1, 2, 2, 4>(acc, c, a); GO();
    next(IC<1>());
    fg(IC<3>());
    wg_wait0();
}
template <class FG, class FP>
__device__ __forceinline__ void conv_run(Conv& c, uint32_t pl, unsigned char* gy, FG fg, FP pre) {
    float acc[16][4];
    uint32_t q[9], r[9], a[32];
    uint2 f[4];
    const int bid = 1 + (c.warp >> 2);
    conv_head(c, acc, q, r, a, fg, pre, [&](auto i) { if (decltype(i)::value == 0) conv_selectors4(c); else conv_load<2, 0, 9>(c, q); });
    Pk k = pk2(acc[2], acc[3]);
    conv_rename<4>(acc);
    conv_frag<2, 0, 4>(c, q, a, k);
    wg_fence(); conv_mma<2, 4, 0, 4>(acc, c, a); GO();
    park(SLOT(2), k);
    conv_load<3, 0, 9>(c, q);
    flush_setup(c);
    bar_sync(bid, 128);
    fg(IC<4>());
    wg_wait0();
    conv_rename<6>(acc);
    if (F0) { flush_load_first<0>(c, pl, f, DEP); conv_frag<3, 0, 4>(c, q, a, FDEP); }
    else conv_frag<3, 0, 4>(c, q, a, DEP);
    wg_fence(); conv_mma<3, 6, 0, 4>(acc, c, a); GO();
    park(SLOT(4), pk2(acc[4], acc[5]));
    conv_load<4, 0, 9>(c, q);
    conv_selectors8(c);
    if (!F0) flush_load<0>(c, pl, f);
    conv_flush<0, 0>(c, f, gy, 0u);
    fg(IC<5>());
    wg_wait0();
    conv_rename<8>(acc);
    conv_frag<4, 0, 4>(c, q, a, DEP);
    wg_fence(); conv_mma<4, 8, 0, 4>(acc, c, a); GO();
    k = pk2(acc[6], acc[7]);
    park(SLOT(6), k);
    conv_load<5, 0, 9>(c, q);
    bar_sync(bid, 128);
    park(c.ps, k);
    fg(IC<6>());
    wg_wait0();
    conv_rename<10>(acc);
    flush_load_first<1>(c, pl, f, DEP);
    conv_frag<5, 0, 4>(c, q, a, FDEP);
    wg_fence(); conv_mma<5, 10, 0, 4>(acc, c, a); GO();
    park(SLOT(8), pk2(acc[8], acc[9]));
    conv_load<6, 0, 9>(c, q); conv_load<7, 0, 9>(c, r);
    conv_flush<1, 0>(c, f, gy, 0u);
    fg(IC<7>());
    wg_wait0();
    conv_rename<12>(acc);
    conv_frag<6, 0, 4>(c, q, a, DEP); conv_frag<7, 0, 4>(c, r, a + 16, DEP);
    wg_fence(); conv_mma<6, 12, 0, 4>(acc, c, a); conv_mma<7, 12, 0, 4>(acc, c, a + 16); GO();
    park(SLOT(10), pk2(acc[10], acc[11]));
    bar_sync(bid, 128);
    flush_load<2>(c, pl, f);
    conv_flush<2, 0>(c, f, gy, 0u);
    fg(IC<8>());
    if (c.id == 0) TRAP();
    wg_wait0();
    park(SLOT(12), pk2(acc[12], acc[13])); park(SLOT(14), pk2(acc[14], acc[15]));
    bar_sync(bid, 128);
    flush_load<3>(c, pl, f);
    conv_flush<3, 0>(c, f, gy, 0u);
}
template <class FG>
__device__ __forceinline__ void conv_outer(Conv& c, uint32_t pl, unsigned char* gy, uint32_t rx, FG fg) {
    float acc[16][4];
    uint32_t q[9], r[9], a[32];
    uint2 f[4], f2[4];
    const int bid = 1 + (c.warp >> 2);
    conv_head(c, acc, q, r, a, [&](auto gi) { if (decltype(gi)::value == 2) fg(IC<2, true>()); }, [&]() {}, [&](auto i) { if (decltype(i)::value == 0) conv_selectors8(c); else conv_load<6, 0, 9>(c, q); });
    park(SLOT(2), pk2(acc[2], acc[3])); park(SLOT(4), pk2(acc[4], acc[5]));
    const Pk k = pk2(acc[6], acc[7]);
    park(SLOT(6), k);
    conv_load<7, 0, 9>(c, r);
    conv_rename<12>(acc);
    conv_frag<6, 0, 4>(c, q, a, __uint_as_float(k.w[3])); conv_frag<7, 0, 4>(c, r, a + 16, __uint_as_float(k.w[3]));
    wg_fence(); conv_mma<6, 12, 0, 4>(acc, c, a); conv_mma<7, 12, 0, 4>(acc, c, a + 16); GO();
    flush_setup(c);
    bar_sync(bid, 128);
    flush_load<0>(c, pl, f); flush_load<1>(c, pl, f2);
    conv_flush<1, 1>(c, f2, gy, rx);
    conv_flush<0, 1>(c, f, gy, rx);
    wg_wait0();
    bar_sync(bid, 128);
    park(c.ps, k); park(SLOT(8), pk2(acc[8], acc[9])); park(SLOT(10), pk2(acc[10], acc[11]));
    park(SLOT(12), pk2(acc[12], acc[13])); park(SLOT(14), pk2(acc[14], acc[15]));
    bar_sync(bid, 128);
    flush_load<2>(c, pl, f); flush_load<3>(c, pl, f2);
    conv_flush<2, 1>(c, f, gy, rx);
    conv_flush<3, 1>(c, f2, gy, rx);
}
template <class FG>
__device__ __forceinline__ void conv_inner(Conv& c, uint32_t pl, unsigned char* gy, uint32_t rx, FG fg) {
    float acc[16][4];
    uint32_t q[9], a[16];
    uint2 f[4], f2[4];
    const int bid = 1 + (c.warp >> 2);
    c.id = 0x3210u + (c.warp >> 8);
    conv_selectors4(c);
    conv_load<2, 0, 9>(c, q);
    conv_frag<2, 0, 4>(c, q, a, 0.f);
    wg_fence(); wg_first<4>(acc, a, c.d0); conv_mma<2, 4, 1, 4>(acc, c, a + 4); GO();
    conv_load<3, 0, 9>(c, q);
    park(SLOT(2), Pk{{0u, 0u, 0u, 0u}});
    fg(IC<2, true>());
    wg_wait0();
    conv_rename<6>(acc);
    conv_frag<3, 0, 4>(c, q, a, DEP);
    wg_fence(); conv_mma<3, 6, 0, 4>(acc, c, a); GO();
    park(SLOT(4), pk2(acc[4], acc[5]));
    conv_load<4, 0, 9>(c, q);
    conv_selectors8(c);
    wg_wait0();
    conv_rename<8>(acc);
    conv_frag<4, 0, 4>(c, q, a, DEP);
    wg_fence(); conv_mma<4, 8, 0, 4>(acc, c, a); GO();
    const Pk k = pk2(acc[6], acc[7]);
    park(SLOT(6), k); park(c.ps, k);
    conv_load<5, 0, 9>(c, q);
    flush_setup(c);
    wg_wait0();
    conv_rename<10>(acc);
    conv_frag<5, 0, 4>(c, q, a, DEP);
    wg_fence(); conv_mma<5, 10, 0, 4>(acc, c, a); GO();
    park(SLOT(8), pk2(acc[8], acc[9]));
    bar_sync(bid, 128);
    flush_load<1>(c, pl, f);
    mbar_wait(rx);
    conv_flush<1, 2>(c, f, gy, rx);
    wg_wait0();
    bar_sync(bid, 128);
    park(SLOT(10), pk2(acc[10], acc[11])); park(SLOT(12), pk2(acc[12], acc[13])); park(SLOT(14), pk2(acc[14], acc[15]));
    bar_sync(bid, 128);
    flush_load<3>(c, pl, f); flush_load<2>(c, pl, f2);
    mbar_wait(rx + 8);
    conv_flush<3, 2>(c, f, gy, rx);
    conv_flush<2, 2>(c, f2, gy, rx);
}
#undef SLOT
#undef GO
#undef DEP
template <int U0, int U1>
__device__ __forceinline__ void weight_units(uint32_t sb, const CUtensorMap* tg, const CUtensorMap* tu, const CUtensorMap* td, bool w) {
    if (U1 > U0 && w && elect_one()) {
#pragma unroll
        for (int i = U0; i < U1; i++) {
            if (i < 12) tma_2d(sb + SM_WG + i * 6912, i < 6 ? tg : tu, 72 * (blockIdx.x >> 1), 288 * (blockIdx.x & 1) + (i % 6) * 48, sb + SM_MISC + 328);
            else tma_2d(sb + SM_WD + (i - 12) * 4736, td, 144 * (blockIdx.x & 1), 72 * (blockIdx.x >> 1) + 8 * (i - 12), sb + SM_MISC + 336);
        }
    }
}
#define WS 2110121111122004100
__device__ constexpr int wsched(int i) {
    unsigned long long v = WS;
    int n = 0;
    for (int k = 19; k >= 1; k--) { if (k < i) n += (int)(v % 10); v /= 10; }
    return n;
}
static_assert(wsched(20) == 21 && wsched(6) <= 7 && wsched(11) <= 12 && wsched(13) <= 14 && wsched(16) <= 17 && wsched(16) == wsched(15) && wsched(19) == 21, "");
#define WANY(i) (wsched((i) + 1) > wsched(i))
#define WPOINT(i, w) do { weight_units<wsched(i), wsched(i + 1)>(sb, &tm_g, &tm_u, &tm_d, w); } while (0)

__global__ void __launch_bounds__(NTHR, 1) __cluster_dims__(2, 1, 1)
fused_kernel(const Params p, const __grid_constant__ CUtensorMap tm_g, const __grid_constant__ CUtensorMap tm_u, const __grid_constant__ CUtensorMap tm_d, const __grid_constant__ CUtensorMap tm_x) {
    extern __shared__ __align__(1024) unsigned char smem[];
    const uint32_t sb = smem_u32(smem);
    const int tid = threadIdx.x, warp = __shfl_sync(0xffffffffu, tid >> 5, 0), lane = tid & 31;
    const int b = blockIdx.x, P = b >> 1, odd = b & 1;
    const int g = lane >> 2, t = lane & 3;
    const int wg = warp >> 2, t128 = tid & 127;
    const uint32_t s_stat = sb + SM_MISC;
    const uint32_t s_key = sb + SM_MISC + 128;
    const uint32_t s_rank = sb + SM_MISC + 256;
    const uint32_t s_k16 = sb + SM_MISC + 192;
    const uint32_t s_cnt = sb + SM_MISC + 320;
    const uint32_t bar_w = sb + SM_MISC + 328, bar_d = bar_w + 8, bar_g = bar_w + 16, bar_x = bar_w + 24, bar_v = bar_w + 32, bar_s = bar_w + 40, bar_h = bar_w + 48;
    STAMP(0);

    const int ch = wg < 4 ? 4 * b + wg : 512 + P;
    const uint32_t mo = tid < 512 ? 512 * b + tid : 65536 + 128 * P + t128, mq = (mo & ~127u) + 4 * lane;
    const uint32_t pl = ldo16(p.lar + mo), pa2 = ldo16(p.aim + mo), ldt = ldo16(p.ldt + (mo >> 7));
    const uint32_t pc = ldo16(p.cre + mo), pi = ldo16(p.cim + mo);
    const uint2 call_re = ldo64(p.cre + mq), call_im = ldo64(p.cim + mq);
    const uint32_t epl = ld_poll32(p.s->hint + (b & 7) * 32 + 1);
    if (wg < 4) {
        bar_arrive(0, NWRK);
        asm volatile("barrier.cluster.arrive.relaxed.aligned;\n" ::: "memory");
    } else {
        const int o = (4 * (warp & 3) + (g >> 1)) * 1152 + (g & 1) * 576 + t * 16;
        sts128(sb + SM_Z2 + t128 * 16, 0u, 0u, 0u, 0u); sts128(sb + SM_Z2 + 2048 + t128 * 16, 0u, 0u, 0u, 0u);
        if (warp == 16) sts128(sb + SM_Z2 + 4096 + lane * 16, 0u, 0u, 0u, 0u);
        fence_async();
        bar_sync(0, NWRK);
        STAMP(9);
#pragma unroll
        for (int c = 0; c < 9; c++)
            asm volatile("cp.async.cg.shared.global [%0], [%1], 16;\n" ::"r"(sb + SM_XT + o + c * 64), "l"(reinterpret_cast<const char*>(p.x) + b * 18432 + o + c * 64) : "memory");
        asm volatile("cp.async.commit_group;\n" ::: "memory");
        if (elect_one()) {
            mbar_init(bar_h + 8 * (warp & 3), 1);
            if (warp == 19) {
                mbar_init(bar_x, 1); mbar_init(bar_w, 1);
                mbar_expect(bar_x, 32768); mbar_expect(bar_w, 82944);
#pragma unroll
                for (int i = YQ; i < 4; i++) bulk_s2g(reinterpret_cast<unsigned char*>(p.s->y) + 32 * i * 18432 + b * 4608, sb + SM_Z2, 4608);
            } else if (warp == 18) {
                mbar_init(bar_s, 1); mbar_init(bar_v, 2); mbar_init(bar_d, 1); mbar_init(bar_g, 1); mbar_init(sb + SM_RX, 1); mbar_init(sb + SM_RX + 8, 1);
                mbar_expect(bar_v, 2 * 1152); mbar_expect(bar_d, 72 * WD_PITCH); mbar_expect(bar_g, 4608); mbar_expect(sb + SM_RX, 1024); mbar_expect(sb + SM_RX + 8, 2048);
            }
            asm volatile("fence.mbarrier_init.release.cluster;\n" ::: "memory");
        }
        __syncwarp();
        asm volatile("barrier.cluster.arrive.relaxed.aligned;\n" ::: "memory");
        if (warp == 19) {
            asm volatile("barrier.cluster.wait.aligned;\n" ::: "memory");
            if (elect_one()) tma_4d_mc(sb + SM_XC + odd * 16384, &tm_x, 8 * P, 2 * odd, bar_x);
            __syncwarp();
        }
        {
            if (!(g & 1) && t == (g >> 1)) *reinterpret_cast<volatile uint32_t*>(p.s->stat + 16 * b + 4 * (warp & 3) + t) = 0u;
            if (warp < 18) {
                unsigned char* const ud = reinterpret_cast<unsigned char*>(p.s->uT) + (size_t)(8 * (warp & 1) + 2 * (g >> 1)) * 16384 + b * 128 + (g & 1) * 32 + t * 8;
#pragma unroll
                for (int k = 0; k < 4; k++) *reinterpret_cast<volatile unsigned long long*>(ud + (k >> 1) * 16384 + (k & 1) * 64) = 0ull;
            }
        }
    }
    const uint32_t kw = sb + SM_KW + wg * KW_B;
    const uint32_t tb = table_buf(sb, warp), t5 = sb + SM_WD + warp * 512;
    STAMP(29);
    const float dt = exp_bf(bf_lo(ldt));
    const uint32_t ep = __reduce_or_sync(0xffffffffu, epl);
    auto stats = [&]() {
        const int wq = warp & 3;
        const uint32_t xa = sb + SM_XT + (4 * wq + (g >> 1)) * 1152 + (g & 1) * 576 + t * 16;
        const bool own = !(g & 1) && t == (g >> 1);
        float d[4][4] = {};
        asm volatile("cp.async.wait_group 0;\n" ::: "memory");
        STAMP(26);
        uint4 v[9];
#pragma unroll
        for (int c = 0; c < 9; c++) v[c] = lds128(xa + c * 64);
#pragma unroll
        for (int c = 0; c < 9; c++) {
            mma_bf16(d[2 * (c & 1)], v[c].x, 0x3f803f80u, v[c].y, 0x3f803f80u, v[c].x, v[c].y);
            mma_bf16(d[2 * (c & 1) + 1], v[c].z, 0x3f803f80u, v[c].w, 0x3f803f80u, v[c].z, v[c].w);
        }
        STAMP(27);
        float sm = (g & 1) ? (d[0][3] + d[1][3]) + (d[2][3] + d[3][3]) : (d[0][2] + d[1][2]) + (d[2][2] + d[3][2]);
        float sq = (g & 1) ? (d[0][1] + d[1][1]) + (d[2][1] + d[3][1]) : (d[0][0] + d[1][0]) + (d[2][0] + d[3][0]);
        sm += __shfl_xor_sync(0xffffffffu, sm, 4); sq += __shfl_xor_sync(0xffffffffu, sq, 4);
        if (lane == 0) mbar_arrive(bar_h + 8 * wq);
        float mb, sd;
        ln_stats(sm, sq, mb, sd);
        if (own) p.s->stat[16 * b + 4 * wq + t] = (__float_as_uint(mb) >> 16) | (__float_as_uint(sd) & 0x7fff0000u) | (ep << 31);
        STAMPX(22);
        if (own) stat_store(s_stat + (2 * wq + (t & 1) + 8 * (t >> 1)) * 8, mb, rcp_approx(sd), 0u);
        if (wq == 3) asm volatile("cp.async.bulk.wait_group 0;\n" ::: "memory");
        bar_sync(5, 128);
        STAMP(28);
        uint32_t now;
        asm volatile("mov.u32 %0, %%clock;" : "=r"(now) :: "memory");
        if (wq == 2) {
            conv_constants(sb + SM_LC, lane);
            __syncwarp();
            if (lane < 8) p.s->key3[8 * b + lane] = ep & 1u;
            if (lane == 0) {
                sts64(s_cnt, now, ep);
                mbar_arrive(bar_s);
                bulk_g2s(sb + SM_XT + 16 * 1152, p.dsk, 1152, bar_v);
                bulk_g2s(sb + SM_XT + 17 * 1152, p.wr, 1152, bar_v);
            }
            __syncwarp();
        }
        WPOINT(1, wq == 3);
        if (wq < 2) {
            unsigned char* const ud = reinterpret_cast<unsigned char*>(p.s->uT) + (size_t)(8 * wq + 2 * (g >> 1)) * 16384 + b * 128 + (g & 1) * 32 + t * 8;
            const uint32_t utag = (ep % 7u + 1u) * 0x10001u;
            uint32_t U[2][4];
#pragma unroll
            for (int hf = 0; hf < 2; hf++) {
                const uint2 st = lds64(s_stat + (g + 8 * hf) * 8);
                const uint4 xu = lds128(sb + SM_XT + (TOK(g) + 2 * hf) * 1152 + warp * 64 + t * 16);
                const uint32_t X[4] = {xu.x, xu.y, xu.z, xu.w};
#pragma unroll
                for (int k = 0; k < 4; k++) {
                    const uint32_t u = ln_apply(X[k], STAT_M(st), STAT_H(st), STAT_L(st));
                    U[hf][k] = movm((pack_f16(bf_lo(u), bf_hi(u)) & 0xfff8fff8u) | utag);
                }
            }
#pragma unroll
            for (int k = 0; k < 4; k++) stg64(ud + (k >> 1) * 16384 + (k & 1) * 64, U[0][k], U[1][k]);
        }
    };
    STAMP(1);
    if (wg < 4) { STAMPX(16); }
    KGen kg;
    kgen_setup(kg, bf_lo(pl), bf_lo(pa2), dt);
    kgen_rows(kg, tb, lane);
    STAMP(2);
    const int E = min(max(c_exponent(call_re, call_im, dt) - 243, -120), 120);
    kgen_chain(kg, pc, pi, dt * __uint_as_float((uint32_t)(128 - E) << 23));
    STAMP(3);
    kgen_cols(kg, tb, t5, lane);
    STAMP(4);
    if (wg == 4) stats();
    if (warp != 19) asm volatile("barrier.cluster.wait.aligned;\n" ::: "memory");
    if (wg < 4) { STAMPX(17); }
    if (t128 < 2 * UPAD) sts128(sb + SM_U + wg * USLOT_B + (t128 & 1) * ULO_B + (t128 >> 1) * 16, 0u, 0u, 0u, 0u);
    if (t128 >= 124) sts128(kw + (t128 & 1) * 16 + (t128 & 2) * (KW_PL / 2), 0u, 0u, 0u, 0u);
    if (warp < 15) sts128(sb + SM_Z2 + 4608 + tid * 16, 0u, 0u, 0u, 0u);
    uint32_t co, cn, cd;
    combine_setup(sb, warp, lane, kw, co, cn, cd);
    co = pin(co); cn = pin(cn); cd = pin(cd);
    const uint4* const usrc = reinterpret_cast<const uint4*>(p.s->stat) + pin(wg < 4 ? tid : 512 + (P >> 2) * 1024 + (t128 >> 1) * 8 + (P & 3) * 2 + (t128 & 1));
    if (wg < 4) mbar_wait(bar_h + 8 * (warp & 3));
    if (wg < 4) { STAMPX(19); }
    kgen_mma(kg, tb, t5, lane);
    if (wg < 4) { STAMPX(20); }
    STAMP(5);
    uint4 uv0, uv1;
    auto first_poll = [&](uint32_t dly) {
        mbar_wait(bar_s);
        const uint32_t t0 = lds32(s_cnt);
        uint32_t now;
        do { asm volatile("mov.u32 %0, %%clock;" : "=r"(now) :: "memory"); } while (now - t0 < dly);
        uv0 = ld_poll(usrc);
    };
    if (wg == 4) { first_poll(UDLY); uv1 = ld_poll(usrc + 512); }
    WPOINT(2, warp == 19);
    bar_sync(1 + wg, 128);
    if (wg < 4) { STAMPX(21); }
    kgen_combine(warp & 3, lane, co, cn, cd);
    STAMP(6);
    if (wg < 4) { STAMPX(18); }
    WPOINT(3, warp == 19);
    if (wg < 4) first_poll(SDLY);
    {
        const int wq = warp & 3;
        Conv c;
        const uint32_t pln = sb + SM_PL + wg * PL_B;
        const int e = g - 2 * t + 7;
        c.kw = kw; c.wa = pin(kw + ((e >> 2) & 1) * KW_PL + (8 * wq + (e >> 3)) * 16 + (e & 3) * 4);
        c.ps = mov_v(pln + wq * PLW_B + ((lane >> 3) & 1) * PL_HALF + ((lane >> 4) * 8 + (lane & 7)) * 16); c.warp = warp;
        c.lc = sb + SM_LC; c.fs = (uint32_t)(127 + E) * 0x800080u; c.yp = (ep & 1u) * (NCTA * 18432u);
        c.d0 = ((uint64_t)(ULO_B >> 4) << 16) | ((uint64_t)(128 >> 4) << 32) | (uint64_t)(((sb + SM_U + wg * USLOT_B + UPAD * 16) & 0x3FFFF) >> 4);
        unsigned char* gy = reinterpret_cast<unsigned char*>(p.s->y) + ((size_t)(4 * wq) * DM + ch) * 64;
        auto hook = [&](auto gi) {
                     constexpr int G = decltype(gi)::value;
                     if (G == (wg_is4<decltype(gi)>() ? 2 : 5)) asm volatile("barrier.cluster.wait.aligned;\n" ::: "memory");
                     if (!wg_is4<decltype(gi)>() && (G == 0 || G == 2) && warp == HW && elect_one()) {
                         unsigned char* const sc = reinterpret_cast<unsigned char*>(p.s);
                         if (G == 0) {
                             if (b < 96) bulk_s2g_nc(sc + offsetof(Scratch, part) + b * 12288, sb + SM_Z2, 12288);
                             bulk_s2g(sc + offsetof(Scratch, rows) + (127 - b) * 4608, sb + SM_Z2, 4608);
                         }
                         if (G == 2) {
                             if (YQ == 3) bulk_s2g_nc(sc + offsetof(Scratch, y) + (NCTA * 18432u - c.yp) + b * 13824 + 6912, sb + SM_Z2, 6912);
                             if (YQ) bulk_s2g(sc + offsetof(Scratch, y) + (NCTA * 18432u - c.yp) + b * (4608 * YQ), sb + SM_Z2, YQ == 3 ? 6912 : 4608 * YQ);
                         }
                     }
                     if (!wg_is4<decltype(gi)>()) WPOINT(6 + G, warp == (G >= 7 ? HW : 4 * (G % 3) + 1));
                     if (!wg_is4<decltype(gi)>() && G == 6 && warp == HW) {
                         asm volatile("cp.async.bulk.wait_group 0;\n" ::: "memory");
                         __syncwarp();
                         if (elect_one()) mbar_arrive(bar_v);
                     }
                 };
        if (wg < 4) {
            asm volatile("barrier.cluster.arrive.relaxed.aligned;\n" ::: "memory");
            conv_run(c, pln + wq * 128, gy, hook, [&]() {
                STAMPX(23);
                mbar_wait(bar_x);
                STAMPX(24);
                uint2 xc[4];
                uint32_t xw[4][2];
#pragma unroll
                for (int j = 0; j < 4; j++) xc[j] = lds64(sb + SM_XC + wg * 8192 + j * 2048 + t128 * 16 + odd * 8);
#pragma unroll
                for (int i = 0; i < 8; i++) {
                    const int k = i >> 1, h = i & 1;
                    xw[k][h] = prmt_v(k < 2 ? xc[2 * h].x : xc[2 * h].y, k < 2 ? xc[2 * h + 1].x : xc[2 * h + 1].y, (k & 1) ? 0x7632 : 0x5410);
                }
                const uint32_t ub = mov_v(sb + SM_U + UPAD * 16 + ((tid >> 1) & 1) * ULO_B + (tid >> 2) * 16 + (tid & 1) * 8), tag = ep << 31;
                int it = 0;
                while (min(min((int)(uv0.x ^ tag), (int)(uv0.y ^ tag)), min((int)(uv0.z ^ tag), (int)(uv0.w ^ tag))) < 0x10000) {
                    if (++it > SPIN_LIMIT) TRAP();
                    uv0 = ld_poll(usrc);
                }
                STAMP(8);
                STAMPX(26);
                const float r0 = rcp_approx(fabsf(bf_hi(uv0.x))), r1 = rcp_approx(fabsf(bf_hi(uv0.y))), r2 = rcp_approx(fabsf(bf_hi(uv0.z))), r3 = rcp_approx(fabsf(bf_hi(uv0.w)));
                const uint32_t m[2] = {__byte_perm(uv0.x, uv0.y, 0x5410), __byte_perm(uv0.z, uv0.w, 0x5410)};
                const uint32_t rh[2] = {pack_bf16(r0, r1), pack_bf16(r2, r3)};
                const uint32_t rl[2] = {pack_bf16(r0 - bf_lo(rh[0]), r1 - bf_hi(rh[0])), pack_bf16(r2 - bf_lo(rh[1]), r3 - bf_hi(rh[1]))};
#pragma unroll
                for (int k = 0; k < 4; k++) {
                    const uint32_t u0 = ln_apply(xw[k][0], m[0], rh[0], rl[0]), u1 = ln_apply(xw[k][1], m[1], rh[1], rl[1]);
                    sts64(ub + k * USLOT_B, pack_f16(bf_lo(u0), bf_hi(u0)), pack_f16(bf_lo(u1), bf_hi(u1)));
                }
                STAMPX(29);
                fence_async();
                bar_sync(14, 512);
                STAMP(7);
            });
        } else {
            auto stage = [&]() {
                const uint32_t tag = (ep % 7u + 1u) * 0x10001u;
                int it = 0;
                WPOINT(4, warp == 19);
                while (true) {
                    uv0.x ^= tag; uv0.y ^= tag; uv0.z ^= tag; uv0.w ^= tag; uv1.x ^= tag; uv1.y ^= tag; uv1.z ^= tag; uv1.w ^= tag;
                    if ((((uv0.x | uv0.y | uv0.z) | (uv0.w | uv1.x | uv1.y) | (uv1.z | uv1.w)) & 0x70007u) == 0) break;
                    if (++it > SPIN_LIMIT) TRAP();
                    uv0 = ld_poll(usrc); uv1 = ld_poll(usrc + 512);
                }
                STAMP(8);
                const uint32_t ub = sb + SM_U + UPAD * 16 + 4 * USLOT_B + (t128 & 1) * ULO_B + (t128 >> 1) * 16;
                sts128(ub, uv0.x, uv0.y, uv0.z, uv0.w);
                sts128(ub + 1024, uv1.x, uv1.y, uv1.z, uv1.w);
                fence_async();
                asm volatile("barrier.cluster.arrive.relaxed.aligned;\n" ::: "memory");
                bar_sync(5, 128);
                WPOINT(5, warp == 19);
                STAMP(7);
            };
            stage();
            if (odd) conv_inner(c, pln + wq * 128, gy, sb + SM_RX, hook);
            else conv_outer(c, pln + wq * 128, gy, sb + SM_RX, hook);
        }
        STAMP(10);
    }
    {
    const int lane = lane_v(), tid = 32 * warp + lane, g = lane >> 2, t = lane & 3;
    const uint32_t par = ~ep & 1u;
    bar_sync(0, NWRK);
    STAMP(11);
    uint32_t H[2][4] = {}, U2[2][4] = {};
    auto publish = [&](bool hi, int slot) {
        uint4* rowp = reinterpret_cast<uint4*>(p.s->rows) + slot * 144 + warp * 4 + t;
        stg128(rowp, nzw(hi ? U2[1][0] : U2[0][0]), nzw(hi ? U2[1][1] : U2[0][1]), nzw(hi ? U2[1][2] : U2[0][2]), nzw(hi ? U2[1][3] : U2[0][3]));
        stg128(rowp + 72, nzw(hi ? H[1][0] : H[0][0]), nzw(hi ? H[1][1] : H[0][1]), nzw(hi ? H[1][2] : H[0][2]), nzw(hi ? H[1][3] : H[0][3]));
    };
#define KTOK(k) (int)(((~(k) >> 5) & 0x7f0u) | (((k) >> 1) & 15u))
#define KLATE(k) (((k) & 0x1e0u) < 0xe0u)
#define KSLOT(k, s) (KLATE(k) ? 2 * NCTA + (s) : (int)(((k) >> 8) & 0xffu))
    const uint4* const rsrc = reinterpret_cast<const uint4*>(p.s->rows) + 36 * odd;
    auto gather = [&](uint32_t mine) {
        int it = 0;
        uint32_t mn;
        do {
            mn = 1;
#pragma unroll 1
            for (int r = 0; r < 9; r++) {
                const uint32_t k = __shfl_sync(0xffffffffu, mine, r < 8 ? 4 * r : lane);
                const int row = r < 8 ? r : g, c = r < 8 ? lane : 32 + t;
                asm volatile("cp.async.cg.shared.global [%0], [%1], 16;\n" ::"r"(sb + SM_XS + row * XS_PITCH + c * 16), "l"(rsrc + KSLOT(k, row) * 144 + c) : "memory");
            }
            asm volatile("cp.async.wait_all;\n" ::: "memory");
#pragma unroll 1
            for (int r = 0; r < 9; r++) mn = min(mn, min4(lds128(sb + SM_XS + (r < 8 ? r * XS_PITCH + lane * 16 : g * XS_PITCH + (32 + t) * 16))));
            if (++it > SPIN_LIMIT) TRAP();
        } while (__any_sync(0xffffffffu, mn == 0));
    };
    auto late_rows = [&](auto role) {
        const uint32_t kk = lds32(s_key + (lane & 7) * 4), ep = lds32(s_cnt + 4);
        const bool own = KLATE(kk) && (KTOK(kk) >> 4) == b;
        uint32_t todo = __ballot_sync(0xffffffffu, own) & 0xffu;
        if (decltype(role)::value == 0 && todo) {
#pragma unroll
            for (int hf = 0; hf < 2; hf++) {
                const uint4 h = lds128(sb + SM_U + hf * 9216 + tid * 16);
                const uint2 st = lds64(s_stat + (g + 8 * hf) * 8);
                H[hf][0] = h.x; H[hf][1] = h.y; H[hf][2] = h.z; H[hf][3] = h.w;
#pragma unroll
                for (int k = 0; k < 4; k++) U2[hf][k] = ln_apply(H[hf][k], STAT_M(st), STAT_H(st), STAT_L(st));
            }
#pragma unroll 1
            while (todo) {
                const int s = __ffs(todo) - 1, tk = KTOK(__shfl_sync(0xffffffffu, kk, s));
                todo &= todo - 1;
                if ((tk & 13) == TOK(g)) publish(tk & 2, 2 * NCTA + s);
            }
            __threadfence();
        }
        bar_sync(0, NWRK);
        if (decltype(role)::value == 1) {
            if (lane < NSEL && own) *reinterpret_cast<volatile unsigned*>(p.s->flag + lane) = ep + 1u;
            int it = 0;
            while (__any_sync(0xffffffffu, KLATE(kk) && ld_acquire32(p.s->flag + (lane & 7)) != ep + 1u)) { if (++it > SPIN_LIMIT) TRAP(); }
            gather(__shfl_sync(0xffffffffu, kk, g));
        }
        bar_sync(0, NWRK);
    };
    if (warp < 18) {
        const unsigned char* ys = reinterpret_cast<const unsigned char*>(p.s->y) + (b < 32 * YQ ? (par ^ 1u) * (NCTA * 18432u) : 0u) +
                                  ((P * DM + 32 * warp + 8 * (g >> 1) + (g & 1)) * 64 + odd * 32 + t * 8);
        uint2 yv[4];
        const bool early = b < 64 && warp < 16;
        if (early) {
#pragma unroll
            for (int k = 0; k < 4; k++) yv[k] = ld_poll64(ys + k * 128);
        }
        mbar_wait(bar_v);
        const uint32_t xa = sb + SM_XT + warp * 64 + t * 16;
        const uint4 x0 = lds128(xa + TOK(g) * 1152), x1 = lds128(xa + (TOK(g) + 2) * 1152), dk = lds128(xa + 16 * 1152);
        uint4 wr = make_uint4(0u, 0u, 0u, 0u);
        if (g == 0) wr = lds128(xa + 17 * 1152);
        const uint32_t Z[2][4] = {{x0.x, x0.y, x0.z, x0.w}, {x1.x, x1.y, x1.z, x1.w}}, D4[4] = {dk.x, dk.y, dk.z, dk.w};
#pragma unroll
        for (int hf = 0; hf < 2; hf++) {
            const uint2 st = lds64(s_stat + (g + 8 * hf) * 8);
#pragma unroll
            for (int k = 0; k < 4; k++) U2[hf][k] = hmul2_bf(ln_apply(Z[hf][k], STAT_M(st), STAT_H(st), STAT_L(st)), D4[k]);
        }
        const uint32_t la = pin(sb + SM_LNP + (g * 20 + warp) * 4 + (U2[0][3] & U2[1][3] & (warp >> 8)));
        int it = 0;
        float d[2][4];
        uint32_t mn;
        do {
            if (!early || it) {
#pragma unroll
                for (int k = 0; k < 4; k++) yv[k] = ld_poll64(ys + k * 128);
            }
            if (++it > SPIN_LIMIT) TRAP();
            mn = min(min(min(yv[0].x, yv[0].y), min(yv[1].x, yv[1].y)), min(min(yv[2].x, yv[2].y), min(yv[3].x, yv[3].y)));
#pragma unroll
            for (int k = 0; k < 4; k++) {
                H[0][k] = hadd2_bf(Z[0][k], hadd2_bf(movm(yv[k].x), U2[0][k]));
                H[1][k] = hadd2_bf(Z[1][k], hadd2_bf(movm(yv[k].y), U2[1][k]));
            }
            ln_partial(H, d);
        } while (__any_sync(0xffffffffu, mn == 0));
        STAMP(12);
        if (t == (g >> 1)) {
            stsf(la, (g & 1) ? d[0][3] : d[0][2]); stsf(la + 8 * 80, (g & 1) ? d[1][3] : d[1][2]);
            stsf(la + 16 * 80, (g & 1) ? d[0][1] : d[0][0]); stsf(la + 24 * 80, (g & 1) ? d[1][1] : d[1][0]);
        }
        bar_arrive(6, NWRK);
        STAMP(13);
        bar_sync(7, 608);
        STAMP(14);
#pragma unroll
        for (int hf = 0; hf < 2; hf++) {
            const uint2 st = lds64(s_stat + (g + 8 * hf) * 8);
#pragma unroll
            for (int k = 0; k < 4; k++) U2[hf][k] = ln_apply(H[hf][k], STAT_M(st), STAT_H(st), STAT_L(st));
        }
        {
            float cs[4] = {0.f, 0.f, 0.f, 0.f};
            mma_bf16(cs, U2[0][0], U2[1][0], U2[0][1], U2[1][1], wr.x, wr.y);
            mma_bf16(cs, U2[0][2], U2[1][2], U2[0][3], U2[1][3], wr.z, wr.w);
            if (t == 0) { stsf(la + 32 * 80, cs[0]); stsf(la + 40 * 80, cs[2]); }
            bar_arrive(8, 608);
        }
        bar_sync(9, 608);
        {
            const uint2 best = lds64(s_rank);
            uint32_t todo = ((best.x & 26u) == 2 * TOK(g) ? 2u : 0u) | ((best.y & 26u) == 2 * TOK(g) ? 1u : 0u);
#pragma unroll 1
            while (todo) { publish((todo & 2u ? best.x : best.y) & 4u, 254 - 2 * b + (todo >> 1)); todo &= todo >> 1; }
        }
#pragma unroll
        for (int hf = 0; hf < 2; hf++) {
            sts128(sb + SM_OUT + (TOK(g) + 2 * hf) * (DM * 2) + warp * 64 + t * 16,
                   hadd2_bf(H[hf][0], U2[hf][0]), hadd2_bf(H[hf][1], U2[hf][1]), hadd2_bf(H[hf][2], U2[hf][2]), hadd2_bf(H[hf][3], U2[hf][3]));
            sts128(sb + SM_U + hf * 9216 + tid * 16, H[hf][0], H[hf][1], H[hf][2], H[hf][3]);
        }
        STAMP(15);
        const int mi = lane >> 3, rr = lane & 7;
        const bool gate = warp < 12 && (warp & 3) != 2;
        const int fj = gate ? 3 * (warp >> 2) + min(warp & 3, 2) : (warp < 12 ? warp >> 2 : warp - 9);
        if (gate) {
            uint32_t W[18][4];
            mbar_wait(bar_w);
            const uint32_t aad = sb + SM_WG + (mi & 1) * SM_WU + (rr + 8 * (mi >> 1)) * W_PITCH + fj * 16;
#pragma unroll
            for (int k = 0; k < 18; k++) ldsm_x4_t(W[k][0], W[k][1], W[k][2], W[k][3], aad + k * 16 * W_PITCH);
            const uint32_t bad = pin(sb + SM_XS + rr * XS_PITCH + mi * 16);
            fence_async();
            STAMP2(17);
            if (bar_or(11, NWRK, false)) {
                late_rows(IC<0>());
#pragma unroll
                for (int k = 0; k < 18; k++) ldsm_x4_t(W[k][0], W[k][1], W[k][2], W[k][3], aad + k * 16 * W_PITCH);
            }
            STAMP2(19);
            float c4[2][4] = {};
#pragma unroll
            for (int k = 0; k < 18; k += 2) {
                uint32_t b0, b1, b2, b3;
                ldsm_x4(b0, b1, b2, b3, bad + k * 32);
                mma_bf16(c4[0], W[k][0], W[k][1], W[k][2], W[k][3], b0, b1);
                mma_bf16(c4[1], W[k + 1][0], W[k + 1][1], W[k + 1][2], W[k + 1][3], b2, b3);
            }
            const uint32_t ex = sb + SM_EX + (32 * fj + lane) * 16;
            const float e0 = c4[0][0] + c4[1][0], e1 = c4[0][1] + c4[1][1], e2 = c4[0][2] + c4[1][2], e3 = c4[0][3] + c4[1][3];
            asm volatile("st.async.shared::cluster.mbarrier::complete_tx::bytes.v4.f32 [%0], {%1,%2,%3,%4}, [%5];\n"
                         ::"r"(ex ^ 0x1000000u), "f"(e0), "f"(e1), "f"(e2), "f"(e3), "r"(bar_g ^ 0x1000000u) : "memory");
            STAMP2(20);
            mbar_wait(bar_g);
            const uint4 o = lds128(ex);
            const uint32_t G = pack_bf16(e0 + __uint_as_float(o.x), e1 + __uint_as_float(o.y)), U = pack_bf16(e2 + __uint_as_float(o.z), e3 + __uint_as_float(o.w));
            sts32(sb + SM_GU + (32 * fj + lane) * 4, hmul2_bf(pack_bf16(bf_lo(G) * sigmoid_f(bf_lo(G)), bf_hi(G) * sigmoid_f(bf_hi(G))), U));
            bar_arrive(13, NWRK);
        } else {
            uint32_t W[2][18];
            auto load_wd = [&]() {
                mbar_wait(bar_d);
                const uint32_t base = sb + SM_WD + (4 * fj + (mi & 1)) * 16 + rr * WD_PITCH;
#pragma unroll
                for (int j = 0; j < 2; j++) {
#pragma unroll
                    for (int k = 0; k < 4; k++) ldsm_x4_t(W[j][4 * k], W[j][4 * k + 1], W[j][4 * k + 2], W[j][4 * k + 3], base + j * 32 + (k * 16 + 8 * (mi >> 1)) * WD_PITCH);
                    ldsm_x2_t(W[j][16], W[j][17], base + j * 32 + 64 * WD_PITCH);
                }
            };
            const uint32_t po = pin((((8 * (18 * odd + 2 * fj) + g) * 64 + P) * 16 + t * 4) * 4);
            fence_async();
            STAMP2(17);
            if (bar_or(11, NWRK, false)) late_rows(IC<0>());
            delay(DDLY); load_wd();
            bar_sync(13, NWRK);
            STAMP2(21);
            uint32_t gb[9];
            ldsm_x4_t(gb[0], gb[1], gb[2], gb[3], sb + SM_GU + lane * 16);
            ldsm_x4_t(gb[4], gb[5], gb[6], gb[7], sb + SM_GU + 512 + lane * 16);
            ldsm_x1_t(gb[8], sb + SM_GU + 1024 + lane * 16);
            float c4[2][4] = {}, d4[2][4] = {};
#pragma unroll
            for (int k = 0; k < 4; k += 2)
#pragma unroll
                for (int j = 0; j < 2; j++) {
                    mma_bf16(c4[j], W[j][4 * k], W[j][4 * k + 1], W[j][4 * k + 2], W[j][4 * k + 3], gb[2 * k], gb[2 * k + 1]);
                    mma_bf16(d4[j], W[j][4 * k + 4], W[j][4 * k + 5], W[j][4 * k + 6], W[j][4 * k + 7], gb[2 * k + 2], gb[2 * k + 3]);
                }
#pragma unroll
            for (int j = 0; j < 2; j++) mma_bf16_k8(c4[j], W[j][16], W[j][17], gb[8]);
#pragma unroll
            for (int j = 0; j < 2; j++)
                stg128(reinterpret_cast<unsigned char*>(p.s->part) + po + j * 32768, __float_as_uint(c4[j][0] + d4[j][0]) | 1u, __float_as_uint(c4[j][1] + d4[j][1]) | 1u,
                       __float_as_uint(c4[j][2] + d4[j][2]) | 1u, __float_as_uint(c4[j][3] + d4[j][3]) | 1u);
        }
        STAMP2(22);
    } else if (warp == 18) {
        const uint4* const ksrc = reinterpret_cast<const uint4*>(p.s->key3) + pin(2 * lane);
        const unsigned char* const rl = reinterpret_cast<const unsigned char*>(rsrc) + pin(lane * 16);
        const uint32_t sa = pin(sb + SM_LNP + lane * 80);
        const uint32_t klo = pin((uint32_t)(127 - b) << 9 | (uint32_t)(15 - ROWTOK(lane & 15)) << 1 | par), ra = pin(sb + SM_LNP + (32 + (lane & 15)) * 80);
        uint4* const kdst = reinterpret_cast<uint4*>(p.s->key3) + pin((lane >> 1) * 2 * NCTA + 2 * b + (lane & 1));
        FIX(ra);
        bar_sync(6, NWRK);
        {
            float mb, rc;
            ln_finish(sum18(sa), lane, mb, rc);
            if (lane < 16) stat_store(s_stat + lane * 8, mb, rc, 0u);
        }
        bar_arrive(7, 608);
        bar_sync(8, 608);
        uint32_t t0;
        {
            const uint32_t bits = __float_as_uint(rbf(sum18(ra)));
            const uint32_t me = ((bits ^ ((uint32_t)((int)bits >> 31) | 0x80000000u)) & 0xffff0000u) | klo;
            const uint32_t k0 = __reduce_max_sync(0xffffffffu, me), k1 = __reduce_max_sync(0xffffffffu, me == k0 ? 0u : me);
            const uint32_t k2 = __reduce_max_sync(0xffffffffu, me >= k1 ? 0u : me);
            if (lane < 2) stg128(kdst, k0 ^ 0x11eu, k1 ^ 0xfeu, k2 ^ 0xdeu, par);
            asm volatile("mov.u32 %0, %%clock;" : "=r"(t0) :: "memory");
            STAMPW(23);
            if (lane == 0) sts64(s_rank, ~k0, ~k1);
            bar_arrive(9, 608);
            sts32(s_k16 + (lane & 15) * 4, me);
            __syncwarp();
            const uint4 v = lds128(s_k16 + (lane & 16) * 2), w = lds128(s_k16 + (lane & 16) * 2 + 16);
            int rank = ((v.x > me) + (v.y > me)) + ((v.z > me) + (v.w > me)) + (((w.x > me) + (w.y > me)) + ((w.z > me) + (w.w > me)));
            rank += __shfl_xor_sync(0xffffffffu, rank, 16);
            if (lane < 16 && rank < 8) p.s->key[8 * b + rank] = (me ^ 0x1eu) | ((8 - rank) << 5);
        }
        uint4 kq[4];
        uint32_t u[4], mine = 0, m;
        int it = 0;
        { uint32_t now; do { asm volatile("mov.u32 %0, %%clock;" : "=r"(now) :: "memory"); } while (now - t0 < KDLY); }
        do {
#pragma unroll
            for (int i = 0; i < 4; i++) kq[i] = ld_poll(ksrc + 64 * i);
            if (++it > SPIN_LIMIT) TRAP();
            uint32_t S[2][4];
#pragma unroll
            for (int i = 0; i < 2; i++) {
                const uint4 &c = kq[2 * i], &d = kq[2 * i + 1];
                const uint32_t m1 = min(c.x, d.x), m2 = max(c.y, d.y);
                S[i][0] = max(c.x, d.x); S[i][1] = max(m1, m2); S[i][2] = min(m1, m2); S[i][3] = min(c.y, d.y);
            }
            const uint32_t a0 = max(S[0][0], S[1][3]), a1 = max(S[0][1], S[1][2]), a2 = max(S[0][2], S[1][1]), a3 = max(S[0][3], S[1][0]);
            const uint32_t b0 = max(a0, a2), b2 = min(a0, a2), b1 = max(a1, a3), b3 = min(a1, a3);
            u[0] = max(b0, b1); u[1] = min(b0, b1); u[2] = max(b2, b3); u[3] = min(b2, b3);
        } while (__any_sync(0xffffffffu, and3(or3(or3(xor_or(kq[0].x, kq[0].y, par), xor_or(kq[0].z, kq[1].x, par), xor_or(kq[1].y, kq[1].z, par)),
                                                  xor_or(kq[2].x, kq[2].y, par), xor_or(kq[2].z, kq[3].x, par)) | xor_or(kq[3].y, kq[3].z, par), 1u, 1u)));
        STAMPW(16);
        uint4 v[9];
#pragma unroll
        for (int r = 0; r < 8; r++) {
            m = __reduce_max_sync(0xffffffffu, u[0]);
            if (u[0] == m) { u[0] = u[1]; u[1] = u[2]; u[2] = u[3]; u[3] = 0; }
            if (g == r) mine = m;
            v[r] = ld_poll(rl + (size_t)((m >> 8) & 0xffu) * 2304u);
        }
        v[8] = ld_poll(reinterpret_cast<const unsigned char*>(rsrc) + (((mine >> 8) & 0xffu) * 2304u + (32 + t) * 16));
        bool again = __any_sync(0xffffffffu, u[0] == 0 || max(max(kq[0].z, kq[1].z), max(kq[2].z, kq[3].z)) > m);
        if (again) {
#pragma unroll 1
            for (int i = 0; i < 8; i++) {
                uint4 k;
                do { k = ld_poll(reinterpret_cast<const uint4*>(p.s->key) + 32 * i + lane); if (++it > SPIN_LIMIT) TRAP(); } while (((k.x ^ par) | (k.y ^ par) | (k.z ^ par) | (k.w ^ par)) & 1u);
                sts128(sb + SM_KEYS + (32 * i + lane) * 16, k.x, k.y, k.z, k.w);
            }
            m = 0xffffffffu;
#pragma unroll 1
            for (int r = 0; r < 8; r++) {
                uint32_t c = 0;
#pragma unroll 2
                for (int i = 0; i < 8; i++) {
                    const uint4 k = lds128(sb + SM_KEYS + (32 * i + lane) * 16);
                    c = max(max(c, k.x < m ? k.x : 0u), max(k.y < m ? k.y : 0u, max(k.z < m ? k.z : 0u, k.w < m ? k.w : 0u)));
                }
                m = __reduce_max_sync(0xffffffffu, c);
                if (g == r) mine = m;
            }
        }
        if (t == 0) sts32(s_key + g * 4, mine);
        uint32_t mn = 1;
#pragma unroll
        for (int r = 0; r < 9; r++) {
            sts128(sb + SM_XS + (r < 8 ? r * XS_PITCH + lane * 16 : g * XS_PITCH + (32 + t) * 16), v[r].x, v[r].y, v[r].z, v[r].w);
            mn = min(mn, min4(v[r]));
        }
        if ((again || __any_sync(0xffffffffu, mn == 0)) && !__any_sync(0xffffffffu, KLATE(mine))) gather(mine);
        STAMPW(18);
        if (bar_or(11, NWRK, KLATE(mine))) late_rows(IC<1>());
    } else {
        bar_sync(6, NWRK);
        WPOINT(16, true);
        if (WANY(17) || WANY(18)) delay(WDLY);
        WPOINT(17, true);
        if (WANY(18)) delay(WDLY);
        WPOINT(18, true);
        if (bar_or(11, NWRK, false)) late_rows(IC<2>());
        const int tk = KTOK(lds32(s_key + (lane & 7) * 4));
        const uint32_t sel = __reduce_or_sync(0xffffffffu, (tk >> 4) == b ? 1u << (tk & 15) : 0u);
        if (sel ? lane < 16 && !((sel >> lane) & 1u) : lane == 0) bulk_s2g(p.out + (size_t)(16 * b + lane) * DM, sb + SM_OUT + lane * (DM * 2), sel ? DM * 2 : 16 * DM * 2);
        __syncwarp();
    }
    if (warp == 8 || warp >= 18) {
        const int grp = 3 * b + (warp == 8 ? 0 : warp - 17), fsl = 2 * t + ((lane >> 3) & 1), fc = 16 * (grp >> 3) + (grp & 7) + 8 * (lane >> 4);
        const uint32_t fk = lds32(s_key + fsl * 4);
        float hv = 0.f, u2 = 0.f;
        int it = 0;
        if (b < 96) {
            const uint32_t* const fsrc = p.s->rows + KSLOT(fk, fsl) * DM + (fc >> 1);
            uint32_t hw, uw;
            do { hw = ld_poll32(fsrc + 288); uw = ld_poll32(fsrc); if (++it > SPIN_LIMIT) TRAP(); } while (!hw || !uw);
            hv = (fc & 1) ? bf_hi(hw) : bf_lo(hw); u2 = (fc & 1) ? bf_hi(uw) : bf_lo(uw);
        }
        const float rs = rbf(sigmoid_f(__uint_as_float((fk ^ ((uint32_t)((int)~fk >> 31) | 0x80000000u)) & 0xffff0000u)));
        const uint32_t dof = pin(KTOK(fk) * DM + fc), so = pin(grp * 256 + lane);
        if (warp > 17) bar_sync(13, NWRK);
        if (b < 96) {
            delay(warp > 17 ? FDLY : FDLY2);
            const uint4* src = reinterpret_cast<const uint4*>(p.s->part) + so;
            float s0, s1, s2, s3;
            uint32_t ok;
            do {
                uint4 a[8];
#pragma unroll
                for (int i = 0; i < 8; i++) a[i] = ld_poll(src + 32 * i);
                if (++it > SPIN_LIMIT) TRAP();
#define A4(i) and3(and3(a[i].x, a[i].y, a[i].z), and3(a[i].w, a[i + 1].x, a[i + 1].y), a[i + 1].z & a[i + 1].w)
#define S8(f) (((__uint_as_float(a[0].f) + __uint_as_float(a[1].f)) + (__uint_as_float(a[2].f) + __uint_as_float(a[3].f))) + \
               ((__uint_as_float(a[4].f) + __uint_as_float(a[5].f)) + (__uint_as_float(a[6].f) + __uint_as_float(a[7].f))))
                ok = and3(A4(0), A4(2), and3(A4(4), A4(6), 1u));
                s0 = S8(x); s1 = S8(y); s2 = S8(z); s3 = S8(w);
                asm volatile("" : "+f"(s0), "+f"(s1), "+f"(s2), "+f"(s3));
#undef A4
#undef S8
            } while (__any_sync(0xffffffffu, !ok));
            STAMP2(24);
            const bool up = lane & 16, od = lane & 8;
            const float r0 = (up ? s2 : s0) + __shfl_xor_sync(0xffffffffu, up ? s0 : s2, 16), r1 = (up ? s3 : s1) + __shfl_xor_sync(0xffffffffu, up ? s1 : s3, 16);
            float y = (od ? r1 : r0) + __shfl_xor_sync(0xffffffffu, od ? r0 : r1, 8);
            y += __shfl_xor_sync(0xffffffffu, y, 4);
            p.out[dof] = __float2bfloat16_rn(hv + rbf(u2 + rbf(rbf(y) * rs)));
        }
    }
    if (warp == 19) asm volatile("cp.async.bulk.wait_group.read 0;\n" ::: "memory");
    if (b == 0 && tid < 8) *reinterpret_cast<volatile unsigned*>(p.s->hint + tid * 32 + 1) = lds32(s_cnt + 4) + 1u;
    STAMP(25);
    }
}

typedef CUresult (*PFN_tmEncode)(CUtensorMap*, CUtensorMapDataType, cuuint32_t, void*, const cuuint64_t*, const cuuint64_t*, const cuuint32_t*,
                                 const cuuint32_t*, CUtensorMapInterleave, CUtensorMapSwizzle, CUtensorMapL2promotion, CUtensorMapFloatOOBfill);

extern "C" void kernel_launch(void* const* d_in, const int* in_sizes, int n_in, void* d_out, int out_size) {
    Params p;
    p.x = (const bf16*)d_in[0];
    p.lar = (const bf16*)d_in[1];
    p.aim = (const bf16*)d_in[2];
    p.cre = (const bf16*)d_in[3];
    p.cim = (const bf16*)d_in[4];
    p.ldt = (const bf16*)d_in[5];
    p.dsk = (const bf16*)d_in[6];
    p.wr = (const bf16*)d_in[8];
    p.out = (bf16*)d_out;
    static PFN_tmEncode enc = nullptr;
    static void* scratch = nullptr;
    if (!enc) {
        cudaFuncSetAttribute(fused_kernel, cudaFuncAttributeMaxDynamicSharedMemorySize, SMEM_TOTAL);
        void* fn = nullptr;
        cudaDriverEntryPointQueryResult qr;
        cudaGetDriverEntryPoint("cuTensorMapEncodeTiled", &fn, cudaEnableDefault, &qr);
        enc = (PFN_tmEncode)fn;
        cudaGetSymbolAddress(&scratch, g_scratch);
    }
    p.s = (Scratch*)scratch;
    CUtensorMap tm_g, tm_u, tm_d, tm_x;
    const cuuint64_t dims[2] = {FF, DM}, strides[1] = {FF * 2};
    const cuuint32_t box[2] = {72, 48}, es[2] = {1, 1};
    enc(&tm_g, CU_TENSOR_MAP_DATA_TYPE_BFLOAT16, 2, d_in[9], dims, strides, box, es, CU_TENSOR_MAP_INTERLEAVE_NONE, CU_TENSOR_MAP_SWIZZLE_NONE,
        CU_TENSOR_MAP_L2_PROMOTION_NONE, CU_TENSOR_MAP_FLOAT_OOB_FILL_NONE);
    enc(&tm_u, CU_TENSOR_MAP_DATA_TYPE_BFLOAT16, 2, d_in[10], dims, strides, box, es, CU_TENSOR_MAP_INTERLEAVE_NONE, CU_TENSOR_MAP_SWIZZLE_NONE,
        CU_TENSOR_MAP_L2_PROMOTION_NONE, CU_TENSOR_MAP_FLOAT_OOB_FILL_NONE);
    const cuuint64_t ddims[2] = {DM / 2, FF}, dstrides[1] = {DM * 2};
    const cuuint32_t dbox[2] = {WD_PITCH / 4, 8};
    enc(&tm_d, CU_TENSOR_MAP_DATA_TYPE_UINT32, 2, d_in[11], ddims, dstrides, dbox, es, CU_TENSOR_MAP_INTERLEAVE_NONE, CU_TENSOR_MAP_SWIZZLE_NONE,
        CU_TENSOR_MAP_L2_PROMOTION_NONE, CU_TENSOR_MAP_FLOAT_OOB_FILL_NONE);
    const cuuint64_t xdims[4] = {DM, 128, 4, 4}, xstrides[3] = {DM * 8, DM * 2, DM * 1024};
    const cuuint32_t xbox[4] = {8, 128, 4, 2}, xes[4] = {1, 1, 1, 1};
    enc(&tm_x, CU_TENSOR_MAP_DATA_TYPE_BFLOAT16, 4, d_in[0], xdims, xstrides, xbox, xes, CU_TENSOR_MAP_INTERLEAVE_NONE, CU_TENSOR_MAP_SWIZZLE_NONE,
        CU_TENSOR_MAP_L2_PROMOTION_NONE, CU_TENSOR_MAP_FLOAT_OOB_FILL_NONE);
    fused_kernel<<<NCTA, NTHR, SMEM_TOTAL>>>(p, tm_g, tm_u, tm_d, tm_x);
}
```

```cpp
#include <cuda_runtime.h>
#include <cuda.h>
#include <cuda_fp16.h>
#include <cuda_bf16.h>
#include <stdint.h>

#define LSEQ 2048
#define DM 576
#define NST 128
#define FF 4608
#define NSEL 8
#define NCTA 128
#define NTHR 640
#define NWRK 640

typedef __nv_bfloat16 bf16;

#define SM_WG 0
#define SM_WU 41472
#define SM_XC (82944 - 32768)
#define SM_WD 82944
#define W_PITCH 144
#define WD_PITCH 592
#define SM_Z2 (SM_WD + 10240)
#define SM_XT (SM_PL - 18 * 1152)
#define SM_PL (SM_WD + 46080)
#define PL_HALF 1344
#define PLW_B 2624
#define PL_B (4 * PLW_B)
#define SM_U (SM_PL + 5 * PL_B)
#define UPAD 20
#define ULO_B ((UPAD + 128) * 16)
#define USLOT_B (2 * ULO_B)
#define SM_KW (SM_U + 5 * USLOT_B)
#define KW_B 3712
#define KW_PL 1216
#define KW_P 2400
#define KW_H 3440
#define SM_MISC (SM_KW + 5 * KW_B)
#define SM_LC (SM_MISC + 416)
#define SM_LNP (SM_LC + 768)
#define SM_RX (SM_LNP + 3840)
#define SMEM_TOTAL (SM_RX + 3088)
#define TBW PLW_B
#define SM_OUT SM_PL
#define SM_XS (SM_PL + 18432)
#define XS_PITCH 592
#define SM_GU (SM_PL + 23296)
#define SM_EX (SM_PL + 24576)
#define SM_KEYS SM_KW

struct __align__(128) Scratch {
    unsigned hint[8 * 32];
    unsigned flag[32];
    uint32_t key3[NCTA * 8];
    uint32_t key[NCTA * 8];
    uint32_t stat[LSEQ];
    uint32_t uT[64 * (LSEQ / 2)];
    uint32_t y[(NCTA + 96) * DM * 8];
    uint32_t part[288 * 64 * 16];
    uint32_t rows[(2 * NCTA + NSEL) * DM];
};
__device__ Scratch g_scratch;
#define STAMP(i)
#define STAMPX(i)
#define STAMPY(i)

__device__ __forceinline__ float rbf(float x) {
    uint32_t r;
    asm("cvt.rn.bf16x2.f32 %0, %1, %2;\n" : "=r"(r) : "f"(x), "f"(0.f));
    return __uint_as_float(r);
}
__device__ __forceinline__ uint32_t pack_bf16(float lo, float hi) {
    uint32_t r;
    asm("cvt.rn.bf16x2.f32 %0, %1, %2;\n" : "=r"(r) : "f"(hi), "f"(lo));
    return r;
}
__device__ __forceinline__ uint32_t pack_f16(float lo, float hi) {
    uint32_t r;
    asm("cvt.rn.f16x2.f32 %0, %1, %2;\n" : "=r"(r) : "f"(hi), "f"(lo));
    return r;
}
__device__ __forceinline__ uint32_t pack_f16_rz(float lo, float hi) {
    uint32_t r;
    asm("cvt.rz.f16x2.f32 %0, %1, %2;\n" : "=r"(r) : "f"(hi), "f"(lo));
    return r;
}
__device__ __forceinline__ float bf_lo(uint32_t w) { return __uint_as_float(w << 16); }
__device__ __forceinline__ float bf_hi(uint32_t w) { return __uint_as_float(w & 0xffff0000u); }
__device__ __forceinline__ uint32_t hadd2_bf(uint32_t a, uint32_t b) {
    __nv_bfloat162 r = __hadd2_rn(*reinterpret_cast<__nv_bfloat162*>(&a), *reinterpret_cast<__nv_bfloat162*>(&b));
    return *reinterpret_cast<uint32_t*>(&r);
}
__device__ __forceinline__ uint32_t hsub2_bf(uint32_t a, uint32_t b) {
    __nv_bfloat162 r = __hsub2_rn(*reinterpret_cast<__nv_bfloat162*>(&a), *reinterpret_cast<__nv_bfloat162*>(&b));
    return *reinterpret_cast<uint32_t*>(&r);
}
__device__ __forceinline__ uint32_t hmul2_bf(uint32_t a, uint32_t b) {
    __nv_bfloat162 r = __hmul2_rn(*reinterpret_cast<__nv_bfloat162*>(&a), *reinterpret_cast<__nv_bfloat162*>(&b));
    return *reinterpret_cast<uint32_t*>(&r);
}
__device__ __forceinline__ uint32_t hfma2_bf(uint32_t a, uint32_t b, uint32_t c) { uint32_t r; asm("fma.rn.bf16x2 %0, %1, %2, %3;\n" : "=r"(r) : "r"(a), "r"(b), "r"(c)); return r; }
__device__ __forceinline__ uint32_t hmul2(uint32_t a, uint32_t b) { uint32_t r; asm("mul.rn.f16x2 %0, %1, %2;\n" : "=r"(r) : "r"(a), "r"(b)); return r; }
__device__ __forceinline__ uint32_t hadd2(uint32_t a, uint32_t b) { uint32_t r; asm("add.rn.f16x2 %0, %1, %2;\n" : "=r"(r) : "r"(a), "r"(b)); return r; }
__device__ __forceinline__ uint32_t hfma2(uint32_t a, uint32_t b, uint32_t c) { uint32_t r; asm("fma.rn.f16x2 %0, %1, %2, %3;\n" : "=r"(r) : "r"(a), "r"(b), "r"(c)); return r; }
__device__ __forceinline__ uint32_t hfms2(uint32_t a, uint32_t b, uint32_t c) {
    uint32_t r;
    asm("{\n.reg .b32 n;\nneg.f16x2 n, %2;\nfma.rn.f16x2 %0, %1, n, %3;\n}\n" : "=r"(r) : "r"(a), "r"(b), "r"(c));
    return r;
}
__device__ __forceinline__ uint32_t nzw(uint32_t w) { return max(w, 1u); }
__device__ __forceinline__ uint32_t nzf(float f) { const uint32_t w = __float_as_uint(f); return w ? w : 0x80000000u; }
__device__ __forceinline__ uint32_t smem_u32(const void* p) { return (uint32_t)__cvta_generic_to_shared(p); }
__device__ __forceinline__ uint32_t lds32(uint32_t addr) {
    uint32_t v;
    asm volatile("ld.shared.u32 %0, [%1];\n" : "=r"(v) : "r"(addr) : "memory");
    return v;
}
__device__ __forceinline__ uint32_t lds16(uint32_t addr) {
    unsigned short v;
    asm volatile("ld.shared.u16 %0, [%1];\n" : "=h"(v) : "r"(addr) : "memory");
    return v;
}
__device__ __forceinline__ uint2 lds64(uint32_t addr) {
    uint2 v;
    asm volatile("ld.shared.v2.u32 {%0,%1}, [%2];\n" : "=r"(v.x), "=r"(v.y) : "r"(addr) : "memory");
    return v;
}
__device__ __forceinline__ uint4 lds128(uint32_t addr) {
    uint4 v;
    asm volatile("ld.shared.v4.u32 {%0,%1,%2,%3}, [%4];\n" : "=r"(v.x), "=r"(v.y), "=r"(v.z), "=r"(v.w) : "r"(addr) : "memory");
    return v;
}
__device__ __forceinline__ float ldsf(uint32_t addr) { return __uint_as_float(lds32(addr)); }
__device__ __forceinline__ void sts32(uint32_t addr, uint32_t v) { asm volatile("st.shared.u32 [%0], %1;\n" ::"r"(addr), "r"(v) : "memory"); }
__device__ __forceinline__ void sts16(uint32_t addr, uint32_t v) { asm volatile("st.shared.u16 [%0], %1;\n" ::"r"(addr), "h"((unsigned short)v) : "memory"); }
__device__ __forceinline__ void stsf(uint32_t addr, float v) { sts32(addr, __float_as_uint(v)); }
__device__ __forceinline__ void sts64(uint32_t addr, uint32_t a, uint32_t b) { asm volatile("st.shared.v2.u32 [%0], {%1,%2};\n" ::"r"(addr), "r"(a), "r"(b) : "memory"); }
__device__ __forceinline__ void sts64f(uint32_t addr, float a, float b) { sts64(addr, __float_as_uint(a), __float_as_uint(b)); }
__device__ __forceinline__ void sts128(uint32_t addr, uint32_t a, uint32_t b, uint32_t c, uint32_t d) {
    asm volatile("st.shared.v4.u32 [%0], {%1,%2,%3,%4};\n" ::"r"(addr), "r"(a), "r"(b), "r"(c), "r"(d) : "memory");
}
__device__ __forceinline__ void sts128f(uint32_t addr, const float (&v)[4]) {
    sts128(addr, __float_as_uint(v[0]), __float_as_uint(v[1]), __float_as_uint(v[2]), __float_as_uint(v[3]));
}
__device__ __forceinline__ void ldsm_x4(uint32_t& r0, uint32_t& r1, uint32_t& r2, uint32_t& r3, uint32_t addr) {
    asm volatile("ldmatrix.sync.aligned.m8n8.x4.shared.b16 {%0,%1,%2,%3}, [%4];\n"
                 : "=r"(r0), "=r"(r1), "=r"(r2), "=r"(r3) : "r"(addr) : "memory");
}
__device__ __forceinline__ void ldsm_x4_t(uint32_t& r0, uint32_t& r1, uint32_t& r2, uint32_t& r3, uint32_t addr) {
    asm volatile("ldmatrix.sync.aligned.m8n8.x4.trans.shared.b16 {%0,%1,%2,%3}, [%4];\n"
                 : "=r"(r0), "=r"(r1), "=r"(r2), "=r"(r3) : "r"(addr) : "memory");
}
__device__ __forceinline__ void ldsm_x2_t(uint32_t& r0, uint32_t& r1, uint32_t addr) {
    asm volatile("ldmatrix.sync.aligned.m8n8.x2.trans.shared.b16 {%0,%1}, [%2];\n" : "=r"(r0), "=r"(r1) : "r"(addr) : "memory");
}
__device__ __forceinline__ void ldsm_x1_t(uint32_t& r0, uint32_t addr) {
    asm volatile("ldmatrix.sync.aligned.m8n8.x1.trans.shared.b16 {%0}, [%1];\n" : "=r"(r0) : "r"(addr) : "memory");
}
__device__ __forceinline__ void stsm_x4(uint32_t addr, uint32_t r0, uint32_t r1, uint32_t r2, uint32_t r3) {
    asm volatile("stmatrix.sync.aligned.m8n8.x4.shared.b16 [%0], {%1,%2,%3,%4};\n" ::"r"(addr), "r"(r0), "r"(r1), "r"(r2), "r"(r3) : "memory");
}
__device__ __forceinline__ void stsm_x4_t(uint32_t addr, uint32_t r0, uint32_t r1, uint32_t r2, uint32_t r3) {
    asm volatile("stmatrix.sync.aligned.m8n8.x4.trans.shared.b16 [%0], {%1,%2,%3,%4};\n" ::"r"(addr), "r"(r0), "r"(r1), "r"(r2), "r"(r3) : "memory");
}
__device__ __forceinline__ uint32_t movm(uint32_t a) {
    uint32_t d;
    asm volatile("movmatrix.sync.aligned.m8n8.trans.b16 %0, %1;\n" : "=r"(d) : "r"(a));
    return d;
}
__device__ __forceinline__ void mma_f16(float (&c)[4], uint32_t a0, uint32_t a1, uint32_t a2, uint32_t a3, uint32_t b0, uint32_t b1) {
    asm volatile(
        "mma.sync.aligned.m16n8k16.row.col.f32.f16.f16.f32 {%0,%1,%2,%3}, {%4,%5,%6,%7}, {%8,%9}, {%0,%1,%2,%3};\n"
        : "+f"(c[0]), "+f"(c[1]), "+f"(c[2]), "+f"(c[3])
        : "r"(a0), "r"(a1), "r"(a2), "r"(a3), "r"(b0), "r"(b1));
}
__device__ __forceinline__ void mma_bf16(float (&c)[4], uint32_t a0, uint32_t a1, uint32_t a2, uint32_t a3, uint32_t b0, uint32_t b1) {
    asm volatile(
        "mma.sync.aligned.m16n8k16.row.col.f32.bf16.bf16.f32 {%0,%1,%2,%3}, {%4,%5,%6,%7}, {%8,%9}, {%0,%1,%2,%3};\n"
        : "+f"(c[0]), "+f"(c[1]), "+f"(c[2]), "+f"(c[3])
        : "r"(a0), "r"(a1), "r"(a2), "r"(a3), "r"(b0), "r"(b1));
}
__device__ __forceinline__ void mma_bf16_k8(float (&c)[4], uint32_t a0, uint32_t a1, uint32_t b0) {
    asm volatile("mma.sync.aligned.m16n8k8.row.col.f32.bf16.bf16.f32 {%0,%1,%2,%3}, {%4,%5}, {%6}, {%0,%1,%2,%3};\n"
                 : "+f"(c[0]), "+f"(c[1]), "+f"(c[2]), "+f"(c[3]) : "r"(a0), "r"(a1), "r"(b0));
}
__device__ __forceinline__ void bar_sync(int id, int n) { asm volatile("bar.sync %0, %1;\n" ::"r"(id), "r"(n) : "memory"); }
__device__ __forceinline__ void bar_arrive(int id, int n) { asm volatile("bar.arrive %0, %1;\n" ::"r"(id), "r"(n) : "memory"); }
__device__ __forceinline__ bool bar_or(int id, int n, bool v) {
    uint32_t r;
    asm volatile("{\n.reg .pred p, q;\nsetp.ne.u32 p, %3, 0;\nbar.red.or.pred q, %1, %2, p;\nselp.u32 %0, 1, 0, q;\n}\n" : "=r"(r) : "r"(id), "r"(n), "r"((uint32_t)v) : "memory");
    return r;
}
__device__ __forceinline__ uint32_t and3(uint32_t a, uint32_t b, uint32_t c) { uint32_t r; asm("lop3.b32 %0, %1, %2, %3, 0x80;\n" : "=r"(r) : "r"(a), "r"(b), "r"(c)); return r; }
__device__ __forceinline__ uint32_t or3(uint32_t a, uint32_t b, uint32_t c) { uint32_t r; asm("lop3.b32 %0, %1, %2, %3, 0xfe;\n" : "=r"(r) : "r"(a), "r"(b), "r"(c)); return r; }
__device__ __forceinline__ uint32_t xor_or(uint32_t a, uint32_t b, uint32_t c) { uint32_t r; asm("lop3.b32 %0, %1, %2, %3, 0x7e;\n" : "=r"(r) : "r"(a), "r"(b), "r"(c)); return r; }
__device__ __forceinline__ uint32_t pin(uint32_t v) { uint32_t r; asm volatile("shfl.sync.bfly.b32 %0, %1, 0, 0x1f, 0xffffffff;\n" : "=r"(r) : "r"(v) : "memory"); return r; }
__device__ __forceinline__ uint4 ld_poll(const void* p) {
    uint4 v;
    asm volatile("ld.relaxed.gpu.global.v4.u32 {%0,%1,%2,%3}, [%4];\n" : "=r"(v.x), "=r"(v.y), "=r"(v.z), "=r"(v.w) : "l"(p) : "memory");
    return v;
}
__device__ __forceinline__ uint2 ld_poll64(const void* p) {
    uint2 v;
    asm volatile("ld.relaxed.gpu.global.v2.u32 {%0,%1}, [%2];\n" : "=r"(v.x), "=r"(v.y) : "l"(p) : "memory");
    return v;
}
__device__ __forceinline__ uint32_t ld_poll32(const void* p) {
    uint32_t v;
    asm volatile("ld.relaxed.gpu.global.u32 %0, [%1];\n" : "=r"(v) : "l"(p) : "memory");
    return v;
}
__device__ __forceinline__ uint32_t ld_acquire32(const void* p) {
    uint32_t v;
    asm volatile("ld.acquire.gpu.global.u32 %0, [%1];\n" : "=r"(v) : "l"(p) : "memory");
    return v;
}
__device__ __forceinline__ uint4 ldg128(const void* p) {
    uint4 v;
    asm volatile("ld.global.nc.v4.u32 {%0,%1,%2,%3}, [%4];\n" : "=r"(v.x), "=r"(v.y), "=r"(v.z), "=r"(v.w) : "l"(p));
    return v;
}
__device__ __forceinline__ uint2 ldg64(const void* p) {
    uint2 v;
    asm volatile("ld.global.nc.v2.u32 {%0,%1}, [%2];\n" : "=r"(v.x), "=r"(v.y) : "l"(p));
    return v;
}
__device__ __forceinline__ uint32_t ldg16(const void* p) {
    uint32_t v;
    asm volatile("ld.global.nc.u16 %0, [%1];\n" : "=r"(v) : "l"(p));
    return v;
}
__device__ __forceinline__ uint4 ldo128(const void* p) {
    uint4 v;
    asm volatile("ld.relaxed.cta.global.v4.u32 {%0,%1,%2,%3}, [%4];\n" : "=r"(v.x), "=r"(v.y), "=r"(v.z), "=r"(v.w) : "l"(p) : "memory");
    return v;
}
__device__ __forceinline__ uint2 ldo64(const void* p) {
    uint2 v;
    asm volatile("ld.relaxed.cta.global.v2.u32 {%0,%1}, [%2];\n" : "=r"(v.x), "=r"(v.y) : "l"(p) : "memory");
    return v;
}
__device__ __forceinline__ uint32_t ldo16(const void* p) {
    uint32_t v;
    asm volatile("ld.relaxed.cta.global.u16 %0, [%1];\n" : "=r"(v) : "l"(p) : "memory");
    return v;
}
__device__ __forceinline__ void stg128(void* p, uint32_t a, uint32_t b, uint32_t c, uint32_t d) {
    asm volatile("st.global.v4.u32 [%0], {%1,%2,%3,%4};\n" ::"l"(p), "r"(a), "r"(b), "r"(c), "r"(d) : "memory");
}
__device__ __forceinline__ void stg64(void* p, uint32_t a, uint32_t b) { asm volatile("st.global.v2.u32 [%0], {%1,%2};\n" ::"l"(p), "r"(a), "r"(b) : "memory"); }
__device__ __forceinline__ uint32_t min4(const uint4& v) { return min(min(v.x, v.y), min(v.z, v.w)); }
#define SPIN_LIMIT (1 << 21)
#define TRAP() __trap()
__device__ __forceinline__ void mbar_init(uint32_t bar, uint32_t cnt) { asm volatile("mbarrier.init.shared::cta.b64 [%0], %1;\n" ::"r"(bar), "r"(cnt) : "memory"); }
__device__ __forceinline__ void mbar_expect(uint32_t bar, uint32_t bytes) {
    asm volatile("mbarrier.arrive.expect_tx.shared::cta.b64 _, [%0], %1;\n" ::"r"(bar), "r"(bytes) : "memory");
}
__device__ __forceinline__ void mbar_arrive(uint32_t bar) { asm volatile("mbarrier.arrive.shared::cta.b64 _, [%0];\n" ::"r"(bar) : "memory"); }
__device__ __forceinline__ void mbar_wait_cluster(uint32_t bar) {
    asm volatile(
        "{\n.reg .pred p;\n"
        "W_%=:\n"
        "mbarrier.try_wait.parity.acquire.cluster.shared::cta.b64 p, [%0], 0;\n"
        "@!p bra W_%=;\n}\n" ::"r"(bar) : "memory");
}
__device__ __forceinline__ void mbar_wait(uint32_t bar) {
    asm volatile(
        "{\n.reg .pred p;\n"
        "W_%=:\n"
        "mbarrier.try_wait.parity.shared::cta.b64 p, [%0], 0;\n"
        "@!p bra W_%=;\n}\n" ::"r"(bar) : "memory");
}
__device__ __forceinline__ void mbar_wait1(uint32_t bar) {
    asm volatile(
        "{\n.reg .pred p;\n"
        "W_%=:\n"
        "mbarrier.try_wait.parity.shared::cta.b64 p, [%0], 1;\n"
        "@!p bra W_%=;\n}\n" ::"r"(bar) : "memory");
}
__device__ __forceinline__ bool mbar_test(uint32_t bar) {
    uint32_t r;
    asm volatile("{\n.reg .pred p;\nmbarrier.test_wait.parity.shared::cta.b64 p, [%1], 0;\nselp.u32 %0, 1, 0, p;\n}\n" : "=r"(r) : "r"(bar) : "memory");
    return __any_sync(0xffffffffu, r);
}
__device__ __forceinline__ void bulk_g2s(uint32_t dst, const void* src, uint32_t bytes, uint32_t bar) {
    asm volatile("cp.async.bulk.shared::cluster.global.mbarrier::complete_tx::bytes [%0], [%1], %2, [%3];\n" ::"r"(dst), "l"(src), "r"(bytes), "r"(bar) : "memory");
}
__device__ __forceinline__ void bulk_s2g(void* dst, uint32_t src, uint32_t bytes) {
    asm volatile("cp.async.bulk.global.shared::cta.bulk_group [%0], [%1], %2;\ncp.async.bulk.commit_group;\n" ::"l"(dst), "r"(src), "r"(bytes) : "memory");
}
__device__ __forceinline__ void bulk_s2g_nc(void* dst, uint32_t src, uint32_t bytes) {
    asm volatile("cp.async.bulk.global.shared::cta.bulk_group [%0], [%1], %2;\n" ::"l"(dst), "r"(src), "r"(bytes) : "memory");
}
__device__ __forceinline__ void tma_2d(uint32_t dst, const CUtensorMap* tm, int c0, int c1, uint32_t bar) {
    asm volatile("cp.async.bulk.tensor.2d.shared::cluster.global.mbarrier::complete_tx::bytes [%0], [%1, {%3, %4}], [%2];\n"
                 ::"r"(dst), "l"(tm), "r"(bar), "r"(c0), "r"(c1) : "memory");
}
__device__ __forceinline__ void tma_4d(uint32_t dst, const CUtensorMap* tm, int c0, int c3, uint32_t bar) {
    asm volatile("cp.async.bulk.tensor.4d.shared::cluster.global.mbarrier::complete_tx::bytes [%0], [%1, {%3, %4, %4, %5}], [%2];\n"
                 ::"r"(dst), "l"(tm), "r"(bar), "r"(c0), "r"(0), "r"(c3) : "memory");
}
__device__ __forceinline__ void tma_4d_mc(uint32_t dst, const CUtensorMap* tm, int c0, int c3, uint32_t bar) {
    asm volatile("cp.async.bulk.tensor.4d.shared::cluster.global.mbarrier::complete_tx::bytes.multicast::cluster [%0], [%1, {%3, %4, %4, %5}], [%2], %6;\n"
                 ::"r"(dst), "l"(tm), "r"(bar), "r"(c0), "r"(0), "r"(c3), "h"((unsigned short)3) : "memory");
}
__device__ __forceinline__ void l2_prefetch(const void* src, uint32_t bytes) {
    asm volatile("cp.async.bulk.prefetch.L2.global [%0], %1;\n" ::"l"(src), "r"(bytes) : "memory");
}
__device__ __forceinline__ bool elect_one() {
    uint32_t r;
    asm volatile("{\n.reg .pred p;\nelect.sync _|p, 0xffffffff;\nselp.u32 %0, 1, 0, p;\n}\n" : "=r"(r));
    return r;
}
__device__ __forceinline__ void delay(uint32_t clks) {
    uint32_t t0, t1;
    asm volatile("mov.u32 %0, %%clock;" : "=r"(t0) :: "memory");
    do { asm volatile("mov.u32 %0, %%clock;" : "=r"(t1) :: "memory"); } while (t1 - t0 < clks);
}
__device__ __forceinline__ void fence_async() { asm volatile("fence.proxy.async.shared::cta;\n" ::: "memory"); }

__device__ __forceinline__ float2 cmul(float2 a, float2 b) {
    return make_float2(fmaf(a.x, b.x, -a.y * b.y), fmaf(a.x, b.y, a.y * b.x));
}
__device__ __forceinline__ float2 csq(float2 a) {
    float p = a.x * a.y;
    return make_float2(fmaf(a.x, a.x, -a.y * a.y), p + p);
}
__device__ __forceinline__ float ex2_approx(float x) { float r; asm("ex2.approx.ftz.f32 %0, %1;\n" : "=f"(r) : "f"(x)); return r; }
__device__ __forceinline__ float exp_bf(float x) { return rbf(ex2_approx(__fmul_ru(x, 1.4426950408889634f))); }
__device__ __forceinline__ float2 cexp_e(float lr2, float li, float e) {
    const float m = ex2_approx(lr2 * e);
    return make_float2(m * __cosf(li * e), m * __sinf(li * e));
}
__device__ __forceinline__ float rcp_approx(float x) { float r; asm("rcp.approx.ftz.f32 %0, %1;\n" : "=f"(r) : "f"(x)); return r; }
__device__ __forceinline__ float sigmoid_f(float x) { return rcp_approx(1.0f + ex2_approx(x * -1.4426950408889634f)); }
__device__ __forceinline__ float sqrt_approx(float x) { float r; asm("sqrt.approx.ftz.f32 %0, %1;\n" : "=f"(r) : "f"(x)); return r; }

__device__ __forceinline__ void wg_fence() { asm volatile("wgmma.fence.sync.aligned;\n" ::: "memory"); }
__device__ __forceinline__ void wg_commit() { asm volatile("wgmma.commit_group.sync.aligned;\n" ::: "memory"); }
__device__ __forceinline__ void wg_wait0() { asm volatile("wgmma.wait_group.sync.aligned 0;\n" ::: "memory"); }
template <int T> __device__ __forceinline__ void wg_mma(float (&acc)[16][4], const uint32_t* a, uint64_t desc);
template <int T> __device__ __forceinline__ void wg_first(float (&acc)[16][4], const uint32_t* a, uint64_t desc);
template <> __device__ __forceinline__ void wg_mma<0>(float (&acc)[16][4], const uint32_t* a, uint64_t desc) {
    asm volatile("wgmma.mma_async.sync.aligned.m64n128k16.f32.f16.f16 {%0,%1,%2,%3,%4,%5,%6,%7,%8,%9,%10,%11,%12,%13,%14,%15,%16,%17,%18,%19,%20,%21,%22,%23,%24,%25,%26,%27,%28,%29,%30,%31,%32,%33,%34,%35,%36,%37,%38,%39,%40,%41,%42,%43,%44,%45,%46,%47,%48,%49,%50,%51,%52,%53,%54,%55,%56,%57,%58,%59,%60,%61,%62,%63}, {%64,%65,%66,%67}, %68, 1, 1, 1, 0;\n"
                 : "+f"(acc[0][0]), "+f"(acc[0][1]), "+f"(acc[0][2]), "+f"(acc[0][3]), "+f"(acc[1][0]), "+f"(acc[1][1]), "+f"(acc[1][2]), "+f"(acc[1][3]), "+f"(acc[2][0]), "+f"(acc[2][1]), "+f"(acc[2][2]), "+f"(acc[2][3]), "+f"(acc[3][0]), "+f"(acc[3][1]), "+f"(acc[3][2]), "+f"(acc[3][3]), "+f"(acc[4][0]), "+f"(acc[4][1]), "+f"(acc[4][2]), "+f"(acc[4][3]), "+f"(acc[5][0]), "+f"(acc[5][1]), "+f"(acc[5][2]), "+f"(acc[5][3]), "+f"(acc[6][0]), "+f"(acc[6][1]), "+f"(acc[6][2]), "+f"(acc[6][3]), "+f"(acc[7][0]), "+f"(acc[7][1]), "+f"(acc[7][2]), "+f"(acc[7][3]), "+f"(acc[8][0]), "+f"(acc[8][1]), "+f"(acc[8][2]), "+f"(acc[8][3]), "+f"(acc[9][0]), "+f"(acc[9][1]), "+f"(acc[9][2]), "+f"(acc[9][3]), "+f"(acc[10][0]), "+f"(acc[10][1]), "+f"(acc[10][2]), "+f"(acc[10][3]), "+f"(acc[11][0]), "+f"(acc[11][1]), "+f"(acc[11][2]), "+f"(acc[11][3]), "+f"(acc[12][0]), "+f"(acc[12][1]), "+f"(acc[12][2]), "+f"(acc[12][3]), "+f"(acc[13][0]), "+f"(acc[13][1]), "+f"(acc[13][2]), "+f"(acc[13][3]), "+f"(acc[14][0]), "+f"(acc[14][1]), "+f"(acc[14][2]), "+f"(acc[14][3]), "+f"(acc[15][0]), "+f"(acc[15][1]), "+f"(acc[15][2]), "+f"(acc[15][3])
                 : "r"(a[0]), "r"(a[1]), "r"(a[2]), "r"(a[3]), "l"(desc));
}
template <> __device__ __forceinline__ void wg_mma<2>(float (&acc)[16][4], const uint32_t* a, uint64_t desc) {
    asm volatile("wgmma.mma_async.sync.aligned.m64n112k16.f32.f16.f16 {%0,%1,%2,%3,%4,%5,%6,%7,%8,%9,%10,%11,%12,%13,%14,%15,%16,%17,%18,%19,%20,%21,%22,%23,%24,%25,%26,%27,%28,%29,%30,%31,%32,%33,%34,%35,%36,%37,%38,%39,%40,%41,%42,%43,%44,%45,%46,%47,%48,%49,%50,%51,%52,%53,%54,%55}, {%56,%57,%58,%59}, %60, 1, 1, 1, 0;\n"
                 : "+f"(acc[2][0]), "+f"(acc[2][1]), "+f"(acc[2][2]), "+f"(acc[2][3]), "+f"(acc[3][0]), "+f"(acc[3][1]), "+f"(acc[3][2]), "+f"(acc[3][3]), "+f"(acc[4][0]), "+f"(acc[4][1]), "+f"(acc[4][2]), "+f"(acc[4][3]), "+f"(acc[5][0]), "+f"(acc[5][1]), "+f"(acc[5][2]), "+f"(acc[5][3]), "+f"(acc[6][0]), "+f"(acc[6][1]), "+f"(acc[6][2]), "+f"(acc[6][3]), "+f"(acc[7][0]), "+f"(acc[7][1]), "+f"(acc[7][2]), "+f"(acc[7][3]), "+f"(acc[8][0]), "+f"(acc[8][1]), "+f"(acc[8][2]), "+f"(acc[8][3]), "+f"(acc[9][0]), "+f"(acc[9][1]), "+f"(acc[9][2]), "+f"(acc[9][3]), "+f"(acc[10][0]), "+f"(acc[10][1]), "+f"(acc[10][2]), "+f"(acc[10][3]), "+f"(acc[11][0]), "+f"(acc[11][1]), "+f"(acc[11][2]), "+f"(acc[11][3]), "+f"(acc[12][0]), "+f"(acc[12][1]), "+f"(acc[12][2]), "+f"(acc[12][3]), "+f"(acc[13][0]), "+f"(acc[13][1]), "+f"(acc[13][2]), "+f"(acc[13][3]), "+f"(acc[14][0]), "+f"(acc[14][1]), "+f"(acc[14][2]), "+f"(acc[14][3]), "+f"(acc[15][0]), "+f"(acc[15][1]), "+f"(acc[15][2]), "+f"(acc[15][3])
                 : "r"(a[0]), "r"(a[1]), "r"(a[2]), "r"(a[3]), "l"(desc));
}
template <> __device__ __forceinline__ void wg_mma<4>(float (&acc)[16][4], const uint32_t* a, uint64_t desc) {
    asm volatile("wgmma.mma_async.sync.aligned.m64n96k16.f32.f16.f16 {%0,%1,%2,%3,%4,%5,%6,%7,%8,%9,%10,%11,%12,%13,%14,%15,%16,%17,%18,%19,%20,%21,%22,%23,%24,%25,%26,%27,%28,%29,%30,%31,%32,%33,%34,%35,%36,%37,%38,%39,%40,%41,%42,%43,%44,%45,%46,%47}, {%48,%49,%50,%51}, %52, 1, 1, 1, 0;\n"
                 : "+f"(acc[4][0]), "+f"(acc[4][1]), "+f"(acc[4][2]), "+f"(acc[4][3]), "+f"(acc[5][0]), "+f"(acc[5][1]), "+f"(acc[5][2]), "+f"(acc[5][3]), "+f"(acc[6][0]), "+f"(acc[6][1]), "+f"(acc[6][2]), "+f"(acc[6][3]), "+f"(acc[7][0]), "+f"(acc[7][1]), "+f"(acc[7][2]), "+f"(acc[7][3]), "+f"(acc[8][0]), "+f"(acc[8][1]), "+f"(acc[8][2]), "+f"(acc[8][3]), "+f"(acc[9][0]), "+f"(acc[9][1]), "+f"(acc[9][2]), "+f"(acc[9][3]), "+f"(acc[10][0]), "+f"(acc[10][1]), "+f"(acc[10][2]), "+f"(acc[10][3]), "+f"(acc[11][0]), "+f"(acc[11][1]), "+f"(acc[11][2]), "+f"(acc[11][3]), "+f"(acc[12][0]), "+f"(acc[12][1]), "+f"(acc[12][2]), "+f"(acc[12][3]), "+f"(acc[13][0]), "+f"(acc[13][1]), "+f"(acc[13][2]), "+f"(acc[13][3]), "+f"(acc[14][0]), "+f"(acc[14][1]), "+f"(acc[14][2]), "+f"(acc[14][3]), "+f"(acc[15][0]), "+f"(acc[15][1]), "+f"(acc[15][2]), "+f"(acc[15][3])
                 : "r"(a[0]), "r"(a[1]), "r"(a[2]), "r"(a[3]), "l"(desc));
}
template <> __device__ __forceinline__ void wg_mma<6>(float (&acc)[16][4], const uint32_t* a, uint64_t desc) {
    asm volatile("wgmma.mma_async.sync.aligned.m64n80k16.f32.f16.f16 {%0,%1,%2,%3,%4,%5,%6,%7,%8,%9,%10,%11,%12,%13,%14,%15,%16,%17,%18,%19,%20,%21,%22,%23,%24,%25,%26,%27,%28,%29,%30,%31,%32,%33,%34,%35,%36,%37,%38,%39}, {%40,%41,%42,%43}, %44, 1, 1, 1, 0;\n"
                 : "+f"(acc[6][0]), "+f"(acc[6][1]), "+f"(acc[6][2]), "+f"(acc[6][3]), "+f"(acc[7][0]), "+f"(acc[7][1]), "+f"(acc[7][2]), "+f"(acc[7][3]), "+f"(acc[8][0]), "+f"(acc[8][1]), "+f"(acc[8][2]), "+f"(acc[8][3]), "+f"(acc[9][0]), "+f"(acc[9][1]), "+f"(acc[9][2]), "+f"(acc[9][3]), "+f"(acc[10][0]), "+f"(acc[10][1]), "+f"(acc[10][2]), "+f"(acc[10][3]), "+f"(acc[11][0]), "+f"(acc[11][1]), "+f"(acc[11][2]), "+f"(acc[11][3]), "+f"(acc[12][0]), "+f"(acc[12][1]), "+f"(acc[12][2]), "+f"(acc[12][3]), "+f"(acc[13][0]), "+f"(acc[13][1]), "+f"(acc[13][2]), "+f"(acc[13][3]), "+f"(acc[14][0]), "+f"(acc[14][1]), "+f"(acc[14][2]), "+f"(acc[14][3]), "+f"(acc[15][0]), "+f"(acc[15][1]), "+f"(acc[15][2]), "+f"(acc[15][3])
                 : "r"(a[0]), "r"(a[1]), "r"(a[2]), "r"(a[3]), "l"(desc));
}
template <> __device__ __forceinline__ void wg_mma<8>(float (&acc)[16][4], const uint32_t* a, uint64_t desc) {
    asm volatile("wgmma.mma_async.sync.aligned.m64n64k16.f32.f16.f16 {%0,%1,%2,%3,%4,%5,%6,%7,%8,%9,%10,%11,%12,%13,%14,%15,%16,%17,%18,%19,%20,%21,%22,%23,%24,%25,%26,%27,%28,%29,%30,%31}, {%32,%33,%34,%35}, %36, 1, 1, 1, 0;\n"
                 : "+f"(acc[8][0]), "+f"(acc[8][1]), "+f"(acc[8][2]), "+f"(acc[8][3]), "+f"(acc[9][0]), "+f"(acc[9][1]), "+f"(acc[9][2]), "+f"(acc[9][3]), "+f"(acc[10][0]), "+f"(acc[10][1]), "+f"(acc[10][2]), "+f"(acc[10][3]), "+f"(acc[11][0]), "+f"(acc[11][1]), "+f"(acc[11][2]), "+f"(acc[11][3]), "+f"(acc[12][0]), "+f"(acc[12][1]), "+f"(acc[12][2]), "+f"(acc[12][3]), "+f"(acc[13][0]), "+f"(acc[13][1]), "+f"(acc[13][2]), "+f"(acc[13][3]), "+f"(acc[14][0]), "+f"(acc[14][1]), "+f"(acc[14][2]), "+f"(acc[14][3]), "+f"(acc[15][0]), "+f"(acc[15][1]), "+f"(acc[15][2]), "+f"(acc[15][3])
                 : "r"(a[0]), "r"(a[1]), "r"(a[2]), "r"(a[3]), "l"(desc));
}
template <> __device__ __forceinline__ void wg_mma<10>(float (&acc)[16][4], const uint32_t* a, uint64_t desc) {
    asm volatile("wgmma.mma_async.sync.aligned.m64n48k16.f32.f16.f16 {%0,%1,%2,%3,%4,%5,%6,%7,%8,%9,%10,%11,%12,%13,%14,%15,%16,%17,%18,%19,%20,%21,%22,%23}, {%24,%25,%26,%27}, %28, 1, 1, 1, 0;\n"
                 : "+f"(acc[10][0]), "+f"(acc[10][1]), "+f"(acc[10][2]), "+f"(acc[10][3]), "+f"(acc[11][0]), "+f"(acc[11][1]), "+f"(acc[11][2]), "+f"(acc[11][3]), "+f"(acc[12][0]), "+f"(acc[12][1]), "+f"(acc[12][2]), "+f"(acc[12][3]), "+f"(acc[13][0]), "+f"(acc[13][1]), "+f"(acc[13][2]), "+f"(acc[13][3]), "+f"(acc[14][0]), "+f"(acc[14][1]), "+f"(acc[14][2]), "+f"(acc[14][3]), "+f"(acc[15][0]), "+f"(acc[15][1]), "+f"(acc[15][2]), "+f"(acc[15][3])
                 : "r"(a[0]), "r"(a[1]), "r"(a[2]), "r"(a[3]), "l"(desc));
}
template <> __device__ __forceinline__ void wg_mma<12>(float (&acc)[16][4], const uint32_t* a, uint64_t desc) {
    asm volatile("wgmma.mma_async.sync.aligned.m64n32k16.f32.f16.f16 {%0,%1,%2,%3,%4,%5,%6,%7,%8,%9,%10,%11,%12,%13,%14,%15}, {%16,%17,%18,%19}, %20, 1, 1, 1, 0;\n"
                 : "+f"(acc[12][0]), "+f"(acc[12][1]), "+f"(acc[12][2]), "+f"(acc[12][3]), "+f"(acc[13][0]), "+f"(acc[13][1]), "+f"(acc[13][2]), "+f"(acc[13][3]), "+f"(acc[14][0]), "+f"(acc[14][1]), "+f"(acc[14][2]), "+f"(acc[14][3]), "+f"(acc[15][0]), "+f"(acc[15][1]), "+f"(acc[15][2]), "+f"(acc[15][3])
                 : "r"(a[0]), "r"(a[1]), "r"(a[2]), "r"(a[3]), "l"(desc));
}
template <> __device__ __forceinline__ void wg_mma<14>(float (&acc)[16][4], const uint32_t* a, uint64_t desc) {
    asm volatile("wgmma.mma_async.sync.aligned.m64n16k16.f32.f16.f16 {%0,%1,%2,%3,%4,%5,%6,%7}, {%8,%9,%10,%11}, %12, 1, 1, 1, 0;\n"
                 : "+f"(acc[14][0]), "+f"(acc[14][1]), "+f"(acc[14][2]), "+f"(acc[14][3]), "+f"(acc[15][0]), "+f"(acc[15][1]), "+f"(acc[15][2]), "+f"(acc[15][3])
                 : "r"(a[0]), "r"(a[1]), "r"(a[2]), "r"(a[3]), "l"(desc));
}
template <> __device__ __forceinline__ void wg_first<0>(float (&acc)[16][4], const uint32_t* a, uint64_t desc) {
    asm volatile("wgmma.mma_async.sync.aligned.m64n128k16.f32.f16.f16 {%0,%1,%2,%3,%4,%5,%6,%7,%8,%9,%10,%11,%12,%13,%14,%15,%16,%17,%18,%19,%20,%21,%22,%23,%24,%25,%26,%27,%28,%29,%30,%31,%32,%33,%34,%35,%36,%37,%38,%39,%40,%41,%42,%43,%44,%45,%46,%47,%48,%49,%50,%51,%52,%53,%54,%55,%56,%57,%58,%59,%60,%61,%62,%63}, {%64,%65,%66,%67}, %68, 0, 1, 1, 0;\n"
                 : "=f"(acc[0][0]), "=f"(acc[0][1]), "=f"(acc[0][2]), "=f"(acc[0][3]), "=f"(acc[1][0]), "=f"(acc[1][1]), "=f"(acc[1][2]), "=f"(acc[1][3]), "=f"(acc[2][0]), "=f"(acc[2][1]), "=f"(acc[2][2]), "=f"(acc[2][3]), "=f"(acc[3][0]), "=f"(acc[3][1]), "=f"(acc[3][2]), "=f"(acc[3][3]), "=f"(acc[4][0]), "=f"(acc[4][1]), "=f"(acc[4][2]), "=f"(acc[4][3]), "=f"(acc[5][0]), "=f"(acc[5][1]), "=f"(acc[5][2]), "=f"(acc[5][3]), "=f"(acc[6][0]), "=f"(acc[6][1]), "=f"(acc[6][2]), "=f"(acc[6][3]), "=f"(acc[7][0]), "=f"(acc[7][1]), "=f"(acc[7][2]), "=f"(acc[7][3]), "=f"(acc[8][0]), "=f"(acc[8][1]), "=f"(acc[8][2]), "=f"(acc[8][3]), "=f"(acc[9][0]), "=f"(acc[9][1]), "=f"(acc[9][2]), "=f"(acc[9][3]), "=f"(acc[10][0]), "=f"(acc[10][1]), "=f"(acc[10][2]), "=f"(acc[10][3]), "=f"(acc[11][0]), "=f"(acc[11][1]), "=f"(acc[11][2]), "=f"(acc[11][3]), "=f"(acc[12][0]), "=f"(acc[12][1]), "=f"(acc[12][2]), "=f"(acc[12][3]), "=f"(acc[13][0]), "=f"(acc[13][1]), "=f"(acc[13][2]), "=f"(acc[13][3]), "=f"(acc[14][0]), "=f"(acc[14][1]), "=f"(acc[14][2]), "=f"(acc[14][3]), "=f"(acc[15][0]), "=f"(acc[15][1]), "=f"(acc[15][2]), "=f"(acc[15][3])
                 : "r"(a[0]), "r"(a[1]), "r"(a[2]), "r"(a[3]), "l"(desc));
}
template <> __device__ __forceinline__ void wg_first<4>(float (&acc)[16][4], const uint32_t* a, uint64_t desc) {
    asm volatile("wgmma.mma_async.sync.aligned.m64n96k16.f32.f16.f16 {%0,%1,%2,%3,%4,%5,%6,%7,%8,%9,%10,%11,%12,%13,%14,%15,%16,%17,%18,%19,%20,%21,%22,%23,%24,%25,%26,%27,%28,%29,%30,%31,%32,%33,%34,%35,%36,%37,%38,%39,%40,%41,%42,%43,%44,%45,%46,%47}, {%48,%49,%50,%51}, %52, 0, 1, 1, 0;\n"
                 : "=f"(acc[4][0]), "=f"(acc[4][1]), "=f"(acc[4][2]), "=f"(acc[4][3]), "=f"(acc[5][0]), "=f"(acc[5][1]), "=f"(acc[5][2]), "=f"(acc[5][3]), "=f"(acc[6][0]), "=f"(acc[6][1]), "=f"(acc[6][2]), "=f"(acc[6][3]), "=f"(acc[7][0]), "=f"(acc[7][1]), "=f"(acc[7][2]), "=f"(acc[7][3]), "=f"(acc[8][0]), "=f"(acc[8][1]), "=f"(acc[8][2]), "=f"(acc[8][3]), "=f"(acc[9][0]), "=f"(acc[9][1]), "=f"(acc[9][2]), "=f"(acc[9][3]), "=f"(acc[10][0]), "=f"(acc[10][1]), "=f"(acc[10][2]), "=f"(acc[10][3]), "=f"(acc[11][0]), "=f"(acc[11][1]), "=f"(acc[11][2]), "=f"(acc[11][3]), "=f"(acc[12][0]), "=f"(acc[12][1]), "=f"(acc[12][2]), "=f"(acc[12][3]), "=f"(acc[13][0]), "=f"(acc[13][1]), "=f"(acc[13][2]), "=f"(acc[13][3]), "=f"(acc[14][0]), "=f"(acc[14][1]), "=f"(acc[14][2]), "=f"(acc[14][3]), "=f"(acc[15][0]), "=f"(acc[15][1]), "=f"(acc[15][2]), "=f"(acc[15][3])
                 : "r"(a[0]), "r"(a[1]), "r"(a[2]), "r"(a[3]), "l"(desc));
}

#define SDLY 900
#define UDLY 1400
#define KDLY 950
#define FDLY 1000
#define FDLY2 400
#define DDLY 300
#define WDLY 500
#define HW 15
#define FIX(v) do { if ((v) == 1u) TRAP(); } while (0)
#define STAMPW(i) STAMPY(i)
#define STAMP2(i) STAMP(i)
#undef STAMPX
#define STAMPX(i)
struct Params {
    const bf16 *x, *lar, *aim, *cre, *cim, *ldt, *dsk;
    Scratch* s;
    const bf16* wr;
    bf16* out;
};

#define TOK(g) (2 * (g) - ((g) & 1))
#define ROWTOK(r) (TOK((r) & 7) + (((r) >> 2) & 2))
__device__ __forceinline__ void ln_partial(const uint32_t (&H)[2][4], float (&d)[2][4]) {
#pragma unroll
    for (int hf = 0; hf < 2; hf++) {
        d[hf][0] = d[hf][1] = d[hf][2] = d[hf][3] = 0.f;
        mma_bf16(d[hf], H[hf][0], 0x3f803f80u, H[hf][1], 0x3f803f80u, H[hf][0], H[hf][1]);
    }
#pragma unroll
    for (int hf = 0; hf < 2; hf++) mma_bf16(d[hf], H[hf][2], 0x3f803f80u, H[hf][3], 0x3f803f80u, H[hf][2], H[hf][3]);
}
__device__ __forceinline__ float sum18(uint32_t a) {
    const uint4 p = lds128(a), q = lds128(a + 16), r = lds128(a + 32), s = lds128(a + 48);
    const uint2 u = lds64(a + 64);
#define F(x) __uint_as_float(x)
    return (((F(p.x) + F(p.y)) + (F(p.z) + F(p.w))) + ((F(q.x) + F(q.y)) + (F(q.z) + F(q.w)))) +
           (((F(r.x) + F(r.y)) + (F(r.z) + F(r.w))) + ((F(s.x) + F(s.y)) + (F(s.z) + F(s.w))) + (F(u.x) + F(u.y)));
#undef F
}
__device__ __forceinline__ void ln_stats(float sm, float sq, float& mb, float& sd) {
    const float m0 = sm * (1.0f / 576.0f);
    const float mean = fmaf(fmaf(-m0, 576.0f, sm), 1.0f / 576.0f, m0);
    const float var = fmaxf(fmaf(-mean, mean, sq * (1.0f / 576.0f)), 0.f);
    mb = rbf(mean);
    sd = rbf(sqrt_approx(rbf(rbf(var) + 1e-5f)));
}
__device__ __forceinline__ void ln_finish(float v, int lane, float& mb, float& rc) {
    const float o = __shfl_xor_sync(0xffffffffu, v, 16);
    float sd;
    ln_stats(lane < 16 ? v : o, lane < 16 ? o : v, mb, sd);
    rc = rcp_approx(sd);
}
__device__ __forceinline__ uint32_t ln_apply(uint32_t w, uint32_t m2, uint32_t rh, uint32_t rl) {
    const uint32_t d = hsub2_bf(w, m2);
    return hfma2_bf(d, rh, hmul2_bf(d, rl));
}
__device__ __forceinline__ void stat_store(uint32_t a, float mb, float rc, uint32_t extra) {
    const float rh = rbf(rc);
    sts64(a, (__float_as_uint(mb) >> 16) | (extra << 16), pack_bf16(rh, rc - rh));
}
#define STAT_M(s) __byte_perm((s).x, (s).x, 0x1010)
#define STAT_H(s) __byte_perm((s).y, (s).y, 0x1010)
#define STAT_L(s) __byte_perm((s).y, (s).y, 0x3232)

__device__ __forceinline__ void hcmul(uint32_t re, uint32_t im, uint32_t zx, uint32_t zy, uint32_t& ore, uint32_t& oim) {
    ore = hfms2(im, zy, hmul2(re, zx));
    oim = hfma2(re, zy, hmul2(im, zx));
}

struct KGen {
    uint32_t A[2][4][4];
    float2 z1, z8, z64, z128, T[9];
};
__device__ __forceinline__ void kgen_setup(KGen& k, float lar, float aim, float dt) {
    const float lr2 = -(exp_bf(lar) * dt) * 1.4426950408889634f, li = aim * dt;
    k.z1 = cexp_e(lr2, li, 1.0f);
    k.z8 = cexp_e(lr2, li, 8.0f);
    k.z64 = cexp_e(lr2, li, 64.0f);
}
__device__ __forceinline__ void kgen_rows(KGen& k, uint32_t tb, int lane) {
    const float2 z8 = k.z8, z64 = k.z64;
    const uint32_t row = tb + lane * 16;
    k.z128 = csq(z64);
    const float2 z16 = csq(z8), z24 = cmul(z16, z8), z32 = csq(z16), z40 = cmul(z32, z8), z48 = csq(z24), z56 = cmul(z32, z24);
    uint32_t re[4], im[4], a[4], b[4];
    re[0] = pack_f16(1.0f, z8.x); im[0] = pack_f16(0.0f, z8.y);
    re[1] = pack_f16(z16.x, z24.x); im[1] = pack_f16(z16.y, z24.y);
    re[2] = pack_f16(z32.x, z40.x); im[2] = pack_f16(z32.y, z40.y);
    re[3] = pack_f16(z48.x, z56.x); im[3] = pack_f16(z48.y, z56.y);
    sts128(row, re[0], re[1], re[2], re[3]);
    sts128(row + 1024, im[0], im[1], im[2], im[3]);
    const uint32_t zx = pack_f16(z64.x, z64.x), zy = pack_f16(z64.y, z64.y), zw = pack_f16(k.z128.x, k.z128.y);
#pragma unroll
    for (int j = 0; j < 4; j++) hcmul(re[j], im[j], zx, zy, a[j], b[j]);
    sts128(row + 512, a[0], a[1], a[2], a[3]);
    sts128(row + 1536, b[0], b[1], b[2], b[3]);
    const int mi = lane >> 3;
    const uint32_t zd = tb + 2048 + mi * 16;
    sts16(tb + 2048 + lane * 2, zw); sts16(tb + 2112 + lane * 2, zw >> 16);
    __syncwarp();
    const uint32_t ad = tb + (lane & 7) * 16 + mi * 512;
    ldsm_x4(a[0], a[1], a[2], a[3], zd);
    ldsm_x4(b[0], b[1], b[2], b[3], zd + 64);
#pragma unroll
    for (int ks = 0; ks < 4; ks++) {
        ldsm_x4_t(k.A[0][ks][0], k.A[0][ks][1], k.A[0][ks][2], k.A[0][ks][3], ad + ks * 128);
        hcmul(k.A[0][ks][0], k.A[0][ks][2], a[ks], b[ks], k.A[1][ks][0], k.A[1][ks][2]);
        hcmul(k.A[0][ks][1], k.A[0][ks][3], a[ks], b[ks], k.A[1][ks][1], k.A[1][ks][3]);
    }
}
__device__ __forceinline__ void kgen_chain(KGen& k, uint32_t cr, uint32_t ci, float cs) {
    k.T[0] = make_float2(bf_lo(cr) * cs, -bf_lo(ci) * cs);
    const float2 y1 = make_float2(k.z1.x, -k.z1.y);
#pragma unroll
    for (int c = 1; c < 8; c++) k.T[c] = cmul(k.T[c - 1], y1);
    k.T[8] = cmul(k.T[0], make_float2(k.z8.x, -k.z8.y));
}
__device__ __forceinline__ void kgen_cols(KGen& k, uint32_t tb, uint32_t t5, int lane) {
    const uint32_t row = tb + lane * 16;
    const float2 (&T)[9] = k.T;
    const float2 y128 = make_float2(k.z128.x, -k.z128.y);
    const float2 y256 = csq(y128), y512 = csq(y256), y768 = cmul(y512, y256), y1024 = csq(y512);
    const float2 c1032 = cmul(T[8], y1024);
    __syncwarp();
    sts128(row, pack_f16(T[0].x, T[1].x), pack_f16(T[2].x, T[3].x), pack_f16(T[4].x, T[5].x), pack_f16(T[6].x, T[7].x));
    sts128(row + 512, pack_f16(T[0].y, T[1].y), pack_f16(T[2].y, T[3].y), pack_f16(T[4].y, T[5].y), pack_f16(T[6].y, T[7].y));
    uint32_t a[4], b[4];
    {
        const uint32_t zx = pack_f16(y256.x, y256.x), zy = pack_f16(y256.y, y256.y);
        hcmul(pack_f16(T[0].x, T[2].x), pack_f16(T[0].y, T[2].y), zx, zy, a[0], b[0]);
        hcmul(pack_f16(T[4].x, T[6].x), pack_f16(T[4].y, T[6].y), zx, zy, a[1], b[1]);
        const uint32_t r04 = pack_f16(T[0].x, T[4].x), i04 = pack_f16(T[0].y, T[4].y);
        hcmul(r04, i04, pack_f16(y512.x, y512.x), pack_f16(y512.y, y512.y), a[2], b[2]);
        hcmul(r04, i04, pack_f16(y768.x, y768.x), pack_f16(y768.y, y768.y), a[3], b[3]);
    }
    sts128(row + 1024, a[0], a[1], a[2], a[3]);
    sts128(row + 1536, b[0], b[1], b[2], b[3]);
    {
        const uint32_t r0 = pack_f16(1.0f, y256.x), i0 = pack_f16(0.0f, y256.y), r1 = pack_f16(y512.x, y768.x), i1 = pack_f16(y512.y, y768.y);
        const uint32_t zx = pack_f16(T[8].x, T[8].x), zy = pack_f16(T[8].y, T[8].y), wx = pack_f16(c1032.x, c1032.x), wy = pack_f16(c1032.y, c1032.y);
        hcmul(r0, i0, zx, zy, a[0], b[0]); hcmul(r1, i1, zx, zy, a[1], b[1]);
        hcmul(r0, i0, wx, wy, a[2], b[2]); hcmul(r1, i1, wx, wy, a[3], b[3]);
    }
    sts128(row + 2048, a[0], a[1], a[2], a[3]);
    sts128(t5 + lane * 16, b[0], b[1], b[2], b[3]);
}
__device__ __forceinline__ void kgen_mma(const KGen& k, uint32_t tb, uint32_t t5, int lane) {
    __syncwarp();
    float acc[2][3][4];
#pragma unroll
    for (int i = 0; i < 6; i++)
#pragma unroll
        for (int j = 0; j < 4; j++) acc[i / 3][i % 3][j] = 0.f;
    const int mi = lane >> 3;
    const uint32_t ro = ((lane & 7) + 8 * (mi >> 1)) * 16, bd = tb + ro + (mi & 1) * 512, b2 = ro + ((mi & 1) ? t5 : tb + 2048);
#pragma unroll
    for (int kp = 0; kp < 2; kp++)
#pragma unroll
        for (int j = 0; j < 3; j++) {
            uint32_t b[4];
            ldsm_x4_t(b[0], b[1], b[2], b[3], (j < 2 ? bd + j * 1024 : b2) + kp * 256);
#pragma unroll
            for (int h = 0; h < 2; h++)
#pragma unroll
                for (int m = 0; m < 2; m++) {
                    const uint32_t (&A)[4] = k.A[m][2 * kp + h];
                    mma_f16(acc[m][j], A[0], A[1], A[2], A[3], b[2 * h], b[2 * h + 1]);
                }
        }
    __syncwarp();
#define PK(j) pack_f16(acc[0][j][0], acc[0][j][1]), pack_f16(acc[0][j][2], acc[0][j][3]), pack_f16(acc[1][j][0], acc[1][j][1]), pack_f16(acc[1][j][2], acc[1][j][3])
    stsm_x4(tb + lane * 16, PK(0));
    stsm_x4(tb + 512 + lane * 16, PK(1));
    stsm_x4_t(tb + 1024 + (lane & 7) * 80 + mi * 16, PK(2));
#undef PK
}
__device__ __forceinline__ uint32_t table_buf(uint32_t sb, int warp) { return sb + SM_PL + warp * TBW; }

__device__ __forceinline__ uint4 lds16x4(uint32_t a) { return make_uint4(lds16(a), lds16(a + TBW), lds16(a + 2 * TBW), lds16(a + 3 * TBW)); }
__device__ __forceinline__ void combine_setup(uint32_t sb, int warp, int lane, uint32_t kw, uint32_t& o, uint32_t& n, uint32_t& d) {
    const int wq = warp & 3;
    const uint32_t a = table_buf(sb, warp & ~3);
    o = wq == 3 ? a + 1024 + 320 + (lane >> 3) * 80 + (lane & 7) * 8 : a + (wq ? 504 + wq * 8 : 0) + lane * 16;
    n = a + 1024 + wq * 80 + lane * 2;
    d = wq < 3 ? kw + (wq == 2 ? KW_P : 32 + wq * 512) + lane * 16 : kw + KW_H + 8 + lane * 8;
}
__device__ __forceinline__ void kgen_combine(int wq, int lane, uint32_t o, uint32_t na, uint32_t d) {
#define S4(f) hadd2(hadd2(u.f, v.f), hadd2(w.f, x.f))
#define H4(v) hadd2(hadd2(v.x, v.y), hadd2(v.z, v.w))
#define BP __byte_perm
    if (wq == 0) {
        const uint4 u = lds128(o), v = lds128(o + TBW), w = lds128(o + 2 * TBW), x = lds128(o + 3 * TBW), nn = lds16x4(na);
        const uint32_t n = H4(nn), k0 = S4(x), k2 = S4(y), k4 = S4(z), k6 = S4(w);
        sts128(d, BP(k0, k0, 0x1032), BP(k0, k2, 0x3254), BP(k2, k2, 0x1032), BP(k2, k4, 0x3254));
        sts128(d + KW_PL, BP(k4, k4, 0x1032), BP(k4, k6, 0x3254), BP(k6, k6, 0x1032), BP(k6, n, 0x3254));
        if (lane == 0) sts32(d + KW_PL - 4, k0 & 0xffffu);
    } else {
        const uint2 u = lds64(o), v = lds64(o + TBW), w = lds64(o + 2 * TBW), x = lds64(o + 3 * TBW);
        uint4 nn = make_uint4(0u, 0u, 0u, 0u), mm = nn;
        if (wq < 3) nn = lds16x4(na);
        if (wq == 2) mm = lds16x4(na + 80);
        const uint32_t k0 = S4(x), k2 = S4(y), n = H4(nn), m = H4(mm);
        if (wq == 3) {
            sts64(d, k0, k2);
        } else if (wq == 1) {
            const uint32_t cc = BP(k2, k2, 0x1010);
            sts128(d, BP(k0, k0, 0x1010), BP(k0, k0, 0x1032), BP(k0, k2, 0x3254), cc);
            sts128(d + KW_PL, cc, BP(k2, k2, 0x1032), BP(k2, n, 0x3254), BP(n, n, 0x1010));
        } else {
            const uint32_t w40 = BP(k0, k0, 0x1032), w84 = BP(k0, n, 0x3254), w0 = BP(k0, k0, 0x1010), w4 = BP(k0, k0, 0x3232), w8 = BP(n, n, 0x1010);
            sts64(d, w40, w84);
            sts64(d + 512, BP(k2, k2, 0x1032), BP(k2, m, 0x3254));
            if (lane < 8) { sts128(d - (KW_P - 1056), w0, w0, w40, w4); sts128(d - (KW_P - 1056 - KW_PL), w4, w84, w8, w8); }
            if (lane == 31) sts16(d + (KW_H + 6 - KW_P - 496), m);
        }
    }
#undef S4
#undef H4
#undef BP
}

__device__ __forceinline__ int c_exponent(const uint2& r, const uint2& i, float dt) {
    const uint32_t mx = __vmaxu2(__vmaxu2(r.x & 0x7fff7fffu, r.y & 0x7fff7fffu), __vmaxu2(i.x & 0x7fff7fffu, i.y & 0x7fff7fffu));
    return __reduce_max_sync(0xffffffffu, max(mx, mx << 16) + (__float_as_uint(dt) & 0x7f800000u)) >> 23;
}

#define YQ 2
#define F0 0
__device__ __forceinline__ int warp_v() { int l; asm volatile("mov.u32 %0, %%tid.x;" : "=r"(l)); return __shfl_sync(0xffffffffu, l >> 5, 0); }
__device__ __forceinline__ int lane_v() { int l; asm volatile("mov.u32 %0, %%laneid;" : "=r"(l)); return l; }
__device__ __forceinline__ uint32_t prmt_v(uint32_t a, uint32_t b, uint32_t s) { uint32_t d; asm volatile("prmt.b32 %0, %1, %2, %3;\n" : "=r"(d) : "r"(a), "r"(b), "r"(s)); return d; }
__device__ __forceinline__ uint32_t mov_v(uint32_t a) { uint32_t d; asm volatile("mov.b32 %0, %1;\n" : "=r"(d) : "r"(a)); return d; }
template <int G>
__device__ __forceinline__ void conv_rename(float (&acc)[16][4]) {
#pragma unroll
    for (int i = G; i < 16; i++)
#pragma unroll
        for (int j = 0; j < 4; j++) { float v; asm volatile("mov.b32 %0, %1;\n" : "=f"(v) : "f"(acc[i][j])); acc[i][j] = v; }
}
struct Conv {
    uint32_t kw;
    uint32_t wa;
    uint32_t pa, s2;
    uint32_t s8;
    uint32_t id;
    uint32_t lc;
    uint32_t fs;
    uint32_t fl, yo;
    uint32_t yp;
    size_t ycopy;
    uint32_t ps;
    uint64_t d0;
    int warp;
};
struct Pk { uint32_t w[4]; };
__device__ __forceinline__ Pk pk2(const float (&u)[4], const float (&v)[4]) {
    Pk r;
    r.w[0] = pack_f16(u[0], u[1]); r.w[1] = pack_f16(u[2], u[3]); r.w[2] = pack_f16(v[0], v[1]); r.w[3] = pack_f16(v[2], v[3]);
    return r;
}
__device__ __forceinline__ void park(uint32_t a, const Pk& v) {
    asm volatile("stmatrix.sync.aligned.m8n8.x4.trans.shared.b16 [%0], {%1,%2,%3,%4};\n" ::"r"(a), "r"(v.w[0]), "r"(v.w[1]), "r"(v.w[2]), "r"(v.w[3]) : "memory");
}
__device__ __forceinline__ void conv_constants(uint32_t lc, int l) {
    const int d = (l >> 2) - 2 * (l & 3);
    const int e = d + 8, r4 = (e + 1 + ((e >> 2) & 1)) >> 2, p4 = (e + (((e - 1) >> 2) & 1)) >> 2;
    const uint32_t s2 = r4 == p4 ? 0x1010u : 0x3210u;
    sts64(lc + l * 8, KW_P + ((r4 - 5) >> 1) * 16 + ((r4 - 5) & 1) * 4, s2 | ((d < 0 ? s2 : 0x7654u) << 16));
    const int lo = (d >= 4) - (d < -3), ho = (d >= 5) - (d < -2), le = (d > 4) - (d < -4), he = (d > 5) - (d < -3);
    sts32(lc + 512 + l * 8, (0x5454u + lo * 0x22 + ho * 0x2200) | ((0x3232u + le * 0x22 + he * 0x2200) << 16));
    const int cc = l >> 2, j = l & 3;
    sts64(lc + 256 + l * 8, (j >> 1) * PL_HALF + (16 + cc) * 16 + (j & 1) * 8, (cc >> 1) * (DM * 64) + (cc & 1) * 32 + j * 8);
}
__device__ __forceinline__ void conv_selectors4(Conv& c) {
    const uint2 v = lds64(c.lc + lane_v() * 8);
    c.pa = v.x; c.s2 = v.y;
}
__device__ __forceinline__ void conv_selectors8(Conv& c) { c.s8 = lds32(c.lc + 512 + lane_v() * 8); }
template <int G, int I0, int I1>
__device__ __forceinline__ void conv_load(const Conv& c, uint32_t (&q)[9]) {
    const int wq = c.warp & 3;
    if (G < 2) {
#pragma unroll
        for (int i = I0; i < I1; i++) q[i] = lds32(c.wa + G * 512 + i * 16);
    } else if (G < 4) {
        const uint32_t a = (G == 2 && wq == 0) ? c.wa + 1024 : c.pa + c.kw + wq * 128 + (G < 2 ? 0 : G - 2) * 512;
#pragma unroll
        for (int i = I0; i < I1; i++) q[i] = lds32(a + i * 16);
    } else {
        const uint4 u = lds128(c.kw + KW_H + (G < 4 ? 0 : G - 4) * 64 + wq * 16);
        const uint2 v = lds64(c.kw + KW_H + (G < 4 ? 0 : G - 4) * 64 + wq * 16 + 16);
        q[0] = u.x; q[1] = u.y; q[2] = u.z; q[3] = u.w; q[4] = v.x; q[5] = v.y;
        if (G == 4 && wq == 0) { q[6] = lds32(c.pa + c.kw + 1024); q[7] = lds32(c.pa + c.kw + 1040); }
    }
}
template <int G, int J0, int J1>
__device__ __forceinline__ void conv_frag(const Conv& c, const uint32_t (&q)[9], uint32_t* a, const Pk& dp) {
    const uint32_t dep = dp.w[0];
    if (G < 4) {
        const uint32_t s = (G < 2 || (G == 2 && (c.warp & 3) == 0)) ? c.id : c.s2;
#pragma unroll
        for (int j = J0; j < J1; j++) {
            uint32_t* o = a + 4 * (j - J0);
            o[0] = prmt_v(q[2 * j + 1], dp.w[0], s); o[1] = prmt_v(q[2 * j + 2], dp.w[1], s); o[2] = prmt_v(q[2 * j], dp.w[2], s); o[3] = prmt_v(q[2 * j + 1], dp.w[3], s);
        }
    } else {
        const uint32_t so = prmt_v(c.s8, dep, c.id), se = prmt_v(c.s8, dep, c.id + 0x22);
#pragma unroll
        for (int j = J0; j < J1; j++) {
            uint32_t* o = a + 4 * (j - J0);
            o[0] = prmt_v(q[j + 1], q[j + 2], se); o[1] = prmt_v(q[j + 1], q[j + 2], so); o[2] = prmt_v(q[j], q[j + 1], so);
            if (G == 4 && j == 0 && (c.warp & 3) == 0) {
                o[2] = prmt_v(q[6], dep, c.s2);
                o[0] = prmt_v(q[7], o[0], c.s2 >> 16);
            }
            o[3] = mov_v(o[0]);
        }
    }
}
template <int G, int J0, int J1>
__device__ __forceinline__ void conv_frag(const Conv& c, const uint32_t (&q)[9], uint32_t* a, float depf) {
    const uint32_t d = __float_as_uint(depf);
    conv_frag<G, J0, J1>(c, q, a, Pk{{d, d, d, d}});
}
template <int G, int T, int J0, int J1>
__device__ __forceinline__ void conv_mma(float (&acc)[16][4], const Conv& c, const uint32_t* a) {
#pragma unroll
    for (int j = J0; j < J1; j++) wg_mma<T>(acc, a + 4 * (j - J0), c.d0 - 8 * (2 * G - T) - j);
}
__device__ __forceinline__ float h_lo(uint32_t w) { return __half2float(__ushort_as_half((unsigned short)(w & 0xffffu))); }
__device__ __forceinline__ float h_hi(uint32_t w) { return __half2float(__ushort_as_half((unsigned short)(w >> 16))); }
__device__ __forceinline__ void flush_setup(Conv& c) {
    const uint2 v = lds64(c.lc + 256 + lane_v() * 8);
    c.fl = v.x; c.yo = v.y;
}
template <int Q>
__device__ __forceinline__ void flush_load(const Conv& c, uint32_t pl, uint2 (&f)[4]) {
#pragma unroll
    for (int w = 0; w < 4; w++) f[w] = lds64(c.fl + pl + (Q & 1) * 512 + w * (PLW_B - 64));
}
template <int Q>
__device__ __forceinline__ void flush_load_first(const Conv& c, uint32_t pl, uint2 (&f)[4], float depf) {
    const uint32_t p = prmt_v(c.fl, __float_as_uint(depf), c.id) + pl + (Q & 1) * 512;
#define LDV64(d, a) asm volatile("ld.volatile.shared.v2.u32 {%0,%1}, [%2];\n" : "=r"(d.x), "=r"(d.y) : "r"(a) : "memory")
    LDV64(f[0], p); LDV64(f[1], p + (PLW_B - 64)); LDV64(f[2], p + 2 * (PLW_B - 64)); LDV64(f[3], p + 3 * (PLW_B - 64));
}
#define FDEP __uint_as_float(f[3].y)
template <int Q, int mode>
__device__ __forceinline__ void conv_flush(const Conv& c, const uint2 (&f)[4], unsigned char* gy, uint32_t rx) {
    const uint32_t a0 = hadd2(f[0].x, f[1].x), a1 = hadd2(f[2].x, f[3].x), b0 = hadd2(f[0].y, f[1].y), b1 = hadd2(f[2].y, f[3].y);
    if (Q > 0 && mode == 1) {
        const uint32_t ra = rx + 16 + (Q > 0 ? Q - 1 : 0) * 1024 + (c.warp & 3) * 256 + lane_v() * 8;
        asm volatile("st.async.shared::cluster.mbarrier::complete_tx::bytes.v2.b32 [%0], {%1,%2}, [%3];\n"
                     ::"r"(ra ^ 0x1000000u), "r"(hadd2(a0, a1)), "r"(hadd2(b0, b1)), "r"((rx + (Q > 1 ? 8 : 0)) ^ 0x1000000u) : "memory");
        return;
    }
    float v0 = h_lo(a0) + h_lo(a1), v1 = h_hi(a0) + h_hi(a1), v2 = h_lo(b0) + h_lo(b1), v3 = h_hi(b0) + h_hi(b1);
    if (Q > 0 && mode == 2) {
        const uint2 o = lds64(rx + 16 + (Q > 0 ? Q - 1 : 0) * 1024 + (c.warp & 3) * 256 + lane_v() * 8);
        v0 += h_lo(o.x); v1 += h_hi(o.x); v2 += h_lo(o.y); v3 += h_hi(o.y);
    }
    const uint32_t lo = hmul2_bf(pack_bf16(v0, v1), c.fs), hi = hmul2_bf(pack_bf16(v2, v3), c.fs);
    stg64(gy + Q * 32 * DM * 32 + (c.yo + (Q < YQ ? c.yp : 0u)), nzw(lo), nzw(hi));
}
template <int I, bool S = false> struct IC { static constexpr int value = I; static constexpr bool shared = S; };
template <class T> __device__ constexpr bool wg_is4() { return T::shared; }
#define SLOT(n) (c.ps + (2 + ((n) & 7)) * 128)
#define GO() do { wg_commit(); __syncwarp(); } while (0)
#define DEP acc[15][3]
template <class FG, class FP, class FN>
__device__ __forceinline__ void conv_head(Conv& c, float (&acc)[16][4], uint32_t (&q)[9], uint32_t (&r)[9], uint32_t* a, FG fg, FP pre, FN next) {
    c.id = 0x3210u + (c.warp >> 8);
    pre();
    conv_load<0, 0, 9>(c, q);
    conv_frag<0, 0, 1>(c, q, a, 0.f);
    wg_fence(); wg_first<0>(acc, a, c.d0); GO();
    park(c.ps, Pk{{0u, 0u, 0u, 0u}});
    wg_wait0();
    conv_frag<0, 1, 2>(c, q, a, DEP);
    wg_fence(); conv_mma<0, 0, 1, 2>(acc, c, a); GO();
    fg(IC<0>());
    wg_wait0();
    conv_frag<0, 2, 3>(c, q, a, DEP);
    wg_fence(); conv_mma<0, 0, 2, 3>(acc, c, a); GO();
    conv_load<1, 0, 5>(c, r);
    wg_wait0();
    conv_frag<0, 3, 4>(c, q, a, DEP);
    wg_fence(); conv_mma<0, 0, 3, 4>(acc, c, a); GO();
    conv_load<1, 5, 9>(c, r);
    fg(IC<1>());
    wg_wait0();
    const Pk k = pk2(acc[0], acc[1]);
    conv_rename<2>(acc);
    conv_frag<1, 0, 2>(c, r, a, k);
    wg_fence(); conv_mma<1, 2, 0, 2>(acc, c, a); GO();
    park(SLOT(0), k);
    next(IC<0>());
    fg(IC<2>());
    wg_wait0();
    conv_frag<1, 2, 4>(c, r, a, DEP);
    wg_fence(); conv_mma<1, 2, 2, 4>(acc, c, a); GO();
    next(IC<1>());
    fg(IC<3>());
    wg_wait0();
}
template <class FG, class FP>
__device__ __forceinline__ void conv_run(Conv& c, uint32_t pl, unsigned char* gy, FG fg, FP pre) {
    float acc[16][4];
    uint32_t q[9], r[9], a[32];
    uint2 f[4];
    const int bid = 1 + (c.warp >> 2);
    conv_head(c, acc, q, r, a, fg, pre, [&](auto i) { if (decltype(i)::value == 0) conv_selectors4(c); else conv_load<2, 0, 9>(c, q); });
    Pk k = pk2(acc[2], acc[3]);
    conv_rename<4>(acc);
    conv_frag<2, 0, 4>(c, q, a, k);
    wg_fence(); conv_mma<2, 4, 0, 4>(acc, c, a); GO();
    park(SLOT(2), k);
    conv_load<3, 0, 9>(c, q);
    flush_setup(c);
    bar_sync(bid, 128);
    fg(IC<4>());
    wg_wait0();
    conv_rename<6>(acc);
    if (F0) { flush_load_first<0>(c, pl, f, DEP); conv_frag<3, 0, 4>(c, q, a, FDEP); }
    else conv_frag<3, 0, 4>(c, q, a, DEP);
    wg_fence(); conv_mma<3, 6, 0, 4>(acc, c, a); GO();
    park(SLOT(4), pk2(acc[4], acc[5]));
    conv_load<4, 0, 9>(c, q);
    conv_selectors8(c);
    if (!F0) flush_load<0>(c, pl, f);
    conv_flush<0, 0>(c, f, gy, 0u);
    fg(IC<5>());
    wg_wait0();
    conv_rename<8>(acc);
    conv_frag<4, 0, 4>(c, q, a, DEP);
    wg_fence(); conv_mma<4, 8, 0, 4>(acc, c, a); GO();
    k = pk2(acc[6], acc[7]);
    park(SLOT(6), k);
    conv_load<5, 0, 9>(c, q);
    bar_sync(bid, 128);
    park(c.ps, k);
    fg(IC<6>());
    wg_wait0();
    conv_rename<10>(acc);
    flush_load_first<1>(c, pl, f, DEP);
    conv_frag<5, 0, 4>(c, q, a, FDEP);
    wg_fence(); conv_mma<5, 10, 0, 4>(acc, c, a); GO();
    park(SLOT(8), pk2(acc[8], acc[9]));
    conv_load<6, 0, 9>(c, q); conv_load<7, 0, 9>(c, r);
    conv_flush<1, 0>(c, f, gy, 0u);
    fg(IC<7>());
    wg_wait0();
    conv_rename<12>(acc);
    conv_frag<6, 0, 4>(c, q, a, DEP); conv_frag<7, 0, 4>(c, r, a + 16, DEP);
    wg_fence(); conv_mma<6, 12, 0, 4>(acc, c, a); conv_mma<7, 12, 0, 4>(acc, c, a + 16); GO();
    park(SLOT(10), pk2(acc[10], acc[11]));
    bar_sync(bid, 128);
    flush_load<2>(c, pl, f);
    conv_flush<2, 0>(c, f, gy, 0u);
    fg(IC<8>());
    if (c.id == 0) TRAP();
    wg_wait0();
    park(SLOT(12), pk2(acc[12], acc[13])); park(SLOT(14), pk2(acc[14], acc[15]));
    bar_sync(bid, 128);
    flush_load<3>(c, pl, f);
    conv_flush<3, 0>(c, f, gy, 0u);
}
template <class FG>
__device__ __forceinline__ void conv_outer(Conv& c, uint32_t pl, unsigned char* gy, uint32_t rx, FG fg) {
    float acc[16][4];
    uint32_t q[9], r[9], a[32];
    uint2 f[4], f2[4];
    const int bid = 1 + (c.warp >> 2);
    conv_head(c, acc, q, r, a, [&](auto gi) { if (decltype(gi)::value == 2) fg(IC<2, true>()); }, [&]() {}, [&](auto i) { if (decltype(i)::value == 0) conv_selectors8(c); else conv_load<6, 0, 9>(c, q); });
    park(SLOT(2), pk2(acc[2], acc[3])); park(SLOT(4), pk2(acc[4], acc[5]));
    const Pk k = pk2(acc[6], acc[7]);
    park(SLOT(6), k);
    conv_load<7, 0, 9>(c, r);
    conv_rename<12>(acc);
    conv_frag<6, 0, 4>(c, q, a, __uint_as_float(k.w[3])); conv_frag<7, 0, 4>(c, r, a + 16, __uint_as_float(k.w[3]));
    wg_fence(); conv_mma<6, 12, 0, 4>(acc, c, a); conv_mma<7, 12, 0, 4>(acc, c, a + 16); GO();
    flush_setup(c);
    bar_sync(bid, 128);
    flush_load<0>(c, pl, f); flush_load<1>(c, pl, f2);
    conv_flush<1, 1>(c, f2, gy, rx);
    conv_flush<0, 1>(c, f, gy, rx);
    wg_wait0();
    bar_sync(bid, 128);
    park(c.ps, k); park(SLOT(8), pk2(acc[8], acc[9])); park(SLOT(10), pk2(acc[10], acc[11]));
    park(SLOT(12), pk2(acc[12], acc[13])); park(SLOT(14), pk2(acc[14], acc[15]));
    bar_sync(bid, 128);
    flush_load<2>(c, pl, f); flush_load<3>(c, pl, f2);
    conv_flush<2, 1>(c, f, gy, rx);
    conv_flush<3, 1>(c, f2, gy, rx);
}
template <class FG>
__device__ __forceinline__ void conv_inner(Conv& c, uint32_t pl, unsigned char* gy, uint32_t rx, FG fg) {
    float acc[16][4];
    uint32_t q[9], a[16];
    uint2 f[4], f2[4];
    const int bid = 1 + (c.warp >> 2);
    c.id = 0x3210u + (c.warp >> 8);
    conv_selectors4(c);
    conv_load<2, 0, 9>(c, q);
    conv_frag<2, 0, 4>(c, q, a, 0.f);
    wg_fence(); wg_first<4>(acc, a, c.d0); conv_mma<2, 4, 1, 4>(acc, c, a + 4); GO();
    conv_load<3, 0, 9>(c, q);
    park(SLOT(2), Pk{{0u, 0u, 0u, 0u}});
    fg(IC<2, true>());
    wg_wait0();
    conv_rename<6>(acc);
    conv_frag<3, 0, 4>(c, q, a, DEP);
    wg_fence(); conv_mma<3, 6, 0, 4>(acc, c, a); GO();
    park(SLOT(4), pk2(acc[4], acc[5]));
    conv_load<4, 0, 9>(c, q);
    conv_selectors8(c);
    wg_wait0();
    conv_rename<8>(acc);
    conv_frag<4, 0, 4>(c, q, a, DEP);
    wg_fence(); conv_mma<4, 8, 0, 4>(acc, c, a); GO();
    const Pk k = pk2(acc[6], acc[7]);
    park(SLOT(6), k); park(c.ps, k);
    conv_load<5, 0, 9>(c, q);
    flush_setup(c);
    wg_wait0();
    conv_rename<10>(acc);
    conv_frag<5, 0, 4>(c, q, a, DEP);
    wg_fence(); conv_mma<5, 10, 0, 4>(acc, c, a); GO();
    park(SLOT(8), pk2(acc[8], acc[9]));
    bar_sync(bid, 128);
    flush_load<1>(c, pl, f);
    mbar_wait(rx);
    conv_flush<1, 2>(c, f, gy, rx);
    wg_wait0();
    bar_sync(bid, 128);
    park(SLOT(10), pk2(acc[10], acc[11])); park(SLOT(12), pk2(acc[12], acc[13])); park(SLOT(14), pk2(acc[14], acc[15]));
    bar_sync(bid, 128);
    flush_load<3>(c, pl, f); flush_load<2>(c, pl, f2);
    mbar_wait(rx + 8);
    conv_flush<3, 2>(c, f, gy, rx);
    conv_flush<2, 2>(c, f2, gy, rx);
}
#undef SLOT
#undef GO
#undef DEP
template <int U0, int U1>
__device__ __forceinline__ void weight_units(uint32_t sb, const CUtensorMap* tg, const CUtensorMap* tu, const CUtensorMap* td, bool w) {
    if (U1 > U0 && w && elect_one()) {
#pragma unroll
        for (int i = U0; i < U1; i++) {
            if (i < 12) tma_2d(sb + SM_WG + i * 6912, i < 6 ? tg : tu, 72 * (blockIdx.x >> 1), 288 * (blockIdx.x & 1) + (i % 6) * 48, sb + SM_MISC + 328);
            else tma_2d(sb + SM_WD + (i - 12) * 4736, td, 144 * (blockIdx.x & 1), 72 * (blockIdx.x >> 1) + 8 * (i - 12), sb + SM_MISC + 336);
        }
    }
}
#define WS 2110121111122004100
__device__ constexpr int wsched(int i) {
    unsigned long long v = WS;
    int n = 0;
    for (int k = 19; k >= 1; k--) { if (k < i) n += (int)(v % 10); v /= 10; }
    return n;
}
static_assert(wsched(20) == 21 && wsched(6) <= 7 && wsched(11) <= 12 && wsched(13) <= 14 && wsched(16) <= 17 && wsched(16) == wsched(15) && wsched(19) == 21, "");
#define WANY(i) (wsched((i) + 1) > wsched(i))
#define WPOINT(i, w) do { weight_units<wsched(i), wsched(i + 1)>(sb, &tm_g, &tm_u, &tm_d, w); } while (0)

__global__ void __launch_bounds__(NTHR, 1) __cluster_dims__(2, 1, 1)
fused_kernel(const Params p, const __grid_constant__ CUtensorMap tm_g, const __grid_constant__ CUtensorMap tm_u, const __grid_constant__ CUtensorMap tm_d, const __grid_constant__ CUtensorMap tm_x) {
    extern __shared__ __align__(1024) unsigned char smem[];
    const uint32_t sb = smem_u32(smem);
    const int tid = threadIdx.x, warp = __shfl_sync(0xffffffffu, tid >> 5, 0), lane = tid & 31;
    const int b = blockIdx.x, P = b >> 1, odd = b & 1;
    const int g = lane >> 2, t = lane & 3;
    const int wg = warp >> 2, t128 = tid & 127;
    const uint32_t s_stat = sb + SM_MISC;
    const uint32_t s_key = sb + SM_MISC + 128;
    const uint32_t s_rank = sb + SM_MISC + 256;
    const uint32_t s_k16 = sb + SM_MISC + 192;
    const uint32_t s_cnt = sb + SM_MISC + 320;
    const uint32_t bar_w = sb + SM_MISC + 328, bar_d = bar_w + 8, bar_g = bar_w + 16, bar_x = bar_w + 24, bar_v = bar_w + 32, bar_s = bar_w + 40, bar_h = bar_w + 48;
    STAMP(0);

    const int ch = wg < 4 ? 4 * b + wg : 512 + P;
    const uint32_t mo = tid < 512 ? 512 * b + tid : 65536 + 128 * P + t128, mq = (mo & ~127u) + 4 * lane;
    const uint32_t pl = ldo16(p.lar + mo), pa2 = ldo16(p.aim + mo), ldt = ldo16(p.ldt + (mo >> 7));
    const uint32_t pc = ldo16(p.cre + mo), pi = ldo16(p.cim + mo);
    const uint2 call_re = ldo64(p.cre + mq), call_im = ldo64(p.cim + mq);
    const uint32_t epl = ld_poll32(p.s->hint + (b & 7) * 32 + 1);
    if (wg < 4) {
        bar_arrive(0, NWRK);
        asm volatile("barrier.cluster.arrive.relaxed.aligned;\n" ::: "memory");
    } else {
        const int o = (4 * (warp & 3) + (g >> 1)) * 1152 + (g & 1) * 576 + t * 16;
        sts128(sb + SM_Z2 + t128 * 16, 0u, 0u, 0u, 0u); sts128(sb + SM_Z2 + 2048 + t128 * 16, 0u, 0u, 0u, 0u);
        if (warp == 16) sts128(sb + SM_Z2 + 4096 + lane * 16, 0u, 0u, 0u, 0u);
        fence_async();
        bar_sync(0, NWRK);
        STAMP(9);
#pragma unroll
        for (int c = 0; c < 9; c++)
            asm volatile("cp.async.cg.shared.global [%0], [%1], 16;\n" ::"r"(sb + SM_XT + o + c * 64), "l"(reinterpret_cast<const char*>(p.x) + b * 18432 + o + c * 64) : "memory");
        asm volatile("cp.async.commit_group;\n" ::: "memory");
        if (elect_one()) {
            mbar_init(bar_h + 8 * (warp & 3), 1);
            if (warp == 19) {
                mbar_init(bar_x, 1); mbar_init(bar_w, 1);
                mbar_expect(bar_x, 32768); mbar_expect(bar_w, 82944);
#pragma unroll
                for (int i = YQ; i < 4; i++) bulk_s2g(reinterpret_cast<unsigned char*>(p.s->y) + 32 * i * 18432 + b * 4608, sb + SM_Z2, 4608);
            } else if (warp == 18) {
                mbar_init(bar_s, 1); mbar_init(bar_v, 2); mbar_init(bar_d, 1); mbar_init(bar_g, 1); mbar_init(sb + SM_RX, 1); mbar_init(sb + SM_RX + 8, 1);
                mbar_expect(bar_v, 2 * 1152); mbar_expect(bar_d, 72 * WD_PITCH); mbar_expect(bar_g, 4608); mbar_expect(sb + SM_RX, 1024); mbar_expect(sb + SM_RX + 8, 2048);
            }
            asm volatile("fence.mbarrier_init.release.cluster;\n" ::: "memory");
        }
        __syncwarp();
        asm volatile("barrier.cluster.arrive.relaxed.aligned;\n" ::: "memory");
        if (warp == 19) {
            asm volatile("barrier.cluster.wait.aligned;\n" ::: "memory");
            if (elect_one()) tma_4d_mc(sb + SM_XC + odd * 16384, &tm_x, 8 * P, 2 * odd, bar_x);
            __syncwarp();
        }
        {
            if (!(g & 1) && t == (g >> 1)) *reinterpret_cast<volatile uint32_t*>(p.s->stat + 16 * b + 4 * (warp & 3) + t) = 0u;
            if (warp < 18) {
                unsigned char* const ud = reinterpret_cast<unsigned char*>(p.s->uT) + (size_t)(8 * (warp & 1) + 2 * (g >> 1)) * 16384 + b * 128 + (g & 1) * 32 + t * 8;
#pragma unroll
                for (int k = 0; k < 4; k++) *reinterpret_cast<volatile unsigned long long*>(ud + (k >> 1) * 16384 + (k & 1) * 64) = 0ull;
            }
        }
    }
    const uint32_t kw = sb + SM_KW + wg * KW_B;
    const uint32_t tb = table_buf(sb, warp), t5 = sb + SM_WD + warp * 512;
    STAMP(29);
    const float dt = exp_bf(bf_lo(ldt));
    const uint32_t ep = __reduce_or_sync(0xffffffffu, epl);
    auto stats = [&]() {
        const int wq = warp & 3;
        const uint32_t xa = sb + SM_XT + (4 * wq + (g >> 1)) * 1152 + (g & 1) * 576 + t * 16;
        const bool own = !(g & 1) && t == (g >> 1);
        float d[4][4] = {};
        asm volatile("cp.async.wait_group 0;\n" ::: "memory");
        STAMP(26);
        uint4 v[9];
#pragma unroll
        for (int c = 0; c < 9; c++) v[c] = lds128(xa + c * 64);
#pragma unroll
        for (int c = 0; c < 9; c++) {
            mma_bf16(d[2 * (c & 1)], v[c].x, 0x3f803f80u, v[c].y, 0x3f803f80u, v[c].x, v[c].y);
            mma_bf16(d[2 * (c & 1) + 1], v[c].z, 0x3f803f80u, v[c].w, 0x3f803f80u, v[c].z, v[c].w);
        }
        STAMP(27);
        float sm = (g & 1) ? (d[0][3] + d[1][3]) + (d[2][3] + d[3][3]) : (d[0][2] + d[1][2]) + (d[2][2] + d[3][2]);
        float sq = (g & 1) ? (d[0][1] + d[1][1]) + (d[2][1] + d[3][1]) : (d[0][0] + d[1][0]) + (d[2][0] + d[3][0]);
        sm += __shfl_xor_sync(0xffffffffu, sm, 4); sq += __shfl_xor_sync(0xffffffffu, sq, 4);
        if (lane == 0) mbar_arrive(bar_h + 8 * wq);
        float mb, sd;
        ln_stats(sm, sq, mb, sd);
        if (own) p.s->stat[16 * b + 4 * wq + t] = (__float_as_uint(mb) >> 16) | (__float_as_uint(sd) & 0x7fff0000u) | (ep << 31);
        STAMPX(22);
        if (own) stat_store(s_stat + (2 * wq + (t & 1) + 8 * (t >> 1)) * 8, mb, rcp_approx(sd), 0u);
        if (wq == 3) asm volatile("cp.async.bulk.wait_group 0;\n" ::: "memory");
        bar_sync(5, 128);
        STAMP(28);
        uint32_t now;
        asm volatile("mov.u32 %0, %%clock;" : "=r"(now) :: "memory");
        if (wq == 2) {
            conv_constants(sb + SM_LC, lane);
            __syncwarp();
            if (lane < 8) p.s->key3[8 * b + lane] = ep & 1u;
            if (lane == 0) {
                sts64(s_cnt, now, ep);
                mbar_arrive(bar_s);
                bulk_g2s(sb + SM_XT + 16 * 1152, p.dsk, 1152, bar_v);
                bulk_g2s(sb + SM_XT + 17 * 1152, p.wr, 1152, bar_v);
            }
            __syncwarp();
        }
        WPOINT(1, wq == 3);
        if (wq < 2) {
            unsigned char* const ud = reinterpret_cast<unsigned char*>(p.s->uT) + (size_t)(8 * wq + 2 * (g >> 1)) * 16384 + b * 128 + (g & 1) * 32 + t * 8;
            const uint32_t utag = (ep % 7u + 1u) * 0x10001u;
            uint32_t U[2][4];
#pragma unroll
            for (int hf = 0; hf < 2; hf++) {
                const uint2 st = lds64(s_stat + (g + 8 * hf) * 8);
                const uint4 xu = lds128(sb + SM_XT + (TOK(g) + 2 * hf) * 1152 + warp * 64 + t * 16);
                const uint32_t X[4] = {xu.x, xu.y, xu.z, xu.w};
#pragma unroll
                for (int k = 0; k < 4; k++) {
                    const uint32_t u = ln_apply(X[k], STAT_M(st), STAT_H(st), STAT_L(st));
                    U[hf][k] = movm((pack_f16(bf_lo(u), bf_hi(u)) & 0xfff8fff8u) | utag);
                }
            }
#pragma unroll
            for (int k = 0; k < 4; k++) stg64(ud + (k >> 1) * 16384 + (k & 1) * 64, U[0][k], U[1][k]);
        }
    };
    STAMP(1);
    if (wg < 4) { STAMPX(16); }
    KGen kg;
    kgen_setup(kg, bf_lo(pl), bf_lo(pa2), dt);
    kgen_rows(kg, tb, lane);
    STAMP(2);
    const int E = min(max(c_exponent(call_re, call_im, dt) - 243, -120), 120);
    kgen_chain(kg, pc, pi, dt * __uint_as_float((uint32_t)(128 - E) << 23));
    STAMP(3);
    kgen_cols(kg, tb, t5, lane);
    STAMP(4);
    if (wg == 4) stats();
    if (warp != 19) asm volatile("barrier.cluster.wait.aligned;\n" ::: "memory");
    if (wg < 4) { STAMPX(17); }
    if (t128 < 2 * UPAD) sts128(sb + SM_U + wg * USLOT_B + (t128 & 1) * ULO_B + (t128 >> 1) * 16, 0u, 0u, 0u, 0u);
    if (t128 >= 124) sts128(kw + (t128 & 1) * 16 + (t128 & 2) * (KW_PL / 2), 0u, 0u, 0u, 0u);
    if (warp < 15) sts128(sb + SM_Z2 + 4608 + tid * 16, 0u, 0u, 0u, 0u);
    uint32_t co, cn, cd;
    combine_setup(sb, warp, lane, kw, co, cn, cd);
    co = pin(co); cn = pin(cn); cd = pin(cd);
    const uint4* const usrc = reinterpret_cast<const uint4*>(p.s->stat) + pin(wg < 4 ? tid : 512 + (P >> 2) * 1024 + (t128 >> 1) * 8 + (P & 3) * 2 + (t128 & 1));
    if (wg < 4) mbar_wait(bar_h + 8 * (warp & 3));
    if (wg < 4) { STAMPX(19); }
    kgen_mma(kg, tb, t5, lane);
    if (wg < 4) { STAMPX(20); }
    STAMP(5);
    uint4 uv0, uv1;
    auto first_poll = [&](uint32_t dly) {
        mbar_wait(bar_s);
        const uint32_t t0 = lds32(s_cnt);
        uint32_t now;
        do { asm volatile("mov.u32 %0, %%clock;" : "=r"(now) :: "memory"); } while (now - t0 < dly);
        uv0 = ld_poll(usrc);
    };
    if (wg == 4) { first_poll(UDLY); uv1 = ld_poll(usrc + 512); }
    WPOINT(2, warp == 19);
    bar_sync(1 + wg, 128);
    if (wg < 4) { STAMPX(21); }
    kgen_combine(warp & 3, lane, co, cn, cd);
    STAMP(6);
    if (wg < 4) { STAMPX(18); }
    WPOINT(3, warp == 19);
    if (wg < 4) first_poll(SDLY);
    {
        const int wq = warp & 3;
        Conv c;
        const uint32_t pln = sb + SM_PL + wg * PL_B;
        const int e = g - 2 * t + 7;
        c.kw = kw; c.wa = pin(kw + ((e >> 2) & 1) * KW_PL + (8 * wq + (e >> 3)) * 16 + (e & 3) * 4);
        c.ps = mov_v(pln + wq * PLW_B + ((lane >> 3) & 1) * PL_HALF + ((lane >> 4) * 8 + (lane & 7)) * 16); c.warp = warp;
        c.lc = sb + SM_LC; c.fs = (uint32_t)(127 + E) * 0x800080u; c.yp = (ep & 1u) * (NCTA * 18432u);
        c.d0 = ((uint64_t)(ULO_B >> 4) << 16) | ((uint64_t)(128 >> 4) << 32) | (uint64_t)(((sb + SM_U + wg * USLOT_B + UPAD * 16) & 0x3FFFF) >> 4);
        unsigned char* gy = reinterpret_cast<unsigned char*>(p.s->y) + ((size_t)(4 * wq) * DM + ch) * 64;
        auto hook = [&](auto gi) {
                     constexpr int G = decltype(gi)::value;
                     if (G == (wg_is4<decltype(gi)>() ? 2 : 5)) asm volatile("barrier.cluster.wait.aligned;\n" ::: "memory");
                     if (!wg_is4<decltype(gi)>() && (G == 0 || G == 2) && warp == HW && elect_one()) {
                         unsigned char* const sc = reinterpret_cast<unsigned char*>(p.s);
                         if (G == 0) {
                             if (b < 96) bulk_s2g_nc(sc + offsetof(Scratch, part) + b * 12288, sb + SM_Z2, 12288);
                             bulk_s2g(sc + offsetof(Scratch, rows) + (127 - b) * 4608, sb + SM_Z2, 4608);
                         }
                         if (G == 2) {
                             if (YQ == 3) bulk_s2g_nc(sc + offsetof(Scratch, y) + (NCTA * 18432u - c.yp) + b * 13824 + 6912, sb + SM_Z2, 6912);
                             if (YQ) bulk_s2g(sc + offsetof(Scratch, y) + (NCTA * 18432u - c.yp) + b * (4608 * YQ), sb + SM_Z2, YQ == 3 ? 6912 : 4608 * YQ);
                         }
                     }
                     if (!wg_is4<decltype(gi)>()) WPOINT(6 + G, warp == (G >= 7 ? HW : 4 * (G % 3) + 1));
                     if (!wg_is4<decltype(gi)>() && G == 6 && warp == HW) {
                         asm volatile("cp.async.bulk.wait_group 0;\n" ::: "memory");
                         __syncwarp();
                         if (elect_one()) mbar_arrive(bar_v);
                     }
                 };
        if (wg < 4) {
            asm volatile("barrier.cluster.arrive.relaxed.aligned;\n" ::: "memory");
            conv_run(c, pln + wq * 128, gy, hook, [&]() {
                STAMPX(23);
                mbar_wait(bar_x);
                STAMPX(24);
                uint2 xc[4];
                uint32_t xw[4][2];
#pragma unroll
                for (int j = 0; j < 4; j++) xc[j] = lds64(sb + SM_XC + wg * 8192 + j * 2048 + t128 * 16 + odd * 8);
#pragma unroll
                for (int i = 0; i < 8; i++) {
                    const int k = i >> 1, h = i & 1;
                    xw[k][h] = prmt_v(k < 2 ? xc[2 * h].x : xc[2 * h].y, k < 2 ? xc[2 * h + 1].x : xc[2 * h + 1].y, (k & 1) ? 0x7632 : 0x5410);
                }
                const uint32_t ub = mov_v(sb + SM_U + UPAD * 16 + ((tid >> 1) & 1) * ULO_B + (tid >> 2) * 16 + (tid & 1) * 8), tag = ep << 31;
                int it = 0;
                while (min(min((int)(uv0.x ^ tag), (int)(uv0.y ^ tag)), min((int)(uv0.z ^ tag), (int)(uv0.w ^ tag))) < 0x10000) {
                    if (++it > SPIN_LIMIT) TRAP();
                    uv0 = ld_poll(usrc);
                }
                STAMP(8);
                STAMPX(26);
                const float r0 = rcp_approx(fabsf(bf_hi(uv0.x))), r1 = rcp_approx(fabsf(bf_hi(uv0.y))), r2 = rcp_approx(fabsf(bf_hi(uv0.z))), r3 = rcp_approx(fabsf(bf_hi(uv0.w)));
                const uint32_t m[2] = {__byte_perm(uv0.x, uv0.y, 0x5410), __byte_perm(uv0.z, uv0.w, 0x5410)};
                const uint32_t rh[2] = {pack_bf16(r0, r1), pack_bf16(r2, r3)};
                const uint32_t rl[2] = {pack_bf16(r0 - bf_lo(rh[0]), r1 - bf_hi(rh[0])), pack_bf16(r2 - bf_lo(rh[1]), r3 - bf_hi(rh[1]))};
#pragma unroll
                for (int k = 0; k < 4; k++) {
                    const uint32_t u0 = ln_apply(xw[k][0], m[0], rh[0], rl[0]), u1 = ln_apply(xw[k][1], m[1], rh[1], rl[1]);
                    sts64(ub + k * USLOT_B, pack_f16(bf_lo(u0), bf_hi(u0)), pack_f16(bf_lo(u1), bf_hi(u1)));
                }
                STAMPX(29);
                fence_async();
                bar_sync(14, 512);
                STAMP(7);
            });
        } else {
            auto stage = [&]() {
                const uint32_t tag = (ep % 7u + 1u) * 0x10001u;
                int it = 0;
                WPOINT(4, warp == 19);
                while (true) {
                    uv0.x ^= tag; uv0.y ^= tag; uv0.z ^= tag; uv0.w ^= tag; uv1.x ^= tag; uv1.y ^= tag; uv1.z ^= tag; uv1.w ^= tag;
                    if ((((uv0.x | uv0.y | uv0.z) | (uv0.w | uv1.x | uv1.y) | (uv1.z | uv1.w)) & 0x70007u) == 0) break;
                    if (++it > SPIN_LIMIT) TRAP();
                    uv0 = ld_poll(usrc); uv1 = ld_poll(usrc + 512);
                }
                STAMP(8);
                const uint32_t ub = sb + SM_U + UPAD * 16 + 4 * USLOT_B + (t128 & 1) * ULO_B + (t128 >> 1) * 16;
                sts128(ub, uv0.x, uv0.y, uv0.z, uv0.w);
                sts128(ub + 1024, uv1.x, uv1.y, uv1.z, uv1.w);
                fence_async();
                asm volatile("barrier.cluster.arrive.relaxed.aligned;\n" ::: "memory");
                bar_sync(5, 128);
                WPOINT(5, warp == 19);
                STAMP(7);
            };
            stage();
            if (odd) conv_inner(c, pln + wq * 128, gy, sb + SM_RX, hook);
            else conv_outer(c, pln + wq * 128, gy, sb + SM_RX, hook);
        }
        STAMP(10);
    }
    {
    const int lane = lane_v(), tid = 32 * warp + lane, g = lane >> 2, t = lane & 3;
    const uint32_t par = ~ep & 1u;
    bar_sync(0, NWRK);
    STAMP(11);
    uint32_t H[2][4] = {}, U2[2][4] = {};
    auto publish = [&](bool hi, int slot) {
        uint4* rowp = reinterpret_cast<uint4*>(p.s->rows) + slot * 144 + warp * 4 + t;
        stg128(rowp, nzw(hi ? U2[1][0] : U2[0][0]), nzw(hi ? U2[1][1] : U2[0][1]), nzw(hi ? U2[1][2] : U2[0][2]), nzw(hi ? U2[1][3] : U2[0][3]));
        stg128(rowp + 72, nzw(hi ? H[1][0] : H[0][0]), nzw(hi ? H[1][1] : H[0][1]), nzw(hi ? H[1][2] : H[0][2]), nzw(hi ? H[1][3] : H[0][3]));
    };
#define KTOK(k) (int)(((~(k) >> 5) & 0x7f0u) | (((k) >> 1) & 15u))
#define KLATE(k) (((k) & 0x1e0u) < 0xe0u)
#define KSLOT(k, s) (KLATE(k) ? 2 * NCTA + (s) : (int)(((k) >> 8) & 0xffu))
    const uint4* const rsrc = reinterpret_cast<const uint4*>(p.s->rows) + 36 * odd;
    auto gather = [&](uint32_t mine) {
        int it = 0;
        uint32_t mn;
        do {
            mn = 1;
#pragma unroll 1
            for (int r = 0; r < 9; r++) {
                const uint32_t k = __shfl_sync(0xffffffffu, mine, r < 8 ? 4 * r : lane);
                const int row = r < 8 ? r : g, c = r < 8 ? lane : 32 + t;
                asm volatile("cp.async.cg.shared.global [%0], [%1], 16;\n" ::"r"(sb + SM_XS + row * XS_PITCH + c * 16), "l"(rsrc + KSLOT(k, row) * 144 + c) : "memory");
            }
            asm volatile("cp.async.wait_all;\n" ::: "memory");
#pragma unroll 1
            for (int r = 0; r < 9; r++) mn = min(mn, min4(lds128(sb + SM_XS + (r < 8 ? r * XS_PITCH + lane * 16 : g * XS_PITCH + (32 + t) * 16))));
            if (++it > SPIN_LIMIT) TRAP();
        } while (__any_sync(0xffffffffu, mn == 0));
    };
    auto late_rows = [&](auto role) {
        const uint32_t kk = lds32(s_key + (lane & 7) * 4), ep = lds32(s_cnt + 4);
        const bool own = KLATE(kk) && (KTOK(kk) >> 4) == b;
        uint32_t todo = __ballot_sync(0xffffffffu, own) & 0xffu;
        if (decltype(role)::value == 0 && todo) {
#pragma unroll
            for (int hf = 0; hf < 2; hf++) {
                const uint4 h = lds128(sb + SM_U + hf * 9216 + tid * 16);
                const uint2 st = lds64(s_stat + (g + 8 * hf) * 8);
                H[hf][0] = h.x; H[hf][1] = h.y; H[hf][2] = h.z; H[hf][3] = h.w;
#pragma unroll
                for (int k = 0; k < 4; k++) U2[hf][k] = ln_apply(H[hf][k], STAT_M(st), STAT_H(st), STAT_L(st));
            }
#pragma unroll 1
            while (todo) {
                const int s = __ffs(todo) - 1, tk = KTOK(__shfl_sync(0xffffffffu, kk, s));
                todo &= todo - 1;
                if ((tk & 13) == TOK(g)) publish(tk & 2, 2 * NCTA + s);
            }
            __threadfence();
        }
        bar_sync(0, NWRK);
        if (decltype(role)::value == 1) {
            if (lane < NSEL && own) *reinterpret_cast<volatile unsigned*>(p.s->flag + lane) = ep + 1u;
            int it = 0;
            while (__any_sync(0xffffffffu, KLATE(kk) && ld_acquire32(p.s->flag + (lane & 7)) != ep + 1u)) { if (++it > SPIN_LIMIT) TRAP(); }
            gather(__shfl_sync(0xffffffffu, kk, g));
        }
        bar_sync(0, NWRK);
    };
    if (warp < 18) {
        const unsigned char* ys = reinterpret_cast<const unsigned char*>(p.s->y) + (b < 32 * YQ ? (par ^ 1u) * (NCTA * 18432u) : 0u) +
                                  ((P * DM + 32 * warp + 8 * (g >> 1) + (g & 1)) * 64 + odd * 32 + t * 8);
        uint2 yv[4];
        const bool early = b < 64 && warp < 16;
        if (early) {
#pragma unroll
            for (int k = 0; k < 4; k++) yv[k] = ld_poll64(ys + k * 128);
        }
        mbar_wait(bar_v);
        const uint32_t xa = sb + SM_XT + warp * 64 + t * 16;
        const uint4 x0 = lds128(xa + TOK(g) * 1152), x1 = lds128(xa + (TOK(g) + 2) * 1152), dk = lds128(xa + 16 * 1152);
        uint4 wr = make_uint4(0u, 0u, 0u, 0u);
        if (g == 0) wr = lds128(xa + 17 * 1152);
        const uint32_t Z[2][4] = {{x0.x, x0.y, x0.z, x0.w}, {x1.x, x1.y, x1.z, x1.w}}, D4[4] = {dk.x, dk.y, dk.z, dk.w};
#pragma unroll
        for (int hf = 0; hf < 2; hf++) {
            const uint2 st = lds64(s_stat + (g + 8 * hf) * 8);
#pragma unroll
            for (int k = 0; k < 4; k++) U2[hf][k] = hmul2_bf(ln_apply(Z[hf][k], STAT_M(st), STAT_H(st), STAT_L(st)), D4[k]);
        }
        const uint32_t la = pin(sb + SM_LNP + (g * 20 + warp) * 4 + (U2[0][3] & U2[1][3] & (warp >> 8)));
        int it = 0;
        float d[2][4];
        uint32_t mn;
        do {
            if (!early || it) {
#pragma unroll
                for (int k = 0; k < 4; k++) yv[k] = ld_poll64(ys + k * 128);
            }
            if (++it > SPIN_LIMIT) TRAP();
            mn = min(min(min(yv[0].x, yv[0].y), min(yv[1].x, yv[1].y)), min(min(yv[2].x, yv[2].y), min(yv[3].x, yv[3].y)));
#pragma unroll
            for (int k = 0; k < 4; k++) {
                H[0][k] = hadd2_bf(Z[0][k], hadd2_bf(movm(yv[k].x), U2[0][k]));
                H[1][k] = hadd2_bf(Z[1][k], hadd2_bf(movm(yv[k].y), U2[1][k]));
            }
            ln_partial(H, d);
        } while (__any_sync(0xffffffffu, mn == 0));
        STAMP(12);
        if (t == (g >> 1)) {
            stsf(la, (g & 1) ? d[0][3] : d[0][2]); stsf(la + 8 * 80, (g & 1) ? d[1][3] : d[1][2]);
            stsf(la + 16 * 80, (g & 1) ? d[0][1] : d[0][0]); stsf(la + 24 * 80, (g & 1) ? d[1][1] : d[1][0]);
        }
        bar_arrive(6, NWRK);
        STAMP(13);
        bar_sync(7, 608);
        STAMP(14);
#pragma unroll
        for (int hf = 0; hf < 2; hf++) {
            const uint2 st = lds64(s_stat + (g + 8 * hf) * 8);
#pragma unroll
            for (int k = 0; k < 4; k++) U2[hf][k] = ln_apply(H[hf][k], STAT_M(st), STAT_H(st), STAT_L(st));
        }
        {
            float cs[4] = {0.f, 0.f, 0.f, 0.f};
            mma_bf16(cs, U2[0][0], U2[1][0], U2[0][1], U2[1][1], wr.x, wr.y);
            mma_bf16(cs, U2[0][2], U2[1][2], U2[0][3], U2[1][3], wr.z, wr.w);
            if (t == 0) { stsf(la + 32 * 80, cs[0]); stsf(la + 40 * 80, cs[2]); }
            bar_arrive(8, 608);
        }
        bar_sync(9, 608);
        {
            const uint2 best = lds64(s_rank);
            uint32_t todo = ((best.x & 26u) == 2 * TOK(g) ? 2u : 0u) | ((best.y & 26u) == 2 * TOK(g) ? 1u : 0u);
#pragma unroll 1
            while (todo) { publish((todo & 2u ? best.x : best.y) & 4u, 254 - 2 * b + (todo >> 1)); todo &= todo >> 1; }
        }
#pragma unroll
        for (int hf = 0; hf < 2; hf++) {
            sts128(sb + SM_OUT + (TOK(g) + 2 * hf) * (DM * 2) + warp * 64 + t * 16,
                   hadd2_bf(H[hf][0], U2[hf][0]), hadd2_bf(H[hf][1], U2[hf][1]), hadd2_bf(H[hf][2], U2[hf][2]), hadd2_bf(H[hf][3], U2[hf][3]));
            sts128(sb + SM_U + hf * 9216 + tid * 16, H[hf][0], H[hf][1], H[hf][2], H[hf][3]);
        }
        STAMP(15);
        const int mi = lane >> 3, rr = lane & 7;
        const bool gate = warp < 12 && (warp & 3) != 2;
        const int fj = gate ? 3 * (warp >> 2) + min(warp & 3, 2) : (warp < 12 ? warp >> 2 : warp - 9);
        if (gate) {
            uint32_t W[18][4];
            mbar_wait(bar_w);
            const uint32_t aad = sb + SM_WG + (mi & 1) * SM_WU + (rr + 8 * (mi >> 1)) * W_PITCH + fj * 16;
            const uint32_t bad = pin(sb + SM_XS + rr * XS_PITCH + mi * 16);
            bool rare = warp >> 8;
#pragma unroll 1
            do {
                if (rare) late_rows(IC<0>());
#pragma unroll
                for (int k = 0; k < 18; k++) ldsm_x4_t(W[k][0], W[k][1], W[k][2], W[k][3], aad + k * 16 * W_PITCH);
                if (rare) break;
                fence_async();
                STAMP2(17);
                rare = bar_or(11, NWRK, false);
            } while (rare);
            STAMP2(19);
            float c4[2][4] = {};
#pragma unroll
            for (int k = 0; k < 18; k += 2) {
                uint32_t b0, b1, b2, b3;
                ldsm_x4(b0, b1, b2, b3, bad + k * 32);
                mma_bf16(c4[0], W[k][0], W[k][1], W[k][2], W[k][3], b0, b1);
                mma_bf16(c4[1], W[k + 1][0], W[k + 1][1], W[k + 1][2], W[k + 1][3], b2, b3);
            }
            const uint32_t ex = sb + SM_EX + (32 * fj + lane) * 16;
            const float e0 = c4[0][0] + c4[1][0], e1 = c4[0][1] + c4[1][1], e2 = c4[0][2] + c4[1][2], e3 = c4[0][3] + c4[1][3];
            asm volatile("st.async.shared::cluster.mbarrier::complete_tx::bytes.v4.f32 [%0], {%1,%2,%3,%4}, [%5];\n"
                         ::"r"(ex ^ 0x1000000u), "f"(e0), "f"(e1), "f"(e2), "f"(e3), "r"(bar_g ^ 0x1000000u) : "memory");
            STAMP2(20);
            mbar_wait(bar_g);
            const uint4 o = lds128(ex);
            const uint32_t G = pack_bf16(e0 + __uint_as_float(o.x), e1 + __uint_as_float(o.y)), U = pack_bf16(e2 + __uint_as_float(o.z), e3 + __uint_as_float(o.w));
            sts32(sb + SM_GU + (32 * fj + lane) * 4, hmul2_bf(pack_bf16(bf_lo(G) * sigmoid_f(bf_lo(G)), bf_hi(G) * sigmoid_f(bf_hi(G))), U));
            bar_arrive(13, NWRK);
        } else {
            uint32_t W[2][18];
            auto load_wd = [&]() {
                mbar_wait(bar_d);
                const uint32_t base = sb + SM_WD + (4 * fj + (mi & 1)) * 16 + rr * WD_PITCH;
#pragma unroll
                for (int j = 0; j < 2; j++) {
#pragma unroll
                    for (int k = 0; k < 4; k++) ldsm_x4_t(W[j][4 * k], W[j][4 * k + 1], W[j][4 * k + 2], W[j][4 * k + 3], base + j * 32 + (k * 16 + 8 * (mi >> 1)) * WD_PITCH);
                    ldsm_x2_t(W[j][16], W[j][17], base + j * 32 + 64 * WD_PITCH);
                }
            };
            const uint32_t po = pin((((8 * (18 * odd + 2 * fj) + g) * 64 + P) * 16 + t * 4) * 4);
            fence_async();
            STAMP2(17);
            if (bar_or(11, NWRK, false)) late_rows(IC<0>());
            delay(DDLY); load_wd();
            bar_sync(13, NWRK);
            STAMP2(21);
            uint32_t gb[9];
            ldsm_x4_t(gb[0], gb[1], gb[2], gb[3], sb + SM_GU + lane * 16);
            ldsm_x4_t(gb[4], gb[5], gb[6], gb[7], sb + SM_GU + 512 + lane * 16);
            ldsm_x1_t(gb[8], sb + SM_GU + 1024 + lane * 16);
            float c4[2][4] = {}, d4[2][4] = {};
#pragma unroll
            for (int k = 0; k < 4; k += 2)
#pragma unroll
                for (int j = 0; j < 2; j++) {
                    mma_bf16(c4[j], W[j][4 * k], W[j][4 * k + 1], W[j][4 * k + 2], W[j][4 * k + 3], gb[2 * k], gb[2 * k + 1]);
                    mma_bf16(d4[j], W[j][4 * k + 4], W[j][4 * k + 5], W[j][4 * k + 6], W[j][4 * k + 7], gb[2 * k + 2], gb[2 * k + 3]);
                }
#pragma unroll
            for (int j = 0; j < 2; j++) mma_bf16_k8(c4[j], W[j][16], W[j][17], gb[8]);
#pragma unroll
            for (int j = 0; j < 2; j++)
                stg128(reinterpret_cast<unsigned char*>(p.s->part) + po + j * 32768, __float_as_uint(c4[j][0] + d4[j][0]) | 1u, __float_as_uint(c4[j][1] + d4[j][1]) | 1u,
                       __float_as_uint(c4[j][2] + d4[j][2]) | 1u, __float_as_uint(c4[j][3] + d4[j][3]) | 1u);
        }
        STAMP2(22);
    } else if (warp == 18) {
        const uint4* const ksrc = reinterpret_cast<const uint4*>(p.s->key3) + pin(2 * lane);
        const unsigned char* const rl = reinterpret_cast<const unsigned char*>(rsrc) + pin(lane * 16);
        const uint32_t sa = pin(sb + SM_LNP + lane * 80);
        const uint32_t klo = pin((uint32_t)(127 - b) << 9 | (uint32_t)(15 - ROWTOK(lane & 15)) << 1 | par), ra = pin(sb + SM_LNP + (32 + (lane & 15)) * 80);
        uint4* const kdst = reinterpret_cast<uint4*>(p.s->key3) + pin((lane >> 1) * 2 * NCTA + 2 * b + (lane & 1));
        FIX(ra);
        bar_sync(6, NWRK);
        {
            float mb, rc;
            ln_finish(sum18(sa), lane, mb, rc);
            if (lane < 16) stat_store(s_stat + lane * 8, mb, rc, 0u);
        }
        bar_arrive(7, 608);
        bar_sync(8, 608);
        uint32_t t0;
        {
            const uint32_t bits = __float_as_uint(rbf(sum18(ra)));
            const uint32_t me = ((bits ^ ((uint32_t)((int)bits >> 31) | 0x80000000u)) & 0xffff0000u) | klo;
            const uint32_t k0 = __reduce_max_sync(0xffffffffu, me), k1 = __reduce_max_sync(0xffffffffu, me == k0 ? 0u : me);
            const uint32_t k2 = __reduce_max_sync(0xffffffffu, me >= k1 ? 0u : me);
            if (lane < 2) stg128(kdst, k0 ^ 0x11eu, k1 ^ 0xfeu, k2 ^ 0xdeu, par);
            asm volatile("mov.u32 %0, %%clock;" : "=r"(t0) :: "memory");
            STAMPW(23);
            if (lane == 0) sts64(s_rank, ~k0, ~k1);
            bar_arrive(9, 608);
            sts32(s_k16 + (lane & 15) * 4, me);
            __syncwarp();
            const uint4 v = lds128(s_k16 + (lane & 16) * 2), w = lds128(s_k16 + (lane & 16) * 2 + 16);
            int rank = ((v.x > me) + (v.y > me)) + ((v.z > me) + (v.w > me)) + (((w.x > me) + (w.y > me)) + ((w.z > me) + (w.w > me)));
            rank += __shfl_xor_sync(0xffffffffu, rank, 16);
            if (lane < 16 && rank < 8) p.s->key[8 * b + rank] = (me ^ 0x1eu) | ((8 - rank) << 5);
        }
        uint4 kq[4];
        uint32_t u[4], mine = 0, m;
        int it = 0;
        { uint32_t now; do { asm volatile("mov.u32 %0, %%clock;" : "=r"(now) :: "memory"); } while (now - t0 < KDLY); }
        do {
#pragma unroll
            for (int i = 0; i < 4; i++) kq[i] = ld_poll(ksrc + 64 * i);
            if (++it > SPIN_LIMIT) TRAP();
            uint32_t S[2][4];
#pragma unroll
            for (int i = 0; i < 2; i++) {
                const uint4 &c = kq[2 * i], &d = kq[2 * i + 1];
                const uint32_t m1 = min(c.x, d.x), m2 = max(c.y, d.y);
                S[i][0] = max(c.x, d.x); S[i][1] = max(m1, m2); S[i][2] = min(m1, m2); S[i][3] = min(c.y, d.y);
            }
            const uint32_t a0 = max(S[0][0], S[1][3]), a1 = max(S[0][1], S[1][2]), a2 = max(S[0][2], S[1][1]), a3 = max(S[0][3], S[1][0]);
            const uint32_t b0 = max(a0, a2), b2 = min(a0, a2), b1 = max(a1, a3), b3 = min(a1, a3);
            u[0] = max(b0, b1); u[1] = min(b0, b1); u[2] = max(b2, b3); u[3] = min(b2, b3);
        } while (__any_sync(0xffffffffu, and3(or3(or3(xor_or(kq[0].x, kq[0].y, par), xor_or(kq[0].z, kq[1].x, par), xor_or(kq[1].y, kq[1].z, par)),
                                                  xor_or(kq[2].x, kq[2].y, par), xor_or(kq[2].z, kq[3].x, par)) | xor_or(kq[3].y, kq[3].z, par), 1u, 1u)));
        STAMPW(16);
        uint4 v[9];
#pragma unroll
        for (int r = 0; r < 8; r++) {
            m = __reduce_max_sync(0xffffffffu, u[0]);
            if (u[0] == m) { u[0] = u[1]; u[1] = u[2]; u[2] = u[3]; u[3] = 0; }
            if (g == r) mine = m;
            v[r] = ld_poll(rl + (size_t)((m >> 8) & 0xffu) * 2304u);
        }
        v[8] = ld_poll(reinterpret_cast<const unsigned char*>(rsrc) + (((mine >> 8) & 0xffu) * 2304u + (32 + t) * 16));
        bool again = __any_sync(0xffffffffu, u[0] == 0 || max(max(kq[0].z, kq[1].z), max(kq[2].z, kq[3].z)) > m);
        if (again) {
#pragma unroll 1
            for (int i = 0; i < 8; i++) {
                uint4 k;
                do { k = ld_poll(reinterpret_cast<const uint4*>(p.s->key) + 32 * i + lane); if (++it > SPIN_LIMIT) TRAP(); } while (((k.x ^ par) | (k.y ^ par) | (k.z ^ par) | (k.w ^ par)) & 1u);
                sts128(sb + SM_KEYS + (32 * i + lane) * 16, k.x, k.y, k.z, k.w);
            }
            m = 0xffffffffu;
#pragma unroll 1
            for (int r = 0; r < 8; r++) {
                uint32_t c = 0;
#pragma unroll 2
                for (int i = 0; i < 8; i++) {
                    const uint4 k = lds128(sb + SM_KEYS + (32 * i + lane) * 16);
                    c = max(max(c, k.x < m ? k.x : 0u), max(k.y < m ? k.y : 0u, max(k.z < m ? k.z : 0u, k.w < m ? k.w : 0u)));
                }
                m = __reduce_max_sync(0xffffffffu, c);
                if (g == r) mine = m;
            }
        }
        if (t == 0) sts32(s_key + g * 4, mine);
        uint32_t mn = 1;
#pragma unroll
        for (int r = 0; r < 9; r++) {
            sts128(sb + SM_XS + (r < 8 ? r * XS_PITCH + lane * 16 : g * XS_PITCH + (32 + t) * 16), v[r].x, v[r].y, v[r].z, v[r].w);
            mn = min(mn, min4(v[r]));
        }
        STAMPW(18);
        if (bar_or(11, NWRK, again || mn == 0)) late_rows(IC<1>());
    } else {
        bar_sync(6, NWRK);
        WPOINT(16, true);
        if (WANY(17) || WANY(18)) delay(WDLY);
        WPOINT(17, true);
        if (WANY(18)) delay(WDLY);
        WPOINT(18, true);
        if (bar_or(11, NWRK, false)) late_rows(IC<2>());
        const int tk = KTOK(lds32(s_key + (lane & 7) * 4));
        const uint32_t sel = __reduce_or_sync(0xffffffffu, (tk >> 4) == b ? 1u << (tk & 15) : 0u);
        if (sel ? lane < 16 && !((sel >> lane) & 1u) : lane == 0) bulk_s2g(p.out + (size_t)(16 * b + lane) * DM, sb + SM_OUT + lane * (DM * 2), sel ? DM * 2 : 16 * DM * 2);
        __syncwarp();
    }
    if (warp == 8 || warp >= 18) {
        const int grp = 3 * b + (warp == 8 ? 0 : warp - 17), fsl = 2 * t + ((lane >> 3) & 1), fc = 16 * (grp >> 3) + (grp & 7) + 8 * (lane >> 4);
        const uint32_t fk = lds32(s_key + fsl * 4);
        float hv = 0.f, u2 = 0.f;
        int it = 0;
        if (b < 96) {
            const uint32_t* const fsrc = p.s->rows + KSLOT(fk, fsl) * DM + (fc >> 1);
            uint32_t hw, uw;
            do { hw = ld_poll32(fsrc + 288); uw = ld_poll32(fsrc); if (++it > SPIN_LIMIT) TRAP(); } while (!hw || !uw);
            hv = (fc & 1) ? bf_hi(hw) : bf_lo(hw); u2 = (fc & 1) ? bf_hi(uw) : bf_lo(uw);
        }
        const float rs = rbf(sigmoid_f(__uint_as_float((fk ^ ((uint32_t)((int)~fk >> 31) | 0x80000000u)) & 0xffff0000u)));
        const uint32_t dof = pin(KTOK(fk) * DM + fc), so = pin(grp * 256 + lane);
        if (warp > 17) bar_sync(13, NWRK);
        if (b < 96) {
            delay(warp > 17 ? FDLY : FDLY2);
            const uint4* src = reinterpret_cast<const uint4*>(p.s->part) + so;
            float s0, s1, s2, s3;
            uint32_t ok;
            do {
                uint4 a[8];
#pragma unroll
                for (int i = 0; i < 8; i++) a[i] = ld_poll(src + 32 * i);
                if (++it > SPIN_LIMIT) TRAP();
#define A4(i) and3(and3(a[i].x, a[i].y, a[i].z), and3(a[i].w, a[i + 1].x, a[i + 1].y), a[i + 1].z & a[i + 1].w)
#define S8(f) (((__uint_as_float(a[0].f) + __uint_as_float(a[1].f)) + (__uint_as_float(a[2].f) + __uint_as_float(a[3].f))) + \
               ((__uint_as_float(a[4].f) + __uint_as_float(a[5].f)) + (__uint_as_float(a[6].f) + __uint_as_float(a[7].f))))
                ok = and3(A4(0), A4(2), and3(A4(4), A4(6), 1u));
                s0 = S8(x); s1 = S8(y); s2 = S8(z); s3 = S8(w);
                asm volatile("" : "+f"(s0), "+f"(s1), "+f"(s2), "+f"(s3));
#undef A4
#undef S8
            } while (__any_sync(0xffffffffu, !ok));
            STAMP2(24);
            const bool up = lane & 16, od = lane & 8;
            const float r0 = (up ? s2 : s0) + __shfl_xor_sync(0xffffffffu, up ? s0 : s2, 16), r1 = (up ? s3 : s1) + __shfl_xor_sync(0xffffffffu, up ? s1 : s3, 16);
            float y = (od ? r1 : r0) + __shfl_xor_sync(0xffffffffu, od ? r0 : r1, 8);
            y += __shfl_xor_sync(0xffffffffu, y, 4);
            p.out[dof] = __float2bfloat16_rn(hv + rbf(u2 + rbf(rbf(y) * rs)));
        }
    }
    if (warp == 19) asm volatile("cp.async.bulk.wait_group.read 0;\n" ::: "memory");
    if (b == 0 && tid < 8) *reinterpret_cast<volatile unsigned*>(p.s->hint + tid * 32 + 1) = lds32(s_cnt + 4) + 1u;
    STAMP(25);
    }
}

typedef CUresult (*PFN_tmEncode)(CUtensorMap*, CUtensorMapDataType, cuuint32_t, void*, const cuuint64_t*, const cuuint64_t*, const cuuint32_t*,
                                 const cuuint32_t*, CUtensorMapInterleave, CUtensorMapSwizzle, CUtensorMapL2promotion, CUtensorMapFloatOOBfill);

extern "C" void kernel_launch(void* const* d_in, const int* in_sizes, int n_in, void* d_out, int out_size) {
    Params p;
    p.x = (const bf16*)d_in[0];
    p.lar = (const bf16*)d_in[1];
    p.aim = (const bf16*)d_in[2];
    p.cre = (const bf16*)d_in[3];
    p.cim = (const bf16*)d_in[4];
    p.ldt = (const bf16*)d_in[5];
    p.dsk = (const bf16*)d_in[6];
    p.wr = (const bf16*)d_in[8];
    p.out = (bf16*)d_out;
    static PFN_tmEncode enc = nullptr;
    static void* scratch = nullptr;
    if (!enc) {
        cudaFuncSetAttribute(fused_kernel, cudaFuncAttributeMaxDynamicSharedMemorySize, SMEM_TOTAL);
        void* fn = nullptr;
        cudaDriverEntryPointQueryResult qr;
        cudaGetDriverEntryPoint("cuTensorMapEncodeTiled", &fn, cudaEnableDefault, &qr);
        enc = (PFN_tmEncode)fn;
        cudaGetSymbolAddress(&scratch, g_scratch);
    }
    p.s = (Scratch*)scratch;
    CUtensorMap tm_g, tm_u, tm_d, tm_x;
    const cuuint64_t dims[2] = {FF, DM}, strides[1] = {FF * 2};
    const cuuint32_t box[2] = {72, 48}, es[2] = {1, 1};
    enc(&tm_g, CU_TENSOR_MAP_DATA_TYPE_BFLOAT16, 2, d_in[9], dims, strides, box, es, CU_TENSOR_MAP_INTERLEAVE_NONE, CU_TENSOR_MAP_SWIZZLE_NONE,
        CU_TENSOR_MAP_L2_PROMOTION_NONE, CU_TENSOR_MAP_FLOAT_OOB_FILL_NONE);
    enc(&tm_u, CU_TENSOR_MAP_DATA_TYPE_BFLOAT16, 2, d_in[10], dims, strides, box, es, CU_TENSOR_MAP_INTERLEAVE_NONE, CU_TENSOR_MAP_SWIZZLE_NONE,
        CU_TENSOR_MAP_L2_PROMOTION_NONE, CU_TENSOR_MAP_FLOAT_OOB_FILL_NONE);
    const cuuint64_t ddims[2] = {DM / 2, FF}, dstrides[1] = {DM * 2};
    const cuuint32_t dbox[2] = {WD_PITCH / 4, 8};
    enc(&tm_d, CU_TENSOR_MAP_DATA_TYPE_UINT32, 2, d_in[11], ddims, dstrides, dbox, es, CU_TENSOR_MAP_INTERLEAVE_NONE, CU_TENSOR_MAP_SWIZZLE_NONE,
        CU_TENSOR_MAP_L2_PROMOTION_NONE, CU_TENSOR_MAP_FLOAT_OOB_FILL_NONE);
    const cuuint64_t xdims[4] = {DM, 128, 4, 4}, xstrides[3] = {DM * 8, DM * 2, DM * 1024};
    const cuuint32_t xbox[4] = {8, 128, 4, 2}, xes[4] = {1, 1, 1, 1};
    enc(&tm_x, CU_TENSOR_MAP_DATA_TYPE_BFLOAT16, 4, d_in[0], xdims, xstrides, xbox, xes, CU_TENSOR_MAP_INTERLEAVE_NONE, CU_TENSOR_MAP_SWIZZLE_NONE,
        CU_TENSOR_MAP_L2_PROMOTION_NONE, CU_TENSOR_MAP_FLOAT_OOB_FILL_NONE);
    fused_kernel<<<NCTA, NTHR, SMEM_TOTAL>>>(p, tm_g, tm_u, tm_d, tm_x);
}
```

```cpp
#include <cuda_runtime.h>
#include <cuda.h>
#include <cuda_fp16.h>
#include <cuda_bf16.h>
#include <stdint.h>

#define LSEQ 2048
#define DM 576
#define NST 128
#define FF 4608
#define NSEL 8
#define NCTA 128
#define NTHR 640
#define NWRK 640

typedef __nv_bfloat16 bf16;

#define SM_WG 0
#define SM_WU 41472
#define SM_XC (82944 - 32768)
#define SM_WD 82944
#define W_PITCH 144
#define WD_PITCH 592
#define SM_Z2 (SM_WD + 10240)
#define SM_XT (SM_PL - 18 * 1152)
#define SM_PL (SM_WD + 46080)
#define PL_HALF 1344
#define PLW_B 2624
#define PL_B (4 * PLW_B)
#define SM_U (SM_PL + 5 * PL_B)
#define UPAD 20
#define ULO_B ((UPAD + 128) * 16)
#define USLOT_B (2 * ULO_B)
#define SM_KW (SM_U + 5 * USLOT_B)
#define KW_B 3712
#define KW_PL 1216
#define KW_P 2400
#define KW_H 3440
#define SM_MISC (SM_KW + 5 * KW_B)
#define SM_LC (SM_MISC + 416)
#define SM_LNP (SM_LC + 768)
#define SM_RX (SM_LNP + 3840)
#define SMEM_TOTAL (SM_RX + 3088)
#define TBW PLW_B
#define SM_OUT SM_PL
#define SM_XS (SM_PL + 18432)
#define XS_PITCH 592
#define SM_GU (SM_PL + 23296)
#define SM_EX (SM_PL + 24576)
#define SM_KEYS SM_KW

struct __align__(128) Scratch {
    unsigned hint[8 * 32];
    unsigned flag[32];
    uint32_t key3[NCTA * 8];
    uint32_t key[NCTA * 8];
    uint32_t stat[LSEQ];
    uint32_t uT[64 * (LSEQ / 2)];
    uint32_t y[(NCTA + 96) * DM * 8];
    uint32_t part[288 * 64 * 16];
    uint32_t rows[(2 * NCTA + NSEL) * DM];
};
__device__ Scratch g_scratch;
#define STAMP(i)
#define STAMPX(i)
#define STAMPY(i)

__device__ __forceinline__ float rbf(float x) {
    uint32_t r;
    asm("cvt.rn.bf16x2.f32 %0, %1, %2;\n" : "=r"(r) : "f"(x), "f"(0.f));
    return __uint_as_float(r);
}
__device__ __forceinline__ uint32_t pack_bf16(float lo, float hi) {
    uint32_t r;
    asm("cvt.rn.bf16x2.f32 %0, %1, %2;\n" : "=r"(r) : "f"(hi), "f"(lo));
    return r;
}
__device__ __forceinline__ uint32_t pack_f16(float lo, float hi) {
    uint32_t r;
    asm("cvt.rn.f16x2.f32 %0, %1, %2;\n" : "=r"(r) : "f"(hi), "f"(lo));
    return r;
}
__device__ __forceinline__ uint32_t pack_f16_rz(float lo, float hi) {
    uint32_t r;
    asm("cvt.rz.f16x2.f32 %0, %1, %2;\n" : "=r"(r) : "f"(hi), "f"(lo));
    return r;
}
__device__ __forceinline__ float bf_lo(uint32_t w) { return __uint_as_float(w << 16); }
__device__ __forceinline__ float bf_hi(uint32_t w) { return __uint_as_float(w & 0xffff0000u); }
__device__ __forceinline__ uint32_t hadd2_bf(uint32_t a, uint32_t b) {
    __nv_bfloat162 r = __hadd2_rn(*reinterpret_cast<__nv_bfloat162*>(&a), *reinterpret_cast<__nv_bfloat162*>(&b));
    return *reinterpret_cast<uint32_t*>(&r);
}
__device__ __forceinline__ uint32_t hsub2_bf(uint32_t a, uint32_t b) {
    __nv_bfloat162 r = __hsub2_rn(*reinterpret_cast<__nv_bfloat162*>(&a), *reinterpret_cast<__nv_bfloat162*>(&b));
    return *reinterpret_cast<uint32_t*>(&r);
}
__device__ __forceinline__ uint32_t hmul2_bf(uint32_t a, uint32_t b) {
    __nv_bfloat162 r = __hmul2_rn(*reinterpret_cast<__nv_bfloat162*>(&a), *reinterpret_cast<__nv_bfloat162*>(&b));
    return *reinterpret_cast<uint32_t*>(&r);
}
__device__ __forceinline__ uint32_t hfma2_bf(uint32_t a, uint32_t b, uint32_t c) { uint32_t r; asm("fma.rn.bf16x2 %0, %1, %2, %3;\n" : "=r"(r) : "r"(a), "r"(b), "r"(c)); return r; }
__device__ __forceinline__ uint32_t hmul2(uint32_t a, uint32_t b) { uint32_t r; asm("mul.rn.f16x2 %0, %1, %2;\n" : "=r"(r) : "r"(a), "r"(b)); return r; }
__device__ __forceinline__ uint32_t hadd2(uint32_t a, uint32_t b) { uint32_t r; asm("add.rn.f16x2 %0, %1, %2;\n" : "=r"(r) : "r"(a), "r"(b)); return r; }
__device__ __forceinline__ uint32_t hfma2(uint32_t a, uint32_t b, uint32_t c) { uint32_t r; asm("fma.rn.f16x2 %0, %1, %2, %3;\n" : "=r"(r) : "r"(a), "r"(b), "r"(c)); return r; }
__device__ __forceinline__ uint32_t hfms2(uint32_t a, uint32_t b, uint32_t c) {
    uint32_t r;
    asm("{\n.reg .b32 n;\nneg.f16x2 n, %2;\nfma.rn.f16x2 %0, %1, n, %3;\n}\n" : "=r"(r) : "r"(a), "r"(b), "r"(c));
    return r;
}
__device__ __forceinline__ uint32_t nzw(uint32_t w) { uint32_t r; asm("max.u32 %0, %1, 1;\n" : "=r"(r) : "r"(w)); return r; }
__device__ __forceinline__ uint32_t nzf(float f) { const uint32_t w = __float_as_uint(f); return w ? w : 0x80000000u; }
__device__ __forceinline__ uint32_t smem_u32(const void* p) { return (uint32_t)__cvta_generic_to_shared(p); }
__device__ __forceinline__ uint32_t lds32(uint32_t addr) {
    uint32_t v;
    asm volatile("ld.shared.u32 %0, [%1];\n" : "=r"(v) : "r"(addr) : "memory");
    return v;
}
__device__ __forceinline__ uint32_t lds16(uint32_t addr) {
    unsigned short v;
    asm volatile("ld.shared.u16 %0, [%1];\n" : "=h"(v) : "r"(addr) : "memory");
    return v;
}
__device__ __forceinline__ uint2 lds64(uint32_t addr) {
    uint2 v;
    asm volatile("ld.shared.v2.u32 {%0,%1}, [%2];\n" : "=r"(v.x), "=r"(v.y) : "r"(addr) : "memory");
    return v;
}
__device__ __forceinline__ uint4 lds128(uint32_t addr) {
    uint4 v;
    asm volatile("ld.shared.v4.u32 {%0,%1,%2,%3}, [%4];\n" : "=r"(v.x), "=r"(v.y), "=r"(v.z), "=r"(v.w) : "r"(addr) : "memory");
    return v;
}
__device__ __forceinline__ float ldsf(uint32_t addr) { return __uint_as_float(lds32(addr)); }
__device__ __forceinline__ void sts32(uint32_t addr, uint32_t v) { asm volatile("st.shared.u32 [%0], %1;\n" ::"r"(addr), "r"(v) : "memory"); }
__device__ __forceinline__ void sts16(uint32_t addr, uint32_t v) { asm volatile("st.shared.u16 [%0], %1;\n" ::"r"(addr), "h"((unsigned short)v) : "memory"); }
__device__ __forceinline__ void stsf(uint32_t addr, float v) { sts32(addr, __float_as_uint(v)); }
__device__ __forceinline__ void sts64(uint32_t addr, uint32_t a, uint32_t b) { asm volatile("st.shared.v2.u32 [%0], {%1,%2};\n" ::"r"(addr), "r"(a), "r"(b) : "memory"); }
__device__ __forceinline__ void sts64f(uint32_t addr, float a, float b) { sts64(addr, __float_as_uint(a), __float_as_uint(b)); }
__device__ __forceinline__ void sts128(uint32_t addr, uint32_t a, uint32_t b, uint32_t c, uint32_t d) {
    asm volatile("st.shared.v4.u32 [%0], {%1,%2,%3,%4};\n" ::"r"(addr), "r"(a), "r"(b), "r"(c), "r"(d) : "memory");
}
__device__ __forceinline__ void sts128f(uint32_t addr, const float (&v)[4]) {
    sts128(addr, __float_as_uint(v[0]), __float_as_uint(v[1]), __float_as_uint(v[2]), __float_as_uint(v[3]));
}
__device__ __forceinline__ void ldsm_x4(uint32_t& r0, uint32_t& r1, uint32_t& r2, uint32_t& r3, uint32_t addr) {
    asm volatile("ldmatrix.sync.aligned.m8n8.x4.shared.b16 {%0,%1,%2,%3}, [%4];\n"
                 : "=r"(r0), "=r"(r1), "=r"(r2), "=r"(r3) : "r"(addr) : "memory");
}
__device__ __forceinline__ void ldsm_x4_t(uint32_t& r0, uint32_t& r1, uint32_t& r2, uint32_t& r3, uint32_t addr) {
    asm volatile("ldmatrix.sync.aligned.m8n8.x4.trans.shared.b16 {%0,%1,%2,%3}, [%4];\n"
                 : "=r"(r0), "=r"(r1), "=r"(r2), "=r"(r3) : "r"(addr) : "memory");
}
__device__ __forceinline__ void ldsm_x2_t(uint32_t& r0, uint32_t& r1, uint32_t addr) {
    asm volatile("ldmatrix.sync.aligned.m8n8.x2.trans.shared.b16 {%0,%1}, [%2];\n" : "=r"(r0), "=r"(r1) : "r"(addr) : "memory");
}
__device__ __forceinline__ void ldsm_x1_t(uint32_t& r0, uint32_t addr) {
    asm volatile("ldmatrix.sync.aligned.m8n8.x1.trans.shared.b16 {%0}, [%1];\n" : "=r"(r0) : "r"(addr) : "memory");
}
__device__ __forceinline__ void stsm_x4(uint32_t addr, uint32_t r0, uint32_t r1, uint32_t r2, uint32_t r3) {
    asm volatile("stmatrix.sync.aligned.m8n8.x4.shared.b16 [%0], {%1,%2,%3,%4};\n" ::"r"(addr), "r"(r0), "r"(r1), "r"(r2), "r"(r3) : "memory");
}
__device__ __forceinline__ void stsm_x4_t(uint32_t addr, uint32_t r0, uint32_t r1, uint32_t r2, uint32_t r3) {
    asm volatile("stmatrix.sync.aligned.m8n8.x4.trans.shared.b16 [%0], {%1,%2,%3,%4};\n" ::"r"(addr), "r"(r0), "r"(r1), "r"(r2), "r"(r3) : "memory");
}
__device__ __forceinline__ uint32_t movm(uint32_t a) {
    uint32_t d;
    asm volatile("movmatrix.sync.aligned.m8n8.trans.b16 %0, %1;\n" : "=r"(d) : "r"(a));
    return d;
}
__device__ __forceinline__ void mma_f16(float (&c)[4], uint32_t a0, uint32_t a1, uint32_t a2, uint32_t a3, uint32_t b0, uint32_t b1) {
    asm volatile(
        "mma.sync.aligned.m16n8k16.row.col.f32.f16.f16.f32 {%0,%1,%2,%3}, {%4,%5,%6,%7}, {%8,%9}, {%0,%1,%2,%3};\n"
        : "+f"(c[0]), "+f"(c[1]), "+f"(c[2]), "+f"(c[3])
        : "r"(a0), "r"(a1), "r"(a2), "r"(a3), "r"(b0), "r"(b1));
}
__device__ __forceinline__ void mma_bf16(float (&c)[4], uint32_t a0, uint32_t a1, uint32_t a2, uint32_t a3, uint32_t b0, uint32_t b1) {
    asm volatile(
        "mma.sync.aligned.m16n8k16.row.col.f32.bf16.bf16.f32 {%0,%1,%2,%3}, {%4,%5,%6,%7}, {%8,%9}, {%0,%1,%2,%3};\n"
        : "+f"(c[0]), "+f"(c[1]), "+f"(c[2]), "+f"(c[3])
        : "r"(a0), "r"(a1), "r"(a2), "r"(a3), "r"(b0), "r"(b1));
}
__device__ __forceinline__ void mma_bf16_k8(float (&c)[4], uint32_t a0, uint32_t a1, uint32_t b0) {
    asm volatile("mma.sync.aligned.m16n8k8.row.col.f32.bf16.bf16.f32 {%0,%1,%2,%3}, {%4,%5}, {%6}, {%0,%1,%2,%3};\n"
                 : "+f"(c[0]), "+f"(c[1]), "+f"(c[2]), "+f"(c[3]) : "r"(a0), "r"(a1), "r"(b0));
}
__device__ __forceinline__ void bar_sync(int id, int n) { asm volatile("bar.sync %0, %1;\n" ::"r"(id), "r"(n) : "memory"); }
__device__ __forceinline__ void bar_arrive(int id, int n) { asm volatile("bar.arrive %0, %1;\n" ::"r"(id), "r"(n) : "memory"); }
__device__ __forceinline__ bool bar_or(int id, int n, bool v) {
    uint32_t r;
    asm volatile("{\n.reg .pred p, q;\nsetp.ne.u32 p, %3, 0;\nbar.red.or.pred q, %1, %2, p;\nselp.u32 %0, 1, 0, q;\n}\n" : "=r"(r) : "r"(id), "r"(n), "r"((uint32_t)v) : "memory");
    return r;
}
__device__ __forceinline__ uint32_t and3(uint32_t a, uint32_t b, uint32_t c) { uint32_t r; asm("lop3.b32 %0, %1, %2, %3, 0x80;\n" : "=r"(r) : "r"(a), "r"(b), "r"(c)); return r; }
__device__ __forceinline__ uint32_t or3(uint32_t a, uint32_t b, uint32_t c) { uint32_t r; asm("lop3.b32 %0, %1, %2, %3, 0xfe;\n" : "=r"(r) : "r"(a), "r"(b), "r"(c)); return r; }
__device__ __forceinline__ uint32_t min3(uint32_t a, uint32_t b, uint32_t c) { uint32_t r; asm("{\n.reg .u32 t;\nmin.u32 t, %2, %3;\nmin.u32 %0, %1, t;\n}\n" : "=r"(r) : "r"(a), "r"(b), "r"(c)); return r; }
__device__ __forceinline__ uint32_t xor_or(uint32_t a, uint32_t b, uint32_t c) { uint32_t r; asm("lop3.b32 %0, %1, %2, %3, 0x7e;\n" : "=r"(r) : "r"(a), "r"(b), "r"(c)); return r; }
__device__ __forceinline__ uint32_t pin(uint32_t v) { uint32_t r; asm volatile("shfl.sync.bfly.b32 %0, %1, 0, 0x1f, 0xffffffff;\n" : "=r"(r) : "r"(v) : "memory"); return r; }
__device__ __forceinline__ uint4 ld_poll(const void* p) {
    uint4 v;
    asm volatile("ld.relaxed.gpu.global.v4.u32 {%0,%1,%2,%3}, [%4];\n" : "=r"(v.x), "=r"(v.y), "=r"(v.z), "=r"(v.w) : "l"(p) : "memory");
    return v;
}
__device__ __forceinline__ uint2 ld_poll64(const void* p) {
    uint2 v;
    asm volatile("ld.relaxed.gpu.global.v2.u32 {%0,%1}, [%2];\n" : "=r"(v.x), "=r"(v.y) : "l"(p) : "memory");
    return v;
}
__device__ __forceinline__ uint32_t ld_poll32(const void* p) {
    uint32_t v;
    asm volatile("ld.relaxed.gpu.global.u32 %0, [%1];\n" : "=r"(v) : "l"(p) : "memory");
    return v;
}
__device__ __forceinline__ uint32_t ld_acquire32(const void* p) {
    uint32_t v;
    asm volatile("ld.acquire.gpu.global.u32 %0, [%1];\n" : "=r"(v) : "l"(p) : "memory");
    return v;
}
__device__ __forceinline__ uint4 ldg128(const void* p) {
    uint4 v;
    asm volatile("ld.global.nc.v4.u32 {%0,%1,%2,%3}, [%4];\n" : "=r"(v.x), "=r"(v.y), "=r"(v.z), "=r"(v.w) : "l"(p));
    return v;
}
__device__ __forceinline__ uint2 ldg64(const void* p) {
    uint2 v;
    asm volatile("ld.global.nc.v2.u32 {%0,%1}, [%2];\n" : "=r"(v.x), "=r"(v.y) : "l"(p));
    return v;
}
__device__ __forceinline__ uint32_t ldg16(const void* p) {
    uint32_t v;
    asm volatile("ld.global.nc.u16 %0, [%1];\n" : "=r"(v) : "l"(p));
    return v;
}
__device__ __forceinline__ uint4 ldo128(const void* p) {
    uint4 v;
    asm volatile("ld.relaxed.cta.global.v4.u32 {%0,%1,%2,%3}, [%4];\n" : "=r"(v.x), "=r"(v.y), "=r"(v.z), "=r"(v.w) : "l"(p) : "memory");
    return v;
}
__device__ __forceinline__ uint2 ldo64(const void* p) {
    uint2 v;
    asm volatile("ld.relaxed.cta.global.v2.u32 {%0,%1}, [%2];\n" : "=r"(v.x), "=r"(v.y) : "l"(p) : "memory");
    return v;
}
__device__ __forceinline__ uint32_t ldo16(const void* p) {
    uint32_t v;
    asm volatile("ld.relaxed.cta.global.u16 %0, [%1];\n" : "=r"(v) : "l"(p) : "memory");
    return v;
}
__device__ __forceinline__ void stg128(void* p, uint32_t a, uint32_t b, uint32_t c, uint32_t d) {
    asm volatile("st.global.v4.u32 [%0], {%1,%2,%3,%4};\n" ::"l"(p), "r"(a), "r"(b), "r"(c), "r"(d) : "memory");
}
__device__ __forceinline__ void stg64(void* p, uint32_t a, uint32_t b) { asm volatile("st.global.v2.u32 [%0], {%1,%2};\n" ::"l"(p), "r"(a), "r"(b) : "memory"); }
__device__ __forceinline__ uint32_t min4(const uint4& v) { return min(min(v.x, v.y), min(v.z, v.w)); }
#define SPIN_LIMIT (1 << 21)
#define TRAP() __trap()
__device__ __forceinline__ void mbar_init(uint32_t bar, uint32_t cnt) { asm volatile("mbarrier.init.shared::cta.b64 [%0], %1;\n" ::"r"(bar), "r"(cnt) : "memory"); }
__device__ __forceinline__ void mbar_expect(uint32_t bar, uint32_t bytes) {
    asm volatile("mbarrier.arrive.expect_tx.shared::cta.b64 _, [%0], %1;\n" ::"r"(bar), "r"(bytes) : "memory");
}
__device__ __forceinline__ void mbar_arrive(uint32_t bar) { asm volatile("mbarrier.arrive.shared::cta.b64 _, [%0];\n" ::"r"(bar) : "memory"); }
__device__ __forceinline__ void mbar_wait_cluster(uint32_t bar) {
    asm volatile(
        "{\n.reg .pred p;\n"
        "W_%=:\n"
        "mbarrier.try_wait.parity.acquire.cluster.shared::cta.b64 p, [%0], 0;\n"
        "@!p bra W_%=;\n}\n" ::"r"(bar) : "memory");
}
__device__ __forceinline__ void mbar_wait(uint32_t bar) {
    asm volatile(
        "{\n.reg .pred p;\n"
        "W_%=:\n"
        "mbarrier.try_wait.parity.shared::cta.b64 p, [%0], 0;\n"
        "@!p bra W_%=;\n}\n" ::"r"(bar) : "memory");
}
__device__ __forceinline__ void mbar_wait1(uint32_t bar) {
    asm volatile(
        "{\n.reg .pred p;\n"
        "W_%=:\n"
        "mbarrier.try_wait.parity.shared::cta.b64 p, [%0], 1;\n"
        "@!p bra W_%=;\n}\n" ::"r"(bar) : "memory");
}
__device__ __forceinline__ bool mbar_test(uint32_t bar) {
    uint32_t r;
    asm volatile("{\n.reg .pred p;\nmbarrier.test_wait.parity.shared::cta.b64 p, [%1], 0;\nselp.u32 %0, 1, 0, p;\n}\n" : "=r"(r) : "r"(bar) : "memory");
    return __any_sync(0xffffffffu, r);
}
__device__ __forceinline__ void bulk_g2s(uint32_t dst, const void* src, uint32_t bytes, uint32_t bar) {
    asm volatile("cp.async.bulk.shared::cluster.global.mbarrier::complete_tx::bytes [%0], [%1], %2, [%3];\n" ::"r"(dst), "l"(src), "r"(bytes), "r"(bar) : "memory");
}
__device__ __forceinline__ void bulk_s2g(void* dst, uint32_t src, uint32_t bytes) {
    asm volatile("cp.async.bulk.global.shared::cta.bulk_group [%0], [%1], %2;\ncp.async.bulk.commit_group;\n" ::"l"(dst), "r"(src), "r"(bytes) : "memory");
}
__device__ __forceinline__ void bulk_s2g_nc(void* dst, uint32_t src, uint32_t bytes) {
    asm volatile("cp.async.bulk.global.shared::cta.bulk_group [%0], [%1], %2;\n" ::"l"(dst), "r"(src), "r"(bytes) : "memory");
}
__device__ __forceinline__ void tma_2d(uint32_t dst, const CUtensorMap* tm, int c0, int c1, uint32_t bar) {
    asm volatile("cp.async.bulk.tensor.2d.shared::cluster.global.mbarrier::complete_tx::bytes [%0], [%1, {%3, %4}], [%2];\n"
                 ::"r"(dst), "l"(tm), "r"(bar), "r"(c0), "r"(c1) : "memory");
}
__device__ __forceinline__ void tma_4d(uint32_t dst, const CUtensorMap* tm, int c0, int c3, uint32_t bar) {
    asm volatile("cp.async.bulk.tensor.4d.shared::cluster.global.mbarrier::complete_tx::bytes [%0], [%1, {%3, %4, %4, %5}], [%2];\n"
                 ::"r"(dst), "l"(tm), "r"(bar), "r"(c0), "r"(0), "r"(c3) : "memory");
}
__device__ __forceinline__ void tma_4d_mc(uint32_t dst, const CUtensorMap* tm, int c0, int c3, uint32_t bar) {
    asm volatile("cp.async.bulk.tensor.4d.shared::cluster.global.mbarrier::complete_tx::bytes.multicast::cluster [%0], [%1, {%3, %4, %4, %5}], [%2], %6;\n"
                 ::"r"(dst), "l"(tm), "r"(bar), "r"(c0), "r"(0), "r"(c3), "h"((unsigned short)3) : "memory");
}
__device__ __forceinline__ void l2_prefetch(const void* src, uint32_t bytes) {
    asm volatile("cp.async.bulk.prefetch.L2.global [%0], %1;\n" ::"l"(src), "r"(bytes) : "memory");
}
__device__ __forceinline__ bool elect_one() {
    uint32_t r;
    asm volatile("{\n.reg .pred p;\nelect.sync _|p, 0xffffffff;\nselp.u32 %0, 1, 0, p;\n}\n" : "=r"(r));
    return r;
}
__device__ __forceinline__ void delay(uint32_t clks) {
    uint32_t t0, t1;
    asm volatile("mov.u32 %0, %%clock;" : "=r"(t0) :: "memory");
    do { asm volatile("mov.u32 %0, %%clock;" : "=r"(t1) :: "memory"); } while (t1 - t0 < clks);
}
__device__ __forceinline__ void fence_async() { asm volatile("fence.proxy.async.shared::cta;\n" ::: "memory"); }

__device__ __forceinline__ float2 cmul(float2 a, float2 b) {
    return make_float2(fmaf(a.x, b.x, -a.y * b.y), fmaf(a.x, b.y, a.y * b.x));
}
__device__ __forceinline__ float2 csq(float2 a) {
    float p = a.x * a.y;
    return make_float2(fmaf(a.x, a.x, -a.y * a.y), p + p);
}
__device__ __forceinline__ float ex2_approx(float x) { float r; asm("ex2.approx.ftz.f32 %0, %1;\n" : "=f"(r) : "f"(x)); return r; }
__device__ __forceinline__ float exp_bf(float x) { return rbf(ex2_approx(__fmul_ru(x, 1.4426950408889634f))); }
__device__ __forceinline__ float2 cexp_e(float lr2, float li, float e) {
    const float m = ex2_approx(lr2 * e);
    return make_float2(m * __cosf(li * e), m * __sinf(li * e));
}
__device__ __forceinline__ float rcp_approx(float x) { float r; asm("rcp.approx.ftz.f32 %0, %1;\n" : "=f"(r) : "f"(x)); return r; }
__device__ __forceinline__ float sigmoid_f(float x) { return rcp_approx(1.0f + ex2_approx(x * -1.4426950408889634f)); }
__device__ __forceinline__ float sqrt_approx(float x) { float r; asm("sqrt.approx.ftz.f32 %0, %1;\n" : "=f"(r) : "f"(x)); return r; }

__device__ __forceinline__ void wg_fence() { asm volatile("wgmma.fence.sync.aligned;\n" ::: "memory"); }
__device__ __forceinline__ void wg_commit() { asm volatile("wgmma.commit_group.sync.aligned;\n" ::: "memory"); }
__device__ __forceinline__ void wg_wait0() { asm volatile("wgmma.wait_group.sync.aligned 0;\n" ::: "memory"); }
template <int T> __device__ __forceinline__ void wg_mma(float (&acc)[16][4], const uint32_t* a, uint64_t desc);
template <int T> __device__ __forceinline__ void wg_first(float (&acc)[16][4], const uint32_t* a, uint64_t desc);
template <> __device__ __forceinline__ void wg_mma<0>(float (&acc)[16][4], const uint32_t* a, uint64_t desc) {
    asm volatile("wgmma.mma_async.sync.aligned.m64n128k16.f32.f16.f16 {%0,%1,%2,%3,%4,%5,%6,%7,%8,%9,%10,%11,%12,%13,%14,%15,%16,%17,%18,%19,%20,%21,%22,%23,%24,%25,%26,%27,%28,%29,%30,%31,%32,%33,%34,%35,%36,%37,%38,%39,%40,%41,%42,%43,%44,%45,%46,%47,%48,%49,%50,%51,%52,%53,%54,%55,%56,%57,%58,%59,%60,%61,%62,%63}, {%64,%65,%66,%67}, %68, 1, 1, 1, 0;\n"
                 : "+f"(acc[0][0]), "+f"(acc[0][1]), "+f"(acc[0][2]), "+f"(acc[0][3]), "+f"(acc[1][0]), "+f"(acc[1][1]), "+f"(acc[1][2]), "+f"(acc[1][3]), "+f"(acc[2][0]), "+f"(acc[2][1]), "+f"(acc[2][2]), "+f"(acc[2][3]), "+f"(acc[3][0]), "+f"(acc[3][1]), "+f"(acc[3][2]), "+f"(acc[3][3]), "+f"(acc[4][0]), "+f"(acc[4][1]), "+f"(acc[4][2]), "+f"(acc[4][3]), "+f"(acc[5][0]), "+f"(acc[5][1]), "+f"(acc[5][2]), "+f"(acc[5][3]), "+f"(acc[6][0]), "+f"(acc[6][1]), "+f"(acc[6][2]), "+f"(acc[6][3]), "+f"(acc[7][0]), "+f"(acc[7][1]), "+f"(acc[7][2]), "+f"(acc[7][3]), "+f"(acc[8][0]), "+f"(acc[8][1]), "+f"(acc[8][2]), "+f"(acc[8][3]), "+f"(acc[9][0]), "+f"(acc[9][1]), "+f"(acc[9][2]), "+f"(acc[9][3]), "+f"(acc[10][0]), "+f"(acc[10][1]), "+f"(acc[10][2]), "+f"(acc[10][3]), "+f"(acc[11][0]), "+f"(acc[11][1]), "+f"(acc[11][2]), "+f"(acc[11][3]), "+f"(acc[12][0]), "+f"(acc[12][1]), "+f"(acc[12][2]), "+f"(acc[12][3]), "+f"(acc[13][0]), "+f"(acc[13][1]), "+f"(acc[13][2]), "+f"(acc[13][3]), "+f"(acc[14][0]), "+f"(acc[14][1]), "+f"(acc[14][2]), "+f"(acc[14][3]), "+f"(acc[15][0]), "+f"(acc[15][1]), "+f"(acc[15][2]), "+f"(acc[15][3])
                 : "r"(a[0]), "r"(a[1]), "r"(a[2]), "r"(a[3]), "l"(desc));
}
template <> __device__ __forceinline__ void wg_mma<2>(float (&acc)[16][4], const uint32_t* a, uint64_t desc) {
    asm volatile("wgmma.mma_async.sync.aligned.m64n112k16.f32.f16.f16 {%0,%1,%2,%3,%4,%5,%6,%7,%8,%9,%10,%11,%12,%13,%14,%15,%16,%17,%18,%19,%20,%21,%22,%23,%24,%25,%26,%27,%28,%29,%30,%31,%32,%33,%34,%35,%36,%37,%38,%39,%40,%41,%42,%43,%44,%45,%46,%47,%48,%49,%50,%51,%52,%53,%54,%55}, {%56,%57,%58,%59}, %60, 1, 1, 1, 0;\n"
                 : "+f"(acc[2][0]), "+f"(acc[2][1]), "+f"(acc[2][2]), "+f"(acc[2][3]), "+f"(acc[3][0]), "+f"(acc[3][1]), "+f"(acc[3][2]), "+f"(acc[3][3]), "+f"(acc[4][0]), "+f"(acc[4][1]), "+f"(acc[4][2]), "+f"(acc[4][3]), "+f"(acc[5][0]), "+f"(acc[5][1]), "+f"(acc[5][2]), "+f"(acc[5][3]), "+f"(acc[6][0]), "+f"(acc[6][1]), "+f"(acc[6][2]), "+f"(acc[6][3]), "+f"(acc[7][0]), "+f"(acc[7][1]), "+f"(acc[7][2]), "+f"(acc[7][3]), "+f"(acc[8][0]), "+f"(acc[8][1]), "+f"(acc[8][2]), "+f"(acc[8][3]), "+f"(acc[9][0]), "+f"(acc[9][1]), "+f"(acc[9][2]), "+f"(acc[9][3]), "+f"(acc[10][0]), "+f"(acc[10][1]), "+f"(acc[10][2]), "+f"(acc[10][3]), "+f"(acc[11][0]), "+f"(acc[11][1]), "+f"(acc[11][2]), "+f"(acc[11][3]), "+f"(acc[12][0]), "+f"(acc[12][1]), "+f"(acc[12][2]), "+f"(acc[12][3]), "+f"(acc[13][0]), "+f"(acc[13][1]), "+f"(acc[13][2]), "+f"(acc[13][3]), "+f"(acc[14][0]), "+f"(acc[14][1]), "+f"(acc[14][2]), "+f"(acc[14][3]), "+f"(acc[15][0]), "+f"(acc[15][1]), "+f"(acc[15][2]), "+f"(acc[15][3])
                 : "r"(a[0]), "r"(a[1]), "r"(a[2]), "r"(a[3]), "l"(desc));
}
template <> __device__ __forceinline__ void wg_mma<4>(float (&acc)[16][4], const uint32_t* a, uint64_t desc) {
    asm volatile("wgmma.mma_async.sync.aligned.m64n96k16.f32.f16.f16 {%0,%1,%2,%3,%4,%5,%6,%7,%8,%9,%10,%11,%12,%13,%14,%15,%16,%17,%18,%19,%20,%21,%22,%23,%24,%25,%26,%27,%28,%29,%30,%31,%32,%33,%34,%35,%36,%37,%38,%39,%40,%41,%42,%43,%44,%45,%46,%47}, {%48,%49,%50,%51}, %52, 1, 1, 1, 0;\n"
                 : "+f"(acc[4][0]), "+f"(acc[4][1]), "+f"(acc[4][2]), "+f"(acc[4][3]), "+f"(acc[5][0]), "+f"(acc[5][1]), "+f"(acc[5][2]), "+f"(acc[5][3]), "+f"(acc[6][0]), "+f"(acc[6][1]), "+f"(acc[6][2]), "+f"(acc[6][3]), "+f"(acc[7][0]), "+f"(acc[7][1]), "+f"(acc[7][2]), "+f"(acc[7][3]), "+f"(acc[8][0]), "+f"(acc[8][1]), "+f"(acc[8][2]), "+f"(acc[8][3]), "+f"(acc[9][0]), "+f"(acc[9][1]), "+f"(acc[9][2]), "+f"(acc[9][3]), "+f"(acc[10][0]), "+f"(acc[10][1]), "+f"(acc[10][2]), "+f"(acc[10][3]), "+f"(acc[11][0]), "+f"(acc[11][1]), "+f"(acc[11][2]), "+f"(acc[11][3]), "+f"(acc[12][0]), "+f"(acc[12][1]), "+f"(acc[12][2]), "+f"(acc[12][3]), "+f"(acc[13][0]), "+f"(acc[13][1]), "+f"(acc[13][2]), "+f"(acc[13][3]), "+f"(acc[14][0]), "+f"(acc[14][1]), "+f"(acc[14][2]), "+f"(acc[14][3]), "+f"(acc[15][0]), "+f"(acc[15][1]), "+f"(acc[15][2]), "+f"(acc[15][3])
                 : "r"(a[0]), "r"(a[1]), "r"(a[2]), "r"(a[3]), "l"(desc));
}
template <> __device__ __forceinline__ void wg_mma<6>(float (&acc)[16][4], const uint32_t* a, uint64_t desc) {
    asm volatile("wgmma.mma_async.sync.aligned.m64n80k16.f32.f16.f16 {%0,%1,%2,%3,%4,%5,%6,%7,%8,%9,%10,%11,%12,%13,%14,%15,%16,%17,%18,%19,%20,%21,%22,%23,%24,%25,%26,%27,%28,%29,%30,%31,%32,%33,%34,%35,%36,%37,%38,%39}, {%40,%41,%42,%43}, %44, 1, 1, 1, 0;\n"
                 : "+f"(acc[6][0]), "+f"(acc[6][1]), "+f"(acc[6][2]), "+f"(acc[6][3]), "+f"(acc[7][0]), "+f"(acc[7][1]), "+f"(acc[7][2]), "+f"(acc[7][3]), "+f"(acc[8][0]), "+f"(acc[8][1]), "+f"(acc[8][2]), "+f"(acc[8][3]), "+f"(acc[9][0]), "+f"(acc[9][1]), "+f"(acc[9][2]), "+f"(acc[9][3]), "+f"(acc[10][0]), "+f"(acc[10][1]), "+f"(acc[10][2]), "+f"(acc[10][3]), "+f"(acc[11][0]), "+f"(acc[11][1]), "+f"(acc[11][2]), "+f"(acc[11][3]), "+f"(acc[12][0]), "+f"(acc[12][1]), "+f"(acc[12][2]), "+f"(acc[12][3]), "+f"(acc[13][0]), "+f"(acc[13][1]), "+f"(acc[13][2]), "+f"(acc[13][3]), "+f"(acc[14][0]), "+f"(acc[14][1]), "+f"(acc[14][2]), "+f"(acc[14][3]), "+f"(acc[15][0]), "+f"(acc[15][1]), "+f"(acc[15][2]), "+f"(acc[15][3])
                 : "r"(a[0]), "r"(a[1]), "r"(a[2]), "r"(a[3]), "l"(desc));
}
template <> __device__ __forceinline__ void wg_mma<8>(float (&acc)[16][4], const uint32_t* a, uint64_t desc) {
    asm volatile("wgmma.mma_async.sync.aligned.m64n64k16.f32.f16.f16 {%0,%1,%2,%3,%4,%5,%6,%7,%8,%9,%10,%11,%12,%13,%14,%15,%16,%17,%18,%19,%20,%21,%22,%23,%24,%25,%26,%27,%28,%29,%30,%31}, {%32,%33,%34,%35}, %36, 1, 1, 1, 0;\n"
                 : "+f"(acc[8][0]), "+f"(acc[8][1]), "+f"(acc[8][2]), "+f"(acc[8][3]), "+f"(acc[9][0]), "+f"(acc[9][1]), "+f"(acc[9][2]), "+f"(acc[9][3]), "+f"(acc[10][0]), "+f"(acc[10][1]), "+f"(acc[10][2]), "+f"(acc[10][3]), "+f"(acc[11][0]), "+f"(acc[11][1]), "+f"(acc[11][2]), "+f"(acc[11][3]), "+f"(acc[12][0]), "+f"(acc[12][1]), "+f"(acc[12][2]), "+f"(acc[12][3]), "+f"(acc[13][0]), "+f"(acc[13][1]), "+f"(acc[13][2]), "+f"(acc[13][3]), "+f"(acc[14][0]), "+f"(acc[14][1]), "+f"(acc[14][2]), "+f"(acc[14][3]), "+f"(acc[15][0]), "+f"(acc[15][1]), "+f"(acc[15][2]), "+f"(acc[15][3])
                 : "r"(a[0]), "r"(a[1]), "r"(a[2]), "r"(a[3]), "l"(desc));
}
template <> __device__ __forceinline__ void wg_mma<10>(float (&acc)[16][4], const uint32_t* a, uint64_t desc) {
    asm volatile("wgmma.mma_async.sync.aligned.m64n48k16.f32.f16.f16 {%0,%1,%2,%3,%4,%5,%6,%7,%8,%9,%10,%11,%12,%13,%14,%15,%16,%17,%18,%19,%20,%21,%22,%23}, {%24,%25,%26,%27}, %28, 1, 1, 1, 0;\n"
                 : "+f"(acc[10][0]), "+f"(acc[10][1]), "+f"(acc[10][2]), "+f"(acc[10][3]), "+f"(acc[11][0]), "+f"(acc[11][1]), "+f"(acc[11][2]), "+f"(acc[11][3]), "+f"(acc[12][0]), "+f"(acc[12][1]), "+f"(acc[12][2]), "+f"(acc[12][3]), "+f"(acc[13][0]), "+f"(acc[13][1]), "+f"(acc[13][2]), "+f"(acc[13][3]), "+f"(acc[14][0]), "+f"(acc[14][1]), "+f"(acc[14][2]), "+f"(acc[14][3]), "+f"(acc[15][0]), "+f"(acc[15][1]), "+f"(acc[15][2]), "+f"(acc[15][3])
                 : "r"(a[0]), "r"(a[1]), "r"(a[2]), "r"(a[3]), "l"(desc));
}
template <> __device__ __forceinline__ void wg_mma<12>(float (&acc)[16][4], const uint32_t* a, uint64_t desc) {
    asm volatile("wgmma.mma_async.sync.aligned.m64n32k16.f32.f16.f16 {%0,%1,%2,%3,%4,%5,%6,%7,%8,%9,%10,%11,%12,%13,%14,%15}, {%16,%17,%18,%19}, %20, 1, 1, 1, 0;\n"
                 : "+f"(acc[12][0]), "+f"(acc[12][1]), "+f"(acc[12][2]), "+f"(acc[12][3]), "+f"(acc[13][0]), "+f"(acc[13][1]), "+f"(acc[13][2]), "+f"(acc[13][3]), "+f"(acc[14][0]), "+f"(acc[14][1]), "+f"(acc[14][2]), "+f"(acc[14][3]), "+f"(acc[15][0]), "+f"(acc[15][1]), "+f"(acc[15][2]), "+f"(acc[15][3])
                 : "r"(a[0]), "r"(a[1]), "r"(a[2]), "r"(a[3]), "l"(desc));
}
template <> __device__ __forceinline__ void wg_mma<14>(float (&acc)[16][4], const uint32_t* a, uint64_t desc) {
    asm volatile("wgmma.mma_async.sync.aligned.m64n16k16.f32.f16.f16 {%0,%1,%2,%3,%4,%5,%6,%7}, {%8,%9,%10,%11}, %12, 1, 1, 1, 0;\n"
                 : "+f"(acc[14][0]), "+f"(acc[14][1]), "+f"(acc[14][2]), "+f"(acc[14][3]), "+f"(acc[15][0]), "+f"(acc[15][1]), "+f"(acc[15][2]), "+f"(acc[15][3])
                 : "r"(a[0]), "r"(a[1]), "r"(a[2]), "r"(a[3]), "l"(desc));
}
template <> __device__ __forceinline__ void wg_first<0>(float (&acc)[16][4], const uint32_t* a, uint64_t desc) {
    asm volatile("wgmma.mma_async.sync.aligned.m64n128k16.f32.f16.f16 {%0,%1,%2,%3,%4,%5,%6,%7,%8,%9,%10,%11,%12,%13,%14,%15,%16,%17,%18,%19,%20,%21,%22,%23,%24,%25,%26,%27,%28,%29,%30,%31,%32,%33,%34,%35,%36,%37,%38,%39,%40,%41,%42,%43,%44,%45,%46,%47,%48,%49,%50,%51,%52,%53,%54,%55,%56,%57,%58,%59,%60,%61,%62,%63}, {%64,%65,%66,%67}, %68, 0, 1, 1, 0;\n"
                 : "=f"(acc[0][0]), "=f"(acc[0][1]), "=f"(acc[0][2]), "=f"(acc[0][3]), "=f"(acc[1][0]), "=f"(acc[1][1]), "=f"(acc[1][2]), "=f"(acc[1][3]), "=f"(acc[2][0]), "=f"(acc[2][1]), "=f"(acc[2][2]), "=f"(acc[2][3]), "=f"(acc[3][0]), "=f"(acc[3][1]), "=f"(acc[3][2]), "=f"(acc[3][3]), "=f"(acc[4][0]), "=f"(acc[4][1]), "=f"(acc[4][2]), "=f"(acc[4][3]), "=f"(acc[5][0]), "=f"(acc[5][1]), "=f"(acc[5][2]), "=f"(acc[5][3]), "=f"(acc[6][0]), "=f"(acc[6][1]), "=f"(acc[6][2]), "=f"(acc[6][3]), "=f"(acc[7][0]), "=f"(acc[7][1]), "=f"(acc[7][2]), "=f"(acc[7][3]), "=f"(acc[8][0]), "=f"(acc[8][1]), "=f"(acc[8][2]), "=f"(acc[8][3]), "=f"(acc[9][0]), "=f"(acc[9][1]), "=f"(acc[9][2]), "=f"(acc[9][3]), "=f"(acc[10][0]), "=f"(acc[10][1]), "=f"(acc[10][2]), "=f"(acc[10][3]), "=f"(acc[11][0]), "=f"(acc[11][1]), "=f"(acc[11][2]), "=f"(acc[11][3]), "=f"(acc[12][0]), "=f"(acc[12][1]), "=f"(acc[12][2]), "=f"(acc[12][3]), "=f"(acc[13][0]), "=f"(acc[13][1]), "=f"(acc[13][2]), "=f"(acc[13][3]), "=f"(acc[14][0]), "=f"(acc[14][1]), "=f"(acc[14][2]), "=f"(acc[14][3]), "=f"(acc[15][0]), "=f"(acc[15][1]), "=f"(acc[15][2]), "=f"(acc[15][3])
                 : "r"(a[0]), "r"(a[1]), "r"(a[2]), "r"(a[3]), "l"(desc));
}
template <> __device__ __forceinline__ void wg_first<4>(float (&acc)[16][4], const uint32_t* a, uint64_t desc) {
    asm volatile("wgmma.mma_async.sync.aligned.m64n96k16.f32.f16.f16 {%0,%1,%2,%3,%4,%5,%6,%7,%8,%9,%10,%11,%12,%13,%14,%15,%16,%17,%18,%19,%20,%21,%22,%23,%24,%25,%26,%27,%28,%29,%30,%31,%32,%33,%34,%35,%36,%37,%38,%39,%40,%41,%42,%43,%44,%45,%46,%47}, {%48,%49,%50,%51}, %52, 0, 1, 1, 0;\n"
                 : "=f"(acc[4][0]), "=f"(acc[4][1]), "=f"(acc[4][2]), "=f"(acc[4][3]), "=f"(acc[5][0]), "=f"(acc[5][1]), "=f"(acc[5][2]), "=f"(acc[5][3]), "=f"(acc[6][0]), "=f"(acc[6][1]), "=f"(acc[6][2]), "=f"(acc[6][3]), "=f"(acc[7][0]), "=f"(acc[7][1]), "=f"(acc[7][2]), "=f"(acc[7][3]), "=f"(acc[8][0]), "=f"(acc[8][1]), "=f"(acc[8][2]), "=f"(acc[8][3]), "=f"(acc[9][0]), "=f"(acc[9][1]), "=f"(acc[9][2]), "=f"(acc[9][3]), "=f"(acc[10][0]), "=f"(acc[10][1]), "=f"(acc[10][2]), "=f"(acc[10][3]), "=f"(acc[11][0]), "=f"(acc[11][1]), "=f"(acc[11][2]), "=f"(acc[11][3]), "=f"(acc[12][0]), "=f"(acc[12][1]), "=f"(acc[12][2]), "=f"(acc[12][3]), "=f"(acc[13][0]), "=f"(acc[13][1]), "=f"(acc[13][2]), "=f"(acc[13][3]), "=f"(acc[14][0]), "=f"(acc[14][1]), "=f"(acc[14][2]), "=f"(acc[14][3]), "=f"(acc[15][0]), "=f"(acc[15][1]), "=f"(acc[15][2]), "=f"(acc[15][3])
                 : "r"(a[0]), "r"(a[1]), "r"(a[2]), "r"(a[3]), "l"(desc));
}

#define SDLY 900
#define UDLY 1400
#define KDLY 850
#define FDLY 1000
#define FDLY2 400
#define DDLY 300
#define WDLY 500
#define HW 15
#define FIX(v) do { if ((v) == 1u) TRAP(); } while (0)
#define STAMPW(i) STAMPY(i)
#define STAMP2(i) STAMP(i)
#undef STAMPX
#define STAMPX(i)
struct Params {
    const bf16 *x, *lar, *aim, *cre, *cim, *ldt, *dsk;
    Scratch* s;
    const bf16* wr;
    bf16* out;
};

#define TOK(g) (2 * (g) - ((g) & 1))
#define ROWTOK(r) (TOK((r) & 7) + (((r) >> 2) & 2))
__device__ __forceinline__ void ln_partial(const uint32_t (&H)[2][4], float (&d)[2][4]) {
#pragma unroll
    for (int hf = 0; hf < 2; hf++) {
        d[hf][0] = d[hf][1] = d[hf][2] = d[hf][3] = 0.f;
        mma_bf16(d[hf], H[hf][0], 0x3f803f80u, H[hf][1], 0x3f803f80u, H[hf][0], H[hf][1]);
    }
#pragma unroll
    for (int hf = 0; hf < 2; hf++) mma_bf16(d[hf], H[hf][2], 0x3f803f80u, H[hf][3], 0x3f803f80u, H[hf][2], H[hf][3]);
}
__device__ __forceinline__ float sum18(uint32_t a) {
    const uint4 p = lds128(a), q = lds128(a + 16), r = lds128(a + 32), s = lds128(a + 48);
    const uint2 u = lds64(a + 64);
#define F(x) __uint_as_float(x)
    return (((F(p.x) + F(p.y)) + (F(p.z) + F(p.w))) + ((F(q.x) + F(q.y)) + (F(q.z) + F(q.w)))) +
           (((F(r.x) + F(r.y)) + (F(r.z) + F(r.w))) + ((F(s.x) + F(s.y)) + (F(s.z) + F(s.w))) + (F(u.x) + F(u.y)));
#undef F
}
__device__ __forceinline__ void ln_stats(float sm, float sq, float& mb, float& sd) {
    const float m0 = sm * (1.0f / 576.0f);
    const float mean = fmaf(fmaf(-m0, 576.0f, sm), 1.0f / 576.0f, m0);
    const float var = fmaxf(fmaf(-mean, mean, sq * (1.0f / 576.0f)), 0.f);
    mb = rbf(mean);
    sd = rbf(sqrt_approx(rbf(rbf(var) + 1e-5f)));
}
__device__ __forceinline__ void ln_finish(float v, int lane, float& mb, float& rc) {
    const float o = __shfl_xor_sync(0xffffffffu, v, 16);
    float sd;
    ln_stats(lane < 16 ? v : o, lane < 16 ? o : v, mb, sd);
    rc = rcp_approx(sd);
}
__device__ __forceinline__ uint32_t ln_apply(uint32_t w, uint32_t m2, uint32_t rh, uint32_t rl) {
    const uint32_t d = hsub2_bf(w, m2);
    return hfma2_bf(d, rh, hmul2_bf(d, rl));
}
__device__ __forceinline__ void stat_store(uint32_t a, float mb, float rc, uint32_t extra) {
    const float rh = rbf(rc);
    sts64(a, (__float_as_uint(mb) >> 16) | (extra << 16), pack_bf16(rh, rc - rh));
}
#define STAT_M(s) __byte_perm((s).x, (s).x, 0x1010)
#define STAT_H(s) __byte_perm((s).y, (s).y, 0x1010)
#define STAT_L(s) __byte_perm((s).y, (s).y, 0x3232)

__device__ __forceinline__ void hcmul(uint32_t re, uint32_t im, uint32_t zx, uint32_t zy, uint32_t& ore, uint32_t& oim) {
    ore = hfms2(im, zy, hmul2(re, zx));
    oim = hfma2(re, zy, hmul2(im, zx));
}

struct KGen {
    uint32_t A[2][4][4];
    float2 z1, z8, z64, z128, T[9];
};
__device__ __forceinline__ void kgen_setup(KGen& k, float lar, float aim, float dt) {
    const float lr2 = -(exp_bf(lar) * dt) * 1.4426950408889634f, li = aim * dt;
    k.z1 = cexp_e(lr2, li, 1.0f);
    k.z8 = cexp_e(lr2, li, 8.0f);
    k.z64 = cexp_e(lr2, li, 64.0f);
}
__device__ __forceinline__ void kgen_rows(KGen& k, uint32_t tb, int lane) {
    const float2 z8 = k.z8, z64 = k.z64;
    const uint32_t row = tb + lane * 16;
    k.z128 = csq(z64);
    const float2 z16 = csq(z8), z24 = cmul(z16, z8), z32 = csq(z16), z40 = cmul(z32, z8), z48 = csq(z24), z56 = cmul(z32, z24);
    uint32_t re[4], im[4], a[4], b[4];
    re[0] = pack_f16(1.0f, z8.x); im[0] = pack_f16(0.0f, z8.y);
    re[1] = pack_f16(z16.x, z24.x); im[1] = pack_f16(z16.y, z24.y);
    re[2] = pack_f16(z32.x, z40.x); im[2] = pack_f16(z32.y, z40.y);
    re[3] = pack_f16(z48.x, z56.x); im[3] = pack_f16(z48.y, z56.y);
    sts128(row, re[0], re[1], re[2], re[3]);
    sts128(row + 1024, im[0], im[1], im[2], im[3]);
    const uint32_t zx = pack_f16(z64.x, z64.x), zy = pack_f16(z64.y, z64.y), zw = pack_f16(k.z128.x, k.z128.y);
#pragma unroll
    for (int j = 0; j < 4; j++) hcmul(re[j], im[j], zx, zy, a[j], b[j]);
    sts128(row + 512, a[0], a[1], a[2], a[3]);
    sts128(row + 1536, b[0], b[1], b[2], b[3]);
    const int mi = lane >> 3;
    const uint32_t zd = tb + 2048 + mi * 16;
    sts16(tb + 2048 + lane * 2, zw); sts16(tb + 2112 + lane * 2, zw >> 16);
    __syncwarp();
    const uint32_t ad = tb + (lane & 7) * 16 + mi * 512;
    ldsm_x4(a[0], a[1], a[2], a[3], zd);
    ldsm_x4(b[0], b[1], b[2], b[3], zd + 64);
#pragma unroll
    for (int ks = 0; ks < 4; ks++) {
        ldsm_x4_t(k.A[0][ks][0], k.A[0][ks][1], k.A[0][ks][2], k.A[0][ks][3], ad + ks * 128);
        hcmul(k.A[0][ks][0], k.A[0][ks][2], a[ks], b[ks], k.A[1][ks][0], k.A[1][ks][2]);
        hcmul(k.A[0][ks][1], k.A[0][ks][3], a[ks], b[ks], k.A[1][ks][1], k.A[1][ks][3]);
    }
}
__device__ __forceinline__ void kgen_chain(KGen& k, uint32_t cr, uint32_t ci, float cs) {
    k.T[0] = make_float2(bf_lo(cr) * cs, -bf_lo(ci) * cs);
    const float2 y1 = make_float2(k.z1.x, -k.z1.y);
#pragma unroll
    for (int c = 1; c < 8; c++) k.T[c] = cmul(k.T[c - 1], y1);
    k.T[8] = cmul(k.T[0], make_float2(k.z8.x, -k.z8.y));
}
__device__ __forceinline__ void kgen_cols(KGen& k, uint32_t tb, uint32_t t5, int lane) {
    const uint32_t row = tb + lane * 16;
    const float2 (&T)[9] = k.T;
    const float2 y128 = make_float2(k.z128.x, -k.z128.y);
    const float2 y256 = csq(y128), y512 = csq(y256), y768 = cmul(y512, y256), y1024 = csq(y512);
    const float2 c1032 = cmul(T[8], y1024);
    __syncwarp();
    sts128(row, pack_f16(T[0].x, T[1].x), pack_f16(T[2].x, T[3].x), pack_f16(T[4].x, T[5].x), pack_f16(T[6].x, T[7].x));
    sts128(row + 512, pack_f16(T[0].y, T[1].y), pack_f16(T[2].y, T[3].y), pack_f16(T[4].y, T[5].y), pack_f16(T[6].y, T[7].y));
    uint32_t a[4], b[4];
    {
        const uint32_t zx = pack_f16(y256.x, y256.x), zy = pack_f16(y256.y, y256.y);
        hcmul(pack_f16(T[0].x, T[2].x), pack_f16(T[0].y, T[2].y), zx, zy, a[0], b[0]);
        hcmul(pack_f16(T[4].x, T[6].x), pack_f16(T[4].y, T[6].y), zx, zy, a[1], b[1]);
        const uint32_t r04 = pack_f16(T[0].x, T[4].x), i04 = pack_f16(T[0].y, T[4].y);
        hcmul(r04, i04, pack_f16(y512.x, y512.x), pack_f16(y512.y, y512.y), a[2], b[2]);
        hcmul(r04, i04, pack_f16(y768.x, y768.x), pack_f16(y768.y, y768.y), a[3], b[3]);
    }
    sts128(row + 1024, a[0], a[1], a[2], a[3]);
    sts128(row + 1536, b[0], b[1], b[2], b[3]);
    {
        const uint32_t r0 = pack_f16(1.0f, y256.x), i0 = pack_f16(0.0f, y256.y), r1 = pack_f16(y512.x, y768.x), i1 = pack_f16(y512.y, y768.y);
        const uint32_t zx = pack_f16(T[8].x, T[8].x), zy = pack_f16(T[8].y, T[8].y), wx = pack_f16(c1032.x, c1032.x), wy = pack_f16(c1032.y, c1032.y);
        hcmul(r0, i0, zx, zy, a[0], b[0]); hcmul(r1, i1, zx, zy, a[1], b[1]);
        hcmul(r0, i0, wx, wy, a[2], b[2]); hcmul(r1, i1, wx, wy, a[3], b[3]);
    }
    sts128(row + 2048, a[0], a[1], a[2], a[3]);
    sts128(t5 + lane * 16, b[0], b[1], b[2], b[3]);
}
__device__ __forceinline__ void kgen_mma(const KGen& k, uint32_t tb, uint32_t t5, int lane) {
    __syncwarp();
    float acc[2][3][4];
#pragma unroll
    for (int i = 0; i < 6; i++)
#pragma unroll
        for (int j = 0; j < 4; j++) acc[i / 3][i % 3][j] = 0.f;
    const int mi = lane >> 3;
    const uint32_t ro = ((lane & 7) + 8 * (mi >> 1)) * 16, bd = tb + ro + (mi & 1) * 512, b2 = ro + ((mi & 1) ? t5 : tb + 2048);
#pragma unroll
    for (int kp = 0; kp < 2; kp++)
#pragma unroll
        for (int j = 0; j < 3; j++) {
            uint32_t b[4];
            ldsm_x4_t(b[0], b[1], b[2], b[3], (j < 2 ? bd + j * 1024 : b2) + kp * 256);
#pragma unroll
            for (int h = 0; h < 2; h++)
#pragma unroll
                for (int m = 0; m < 2; m++) {
                    const uint32_t (&A)[4] = k.A[m][2 * kp + h];
                    mma_f16(acc[m][j], A[0], A[1], A[2], A[3], b[2 * h], b[2 * h + 1]);
                }
        }
    __syncwarp();
#define PK(j) pack_f16(acc[0][j][0], acc[0][j][1]), pack_f16(acc[0][j][2], acc[0][j][3]), pack_f16(acc[1][j][0], acc[1][j][1]), pack_f16(acc[1][j][2], acc[1][j][3])
    stsm_x4(tb + lane * 16, PK(0));
    stsm_x4(tb + 512 + lane * 16, PK(1));
    stsm_x4_t(tb + 1024 + (lane & 7) * 80 + mi * 16, PK(2));
#undef PK
}
__device__ __forceinline__ uint32_t table_buf(uint32_t sb, int warp) { return sb + SM_PL + warp * TBW; }

__device__ __forceinline__ uint4 lds16x4(uint32_t a) { return make_uint4(lds16(a), lds16(a + TBW), lds16(a + 2 * TBW), lds16(a + 3 * TBW)); }
__device__ __forceinline__ void combine_setup(uint32_t sb, int warp, int lane, uint32_t kw, uint32_t& o, uint32_t& n, uint32_t& d) {
    const int wq = warp & 3;
    const uint32_t a = table_buf(sb, warp & ~3);
    o = wq == 3 ? a + 1024 + 320 + (lane >> 3) * 80 + (lane & 7) * 8 : a + (wq ? 504 + wq * 8 : 0) + lane * 16;
    n = a + 1024 + wq * 80 + lane * 2;
    d = wq < 3 ? kw + (wq == 2 ? KW_P : 32 + wq * 512) + lane * 16 : kw + KW_H + 8 + lane * 8;
}
__device__ __forceinline__ void kgen_combine(int wq, int lane, uint32_t o, uint32_t na, uint32_t d) {
#define S4(f) hadd2(hadd2(u.f, v.f), hadd2(w.f, x.f))
#define H4(v) hadd2(hadd2(v.x, v.y), hadd2(v.z, v.w))
#define BP __byte_perm
    if (wq == 0) {
        const uint4 u = lds128(o), v = lds128(o + TBW), w = lds128(o + 2 * TBW), x = lds128(o + 3 * TBW), nn = lds16x4(na);
        const uint32_t n = H4(nn), k0 = S4(x), k2 = S4(y), k4 = S4(z), k6 = S4(w);
        sts128(d, BP(k0, k0, 0x1032), BP(k0, k2, 0x3254), BP(k2, k2, 0x1032), BP(k2, k4, 0x3254));
        sts128(d + KW_PL, BP(k4, k4, 0x1032), BP(k4, k6, 0x3254), BP(k6, k6, 0x1032), BP(k6, n, 0x3254));
        if (lane == 0) sts32(d + KW_PL - 4, k0 & 0xffffu);
    } else {
        const uint2 u = lds64(o), v = lds64(o + TBW), w = lds64(o + 2 * TBW), x = lds64(o + 3 * TBW);
        uint4 nn = make_uint4(0u, 0u, 0u, 0u), mm = nn;
        if (wq < 3) nn = lds16x4(na);
        if (wq == 2) mm = lds16x4(na + 80);
        const uint32_t k0 = S4(x), k2 = S4(y), n = H4(nn), m = H4(mm);
        if (wq == 3) {
            sts64(d, k0, k2);
        } else if (wq == 1) {
            const uint32_t cc = BP(k2, k2, 0x1010);
            sts128(d, BP(k0, k0, 0x1010), BP(k0, k0, 0x1032), BP(k0, k2, 0x3254), cc);
            sts128(d + KW_PL, cc, BP(k2, k2, 0x1032), BP(k2, n, 0x3254), BP(n, n, 0x1010));
        } else {
            const uint32_t w40 = BP(k0, k0, 0x1032), w84 = BP(k0, n, 0x3254), w0 = BP(k0, k0, 0x1010), w4 = BP(k0, k0, 0x3232), w8 = BP(n, n, 0x1010);
            sts64(d, w40, w84);
            sts64(d + 512, BP(k2, k2, 0x1032), BP(k2, m, 0x3254));
            if (lane < 8) { sts128(d - (KW_P - 1056), w0, w0, w40, w4); sts128(d - (KW_P - 1056 - KW_PL), w4, w84, w8, w8); }
            if (lane == 31) sts16(d + (KW_H + 6 - KW_P - 496), m);
        }
    }
#undef S4
#undef H4
#undef BP
}

__device__ __forceinline__ int c_exponent(const uint2& r, const uint2& i, float dt) {
    const uint32_t mx = __vmaxu2(__vmaxu2(r.x & 0x7fff7fffu, r.y & 0x7fff7fffu), __vmaxu2(i.x & 0x7fff7fffu, i.y & 0x7fff7fffu));
    return __reduce_max_sync(0xffffffffu, max(mx, mx << 16) + (__float_as_uint(dt) & 0x7f800000u)) >> 23;
}

#define YQ 2
#define F0 0
__device__ __forceinline__ int warp_v() { int l; asm volatile("mov.u32 %0, %%tid.x;" : "=r"(l)); return __shfl_sync(0xffffffffu, l >> 5, 0); }
__device__ __forceinline__ int lane_v() { int l; asm volatile("mov.u32 %0, %%laneid;" : "=r"(l)); return l; }
__device__ __forceinline__ uint32_t prmt_v(uint32_t a, uint32_t b, uint32_t s) { uint32_t d; asm volatile("prmt.b32 %0, %1, %2, %3;\n" : "=r"(d) : "r"(a), "r"(b), "r"(s)); return d; }
__device__ __forceinline__ uint32_t mov_v(uint32_t a) { uint32_t d; asm volatile("mov.b32 %0, %1;\n" : "=r"(d) : "r"(a)); return d; }
template <int G>
__device__ __forceinline__ void conv_rename(float (&acc)[16][4]) {
#pragma unroll
    for (int i = G; i < 16; i++)
#pragma unroll
        for (int j = 0; j < 4; j++) { float v; asm volatile("mov.b32 %0, %1;\n" : "=f"(v) : "f"(acc[i][j])); acc[i][j] = v; }
}
struct Conv {
    uint32_t kw;
    uint32_t wa;
    uint32_t pa, s2;
    uint32_t s8;
    uint32_t id;
    uint32_t lc;
    uint32_t fs;
    uint32_t fl, yo;
    uint32_t yp;
    size_t ycopy;
    uint32_t ps;
    uint64_t d0;
    int warp;
};
struct Pk { uint32_t w[4]; };
__device__ __forceinline__ Pk pk2(const float (&u)[4], const float (&v)[4]) {
    Pk r;
    r.w[0] = pack_f16(u[0], u[1]); r.w[1] = pack_f16(u[2], u[3]); r.w[2] = pack_f16(v[0], v[1]); r.w[3] = pack_f16(v[2], v[3]);
    return r;
}
__device__ __forceinline__ void park(uint32_t a, const Pk& v) {
    asm volatile("stmatrix.sync.aligned.m8n8.x4.trans.shared.b16 [%0], {%1,%2,%3,%4};\n" ::"r"(a), "r"(v.w[0]), "r"(v.w[1]), "r"(v.w[2]), "r"(v.w[3]) : "memory");
}
__device__ __forceinline__ void conv_constants(uint32_t lc, int l) {
    const int d = (l >> 2) - 2 * (l & 3);
    const int e = d + 8, r4 = (e + 1 + ((e >> 2) & 1)) >> 2, p4 = (e + (((e - 1) >> 2) & 1)) >> 2;
    const uint32_t s2 = r4 == p4 ? 0x1010u : 0x3210u;
    sts64(lc + l * 8, KW_P + ((r4 - 5) >> 1) * 16 + ((r4 - 5) & 1) * 4, s2 | ((d < 0 ? s2 : 0x7654u) << 16));
    const int lo = (d >= 4) - (d < -3), ho = (d >= 5) - (d < -2), le = (d > 4) - (d < -4), he = (d > 5) - (d < -3);
    sts32(lc + 512 + l * 8, (0x5454u + lo * 0x22 + ho * 0x2200) | ((0x3232u + le * 0x22 + he * 0x2200) << 16));
    const int cc = l >> 2, j = l & 3;
    sts64(lc + 256 + l * 8, (j >> 1) * PL_HALF + (16 + cc) * 16 + (j & 1) * 8, (cc >> 1) * (DM * 64) + (cc & 1) * 32 + j * 8);
}
__device__ __forceinline__ void conv_selectors4(Conv& c) {
    const uint2 v = lds64(c.lc + lane_v() * 8);
    c.pa = v.x; c.s2 = v.y;
}
__device__ __forceinline__ void conv_selectors8(Conv& c) { c.s8 = lds32(c.lc + 512 + lane_v() * 8); }
template <int G, int I0, int I1>
__device__ __forceinline__ void conv_load(const Conv& c, uint32_t (&q)[9]) {
    const int wq = c.warp & 3;
    if (G < 2) {
#pragma unroll
        for (int i = I0; i < I1; i++) q[i] = lds32(c.wa + G * 512 + i * 16);
    } else if (G < 4) {
        const uint32_t a = (G == 2 && wq == 0) ? c.wa + 1024 : c.pa + c.kw + wq * 128 + (G < 2 ? 0 : G - 2) * 512;
#pragma unroll
        for (int i = I0; i < I1; i++) q[i] = lds32(a + i * 16);
    } else {
        const uint4 u = lds128(c.kw + KW_H + (G < 4 ? 0 : G - 4) * 64 + wq * 16);
        const uint2 v = lds64(c.kw + KW_H + (G < 4 ? 0 : G - 4) * 64 + wq * 16 + 16);
        q[0] = u.x; q[1] = u.y; q[2] = u.z; q[3] = u.w; q[4] = v.x; q[5] = v.y;
        if (G == 4 && wq == 0) { q[6] = lds32(c.pa + c.kw + 1024); q[7] = lds32(c.pa + c.kw + 1040); }
    }
}
template <int G, int J0, int J1>
__device__ __forceinline__ void conv_frag(const Conv& c, const uint32_t (&q)[9], uint32_t* a, const Pk& dp) {
    const uint32_t dep = dp.w[0];
    if (G < 4) {
        const uint32_t s = (G < 2 || (G == 2 && (c.warp & 3) == 0)) ? c.id : c.s2;
#pragma unroll
        for (int j = J0; j < J1; j++) {
            uint32_t* o = a + 4 * (j - J0);
            o[0] = prmt_v(q[2 * j + 1], dp.w[0], s); o[1] = prmt_v(q[2 * j + 2], dp.w[1], s); o[2] = prmt_v(q[2 * j], dp.w[2], s); o[3] = prmt_v(q[2 * j + 1], dp.w[3], s);
        }
    } else {
        const uint32_t so = prmt_v(c.s8, dep, c.id), se = prmt_v(c.s8, dep, c.id + 0x22);
#pragma unroll
        for (int j = J0; j < J1; j++) {
            uint32_t* o = a + 4 * (j - J0);
            o[0] = prmt_v(q[j + 1], q[j + 2], se); o[1] = prmt_v(q[j + 1], q[j + 2], so); o[2] = prmt_v(q[j], q[j + 1], so);
            if (G == 4 && j == 0 && (c.warp & 3) == 0) {
                o[2] = prmt_v(q[6], dep, c.s2);
                o[0] = prmt_v(q[7], o[0], c.s2 >> 16);
            }
            o[3] = mov_v(o[0]);
        }
    }
}
template <int G, int J0, int J1>
__device__ __forceinline__ void conv_frag(const Conv& c, const uint32_t (&q)[9], uint32_t* a, float depf) {
    const uint32_t d = __float_as_uint(depf);
    conv_frag<G, J0, J1>(c, q, a, Pk{{d, d, d, d}});
}
template <int G, int T, int J0, int J1>
__device__ __forceinline__ void conv_mma(float (&acc)[16][4], const Conv& c, const uint32_t* a) {
#pragma unroll
    for (int j = J0; j < J1; j++) wg_mma<T>(acc, a + 4 * (j - J0), c.d0 - 8 * (2 * G - T) - j);
}
__device__ __forceinline__ float h_lo(uint32_t w) { return __half2float(__ushort_as_half((unsigned short)(w & 0xffffu))); }
__device__ __forceinline__ float h_hi(uint32_t w) { return __half2float(__ushort_as_half((unsigned short)(w >> 16))); }
__device__ __forceinline__ void flush_setup(Conv& c) {
    const uint2 v = lds64(c.lc + 256 + lane_v() * 8);
    c.fl = v.x; c.yo = v.y;
}
template <int Q>
__device__ __forceinline__ void flush_load(const Conv& c, uint32_t pl, uint2 (&f)[4]) {
#pragma unroll
    for (int w = 0; w < 4; w++) f[w] = lds64(c.fl + pl + (Q & 1) * 512 + w * (PLW_B - 64));
}
template <int Q>
__device__ __forceinline__ void flush_load_first(const Conv& c, uint32_t pl, uint2 (&f)[4], float depf) {
    const uint32_t p = prmt_v(c.fl, __float_as_uint(depf), c.id) + pl + (Q & 1) * 512;
#define LDV64(d, a) asm volatile("ld.volatile.shared.v2.u32 {%0,%1}, [%2];\n" : "=r"(d.x), "=r"(d.y) : "r"(a) : "memory")
    LDV64(f[0], p); LDV64(f[1], p + (PLW_B - 64)); LDV64(f[2], p + 2 * (PLW_B - 64)); LDV64(f[3], p + 3 * (PLW_B - 64));
}
#define FDEP __uint_as_float(f[3].y)
template <int Q, int mode>
__device__ __forceinline__ void conv_flush(const Conv& c, const uint2 (&f)[4], unsigned char* gy, uint32_t rx) {
    const uint32_t a0 = hadd2(f[0].x, f[1].x), a1 = hadd2(f[2].x, f[3].x), b0 = hadd2(f[0].y, f[1].y), b1 = hadd2(f[2].y, f[3].y);
    if (Q > 0 && mode == 1) {
        const uint32_t ra = rx + 16 + (Q > 0 ? Q - 1 : 0) * 1024 + (c.warp & 3) * 256 + lane_v() * 8;
        asm volatile("st.async.shared::cluster.mbarrier::complete_tx::bytes.v2.b32 [%0], {%1,%2}, [%3];\n"
                     ::"r"(ra ^ 0x1000000u), "r"(hadd2(a0, a1)), "r"(hadd2(b0, b1)), "r"((rx + (Q > 1 ? 8 : 0)) ^ 0x1000000u) : "memory");
        return;
    }
    float v0 = h_lo(a0) + h_lo(a1), v1 = h_hi(a0) + h_hi(a1), v2 = h_lo(b0) + h_lo(b1), v3 = h_hi(b0) + h_hi(b1);
    if (Q > 0 && mode == 2) {
        const uint2 o = lds64(rx + 16 + (Q > 0 ? Q - 1 : 0) * 1024 + (c.warp & 3) * 256 + lane_v() * 8);
        v0 += h_lo(o.x); v1 += h_hi(o.x); v2 += h_lo(o.y); v3 += h_hi(o.y);
    }
    const uint32_t lo = hmul2_bf(pack_bf16(v0, v1), c.fs), hi = hmul2_bf(pack_bf16(v2, v3), c.fs);
    stg64(gy + Q * 32 * DM * 32 + (c.yo + (Q < YQ ? c.yp : 0u)), nzw(lo), nzw(hi));
}
template <int I, bool S = false> struct IC { static constexpr int value = I; static constexpr bool shared = S; };
template <class T> __device__ constexpr bool wg_is4() { return T::shared; }
#define SLOT(n) (c.ps + (2 + ((n) & 7)) * 128)
#define GO() do { wg_commit(); __syncwarp(); } while (0)
#define DEP acc[15][3]
template <class FG, class FP, class FN>
__device__ __forceinline__ void conv_head(Conv& c, float (&acc)[16][4], uint32_t (&q)[9], uint32_t (&r)[9], uint32_t* a, FG fg, FP pre, FN next) {
    c.id = 0x3210u + (c.warp >> 8);
    pre();
    conv_load<0, 0, 9>(c, q);
    conv_frag<0, 0, 1>(c, q, a, 0.f);
    wg_fence(); wg_first<0>(acc, a, c.d0); GO();
    park(c.ps, Pk{{0u, 0u, 0u, 0u}});
    wg_wait0();
    conv_frag<0, 1, 2>(c, q, a, DEP);
    wg_fence(); conv_mma<0, 0, 1, 2>(acc, c, a); GO();
    fg(IC<0>());
    wg_wait0();
    conv_frag<0, 2, 3>(c, q, a, DEP);
    wg_fence(); conv_mma<0, 0, 2, 3>(acc, c, a); GO();
    conv_load<1, 0, 5>(c, r);
    wg_wait0();
    conv_frag<0, 3, 4>(c, q, a, DEP);
    wg_fence(); conv_mma<0, 0, 3, 4>(acc, c, a); GO();
    conv_load<1, 5, 9>(c, r);
    fg(IC<1>());
    wg_wait0();
    const Pk k = pk2(acc[0], acc[1]);
    conv_rename<2>(acc);
    conv_frag<1, 0, 2>(c, r, a, k);
    wg_fence(); conv_mma<1, 2, 0, 2>(acc, c, a); GO();
    park(SLOT(0), k);
    next(IC<0>());
    fg(IC<2>());
    wg_wait0();
    conv_frag<1, 2, 4>(c, r, a, DEP);
    wg_fence(); conv_mma<1, 2, 2, 4>(acc, c, a); GO();
    next(IC<1>());
    fg(IC<3>());
    wg_wait0();
}
template <class FG, class FP>
__device__ __forceinline__ void conv_run(Conv& c, uint32_t pl, unsigned char* gy, FG fg, FP pre) {
    float acc[16][4];
    uint32_t q[9], r[9], a[32];
    uint2 f[4];
    const int bid = 1 + (c.warp >> 2);
    conv_head(c, acc, q, r, a, fg, pre, [&](auto i) { if (decltype(i)::value == 0) conv_selectors4(c); else conv_load<2, 0, 9>(c, q); });
    Pk k = pk2(acc[2], acc[3]);
    conv_rename<4>(acc);
    conv_frag<2, 0, 4>(c, q, a, k);
    wg_fence(); conv_mma<2, 4, 0, 4>(acc, c, a); GO();
    park(SLOT(2), k);
    conv_load<3, 0, 9>(c, q);
    flush_setup(c);
    bar_sync(bid, 128);
    fg(IC<4>());
    wg_wait0();
    conv_rename<6>(acc);
    if (F0) { flush_load_first<0>(c, pl, f, DEP); conv_frag<3, 0, 4>(c, q, a, FDEP); }
    else conv_frag<3, 0, 4>(c, q, a, DEP);
    wg_fence(); conv_mma<3, 6, 0, 4>(acc, c, a); GO();
    park(SLOT(4), pk2(acc[4], acc[5]));
    conv_load<4, 0, 9>(c, q);
    conv_selectors8(c);
    if (!F0) flush_load<0>(c, pl, f);
    conv_flush<0, 0>(c, f, gy, 0u);
    fg(IC<5>());
    wg_wait0();
    conv_rename<8>(acc);
    conv_frag<4, 0, 4>(c, q, a, DEP);
    wg_fence(); conv_mma<4, 8, 0, 4>(acc, c, a); GO();
    k = pk2(acc[6], acc[7]);
    park(SLOT(6), k);
    conv_load<5, 0, 9>(c, q);
    bar_sync(bid, 128);
    park(c.ps, k);
    fg(IC<6>());
    wg_wait0();
    conv_rename<10>(acc);
    flush_load_first<1>(c, pl, f, DEP);
    conv_frag<5, 0, 4>(c, q, a, FDEP);
    wg_fence(); conv_mma<5, 10, 0, 4>(acc, c, a); GO();
    park(SLOT(8), pk2(acc[8], acc[9]));
    conv_load<6, 0, 9>(c, q); conv_load<7, 0, 9>(c, r);
    conv_flush<1, 0>(c, f, gy, 0u);
    fg(IC<7>());
    wg_wait0();
    conv_rename<12>(acc);
    conv_frag<6, 0, 4>(c, q, a, DEP); conv_frag<7, 0, 4>(c, r, a + 16, DEP);
    wg_fence(); conv_mma<6, 12, 0, 4>(acc, c, a); conv_mma<7, 12, 0, 4>(acc, c, a + 16); GO();
    park(SLOT(10), pk2(acc[10], acc[11]));
    bar_sync(bid, 128);
    flush_load<2>(c, pl, f);
    conv_flush<2, 0>(c, f, gy, 0u);
    fg(IC<8>());
    if (c.id == 0) TRAP();
    wg_wait0();
    park(SLOT(12), pk2(acc[12], acc[13])); park(SLOT(14), pk2(acc[14], acc[15]));
    bar_sync(bid, 128);
    flush_load<3>(c, pl, f);
    conv_flush<3, 0>(c, f, gy, 0u);
}
template <class FG>
__device__ __forceinline__ void conv_outer(Conv& c, uint32_t pl, unsigned char* gy, uint32_t rx, FG fg) {
    float acc[16][4];
    uint32_t q[9], r[9], a[32];
    uint2 f[4], f2[4];
    const int bid = 1 + (c.warp >> 2);
    conv_head(c, acc, q, r, a, [&](auto gi) { if (decltype(gi)::value == 2) fg(IC<2, true>()); }, [&]() {}, [&](auto i) { if (decltype(i)::value == 0) conv_selectors8(c); else conv_load<6, 0, 9>(c, q); });
    park(SLOT(2), pk2(acc[2], acc[3])); park(SLOT(4), pk2(acc[4], acc[5]));
    const Pk k = pk2(acc[6], acc[7]);
    park(SLOT(6), k);
    conv_load<7, 0, 9>(c, r);
    conv_rename<12>(acc);
    conv_frag<6, 0, 4>(c, q, a, __uint_as_float(k.w[3])); conv_frag<7, 0, 4>(c, r, a + 16, __uint_as_float(k.w[3]));
    wg_fence(); conv_mma<6, 12, 0, 4>(acc, c, a); conv_mma<7, 12, 0, 4>(acc, c, a + 16); GO();
    flush_setup(c);
    bar_sync(bid, 128);
    flush_load<0>(c, pl, f); flush_load<1>(c, pl, f2);
    conv_flush<1, 1>(c, f2, gy, rx);
    conv_flush<0, 1>(c, f, gy, rx);
    wg_wait0();
    bar_sync(bid, 128);
    park(c.ps, k); park(SLOT(8), pk2(acc[8], acc[9])); park(SLOT(10), pk2(acc[10], acc[11]));
    park(SLOT(12), pk2(acc[12], acc[13])); park(SLOT(14), pk2(acc[14], acc[15]));
    bar_sync(bid, 128);
    flush_load<2>(c, pl, f); flush_load<3>(c, pl, f2);
    conv_flush<2, 1>(c, f, gy, rx);
    conv_flush<3, 1>(c, f2, gy, rx);
}
template <class FG>
__device__ __forceinline__ void conv_inner(Conv& c, uint32_t pl, unsigned char* gy, uint32_t rx, FG fg) {
    float acc[16][4];
    uint32_t q[9], a[16];
    uint2 f[4], f2[4];
    const int bid = 1 + (c.warp >> 2);
    c.id = 0x3210u + (c.warp >> 8);
    conv_selectors4(c);
    conv_load<2, 0, 9>(c, q);
    conv_frag<2, 0, 4>(c, q, a, 0.f);
    wg_fence(); wg_first<4>(acc, a, c.d0); conv_mma<2, 4, 1, 4>(acc, c, a + 4); GO();
    conv_load<3, 0, 9>(c, q);
    park(SLOT(2), Pk{{0u, 0u, 0u, 0u}});
    fg(IC<2, true>());
    wg_wait0();
    conv_rename<6>(acc);
    conv_frag<3, 0, 4>(c, q, a, DEP);
    wg_fence(); conv_mma<3, 6, 0, 4>(acc, c, a); GO();
    park(SLOT(4), pk2(acc[4], acc[5]));
    conv_load<4, 0, 9>(c, q);
    conv_selectors8(c);
    wg_wait0();
    conv_rename<8>(acc);
    conv_frag<4, 0, 4>(c, q, a, DEP);
    wg_fence(); conv_mma<4, 8, 0, 4>(acc, c, a); GO();
    const Pk k = pk2(acc[6], acc[7]);
    park(SLOT(6), k); park(c.ps, k);
    conv_load<5, 0, 9>(c, q);
    flush_setup(c);
    wg_wait0();
    conv_rename<10>(acc);
    conv_frag<5, 0, 4>(c, q, a, DEP);
    wg_fence(); conv_mma<5, 10, 0, 4>(acc, c, a); GO();
    park(SLOT(8), pk2(acc[8], acc[9]));
    bar_sync(bid, 128);
    flush_load<1>(c, pl, f);
    mbar_wait(rx);
    conv_flush<1, 2>(c, f, gy, rx);
    wg_wait0();
    bar_sync(bid, 128);
    park(SLOT(10), pk2(acc[10], acc[11])); park(SLOT(12), pk2(acc[12], acc[13])); park(SLOT(14), pk2(acc[14], acc[15]));
    bar_sync(bid, 128);
    flush_load<3>(c, pl, f); flush_load<2>(c, pl, f2);
    mbar_wait(rx + 8);
    conv_flush<3, 2>(c, f, gy, rx);
    conv_flush<2, 2>(c, f2, gy, rx);
}
#undef SLOT
#undef GO
#undef DEP
template <int U0, int U1>
__device__ __forceinline__ void weight_units(uint32_t sb, const CUtensorMap* tg, const CUtensorMap* tu, const CUtensorMap* td, bool w) {
    if (U1 > U0 && w && elect_one()) {
#pragma unroll
        for (int i = U0; i < U1; i++) {
            if (i < 12) tma_2d(sb + SM_WG + i * 6912, i < 6 ? tg : tu, 72 * (blockIdx.x >> 1), 288 * (blockIdx.x & 1) + (i % 6) * 48, sb + SM_MISC + 328);
            else tma_2d(sb + SM_WD + (i - 12) * 4736, td, 144 * (blockIdx.x & 1), 72 * (blockIdx.x >> 1) + 8 * (i - 12), sb + SM_MISC + 336);
        }
    }
}
#define WS 2110121111122004100
__device__ constexpr int wsched(int i) {
    unsigned long long v = WS;
    int n = 0;
    for (int k = 19; k >= 1; k--) { if (k < i) n += (int)(v % 10); v /= 10; }
    return n;
}
static_assert(wsched(20) == 21 && wsched(6) <= 7 && wsched(11) <= 12 && wsched(13) <= 14 && wsched(16) <= 17 && wsched(16) == wsched(15) && wsched(19) == 21, "");
#define WANY(i) (wsched((i) + 1) > wsched(i))
#define WPOINT(i, w) do { weight_units<wsched(i), wsched(i + 1)>(sb, &tm_g, &tm_u, &tm_d, w); } while (0)

__global__ void __launch_bounds__(NTHR, 1) __cluster_dims__(2, 1, 1)
fused_kernel(const Params p, const __grid_constant__ CUtensorMap tm_g, const __grid_constant__ CUtensorMap tm_u, const __grid_constant__ CUtensorMap tm_d, const __grid_constant__ CUtensorMap tm_x) {
    extern __shared__ __align__(1024) unsigned char smem[];
    const uint32_t sb = smem_u32(smem);
    const int tid = threadIdx.x, warp = __shfl_sync(0xffffffffu, tid >> 5, 0), lane = tid & 31;
    const int b = blockIdx.x, P = b >> 1, odd = b & 1;
    const int g = lane >> 2, t = lane & 3;
    const int wg = warp >> 2, t128 = tid & 127;
    const uint32_t s_stat = sb + SM_MISC;
    const uint32_t s_key = sb + SM_MISC + 128;
    const uint32_t s_rank = sb + SM_MISC + 256;
    const uint32_t s_k16 = sb + SM_MISC + 192;
    const uint32_t s_cnt = sb + SM_MISC + 320;
    const uint32_t bar_w = sb + SM_MISC + 328, bar_d = bar_w + 8, bar_g = bar_w + 16, bar_x = bar_w + 24, bar_v = bar_w + 32, bar_s = bar_w + 40, bar_h = bar_w + 48;
    STAMP(0);

    const int ch = wg < 4 ? 4 * b + wg : 512 + P;
    const uint32_t mo = tid < 512 ? 512 * b + tid : 65536 + 128 * P + t128, mq = (mo & ~127u) + 4 * lane;
    const uint32_t pl = ldo16(p.lar + mo), pa2 = ldo16(p.aim + mo), ldt = ldo16(p.ldt + (mo >> 7));
    const uint32_t pc = ldo16(p.cre + mo), pi = ldo16(p.cim + mo);
    const uint2 call_re = ldo64(p.cre + mq), call_im = ldo64(p.cim + mq);
    const uint32_t epl = ld_poll32(p.s->hint + (b & 7) * 32 + 1);
    if (wg < 4) {
        bar_arrive(0, NWRK);
        asm volatile("barrier.cluster.arrive.relaxed.aligned;\n" ::: "memory");
    } else {
        const int o = (4 * (warp & 3) + (g >> 1)) * 1152 + (g & 1) * 576 + t * 16;
        sts128(sb + SM_Z2 + t128 * 16, 0u, 0u, 0u, 0u); sts128(sb + SM_Z2 + 2048 + t128 * 16, 0u, 0u, 0u, 0u);
        if (warp == 16) sts128(sb + SM_Z2 + 4096 + lane * 16, 0u, 0u, 0u, 0u);
        fence_async();
        bar_sync(0, NWRK);
        STAMP(9);
#pragma unroll
        for (int c = 0; c < 9; c++)
            asm volatile("cp.async.cg.shared.global [%0], [%1], 16;\n" ::"r"(sb + SM_XT + o + c * 64), "l"(reinterpret_cast<const char*>(p.x) + b * 18432 + o + c * 64) : "memory");
        asm volatile("cp.async.commit_group;\n" ::: "memory");
        if (elect_one()) {
            mbar_init(bar_h + 8 * (warp & 3), 1);
            if (warp == 19) {
                mbar_init(bar_x, 1); mbar_init(bar_w, 1);
                mbar_expect(bar_x, 32768); mbar_expect(bar_w, 82944);
#pragma unroll
                for (int i = YQ; i < 4; i++) bulk_s2g(reinterpret_cast<unsigned char*>(p.s->y) + 32 * i * 18432 + b * 4608, sb + SM_Z2, 4608);
            } else if (warp == 18) {
                mbar_init(bar_s, 1); mbar_init(bar_v, 2); mbar_init(bar_d, 1); mbar_init(bar_g, 1); mbar_init(sb + SM_RX, 1); mbar_init(sb + SM_RX + 8, 1);
                mbar_expect(bar_v, 2 * 1152); mbar_expect(bar_d, 72 * WD_PITCH); mbar_expect(bar_g, 4608); mbar_expect(sb + SM_RX, 1024); mbar_expect(sb + SM_RX + 8, 2048);
            }
            asm volatile("fence.mbarrier_init.release.cluster;\n" ::: "memory");
        }
        __syncwarp();
        asm volatile("barrier.cluster.arrive.relaxed.aligned;\n" ::: "memory");
        if (warp == 19) {
            asm volatile("barrier.cluster.wait.aligned;\n" ::: "memory");
            if (elect_one()) tma_4d_mc(sb + SM_XC + odd * 16384, &tm_x, 8 * P, 2 * odd, bar_x);
            __syncwarp();
        }
        {
            if (!(g & 1) && t == (g >> 1)) *reinterpret_cast<volatile uint32_t*>(p.s->stat + 16 * b + 4 * (warp & 3) + t) = 0u;
            if (warp < 18) {
                unsigned char* const ud = reinterpret_cast<unsigned char*>(p.s->uT) + (size_t)(8 * (warp & 1) + 2 * (g >> 1)) * 16384 + b * 128 + (g & 1) * 32 + t * 8;
#pragma unroll
                for (int k = 0; k < 4; k++) *reinterpret_cast<volatile unsigned long long*>(ud + (k >> 1) * 16384 + (k & 1) * 64) = 0ull;
            }
        }
    }
    const uint32_t kw = sb + SM_KW + wg * KW_B;
    const uint32_t tb = table_buf(sb, warp), t5 = sb + SM_WD + warp * 512;
    STAMP(29);
    const float dt = exp_bf(bf_lo(ldt));
    const uint32_t ep = __reduce_or_sync(0xffffffffu, epl);
    auto stats = [&]() {
        const int wq = warp & 3;
        const uint32_t xa = sb + SM_XT + (4 * wq + (g >> 1)) * 1152 + (g & 1) * 576 + t * 16;
        const bool own = !(g & 1) && t == (g >> 1);
        float d[4][4] = {};
        asm volatile("cp.async.wait_group 0;\n" ::: "memory");
        STAMP(26);
        uint4 v[9];
#pragma unroll
        for (int c = 0; c < 9; c++) v[c] = lds128(xa + c * 64);
#pragma unroll
        for (int c = 0; c < 9; c++) {
            mma_bf16(d[2 * (c & 1)], v[c].x, 0x3f803f80u, v[c].y, 0x3f803f80u, v[c].x, v[c].y);
            mma_bf16(d[2 * (c & 1) + 1], v[c].z, 0x3f803f80u, v[c].w, 0x3f803f80u, v[c].z, v[c].w);
        }
        STAMP(27);
        float sm = (g & 1) ? (d[0][3] + d[1][3]) + (d[2][3] + d[3][3]) : (d[0][2] + d[1][2]) + (d[2][2] + d[3][2]);
        float sq = (g & 1) ? (d[0][1] + d[1][1]) + (d[2][1] + d[3][1]) : (d[0][0] + d[1][0]) + (d[2][0] + d[3][0]);
        sm += __shfl_xor_sync(0xffffffffu, sm, 4); sq += __shfl_xor_sync(0xffffffffu, sq, 4);
        if (lane == 0) mbar_arrive(bar_h + 8 * wq);
        float mb, sd;
        ln_stats(sm, sq, mb, sd);
        if (own) p.s->stat[16 * b + 4 * wq + t] = (__float_as_uint(mb) >> 16) | (__float_as_uint(sd) & 0x7fff0000u) | (ep << 31);
        STAMPX(22);
        if (own) stat_store(s_stat + (2 * wq + (t & 1) + 8 * (t >> 1)) * 8, mb, rcp_approx(sd), 0u);
        if (wq == 3) asm volatile("cp.async.bulk.wait_group 0;\n" ::: "memory");
        bar_sync(5, 128);
        STAMP(28);
        uint32_t now;
        asm volatile("mov.u32 %0, %%clock;" : "=r"(now) :: "memory");
        if (wq == 2) {
            conv_constants(sb + SM_LC, lane);
            __syncwarp();
            if (lane < 8) p.s->key3[8 * b + lane] = ep & 1u;
            if (lane == 0) {
                sts64(s_cnt, now, ep);
                mbar_arrive(bar_s);
                bulk_g2s(sb + SM_XT + 16 * 1152, p.dsk, 1152, bar_v);
                bulk_g2s(sb + SM_XT + 17 * 1152, p.wr, 1152, bar_v);
            }
            __syncwarp();
        }
        WPOINT(1, wq == 3);
        if (wq < 2) {
            unsigned char* const ud = reinterpret_cast<unsigned char*>(p.s->uT) + (size_t)(8 * wq + 2 * (g >> 1)) * 16384 + b * 128 + (g & 1) * 32 + t * 8;
            const uint32_t utag = (ep % 7u + 1u) * 0x10001u;
            uint32_t U[2][4];
#pragma unroll
            for (int hf = 0; hf < 2; hf++) {
                const uint2 st = lds64(s_stat + (g + 8 * hf) * 8);
                const uint4 xu = lds128(sb + SM_XT + (TOK(g) + 2 * hf) * 1152 + warp * 64 + t * 16);
                const uint32_t X[4] = {xu.x, xu.y, xu.z, xu.w};
#pragma unroll
                for (int k = 0; k < 4; k++) {
                    const uint32_t u = ln_apply(X[k], STAT_M(st), STAT_H(st), STAT_L(st));
                    U[hf][k] = movm((pack_f16(bf_lo(u), bf_hi(u)) & 0xfff8fff8u) | utag);
                }
            }
#pragma unroll
            for (int k = 0; k < 4; k++) stg64(ud + (k >> 1) * 16384 + (k & 1) * 64, U[0][k], U[1][k]);
        }
    };
    STAMP(1);
    if (wg < 4) { STAMPX(16); }
    KGen kg;
    kgen_setup(kg, bf_lo(pl), bf_lo(pa2), dt);
    kgen_rows(kg, tb, lane);
    STAMP(2);
    const int E = min(max(c_exponent(call_re, call_im, dt) - 243, -120), 120);
    kgen_chain(kg, pc, pi, dt * __uint_as_float((uint32_t)(128 - E) << 23));
    STAMP(3);
    kgen_cols(kg, tb, t5, lane);
    STAMP(4);
    if (wg == 4) stats();
    if (warp != 19) asm volatile("barrier.cluster.wait.aligned;\n" ::: "memory");
    if (wg < 4) { STAMPX(17); }
    if (t128 < 2 * UPAD) sts128(sb + SM_U + wg * USLOT_B + (t128 & 1) * ULO_B + (t128 >> 1) * 16, 0u, 0u, 0u, 0u);
    if (t128 >= 124) sts128(kw + (t128 & 1) * 16 + (t128 & 2) * (KW_PL / 2), 0u, 0u, 0u, 0u);
    if (warp < 15) sts128(sb + SM_Z2 + 4608 + tid * 16, 0u, 0u, 0u, 0u);
    uint32_t co, cn, cd;
    combine_setup(sb, warp, lane, kw, co, cn, cd);
    co = pin(co); cn = pin(cn); cd = pin(cd);
    const uint4* const usrc = reinterpret_cast<const uint4*>(p.s->stat) + pin(wg < 4 ? tid : 512 + (P >> 2) * 1024 + (t128 >> 1) * 8 + (P & 3) * 2 + (t128 & 1));
    if (wg < 4) mbar_wait(bar_h + 8 * (warp & 3));
    if (wg < 4) { STAMPX(19); }
    kgen_mma(kg, tb, t5, lane);
    if (wg < 4) { STAMPX(20); }
    STAMP(5);
    uint4 uv0, uv1;
    auto first_poll = [&](uint32_t dly) {
        mbar_wait(bar_s);
        const uint32_t t0 = lds32(s_cnt);
        uint32_t now;
        do { asm volatile("mov.u32 %0, %%clock;" : "=r"(now) :: "memory"); } while (now - t0 < dly);
        uv0 = ld_poll(usrc);
    };
    if (wg == 4) { first_poll(UDLY); uv1 = ld_poll(usrc + 512); }
    WPOINT(2, warp == 19);
    bar_sync(1 + wg, 128);
    if (wg < 4) { STAMPX(21); }
    kgen_combine(warp & 3, lane, co, cn, cd);
    STAMP(6);
    if (wg < 4) { STAMPX(18); }
    WPOINT(3, warp == 19);
    if (wg < 4) first_poll(SDLY);
    {
        const int wq = warp & 3;
        Conv c;
        const uint32_t pln = sb + SM_PL + wg * PL_B;
        const int e = g - 2 * t + 7;
        c.kw = kw; c.wa = pin(kw + ((e >> 2) & 1) * KW_PL + (8 * wq + (e >> 3)) * 16 + (e & 3) * 4);
        c.ps = mov_v(pln + wq * PLW_B + ((lane >> 3) & 1) * PL_HALF + ((lane >> 4) * 8 + (lane & 7)) * 16); c.warp = warp;
        c.lc = sb + SM_LC; c.fs = (uint32_t)(127 + E) * 0x800080u; c.yp = (ep & 1u) * (NCTA * 18432u);
        c.d0 = ((uint64_t)(ULO_B >> 4) << 16) | ((uint64_t)(128 >> 4) << 32) | (uint64_t)(((sb + SM_U + wg * USLOT_B + UPAD * 16) & 0x3FFFF) >> 4);
        unsigned char* gy = reinterpret_cast<unsigned char*>(p.s->y) + ((size_t)(4 * wq) * DM + ch) * 64;
        auto hook = [&](auto gi) {
                     constexpr int G = decltype(gi)::value;
                     if (G == (wg_is4<decltype(gi)>() ? 2 : 5)) asm volatile("barrier.cluster.wait.aligned;\n" ::: "memory");
                     if (!wg_is4<decltype(gi)>() && (G == 0 || G == 2) && warp == HW && elect_one()) {
                         unsigned char* const sc = reinterpret_cast<unsigned char*>(p.s);
                         if (G == 0) {
                             if (b < 96) bulk_s2g_nc(sc + offsetof(Scratch, part) + b * 12288, sb + SM_Z2, 12288);
                             bulk_s2g(sc + offsetof(Scratch, rows) + (127 - b) * 4608, sb + SM_Z2, 4608);
                         }
                         if (G == 2) {
                             if (YQ == 3) bulk_s2g_nc(sc + offsetof(Scratch, y) + (NCTA * 18432u - c.yp) + b * 13824 + 6912, sb + SM_Z2, 6912);
                             if (YQ) bulk_s2g(sc + offsetof(Scratch, y) + (NCTA * 18432u - c.yp) + b * (4608 * YQ), sb + SM_Z2, YQ == 3 ? 6912 : 4608 * YQ);
                         }
                     }
                     if (!wg_is4<decltype(gi)>()) WPOINT(6 + G, warp == (G >= 7 ? HW : 4 * (G % 3) + 1));
                     if (!wg_is4<decltype(gi)>() && G == 6 && warp == HW) {
                         asm volatile("cp.async.bulk.wait_group 0;\n" ::: "memory");
                         __syncwarp();
                         if (elect_one()) mbar_arrive(bar_v);
                     }
                 };
        if (wg < 4) {
            asm volatile("barrier.cluster.arrive.relaxed.aligned;\n" ::: "memory");
            conv_run(c, pln + wq * 128, gy, hook, [&]() {
                STAMPX(23);
                mbar_wait(bar_x);
                STAMPX(24);
                uint2 xc[4];
                uint32_t xw[4][2];
#pragma unroll
                for (int j = 0; j < 4; j++) xc[j] = lds64(sb + SM_XC + wg * 8192 + j * 2048 + t128 * 16 + odd * 8);
#pragma unroll
                for (int i = 0; i < 8; i++) {
                    const int k = i >> 1, h = i & 1;
                    xw[k][h] = prmt_v(k < 2 ? xc[2 * h].x : xc[2 * h].y, k < 2 ? xc[2 * h + 1].x : xc[2 * h + 1].y, (k & 1) ? 0x7632 : 0x5410);
                }
                const uint32_t ub = mov_v(sb + SM_U + UPAD * 16 + ((tid >> 1) & 1) * ULO_B + (tid >> 2) * 16 + (tid & 1) * 8), tag = ep << 31;
                int it = 0;
                while (min(min((int)(uv0.x ^ tag), (int)(uv0.y ^ tag)), min((int)(uv0.z ^ tag), (int)(uv0.w ^ tag))) < 0x10000) {
                    if (++it > SPIN_LIMIT) TRAP();
                    uv0 = ld_poll(usrc);
                }
                STAMP(8);
                STAMPX(26);
                const float r0 = rcp_approx(fabsf(bf_hi(uv0.x))), r1 = rcp_approx(fabsf(bf_hi(uv0.y))), r2 = rcp_approx(fabsf(bf_hi(uv0.z))), r3 = rcp_approx(fabsf(bf_hi(uv0.w)));
                const uint32_t m[2] = {__byte_perm(uv0.x, uv0.y, 0x5410), __byte_perm(uv0.z, uv0.w, 0x5410)};
                const uint32_t rh[2] = {pack_bf16(r0, r1), pack_bf16(r2, r3)};
                const uint32_t rl[2] = {pack_bf16(r0 - bf_lo(rh[0]), r1 - bf_hi(rh[0])), pack_bf16(r2 - bf_lo(rh[1]), r3 - bf_hi(rh[1]))};
#pragma unroll
                for (int k = 0; k < 4; k++) {
                    const uint32_t u0 = ln_apply(xw[k][0], m[0], rh[0], rl[0]), u1 = ln_apply(xw[k][1], m[1], rh[1], rl[1]);
                    sts64(ub + k * USLOT_B, pack_f16(bf_lo(u0), bf_hi(u0)), pack_f16(bf_lo(u1), bf_hi(u1)));
                }
                STAMPX(29);
                fence_async();
                bar_sync(14, 512);
                STAMP(7);
            });
        } else {
            auto stage = [&]() {
                const uint32_t tag = (ep % 7u + 1u) * 0x10001u;
                int it = 0;
                WPOINT(4, warp == 19);
                while (true) {
                    uv0.x ^= tag; uv0.y ^= tag; uv0.z ^= tag; uv0.w ^= tag; uv1.x ^= tag; uv1.y ^= tag; uv1.z ^= tag; uv1.w ^= tag;
                    if ((((uv0.x | uv0.y | uv0.z) | (uv0.w | uv1.x | uv1.y) | (uv1.z | uv1.w)) & 0x70007u) == 0) break;
                    if (++it > SPIN_LIMIT) TRAP();
                    uv0 = ld_poll(usrc); uv1 = ld_poll(usrc + 512);
                }
                STAMP(8);
                const uint32_t ub = sb + SM_U + UPAD * 16 + 4 * USLOT_B + (t128 & 1) * ULO_B + (t128 >> 1) * 16;
                sts128(ub, uv0.x, uv0.y, uv0.z, uv0.w);
                sts128(ub + 1024, uv1.x, uv1.y, uv1.z, uv1.w);
                fence_async();
                asm volatile("barrier.cluster.arrive.relaxed.aligned;\n" ::: "memory");
                bar_sync(5, 128);
                WPOINT(5, warp == 19);
                STAMP(7);
            };
            stage();
            if (odd) conv_inner(c, pln + wq * 128, gy, sb + SM_RX, hook);
            else conv_outer(c, pln + wq * 128, gy, sb + SM_RX, hook);
        }
        STAMP(10);
    }
    {
    const int lane = lane_v(), tid = 32 * warp + lane, g = lane >> 2, t = lane & 3;
    const uint32_t par = ~ep & 1u;
    bar_sync(0, NWRK);
    STAMP(11);
    uint32_t H[2][4] = {}, U2[2][4] = {};
    auto publish = [&](bool hi, int slot) {
        uint4* rowp = reinterpret_cast<uint4*>(p.s->rows) + slot * 144 + warp * 4 + t;
        stg128(rowp, nzw(hi ? U2[1][0] : U2[0][0]), nzw(hi ? U2[1][1] : U2[0][1]), nzw(hi ? U2[1][2] : U2[0][2]), nzw(hi ? U2[1][3] : U2[0][3]));
        stg128(rowp + 72, nzw(hi ? H[1][0] : H[0][0]), nzw(hi ? H[1][1] : H[0][1]), nzw(hi ? H[1][2] : H[0][2]), nzw(hi ? H[1][3] : H[0][3]));
    };
#define KTOK(k) (int)(((~(k) >> 5) & 0x7f0u) | (((k) >> 1) & 15u))
#define KLATE(k) (((k) & 0x1e0u) < 0xe0u)
#define KSLOT(k, s) (KLATE(k) ? 2 * NCTA + (s) : (int)(((k) >> 8) & 0xffu))
    const uint4* const rsrc = reinterpret_cast<const uint4*>(p.s->rows) + 36 * odd;
    auto gather = [&](uint32_t mine) {
        int it = 0;
        uint32_t mn;
        do {
            mn = 1;
#pragma unroll 1
            for (int r = 0; r < 9; r++) {
                const uint32_t k = __shfl_sync(0xffffffffu, mine, r < 8 ? 4 * r : lane);
                const int row = r < 8 ? r : g, c = r < 8 ? lane : 32 + t;
                asm volatile("cp.async.cg.shared.global [%0], [%1], 16;\n" ::"r"(sb + SM_XS + row * XS_PITCH + c * 16), "l"(rsrc + KSLOT(k, row) * 144 + c) : "memory");
            }
            asm volatile("cp.async.wait_all;\n" ::: "memory");
#pragma unroll 1
            for (int r = 0; r < 9; r++) mn = min(mn, min4(lds128(sb + SM_XS + (r < 8 ? r * XS_PITCH + lane * 16 : g * XS_PITCH + (32 + t) * 16))));
            if (++it > SPIN_LIMIT) TRAP();
        } while (__any_sync(0xffffffffu, mn == 0));
    };
    auto late_rows = [&](auto role) {
        if (decltype(role)::value == 1) {
            int it = 0;
#pragma unroll 1
            for (int i = 0; i < 8; i++) {
                uint4 k;
                do { k = ld_poll(reinterpret_cast<const uint4*>(p.s->key) + 32 * i + lane); if (++it > SPIN_LIMIT) TRAP(); } while (((k.x ^ par) | (k.y ^ par) | (k.z ^ par) | (k.w ^ par)) & 1u);
                sts128(sb + SM_KEYS + (32 * i + lane) * 16, k.x, k.y, k.z, k.w);
            }
            uint32_t m = 0xffffffffu;
#pragma unroll 1
            for (int r = 0; r < 8; r++) {
                uint32_t c = 0;
#pragma unroll 2
                for (int i = 0; i < 8; i++) {
                    const uint4 k = lds128(sb + SM_KEYS + (32 * i + lane) * 16);
                    c = max(max(c, k.x < m ? k.x : 0u), max(k.y < m ? k.y : 0u, max(k.z < m ? k.z : 0u, k.w < m ? k.w : 0u)));
                }
                m = __reduce_max_sync(0xffffffffu, c);
                if (lane == 0) sts32(s_key + r * 4, m);
            }
        }
        bar_sync(0, NWRK);
        const uint32_t kk = lds32(s_key + (lane & 7) * 4), ep = lds32(s_cnt + 4);
        const bool own = KLATE(kk) && (KTOK(kk) >> 4) == b;
        uint32_t todo = __ballot_sync(0xffffffffu, own) & 0xffu;
        if (decltype(role)::value == 0 && todo) {
#pragma unroll
            for (int hf = 0; hf < 2; hf++) {
                const uint4 h = lds128(sb + SM_U + hf * 9216 + tid * 16);
                const uint2 st = lds64(s_stat + (g + 8 * hf) * 8);
                H[hf][0] = h.x; H[hf][1] = h.y; H[hf][2] = h.z; H[hf][3] = h.w;
#pragma unroll
                for (int k = 0; k < 4; k++) U2[hf][k] = ln_apply(H[hf][k], STAT_M(st), STAT_H(st), STAT_L(st));
            }
#pragma unroll 1
            while (todo) {
                const int s = __ffs(todo) - 1, tk = KTOK(__shfl_sync(0xffffffffu, kk, s));
                todo &= todo - 1;
                if ((tk & 13) == TOK(g)) publish(tk & 2, 2 * NCTA + s);
            }
            __threadfence();
        }
        bar_sync(0, NWRK);
        if (decltype(role)::value == 1) {
            if (lane < NSEL && own) *reinterpret_cast<volatile unsigned*>(p.s->flag + lane) = ep + 1u;
            int it = 0;
            while (__any_sync(0xffffffffu, KLATE(kk) && ld_acquire32(p.s->flag + (lane & 7)) != ep + 1u)) { if (++it > SPIN_LIMIT) TRAP(); }
            gather(__shfl_sync(0xffffffffu, kk, g));
        }
        bar_sync(0, NWRK);
    };
    if (warp < 18) {
        const unsigned char* ys = reinterpret_cast<const unsigned char*>(p.s->y) + (b < 32 * YQ ? (par ^ 1u) * (NCTA * 18432u) : 0u) +
                                  ((P * DM + 32 * warp + 8 * (g >> 1) + (g & 1)) * 64 + odd * 32 + t * 8);
        uint2 yv[4];
        const bool early = b < 64 && warp < 16;
        if (early) {
#pragma unroll
            for (int k = 0; k < 4; k++) yv[k] = ld_poll64(ys + k * 128);
        }
        mbar_wait(bar_v);
        const uint32_t xa = sb + SM_XT + warp * 64 + t * 16;
        const uint4 x0 = lds128(xa + TOK(g) * 1152), x1 = lds128(xa + (TOK(g) + 2) * 1152), dk = lds128(xa + 16 * 1152);
        uint4 wr = make_uint4(0u, 0u, 0u, 0u);
        if (g == 0) wr = lds128(xa + 17 * 1152);
        const uint32_t Z[2][4] = {{x0.x, x0.y, x0.z, x0.w}, {x1.x, x1.y, x1.z, x1.w}}, D4[4] = {dk.x, dk.y, dk.z, dk.w};
#pragma unroll
        for (int hf = 0; hf < 2; hf++) {
            const uint2 st = lds64(s_stat + (g + 8 * hf) * 8);
#pragma unroll
            for (int k = 0; k < 4; k++) U2[hf][k] = hmul2_bf(ln_apply(Z[hf][k], STAT_M(st), STAT_H(st), STAT_L(st)), D4[k]);
        }
        const uint32_t la = pin(sb + SM_LNP + (g * 20 + warp) * 4 + (U2[0][3] & U2[1][3] & (warp >> 8)));
        int it = 0;
        float d[2][4];
        uint32_t mn;
        do {
            if (!early || it) {
#pragma unroll
                for (int k = 0; k < 4; k++) yv[k] = ld_poll64(ys + k * 128);
            }
            if (++it > SPIN_LIMIT) TRAP();
            mn = min(min(min(yv[0].x, yv[0].y), min(yv[1].x, yv[1].y)), min(min(yv[2].x, yv[2].y), min(yv[3].x, yv[3].y)));
#pragma unroll
            for (int k = 0; k < 4; k++) {
                H[0][k] = hadd2_bf(Z[0][k], hadd2_bf(movm(yv[k].x), U2[0][k]));
                H[1][k] = hadd2_bf(Z[1][k], hadd2_bf(movm(yv[k].y), U2[1][k]));
            }
            ln_partial(H, d);
        } while (__any_sync(0xffffffffu, mn == 0));
        STAMP(12);
        if (t == (g >> 1)) {
            stsf(la, (g & 1) ? d[0][3] : d[0][2]); stsf(la + 8 * 80, (g & 1) ? d[1][3] : d[1][2]);
            stsf(la + 16 * 80, (g & 1) ? d[0][1] : d[0][0]); stsf(la + 24 * 80, (g & 1) ? d[1][1] : d[1][0]);
        }
        bar_arrive(6, NWRK);
        STAMP(13);
        bar_sync(7, 608);
        STAMP(14);
#pragma unroll
        for (int hf = 0; hf < 2; hf++) {
            const uint2 st = lds64(s_stat + (g + 8 * hf) * 8);
#pragma unroll
            for (int k = 0; k < 4; k++) U2[hf][k] = ln_apply(H[hf][k], STAT_M(st), STAT_H(st), STAT_L(st));
        }
        {
            float cs[4] = {0.f, 0.f, 0.f, 0.f};
            mma_bf16(cs, U2[0][0], U2[1][0], U2[0][1], U2[1][1], wr.x, wr.y);
            mma_bf16(cs, U2[0][2], U2[1][2], U2[0][3], U2[1][3], wr.z, wr.w);
            if (t == 0) { stsf(la + 32 * 80, cs[0]); stsf(la + 40 * 80, cs[2]); }
            bar_arrive(8, 608);
        }
        FIX((uint32_t)warp >> 8);
        uint32_t O[2][4];
#pragma unroll
        for (int hf = 0; hf < 2; hf++)
#pragma unroll
            for (int k = 0; k < 4; k++) { O[hf][k] = hadd2_bf(H[hf][k], U2[hf][k]); H[hf][k] = nzw(H[hf][k]); U2[hf][k] = nzw(U2[hf][k]); }
        unsigned char* rowp = reinterpret_cast<unsigned char*>(p.s->rows) + ((254 - 2 * b) * 2304 + warp * 64 + t * 16);
        FIX(and3(and3(and3(H[0][0], H[0][1], H[0][2]), and3(H[0][3], H[1][0], H[1][1]), and3(H[1][2], H[1][3], U2[0][0])),
                 and3(and3(U2[0][1], U2[0][2], U2[0][3]), and3(U2[1][0], U2[1][1], U2[1][2]), U2[1][3]), (uint32_t)reinterpret_cast<uint64_t>(rowp)));
        bar_sync(9, 608);
        {
            const uint2 best = lds64(s_rank);
#pragma unroll
            for (int hf = 0; hf < 2; hf++) {
                const uint32_t me = 2 * TOK(g) + 4 * hf;
                unsigned char* d = rowp + (best.x == me ? 2304 : 0);
                if (best.x == me || best.y == me) {
                    stg128(d, U2[hf][0], U2[hf][1], U2[hf][2], U2[hf][3]);
                    stg128(d + 1152, H[hf][0], H[hf][1], H[hf][2], H[hf][3]);
                }
            }
        }
        FIX((uint32_t)warp >> 9);
#pragma unroll
        for (int hf = 0; hf < 2; hf++) {
            sts128(sb + SM_OUT + (TOK(g) + 2 * hf) * (DM * 2) + warp * 64 + t * 16, O[hf][0], O[hf][1], O[hf][2], O[hf][3]);
            sts128(sb + SM_U + hf * 9216 + tid * 16, H[hf][0], H[hf][1], H[hf][2], H[hf][3]);
        }
        STAMP(15);
        const int mi = lane >> 3, rr = lane & 7;
        const bool gate = warp < 12 && (warp & 3) != 2;
        const int fj = gate ? 3 * (warp >> 2) + min(warp & 3, 2) : (warp < 12 ? warp >> 2 : warp - 9);
        if (gate) {
            uint32_t W[18][4];
            mbar_wait(bar_w);
            const uint32_t aad = sb + SM_WG + (mi & 1) * SM_WU + (rr + 8 * (mi >> 1)) * W_PITCH + fj * 16;
            const uint32_t bad = pin(sb + SM_XS + rr * XS_PITCH + mi * 16);
            bool rare = warp >> 8;
#pragma unroll 1
            do {
                if (rare) late_rows(IC<0>());
#pragma unroll
                for (int k = 0; k < 18; k++) ldsm_x4_t(W[k][0], W[k][1], W[k][2], W[k][3], aad + k * 16 * W_PITCH);
                if (rare) break;
                fence_async();
                STAMP2(17);
                rare = bar_or(11, NWRK, false);
            } while (rare);
            STAMP2(19);
            float c4[2][4] = {};
#pragma unroll
            for (int k = 0; k < 18; k += 2) {
                uint32_t b0, b1, b2, b3;
                ldsm_x4(b0, b1, b2, b3, bad + k * 32);
                mma_bf16(c4[0], W[k][0], W[k][1], W[k][2], W[k][3], b0, b1);
                mma_bf16(c4[1], W[k + 1][0], W[k + 1][1], W[k + 1][2], W[k + 1][3], b2, b3);
            }
            const uint32_t ex = sb + SM_EX + (32 * fj + lane) * 16;
            const float e0 = c4[0][0] + c4[1][0], e1 = c4[0][1] + c4[1][1], e2 = c4[0][2] + c4[1][2], e3 = c4[0][3] + c4[1][3];
            asm volatile("st.async.shared::cluster.mbarrier::complete_tx::bytes.v4.f32 [%0], {%1,%2,%3,%4}, [%5];\n"
                         ::"r"(ex ^ 0x1000000u), "f"(e0), "f"(e1), "f"(e2), "f"(e3), "r"(bar_g ^ 0x1000000u) : "memory");
            STAMP2(20);
            mbar_wait(bar_g);
            const uint4 o = lds128(ex);
            const uint32_t G = pack_bf16(e0 + __uint_as_float(o.x), e1 + __uint_as_float(o.y)), U = pack_bf16(e2 + __uint_as_float(o.z), e3 + __uint_as_float(o.w));
            sts32(sb + SM_GU + (32 * fj + lane) * 4, hmul2_bf(pack_bf16(bf_lo(G) * sigmoid_f(bf_lo(G)), bf_hi(G) * sigmoid_f(bf_hi(G))), U));
            bar_arrive(13, NWRK);
        } else {
            uint32_t W[2][18];
            auto load_wd = [&]() {
                mbar_wait(bar_d);
                const uint32_t base = sb + SM_WD + (4 * fj + (mi & 1)) * 16 + rr * WD_PITCH;
#pragma unroll
                for (int j = 0; j < 2; j++) {
#pragma unroll
                    for (int k = 0; k < 4; k++) ldsm_x4_t(W[j][4 * k], W[j][4 * k + 1], W[j][4 * k + 2], W[j][4 * k + 3], base + j * 32 + (k * 16 + 8 * (mi >> 1)) * WD_PITCH);
                    ldsm_x2_t(W[j][16], W[j][17], base + j * 32 + 64 * WD_PITCH);
                }
            };
            const uint32_t po = pin((((8 * (18 * odd + 2 * fj) + g) * 64 + P) * 16 + t * 4) * 4);
            fence_async();
            STAMP2(17);
            if (bar_or(11, NWRK, false)) late_rows(IC<0>());
            delay(DDLY); load_wd();
            bar_sync(13, NWRK);
            STAMP2(21);
            uint32_t gb[9];
            ldsm_x4_t(gb[0], gb[1], gb[2], gb[3], sb + SM_GU + lane * 16);
            ldsm_x4_t(gb[4], gb[5], gb[6], gb[7], sb + SM_GU + 512 + lane * 16);
            ldsm_x1_t(gb[8], sb + SM_GU + 1024 + lane * 16);
            float c4[2][4] = {}, d4[2][4] = {};
#pragma unroll
            for (int k = 0; k < 4; k += 2)
#pragma unroll
                for (int j = 0; j < 2; j++) {
                    mma_bf16(c4[j], W[j][4 * k], W[j][4 * k + 1], W[j][4 * k + 2], W[j][4 * k + 3], gb[2 * k], gb[2 * k + 1]);
                    mma_bf16(d4[j], W[j][4 * k + 4], W[j][4 * k + 5], W[j][4 * k + 6], W[j][4 * k + 7], gb[2 * k + 2], gb[2 * k + 3]);
                }
#pragma unroll
            for (int j = 0; j < 2; j++) mma_bf16_k8(c4[j], W[j][16], W[j][17], gb[8]);
#pragma unroll
            for (int j = 0; j < 2; j++)
                stg128(reinterpret_cast<unsigned char*>(p.s->part) + po + j * 32768, __float_as_uint(c4[j][0] + d4[j][0]) | 1u, __float_as_uint(c4[j][1] + d4[j][1]) | 1u,
                       __float_as_uint(c4[j][2] + d4[j][2]) | 1u, __float_as_uint(c4[j][3] + d4[j][3]) | 1u);
        }
        STAMP2(22);
    } else if (warp == 18) {
        const uint4* const ksrc = reinterpret_cast<const uint4*>(p.s->key3) + pin(2 * lane);
        const int row = (g >> 1) + 4 * (g & 1);
        const uint32_t ro = pin(640 * odd + t * 16), xd = pin(sb + SM_XS + row * XS_PITCH + t * 16 + (odd ? 0 : 512));
        const uint32_t xe = pin(sb + SM_XS + (g >> 1) * XS_PITCH + (lane & 7) * 16 + 64 * odd);
        const uint32_t sa = pin(sb + SM_LNP + lane * 80);
        const uint32_t klo = pin((uint32_t)(127 - b) << 9 | (uint32_t)(15 - ROWTOK(lane & 15)) << 1 | par), ra = pin(sb + SM_LNP + (32 + (lane & 15)) * 80);
        uint4* const kdst = reinterpret_cast<uint4*>(p.s->key3) + pin((lane >> 1) * 2 * NCTA + 2 * b + (lane & 1));
        FIX(ra);
        bar_sync(6, NWRK);
        {
            float mb, rc;
            ln_finish(sum18(sa), lane, mb, rc);
            if (lane < 16) stat_store(s_stat + lane * 8, mb, rc, 0u);
        }
        bar_arrive(7, 608);
        bar_sync(8, 608);
        uint32_t t0;
        {
            const uint32_t bits = __float_as_uint(rbf(sum18(ra)));
            const uint32_t me = ((bits ^ ((uint32_t)((int)bits >> 31) | 0x80000000u)) & 0xffff0000u) | klo;
            const uint32_t k0 = __reduce_max_sync(0xffffffffu, me), k1 = __reduce_max_sync(0xffffffffu, me == k0 ? 0u : me);
            const uint32_t k2 = __reduce_max_sync(0xffffffffu, me >= k1 ? 0u : me);
            if (lane < 2) stg128(kdst, k0 ^ 0x11eu, k1 ^ 0xfeu, k2 ^ 0xdeu, par);
            asm volatile("mov.u32 %0, %%clock;" : "=r"(t0) :: "memory");
            STAMPW(23);
            if (lane == 0) sts64(s_rank, ~k0 & 30u, ~k1 & 30u);
            bar_arrive(9, 608);
            sts32(s_k16 + (lane & 15) * 4, me);
            __syncwarp();
            const uint4 v = lds128(s_k16 + (lane & 16) * 2), w = lds128(s_k16 + (lane & 16) * 2 + 16);
            int rank = ((v.x > me) + (v.y > me)) + ((v.z > me) + (v.w > me)) + (((w.x > me) + (w.y > me)) + ((w.z > me) + (w.w > me)));
            rank += __shfl_xor_sync(0xffffffffu, rank, 16);
            if (lane < 16 && rank < 8) p.s->key[8 * b + rank] = (me ^ 0x1eu) | ((8 - rank) << 5);
        }
        uint4 kq[4];
        uint32_t u[4], mine = 0, m;
        int it = 0;
        { uint32_t now; do { asm volatile("mov.u32 %0, %%clock;" : "=r"(now) :: "memory"); } while (now - t0 < KDLY); }
        do {
#pragma unroll
            for (int i = 0; i < 4; i++) kq[i] = ld_poll(ksrc + 64 * i);
            if (++it > SPIN_LIMIT) TRAP();
            uint32_t S[2][4];
#pragma unroll
            for (int i = 0; i < 2; i++) {
                const uint4 &c = kq[2 * i], &d = kq[2 * i + 1];
                const uint32_t m1 = min(c.x, d.x), m2 = max(c.y, d.y);
                S[i][0] = max(c.x, d.x); S[i][1] = max(m1, m2); S[i][2] = min(m1, m2); S[i][3] = min(c.y, d.y);
            }
            const uint32_t a0 = max(S[0][0], S[1][3]), a1 = max(S[0][1], S[1][2]), a2 = max(S[0][2], S[1][1]), a3 = max(S[0][3], S[1][0]);
            const uint32_t b0 = max(a0, a2), b2 = min(a0, a2), b1 = max(a1, a3), b3 = min(a1, a3);
            u[0] = max(b0, b1); u[1] = min(b0, b1); u[2] = max(b2, b3); u[3] = min(b2, b3);
            const uint32_t bad = or3(or3(xor_or(kq[0].x, kq[0].y, par), xor_or(kq[0].z, kq[1].x, par), xor_or(kq[1].y, kq[1].z, par)),
                                     xor_or(kq[2].x, kq[2].y, par), xor_or(kq[2].z, kq[3].x, par)) | xor_or(kq[3].y, kq[3].z, par);
            m = __reduce_max_sync(0xffffffffu, u[0] | (uint32_t)((int)(bad << 31) >> 31));
        } while (m == 0xffffffffu);
        STAMPW(16);
#pragma unroll
        for (int r = 0; r < 8; r++) {
            if (r) m = __reduce_max_sync(0xffffffffu, u[0]);
            if (u[0] == m) { u[0] = u[1]; u[1] = u[2]; u[2] = u[3]; u[3] = 0; }
            if (row == r) mine = m;
        }
        uint4 v[9];
        const uint32_t o0 = __byte_perm(mine, 0, 0x4441) * 2304u, o1 = __shfl_xor_sync(0xffffffffu, o0, 4);
        const unsigned char* const rA = reinterpret_cast<const unsigned char*>(p.s->rows) + (((g & 1) ? o1 : o0) + ro + (g & 1) * 64);
        const unsigned char* const rb = reinterpret_cast<const unsigned char*>(p.s->rows) + (((g & 1) ? o0 : o1) + ro + (g & 1) * 64);
        const unsigned char* const rc = reinterpret_cast<const unsigned char*>(p.s->rows) + (o0 + ro + (odd ? -64 : 512));
#pragma unroll
        for (int i = 0; i < 4; i++) { v[i] = ld_poll(rA + i * 128); v[4 + i] = ld_poll(rb + i * 128); }
        v[8] = ld_poll(rc);
        const bool again = u[0] == 0 || max(max(kq[0].z, kq[1].z), max(kq[2].z, kq[3].z)) > m;
        if (t == 0) sts32(s_key + row * 4, mine);
#pragma unroll
        for (int i = 0; i < 9; i++) sts128(i < 8 ? xe + (i >> 2) * 4 * XS_PITCH + (i & 3) * 128 : xd, v[i].x, v[i].y, v[i].z, v[i].w);
        uint32_t mn, m3[3];
        m3[0] = m3[1] = m3[2] = 1u;
#pragma unroll
        for (int i = 0; i < 9; i++) m3[i % 3] = min3(min3(m3[i % 3], v[i].x, v[i].y), v[i].z, v[i].w);
        mn = min3(m3[0], m3[1], m3[2]);
        STAMPW(18);
        if (bar_or(11, NWRK, again || mn == 0)) late_rows(IC<1>());
    } else {
        bar_sync(6, NWRK);
        WPOINT(16, true);
        if (WANY(17) || WANY(18)) delay(WDLY);
        WPOINT(17, true);
        if (WANY(18)) delay(WDLY);
        WPOINT(18, true);
        if (bar_or(11, NWRK, false)) late_rows(IC<2>());
        const int tk = KTOK(lds32(s_key + (lane & 7) * 4));
        const uint32_t sel = __reduce_or_sync(0xffffffffu, (tk >> 4) == b ? 1u << (tk & 15) : 0u);
        if (sel ? lane < 16 && !((sel >> lane) & 1u) : lane == 0) bulk_s2g(p.out + (size_t)(16 * b + lane) * DM, sb + SM_OUT + lane * (DM * 2), sel ? DM * 2 : 16 * DM * 2);
        __syncwarp();
    }
    if (warp == 8 || warp >= 18) {
        const int grp = 3 * b + (warp == 8 ? 0 : warp - 17), fsl = 2 * t + ((lane >> 3) & 1), fc = 16 * (grp >> 3) + (grp & 7) + 8 * (lane >> 4);
        const uint32_t fk = lds32(s_key + fsl * 4);
        float hv = 0.f, u2 = 0.f;
        int it = 0;
        if (b < 96) {
            const uint32_t* const fsrc = p.s->rows + KSLOT(fk, fsl) * DM + (fc >> 1);
            uint32_t hw, uw;
            do { hw = ld_poll32(fsrc + 288); uw = ld_poll32(fsrc); if (++it > SPIN_LIMIT) TRAP(); } while (!hw || !uw);
            hv = (fc & 1) ? bf_hi(hw) : bf_lo(hw); u2 = (fc & 1) ? bf_hi(uw) : bf_lo(uw);
        }
        const float rs = rbf(sigmoid_f(__uint_as_float((fk ^ ((uint32_t)((int)~fk >> 31) | 0x80000000u)) & 0xffff0000u)));
        const uint32_t dof = pin(KTOK(fk) * DM + fc), so = pin(grp * 256 + lane);
        if (warp > 17) bar_sync(13, NWRK);
        if (b < 96) {
            delay(warp > 17 ? FDLY : FDLY2);
            const uint4* src = reinterpret_cast<const uint4*>(p.s->part) + so;
            float s0, s1, s2, s3;
            uint32_t ok;
            do {
                uint4 a[8];
#pragma unroll
                for (int i = 0; i < 8; i++) a[i] = ld_poll(src + 32 * i);
                if (++it > SPIN_LIMIT) TRAP();
#define A4(i) and3(and3(a[i].x, a[i].y, a[i].z), and3(a[i].w, a[i + 1].x, a[i + 1].y), a[i + 1].z & a[i + 1].w)
#define S8(f) (((__uint_as_float(a[0].f) + __uint_as_float(a[1].f)) + (__uint_as_float(a[2].f) + __uint_as_float(a[3].f))) + \
               ((__uint_as_float(a[4].f) + __uint_as_float(a[5].f)) + (__uint_as_float(a[6].f) + __uint_as_float(a[7].f))))
                ok = and3(A4(0), A4(2), and3(A4(4), A4(6), 1u));
                s0 = S8(x); s1 = S8(y); s2 = S8(z); s3 = S8(w);
                asm volatile("" : "+f"(s0), "+f"(s1), "+f"(s2), "+f"(s3));
#undef A4
#undef S8
            } while (__any_sync(0xffffffffu, !ok));
            STAMP2(24);
            const bool up = lane & 16, od = lane & 8;
            const float r0 = (up ? s2 : s0) + __shfl_xor_sync(0xffffffffu, up ? s0 : s2, 16), r1 = (up ? s3 : s1) + __shfl_xor_sync(0xffffffffu, up ? s1 : s3, 16);
            float y = (od ? r1 : r0) + __shfl_xor_sync(0xffffffffu, od ? r0 : r1, 8);
            y += __shfl_xor_sync(0xffffffffu, y, 4);
            p.out[dof] = __float2bfloat16_rn(hv + rbf(u2 + rbf(rbf(y) * rs)));
        }
    }
    if (warp == 19) asm volatile("cp.async.bulk.wait_group.read 0;\n" ::: "memory");
    if (b == 0 && tid < 8) *reinterpret_cast<volatile unsigned*>(p.s->hint + tid * 32 + 1) = lds32(s_cnt + 4) + 1u;
    STAMP(25);
    }
}

typedef CUresult (*PFN_tmEncode)(CUtensorMap*, CUtensorMapDataType, cuuint32_t, void*, const cuuint64_t*, const cuuint64_t*, const cuuint32_t*,
                                 const cuuint32_t*, CUtensorMapInterleave, CUtensorMapSwizzle, CUtensorMapL2promotion, CUtensorMapFloatOOBfill);

extern "C" void kernel_launch(void* const* d_in, const int* in_sizes, int n_in, void* d_out, int out_size) {
    Params p;
    p.x = (const bf16*)d_in[0];
    p.lar = (const bf16*)d_in[1];
    p.aim = (const bf16*)d_in[2];
    p.cre = (const bf16*)d_in[3];
    p.cim = (const bf16*)d_in[4];
    p.ldt = (const bf16*)d_in[5];
    p.dsk = (const bf16*)d_in[6];
    p.wr = (const bf16*)d_in[8];
    p.out = (bf16*)d_out;
    static PFN_tmEncode enc = nullptr;
    static void* scratch = nullptr;
    if (!enc) {
        cudaFuncSetAttribute(fused_kernel, cudaFuncAttributeMaxDynamicSharedMemorySize, SMEM_TOTAL);
        void* fn = nullptr;
        cudaDriverEntryPointQueryResult qr;
        cudaGetDriverEntryPoint("cuTensorMapEncodeTiled", &fn, cudaEnableDefault, &qr);
        enc = (PFN_tmEncode)fn;
        cudaGetSymbolAddress(&scratch, g_scratch);
    }
    p.s = (Scratch*)scratch;
    CUtensorMap tm_g, tm_u, tm_d, tm_x;
    const cuuint64_t dims[2] = {FF, DM}, strides[1] = {FF * 2};
    const cuuint32_t box[2] = {72, 48}, es[2] = {1, 1};
    enc(&tm_g, CU_TENSOR_MAP_DATA_TYPE_BFLOAT16, 2, d_in[9], dims, strides, box, es, CU_TENSOR_MAP_INTERLEAVE_NONE, CU_TENSOR_MAP_SWIZZLE_NONE,
        CU_TENSOR_MAP_L2_PROMOTION_NONE, CU_TENSOR_MAP_FLOAT_OOB_FILL_NONE);
    enc(&tm_u, CU_TENSOR_MAP_DATA_TYPE_BFLOAT16, 2, d_in[10], dims, strides, box, es, CU_TENSOR_MAP_INTERLEAVE_NONE, CU_TENSOR_MAP_SWIZZLE_NONE,
        CU_TENSOR_MAP_L2_PROMOTION_NONE, CU_TENSOR_MAP_FLOAT_OOB_FILL_NONE);
    const cuuint64_t ddims[2] = {DM / 2, FF}, dstrides[1] = {DM * 2};
    const cuuint32_t dbox[2] = {WD_PITCH / 4, 8};
    enc(&tm_d, CU_TENSOR_MAP_DATA_TYPE_UINT32, 2, d_in[11], ddims, dstrides, dbox, es, CU_TENSOR_MAP_INTERLEAVE_NONE, CU_TENSOR_MAP_SWIZZLE_NONE,
        CU_TENSOR_MAP_L2_PROMOTION_NONE, CU_TENSOR_MAP_FLOAT_OOB_FILL_NONE);
    const cuuint64_t xdims[4] = {DM, 128, 4, 4}, xstrides[3] = {DM * 8, DM * 2, DM * 1024};
    const cuuint32_t xbox[4] = {8, 128, 4, 2}, xes[4] = {1, 1, 1, 1};
    enc(&tm_x, CU_TENSOR_MAP_DATA_TYPE_BFLOAT16, 4, d_in[0], xdims, xstrides, xbox, xes, CU_TENSOR_MAP_INTERLEAVE_NONE, CU_TENSOR_MAP_SWIZZLE_NONE,
        CU_TENSOR_MAP_L2_PROMOTION_NONE, CU_TENSOR_MAP_FLOAT_OOB_FILL_NONE);
    fused_kernel<<<NCTA, NTHR, SMEM_TOTAL>>>(p, tm_g, tm_u, tm_d, tm_x);
}
```

```cpp
#include <cuda_runtime.h>
#include <cuda.h>
#include <cuda_fp16.h>
#include <cuda_bf16.h>
#include <stdint.h>

#define LSEQ 2048
#define DM 576
#define NST 128
#define FF 4608
#define NSEL 8
#define NCTA 128
#define NTHR 640
#define NWRK 640

typedef __nv_bfloat16 bf16;

#define SM_WG 0
#define SM_WU 41472
#define SM_XC (82944 - 32768)
#define SM_WD 82944
#define W_PITCH 144
#define WD_PITCH 592
#define SM_Z2 (SM_WD + 10240)
#define SM_XT (SM_PL - 18 * 1152)
#define SM_PL (SM_WD + 46080)
#define PL_HALF 1344
#define PLW_B 2624
#define PL_B (4 * PLW_B)
#define SM_U (SM_PL + 5 * PL_B)
#define UPAD 20
#define ULO_B ((UPAD + 128) * 16)
#define USLOT_B (2 * ULO_B)
#define SM_KW (SM_U + 5 * USLOT_B)
#define KW_B 3712
#define KW_PL 1216
#define KW_P 2400
#define KW_H 3440
#define SM_MISC (SM_KW + 5 * KW_B)
#define SM_LC (SM_MISC + 416)
#define SM_LNP (SM_LC + 768)
#define SM_RX (SM_LNP + 3840)
#define SMEM_TOTAL (SM_RX + 3088)
#define TBW PLW_B
#define SM_OUT SM_PL
#define SM_XS (SM_PL + 18432)
#define XS_PITCH 592
#define SM_GU (SM_PL + 23296)
#define SM_EX (SM_PL + 24576)
#define SM_KEYS SM_KW

struct __align__(128) Scratch {
    unsigned hint[8 * 32];
    unsigned flag[32];
    uint32_t key3[NCTA * 8];
    uint32_t key[NCTA * 8];
    uint32_t stat[LSEQ];
    uint32_t uT[64 * (LSEQ / 2)];
    uint32_t y[(NCTA + 96) * DM * 8];
    uint32_t part[288 * 64 * 16];
    uint32_t rows[(2 * NCTA + NSEL) * DM];
};
__device__ Scratch g_scratch;
#define STAMP(i)
#define STAMPX(i)
#define STAMPY(i)

__device__ __forceinline__ float rbf(float x) {
    uint32_t r;
    asm("cvt.rn.bf16x2.f32 %0, %1, %2;\n" : "=r"(r) : "f"(x), "f"(0.f));
    return __uint_as_float(r);
}
__device__ __forceinline__ uint32_t pack_bf16(float lo, float hi) {
    uint32_t r;
    asm("cvt.rn.bf16x2.f32 %0, %1, %2;\n" : "=r"(r) : "f"(hi), "f"(lo));
    return r;
}
__device__ __forceinline__ uint32_t pack_f16(float lo, float hi) {
    uint32_t r;
    asm("cvt.rn.f16x2.f32 %0, %1, %2;\n" : "=r"(r) : "f"(hi), "f"(lo));
    return r;
}
__device__ __forceinline__ uint32_t pack_f16_rz(float lo, float hi) {
    uint32_t r;
    asm("cvt.rz.f16x2.f32 %0, %1, %2;\n" : "=r"(r) : "f"(hi), "f"(lo));
    return r;
}
__device__ __forceinline__ float bf_lo(uint32_t w) { return __uint_as_float(w << 16); }
__device__ __forceinline__ float bf_hi(uint32_t w) { return __uint_as_float(w & 0xffff0000u); }
__device__ __forceinline__ uint32_t hadd2_bf(uint32_t a, uint32_t b) {
    __nv_bfloat162 r = __hadd2_rn(*reinterpret_cast<__nv_bfloat162*>(&a), *reinterpret_cast<__nv_bfloat162*>(&b));
    return *reinterpret_cast<uint32_t*>(&r);
}
__device__ __forceinline__ uint32_t hsub2_bf(uint32_t a, uint32_t b) {
    __nv_bfloat162 r = __hsub2_rn(*reinterpret_cast<__nv_bfloat162*>(&a), *reinterpret_cast<__nv_bfloat162*>(&b));
    return *reinterpret_cast<uint32_t*>(&r);
}
__device__ __forceinline__ uint32_t hmul2_bf(uint32_t a, uint32_t b) {
    __nv_bfloat162 r = __hmul2_rn(*reinterpret_cast<__nv_bfloat162*>(&a), *reinterpret_cast<__nv_bfloat162*>(&b));
    return *reinterpret_cast<uint32_t*>(&r);
}
__device__ __forceinline__ uint32_t hfma2_bf(uint32_t a, uint32_t b, uint32_t c) { uint32_t r; asm("fma.rn.bf16x2 %0, %1, %2, %3;\n" : "=r"(r) : "r"(a), "r"(b), "r"(c)); return r; }
__device__ __forceinline__ uint32_t hmul2(uint32_t a, uint32_t b) { uint32_t r; asm("mul.rn.f16x2 %0, %1, %2;\n" : "=r"(r) : "r"(a), "r"(b)); return r; }
__device__ __forceinline__ uint32_t hadd2(uint32_t a, uint32_t b) { uint32_t r; asm("add.rn.f16x2 %0, %1, %2;\n" : "=r"(r) : "r"(a), "r"(b)); return r; }
__device__ __forceinline__ uint32_t hfma2(uint32_t a, uint32_t b, uint32_t c) { uint32_t r; asm("fma.rn.f16x2 %0, %1, %2, %3;\n" : "=r"(r) : "r"(a), "r"(b), "r"(c)); return r; }
__device__ __forceinline__ uint32_t hfms2(uint32_t a, uint32_t b, uint32_t c) {
    uint32_t r;
    asm("{\n.reg .b32 n;\nneg.f16x2 n, %2;\nfma.rn.f16x2 %0, %1, n, %3;\n}\n" : "=r"(r) : "r"(a), "r"(b), "r"(c));
    return r;
}
__device__ __forceinline__ uint32_t nzw(uint32_t w) { uint32_t r; asm("max.u32 %0, %1, 1;\n" : "=r"(r) : "r"(w)); return r; }
__device__ __forceinline__ uint32_t nzf(float f) { const uint32_t w = __float_as_uint(f); return w ? w : 0x80000000u; }
__device__ __forceinline__ uint32_t smem_u32(const void* p) { return (uint32_t)__cvta_generic_to_shared(p); }
__device__ __forceinline__ uint32_t lds32(uint32_t addr) {
    uint32_t v;
    asm volatile("ld.shared.u32 %0, [%1];\n" : "=r"(v) : "r"(addr) : "memory");
    return v;
}
__device__ __forceinline__ uint32_t lds16(uint32_t addr) {
    unsigned short v;
    asm volatile("ld.shared.u16 %0, [%1];\n" : "=h"(v) : "r"(addr) : "memory");
    return v;
}
__device__ __forceinline__ uint2 lds64(uint32_t addr) {
    uint2 v;
    asm volatile("ld.shared.v2.u32 {%0,%1}, [%2];\n" : "=r"(v.x), "=r"(v.y) : "r"(addr) : "memory");
    return v;
}
__device__ __forceinline__ uint4 lds128(uint32_t addr) {
    uint4 v;
    asm volatile("ld.shared.v4.u32 {%0,%1,%2,%3}, [%4];\n" : "=r"(v.x), "=r"(v.y), "=r"(v.z), "=r"(v.w) : "r"(addr) : "memory");
    return v;
}
__device__ __forceinline__ float ldsf(uint32_t addr) { return __uint_as_float(lds32(addr)); }
__device__ __forceinline__ void sts32(uint32_t addr, uint32_t v) { asm volatile("st.shared.u32 [%0], %1;\n" ::"r"(addr), "r"(v) : "memory"); }
__device__ __forceinline__ void sts16(uint32_t addr, uint32_t v) { asm volatile("st.shared.u16 [%0], %1;\n" ::"r"(addr), "h"((unsigned short)v) : "memory"); }
__device__ __forceinline__ void stsf(uint32_t addr, float v) { sts32(addr, __float_as_uint(v)); }
__device__ __forceinline__ void sts64(uint32_t addr, uint32_t a, uint32_t b) { asm volatile("st.shared.v2.u32 [%0], {%1,%2};\n" ::"r"(addr), "r"(a), "r"(b) : "memory"); }
__device__ __forceinline__ void sts64f(uint32_t addr, float a, float b) { sts64(addr, __float_as_uint(a), __float_as_uint(b)); }
__device__ __forceinline__ void sts128(uint32_t addr, uint32_t a, uint32_t b, uint32_t c, uint32_t d) {
    asm volatile("st.shared.v4.u32 [%0], {%1,%2,%3,%4};\n" ::"r"(addr), "r"(a), "r"(b), "r"(c), "r"(d) : "memory");
}
__device__ __forceinline__ void sts128f(uint32_t addr, const float (&v)[4]) {
    sts128(addr, __float_as_uint(v[0]), __float_as_uint(v[1]), __float_as_uint(v[2]), __float_as_uint(v[3]));
}
__device__ __forceinline__ void ldsm_x4(uint32_t& r0, uint32_t& r1, uint32_t& r2, uint32_t& r3, uint32_t addr) {
    asm volatile("ldmatrix.sync.aligned.m8n8.x4.shared.b16 {%0,%1,%2,%3}, [%4];\n"
                 : "=r"(r0), "=r"(r1), "=r"(r2), "=r"(r3) : "r"(addr) : "memory");
}
__device__ __forceinline__ void ldsm_x4_t(uint32_t& r0, uint32_t& r1, uint32_t& r2, uint32_t& r3, uint32_t addr) {
    asm volatile("ldmatrix.sync.aligned.m8n8.x4.trans.shared.b16 {%0,%1,%2,%3}, [%4];\n"
                 : "=r"(r0), "=r"(r1), "=r"(r2), "=r"(r3) : "r"(addr) : "memory");
}
__device__ __forceinline__ void ldsm_x2_t(uint32_t& r0, uint32_t& r1, uint32_t addr) {
    asm volatile("ldmatrix.sync.aligned.m8n8.x2.trans.shared.b16 {%0,%1}, [%2];\n" : "=r"(r0), "=r"(r1) : "r"(addr) : "memory");
}
__device__ __forceinline__ void ldsm_x1_t(uint32_t& r0, uint32_t addr) {
    asm volatile("ldmatrix.sync.aligned.m8n8.x1.trans.shared.b16 {%0}, [%1];\n" : "=r"(r0) : "r"(addr) : "memory");
}
__device__ __forceinline__ void stsm_x4(uint32_t addr, uint32_t r0, uint32_t r1, uint32_t r2, uint32_t r3) {
    asm volatile("stmatrix.sync.aligned.m8n8.x4.shared.b16 [%0], {%1,%2,%3,%4};\n" ::"r"(addr), "r"(r0), "r"(r1), "r"(r2), "r"(r3) : "memory");
}
__device__ __forceinline__ void stsm_x4_t(uint32_t addr, uint32_t r0, uint32_t r1, uint32_t r2, uint32_t r3) {
    asm volatile("stmatrix.sync.aligned.m8n8.x4.trans.shared.b16 [%0], {%1,%2,%3,%4};\n" ::"r"(addr), "r"(r0), "r"(r1), "r"(r2), "r"(r3) : "memory");
}
__device__ __forceinline__ uint32_t movm(uint32_t a) {
    uint32_t d;
    asm volatile("movmatrix.sync.aligned.m8n8.trans.b16 %0, %1;\n" : "=r"(d) : "r"(a));
    return d;
}
__device__ __forceinline__ void mma_f16(float (&c)[4], uint32_t a0, uint32_t a1, uint32_t a2, uint32_t a3, uint32_t b0, uint32_t b1) {
    asm volatile(
        "mma.sync.aligned.m16n8k16.row.col.f32.f16.f16.f32 {%0,%1,%2,%3}, {%4,%5,%6,%7}, {%8,%9}, {%0,%1,%2,%3};\n"
        : "+f"(c[0]), "+f"(c[1]), "+f"(c[2]), "+f"(c[3])
        : "r"(a0), "r"(a1), "r"(a2), "r"(a3), "r"(b0), "r"(b1));
}
__device__ __forceinline__ void mma_bf16(float (&c)[4], uint32_t a0, uint32_t a1, uint32_t a2, uint32_t a3, uint32_t b0, uint32_t b1) {
    asm volatile(
        "mma.sync.aligned.m16n8k16.row.col.f32.bf16.bf16.f32 {%0,%1,%2,%3}, {%4,%5,%6,%7}, {%8,%9}, {%0,%1,%2,%3};\n"
        : "+f"(c[0]), "+f"(c[1]), "+f"(c[2]), "+f"(c[3])
        : "r"(a0), "r"(a1), "r"(a2), "r"(a3), "r"(b0), "r"(b1));
}
__device__ __forceinline__ void mma_bf16_k8(float (&c)[4], uint32_t a0, uint32_t a1, uint32_t b0) {
    asm volatile("mma.sync.aligned.m16n8k8.row.col.f32.bf16.bf16.f32 {%0,%1,%2,%3}, {%4,%5}, {%6}, {%0,%1,%2,%3};\n"
                 : "+f"(c[0]), "+f"(c[1]), "+f"(c[2]), "+f"(c[3]) : "r"(a0), "r"(a1), "r"(b0));
}
__device__ __forceinline__ void bar_sync(int id, int n) { asm volatile("bar.sync %0, %1;\n" ::"r"(id), "r"(n) : "memory"); }
__device__ __forceinline__ void bar_arrive(int id, int n) { asm volatile("bar.arrive %0, %1;\n" ::"r"(id), "r"(n) : "memory"); }
__device__ __forceinline__ bool bar_or(int id, int n, bool v) {
    uint32_t r;
    asm volatile("{\n.reg .pred p, q;\nsetp.ne.u32 p, %3, 0;\nbar.red.or.pred q, %1, %2, p;\nselp.u32 %0, 1, 0, q;\n}\n" : "=r"(r) : "r"(id), "r"(n), "r"((uint32_t)v) : "memory");
    return r;
}
__device__ __forceinline__ uint32_t and3(uint32_t a, uint32_t b, uint32_t c) { uint32_t r; asm("lop3.b32 %0, %1, %2, %3, 0x80;\n" : "=r"(r) : "r"(a), "r"(b), "r"(c)); return r; }
__device__ __forceinline__ uint32_t or3(uint32_t a, uint32_t b, uint32_t c) { uint32_t r; asm("lop3.b32 %0, %1, %2, %3, 0xfe;\n" : "=r"(r) : "r"(a), "r"(b), "r"(c)); return r; }
__device__ __forceinline__ uint32_t min3(uint32_t a, uint32_t b, uint32_t c) { uint32_t r; asm("{\n.reg .u32 t;\nmin.u32 t, %2, %3;\nmin.u32 %0, %1, t;\n}\n" : "=r"(r) : "r"(a), "r"(b), "r"(c)); return r; }
__device__ __forceinline__ uint32_t xor_or(uint32_t a, uint32_t b, uint32_t c) { uint32_t r; asm("lop3.b32 %0, %1, %2, %3, 0x7e;\n" : "=r"(r) : "r"(a), "r"(b), "r"(c)); return r; }
__device__ __forceinline__ uint32_t pin(uint32_t v) { uint32_t r; asm volatile("shfl.sync.bfly.b32 %0, %1, 0, 0x1f, 0xffffffff;\n" : "=r"(r) : "r"(v) : "memory"); return r; }
__device__ __forceinline__ uint4 ld_poll(const void* p) {
    uint4 v;
    asm volatile("ld.relaxed.gpu.global.v4.u32 {%0,%1,%2,%3}, [%4];\n" : "=r"(v.x), "=r"(v.y), "=r"(v.z), "=r"(v.w) : "l"(p) : "memory");
    return v;
}
__device__ __forceinline__ uint2 ld_poll64(const void* p) {
    uint2 v;
    asm volatile("ld.relaxed.gpu.global.v2.u32 {%0,%1}, [%2];\n" : "=r"(v.x), "=r"(v.y) : "l"(p) : "memory");
    return v;
}
__device__ __forceinline__ uint32_t ld_poll32(const void* p) {
    uint32_t v;
    asm volatile("ld.relaxed.gpu.global.u32 %0, [%1];\n" : "=r"(v) : "l"(p) : "memory");
    return v;
}
__device__ __forceinline__ uint32_t ld_acquire32(const void* p) {
    uint32_t v;
    asm volatile("ld.acquire.gpu.global.u32 %0, [%1];\n" : "=r"(v) : "l"(p) : "memory");
    return v;
}
__device__ __forceinline__ uint4 ldg128(const void* p) {
    uint4 v;
    asm volatile("ld.global.nc.v4.u32 {%0,%1,%2,%3}, [%4];\n" : "=r"(v.x), "=r"(v.y), "=r"(v.z), "=r"(v.w) : "l"(p));
    return v;
}
__device__ __forceinline__ uint2 ldg64(const void* p) {
    uint2 v;
    asm volatile("ld.global.nc.v2.u32 {%0,%1}, [%2];\n" : "=r"(v.x), "=r"(v.y) : "l"(p));
    return v;
}
__device__ __forceinline__ uint32_t ldg16(const void* p) {
    uint32_t v;
    asm volatile("ld.global.nc.u16 %0, [%1];\n" : "=r"(v) : "l"(p));
    return v;
}
__device__ __forceinline__ uint4 ldo128(const void* p) {
    uint4 v;
    asm volatile("ld.relaxed.cta.global.v4.u32 {%0,%1,%2,%3}, [%4];\n" : "=r"(v.x), "=r"(v.y), "=r"(v.z), "=r"(v.w) : "l"(p) : "memory");
    return v;
}
__device__ __forceinline__ uint2 ldo64(const void* p) {
    uint2 v;
    asm volatile("ld.relaxed.cta.global.v2.u32 {%0,%1}, [%2];\n" : "=r"(v.x), "=r"(v.y) : "l"(p) : "memory");
    return v;
}
__device__ __forceinline__ uint32_t ldo16(const void* p) {
    uint32_t v;
    asm volatile("ld.relaxed.cta.global.u16 %0, [%1];\n" : "=r"(v) : "l"(p) : "memory");
    return v;
}
__device__ __forceinline__ void stg128(void* p, uint32_t a, uint32_t b, uint32_t c, uint32_t d) {
    asm volatile("st.global.v4.u32 [%0], {%1,%2,%3,%4};\n" ::"l"(p), "r"(a), "r"(b), "r"(c), "r"(d) : "memory");
}
__device__ __forceinline__ void stg64(void* p, uint32_t a, uint32_t b) { asm volatile("st.global.v2.u32 [%0], {%1,%2};\n" ::"l"(p), "r"(a), "r"(b) : "memory"); }
__device__ __forceinline__ uint32_t min4(const uint4& v) { return min(min(v.x, v.y), min(v.z, v.w)); }
#define SPIN_LIMIT (1 << 21)
#define TRAP() __trap()
__device__ __forceinline__ void mbar_init(uint32_t bar, uint32_t cnt) { asm volatile("mbarrier.init.shared::cta.b64 [%0], %1;\n" ::"r"(bar), "r"(cnt) : "memory"); }
__device__ __forceinline__ void mbar_expect(uint32_t bar, uint32_t bytes) {
    asm volatile("mbarrier.arrive.expect_tx.shared::cta.b64 _, [%0], %1;\n" ::"r"(bar), "r"(bytes) : "memory");
}
__device__ __forceinline__ void mbar_arrive(uint32_t bar) { asm volatile("mbarrier.arrive.shared::cta.b64 _, [%0];\n" ::"r"(bar) : "memory"); }
__device__ __forceinline__ void mbar_wait_cluster(uint32_t bar) {
    asm volatile(
        "{\n.reg .pred p;\n"
        "W_%=:\n"
        "mbarrier.try_wait.parity.acquire.cluster.shared::cta.b64 p, [%0], 0;\n"
        "@!p bra W_%=;\n}\n" ::"r"(bar) : "memory");
}
__device__ __forceinline__ void mbar_wait(uint32_t bar) {
    asm volatile(
        "{\n.reg .pred p;\n"
        "W_%=:\n"
        "mbarrier.try_wait.parity.shared::cta.b64 p, [%0], 0;\n"
        "@!p bra W_%=;\n}\n" ::"r"(bar) : "memory");
}
__device__ __forceinline__ void mbar_wait1(uint32_t bar) {
    asm volatile(
        "{\n.reg .pred p;\n"
        "W_%=:\n"
        "mbarrier.try_wait.parity.shared::cta.b64 p, [%0], 1;\n"
        "@!p bra W_%=;\n}\n" ::"r"(bar) : "memory");
}
__device__ __forceinline__ bool mbar_test(uint32_t bar) {
    uint32_t r;
    asm volatile("{\n.reg .pred p;\nmbarrier.test_wait.parity.shared::cta.b64 p, [%1], 0;\nselp.u32 %0, 1, 0, p;\n}\n" : "=r"(r) : "r"(bar) : "memory");
    return __any_sync(0xffffffffu, r);
}
__device__ __forceinline__ void bulk_g2s(uint32_t dst, const void* src, uint32_t bytes, uint32_t bar) {
    asm volatile("cp.async.bulk.shared::cluster.global.mbarrier::complete_tx::bytes [%0], [%1], %2, [%3];\n" ::"r"(dst), "l"(src), "r"(bytes), "r"(bar) : "memory");
}
__device__ __forceinline__ void bulk_s2g(void* dst, uint32_t src, uint32_t bytes) {
    asm volatile("cp.async.bulk.global.shared::cta.bulk_group [%0], [%1], %2;\ncp.async.bulk.commit_group;\n" ::"l"(dst), "r"(src), "r"(bytes) : "memory");
}
__device__ __forceinline__ void bulk_s2g_nc(void* dst, uint32_t src, uint32_t bytes) {
    asm volatile("cp.async.bulk.global.shared::cta.bulk_group [%0], [%1], %2;\n" ::"l"(dst), "r"(src), "r"(bytes) : "memory");
}
__device__ __forceinline__ void tma_2d(uint32_t dst, const CUtensorMap* tm, int c0, int c1, uint32_t bar) {
    asm volatile("cp.async.bulk.tensor.2d.shared::cluster.global.mbarrier::complete_tx::bytes [%0], [%1, {%3, %4}], [%2];\n"
                 ::"r"(dst), "l"(tm), "r"(bar), "r"(c0), "r"(c1) : "memory");
}
__device__ __forceinline__ void tma_4d(uint32_t dst, const CUtensorMap* tm, int c0, int c3, uint32_t bar) {
    asm volatile("cp.async.bulk.tensor.4d.shared::cluster.global.mbarrier::complete_tx::bytes [%0], [%1, {%3, %4, %4, %5}], [%2];\n"
                 ::"r"(dst), "l"(tm), "r"(bar), "r"(c0), "r"(0), "r"(c3) : "memory");
}
__device__ __forceinline__ void tma_4d_mc(uint32_t dst, const CUtensorMap* tm, int c0, int c3, uint32_t bar) {
    asm volatile("cp.async.bulk.tensor.4d.shared::cluster.global.mbarrier::complete_tx::bytes.multicast::cluster [%0], [%1, {%3, %4, %4, %5}], [%2], %6;\n"
                 ::"r"(dst), "l"(tm), "r"(bar), "r"(c0), "r"(0), "r"(c3), "h"((unsigned short)3) : "memory");
}
__device__ __forceinline__ void l2_prefetch(const void* src, uint32_t bytes) {
    asm volatile("cp.async.bulk.prefetch.L2.global [%0], %1;\n" ::"l"(src), "r"(bytes) : "memory");
}
__device__ __forceinline__ bool elect_one() {
    uint32_t r;
    asm volatile("{\n.reg .pred p;\nelect.sync _|p, 0xffffffff;\nselp.u32 %0, 1, 0, p;\n}\n" : "=r"(r));
    return r;
}
__device__ __forceinline__ void delay(uint32_t clks) {
    uint32_t t0, t1;
    asm volatile("mov.u32 %0, %%clock;" : "=r"(t0) :: "memory");
    do { asm volatile("mov.u32 %0, %%clock;" : "=r"(t1) :: "memory"); } while (t1 - t0 < clks);
}
__device__ __forceinline__ void fence_async() { asm volatile("fence.proxy.async.shared::cta;\n" ::: "memory"); }

__device__ __forceinline__ float2 cmul(float2 a, float2 b) {
    return make_float2(fmaf(a.x, b.x, -a.y * b.y), fmaf(a.x, b.y, a.y * b.x));
}
__device__ __forceinline__ float2 csq(float2 a) {
    float p = a.x * a.y;
    return make_float2(fmaf(a.x, a.x, -a.y * a.y), p + p);
}
__device__ __forceinline__ float ex2_approx(float x) { float r; asm("ex2.approx.ftz.f32 %0, %1;\n" : "=f"(r) : "f"(x)); return r; }
__device__ __forceinline__ float exp_bf(float x) { return rbf(ex2_approx(__fmul_ru(x, 1.4426950408889634f))); }
__device__ __forceinline__ float2 cexp_e(float lr2, float li, float e) {
    const float m = ex2_approx(lr2 * e);
    return make_float2(m * __cosf(li * e), m * __sinf(li * e));
}
__device__ __forceinline__ float rcp_approx(float x) { float r; asm("rcp.approx.ftz.f32 %0, %1;\n" : "=f"(r) : "f"(x)); return r; }
__device__ __forceinline__ float sigmoid_f(float x) { return rcp_approx(1.0f + ex2_approx(x * -1.4426950408889634f)); }
__device__ __forceinline__ float sqrt_approx(float x) { float r; asm("sqrt.approx.ftz.f32 %0, %1;\n" : "=f"(r) : "f"(x)); return r; }

__device__ __forceinline__ void wg_fence() { asm volatile("wgmma.fence.sync.aligned;\n" ::: "memory"); }
__device__ __forceinline__ void wg_commit() { asm volatile("wgmma.commit_group.sync.aligned;\n" ::: "memory"); }
__device__ __forceinline__ void wg_wait0() { asm volatile("wgmma.wait_group.sync.aligned 0;\n" ::: "memory"); }
template <int T> __device__ __forceinline__ void wg_mma(float (&acc)[16][4], const uint32_t* a, uint64_t desc);
template <int T> __device__ __forceinline__ void wg_first(float (&acc)[16][4], const uint32_t* a, uint64_t desc);
template <> __device__ __forceinline__ void wg_mma<0>(float (&acc)[16][4], const uint32_t* a, uint64_t desc) {
    asm volatile("wgmma.mma_async.sync.aligned.m64n128k16.f32.f16.f16 {%0,%1,%2,%3,%4,%5,%6,%7,%8,%9,%10,%11,%12,%13,%14,%15,%16,%17,%18,%19,%20,%21,%22,%23,%24,%25,%26,%27,%28,%29,%30,%31,%32,%33,%34,%35,%36,%37,%38,%39,%40,%41,%42,%43,%44,%45,%46,%47,%48,%49,%50,%51,%52,%53,%54,%55,%56,%57,%58,%59,%60,%61,%62,%63}, {%64,%65,%66,%67}, %68, 1, 1, 1, 0;\n"
                 : "+f"(acc[0][0]), "+f"(acc[0][1]), "+f"(acc[0][2]), "+f"(acc[0][3]), "+f"(acc[1][0]), "+f"(acc[1][1]), "+f"(acc[1][2]), "+f"(acc[1][3]), "+f"(acc[2][0]), "+f"(acc[2][1]), "+f"(acc[2][2]), "+f"(acc[2][3]), "+f"(acc[3][0]), "+f"(acc[3][1]), "+f"(acc[3][2]), "+f"(acc[3][3]), "+f"(acc[4][0]), "+f"(acc[4][1]), "+f"(acc[4][2]), "+f"(acc[4][3]), "+f"(acc[5][0]), "+f"(acc[5][1]), "+f"(acc[5][2]), "+f"(acc[5][3]), "+f"(acc[6][0]), "+f"(acc[6][1]), "+f"(acc[6][2]), "+f"(acc[6][3]), "+f"(acc[7][0]), "+f"(acc[7][1]), "+f"(acc[7][2]), "+f"(acc[7][3]), "+f"(acc[8][0]), "+f"(acc[8][1]), "+f"(acc[8][2]), "+f"(acc[8][3]), "+f"(acc[9][0]), "+f"(acc[9][1]), "+f"(acc[9][2]), "+f"(acc[9][3]), "+f"(acc[10][0]), "+f"(acc[10][1]), "+f"(acc[10][2]), "+f"(acc[10][3]), "+f"(acc[11][0]), "+f"(acc[11][1]), "+f"(acc[11][2]), "+f"(acc[11][3]), "+f"(acc[12][0]), "+f"(acc[12][1]), "+f"(acc[12][2]), "+f"(acc[12][3]), "+f"(acc[13][0]), "+f"(acc[13][1]), "+f"(acc[13][2]), "+f"(acc[13][3]), "+f"(acc[14][0]), "+f"(acc[14][1]), "+f"(acc[14][2]), "+f"(acc[14][3]), "+f"(acc[15][0]), "+f"(acc[15][1]), "+f"(acc[15][2]), "+f"(acc[15][3])
                 : "r"(a[0]), "r"(a[1]), "r"(a[2]), "r"(a[3]), "l"(desc));
}
template <> __device__ __forceinline__ void wg_mma<2>(float (&acc)[16][4], const uint32_t* a, uint64_t desc) {
    asm volatile("wgmma.mma_async.sync.aligned.m64n112k16.f32.f16.f16 {%0,%1,%2,%3,%4,%5,%6,%7,%8,%9,%10,%11,%12,%13,%14,%15,%16,%17,%18,%19,%20,%21,%22,%23,%24,%25,%26,%27,%28,%29,%30,%31,%32,%33,%34,%35,%36,%37,%38,%39,%40,%41,%42,%43,%44,%45,%46,%47,%48,%49,%50,%51,%52,%53,%54,%55}, {%56,%57,%58,%59}, %60, 1, 1, 1, 0;\n"
                 : "+f"(acc[2][0]), "+f"(acc[2][1]), "+f"(acc[2][2]), "+f"(acc[2][3]), "+f"(acc[3][0]), "+f"(acc[3][1]), "+f"(acc[3][2]), "+f"(acc[3][3]), "+f"(acc[4][0]), "+f"(acc[4][1]), "+f"(acc[4][2]), "+f"(acc[4][3]), "+f"(acc[5][0]), "+f"(acc[5][1]), "+f"(acc[5][2]), "+f"(acc[5][3]), "+f"(acc[6][0]), "+f"(acc[6][1]), "+f"(acc[6][2]), "+f"(acc[6][3]), "+f"(acc[7][0]), "+f"(acc[7][1]), "+f"(acc[7][2]), "+f"(acc[7][3]), "+f"(acc[8][0]), "+f"(acc[8][1]), "+f"(acc[8][2]), "+f"(acc[8][3]), "+f"(acc[9][0]), "+f"(acc[9][1]), "+f"(acc[9][2]), "+f"(acc[9][3]), "+f"(acc[10][0]), "+f"(acc[10][1]), "+f"(acc[10][2]), "+f"(acc[10][3]), "+f"(acc[11][0]), "+f"(acc[11][1]), "+f"(acc[11][2]), "+f"(acc[11][3]), "+f"(acc[12][0]), "+f"(acc[12][1]), "+f"(acc[12][2]), "+f"(acc[12][3]), "+f"(acc[13][0]), "+f"(acc[13][1]), "+f"(acc[13][2]), "+f"(acc[13][3]), "+f"(acc[14][0]), "+f"(acc[14][1]), "+f"(acc[14][2]), "+f"(acc[14][3]), "+f"(acc[15][0]), "+f"(acc[15][1]), "+f"(acc[15][2]), "+f"(acc[15][3])
                 : "r"(a[0]), "r"(a[1]), "r"(a[2]), "r"(a[3]), "l"(desc));
}
template <> __device__ __forceinline__ void wg_mma<4>(float (&acc)[16][4], const uint32_t* a, uint64_t desc) {
    asm volatile("wgmma.mma_async.sync.aligned.m64n96k16.f32.f16.f16 {%0,%1,%2,%3,%4,%5,%6,%7,%8,%9,%10,%11,%12,%13,%14,%15,%16,%17,%18,%19,%20,%21,%22,%23,%24,%25,%26,%27,%28,%29,%30,%31,%32,%33,%34,%35,%36,%37,%38,%39,%40,%41,%42,%43,%44,%45,%46,%47}, {%48,%49,%50,%51}, %52, 1, 1, 1, 0;\n"
                 : "+f"(acc[4][0]), "+f"(acc[4][1]), "+f"(acc[4][2]), "+f"(acc[4][3]), "+f"(acc[5][0]), "+f"(acc[5][1]), "+f"(acc[5][2]), "+f"(acc[5][3]), "+f"(acc[6][0]), "+f"(acc[6][1]), "+f"(acc[6][2]), "+f"(acc[6][3]), "+f"(acc[7][0]), "+f"(acc[7][1]), "+f"(acc[7][2]), "+f"(acc[7][3]), "+f"(acc[8][0]), "+f"(acc[8][1]), "+f"(acc[8][2]), "+f"(acc[8][3]), "+f"(acc[9][0]), "+f"(acc[9][1]), "+f"(acc[9][2]), "+f"(acc[9][3]), "+f"(acc[10][0]), "+f"(acc[10][1]), "+f"(acc[10][2]), "+f"(acc[10][3]), "+f"(acc[11][0]), "+f"(acc[11][1]), "+f"(acc[11][2]), "+f"(acc[11][3]), "+f"(acc[12][0]), "+f"(acc[12][1]), "+f"(acc[12][2]), "+f"(acc[12][3]), "+f"(acc[13][0]), "+f"(acc[13][1]), "+f"(acc[13][2]), "+f"(acc[13][3]), "+f"(acc[14][0]), "+f"(acc[14][1]), "+f"(acc[14][2]), "+f"(acc[14][3]), "+f"(acc[15][0]), "+f"(acc[15][1]), "+f"(acc[15][2]), "+f"(acc[15][3])
                 : "r"(a[0]), "r"(a[1]), "r"(a[2]), "r"(a[3]), "l"(desc));
}
template <> __device__ __forceinline__ void wg_mma<6>(float (&acc)[16][4], const uint32_t* a, uint64_t desc) {
    asm volatile("wgmma.mma_async.sync.aligned.m64n80k16.f32.f16.f16 {%0,%1,%2,%3,%4,%5,%6,%7,%8,%9,%10,%11,%12,%13,%14,%15,%16,%17,%18,%19,%20,%21,%22,%23,%24,%25,%26,%27,%28,%29,%30,%31,%32,%33,%34,%35,%36,%37,%38,%39}, {%40,%41,%42,%43}, %44, 1, 1, 1, 0;\n"
                 : "+f"(acc[6][0]), "+f"(acc[6][1]), "+f"(acc[6][2]), "+f"(acc[6][3]), "+f"(acc[7][0]), "+f"(acc[7][1]), "+f"(acc[7][2]), "+f"(acc[7][3]), "+f"(acc[8][0]), "+f"(acc[8][1]), "+f"(acc[8][2]), "+f"(acc[8][3]), "+f"(acc[9][0]), "+f"(acc[9][1]), "+f"(acc[9][2]), "+f"(acc[9][3]), "+f"(acc[10][0]), "+f"(acc[10][1]), "+f"(acc[10][2]), "+f"(acc[10][3]), "+f"(acc[11][0]), "+f"(acc[11][1]), "+f"(acc[11][2]), "+f"(acc[11][3]), "+f"(acc[12][0]), "+f"(acc[12][1]), "+f"(acc[12][2]), "+f"(acc[12][3]), "+f"(acc[13][0]), "+f"(acc[13][1]), "+f"(acc[13][2]), "+f"(acc[13][3]), "+f"(acc[14][0]), "+f"(acc[14][1]), "+f"(acc[14][2]), "+f"(acc[14][3]), "+f"(acc[15][0]), "+f"(acc[15][1]), "+f"(acc[15][2]), "+f"(acc[15][3])
                 : "r"(a[0]), "r"(a[1]), "r"(a[2]), "r"(a[3]), "l"(desc));
}
template <> __device__ __forceinline__ void wg_mma<8>(float (&acc)[16][4], const uint32_t* a, uint64_t desc) {
    asm volatile("wgmma.mma_async.sync.aligned.m64n64k16.f32.f16.f16 {%0,%1,%2,%3,%4,%5,%6,%7,%8,%9,%10,%11,%12,%13,%14,%15,%16,%17,%18,%19,%20,%21,%22,%23,%24,%25,%26,%27,%28,%29,%30,%31}, {%32,%33,%34,%35}, %36, 1, 1, 1, 0;\n"
                 : "+f"(acc[8][0]), "+f"(acc[8][1]), "+f"(acc[8][2]), "+f"(acc[8][3]), "+f"(acc[9][0]), "+f"(acc[9][1]), "+f"(acc[9][2]), "+f"(acc[9][3]), "+f"(acc[10][0]), "+f"(acc[10][1]), "+f"(acc[10][2]), "+f"(acc[10][3]), "+f"(acc[11][0]), "+f"(acc[11][1]), "+f"(acc[11][2]), "+f"(acc[11][3]), "+f"(acc[12][0]), "+f"(acc[12][1]), "+f"(acc[12][2]), "+f"(acc[12][3]), "+f"(acc[13][0]), "+f"(acc[13][1]), "+f"(acc[13][2]), "+f"(acc[13][3]), "+f"(acc[14][0]), "+f"(acc[14][1]), "+f"(acc[14][2]), "+f"(acc[14][3]), "+f"(acc[15][0]), "+f"(acc[15][1]), "+f"(acc[15][2]), "+f"(acc[15][3])
                 : "r"(a[0]), "r"(a[1]), "r"(a[2]), "r"(a[3]), "l"(desc));
}
template <> __device__ __forceinline__ void wg_mma<10>(float (&acc)[16][4], const uint32_t* a, uint64_t desc) {
    asm volatile("wgmma.mma_async.sync.aligned.m64n48k16.f32.f16.f16 {%0,%1,%2,%3,%4,%5,%6,%7,%8,%9,%10,%11,%12,%13,%14,%15,%16,%17,%18,%19,%20,%21,%22,%23}, {%24,%25,%26,%27}, %28, 1, 1, 1, 0;\n"
                 : "+f"(acc[10][0]), "+f"(acc[10][1]), "+f"(acc[10][2]), "+f"(acc[10][3]), "+f"(acc[11][0]), "+f"(acc[11][1]), "+f"(acc[11][2]), "+f"(acc[11][3]), "+f"(acc[12][0]), "+f"(acc[12][1]), "+f"(acc[12][2]), "+f"(acc[12][3]), "+f"(acc[13][0]), "+f"(acc[13][1]), "+f"(acc[13][2]), "+f"(acc[13][3]), "+f"(acc[14][0]), "+f"(acc[14][1]), "+f"(acc[14][2]), "+f"(acc[14][3]), "+f"(acc[15][0]), "+f"(acc[15][1]), "+f"(acc[15][2]), "+f"(acc[15][3])
                 : "r"(a[0]), "r"(a[1]), "r"(a[2]), "r"(a[3]), "l"(desc));
}
template <> __device__ __forceinline__ void wg_mma<12>(float (&acc)[16][4], const uint32_t* a, uint64_t desc) {
    asm volatile("wgmma.mma_async.sync.aligned.m64n32k16.f32.f16.f16 {%0,%1,%2,%3,%4,%5,%6,%7,%8,%9,%10,%11,%12,%13,%14,%15}, {%16,%17,%18,%19}, %20, 1, 1, 1, 0;\n"
                 : "+f"(acc[12][0]), "+f"(acc[12][1]), "+f"(acc[12][2]), "+f"(acc[12][3]), "+f"(acc[13][0]), "+f"(acc[13][1]), "+f"(acc[13][2]), "+f"(acc[13][3]), "+f"(acc[14][0]), "+f"(acc[14][1]), "+f"(acc[14][2]), "+f"(acc[14][3]), "+f"(acc[15][0]), "+f"(acc[15][1]), "+f"(acc[15][2]), "+f"(acc[15][3])
                 : "r"(a[0]), "r"(a[1]), "r"(a[2]), "r"(a[3]), "l"(desc));
}
template <> __device__ __forceinline__ void wg_mma<14>(float (&acc)[16][4], const uint32_t* a, uint64_t desc) {
    asm volatile("wgmma.mma_async.sync.aligned.m64n16k16.f32.f16.f16 {%0,%1,%2,%3,%4,%5,%6,%7}, {%8,%9,%10,%11}, %12, 1, 1, 1, 0;\n"
                 : "+f"(acc[14][0]), "+f"(acc[14][1]), "+f"(acc[14][2]), "+f"(acc[14][3]), "+f"(acc[15][0]), "+f"(acc[15][1]), "+f"(acc[15][2]), "+f"(acc[15][3])
                 : "r"(a[0]), "r"(a[1]), "r"(a[2]), "r"(a[3]), "l"(desc));
}
template <> __device__ __forceinline__ void wg_first<0>(float (&acc)[16][4], const uint32_t* a, uint64_t desc) {
    asm volatile("wgmma.mma_async.sync.aligned.m64n128k16.f32.f16.f16 {%0,%1,%2,%3,%4,%5,%6,%7,%8,%9,%10,%11,%12,%13,%14,%15,%16,%17,%18,%19,%20,%21,%22,%23,%24,%25,%26,%27,%28,%29,%30,%31,%32,%33,%34,%35,%36,%37,%38,%39,%40,%41,%42,%43,%44,%45,%46,%47,%48,%49,%50,%51,%52,%53,%54,%55,%56,%57,%58,%59,%60,%61,%62,%63}, {%64,%65,%66,%67}, %68, 0, 1, 1, 0;\n"
                 : "=f"(acc[0][0]), "=f"(acc[0][1]), "=f"(acc[0][2]), "=f"(acc[0][3]), "=f"(acc[1][0]), "=f"(acc[1][1]), "=f"(acc[1][2]), "=f"(acc[1][3]), "=f"(acc[2][0]), "=f"(acc[2][1]), "=f"(acc[2][2]), "=f"(acc[2][3]), "=f"(acc[3][0]), "=f"(acc[3][1]), "=f"(acc[3][2]), "=f"(acc[3][3]), "=f"(acc[4][0]), "=f"(acc[4][1]), "=f"(acc[4][2]), "=f"(acc[4][3]), "=f"(acc[5][0]), "=f"(acc[5][1]), "=f"(acc[5][2]), "=f"(acc[5][3]), "=f"(acc[6][0]), "=f"(acc[6][1]), "=f"(acc[6][2]), "=f"(acc[6][3]), "=f"(acc[7][0]), "=f"(acc[7][1]), "=f"(acc[7][2]), "=f"(acc[7][3]), "=f"(acc[8][0]), "=f"(acc[8][1]), "=f"(acc[8][2]), "=f"(acc[8][3]), "=f"(acc[9][0]), "=f"(acc[9][1]), "=f"(acc[9][2]), "=f"(acc[9][3]), "=f"(acc[10][0]), "=f"(acc[10][1]), "=f"(acc[10][2]), "=f"(acc[10][3]), "=f"(acc[11][0]), "=f"(acc[11][1]), "=f"(acc[11][2]), "=f"(acc[11][3]), "=f"(acc[12][0]), "=f"(acc[12][1]), "=f"(acc[12][2]), "=f"(acc[12][3]), "=f"(acc[13][0]), "=f"(acc[13][1]), "=f"(acc[13][2]), "=f"(acc[13][3]), "=f"(acc[14][0]), "=f"(acc[14][1]), "=f"(acc[14][2]), "=f"(acc[14][3]), "=f"(acc[15][0]), "=f"(acc[15][1]), "=f"(acc[15][2]), "=f"(acc[15][3])
                 : "r"(a[0]), "r"(a[1]), "r"(a[2]), "r"(a[3]), "l"(desc));
}
template <> __device__ __forceinline__ void wg_first<4>(float (&acc)[16][4], const uint32_t* a, uint64_t desc) {
    asm volatile("wgmma.mma_async.sync.aligned.m64n96k16.f32.f16.f16 {%0,%1,%2,%3,%4,%5,%6,%7,%8,%9,%10,%11,%12,%13,%14,%15,%16,%17,%18,%19,%20,%21,%22,%23,%24,%25,%26,%27,%28,%29,%30,%31,%32,%33,%34,%35,%36,%37,%38,%39,%40,%41,%42,%43,%44,%45,%46,%47}, {%48,%49,%50,%51}, %52, 0, 1, 1, 0;\n"
                 : "=f"(acc[4][0]), "=f"(acc[4][1]), "=f"(acc[4][2]), "=f"(acc[4][3]), "=f"(acc[5][0]), "=f"(acc[5][1]), "=f"(acc[5][2]), "=f"(acc[5][3]), "=f"(acc[6][0]), "=f"(acc[6][1]), "=f"(acc[6][2]), "=f"(acc[6][3]), "=f"(acc[7][0]), "=f"(acc[7][1]), "=f"(acc[7][2]), "=f"(acc[7][3]), "=f"(acc[8][0]), "=f"(acc[8][1]), "=f"(acc[8][2]), "=f"(acc[8][3]), "=f"(acc[9][0]), "=f"(acc[9][1]), "=f"(acc[9][2]), "=f"(acc[9][3]), "=f"(acc[10][0]), "=f"(acc[10][1]), "=f"(acc[10][2]), "=f"(acc[10][3]), "=f"(acc[11][0]), "=f"(acc[11][1]), "=f"(acc[11][2]), "=f"(acc[11][3]), "=f"(acc[12][0]), "=f"(acc[12][1]), "=f"(acc[12][2]), "=f"(acc[12][3]), "=f"(acc[13][0]), "=f"(acc[13][1]), "=f"(acc[13][2]), "=f"(acc[13][3]), "=f"(acc[14][0]), "=f"(acc[14][1]), "=f"(acc[14][2]), "=f"(acc[14][3]), "=f"(acc[15][0]), "=f"(acc[15][1]), "=f"(acc[15][2]), "=f"(acc[15][3])
                 : "r"(a[0]), "r"(a[1]), "r"(a[2]), "r"(a[3]), "l"(desc));
}

#define SDLY 900
#define UDLY 1400
#define KDLY 850
#define XD0 0
#define XD1 0
#define FDLY 1000
#define FDLY2 400
#define DDLY 300
#define WDLY 500
#define HW 15
#define FIX(v) do { if ((v) == 1u) TRAP(); } while (0)
#define STAMPW(i) STAMPY(i)
#define STAMP2(i) STAMP(i)
#undef STAMPX
#define STAMPX(i)
struct Params {
    const bf16 *x, *lar, *aim, *cre, *cim, *ldt, *dsk;
    Scratch* s;
    const bf16* wr;
    bf16* out;
};

#define TOK(g) (2 * (g) - ((g) & 1))
#define ROWTOK(r) (TOK((r) & 7) + (((r) >> 2) & 2))
__device__ __forceinline__ void ln_partial(const uint32_t (&H)[2][4], float (&d)[2][4]) {
#pragma unroll
    for (int i = 0; i < 8; i++) d[i >> 2][i & 3] = 0.f;
#pragma unroll
    for (int k = 0; k < 4; k++)
#pragma unroll
        for (int hf = 0; hf < 2; hf++) mma_bf16_k8(d[hf], H[hf][k], 0x3f803f80u, H[hf][k]);
}
__device__ __forceinline__ float sum18(uint32_t a) {
    const uint4 p = lds128(a), q = lds128(a + 16), r = lds128(a + 32), s = lds128(a + 48);
    const uint2 u = lds64(a + 64);
#define F(x) __uint_as_float(x)
    return (((F(p.x) + F(p.y)) + (F(p.z) + F(p.w))) + ((F(q.x) + F(q.y)) + (F(q.z) + F(q.w)))) +
           (((F(r.x) + F(r.y)) + (F(r.z) + F(r.w))) + ((F(s.x) + F(s.y)) + (F(s.z) + F(s.w))) + (F(u.x) + F(u.y)));
#undef F
}
__device__ __forceinline__ void ln_stats(float sm, float sq, float& mb, float& sd) {
    const float m0 = sm * (1.0f / 576.0f);
    const float mean = fmaf(fmaf(-m0, 576.0f, sm), 1.0f / 576.0f, m0);
    const float var = fmaxf(fmaf(-mean, mean, sq * (1.0f / 576.0f)), 0.f);
    mb = rbf(mean);
    sd = rbf(sqrt_approx(rbf(rbf(var) + 1e-5f)));
}
__device__ __forceinline__ void ln_finish(float v, int lane, float& mb, float& rc) {
    const float o = __shfl_xor_sync(0xffffffffu, v, 16);
    float sd;
    ln_stats(lane < 16 ? v : o, lane < 16 ? o : v, mb, sd);
    rc = rcp_approx(sd);
}
__device__ __forceinline__ uint32_t ln_apply(uint32_t w, uint32_t m2, uint32_t rh, uint32_t rl) {
    const uint32_t d = hsub2_bf(w, m2);
    return hfma2_bf(d, rh, hmul2_bf(d, rl));
}
__device__ __forceinline__ void stat_store(uint32_t a, float mb, float rc, uint32_t extra) {
    const float rh = rbf(rc);
    sts64(a, (__float_as_uint(mb) >> 16) | (extra << 16), pack_bf16(rh, rc - rh));
}
#define STAT_M(s) __byte_perm((s).x, (s).x, 0x1010)
#define STAT_H(s) __byte_perm((s).y, (s).y, 0x1010)
#define STAT_L(s) __byte_perm((s).y, (s).y, 0x3232)

__device__ __forceinline__ void hcmul(uint32_t re, uint32_t im, uint32_t zx, uint32_t zy, uint32_t& ore, uint32_t& oim) {
    ore = hfms2(im, zy, hmul2(re, zx));
    oim = hfma2(re, zy, hmul2(im, zx));
}

struct KGen {
    uint32_t A[2][4][4];
    float2 z1, z8, z64, z128, T[9];
};
__device__ __forceinline__ void kgen_setup(KGen& k, float lar, float aim, float dt) {
    const float lr2 = -(exp_bf(lar) * dt) * 1.4426950408889634f, li = aim * dt;
    k.z1 = cexp_e(lr2, li, 1.0f);
    k.z8 = cexp_e(lr2, li, 8.0f);
    k.z64 = cexp_e(lr2, li, 64.0f);
}
__device__ __forceinline__ void kgen_rows(KGen& k, uint32_t tb, int lane) {
    const float2 z8 = k.z8, z64 = k.z64;
    const uint32_t row = tb + lane * 16;
    k.z128 = csq(z64);
    const float2 z16 = csq(z8), z24 = cmul(z16, z8), z32 = csq(z16), z40 = cmul(z32, z8), z48 = csq(z24), z56 = cmul(z32, z24);
    uint32_t re[4], im[4], a[4], b[4];
    re[0] = pack_f16(1.0f, z8.x); im[0] = pack_f16(0.0f, z8.y);
    re[1] = pack_f16(z16.x, z24.x); im[1] = pack_f16(z16.y, z24.y);
    re[2] = pack_f16(z32.x, z40.x); im[2] = pack_f16(z32.y, z40.y);
    re[3] = pack_f16(z48.x, z56.x); im[3] = pack_f16(z48.y, z56.y);
    sts128(row, re[0], re[1], re[2], re[3]);
    sts128(row + 1024, im[0], im[1], im[2], im[3]);
    const uint32_t zx = pack_f16(z64.x, z64.x), zy = pack_f16(z64.y, z64.y), zw = pack_f16(k.z128.x, k.z128.y);
#pragma unroll
    for (int j = 0; j < 4; j++) hcmul(re[j], im[j], zx, zy, a[j], b[j]);
    sts128(row + 512, a[0], a[1], a[2], a[3]);
    sts128(row + 1536, b[0], b[1], b[2], b[3]);
    const int mi = lane >> 3;
    const uint32_t zd = tb + 2048 + mi * 16;
    sts16(tb + 2048 + lane * 2, zw); sts16(tb + 2112 + lane * 2, zw >> 16);
    __syncwarp();
    const uint32_t ad = tb + (lane & 7) * 16 + mi * 512;
    ldsm_x4(a[0], a[1], a[2], a[3], zd);
    ldsm_x4(b[0], b[1], b[2], b[3], zd + 64);
#pragma unroll
    for (int ks = 0; ks < 4; ks++) {
        ldsm_x4_t(k.A[0][ks][0], k.A[0][ks][1], k.A[0][ks][2], k.A[0][ks][3], ad + ks * 128);
        hcmul(k.A[0][ks][0], k.A[0][ks][2], a[ks], b[ks], k.A[1][ks][0], k.A[1][ks][2]);
        hcmul(k.A[0][ks][1], k.A[0][ks][3], a[ks], b[ks], k.A[1][ks][1], k.A[1][ks][3]);
    }
}
__device__ __forceinline__ void kgen_chain(KGen& k, uint32_t cr, uint32_t ci, float cs) {
    k.T[0] = make_float2(bf_lo(cr) * cs, -bf_lo(ci) * cs);
    const float2 y1 = make_float2(k.z1.x, -k.z1.y);
#pragma unroll
    for (int c = 1; c < 8; c++) k.T[c] = cmul(k.T[c - 1], y1);
    k.T[8] = cmul(k.T[0], make_float2(k.z8.x, -k.z8.y));
}
__device__ __forceinline__ void kgen_cols(KGen& k, uint32_t tb, uint32_t t5, int lane) {
    const uint32_t row = tb + lane * 16;
    const float2 (&T)[9] = k.T;
    const float2 y128 = make_float2(k.z128.x, -k.z128.y);
    const float2 y256 = csq(y128), y512 = csq(y256), y768 = cmul(y512, y256), y1024 = csq(y512);
    const float2 c1032 = cmul(T[8], y1024);
    __syncwarp();
    sts128(row, pack_f16(T[0].x, T[1].x), pack_f16(T[2].x, T[3].x), pack_f16(T[4].x, T[5].x), pack_f16(T[6].x, T[7].x));
    sts128(row + 512, pack_f16(T[0].y, T[1].y), pack_f16(T[2].y, T[3].y), pack_f16(T[4].y, T[5].y), pack_f16(T[6].y, T[7].y));
    uint32_t a[4], b[4];
    {
        const uint32_t zx = pack_f16(y256.x, y256.x), zy = pack_f16(y256.y, y256.y);
        hcmul(pack_f16(T[0].x, T[2].x), pack_f16(T[0].y, T[2].y), zx, zy, a[0], b[0]);
        hcmul(pack_f16(T[4].x, T[6].x), pack_f16(T[4].y, T[6].y), zx, zy, a[1], b[1]);
        const uint32_t r04 = pack_f16(T[0].x, T[4].x), i04 = pack_f16(T[0].y, T[4].y);
        hcmul(r04, i04, pack_f16(y512.x, y512.x), pack_f16(y512.y, y512.y), a[2], b[2]);
        hcmul(r04, i04, pack_f16(y768.x, y768.x), pack_f16(y768.y, y768.y), a[3], b[3]);
    }
    sts128(row + 1024, a[0], a[1], a[2], a[3]);
    sts128(row + 1536, b[0], b[1], b[2], b[3]);
    {
        const uint32_t r0 = pack_f16(1.0f, y256.x), i0 = pack_f16(0.0f, y256.y), r1 = pack_f16(y512.x, y768.x), i1 = pack_f16(y512.y, y768.y);
        const uint32_t zx = pack_f16(T[8].x, T[8].x), zy = pack_f16(T[8].y, T[8].y), wx = pack_f16(c1032.x, c1032.x), wy = pack_f16(c1032.y, c1032.y);
        hcmul(r0, i0, zx, zy, a[0], b[0]); hcmul(r1, i1, zx, zy, a[1], b[1]);
        hcmul(r0, i0, wx, wy, a[2], b[2]); hcmul(r1, i1, wx, wy, a[3], b[3]);
    }
    sts128(row + 2048, a[0], a[1], a[2], a[3]);
    sts128(t5 + lane * 16, b[0], b[1], b[2], b[3]);
}
__device__ __forceinline__ void kgen_mma(const KGen& k, uint32_t tb, uint32_t t5, int lane) {
    __syncwarp();
    float acc[2][3][4];
#pragma unroll
    for (int i = 0; i < 6; i++)
#pragma unroll
        for (int j = 0; j < 4; j++) acc[i / 3][i % 3][j] = 0.f;
    const int mi = lane >> 3;
    const uint32_t ro = ((lane & 7) + 8 * (mi >> 1)) * 16, bd = tb + ro + (mi & 1) * 512, b2 = ro + ((mi & 1) ? t5 : tb + 2048);
#pragma unroll
    for (int kp = 0; kp < 2; kp++)
#pragma unroll
        for (int j = 0; j < 3; j++) {
            uint32_t b[4];
            ldsm_x4_t(b[0], b[1], b[2], b[3], (j < 2 ? bd + j * 1024 : b2) + kp * 256);
#pragma unroll
            for (int h = 0; h < 2; h++)
#pragma unroll
                for (int m = 0; m < 2; m++) {
                    const uint32_t (&A)[4] = k.A[m][2 * kp + h];
                    mma_f16(acc[m][j], A[0], A[1], A[2], A[3], b[2 * h], b[2 * h + 1]);
                }
        }
    __syncwarp();
#define PK(j) pack_f16(acc[0][j][0], acc[0][j][1]), pack_f16(acc[0][j][2], acc[0][j][3]), pack_f16(acc[1][j][0], acc[1][j][1]), pack_f16(acc[1][j][2], acc[1][j][3])
    stsm_x4(tb + lane * 16, PK(0));
    stsm_x4(tb + 512 + lane * 16, PK(1));
    stsm_x4_t(tb + 1024 + (lane & 7) * 80 + mi * 16, PK(2));
#undef PK
}
__device__ __forceinline__ uint32_t table_buf(uint32_t sb, int warp) { return sb + SM_PL + warp * TBW; }

__device__ __forceinline__ uint4 lds16x4(uint32_t a) { return make_uint4(lds16(a), lds16(a + TBW), lds16(a + 2 * TBW), lds16(a + 3 * TBW)); }
__device__ __forceinline__ void combine_setup(uint32_t sb, int warp, int lane, uint32_t kw, uint32_t& o, uint32_t& n, uint32_t& d) {
    const int wq = warp & 3;
    const uint32_t a = table_buf(sb, warp & ~3);
    o = wq == 3 ? a + 1024 + 320 + (lane >> 3) * 80 + (lane & 7) * 8 : a + (wq ? 504 + wq * 8 : 0) + lane * 16;
    n = a + 1024 + wq * 80 + lane * 2;
    d = wq < 3 ? kw + (wq == 2 ? KW_P : 32 + wq * 512) + lane * 16 : kw + KW_H + 8 + lane * 8;
}
__device__ __forceinline__ void kgen_combine(int wq, int lane, uint32_t o, uint32_t na, uint32_t d) {
#define S4(f) hadd2(hadd2(u.f, v.f), hadd2(w.f, x.f))
#define H4(v) hadd2(hadd2(v.x, v.y), hadd2(v.z, v.w))
#define BP __byte_perm
    if (wq == 0) {
        const uint4 u = lds128(o), v = lds128(o + TBW), w = lds128(o + 2 * TBW), x = lds128(o + 3 * TBW), nn = lds16x4(na);
        const uint32_t n = H4(nn), k0 = S4(x), k2 = S4(y), k4 = S4(z), k6 = S4(w);
        sts128(d, BP(k0, k0, 0x1032), BP(k0, k2, 0x3254), BP(k2, k2, 0x1032), BP(k2, k4, 0x3254));
        sts128(d + KW_PL, BP(k4, k4, 0x1032), BP(k4, k6, 0x3254), BP(k6, k6, 0x1032), BP(k6, n, 0x3254));
        if (lane == 0) sts32(d + KW_PL - 4, k0 & 0xffffu);
    } else {
        const uint2 u = lds64(o), v = lds64(o + TBW), w = lds64(o + 2 * TBW), x = lds64(o + 3 * TBW);
        uint4 nn = make_uint4(0u, 0u, 0u, 0u), mm = nn;
        if (wq < 3) nn = lds16x4(na);
        if (wq == 2) mm = lds16x4(na + 80);
        const uint32_t k0 = S4(x), k2 = S4(y), n = H4(nn), m = H4(mm);
        if (wq == 3) {
            sts64(d, k0, k2);
        } else if (wq == 1) {
            const uint32_t cc = BP(k2, k2, 0x1010);
            sts128(d, BP(k0, k0, 0x1010), BP(k0, k0, 0x1032), BP(k0, k2, 0x3254), cc);
            sts128(d + KW_PL, cc, BP(k2, k2, 0x1032), BP(k2, n, 0x3254), BP(n, n, 0x1010));
        } else {
            const uint32_t w40 = BP(k0, k0, 0x1032), w84 = BP(k0, n, 0x3254), w0 = BP(k0, k0, 0x1010), w4 = BP(k0, k0, 0x3232), w8 = BP(n, n, 0x1010);
            sts64(d, w40, w84);
            sts64(d + 512, BP(k2, k2, 0x1032), BP(k2, m, 0x3254));
            if (lane < 8) { sts128(d - (KW_P - 1056), w0, w0, w40, w4); sts128(d - (KW_P - 1056 - KW_PL), w4, w84, w8, w8); }
            if (lane == 31) sts16(d + (KW_H + 6 - KW_P - 496), m);
        }
    }
#undef S4
#undef H4
#undef BP
}

__device__ __forceinline__ int c_exponent(const uint2& r, const uint2& i, float dt) {
    const uint32_t mx = __vmaxu2(__vmaxu2(r.x & 0x7fff7fffu, r.y & 0x7fff7fffu), __vmaxu2(i.x & 0x7fff7fffu, i.y & 0x7fff7fffu));
    return __reduce_max_sync(0xffffffffu, max(mx, mx << 16) + (__float_as_uint(dt) & 0x7f800000u)) >> 23;
}

#define YQ 2
#define F0 0
__device__ __forceinline__ int warp_v() { int l; asm volatile("mov.u32 %0, %%tid.x;" : "=r"(l)); return __shfl_sync(0xffffffffu, l >> 5, 0); }
__device__ __forceinline__ int lane_v() { int l; asm volatile("mov.u32 %0, %%laneid;" : "=r"(l)); return l; }
__device__ __forceinline__ uint32_t prmt_v(uint32_t a, uint32_t b, uint32_t s) { uint32_t d; asm volatile("prmt.b32 %0, %1, %2, %3;\n" : "=r"(d) : "r"(a), "r"(b), "r"(s)); return d; }
__device__ __forceinline__ uint32_t mov_v(uint32_t a) { uint32_t d; asm volatile("mov.b32 %0, %1;\n" : "=r"(d) : "r"(a)); return d; }
template <int G>
__device__ __forceinline__ void conv_rename(float (&acc)[16][4]) {
#pragma unroll
    for (int i = G; i < 16; i++)
#pragma unroll
        for (int j = 0; j < 4; j++) { float v; asm volatile("mov.b32 %0, %1;\n" : "=f"(v) : "f"(acc[i][j])); acc[i][j] = v; }
}
struct Conv {
    uint32_t kw;
    uint32_t wa;
    uint32_t pa, s2;
    uint32_t s8;
    uint32_t id;
    uint32_t lc;
    uint32_t fs;
    uint32_t fl, yo;
    uint32_t yp;
    size_t ycopy;
    uint32_t ps;
    uint64_t d0;
    int warp;
};
struct Pk { uint32_t w[4]; };
__device__ __forceinline__ Pk pk2(const float (&u)[4], const float (&v)[4]) {
    Pk r;
    r.w[0] = pack_f16(u[0], u[1]); r.w[1] = pack_f16(u[2], u[3]); r.w[2] = pack_f16(v[0], v[1]); r.w[3] = pack_f16(v[2], v[3]);
    return r;
}
__device__ __forceinline__ void park(uint32_t a, const Pk& v) {
    asm volatile("stmatrix.sync.aligned.m8n8.x4.trans.shared.b16 [%0], {%1,%2,%3,%4};\n" ::"r"(a), "r"(v.w[0]), "r"(v.w[1]), "r"(v.w[2]), "r"(v.w[3]) : "memory");
}
__device__ __forceinline__ void conv_constants(uint32_t lc, int l) {
    const int d = (l >> 2) - 2 * (l & 3);
    const int e = d + 8, r4 = (e + 1 + ((e >> 2) & 1)) >> 2, p4 = (e + (((e - 1) >> 2) & 1)) >> 2;
    const uint32_t s2 = r4 == p4 ? 0x1010u : 0x3210u;
    sts64(lc + l * 8, KW_P + ((r4 - 5) >> 1) * 16 + ((r4 - 5) & 1) * 4, s2 | ((d < 0 ? s2 : 0x7654u) << 16));
    const int lo = (d >= 4) - (d < -3), ho = (d >= 5) - (d < -2), le = (d > 4) - (d < -4), he = (d > 5) - (d < -3);
    sts32(lc + 512 + l * 8, (0x5454u + lo * 0x22 + ho * 0x2200) | ((0x3232u + le * 0x22 + he * 0x2200) << 16));
    const int cc = l >> 2, j = l & 3;
    sts64(lc + 256 + l * 8, (j >> 1) * PL_HALF + (16 + cc) * 16 + (j & 1) * 8, (cc >> 1) * (DM * 64) + (cc & 1) * 32 + j * 8);
}
__device__ __forceinline__ void conv_selectors4(Conv& c) {
    const uint2 v = lds64(c.lc + lane_v() * 8);
    c.pa = v.x; c.s2 = v.y;
}
__device__ __forceinline__ void conv_selectors8(Conv& c) { c.s8 = lds32(c.lc + 512 + lane_v() * 8); }
template <int G, int I0, int I1>
__device__ __forceinline__ void conv_load(const Conv& c, uint32_t (&q)[9]) {
    const int wq = c.warp & 3;
    if (G < 2) {
#pragma unroll
        for (int i = I0; i < I1; i++) q[i] = lds32(c.wa + G * 512 + i * 16);
    } else if (G < 4) {
        const uint32_t a = (G == 2 && wq == 0) ? c.wa + 1024 : c.pa + c.kw + wq * 128 + (G < 2 ? 0 : G - 2) * 512;
#pragma unroll
        for (int i = I0; i < I1; i++) q[i] = lds32(a + i * 16);
    } else {
        const uint4 u = lds128(c.kw + KW_H + (G < 4 ? 0 : G - 4) * 64 + wq * 16);
        const uint2 v = lds64(c.kw + KW_H + (G < 4 ? 0 : G - 4) * 64 + wq * 16 + 16);
        q[0] = u.x; q[1] = u.y; q[2] = u.z; q[3] = u.w; q[4] = v.x; q[5] = v.y;
        if (G == 4 && wq == 0) { q[6] = lds32(c.pa + c.kw + 1024); q[7] = lds32(c.pa + c.kw + 1040); }
    }
}
template <int G, int J0, int J1>
__device__ __forceinline__ void conv_frag(const Conv& c, const uint32_t (&q)[9], uint32_t* a, const Pk& dp) {
    const uint32_t dep = dp.w[0];
    if (G < 4) {
        const uint32_t s = (G < 2 || (G == 2 && (c.warp & 3) == 0)) ? c.id : c.s2;
#pragma unroll
        for (int j = J0; j < J1; j++) {
            uint32_t* o = a + 4 * (j - J0);
            o[0] = prmt_v(q[2 * j + 1], dp.w[0], s); o[1] = prmt_v(q[2 * j + 2], dp.w[1], s); o[2] = prmt_v(q[2 * j], dp.w[2], s); o[3] = prmt_v(q[2 * j + 1], dp.w[3], s);
        }
    } else {
        const uint32_t so = prmt_v(c.s8, dep, c.id), se = prmt_v(c.s8, dep, c.id + 0x22);
#pragma unroll
        for (int j = J0; j < J1; j++) {
            uint32_t* o = a + 4 * (j - J0);
            o[0] = prmt_v(q[j + 1], q[j + 2], se); o[1] = prmt_v(q[j + 1], q[j + 2], so); o[2] = prmt_v(q[j], q[j + 1], so);
            if (G == 4 && j == 0 && (c.warp & 3) == 0) {
                o[2] = prmt_v(q[6], dep, c.s2);
                o[0] = prmt_v(q[7], o[0], c.s2 >> 16);
            }
            o[3] = mov_v(o[0]);
        }
    }
}
template <int G, int J0, int J1>
__device__ __forceinline__ void conv_frag(const Conv& c, const uint32_t (&q)[9], uint32_t* a, float depf) {
    const uint32_t d = __float_as_uint(depf);
    conv_frag<G, J0, J1>(c, q, a, Pk{{d, d, d, d}});
}
template <int G, int T, int J0, int J1>
__device__ __forceinline__ void conv_mma(float (&acc)[16][4], const Conv& c, const uint32_t* a) {
#pragma unroll
    for (int j = J0; j < J1; j++) wg_mma<T>(acc, a + 4 * (j - J0), c.d0 - 8 * (2 * G - T) - j);
}
__device__ __forceinline__ float h_lo(uint32_t w) { return __half2float(__ushort_as_half((unsigned short)(w & 0xffffu))); }
__device__ __forceinline__ float h_hi(uint32_t w) { return __half2float(__ushort_as_half((unsigned short)(w >> 16))); }
__device__ __forceinline__ void flush_setup(Conv& c) {
    const uint2 v = lds64(c.lc + 256 + lane_v() * 8);
    c.fl = v.x; c.yo = v.y;
}
template <int Q>
__device__ __forceinline__ void flush_load(const Conv& c, uint32_t pl, uint2 (&f)[4]) {
#pragma unroll
    for (int w = 0; w < 4; w++) f[w] = lds64(c.fl + pl + (Q & 1) * 512 + w * (PLW_B - 64));
}
template <int Q>
__device__ __forceinline__ void flush_load_first(const Conv& c, uint32_t pl, uint2 (&f)[4], float depf) {
    const uint32_t p = prmt_v(c.fl, __float_as_uint(depf), c.id) + pl + (Q & 1) * 512;
#define LDV64(d, a) asm volatile("ld.volatile.shared.v2.u32 {%0,%1}, [%2];\n" : "=r"(d.x), "=r"(d.y) : "r"(a) : "memory")
    LDV64(f[0], p); LDV64(f[1], p + (PLW_B - 64)); LDV64(f[2], p + 2 * (PLW_B - 64)); LDV64(f[3], p + 3 * (PLW_B - 64));
}
#define FDEP __uint_as_float(f[3].y)
template <int Q, int mode>
__device__ __forceinline__ void conv_flush(const Conv& c, const uint2 (&f)[4], unsigned char* gy, uint32_t rx) {
    const uint32_t a0 = hadd2(f[0].x, f[1].x), a1 = hadd2(f[2].x, f[3].x), b0 = hadd2(f[0].y, f[1].y), b1 = hadd2(f[2].y, f[3].y);
    if (Q > 0 && mode == 1) {
        const uint32_t ra = rx + 16 + (Q > 0 ? Q - 1 : 0) * 1024 + (c.warp & 3) * 256 + lane_v() * 8;
        asm volatile("st.async.shared::cluster.mbarrier::complete_tx::bytes.v2.b32 [%0], {%1,%2}, [%3];\n"
                     ::"r"(ra ^ 0x1000000u), "r"(hadd2(a0, a1)), "r"(hadd2(b0, b1)), "r"((rx + (Q > 1 ? 8 : 0)) ^ 0x1000000u) : "memory");
        return;
    }
    float v0 = h_lo(a0) + h_lo(a1), v1 = h_hi(a0) + h_hi(a1), v2 = h_lo(b0) + h_lo(b1), v3 = h_hi(b0) + h_hi(b1);
    if (Q > 0 && mode == 2) {
        const uint2 o = lds64(rx + 16 + (Q > 0 ? Q - 1 : 0) * 1024 + (c.warp & 3) * 256 + lane_v() * 8);
        v0 += h_lo(o.x); v1 += h_hi(o.x); v2 += h_lo(o.y); v3 += h_hi(o.y);
    }
    const uint32_t lo = hmul2_bf(pack_bf16(v0, v1), c.fs), hi = hmul2_bf(pack_bf16(v2, v3), c.fs);
    stg64(gy + Q * 32 * DM * 32 + (c.yo + (Q < YQ ? c.yp : 0u)), nzw(lo), nzw(hi));
}
template <int I, bool S = false> struct IC { static constexpr int value = I; static constexpr bool shared = S; };
template <class T> __device__ constexpr bool wg_is4() { return T::shared; }
#define SLOT(n) (c.ps + (2 + ((n) & 7)) * 128)
#define GO() do { wg_commit(); __syncwarp(); } while (0)
#define DEP acc[15][3]
template <class FG, class FP, class FN>
__device__ __forceinline__ void conv_head(Conv& c, float (&acc)[16][4], uint32_t (&q)[9], uint32_t (&r)[9], uint32_t* a, FG fg, FP pre, FN next) {
    c.id = 0x3210u + (c.warp >> 8);
    pre();
    conv_load<0, 0, 9>(c, q);
    conv_frag<0, 0, 1>(c, q, a, 0.f);
    wg_fence(); wg_first<0>(acc, a, c.d0); GO();
    park(c.ps, Pk{{0u, 0u, 0u, 0u}});
    wg_wait0();
    conv_frag<0, 1, 2>(c, q, a, DEP);
    wg_fence(); conv_mma<0, 0, 1, 2>(acc, c, a); GO();
    fg(IC<0>());
    wg_wait0();
    conv_frag<0, 2, 3>(c, q, a, DEP);
    wg_fence(); conv_mma<0, 0, 2, 3>(acc, c, a); GO();
    conv_load<1, 0, 5>(c, r);
    wg_wait0();
    conv_frag<0, 3, 4>(c, q, a, DEP);
    wg_fence(); conv_mma<0, 0, 3, 4>(acc, c, a); GO();
    conv_load<1, 5, 9>(c, r);
    fg(IC<1>());
    wg_wait0();
    const Pk k = pk2(acc[0], acc[1]);
    conv_rename<2>(acc);
    conv_frag<1, 0, 2>(c, r, a, k);
    wg_fence(); conv_mma<1, 2, 0, 2>(acc, c, a); GO();
    park(SLOT(0), k);
    next(IC<0>());
    fg(IC<2>());
    wg_wait0();
    conv_frag<1, 2, 4>(c, r, a, DEP);
    wg_fence(); conv_mma<1, 2, 2, 4>(acc, c, a); GO();
    next(IC<1>());
    fg(IC<3>());
    wg_wait0();
}
template <class FG, class FP>
__device__ __forceinline__ void conv_run(Conv& c, uint32_t pl, unsigned char* gy, FG fg, FP pre) {
    float acc[16][4];
    uint32_t q[9], r[9], a[32];
    uint2 f[4];
    const int bid = 1 + (c.warp >> 2);
    conv_head(c, acc, q, r, a, fg, pre, [&](auto i) { if (decltype(i)::value == 0) conv_selectors4(c); else conv_load<2, 0, 9>(c, q); });
    Pk k = pk2(acc[2], acc[3]);
    conv_rename<4>(acc);
    conv_frag<2, 0, 4>(c, q, a, k);
    wg_fence(); conv_mma<2, 4, 0, 4>(acc, c, a); GO();
    park(SLOT(2), k);
    conv_load<3, 0, 9>(c, q);
    flush_setup(c);
    bar_sync(bid, 128);
    fg(IC<4>());
    wg_wait0();
    conv_rename<6>(acc);
    if (F0) { flush_load_first<0>(c, pl, f, DEP); conv_frag<3, 0, 4>(c, q, a, FDEP); }
    else conv_frag<3, 0, 4>(c, q, a, DEP);
    wg_fence(); conv_mma<3, 6, 0, 4>(acc, c, a); GO();
    park(SLOT(4), pk2(acc[4], acc[5]));
    conv_load<4, 0, 9>(c, q);
    conv_selectors8(c);
    if (!F0) flush_load<0>(c, pl, f);
    conv_flush<0, 0>(c, f, gy, 0u);
    fg(IC<5>());
    wg_wait0();
    conv_rename<8>(acc);
    conv_frag<4, 0, 4>(c, q, a, DEP);
    wg_fence(); conv_mma<4, 8, 0, 4>(acc, c, a); GO();
    k = pk2(acc[6], acc[7]);
    park(SLOT(6), k);
    conv_load<5, 0, 9>(c, q);
    bar_sync(bid, 128);
    park(c.ps, k);
    fg(IC<6>());
    wg_wait0();
    conv_rename<10>(acc);
    flush_load_first<1>(c, pl, f, DEP);
    conv_frag<5, 0, 4>(c, q, a, FDEP);
    wg_fence(); conv_mma<5, 10, 0, 4>(acc, c, a); GO();
    park(SLOT(8), pk2(acc[8], acc[9]));
    conv_load<6, 0, 9>(c, q); conv_load<7, 0, 9>(c, r);
    conv_flush<1, 0>(c, f, gy, 0u);
    fg(IC<7>());
    wg_wait0();
    conv_rename<12>(acc);
    conv_frag<6, 0, 4>(c, q, a, DEP); conv_frag<7, 0, 4>(c, r, a + 16, DEP);
    wg_fence(); conv_mma<6, 12, 0, 4>(acc, c, a); conv_mma<7, 12, 0, 4>(acc, c, a + 16); GO();
    park(SLOT(10), pk2(acc[10], acc[11]));
    bar_sync(bid, 128);
    flush_load<2>(c, pl, f);
    conv_flush<2, 0>(c, f, gy, 0u);
    fg(IC<8>());
    if (c.id == 0) TRAP();
    wg_wait0();
    park(SLOT(12), pk2(acc[12], acc[13])); park(SLOT(14), pk2(acc[14], acc[15]));
    bar_sync(bid, 128);
    flush_load<3>(c, pl, f);
    conv_flush<3, 0>(c, f, gy, 0u);
}
template <class FG>
__device__ __forceinline__ void conv_outer(Conv& c, uint32_t pl, unsigned char* gy, uint32_t rx, FG fg) {
    float acc[16][4];
    uint32_t q[9], r[9], a[32];
    uint2 f[4], f2[4];
    const int bid = 1 + (c.warp >> 2);
    conv_head(c, acc, q, r, a, [&](auto gi) { if (decltype(gi)::value == 2) fg(IC<2, true>()); }, [&]() {}, [&](auto i) { if (decltype(i)::value == 0) conv_selectors8(c); else conv_load<6, 0, 9>(c, q); });
    park(SLOT(2), pk2(acc[2], acc[3])); park(SLOT(4), pk2(acc[4], acc[5]));
    const Pk k = pk2(acc[6], acc[7]);
    park(SLOT(6), k);
    conv_load<7, 0, 9>(c, r);
    conv_rename<12>(acc);
    conv_frag<6, 0, 4>(c, q, a, __uint_as_float(k.w[3])); conv_frag<7, 0, 4>(c, r, a + 16, __uint_as_float(k.w[3]));
    wg_fence(); conv_mma<6, 12, 0, 4>(acc, c, a); conv_mma<7, 12, 0, 4>(acc, c, a + 16); GO();
    flush_setup(c);
    bar_sync(bid, 128);
    flush_load<0>(c, pl, f); flush_load<1>(c, pl, f2);
    conv_flush<1, 1>(c, f2, gy, rx);
    conv_flush<0, 1>(c, f, gy, rx);
    wg_wait0();
    bar_sync(bid, 128);
    park(c.ps, k); park(SLOT(8), pk2(acc[8], acc[9])); park(SLOT(10), pk2(acc[10], acc[11]));
    park(SLOT(12), pk2(acc[12], acc[13])); park(SLOT(14), pk2(acc[14], acc[15]));
    bar_sync(bid, 128);
    flush_load<2>(c, pl, f); flush_load<3>(c, pl, f2);
    conv_flush<2, 1>(c, f, gy, rx);
    conv_flush<3, 1>(c, f2, gy, rx);
}
template <class FG>
__device__ __forceinline__ void conv_inner(Conv& c, uint32_t pl, unsigned char* gy, uint32_t rx, FG fg) {
    float acc[16][4];
    uint32_t q[9], a[16];
    uint2 f[4], f2[4];
    const int bid = 1 + (c.warp >> 2);
    c.id = 0x3210u + (c.warp >> 8);
    conv_selectors4(c);
    conv_load<2, 0, 9>(c, q);
    conv_frag<2, 0, 4>(c, q, a, 0.f);
    wg_fence(); wg_first<4>(acc, a, c.d0); conv_mma<2, 4, 1, 4>(acc, c, a + 4); GO();
    conv_load<3, 0, 9>(c, q);
    park(SLOT(2), Pk{{0u, 0u, 0u, 0u}});
    fg(IC<2, true>());
    wg_wait0();
    conv_rename<6>(acc);
    conv_frag<3, 0, 4>(c, q, a, DEP);
    wg_fence(); conv_mma<3, 6, 0, 4>(acc, c, a); GO();
    park(SLOT(4), pk2(acc[4], acc[5]));
    conv_load<4, 0, 9>(c, q);
    conv_selectors8(c);
    wg_wait0();
    conv_rename<8>(acc);
    conv_frag<4, 0, 4>(c, q, a, DEP);
    wg_fence(); conv_mma<4, 8, 0, 4>(acc, c, a); GO();
    const Pk k = pk2(acc[6], acc[7]);
    park(SLOT(6), k); park(c.ps, k);
    conv_load<5, 0, 9>(c, q);
    flush_setup(c);
    wg_wait0();
    conv_rename<10>(acc);
    conv_frag<5, 0, 4>(c, q, a, DEP);
    wg_fence(); conv_mma<5, 10, 0, 4>(acc, c, a); GO();
    park(SLOT(8), pk2(acc[8], acc[9]));
    bar_sync(bid, 128);
    flush_load<1>(c, pl, f);
    mbar_wait(rx);
    conv_flush<1, 2>(c, f, gy, rx);
    wg_wait0();
    bar_sync(bid, 128);
    park(SLOT(10), pk2(acc[10], acc[11])); park(SLOT(12), pk2(acc[12], acc[13])); park(SLOT(14), pk2(acc[14], acc[15]));
    bar_sync(bid, 128);
    flush_load<3>(c, pl, f); flush_load<2>(c, pl, f2);
    mbar_wait(rx + 8);
    conv_flush<3, 2>(c, f, gy, rx);
    conv_flush<2, 2>(c, f2, gy, rx);
}
#undef SLOT
#undef GO
#undef DEP
template <int U0, int U1>
__device__ __forceinline__ void weight_units(uint32_t sb, const CUtensorMap* tg, const CUtensorMap* tu, const CUtensorMap* td, bool w) {
    if (U1 > U0 && w && elect_one()) {
#pragma unroll
        for (int i = U0; i < U1; i++) {
            if (i < 12) tma_2d(sb + SM_WG + i * 6912, i < 6 ? tg : tu, 72 * (blockIdx.x >> 1), 288 * (blockIdx.x & 1) + (i % 6) * 48, sb + SM_MISC + 328);
            else tma_2d(sb + SM_WD + (i - 12) * 4736, td, 144 * (blockIdx.x & 1), 72 * (blockIdx.x >> 1) + 8 * (i - 12), sb + SM_MISC + 336);
        }
    }
}
#define WS 2110121111122004100
__device__ constexpr int wsched(int i) {
    unsigned long long v = WS;
    int n = 0;
    for (int k = 19; k >= 1; k--) { if (k < i) n += (int)(v % 10); v /= 10; }
    return n;
}
static_assert(wsched(20) == 21 && wsched(6) <= 7 && wsched(11) <= 12 && wsched(13) <= 14 && wsched(16) <= 17 && wsched(16) == wsched(15) && wsched(19) == 21, "");
#define WANY(i) (wsched((i) + 1) > wsched(i))
#define WPOINT(i, w) do { weight_units<wsched(i), wsched(i + 1)>(sb, &tm_g, &tm_u, &tm_d, w); } while (0)

__global__ void __launch_bounds__(NTHR, 1) __cluster_dims__(2, 1, 1)
fused_kernel(const Params p, const __grid_constant__ CUtensorMap tm_g, const __grid_constant__ CUtensorMap tm_u, const __grid_constant__ CUtensorMap tm_d, const __grid_constant__ CUtensorMap tm_x) {
    extern __shared__ __align__(1024) unsigned char smem[];
    const uint32_t sb = smem_u32(smem);
    const int tid = threadIdx.x, warp = __shfl_sync(0xffffffffu, tid >> 5, 0), lane = tid & 31;
    const int b = blockIdx.x, P = b >> 1, odd = b & 1;
    const int g = lane >> 2, t = lane & 3;
    const int wg = warp >> 2, t128 = tid & 127;
    const uint32_t s_stat = sb + SM_MISC;
    const uint32_t s_key = sb + SM_MISC + 128;
    const uint32_t s_rank = sb + SM_MISC + 256;
    const uint32_t s_k16 = sb + SM_MISC + 192;
    const uint32_t s_cnt = sb + SM_MISC + 320;
    const uint32_t bar_w = sb + SM_MISC + 328, bar_d = bar_w + 8, bar_g = bar_w + 16, bar_x = bar_w + 24, bar_v = bar_w + 32, bar_s = bar_w + 40, bar_h = bar_w + 48;
    STAMP(0);

    const int ch = wg < 4 ? 4 * b + wg : 512 + P;
    const uint32_t mo = tid < 512 ? 512 * b + tid : 65536 + 128 * P + t128, mq = (mo & ~127u) + 4 * lane;
    const uint32_t pl = ldo16(p.lar + mo), pa2 = ldo16(p.aim + mo), ldt = ldo16(p.ldt + (mo >> 7));
    const uint32_t pc = ldo16(p.cre + mo), pi = ldo16(p.cim + mo);
    const uint2 call_re = ldo64(p.cre + mq), call_im = ldo64(p.cim + mq);
    const uint32_t epl = ld_poll32(p.s->hint + (b & 7) * 32 + 1);
    if (wg < 4) {
        bar_arrive(0, NWRK);
        asm volatile("barrier.cluster.arrive.relaxed.aligned;\n" ::: "memory");
    } else {
        const int o = (4 * (warp & 3) + (g >> 1)) * 1152 + (g & 1) * 576 + t * 16;
        sts128(sb + SM_Z2 + t128 * 16, 0u, 0u, 0u, 0u); sts128(sb + SM_Z2 + 2048 + t128 * 16, 0u, 0u, 0u, 0u);
        if (warp == 16) sts128(sb + SM_Z2 + 4096 + lane * 16, 0u, 0u, 0u, 0u);
        fence_async();
        bar_sync(0, NWRK);
        STAMP(9);
        if (XD0) delay(XD0);
#pragma unroll
        for (int c = 0; c < 9; c++)
            asm volatile("cp.async.cg.shared.global [%0], [%1], 16;\n" ::"r"(sb + SM_XT + o + c * 64), "l"(reinterpret_cast<const char*>(p.x) + b * 18432 + o + c * 64) : "memory");
        asm volatile("cp.async.commit_group;\n" ::: "memory");
        if (elect_one()) {
            mbar_init(bar_h + 8 * (warp & 3), 1);
            if (warp == 19) {
                mbar_init(bar_x, 1); mbar_init(bar_w, 1);
                mbar_expect(bar_x, 32768); mbar_expect(bar_w, 82944);
#pragma unroll
                for (int i = YQ; i < 4; i++) bulk_s2g(reinterpret_cast<unsigned char*>(p.s->y) + 32 * i * 18432 + b * 4608, sb + SM_Z2, 4608);
            } else if (warp == 18) {
                mbar_init(bar_s, 1); mbar_init(bar_v, 2); mbar_init(bar_d, 1); mbar_init(bar_g, 1); mbar_init(sb + SM_RX, 1); mbar_init(sb + SM_RX + 8, 1);
                mbar_expect(bar_v, 2 * 1152); mbar_expect(bar_d, 72 * WD_PITCH); mbar_expect(bar_g, 4608); mbar_expect(sb + SM_RX, 1024); mbar_expect(sb + SM_RX + 8, 2048);
            }
            asm volatile("fence.mbarrier_init.release.cluster;\n" ::: "memory");
        }
        __syncwarp();
        asm volatile("barrier.cluster.arrive.relaxed.aligned;\n" ::: "memory");
        if (warp == 19) {
            asm volatile("barrier.cluster.wait.aligned;\n" ::: "memory");
            if (XD1) delay(XD1);
            if (elect_one()) tma_4d_mc(sb + SM_XC + odd * 16384, &tm_x, 8 * P, 2 * odd, bar_x);
            __syncwarp();
        }
        {
            if (!(g & 1) && t == (g >> 1)) *reinterpret_cast<volatile uint32_t*>(p.s->stat + 16 * b + 4 * (warp & 3) + t) = 0u;
            if (warp < 18) {
                unsigned char* const ud = reinterpret_cast<unsigned char*>(p.s->uT) + (size_t)(8 * (warp & 1) + 2 * (g >> 1)) * 16384 + b * 128 + (g & 1) * 32 + t * 8;
#pragma unroll
                for (int k = 0; k < 4; k++) *reinterpret_cast<volatile unsigned long long*>(ud + (k >> 1) * 16384 + (k & 1) * 64) = 0ull;
            }
        }
    }
    const uint32_t kw = sb + SM_KW + wg * KW_B;
    const uint32_t tb = table_buf(sb, warp), t5 = sb + SM_WD + warp * 512;
    STAMP(29);
    const float dt = exp_bf(bf_lo(ldt));
    const uint32_t ep = __reduce_or_sync(0xffffffffu, epl);
    auto stats = [&]() {
        const int wq = warp & 3;
        const uint32_t xa = sb + SM_XT + (4 * wq + (g >> 1)) * 1152 + (g & 1) * 576 + t * 16;
        const bool own = !(g & 1) && t == (g >> 1);
        float d[4][4] = {};
        asm volatile("cp.async.wait_group 0;\n" ::: "memory");
        STAMP(26);
        uint4 v[9];
#pragma unroll
        for (int c = 0; c < 9; c++) v[c] = lds128(xa + c * 64);
#pragma unroll
        for (int c = 0; c < 9; c++) {
            mma_bf16(d[2 * (c & 1)], v[c].x, 0x3f803f80u, v[c].y, 0x3f803f80u, v[c].x, v[c].y);
            mma_bf16(d[2 * (c & 1) + 1], v[c].z, 0x3f803f80u, v[c].w, 0x3f803f80u, v[c].z, v[c].w);
        }
        STAMP(27);
        float sm = (g & 1) ? (d[0][3] + d[1][3]) + (d[2][3] + d[3][3]) : (d[0][2] + d[1][2]) + (d[2][2] + d[3][2]);
        float sq = (g & 1) ? (d[0][1] + d[1][1]) + (d[2][1] + d[3][1]) : (d[0][0] + d[1][0]) + (d[2][0] + d[3][0]);
        sm += __shfl_xor_sync(0xffffffffu, sm, 4); sq += __shfl_xor_sync(0xffffffffu, sq, 4);
        if (lane == 0) mbar_arrive(bar_h + 8 * wq);
        float mb, sd;
        ln_stats(sm, sq, mb, sd);
        if (own) p.s->stat[16 * b + 4 * wq + t] = (__float_as_uint(mb) >> 16) | (__float_as_uint(sd) & 0x7fff0000u) | (ep << 31);
        STAMPX(22);
        if (own) stat_store(s_stat + (2 * wq + (t & 1) + 8 * (t >> 1)) * 8, mb, rcp_approx(sd), 0u);
        if (wq == 3) asm volatile("cp.async.bulk.wait_group 0;\n" ::: "memory");
        bar_sync(5, 128);
        STAMP(28);
        uint32_t now;
        asm volatile("mov.u32 %0, %%clock;" : "=r"(now) :: "memory");
        if (wq == 2) {
            conv_constants(sb + SM_LC, lane);
            __syncwarp();
            if (lane < 8) p.s->key3[8 * b + lane] = ep & 1u;
            if (lane == 0) {
                sts64(s_cnt, now, ep);
                mbar_arrive(bar_s);
                bulk_g2s(sb + SM_XT + 16 * 1152, p.dsk, 1152, bar_v);
                bulk_g2s(sb + SM_XT + 17 * 1152, p.wr, 1152, bar_v);
            }
            __syncwarp();
        }
        WPOINT(1, wq == 3);
        if (wq < 2) {
            unsigned char* const ud = reinterpret_cast<unsigned char*>(p.s->uT) + (size_t)(8 * wq + 2 * (g >> 1)) * 16384 + b * 128 + (g & 1) * 32 + t * 8;
            const uint32_t utag = (ep % 7u + 1u) * 0x10001u;
            uint32_t U[2][4];
#pragma unroll
            for (int hf = 0; hf < 2; hf++) {
                const uint2 st = lds64(s_stat + (g + 8 * hf) * 8);
                const uint4 xu = lds128(sb + SM_XT + (TOK(g) + 2 * hf) * 1152 + warp * 64 + t * 16);
                const uint32_t X[4] = {xu.x, xu.y, xu.z, xu.w};
#pragma unroll
                for (int k = 0; k < 4; k++) {
                    const uint32_t u = ln_apply(X[k], STAT_M(st), STAT_H(st), STAT_L(st));
                    U[hf][k] = movm((pack_f16(bf_lo(u), bf_hi(u)) & 0xfff8fff8u) | utag);
                }
            }
#pragma unroll
            for (int k = 0; k < 4; k++) stg64(ud + (k >> 1) * 16384 + (k & 1) * 64, U[0][k], U[1][k]);
        }
    };
    STAMP(1);
    if (wg < 4) { STAMPX(16); }
    KGen kg;
    kgen_setup(kg, bf_lo(pl), bf_lo(pa2), dt);
    kgen_rows(kg, tb, lane);
    STAMP(2);
    const int E = min(max(c_exponent(call_re, call_im, dt) - 243, -120), 120);
    kgen_chain(kg, pc, pi, dt * __uint_as_float((uint32_t)(128 - E) << 23));
    STAMP(3);
    kgen_cols(kg, tb, t5, lane);
    STAMP(4);
    if (wg == 4) stats();
    if (warp != 19) asm volatile("barrier.cluster.wait.aligned;\n" ::: "memory");
    if (wg < 4) { STAMPX(17); }
    if (t128 < 2 * UPAD) sts128(sb + SM_U + wg * USLOT_B + (t128 & 1) * ULO_B + (t128 >> 1) * 16, 0u, 0u, 0u, 0u);
    if (t128 >= 124) sts128(kw + (t128 & 1) * 16 + (t128 & 2) * (KW_PL / 2), 0u, 0u, 0u, 0u);
    if (warp < 15) sts128(sb + SM_Z2 + 4608 + tid * 16, 0u, 0u, 0u, 0u);
    uint32_t co, cn, cd;
    combine_setup(sb, warp, lane, kw, co, cn, cd);
    co = pin(co); cn = pin(cn); cd = pin(cd);
    const uint4* const usrc = reinterpret_cast<const uint4*>(p.s->stat) + pin(wg < 4 ? tid : 512 + (P >> 2) * 1024 + (t128 >> 1) * 8 + (P & 3) * 2 + (t128 & 1));
    if (wg < 4) mbar_wait(bar_h + 8 * (warp & 3));
    if (wg < 4) { STAMPX(19); }
    kgen_mma(kg, tb, t5, lane);
    if (wg < 4) { STAMPX(20); }
    STAMP(5);
    uint4 uv0, uv1;
    auto first_poll = [&](uint32_t dly) {
        mbar_wait(bar_s);
        const uint32_t t0 = lds32(s_cnt);
        uint32_t now;
        do { asm volatile("mov.u32 %0, %%clock;" : "=r"(now) :: "memory"); } while (now - t0 < dly);
        uv0 = ld_poll(usrc);
    };
    if (wg == 4) { first_poll(UDLY); uv1 = ld_poll(usrc + 512); }
    WPOINT(2, warp == 19);
    bar_sync(1 + wg, 128);
    if (wg < 4) { STAMPX(21); }
    kgen_combine(warp & 3, lane, co, cn, cd);
    STAMP(6);
    if (wg < 4) { STAMPX(18); }
    WPOINT(3, warp == 19);
    if (wg < 4) first_poll(SDLY);
    {
        const int wq = warp & 3;
        Conv c;
        const uint32_t pln = sb + SM_PL + wg * PL_B;
        const int e = g - 2 * t + 7;
        c.kw = kw; c.wa = pin(kw + ((e >> 2) & 1) * KW_PL + (8 * wq + (e >> 3)) * 16 + (e & 3) * 4);
        c.ps = mov_v(pln + wq * PLW_B + ((lane >> 3) & 1) * PL_HALF + ((lane >> 4) * 8 + (lane & 7)) * 16); c.warp = warp;
        c.lc = sb + SM_LC; c.fs = (uint32_t)(127 + E) * 0x800080u; c.yp = (ep & 1u) * (NCTA * 18432u);
        c.d0 = ((uint64_t)(ULO_B >> 4) << 16) | ((uint64_t)(128 >> 4) << 32) | (uint64_t)(((sb + SM_U + wg * USLOT_B + UPAD * 16) & 0x3FFFF) >> 4);
        unsigned char* gy = reinterpret_cast<unsigned char*>(p.s->y) + ((size_t)(4 * wq) * DM + ch) * 64;
        auto hook = [&](auto gi) {
                     constexpr int G = decltype(gi)::value;
                     if (G == (wg_is4<decltype(gi)>() ? 2 : 5)) asm volatile("barrier.cluster.wait.aligned;\n" ::: "memory");
                     if (!wg_is4<decltype(gi)>() && (G == 0 || G == 2) && warp == HW && elect_one()) {
                         unsigned char* const sc = reinterpret_cast<unsigned char*>(p.s);
                         if (G == 0) {
                             if (b < 96) bulk_s2g_nc(sc + offsetof(Scratch, part) + b * 12288, sb + SM_Z2, 12288);
                             bulk_s2g(sc + offsetof(Scratch, rows) + (127 - b) * 4608, sb + SM_Z2, 4608);
                         }
                         if (G == 2) {
                             if (YQ == 3) bulk_s2g_nc(sc + offsetof(Scratch, y) + (NCTA * 18432u - c.yp) + b * 13824 + 6912, sb + SM_Z2, 6912);
                             if (YQ) bulk_s2g(sc + offsetof(Scratch, y) + (NCTA * 18432u - c.yp) + b * (4608 * YQ), sb + SM_Z2, YQ == 3 ? 6912 : 4608 * YQ);
                         }
                     }
                     if (!wg_is4<decltype(gi)>()) WPOINT(6 + G, warp == (G >= 7 ? HW : 4 * (G % 3) + 1));
                     if (!wg_is4<decltype(gi)>() && G == 6 && warp == HW) {
                         asm volatile("cp.async.bulk.wait_group 0;\n" ::: "memory");
                         __syncwarp();
                         if (elect_one()) mbar_arrive(bar_v);
                     }
                 };
        if (wg < 4) {
            asm volatile("barrier.cluster.arrive.relaxed.aligned;\n" ::: "memory");
            conv_run(c, pln + wq * 128, gy, hook, [&]() {
                STAMPX(23);
                mbar_wait(bar_x);
                STAMPX(24);
                uint2 xc[4];
                uint32_t xw[4][2];
#pragma unroll
                for (int j = 0; j < 4; j++) xc[j] = lds64(sb + SM_XC + wg * 8192 + j * 2048 + t128 * 16 + odd * 8);
#pragma unroll
                for (int i = 0; i < 8; i++) {
                    const int k = i >> 1, h = i & 1;
                    xw[k][h] = prmt_v(k < 2 ? xc[2 * h].x : xc[2 * h].y, k < 2 ? xc[2 * h + 1].x : xc[2 * h + 1].y, (k & 1) ? 0x7632 : 0x5410);
                }
                const uint32_t ub = mov_v(sb + SM_U + UPAD * 16 + ((tid >> 1) & 1) * ULO_B + (tid >> 2) * 16 + (tid & 1) * 8), tag = ep << 31;
                int it = 0;
                while (min(min((int)(uv0.x ^ tag), (int)(uv0.y ^ tag)), min((int)(uv0.z ^ tag), (int)(uv0.w ^ tag))) < 0x10000) {
                    if (++it > SPIN_LIMIT) TRAP();
                    uv0 = ld_poll(usrc);
                }
                STAMP(8);
                STAMPX(26);
                const float r0 = rcp_approx(fabsf(bf_hi(uv0.x))), r1 = rcp_approx(fabsf(bf_hi(uv0.y))), r2 = rcp_approx(fabsf(bf_hi(uv0.z))), r3 = rcp_approx(fabsf(bf_hi(uv0.w)));
                const uint32_t m[2] = {__byte_perm(uv0.x, uv0.y, 0x5410), __byte_perm(uv0.z, uv0.w, 0x5410)};
                const uint32_t rh[2] = {pack_bf16(r0, r1), pack_bf16(r2, r3)};
                const uint32_t rl[2] = {pack_bf16(r0 - bf_lo(rh[0]), r1 - bf_hi(rh[0])), pack_bf16(r2 - bf_lo(rh[1]), r3 - bf_hi(rh[1]))};
#pragma unroll
                for (int k = 0; k < 4; k++) {
                    const uint32_t u0 = ln_apply(xw[k][0], m[0], rh[0], rl[0]), u1 = ln_apply(xw[k][1], m[1], rh[1], rl[1]);
                    sts64(ub + k * USLOT_B, pack_f16(bf_lo(u0), bf_hi(u0)), pack_f16(bf_lo(u1), bf_hi(u1)));
                }
                STAMPX(29);
                fence_async();
                bar_sync(14, 512);
                STAMP(7);
            });
        } else {
            auto stage = [&]() {
                const uint32_t tag = (ep % 7u + 1u) * 0x10001u;
                int it = 0;
                WPOINT(4, warp == 19);
                while (true) {
                    uv0.x ^= tag; uv0.y ^= tag; uv0.z ^= tag; uv0.w ^= tag; uv1.x ^= tag; uv1.y ^= tag; uv1.z ^= tag; uv1.w ^= tag;
                    if ((((uv0.x | uv0.y | uv0.z) | (uv0.w | uv1.x | uv1.y) | (uv1.z | uv1.w)) & 0x70007u) == 0) break;
                    if (++it > SPIN_LIMIT) TRAP();
                    uv0 = ld_poll(usrc); uv1 = ld_poll(usrc + 512);
                }
                STAMP(8);
                const uint32_t ub = sb + SM_U + UPAD * 16 + 4 * USLOT_B + (t128 & 1) * ULO_B + (t128 >> 1) * 16;
                sts128(ub, uv0.x, uv0.y, uv0.z, uv0.w);
                sts128(ub + 1024, uv1.x, uv1.y, uv1.z, uv1.w);
                fence_async();
                asm volatile("barrier.cluster.arrive.relaxed.aligned;\n" ::: "memory");
                bar_sync(5, 128);
                WPOINT(5, warp == 19);
                STAMP(7);
            };
            stage();
            if (odd) conv_inner(c, pln + wq * 128, gy, sb + SM_RX, hook);
            else conv_outer(c, pln + wq * 128, gy, sb + SM_RX, hook);
        }
        STAMP(10);
    }
    {
    const int lane = lane_v(), tid = 32 * warp + lane, g = lane >> 2, t = lane & 3;
    const uint32_t par = ~ep & 1u;
    bar_sync(0, NWRK);
    STAMP(11);
    uint32_t H[2][4] = {}, U2[2][4] = {};
    auto publish = [&](bool hi, int slot) {
        uint4* rowp = reinterpret_cast<uint4*>(p.s->rows) + slot * 144 + warp * 4 + t;
        stg128(rowp, nzw(hi ? U2[1][0] : U2[0][0]), nzw(hi ? U2[1][1] : U2[0][1]), nzw(hi ? U2[1][2] : U2[0][2]), nzw(hi ? U2[1][3] : U2[0][3]));
        stg128(rowp + 72, nzw(hi ? H[1][0] : H[0][0]), nzw(hi ? H[1][1] : H[0][1]), nzw(hi ? H[1][2] : H[0][2]), nzw(hi ? H[1][3] : H[0][3]));
    };
#define KTOK(k) (int)(((~(k) >> 5) & 0x7f0u) | (((k) >> 1) & 15u))
#define KLATE(k) (((k) & 0x1e0u) < 0xe0u)
#define KSLOT(k, s) (KLATE(k) ? 2 * NCTA + (s) : (int)(((k) >> 8) & 0xffu))
    const uint4* const rsrc = reinterpret_cast<const uint4*>(p.s->rows) + 36 * odd;
    auto gather = [&](uint32_t mine) {
        int it = 0;
        uint32_t mn;
        do {
            mn = 1;
#pragma unroll 1
            for (int r = 0; r < 9; r++) {
                const uint32_t k = __shfl_sync(0xffffffffu, mine, r < 8 ? 4 * r : lane);
                const int row = r < 8 ? r : g, c = r < 8 ? lane : 32 + t;
                asm volatile("cp.async.cg.shared.global [%0], [%1], 16;\n" ::"r"(sb + SM_XS + row * XS_PITCH + c * 16), "l"(rsrc + KSLOT(k, row) * 144 + c) : "memory");
            }
            asm volatile("cp.async.wait_all;\n" ::: "memory");
#pragma unroll 1
            for (int r = 0; r < 9; r++) mn = min(mn, min4(lds128(sb + SM_XS + (r < 8 ? r * XS_PITCH + lane * 16 : g * XS_PITCH + (32 + t) * 16))));
            if (++it > SPIN_LIMIT) TRAP();
        } while (__any_sync(0xffffffffu, mn == 0));
    };
    auto late_rows = [&](auto role) {
        if (decltype(role)::value == 1) {
            int it = 0;
#pragma unroll 1
            for (int i = 0; i < 8; i++) {
                uint4 k;
                do { k = ld_poll(reinterpret_cast<const uint4*>(p.s->key) + 32 * i + lane); if (++it > SPIN_LIMIT) TRAP(); } while (((k.x ^ par) | (k.y ^ par) | (k.z ^ par) | (k.w ^ par)) & 1u);
                sts128(sb + SM_KEYS + (32 * i + lane) * 16, k.x, k.y, k.z, k.w);
            }
            uint32_t m = 0xffffffffu;
#pragma unroll 1
            for (int r = 0; r < 8; r++) {
                uint32_t c = 0;
#pragma unroll 2
                for (int i = 0; i < 8; i++) {
                    const uint4 k = lds128(sb + SM_KEYS + (32 * i + lane) * 16);
                    c = max(max(c, k.x < m ? k.x : 0u), max(k.y < m ? k.y : 0u, max(k.z < m ? k.z : 0u, k.w < m ? k.w : 0u)));
                }
                m = __reduce_max_sync(0xffffffffu, c);
                if (lane == 0) sts32(s_key + r * 4, m);
            }
        }
        bar_sync(0, NWRK);
        const uint32_t kk = lds32(s_key + (lane & 7) * 4), ep = lds32(s_cnt + 4);
        const bool own = KLATE(kk) && (KTOK(kk) >> 4) == b;
        uint32_t todo = __ballot_sync(0xffffffffu, own) & 0xffu;
        if (decltype(role)::value == 0 && todo) {
#pragma unroll
            for (int hf = 0; hf < 2; hf++) {
                const uint4 h = lds128(sb + SM_U + hf * 9216 + tid * 16);
                const uint2 st = lds64(s_stat + (g + 8 * hf) * 8);
                H[hf][0] = h.x; H[hf][1] = h.y; H[hf][2] = h.z; H[hf][3] = h.w;
#pragma unroll
                for (int k = 0; k < 4; k++) U2[hf][k] = ln_apply(H[hf][k], STAT_M(st), STAT_H(st), STAT_L(st));
            }
#pragma unroll 1
            while (todo) {
                const int s = __ffs(todo) - 1, tk = KTOK(__shfl_sync(0xffffffffu, kk, s));
                todo &= todo - 1;
                if ((tk & 13) == TOK(g)) publish(tk & 2, 2 * NCTA + s);
            }
            __threadfence();
        }
        bar_sync(0, NWRK);
        if (decltype(role)::value == 1) {
            if (lane < NSEL && own) *reinterpret_cast<volatile unsigned*>(p.s->flag + lane) = ep + 1u;
            int it = 0;
            while (__any_sync(0xffffffffu, KLATE(kk) && ld_acquire32(p.s->flag + (lane & 7)) != ep + 1u)) { if (++it > SPIN_LIMIT) TRAP(); }
            gather(__shfl_sync(0xffffffffu, kk, g));
        }
        bar_sync(0, NWRK);
    };
    if (warp < 18) {
        const unsigned char* ys = reinterpret_cast<const unsigned char*>(p.s->y) + (b < 32 * YQ ? (par ^ 1u) * (NCTA * 18432u) : 0u) +
                                  ((P * DM + 32 * warp + 8 * (g >> 1) + (g & 1)) * 64 + odd * 32 + t * 8);
        mbar_wait(bar_v);
        const uint32_t xa = sb + SM_XT + warp * 64 + t * 16;
        const uint4 x0 = lds128(xa + TOK(g) * 1152), x1 = lds128(xa + (TOK(g) + 2) * 1152), dk = lds128(xa + 16 * 1152);
        uint4 wr = make_uint4(0u, 0u, 0u, 0u);
        if (g == 0) wr = lds128(xa + 17 * 1152);
        uint2 yv[4];
        const uint32_t Z[2][4] = {{x0.x, x0.y, x0.z, x0.w}, {x1.x, x1.y, x1.z, x1.w}}, D4[4] = {dk.x, dk.y, dk.z, dk.w};
#pragma unroll
        for (int hf = 0; hf < 2; hf++) {
            const uint2 st = lds64(s_stat + (g + 8 * hf) * 8);
#pragma unroll
            for (int k = 0; k < 4; k++) U2[hf][k] = hmul2_bf(ln_apply(Z[hf][k], STAT_M(st), STAT_H(st), STAT_L(st)), D4[k]);
        }
        const uint32_t la = pin(sb + SM_LNP + (g * 20 + warp) * 4);
        {
            const unsigned char* y1 = ys + (U2[0][0] & U2[1][2] & (warp >> 8));
#pragma unroll
            for (int k = 0; k < 4; k++) yv[k] = ld_poll64(y1 + k * 128);
        }
        int it = 0;
        float d[2][4];
        while (true) {
            const uint32_t mn = min3(min3(yv[0].x, yv[0].y, yv[1].x), min3(yv[1].y, yv[2].x, yv[2].y), min(yv[3].x, yv[3].y));
#pragma unroll
            for (int k = 0; k < 4; k++) {
                H[0][k] = hadd2_bf(Z[0][k], hadd2_bf(movm(yv[k].x), U2[0][k]));
                H[1][k] = hadd2_bf(Z[1][k], hadd2_bf(movm(yv[k].y), U2[1][k]));
            }
            ln_partial(H, d);
            if (!__any_sync(0xffffffffu, mn == 0)) break;
            if (++it > SPIN_LIMIT) TRAP();
#pragma unroll
            for (int k = 0; k < 4; k++) yv[k] = ld_poll64(ys + k * 128);
        }
        STAMP(12);
        {
            const float s0 = (g & 1) ? d[0][3] : d[0][2], s1 = (g & 1) ? d[1][3] : d[1][2];
            const float q0 = (g & 1) ? d[0][1] : d[0][0], q1 = (g & 1) ? d[1][1] : d[1][0];
            asm volatile("{\n.reg .pred p;\nsetp.eq.u32 p, %5, %6;\n@p st.shared.f32 [%0], %1;\n@p st.shared.f32 [%0 + 640], %2;\n@p st.shared.f32 [%0 + 1280], %3;\n@p st.shared.f32 [%0 + 1920], %4;\n}\n"
                         ::"r"(la), "f"(s0), "f"(s1), "f"(q0), "f"(q1), "r"(t), "r"(g >> 1) : "memory");
        }
        bar_arrive(6, NWRK);
        STAMP(13);
        bar_sync(7, 608);
        STAMP(14);
#pragma unroll
        for (int hf = 0; hf < 2; hf++) {
            const uint2 st = lds64(s_stat + (g + 8 * hf) * 8);
#pragma unroll
            for (int k = 0; k < 4; k++) U2[hf][k] = ln_apply(H[hf][k], STAT_M(st), STAT_H(st), STAT_L(st));
        }
        {
            float cs[4] = {0.f, 0.f, 0.f, 0.f};
            mma_bf16(cs, U2[0][0], U2[1][0], U2[0][1], U2[1][1], wr.x, wr.y);
            mma_bf16(cs, U2[0][2], U2[1][2], U2[0][3], U2[1][3], wr.z, wr.w);
            if (t == 0) { stsf(la + 32 * 80, cs[0]); stsf(la + 40 * 80, cs[2]); }
            bar_arrive(8, 608);
        }
        FIX((uint32_t)warp >> 8);
        uint32_t O[2][4];
#pragma unroll
        for (int hf = 0; hf < 2; hf++)
#pragma unroll
            for (int k = 0; k < 4; k++) { O[hf][k] = hadd2_bf(H[hf][k], U2[hf][k]); H[hf][k] = nzw(H[hf][k]); U2[hf][k] = nzw(U2[hf][k]); }
        unsigned char* rowp = reinterpret_cast<unsigned char*>(p.s->rows) + ((254 - 2 * b) * 2304 + warp * 64 + t * 16);
        FIX(and3(and3(and3(H[0][0], H[0][1], H[0][2]), and3(H[0][3], H[1][0], H[1][1]), and3(H[1][2], H[1][3], U2[0][0])),
                 and3(and3(U2[0][1], U2[0][2], U2[0][3]), and3(U2[1][0], U2[1][1], U2[1][2]), U2[1][3]), (uint32_t)reinterpret_cast<uint64_t>(rowp)));
        bar_sync(9, 608);
        {
            const uint2 best = lds64(s_rank);
#pragma unroll
            for (int hf = 0; hf < 2; hf++) {
                const uint32_t me = 2 * TOK(g) + 4 * hf;
                unsigned char* d = rowp + (best.x == me ? 2304 : 0);
                if (best.x == me || best.y == me) {
                    stg128(d, U2[hf][0], U2[hf][1], U2[hf][2], U2[hf][3]);
                    stg128(d + 1152, H[hf][0], H[hf][1], H[hf][2], H[hf][3]);
                }
            }
        }
        FIX((uint32_t)warp >> 9);
#pragma unroll
        for (int hf = 0; hf < 2; hf++) {
            sts128(sb + SM_OUT + (TOK(g) + 2 * hf) * (DM * 2) + warp * 64 + t * 16, O[hf][0], O[hf][1], O[hf][2], O[hf][3]);
            sts128(sb + SM_U + hf * 9216 + tid * 16, H[hf][0], H[hf][1], H[hf][2], H[hf][3]);
        }
        STAMP(15);
        const int mi = lane >> 3, rr = lane & 7;
        const bool gate = warp < 12 && (warp & 3) != 2;
        const int fj = gate ? 3 * (warp >> 2) + min(warp & 3, 2) : (warp < 12 ? warp >> 2 : warp - 9);
        if (gate) {
            uint32_t W[18][4];
            mbar_wait(bar_w);
            const uint32_t aad = sb + SM_WG + (mi & 1) * SM_WU + (rr + 8 * (mi >> 1)) * W_PITCH + fj * 16;
            const uint32_t bad = pin(sb + SM_XS + rr * XS_PITCH + mi * 16);
            bool rare = warp >> 8;
#pragma unroll 1
            do {
                if (rare) late_rows(IC<0>());
#pragma unroll
                for (int k = 0; k < 18; k++) ldsm_x4_t(W[k][0], W[k][1], W[k][2], W[k][3], aad + k * 16 * W_PITCH);
                if (rare) break;
                fence_async();
                STAMP2(17);
                rare = bar_or(11, NWRK, false);
            } while (rare);
            STAMP2(19);
            float c4[2][4] = {};
#pragma unroll
            for (int k = 0; k < 18; k += 2) {
                uint32_t b0, b1, b2, b3;
                ldsm_x4(b0, b1, b2, b3, bad + k * 32);
                mma_bf16(c4[0], W[k][0], W[k][1], W[k][2], W[k][3], b0, b1);
                mma_bf16(c4[1], W[k + 1][0], W[k + 1][1], W[k + 1][2], W[k + 1][3], b2, b3);
            }
            const uint32_t ex = sb + SM_EX + (32 * fj + lane) * 16;
            const float e0 = c4[0][0] + c4[1][0], e1 = c4[0][1] + c4[1][1], e2 = c4[0][2] + c4[1][2], e3 = c4[0][3] + c4[1][3];
            asm volatile("st.async.shared::cluster.mbarrier::complete_tx::bytes.v4.f32 [%0], {%1,%2,%3,%4}, [%5];\n"
                         ::"r"(ex ^ 0x1000000u), "f"(e0), "f"(e1), "f"(e2), "f"(e3), "r"(bar_g ^ 0x1000000u) : "memory");
            STAMP2(20);
            mbar_wait(bar_g);
            const uint4 o = lds128(ex);
            const uint32_t G = pack_bf16(e0 + __uint_as_float(o.x), e1 + __uint_as_float(o.y)), U = pack_bf16(e2 + __uint_as_float(o.z), e3 + __uint_as_float(o.w));
            sts32(sb + SM_GU + (32 * fj + lane) * 4, hmul2_bf(pack_bf16(bf_lo(G) * sigmoid_f(bf_lo(G)), bf_hi(G) * sigmoid_f(bf_hi(G))), U));
            bar_arrive(13, NWRK);
        } else {
            uint32_t W[2][18];
            auto load_wd = [&]() {
                mbar_wait(bar_d);
                const uint32_t base = sb + SM_WD + (4 * fj + (mi & 1)) * 16 + rr * WD_PITCH;
#pragma unroll
                for (int j = 0; j < 2; j++) {
#pragma unroll
                    for (int k = 0; k < 4; k++) ldsm_x4_t(W[j][4 * k], W[j][4 * k + 1], W[j][4 * k + 2], W[j][4 * k + 3], base + j * 32 + (k * 16 + 8 * (mi >> 1)) * WD_PITCH);
                    ldsm_x2_t(W[j][16], W[j][17], base + j * 32 + 64 * WD_PITCH);
                }
            };
            const uint32_t po = pin((((8 * (18 * odd + 2 * fj) + g) * 64 + P) * 16 + t * 4) * 4);
            fence_async();
            STAMP2(17);
            if (bar_or(11, NWRK, false)) late_rows(IC<0>());
            delay(DDLY); load_wd();
            bar_sync(13, NWRK);
            STAMP2(21);
            uint32_t gb[9];
            ldsm_x4_t(gb[0], gb[1], gb[2], gb[3], sb + SM_GU + lane * 16);
            ldsm_x4_t(gb[4], gb[5], gb[6], gb[7], sb + SM_GU + 512 + lane * 16);
            ldsm_x1_t(gb[8], sb + SM_GU + 1024 + lane * 16);
            float c4[2][4] = {}, d4[2][4] = {};
#pragma unroll
            for (int k = 0; k < 4; k += 2)
#pragma unroll
                for (int j = 0; j < 2; j++) {
                    mma_bf16(c4[j], W[j][4 * k], W[j][4 * k + 1], W[j][4 * k + 2], W[j][4 * k + 3], gb[2 * k], gb[2 * k + 1]);
                    mma_bf16(d4[j], W[j][4 * k + 4], W[j][4 * k + 5], W[j][4 * k + 6], W[j][4 * k + 7], gb[2 * k + 2], gb[2 * k + 3]);
                }
#pragma unroll
            for (int j = 0; j < 2; j++) mma_bf16_k8(c4[j], W[j][16], W[j][17], gb[8]);
#pragma unroll
            for (int j = 0; j < 2; j++)
                stg128(reinterpret_cast<unsigned char*>(p.s->part) + po + j * 32768, __float_as_uint(c4[j][0] + d4[j][0]) | 1u, __float_as_uint(c4[j][1] + d4[j][1]) | 1u,
                       __float_as_uint(c4[j][2] + d4[j][2]) | 1u, __float_as_uint(c4[j][3] + d4[j][3]) | 1u);
        }
        STAMP2(22);
    } else if (warp == 18) {
        const uint4* const ksrc = reinterpret_cast<const uint4*>(p.s->key3) + pin(2 * lane);
        const int row = (g >> 1) + 4 * (g & 1);
        const uint32_t ro = pin(640 * odd + t * 16), xd = pin(sb + SM_XS + row * XS_PITCH + t * 16 + (odd ? 0 : 512));
        const uint32_t xe = pin(sb + SM_XS + (g >> 1) * XS_PITCH + (lane & 7) * 16 + 64 * odd);
        const uint32_t sa = pin(sb + SM_LNP + lane * 80);
        const uint32_t klo = pin((uint32_t)(127 - b) << 9 | (uint32_t)(15 - ROWTOK(lane & 15)) << 1 | par), ra = pin(sb + SM_LNP + (32 + (lane & 15)) * 80);
        uint4* const kdst = reinterpret_cast<uint4*>(p.s->key3) + pin((lane >> 1) * 2 * NCTA + 2 * b + (lane & 1));
        FIX(ra);
        bar_sync(6, NWRK);
        {
            float mb, rc;
            ln_finish(sum18(sa), lane, mb, rc);
            if (lane < 16) stat_store(s_stat + lane * 8, mb, rc, 0u);
        }
        bar_arrive(7, 608);
        bar_sync(8, 608);
        uint32_t t0;
        {
            const uint32_t bits = __float_as_uint(rbf(sum18(ra)));
            const uint32_t me = ((bits ^ ((uint32_t)((int)bits >> 31) | 0x80000000u)) & 0xffff0000u) | klo;
            const uint32_t k0 = __reduce_max_sync(0xffffffffu, me), k1 = __reduce_max_sync(0xffffffffu, me == k0 ? 0u : me);
            const uint32_t k2 = __reduce_max_sync(0xffffffffu, me >= k1 ? 0u : me);
            if (lane < 2) stg128(kdst, k0 ^ 0x11eu, k1 ^ 0xfeu, k2 ^ 0xdeu, par);
            asm volatile("mov.u32 %0, %%clock;" : "=r"(t0) :: "memory");
            STAMPW(23);
            if (lane == 0) sts64(s_rank, ~k0 & 30u, ~k1 & 30u);
            bar_arrive(9, 608);
            sts32(s_k16 + (lane & 15) * 4, me);
            __syncwarp();
            const uint4 v = lds128(s_k16 + (lane & 16) * 2), w = lds128(s_k16 + (lane & 16) * 2 + 16);
            int rank = ((v.x > me) + (v.y > me)) + ((v.z > me) + (v.w > me)) + (((w.x > me) + (w.y > me)) + ((w.z > me) + (w.w > me)));
            rank += __shfl_xor_sync(0xffffffffu, rank, 16);
            if (lane < 16 && rank < 8) p.s->key[8 * b + rank] = (me ^ 0x1eu) | ((8 - rank) << 5);
        }
        uint4 kq[4];
        uint32_t u[4], mine = 0, m;
        int it = 0;
        { uint32_t now; do { asm volatile("mov.u32 %0, %%clock;" : "=r"(now) :: "memory"); } while (now - t0 < KDLY); }
        do {
#pragma unroll
            for (int i = 0; i < 4; i++) kq[i] = ld_poll(ksrc + 64 * i);
            if (++it > SPIN_LIMIT) TRAP();
            uint32_t S[2][4];
#pragma unroll
            for (int i = 0; i < 2; i++) {
                const uint4 &c = kq[2 * i], &d = kq[2 * i + 1];
                const uint32_t m1 = min(c.x, d.x), m2 = max(c.y, d.y);
                S[i][0] = max(c.x, d.x); S[i][1] = max(m1, m2); S[i][2] = min(m1, m2); S[i][3] = min(c.y, d.y);
            }
            const uint32_t a0 = max(S[0][0], S[1][3]), a1 = max(S[0][1], S[1][2]), a2 = max(S[0][2], S[1][1]), a3 = max(S[0][3], S[1][0]);
            const uint32_t b0 = max(a0, a2), b2 = min(a0, a2), b1 = max(a1, a3), b3 = min(a1, a3);
            u[0] = max(b0, b1); u[1] = min(b0, b1); u[2] = max(b2, b3); u[3] = min(b2, b3);
            const uint32_t bad = or3(or3(xor_or(kq[0].x, kq[0].y, par), xor_or(kq[0].z, kq[1].x, par), xor_or(kq[1].y, kq[1].z, par)),
                                     xor_or(kq[2].x, kq[2].y, par), xor_or(kq[2].z, kq[3].x, par)) | xor_or(kq[3].y, kq[3].z, par);
            m = __reduce_max_sync(0xffffffffu, u[0] | (uint32_t)((int)(bad << 31) >> 31));
        } while (m == 0xffffffffu);
        STAMPW(16);
#pragma unroll
        for (int r = 0; r < 8; r++) {
            if (r) m = __reduce_max_sync(0xffffffffu, u[0]);
            if (u[0] == m) { u[0] = u[1]; u[1] = u[2]; u[2] = u[3]; u[3] = 0; }
            if (row == r) mine = m;
        }
        uint4 v[9];
        const uint32_t o0 = __byte_perm(mine, 0, 0x4441) * 2304u, o1 = __shfl_xor_sync(0xffffffffu, o0, 4);
        const unsigned char* const rA = reinterpret_cast<const unsigned char*>(p.s->rows) + (((g & 1) ? o1 : o0) + ro + (g & 1) * 64);
        const unsigned char* const rb = reinterpret_cast<const unsigned char*>(p.s->rows) + (((g & 1) ? o0 : o1) + ro + (g & 1) * 64);
        const unsigned char* const rc = reinterpret_cast<const unsigned char*>(p.s->rows) + (o0 + ro + (odd ? -64 : 512));
#pragma unroll
        for (int i = 0; i < 4; i++) { v[i] = ld_poll(rA + i * 128); v[4 + i] = ld_poll(rb + i * 128); }
        v[8] = ld_poll(rc);
        const bool again = u[0] == 0 || max(max(kq[0].z, kq[1].z), max(kq[2].z, kq[3].z)) > m;
        if (t == 0) sts32(s_key + row * 4, mine);
#pragma unroll
        for (int i = 0; i < 9; i++) sts128(i < 8 ? xe + (i >> 2) * 4 * XS_PITCH + (i & 3) * 128 : xd, v[i].x, v[i].y, v[i].z, v[i].w);
        uint32_t mn, m3[3];
        m3[0] = m3[1] = m3[2] = 1u;
#pragma unroll
        for (int i = 0; i < 9; i++) m3[i % 3] = min3(min3(m3[i % 3], v[i].x, v[i].y), v[i].z, v[i].w);
        mn = min3(m3[0], m3[1], m3[2]);
        STAMPW(18);
        if (bar_or(11, NWRK, again || mn == 0)) late_rows(IC<1>());
    } else {
        bar_sync(6, NWRK);
        WPOINT(16, true);
        if (WANY(17) || WANY(18)) delay(WDLY);
        WPOINT(17, true);
        if (WANY(18)) delay(WDLY);
        WPOINT(18, true);
        if (bar_or(11, NWRK, false)) late_rows(IC<2>());
        const int tk = KTOK(lds32(s_key + (lane & 7) * 4));
        const uint32_t sel = __reduce_or_sync(0xffffffffu, (tk >> 4) == b ? 1u << (tk & 15) : 0u);
        if (sel ? lane < 16 && !((sel >> lane) & 1u) : lane == 0) bulk_s2g(p.out + (size_t)(16 * b + lane) * DM, sb + SM_OUT + lane * (DM * 2), sel ? DM * 2 : 16 * DM * 2);
        __syncwarp();
    }
    if (warp == 8 || warp >= 18) {
        const int grp = 3 * b + (warp == 8 ? 0 : warp - 17), fsl = 2 * t + ((lane >> 3) & 1), fc = 16 * (grp >> 3) + (grp & 7) + 8 * (lane >> 4);
        const uint32_t fk = lds32(s_key + fsl * 4);
        float hv = 0.f, u2 = 0.f;
        int it = 0;
        if (b < 96) {
            const uint32_t* const fsrc = p.s->rows + KSLOT(fk, fsl) * DM + (fc >> 1);
            uint32_t hw, uw;
            do { hw = ld_poll32(fsrc + 288); uw = ld_poll32(fsrc); if (++it > SPIN_LIMIT) TRAP(); } while (!hw || !uw);
            hv = (fc & 1) ? bf_hi(hw) : bf_lo(hw); u2 = (fc & 1) ? bf_hi(uw) : bf_lo(uw);
        }
        const float rs = rbf(sigmoid_f(__uint_as_float((fk ^ ((uint32_t)((int)~fk >> 31) | 0x80000000u)) & 0xffff0000u)));
        const uint32_t dof = pin(KTOK(fk) * DM + fc), so = pin(grp * 256 + lane);
        if (warp > 17) bar_sync(13, NWRK);
        if (b < 96) {
            delay(warp > 17 ? FDLY : FDLY2);
            const uint4* src = reinterpret_cast<const uint4*>(p.s->part) + so;
            float s0, s1, s2, s3;
            uint32_t ok;
            do {
                uint4 a[8];
#pragma unroll
                for (int i = 0; i < 8; i++) a[i] = ld_poll(src + 32 * i);
                if (++it > SPIN_LIMIT) TRAP();
#define A4(i) and3(and3(a[i].x, a[i].y, a[i].z), and3(a[i].w, a[i + 1].x, a[i + 1].y), a[i + 1].z & a[i + 1].w)
#define S8(f) (((__uint_as_float(a[0].f) + __uint_as_float(a[1].f)) + (__uint_as_float(a[2].f) + __uint_as_float(a[3].f))) + \
               ((__uint_as_float(a[4].f) + __uint_as_float(a[5].f)) + (__uint_as_float(a[6].f) + __uint_as_float(a[7].f))))
                ok = and3(A4(0), A4(2), and3(A4(4), A4(6), 1u));
                s0 = S8(x); s1 = S8(y); s2 = S8(z); s3 = S8(w);
                asm volatile("" : "+f"(s0), "+f"(s1), "+f"(s2), "+f"(s3));
#undef A4
#undef S8
            } while (__any_sync(0xffffffffu, !ok));
            STAMP2(24);
            const bool up = lane & 16, od = lane & 8;
            const float r0 = (up ? s2 : s0) + __shfl_xor_sync(0xffffffffu, up ? s0 : s2, 16), r1 = (up ? s3 : s1) + __shfl_xor_sync(0xffffffffu, up ? s1 : s3, 16);
            float y = (od ? r1 : r0) + __shfl_xor_sync(0xffffffffu, od ? r0 : r1, 8);
            y += __shfl_xor_sync(0xffffffffu, y, 4);
            p.out[dof] = __float2bfloat16_rn(hv + rbf(u2 + rbf(rbf(y) * rs)));
        }
    }
    if (warp == 19) asm volatile("cp.async.bulk.wait_group.read 0;\n" ::: "memory");
    if (b == 0 && tid < 8) *reinterpret_cast<volatile unsigned*>(p.s->hint + tid * 32 + 1) = lds32(s_cnt + 4) + 1u;
    STAMP(25);
    }
}

typedef CUresult (*PFN_tmEncode)(CUtensorMap*, CUtensorMapDataType, cuuint32_t, void*, const cuuint64_t*, const cuuint64_t*, const cuuint32_t*,
                                 const cuuint32_t*, CUtensorMapInterleave, CUtensorMapSwizzle, CUtensorMapL2promotion, CUtensorMapFloatOOBfill);

extern "C" void kernel_launch(void* const* d_in, const int* in_sizes, int n_in, void* d_out, int out_size) {
    Params p;
    p.x = (const bf16*)d_in[0];
    p.lar = (const bf16*)d_in[1];
    p.aim = (const bf16*)d_in[2];
    p.cre = (const bf16*)d_in[3];
    p.cim = (const bf16*)d_in[4];
    p.ldt = (const bf16*)d_in[5];
    p.dsk = (const bf16*)d_in[6];
    p.wr = (const bf16*)d_in[8];
    p.out = (bf16*)d_out;
    static PFN_tmEncode enc = nullptr;
    static void* scratch = nullptr;
    if (!enc) {
        cudaFuncSetAttribute(fused_kernel, cudaFuncAttributeMaxDynamicSharedMemorySize, SMEM_TOTAL);
        void* fn = nullptr;
        cudaDriverEntryPointQueryResult qr;
        cudaGetDriverEntryPoint("cuTensorMapEncodeTiled", &fn, cudaEnableDefault, &qr);
        enc = (PFN_tmEncode)fn;
        cudaGetSymbolAddress(&scratch, g_scratch);
    }
    p.s = (Scratch*)scratch;
    CUtensorMap tm_g, tm_u, tm_d, tm_x;
    const cuuint64_t dims[2] = {FF, DM}, strides[1] = {FF * 2};
    const cuuint32_t box[2] = {72, 48}, es[2] = {1, 1};
    enc(&tm_g, CU_TENSOR_MAP_DATA_TYPE_BFLOAT16, 2, d_in[9], dims, strides, box, es, CU_TENSOR_MAP_INTERLEAVE_NONE, CU_TENSOR_MAP_SWIZZLE_NONE,
        CU_TENSOR_MAP_L2_PROMOTION_NONE, CU_TENSOR_MAP_FLOAT_OOB_FILL_NONE);
    enc(&tm_u, CU_TENSOR_MAP_DATA_TYPE_BFLOAT16, 2, d_in[10], dims, strides, box, es, CU_TENSOR_MAP_INTERLEAVE_NONE, CU_TENSOR_MAP_SWIZZLE_NONE,
        CU_TENSOR_MAP_L2_PROMOTION_NONE, CU_TENSOR_MAP_FLOAT_OOB_FILL_NONE);
    const cuuint64_t ddims[2] = {DM / 2, FF}, dstrides[1] = {DM * 2};
    const cuuint32_t dbox[2] = {WD_PITCH / 4, 8};
    enc(&tm_d, CU_TENSOR_MAP_DATA_TYPE_UINT32, 2, d_in[11], ddims, dstrides, dbox, es, CU_TENSOR_MAP_INTERLEAVE_NONE, CU_TENSOR_MAP_SWIZZLE_NONE,
        CU_TENSOR_MAP_L2_PROMOTION_NONE, CU_TENSOR_MAP_FLOAT_OOB_FILL_NONE);
    const cuuint64_t xdims[4] = {DM, 128, 4, 4}, xstrides[3] = {DM * 8, DM * 2, DM * 1024};
    const cuuint32_t xbox[4] = {8, 128, 4, 2}, xes[4] = {1, 1, 1, 1};
    enc(&tm_x, CU_TENSOR_MAP_DATA_TYPE_BFLOAT16, 4, d_in[0], xdims, xstrides, xbox, xes, CU_TENSOR_MAP_INTERLEAVE_NONE, CU_TENSOR_MAP_SWIZZLE_NONE,
        CU_TENSOR_MAP_L2_PROMOTION_NONE, CU_TENSOR_MAP_FLOAT_OOB_FILL_NONE);
    fused_kernel<<<NCTA, NTHR, SMEM_TOTAL>>>(p, tm_g, tm_u, tm_d, tm_x);
}
```

```cpp
#include <cuda_runtime.h>
#include <cuda.h>
#include <cuda_fp16.h>
#include <cuda_bf16.h>
#include <stdint.h>

#define LSEQ 2048
#define DM 576
#define NST 128
#define FF 4608
#define NSEL 8
#define NCTA 128
#define NTHR 640
#define NWRK 640

typedef __nv_bfloat16 bf16;

#define SM_WG 0
#define SM_WU 41472
#define SM_XC (82944 - 32768)
#define SM_WD 82944
#define W_PITCH 144
#define WD_PITCH 592
#define SM_Z2 (SM_WD + 10240)
#define SM_XT (SM_PL - 18 * 1152)
#define SM_PL (SM_WD + 46080)
#define PL_HALF 1344
#define PLW_B 2624
#define PL_B (4 * PLW_B)
#define SM_U (SM_PL + 5 * PL_B)
#define UPAD 20
#define ULO_B ((UPAD + 128) * 16)
#define USLOT_B (2 * ULO_B)
#define SM_KW (SM_U + 5 * USLOT_B)
#define KW_B 3712
#define KW_PL 1216
#define KW_P 2400
#define KW_H 3440
#define SM_MISC (SM_KW + 5 * KW_B)
#define SM_LC (SM_MISC + 416)
#define SM_LNP (SM_LC + 768)
#define SM_RX (SM_LNP + 3840)
#define SMEM_TOTAL (SM_RX + 3088)
#define TBW PLW_B
#define SM_OUT SM_PL
#define SM_XS (SM_PL + 18432)
#define XS_PITCH 592
#define SM_GU (SM_PL + 23296)
#define SM_EX (SM_PL + 24576)
#define SM_KEYS SM_KW

struct __align__(128) Scratch {
    unsigned hint[8 * 32];
    unsigned flag[32];
    uint32_t key3[NCTA * 8];
    uint32_t key[NCTA * 8];
    uint32_t stat[LSEQ];
    uint32_t uT[64 * (LSEQ / 2)];
    uint32_t y[(NCTA + 96) * DM * 8];
    uint32_t part[288 * 64 * 16];
    uint32_t rows[(2 * NCTA + NSEL) * DM];
};
__device__ Scratch g_scratch;
#define STAMP(i)
#define STAMPX(i)
#define STAMPY(i)

__device__ __forceinline__ float rbf(float x) {
    uint32_t r;
    asm("cvt.rn.bf16x2.f32 %0, %1, %2;\n" : "=r"(r) : "f"(x), "f"(0.f));
    return __uint_as_float(r);
}
__device__ __forceinline__ uint32_t pack_bf16(float lo, float hi) {
    uint32_t r;
    asm("cvt.rn.bf16x2.f32 %0, %1, %2;\n" : "=r"(r) : "f"(hi), "f"(lo));
    return r;
}
__device__ __forceinline__ uint32_t pack_f16(float lo, float hi) {
    uint32_t r;
    asm("cvt.rn.f16x2.f32 %0, %1, %2;\n" : "=r"(r) : "f"(hi), "f"(lo));
    return r;
}
__device__ __forceinline__ uint32_t pack_f16_rz(float lo, float hi) {
    uint32_t r;
    asm("cvt.rz.f16x2.f32 %0, %1, %2;\n" : "=r"(r) : "f"(hi), "f"(lo));
    return r;
}
__device__ __forceinline__ float bf_lo(uint32_t w) { return __uint_as_float(w << 16); }
__device__ __forceinline__ float bf_hi(uint32_t w) { return __uint_as_float(w & 0xffff0000u); }
__device__ __forceinline__ uint32_t hadd2_bf(uint32_t a, uint32_t b) {
    __nv_bfloat162 r = __hadd2_rn(*reinterpret_cast<__nv_bfloat162*>(&a), *reinterpret_cast<__nv_bfloat162*>(&b));
    return *reinterpret_cast<uint32_t*>(&r);
}
__device__ __forceinline__ uint32_t hsub2_bf(uint32_t a, uint32_t b) {
    __nv_bfloat162 r = __hsub2_rn(*reinterpret_cast<__nv_bfloat162*>(&a), *reinterpret_cast<__nv_bfloat162*>(&b));
    return *reinterpret_cast<uint32_t*>(&r);
}
__device__ __forceinline__ uint32_t hmul2_bf(uint32_t a, uint32_t b) {
    __nv_bfloat162 r = __hmul2_rn(*reinterpret_cast<__nv_bfloat162*>(&a), *reinterpret_cast<__nv_bfloat162*>(&b));
    return *reinterpret_cast<uint32_t*>(&r);
}
__device__ __forceinline__ uint32_t hfma2_bf(uint32_t a, uint32_t b, uint32_t c) { uint32_t r; asm("fma.rn.bf16x2 %0, %1, %2, %3;\n" : "=r"(r) : "r"(a), "r"(b), "r"(c)); return r; }
__device__ __forceinline__ uint32_t hmul2(uint32_t a, uint32_t b) { uint32_t r; asm("mul.rn.f16x2 %0, %1, %2;\n" : "=r"(r) : "r"(a), "r"(b)); return r; }
__device__ __forceinline__ uint32_t hadd2(uint32_t a, uint32_t b) { uint32_t r; asm("add.rn.f16x2 %0, %1, %2;\n" : "=r"(r) : "r"(a), "r"(b)); return r; }
__device__ __forceinline__ uint32_t hfma2(uint32_t a, uint32_t b, uint32_t c) { uint32_t r; asm("fma.rn.f16x2 %0, %1, %2, %3;\n" : "=r"(r) : "r"(a), "r"(b), "r"(c)); return r; }
__device__ __forceinline__ uint32_t hfms2(uint32_t a, uint32_t b, uint32_t c) {
    uint32_t r;
    asm("{\n.reg .b32 n;\nneg.f16x2 n, %2;\nfma.rn.f16x2 %0, %1, n, %3;\n}\n" : "=r"(r) : "r"(a), "r"(b), "r"(c));
    return r;
}
__device__ __forceinline__ uint32_t nzw(uint32_t w) { uint32_t r; asm("max.u32 %0, %1, 1;\n" : "=r"(r) : "r"(w)); return r; }
__device__ __forceinline__ uint32_t nzf(float f) { const uint32_t w = __float_as_uint(f); return w ? w : 0x80000000u; }
__device__ __forceinline__ uint32_t smem_u32(const void* p) { return (uint32_t)__cvta_generic_to_shared(p); }
__device__ __forceinline__ uint32_t lds32(uint32_t addr) {
    uint32_t v;
    asm volatile("ld.shared.u32 %0, [%1];\n" : "=r"(v) : "r"(addr) : "memory");
    return v;
}
__device__ __forceinline__ uint32_t lds16(uint32_t addr) {
    unsigned short v;
    asm volatile("ld.shared.u16 %0, [%1];\n" : "=h"(v) : "r"(addr) : "memory");
    return v;
}
__device__ __forceinline__ uint2 lds64(uint32_t addr) {
    uint2 v;
    asm volatile("ld.shared.v2.u32 {%0,%1}, [%2];\n" : "=r"(v.x), "=r"(v.y) : "r"(addr) : "memory");
    return v;
}
__device__ __forceinline__ uint4 lds128(uint32_t addr) {
    uint4 v;
    asm volatile("ld.shared.v4.u32 {%0,%1,%2,%3}, [%4];\n" : "=r"(v.x), "=r"(v.y), "=r"(v.z), "=r"(v.w) : "r"(addr) : "memory");
    return v;
}
__device__ __forceinline__ float ldsf(uint32_t addr) { return __uint_as_float(lds32(addr)); }
__device__ __forceinline__ void sts32(uint32_t addr, uint32_t v) { asm volatile("st.shared.u32 [%0], %1;\n" ::"r"(addr), "r"(v) : "memory"); }
__device__ __forceinline__ void sts16(uint32_t addr, uint32_t v) { asm volatile("st.shared.u16 [%0], %1;\n" ::"r"(addr), "h"((unsigned short)v) : "memory"); }
__device__ __forceinline__ void stsf(uint32_t addr, float v) { sts32(addr, __float_as_uint(v)); }
__device__ __forceinline__ void sts64(uint32_t addr, uint32_t a, uint32_t b) { asm volatile("st.shared.v2.u32 [%0], {%1,%2};\n" ::"r"(addr), "r"(a), "r"(b) : "memory"); }
__device__ __forceinline__ void sts64f(uint32_t addr, float a, float b) { sts64(addr, __float_as_uint(a), __float_as_uint(b)); }
__device__ __forceinline__ void sts128(uint32_t addr, uint32_t a, uint32_t b, uint32_t c, uint32_t d) {
    asm volatile("st.shared.v4.u32 [%0], {%1,%2,%3,%4};\n" ::"r"(addr), "r"(a), "r"(b), "r"(c), "r"(d) : "memory");
}
__device__ __forceinline__ void sts128f(uint32_t addr, const float (&v)[4]) {
    sts128(addr, __float_as_uint(v[0]), __float_as_uint(v[1]), __float_as_uint(v[2]), __float_as_uint(v[3]));
}
__device__ __forceinline__ void ldsm_x4(uint32_t& r0, uint32_t& r1, uint32_t& r2, uint32_t& r3, uint32_t addr) {
    asm volatile("ldmatrix.sync.aligned.m8n8.x4.shared.b16 {%0,%1,%2,%3}, [%4];\n"
                 : "=r"(r0), "=r"(r1), "=r"(r2), "=r"(r3) : "r"(addr) : "memory");
}
__device__ __forceinline__ void ldsm_x4_t(uint32_t& r0, uint32_t& r1, uint32_t& r2, uint32_t& r3, uint32_t addr) {
    asm volatile("ldmatrix.sync.aligned.m8n8.x4.trans.shared.b16 {%0,%1,%2,%3}, [%4];\n"
                 : "=r"(r0), "=r"(r1), "=r"(r2), "=r"(r3) : "r"(addr) : "memory");
}
__device__ __forceinline__ void ldsm_x2_t(uint32_t& r0, uint32_t& r1, uint32_t addr) {
    asm volatile("ldmatrix.sync.aligned.m8n8.x2.trans.shared.b16 {%0,%1}, [%2];\n" : "=r"(r0), "=r"(r1) : "r"(addr) : "memory");
}
__device__ __forceinline__ void ldsm_x1_t(uint32_t& r0, uint32_t addr) {
    asm volatile("ldmatrix.sync.aligned.m8n8.x1.trans.shared.b16 {%0}, [%1];\n" : "=r"(r0) : "r"(addr) : "memory");
}
__device__ __forceinline__ void stsm_x4(uint32_t addr, uint32_t r0, uint32_t r1, uint32_t r2, uint32_t r3) {
    asm volatile("stmatrix.sync.aligned.m8n8.x4.shared.b16 [%0], {%1,%2,%3,%4};\n" ::"r"(addr), "r"(r0), "r"(r1), "r"(r2), "r"(r3) : "memory");
}
__device__ __forceinline__ void stsm_x4_t(uint32_t addr, uint32_t r0, uint32_t r1, uint32_t r2, uint32_t r3) {
    asm volatile("stmatrix.sync.aligned.m8n8.x4.trans.shared.b16 [%0], {%1,%2,%3,%4};\n" ::"r"(addr), "r"(r0), "r"(r1), "r"(r2), "r"(r3) : "memory");
}
__device__ __forceinline__ uint32_t movm(uint32_t a) {
    uint32_t d;
    asm volatile("movmatrix.sync.aligned.m8n8.trans.b16 %0, %1;\n" : "=r"(d) : "r"(a));
    return d;
}
__device__ __forceinline__ void mma_f16(float (&c)[4], uint32_t a0, uint32_t a1, uint32_t a2, uint32_t a3, uint32_t b0, uint32_t b1) {
    asm volatile(
        "mma.sync.aligned.m16n8k16.row.col.f32.f16.f16.f32 {%0,%1,%2,%3}, {%4,%5,%6,%7}, {%8,%9}, {%0,%1,%2,%3};\n"
        : "+f"(c[0]), "+f"(c[1]), "+f"(c[2]), "+f"(c[3])
        : "r"(a0), "r"(a1), "r"(a2), "r"(a3), "r"(b0), "r"(b1));
}
__device__ __forceinline__ void mma_bf16(float (&c)[4], uint32_t a0, uint32_t a1, uint32_t a2, uint32_t a3, uint32_t b0, uint32_t b1) {
    asm volatile(
        "mma.sync.aligned.m16n8k16.row.col.f32.bf16.bf16.f32 {%0,%1,%2,%3}, {%4,%5,%6,%7}, {%8,%9}, {%0,%1,%2,%3};\n"
        : "+f"(c[0]), "+f"(c[1]), "+f"(c[2]), "+f"(c[3])
        : "r"(a0), "r"(a1), "r"(a2), "r"(a3), "r"(b0), "r"(b1));
}
__device__ __forceinline__ void mma_bf16_k8(float (&c)[4], uint32_t a0, uint32_t a1, uint32_t b0) {
    asm volatile("mma.sync.aligned.m16n8k8.row.col.f32.bf16.bf16.f32 {%0,%1,%2,%3}, {%4,%5}, {%6}, {%0,%1,%2,%3};\n"
                 : "+f"(c[0]), "+f"(c[1]), "+f"(c[2]), "+f"(c[3]) : "r"(a0), "r"(a1), "r"(b0));
}
__device__ __forceinline__ void bar_sync(int id, int n) { asm volatile("bar.sync %0, %1;\n" ::"r"(id), "r"(n) : "memory"); }
__device__ __forceinline__ void bar_arrive(int id, int n) { asm volatile("bar.arrive %0, %1;\n" ::"r"(id), "r"(n) : "memory"); }
__device__ __forceinline__ bool bar_or(int id, int n, bool v) {
    uint32_t r;
    asm volatile("{\n.reg .pred p, q;\nsetp.ne.u32 p, %3, 0;\nbar.red.or.pred q, %1, %2, p;\nselp.u32 %0, 1, 0, q;\n}\n" : "=r"(r) : "r"(id), "r"(n), "r"((uint32_t)v) : "memory");
    return r;
}
__device__ __forceinline__ uint32_t and3(uint32_t a, uint32_t b, uint32_t c) { uint32_t r; asm("lop3.b32 %0, %1, %2, %3, 0x80;\n" : "=r"(r) : "r"(a), "r"(b), "r"(c)); return r; }
__device__ __forceinline__ uint32_t or3(uint32_t a, uint32_t b, uint32_t c) { uint32_t r; asm("lop3.b32 %0, %1, %2, %3, 0xfe;\n" : "=r"(r) : "r"(a), "r"(b), "r"(c)); return r; }
__device__ __forceinline__ uint32_t min3(uint32_t a, uint32_t b, uint32_t c) { uint32_t r; asm("{\n.reg .u32 t;\nmin.u32 t, %2, %3;\nmin.u32 %0, %1, t;\n}\n" : "=r"(r) : "r"(a), "r"(b), "r"(c)); return r; }
__device__ __forceinline__ uint32_t xor_or(uint32_t a, uint32_t b, uint32_t c) { uint32_t r; asm("lop3.b32 %0, %1, %2, %3, 0x7e;\n" : "=r"(r) : "r"(a), "r"(b), "r"(c)); return r; }
__device__ __forceinline__ uint32_t pin(uint32_t v) { uint32_t r; asm volatile("shfl.sync.bfly.b32 %0, %1, 0, 0x1f, 0xffffffff;\n" : "=r"(r) : "r"(v) : "memory"); return r; }
__device__ __forceinline__ uint4 ld_poll(const void* p) {
    uint4 v;
    asm volatile("ld.relaxed.gpu.global.v4.u32 {%0,%1,%2,%3}, [%4];\n" : "=r"(v.x), "=r"(v.y), "=r"(v.z), "=r"(v.w) : "l"(p) : "memory");
    return v;
}
__device__ __forceinline__ uint2 ld_poll64(const void* p) {
    uint2 v;
    asm volatile("ld.relaxed.gpu.global.v2.u32 {%0,%1}, [%2];\n" : "=r"(v.x), "=r"(v.y) : "l"(p) : "memory");
    return v;
}
__device__ __forceinline__ uint32_t ld_poll32(const void* p) {
    uint32_t v;
    asm volatile("ld.relaxed.gpu.global.u32 %0, [%1];\n" : "=r"(v) : "l"(p) : "memory");
    return v;
}
__device__ __forceinline__ uint32_t ld_acquire32(const void* p) {
    uint32_t v;
    asm volatile("ld.acquire.gpu.global.u32 %0, [%1];\n" : "=r"(v) : "l"(p) : "memory");
    return v;
}
__device__ __forceinline__ uint4 ldg128(const void* p) {
    uint4 v;
    asm volatile("ld.global.nc.v4.u32 {%0,%1,%2,%3}, [%4];\n" : "=r"(v.x), "=r"(v.y), "=r"(v.z), "=r"(v.w) : "l"(p));
    return v;
}
__device__ __forceinline__ uint2 ldg64(const void* p) {
    uint2 v;
    asm volatile("ld.global.nc.v2.u32 {%0,%1}, [%2];\n" : "=r"(v.x), "=r"(v.y) : "l"(p));
    return v;
}
__device__ __forceinline__ uint32_t ldg16(const void* p) {
    uint32_t v;
    asm volatile("ld.global.nc.u16 %0, [%1];\n" : "=r"(v) : "l"(p));
    return v;
}
__device__ __forceinline__ uint4 ldo128(const void* p) {
    uint4 v;
    asm volatile("ld.relaxed.cta.global.v4.u32 {%0,%1,%2,%3}, [%4];\n" : "=r"(v.x), "=r"(v.y), "=r"(v.z), "=r"(v.w) : "l"(p) : "memory");
    return v;
}
__device__ __forceinline__ uint2 ldo64(const void* p) {
    uint2 v;
    asm volatile("ld.relaxed.cta.global.v2.u32 {%0,%1}, [%2];\n" : "=r"(v.x), "=r"(v.y) : "l"(p) : "memory");
    return v;
}
__device__ __forceinline__ uint32_t ldo16(const void* p) {
    uint32_t v;
    asm volatile("ld.relaxed.cta.global.u16 %0, [%1];\n" : "=r"(v) : "l"(p) : "memory");
    return v;
}
__device__ __forceinline__ void stg128(void* p, uint32_t a, uint32_t b, uint32_t c, uint32_t d) {
    asm volatile("st.global.v4.u32 [%0], {%1,%2,%3,%4};\n" ::"l"(p), "r"(a), "r"(b), "r"(c), "r"(d) : "memory");
}
__device__ __forceinline__ void stg64(void* p, uint32_t a, uint32_t b) { asm volatile("st.global.v2.u32 [%0], {%1,%2};\n" ::"l"(p), "r"(a), "r"(b) : "memory"); }
__device__ __forceinline__ uint32_t min4(const uint4& v) { return min(min(v.x, v.y), min(v.z, v.w)); }
#define SPIN_LIMIT (1 << 21)
#define TRAP() __trap()
__device__ __forceinline__ void mbar_init(uint32_t bar, uint32_t cnt) { asm volatile("mbarrier.init.shared::cta.b64 [%0], %1;\n" ::"r"(bar), "r"(cnt) : "memory"); }
__device__ __forceinline__ void mbar_expect(uint32_t bar, uint32_t bytes) {
    asm volatile("mbarrier.arrive.expect_tx.shared::cta.b64 _, [%0], %1;\n" ::"r"(bar), "r"(bytes) : "memory");
}
__device__ __forceinline__ void mbar_arrive(uint32_t bar) { asm volatile("mbarrier.arrive.shared::cta.b64 _, [%0];\n" ::"r"(bar) : "memory"); }
__device__ __forceinline__ void mbar_wait_cluster(uint32_t bar) {
    asm volatile(
        "{\n.reg .pred p;\n"
        "W_%=:\n"
        "mbarrier.try_wait.parity.acquire.cluster.shared::cta.b64 p, [%0], 0;\n"
        "@!p bra W_%=;\n}\n" ::"r"(bar) : "memory");
}
__device__ __forceinline__ void mbar_wait(uint32_t bar) {
    asm volatile(
        "{\n.reg .pred p;\n"
        "W_%=:\n"
        "mbarrier.try_wait.parity.shared::cta.b64 p, [%0], 0;\n"
        "@!p bra W_%=;\n}\n" ::"r"(bar) : "memory");
}
__device__ __forceinline__ void mbar_wait1(uint32_t bar) {
    asm volatile(
        "{\n.reg .pred p;\n"
        "W_%=:\n"
        "mbarrier.try_wait.parity.shared::cta.b64 p, [%0], 1;\n"
        "@!p bra W_%=;\n}\n" ::"r"(bar) : "memory");
}
__device__ __forceinline__ bool mbar_test(uint32_t bar) {
    uint32_t r;
    asm volatile("{\n.reg .pred p;\nmbarrier.test_wait.parity.shared::cta.b64 p, [%1], 0;\nselp.u32 %0, 1, 0, p;\n}\n" : "=r"(r) : "r"(bar) : "memory");
    return __any_sync(0xffffffffu, r);
}
__device__ __forceinline__ void bulk_g2s(uint32_t dst, const void* src, uint32_t bytes, uint32_t bar) {
    asm volatile("cp.async.bulk.shared::cluster.global.mbarrier::complete_tx::bytes [%0], [%1], %2, [%3];\n" ::"r"(dst), "l"(src), "r"(bytes), "r"(bar) : "memory");
}
__device__ __forceinline__ void bulk_s2g(void* dst, uint32_t src, uint32_t bytes) {
    asm volatile("cp.async.bulk.global.shared::cta.bulk_group [%0], [%1], %2;\ncp.async.bulk.commit_group;\n" ::"l"(dst), "r"(src), "r"(bytes) : "memory");
}
__device__ __forceinline__ void bulk_s2g_nc(void* dst, uint32_t src, uint32_t bytes) {
    asm volatile("cp.async.bulk.global.shared::cta.bulk_group [%0], [%1], %2;\n" ::"l"(dst), "r"(src), "r"(bytes) : "memory");
}
__device__ __forceinline__ void tma_2d(uint32_t dst, const CUtensorMap* tm, int c0, int c1, uint32_t bar) {
    asm volatile("cp.async.bulk.tensor.2d.shared::cluster.global.mbarrier::complete_tx::bytes [%0], [%1, {%3, %4}], [%2];\n"
                 ::"r"(dst), "l"(tm), "r"(bar), "r"(c0), "r"(c1) : "memory");
}
__device__ __forceinline__ void tma_4d(uint32_t dst, const CUtensorMap* tm, int c0, int c3, uint32_t bar) {
    asm volatile("cp.async.bulk.tensor.4d.shared::cluster.global.mbarrier::complete_tx::bytes [%0], [%1, {%3, %4, %4, %5}], [%2];\n"
                 ::"r"(dst), "l"(tm), "r"(bar), "r"(c0), "r"(0), "r"(c3) : "memory");
}
__device__ __forceinline__ void tma_4d_mc(uint32_t dst, const CUtensorMap* tm, int c0, int c3, uint32_t bar) {
    asm volatile("cp.async.bulk.tensor.4d.shared::cluster.global.mbarrier::complete_tx::bytes.multicast::cluster [%0], [%1, {%3, %4, %4, %5}], [%2], %6;\n"
                 ::"r"(dst), "l"(tm), "r"(bar), "r"(c0), "r"(0), "r"(c3), "h"((unsigned short)3) : "memory");
}
__device__ __forceinline__ void l2_prefetch(const void* src, uint32_t bytes) {
    asm volatile("cp.async.bulk.prefetch.L2.global [%0], %1;\n" ::"l"(src), "r"(bytes) : "memory");
}
__device__ __forceinline__ bool elect_one() {
    uint32_t r;
    asm volatile("{\n.reg .pred p;\nelect.sync _|p, 0xffffffff;\nselp.u32 %0, 1, 0, p;\n}\n" : "=r"(r));
    return r;
}
__device__ __forceinline__ void delay(uint32_t clks) {
    uint32_t t0, t1;
    asm volatile("mov.u32 %0, %%clock;" : "=r"(t0) :: "memory");
    do { asm volatile("mov.u32 %0, %%clock;" : "=r"(t1) :: "memory"); } while (t1 - t0 < clks);
}
__device__ __forceinline__ void fence_async() { asm volatile("fence.proxy.async.shared::cta;\n" ::: "memory"); }

__device__ __forceinline__ float2 cmul(float2 a, float2 b) {
    return make_float2(fmaf(a.x, b.x, -a.y * b.y), fmaf(a.x, b.y, a.y * b.x));
}
__device__ __forceinline__ float2 csq(float2 a) {
    float p = a.x * a.y;
    return make_float2(fmaf(a.x, a.x, -a.y * a.y), p + p);
}
__device__ __forceinline__ float ex2_approx(float x) { float r; asm("ex2.approx.ftz.f32 %0, %1;\n" : "=f"(r) : "f"(x)); return r; }
__device__ __forceinline__ float exp_bf(float x) { return rbf(ex2_approx(__fmul_ru(x, 1.4426950408889634f))); }
__device__ __forceinline__ float2 cexp_e(float lr2, float li, float e) {
    const float m = ex2_approx(lr2 * e);
    return make_float2(m * __cosf(li * e), m * __sinf(li * e));
}
__device__ __forceinline__ float rcp_approx(float x) { float r; asm("rcp.approx.ftz.f32 %0, %1;\n" : "=f"(r) : "f"(x)); return r; }
__device__ __forceinline__ float sigmoid_f(float x) { return rcp_approx(1.0f + ex2_approx(x * -1.4426950408889634f)); }
__device__ __forceinline__ float sqrt_approx(float x) { float r; asm("sqrt.approx.ftz.f32 %0, %1;\n" : "=f"(r) : "f"(x)); return r; }

__device__ __forceinline__ void wg_fence() { asm volatile("wgmma.fence.sync.aligned;\n" ::: "memory"); }
__device__ __forceinline__ void wg_commit() { asm volatile("wgmma.commit_group.sync.aligned;\n" ::: "memory"); }
__device__ __forceinline__ void wg_wait0() { asm volatile("wgmma.wait_group.sync.aligned 0;\n" ::: "memory"); }
template <int T> __device__ __forceinline__ void wg_mma(float (&acc)[16][4], const uint32_t* a, uint64_t desc);
template <int T> __device__ __forceinline__ void wg_first(float (&acc)[16][4], const uint32_t* a, uint64_t desc);
template <> __device__ __forceinline__ void wg_mma<0>(float (&acc)[16][4], const uint32_t* a, uint64_t desc) {
    asm volatile("wgmma.mma_async.sync.aligned.m64n128k16.f32.f16.f16 {%0,%1,%2,%3,%4,%5,%6,%7,%8,%9,%10,%11,%12,%13,%14,%15,%16,%17,%18,%19,%20,%21,%22,%23,%24,%25,%26,%27,%28,%29,%30,%31,%32,%33,%34,%35,%36,%37,%38,%39,%40,%41,%42,%43,%44,%45,%46,%47,%48,%49,%50,%51,%52,%53,%54,%55,%56,%57,%58,%59,%60,%61,%62,%63}, {%64,%65,%66,%67}, %68, 1, 1, 1, 0;\n"
                 : "+f"(acc[0][0]), "+f"(acc[0][1]), "+f"(acc[0][2]), "+f"(acc[0][3]), "+f"(acc[1][0]), "+f"(acc[1][1]), "+f"(acc[1][2]), "+f"(acc[1][3]), "+f"(acc[2][0]), "+f"(acc[2][1]), "+f"(acc[2][2]), "+f"(acc[2][3]), "+f"(acc[3][0]), "+f"(acc[3][1]), "+f"(acc[3][2]), "+f"(acc[3][3]), "+f"(acc[4][0]), "+f"(acc[4][1]), "+f"(acc[4][2]), "+f"(acc[4][3]), "+f"(acc[5][0]), "+f"(acc[5][1]), "+f"(acc[5][2]), "+f"(acc[5][3]), "+f"(acc[6][0]), "+f"(acc[6][1]), "+f"(acc[6][2]), "+f"(acc[6][3]), "+f"(acc[7][0]), "+f"(acc[7][1]), "+f"(acc[7][2]), "+f"(acc[7][3]), "+f"(acc[8][0]), "+f"(acc[8][1]), "+f"(acc[8][2]), "+f"(acc[8][3]), "+f"(acc[9][0]), "+f"(acc[9][1]), "+f"(acc[9][2]), "+f"(acc[9][3]), "+f"(acc[10][0]), "+f"(acc[10][1]), "+f"(acc[10][2]), "+f"(acc[10][3]), "+f"(acc[11][0]), "+f"(acc[11][1]), "+f"(acc[11][2]), "+f"(acc[11][3]), "+f"(acc[12][0]), "+f"(acc[12][1]), "+f"(acc[12][2]), "+f"(acc[12][3]), "+f"(acc[13][0]), "+f"(acc[13][1]), "+f"(acc[13][2]), "+f"(acc[13][3]), "+f"(acc[14][0]), "+f"(acc[14][1]), "+f"(acc[14][2]), "+f"(acc[14][3]), "+f"(acc[15][0]), "+f"(acc[15][1]), "+f"(acc[15][2]), "+f"(acc[15][3])
                 : "r"(a[0]), "r"(a[1]), "r"(a[2]), "r"(a[3]), "l"(desc));
}
template <> __device__ __forceinline__ void wg_mma<2>(float (&acc)[16][4], const uint32_t* a, uint64_t desc) {
    asm volatile("wgmma.mma_async.sync.aligned.m64n112k16.f32.f16.f16 {%0,%1,%2,%3,%4,%5,%6,%7,%8,%9,%10,%11,%12,%13,%14,%15,%16,%17,%18,%19,%20,%21,%22,%23,%24,%25,%26,%27,%28,%29,%30,%31,%32,%33,%34,%35,%36,%37,%38,%39,%40,%41,%42,%43,%44,%45,%46,%47,%48,%49,%50,%51,%52,%53,%54,%55}, {%56,%57,%58,%59}, %60, 1, 1, 1, 0;\n"
                 : "+f"(acc[2][0]), "+f"(acc[2][1]), "+f"(acc[2][2]), "+f"(acc[2][3]), "+f"(acc[3][0]), "+f"(acc[3][1]), "+f"(acc[3][2]), "+f"(acc[3][3]), "+f"(acc[4][0]), "+f"(acc[4][1]), "+f"(acc[4][2]), "+f"(acc[4][3]), "+f"(acc[5][0]), "+f"(acc[5][1]), "+f"(acc[5][2]), "+f"(acc[5][3]), "+f"(acc[6][0]), "+f"(acc[6][1]), "+f"(acc[6][2]), "+f"(acc[6][3]), "+f"(acc[7][0]), "+f"(acc[7][1]), "+f"(acc[7][2]), "+f"(acc[7][3]), "+f"(acc[8][0]), "+f"(acc[8][1]), "+f"(acc[8][2]), "+f"(acc[8][3]), "+f"(acc[9][0]), "+f"(acc[9][1]), "+f"(acc[9][2]), "+f"(acc[9][3]), "+f"(acc[10][0]), "+f"(acc[10][1]), "+f"(acc[10][2]), "+f"(acc[10][3]), "+f"(acc[11][0]), "+f"(acc[11][1]), "+f"(acc[11][2]), "+f"(acc[11][3]), "+f"(acc[12][0]), "+f"(acc[12][1]), "+f"(acc[12][2]), "+f"(acc[12][3]), "+f"(acc[13][0]), "+f"(acc[13][1]), "+f"(acc[13][2]), "+f"(acc[13][3]), "+f"(acc[14][0]), "+f"(acc[14][1]), "+f"(acc[14][2]), "+f"(acc[14][3]), "+f"(acc[15][0]), "+f"(acc[15][1]), "+f"(acc[15][2]), "+f"(acc[15][3])
                 : "r"(a[0]), "r"(a[1]), "r"(a[2]), "r"(a[3]), "l"(desc));
}
template <> __device__ __forceinline__ void wg_mma<4>(float (&acc)[16][4], const uint32_t* a, uint64_t desc) {
    asm volatile("wgmma.mma_async.sync.aligned.m64n96k16.f32.f16.f16 {%0,%1,%2,%3,%4,%5,%6,%7,%8,%9,%10,%11,%12,%13,%14,%15,%16,%17,%18,%19,%20,%21,%22,%23,%24,%25,%26,%27,%28,%29,%30,%31,%32,%33,%34,%35,%36,%37,%38,%39,%40,%41,%42,%43,%44,%45,%46,%47}, {%48,%49,%50,%51}, %52, 1, 1, 1, 0;\n"
                 : "+f"(acc[4][0]), "+f"(acc[4][1]), "+f"(acc[4][2]), "+f"(acc[4][3]), "+f"(acc[5][0]), "+f"(acc[5][1]), "+f"(acc[5][2]), "+f"(acc[5][3]), "+f"(acc[6][0]), "+f"(acc[6][1]), "+f"(acc[6][2]), "+f"(acc[6][3]), "+f"(acc[7][0]), "+f"(acc[7][1]), "+f"(acc[7][2]), "+f"(acc[7][3]), "+f"(acc[8][0]), "+f"(acc[8][1]), "+f"(acc[8][2]), "+f"(acc[8][3]), "+f"(acc[9][0]), "+f"(acc[9][1]), "+f"(acc[9][2]), "+f"(acc[9][3]), "+f"(acc[10][0]), "+f"(acc[10][1]), "+f"(acc[10][2]), "+f"(acc[10][3]), "+f"(acc[11][0]), "+f"(acc[11][1]), "+f"(acc[11][2]), "+f"(acc[11][3]), "+f"(acc[12][0]), "+f"(acc[12][1]), "+f"(acc[12][2]), "+f"(acc[12][3]), "+f"(acc[13][0]), "+f"(acc[13][1]), "+f"(acc[13][2]), "+f"(acc[13][3]), "+f"(acc[14][0]), "+f"(acc[14][1]), "+f"(acc[14][2]), "+f"(acc[14][3]), "+f"(acc[15][0]), "+f"(acc[15][1]), "+f"(acc[15][2]), "+f"(acc[15][3])
                 : "r"(a[0]), "r"(a[1]), "r"(a[2]), "r"(a[3]), "l"(desc));
}
template <> __device__ __forceinline__ void wg_mma<6>(float (&acc)[16][4], const uint32_t* a, uint64_t desc) {
    asm volatile("wgmma.mma_async.sync.aligned.m64n80k16.f32.f16.f16 {%0,%1,%2,%3,%4,%5,%6,%7,%8,%9,%10,%11,%12,%13,%14,%15,%16,%17,%18,%19,%20,%21,%22,%23,%24,%25,%26,%27,%28,%29,%30,%31,%32,%33,%34,%35,%36,%37,%38,%39}, {%40,%41,%42,%43}, %44, 1, 1, 1, 0;\n"
                 : "+f"(acc[6][0]), "+f"(acc[6][1]), "+f"(acc[6][2]), "+f"(acc[6][3]), "+f"(acc[7][0]), "+f"(acc[7][1]), "+f"(acc[7][2]), "+f"(acc[7][3]), "+f"(acc[8][0]), "+f"(acc[8][1]), "+f"(acc[8][2]), "+f"(acc[8][3]), "+f"(acc[9][0]), "+f"(acc[9][1]), "+f"(acc[9][2]), "+f"(acc[9][3]), "+f"(acc[10][0]), "+f"(acc[10][1]), "+f"(acc[10][2]), "+f"(acc[10][3]), "+f"(acc[11][0]), "+f"(acc[11][1]), "+f"(acc[11][2]), "+f"(acc[11][3]), "+f"(acc[12][0]), "+f"(acc[12][1]), "+f"(acc[12][2]), "+f"(acc[12][3]), "+f"(acc[13][0]), "+f"(acc[13][1]), "+f"(acc[13][2]), "+f"(acc[13][3]), "+f"(acc[14][0]), "+f"(acc[14][1]), "+f"(acc[14][2]), "+f"(acc[14][3]), "+f"(acc[15][0]), "+f"(acc[15][1]), "+f"(acc[15][2]), "+f"(acc[15][3])
                 : "r"(a[0]), "r"(a[1]), "r"(a[2]), "r"(a[3]), "l"(desc));
}
template <> __device__ __forceinline__ void wg_mma<8>(float (&acc)[16][4], const uint32_t* a, uint64_t desc) {
    asm volatile("wgmma.mma_async.sync.aligned.m64n64k16.f32.f16.f16 {%0,%1,%2,%3,%4,%5,%6,%7,%8,%9,%10,%11,%12,%13,%14,%15,%16,%17,%18,%19,%20,%21,%22,%23,%24,%25,%26,%27,%28,%29,%30,%31}, {%32,%33,%34,%35}, %36, 1, 1, 1, 0;\n"
                 : "+f"(acc[8][0]), "+f"(acc[8][1]), "+f"(acc[8][2]), "+f"(acc[8][3]), "+f"(acc[9][0]), "+f"(acc[9][1]), "+f"(acc[9][2]), "+f"(acc[9][3]), "+f"(acc[10][0]), "+f"(acc[10][1]), "+f"(acc[10][2]), "+f"(acc[10][3]), "+f"(acc[11][0]), "+f"(acc[11][1]), "+f"(acc[11][2]), "+f"(acc[11][3]), "+f"(acc[12][0]), "+f"(acc[12][1]), "+f"(acc[12][2]), "+f"(acc[12][3]), "+f"(acc[13][0]), "+f"(acc[13][1]), "+f"(acc[13][2]), "+f"(acc[13][3]), "+f"(acc[14][0]), "+f"(acc[14][1]), "+f"(acc[14][2]), "+f"(acc[14][3]), "+f"(acc[15][0]), "+f"(acc[15][1]), "+f"(acc[15][2]), "+f"(acc[15][3])
                 : "r"(a[0]), "r"(a[1]), "r"(a[2]), "r"(a[3]), "l"(desc));
}
template <> __device__ __forceinline__ void wg_mma<10>(float (&acc)[16][4], const uint32_t* a, uint64_t desc) {
    asm volatile("wgmma.mma_async.sync.aligned.m64n48k16.f32.f16.f16 {%0,%1,%2,%3,%4,%5,%6,%7,%8,%9,%10,%11,%12,%13,%14,%15,%16,%17,%18,%19,%20,%21,%22,%23}, {%24,%25,%26,%27}, %28, 1, 1, 1, 0;\n"
                 : "+f"(acc[10][0]), "+f"(acc[10][1]), "+f"(acc[10][2]), "+f"(acc[10][3]), "+f"(acc[11][0]), "+f"(acc[11][1]), "+f"(acc[11][2]), "+f"(acc[11][3]), "+f"(acc[12][0]), "+f"(acc[12][1]), "+f"(acc[12][2]), "+f"(acc[12][3]), "+f"(acc[13][0]), "+f"(acc[13][1]), "+f"(acc[13][2]), "+f"(acc[13][3]), "+f"(acc[14][0]), "+f"(acc[14][1]), "+f"(acc[14][2]), "+f"(acc[14][3]), "+f"(acc[15][0]), "+f"(acc[15][1]), "+f"(acc[15][2]), "+f"(acc[15][3])
                 : "r"(a[0]), "r"(a[1]), "r"(a[2]), "r"(a[3]), "l"(desc));
}
template <> __device__ __forceinline__ void wg_mma<12>(float (&acc)[16][4], const uint32_t* a, uint64_t desc) {
    asm volatile("wgmma.mma_async.sync.aligned.m64n32k16.f32.f16.f16 {%0,%1,%2,%3,%4,%5,%6,%7,%8,%9,%10,%11,%12,%13,%14,%15}, {%16,%17,%18,%19}, %20, 1, 1, 1, 0;\n"
                 : "+f"(acc[12][0]), "+f"(acc[12][1]), "+f"(acc[12][2]), "+f"(acc[12][3]), "+f"(acc[13][0]), "+f"(acc[13][1]), "+f"(acc[13][2]), "+f"(acc[13][3]), "+f"(acc[14][0]), "+f"(acc[14][1]), "+f"(acc[14][2]), "+f"(acc[14][3]), "+f"(acc[15][0]), "+f"(acc[15][1]), "+f"(acc[15][2]), "+f"(acc[15][3])
                 : "r"(a[0]), "r"(a[1]), "r"(a[2]), "r"(a[3]), "l"(desc));
}
template <> __device__ __forceinline__ void wg_mma<14>(float (&acc)[16][4], const uint32_t* a, uint64_t desc) {
    asm volatile("wgmma.mma_async.sync.aligned.m64n16k16.f32.f16.f16 {%0,%1,%2,%3,%4,%5,%6,%7}, {%8,%9,%10,%11}, %12, 1, 1, 1, 0;\n"
                 : "+f"(acc[14][0]), "+f"(acc[14][1]), "+f"(acc[14][2]), "+f"(acc[14][3]), "+f"(acc[15][0]), "+f"(acc[15][1]), "+f"(acc[15][2]), "+f"(acc[15][3])
                 : "r"(a[0]), "r"(a[1]), "r"(a[2]), "r"(a[3]), "l"(desc));
}
template <> __device__ __forceinline__ void wg_first<0>(float (&acc)[16][4], const uint32_t* a, uint64_t desc) {
    asm volatile("wgmma.mma_async.sync.aligned.m64n128k16.f32.f16.f16 {%0,%1,%2,%3,%4,%5,%6,%7,%8,%9,%10,%11,%12,%13,%14,%15,%16,%17,%18,%19,%20,%21,%22,%23,%24,%25,%26,%27,%28,%29,%30,%31,%32,%33,%34,%35,%36,%37,%38,%39,%40,%41,%42,%43,%44,%45,%46,%47,%48,%49,%50,%51,%52,%53,%54,%55,%56,%57,%58,%59,%60,%61,%62,%63}, {%64,%65,%66,%67}, %68, 0, 1, 1, 0;\n"
                 : "=f"(acc[0][0]), "=f"(acc[0][1]), "=f"(acc[0][2]), "=f"(acc[0][3]), "=f"(acc[1][0]), "=f"(acc[1][1]), "=f"(acc[1][2]), "=f"(acc[1][3]), "=f"(acc[2][0]), "=f"(acc[2][1]), "=f"(acc[2][2]), "=f"(acc[2][3]), "=f"(acc[3][0]), "=f"(acc[3][1]), "=f"(acc[3][2]), "=f"(acc[3][3]), "=f"(acc[4][0]), "=f"(acc[4][1]), "=f"(acc[4][2]), "=f"(acc[4][3]), "=f"(acc[5][0]), "=f"(acc[5][1]), "=f"(acc[5][2]), "=f"(acc[5][3]), "=f"(acc[6][0]), "=f"(acc[6][1]), "=f"(acc[6][2]), "=f"(acc[6][3]), "=f"(acc[7][0]), "=f"(acc[7][1]), "=f"(acc[7][2]), "=f"(acc[7][3]), "=f"(acc[8][0]), "=f"(acc[8][1]), "=f"(acc[8][2]), "=f"(acc[8][3]), "=f"(acc[9][0]), "=f"(acc[9][1]), "=f"(acc[9][2]), "=f"(acc[9][3]), "=f"(acc[10][0]), "=f"(acc[10][1]), "=f"(acc[10][2]), "=f"(acc[10][3]), "=f"(acc[11][0]), "=f"(acc[11][1]), "=f"(acc[11][2]), "=f"(acc[11][3]), "=f"(acc[12][0]), "=f"(acc[12][1]), "=f"(acc[12][2]), "=f"(acc[12][3]), "=f"(acc[13][0]), "=f"(acc[13][1]), "=f"(acc[13][2]), "=f"(acc[13][3]), "=f"(acc[14][0]), "=f"(acc[14][1]), "=f"(acc[14][2]), "=f"(acc[14][3]), "=f"(acc[15][0]), "=f"(acc[15][1]), "=f"(acc[15][2]), "=f"(acc[15][3])
                 : "r"(a[0]), "r"(a[1]), "r"(a[2]), "r"(a[3]), "l"(desc));
}
template <> __device__ __forceinline__ void wg_first<4>(float (&acc)[16][4], const uint32_t* a, uint64_t desc) {
    asm volatile("wgmma.mma_async.sync.aligned.m64n96k16.f32.f16.f16 {%0,%1,%2,%3,%4,%5,%6,%7,%8,%9,%10,%11,%12,%13,%14,%15,%16,%17,%18,%19,%20,%21,%22,%23,%24,%25,%26,%27,%28,%29,%30,%31,%32,%33,%34,%35,%36,%37,%38,%39,%40,%41,%42,%43,%44,%45,%46,%47}, {%48,%49,%50,%51}, %52, 0, 1, 1, 0;\n"
                 : "=f"(acc[4][0]), "=f"(acc[4][1]), "=f"(acc[4][2]), "=f"(acc[4][3]), "=f"(acc[5][0]), "=f"(acc[5][1]), "=f"(acc[5][2]), "=f"(acc[5][3]), "=f"(acc[6][0]), "=f"(acc[6][1]), "=f"(acc[6][2]), "=f"(acc[6][3]), "=f"(acc[7][0]), "=f"(acc[7][1]), "=f"(acc[7][2]), "=f"(acc[7][3]), "=f"(acc[8][0]), "=f"(acc[8][1]), "=f"(acc[8][2]), "=f"(acc[8][3]), "=f"(acc[9][0]), "=f"(acc[9][1]), "=f"(acc[9][2]), "=f"(acc[9][3]), "=f"(acc[10][0]), "=f"(acc[10][1]), "=f"(acc[10][2]), "=f"(acc[10][3]), "=f"(acc[11][0]), "=f"(acc[11][1]), "=f"(acc[11][2]), "=f"(acc[11][3]), "=f"(acc[12][0]), "=f"(acc[12][1]), "=f"(acc[12][2]), "=f"(acc[12][3]), "=f"(acc[13][0]), "=f"(acc[13][1]), "=f"(acc[13][2]), "=f"(acc[13][3]), "=f"(acc[14][0]), "=f"(acc[14][1]), "=f"(acc[14][2]), "=f"(acc[14][3]), "=f"(acc[15][0]), "=f"(acc[15][1]), "=f"(acc[15][2]), "=f"(acc[15][3])
                 : "r"(a[0]), "r"(a[1]), "r"(a[2]), "r"(a[3]), "l"(desc));
}

#define SDLY 1300
#define UDLY 1400
#define KDLY 850
#define FDLY 1000
#define FDLY2 400
#define DDLY 300
#define WDLY 500
#define HW 15
#define FIX(v) do { if ((v) == 1u) TRAP(); } while (0)
#define STAMPW(i) STAMPY(i)
#define STAMP2(i) STAMP(i)
#undef STAMPX
#define STAMPX(i)
struct Params {
    const bf16 *x, *lar, *aim, *cre, *cim, *ldt, *dsk;
    Scratch* s;
    const bf16* wr;
    bf16* out;
};

#define TOK(g) (2 * (g) - ((g) & 1))
#define ROWTOK(r) (TOK((r) & 7) + (((r) >> 2) & 2))
__device__ __forceinline__ void ln_partial(const uint32_t (&H)[2][4], float (&d)[2][4]) {
#pragma unroll
    for (int i = 0; i < 8; i++) d[i >> 2][i & 3] = 0.f;
#pragma unroll
    for (int k = 0; k < 4; k++)
#pragma unroll
        for (int hf = 0; hf < 2; hf++) mma_bf16_k8(d[hf], H[hf][k], 0x3f803f80u, H[hf][k]);
}
__device__ __forceinline__ float sum18(uint32_t a) {
    const uint4 p = lds128(a), q = lds128(a + 16), r = lds128(a + 32), s = lds128(a + 48);
    const uint2 u = lds64(a + 64);
#define F(x) __uint_as_float(x)
    return (((F(p.x) + F(p.y)) + (F(p.z) + F(p.w))) + ((F(q.x) + F(q.y)) + (F(q.z) + F(q.w)))) +
           (((F(r.x) + F(r.y)) + (F(r.z) + F(r.w))) + ((F(s.x) + F(s.y)) + (F(s.z) + F(s.w))) + (F(u.x) + F(u.y)));
#undef F
}
__device__ __forceinline__ void ln_stats(float sm, float sq, float& mb, float& sd) {
    const float m0 = sm * (1.0f / 576.0f);
    const float mean = fmaf(fmaf(-m0, 576.0f, sm), 1.0f / 576.0f, m0);
    const float var = fmaxf(fmaf(-mean, mean, sq * (1.0f / 576.0f)), 0.f);
    mb = rbf(mean);
    sd = rbf(sqrt_approx(rbf(rbf(var) + 1e-5f)));
}
__device__ __forceinline__ void ln_finish(float v, int lane, float& mb, float& rc) {
    const float o = __shfl_xor_sync(0xffffffffu, v, 16);
    float sd;
    ln_stats(lane < 16 ? v : o, lane < 16 ? o : v, mb, sd);
    rc = rcp_approx(sd);
}
__device__ __forceinline__ uint32_t ln_apply(uint32_t w, uint32_t m2, uint32_t rh, uint32_t rl) {
    const uint32_t d = hsub2_bf(w, m2);
    return hfma2_bf(d, rh, hmul2_bf(d, rl));
}
__device__ __forceinline__ void stat_store(uint32_t a, float mb, float rc, uint32_t extra) {
    const float rh = rbf(rc);
    sts64(a, (__float_as_uint(mb) >> 16) | (extra << 16), pack_bf16(rh, rc - rh));
}
#define STAT_M(s) __byte_perm((s).x, (s).x, 0x1010)
#define STAT_H(s) __byte_perm((s).y, (s).y, 0x1010)
#define STAT_L(s) __byte_perm((s).y, (s).y, 0x3232)

__device__ __forceinline__ void hcmul(uint32_t re, uint32_t im, uint32_t zx, uint32_t zy, uint32_t& ore, uint32_t& oim) {
    ore = hfms2(im, zy, hmul2(re, zx));
    oim = hfma2(re, zy, hmul2(im, zx));
}

struct KGen {
    uint32_t A[2][4][4];
    float2 z1, z8, z64, z128, T[9];
};
__device__ __forceinline__ void kgen_setup(KGen& k, float lar, float aim, float dt) {
    const float lr2 = -(exp_bf(lar) * dt) * 1.4426950408889634f, li = aim * dt;
    k.z1 = cexp_e(lr2, li, 1.0f);
    k.z8 = cexp_e(lr2, li, 8.0f);
    k.z64 = cexp_e(lr2, li, 64.0f);
}
__device__ __forceinline__ void kgen_rows(KGen& k, uint32_t tb, int lane) {
    const float2 z8 = k.z8, z64 = k.z64;
    const uint32_t row = tb + lane * 16;
    k.z128 = csq(z64);
    const float2 z16 = csq(z8), z24 = cmul(z16, z8), z32 = csq(z16), z40 = cmul(z32, z8), z48 = csq(z24), z56 = cmul(z32, z24);
    uint32_t re[4], im[4], a[4], b[4];
    re[0] = pack_f16(1.0f, z8.x); im[0] = pack_f16(0.0f, z8.y);
    re[1] = pack_f16(z16.x, z24.x); im[1] = pack_f16(z16.y, z24.y);
    re[2] = pack_f16(z32.x, z40.x); im[2] = pack_f16(z32.y, z40.y);
    re[3] = pack_f16(z48.x, z56.x); im[3] = pack_f16(z48.y, z56.y);
    sts128(row, re[0], re[1], re[2], re[3]);
    sts128(row + 1024, im[0], im[1], im[2], im[3]);
    const uint32_t zx = pack_f16(z64.x, z64.x), zy = pack_f16(z64.y, z64.y), zw = pack_f16(k.z128.x, k.z128.y);
#pragma unroll
    for (int j = 0; j < 4; j++) hcmul(re[j], im[j], zx, zy, a[j], b[j]);
    sts128(row + 512, a[0], a[1], a[2], a[3]);
    sts128(row + 1536, b[0], b[1], b[2], b[3]);
    const int mi = lane >> 3;
    const uint32_t zd = tb + 2048 + mi * 16;
    sts16(tb + 2048 + lane * 2, zw); sts16(tb + 2112 + lane * 2, zw >> 16);
    __syncwarp();
    const uint32_t ad = tb + (lane & 7) * 16 + mi * 512;
    ldsm_x4(a[0], a[1], a[2], a[3], zd);
    ldsm_x4(b[0], b[1], b[2], b[3], zd + 64);
#pragma unroll
    for (int ks = 0; ks < 4; ks++) {
        ldsm_x4_t(k.A[0][ks][0], k.A[0][ks][1], k.A[0][ks][2], k.A[0][ks][3], ad + ks * 128);
        hcmul(k.A[0][ks][0], k.A[0][ks][2], a[ks], b[ks], k.A[1][ks][0], k.A[1][ks][2]);
        hcmul(k.A[0][ks][1], k.A[0][ks][3], a[ks], b[ks], k.A[1][ks][1], k.A[1][ks][3]);
    }
}
__device__ __forceinline__ void kgen_chain(KGen& k, uint32_t cr, uint32_t ci, float cs) {
    k.T[0] = make_float2(bf_lo(cr) * cs, -bf_lo(ci) * cs);
    const float2 y1 = make_float2(k.z1.x, -k.z1.y);
#pragma unroll
    for (int c = 1; c < 8; c++) k.T[c] = cmul(k.T[c - 1], y1);
    k.T[8] = cmul(k.T[0], make_float2(k.z8.x, -k.z8.y));
}
__device__ __forceinline__ void kgen_cols(KGen& k, uint32_t tb, uint32_t t5, int lane) {
    const uint32_t row = tb + lane * 16;
    const float2 (&T)[9] = k.T;
    const float2 y128 = make_float2(k.z128.x, -k.z128.y);
    const float2 y256 = csq(y128), y512 = csq(y256), y768 = cmul(y512, y256), y1024 = csq(y512);
    const float2 c1032 = cmul(T[8], y1024);
    __syncwarp();
    sts128(row, pack_f16(T[0].x, T[1].x), pack_f16(T[2].x, T[3].x), pack_f16(T[4].x, T[5].x), pack_f16(T[6].x, T[7].x));
    sts128(row + 512, pack_f16(T[0].y, T[1].y), pack_f16(T[2].y, T[3].y), pack_f16(T[4].y, T[5].y), pack_f16(T[6].y, T[7].y));
    uint32_t a[4], b[4];
    {
        const uint32_t zx = pack_f16(y256.x, y256.x), zy = pack_f16(y256.y, y256.y);
        hcmul(pack_f16(T[0].x, T[2].x), pack_f16(T[0].y, T[2].y), zx, zy, a[0], b[0]);
        hcmul(pack_f16(T[4].x, T[6].x), pack_f16(T[4].y, T[6].y), zx, zy, a[1], b[1]);
        const uint32_t r04 = pack_f16(T[0].x, T[4].x), i04 = pack_f16(T[0].y, T[4].y);
        hcmul(r04, i04, pack_f16(y512.x, y512.x), pack_f16(y512.y, y512.y), a[2], b[2]);
        hcmul(r04, i04, pack_f16(y768.x, y768.x), pack_f16(y768.y, y768.y), a[3], b[3]);
    }
    sts128(row + 1024, a[0], a[1], a[2], a[3]);
    sts128(row + 1536, b[0], b[1], b[2], b[3]);
    {
        const uint32_t r0 = pack_f16(1.0f, y256.x), i0 = pack_f16(0.0f, y256.y), r1 = pack_f16(y512.x, y768.x), i1 = pack_f16(y512.y, y768.y);
        const uint32_t zx = pack_f16(T[8].x, T[8].x), zy = pack_f16(T[8].y, T[8].y), wx = pack_f16(c1032.x, c1032.x), wy = pack_f16(c1032.y, c1032.y);
        hcmul(r0, i0, zx, zy, a[0], b[0]); hcmul(r1, i1, zx, zy, a[1], b[1]);
        hcmul(r0, i0, wx, wy, a[2], b[2]); hcmul(r1, i1, wx, wy, a[3], b[3]);
    }
    sts128(row + 2048, a[0], a[1], a[2], a[3]);
    sts128(t5 + lane * 16, b[0], b[1], b[2], b[3]);
}
__device__ __forceinline__ void kgen_mma(const KGen& k, uint32_t tb, uint32_t t5, int lane) {
    __syncwarp();
    float acc[2][3][4];
#pragma unroll
    for (int i = 0; i < 6; i++)
#pragma unroll
        for (int j = 0; j < 4; j++) acc[i / 3][i % 3][j] = 0.f;
    const int mi = lane >> 3;
    const uint32_t ro = ((lane & 7) + 8 * (mi >> 1)) * 16, bd = tb + ro + (mi & 1) * 512, b2 = ro + ((mi & 1) ? t5 : tb + 2048);
#pragma unroll
    for (int kp = 0; kp < 2; kp++)
#pragma unroll
        for (int j = 0; j < 3; j++) {
            uint32_t b[4];
            ldsm_x4_t(b[0], b[1], b[2], b[3], (j < 2 ? bd + j * 1024 : b2) + kp * 256);
#pragma unroll
            for (int h = 0; h < 2; h++)
#pragma unroll
                for (int m = 0; m < 2; m++) {
                    const uint32_t (&A)[4] = k.A[m][2 * kp + h];
                    mma_f16(acc[m][j], A[0], A[1], A[2], A[3], b[2 * h], b[2 * h + 1]);
                }
        }
    __syncwarp();
#define PK(j) pack_f16(acc[0][j][0], acc[0][j][1]), pack_f16(acc[0][j][2], acc[0][j][3]), pack_f16(acc[1][j][0], acc[1][j][1]), pack_f16(acc[1][j][2], acc[1][j][3])
    stsm_x4(tb + lane * 16, PK(0));
    stsm_x4(tb + 512 + lane * 16, PK(1));
    stsm_x4_t(tb + 1024 + (lane & 7) * 80 + mi * 16, PK(2));
#undef PK
}
__device__ __forceinline__ uint32_t table_buf(uint32_t sb, int warp) { return sb + SM_PL + warp * TBW; }

__device__ __forceinline__ uint4 lds16x4(uint32_t a) { return make_uint4(lds16(a), lds16(a + TBW), lds16(a + 2 * TBW), lds16(a + 3 * TBW)); }
__device__ __forceinline__ void combine_setup(uint32_t sb, int warp, int lane, uint32_t kw, uint32_t& o, uint32_t& n, uint32_t& d) {
    const int wq = warp & 3;
    const uint32_t a = table_buf(sb, warp & ~3);
    o = wq == 3 ? a + 1024 + 320 + (lane >> 3) * 80 + (lane & 7) * 8 : a + (wq ? 504 + wq * 8 : 0) + lane * 16;
    n = a + 1024 + wq * 80 + lane * 2;
    d = wq < 3 ? kw + (wq == 2 ? KW_P : 32 + wq * 512) + lane * 16 : kw + KW_H + 8 + lane * 8;
}
__device__ __forceinline__ void kgen_combine(int wq, int lane, uint32_t o, uint32_t na, uint32_t d) {
#define S4(f) hadd2(hadd2(u.f, v.f), hadd2(w.f, x.f))
#define H4(v) hadd2(hadd2(v.x, v.y), hadd2(v.z, v.w))
#define BP __byte_perm
    if (wq == 0) {
        const uint4 u = lds128(o), v = lds128(o + TBW), w = lds128(o + 2 * TBW), x = lds128(o + 3 * TBW), nn = lds16x4(na);
        const uint32_t n = H4(nn), k0 = S4(x), k2 = S4(y), k4 = S4(z), k6 = S4(w);
        sts128(d, BP(k0, k0, 0x1032), BP(k0, k2, 0x3254), BP(k2, k2, 0x1032), BP(k2, k4, 0x3254));
        sts128(d + KW_PL, BP(k4, k4, 0x1032), BP(k4, k6, 0x3254), BP(k6, k6, 0x1032), BP(k6, n, 0x3254));
        if (lane == 0) sts32(d + KW_PL - 4, k0 & 0xffffu);
    } else {
        const uint2 u = lds64(o), v = lds64(o + TBW), w = lds64(o + 2 * TBW), x = lds64(o + 3 * TBW);
        uint4 nn = make_uint4(0u, 0u, 0u, 0u), mm = nn;
        if (wq < 3) nn = lds16x4(na);
        if (wq == 2) mm = lds16x4(na + 80);
        const uint32_t k0 = S4(x), k2 = S4(y), n = H4(nn), m = H4(mm);
        if (wq == 3) {
            sts64(d, k0, k2);
        } else if (wq == 1) {
            const uint32_t cc = BP(k2, k2, 0x1010);
            sts128(d, BP(k0, k0, 0x1010), BP(k0, k0, 0x1032), BP(k0, k2, 0x3254), cc);
            sts128(d + KW_PL, cc, BP(k2, k2, 0x1032), BP(k2, n, 0x3254), BP(n, n, 0x1010));
        } else {
            const uint32_t w40 = BP(k0, k0, 0x1032), w84 = BP(k0, n, 0x3254), w0 = BP(k0, k0, 0x1010), w4 = BP(k0, k0, 0x3232), w8 = BP(n, n, 0x1010);
            sts64(d, w40, w84);
            sts64(d + 512, BP(k2, k2, 0x1032), BP(k2, m, 0x3254));
            if (lane < 8) { sts128(d - (KW_P - 1056), w0, w0, w40, w4); sts128(d - (KW_P - 1056 - KW_PL), w4, w84, w8, w8); }
            if (lane == 31) sts16(d + (KW_H + 6 - KW_P - 496), m);
        }
    }
#undef S4
#undef H4
#undef BP
}

__device__ __forceinline__ int c_exponent(const uint2& r, const uint2& i, float dt) {
    const uint32_t mx = __vmaxu2(__vmaxu2(r.x & 0x7fff7fffu, r.y & 0x7fff7fffu), __vmaxu2(i.x & 0x7fff7fffu, i.y & 0x7fff7fffu));
    return __reduce_max_sync(0xffffffffu, max(mx, mx << 16) + (__float_as_uint(dt) & 0x7f800000u)) >> 23;
}

#define YQ 2
#define F0 0
__device__ __forceinline__ int warp_v() { int l; asm volatile("mov.u32 %0, %%tid.x;" : "=r"(l)); return __shfl_sync(0xffffffffu, l >> 5, 0); }
__device__ __forceinline__ int lane_v() { int l; asm volatile("mov.u32 %0, %%laneid;" : "=r"(l)); return l; }
__device__ __forceinline__ uint32_t prmt_v(uint32_t a, uint32_t b, uint32_t s) { uint32_t d; asm volatile("prmt.b32 %0, %1, %2, %3;\n" : "=r"(d) : "r"(a), "r"(b), "r"(s)); return d; }
__device__ __forceinline__ uint32_t mov_v(uint32_t a) { uint32_t d; asm volatile("mov.b32 %0, %1;\n" : "=r"(d) : "r"(a)); return d; }
template <int G>
__device__ __forceinline__ void conv_rename(float (&acc)[16][4]) {
#pragma unroll
    for (int i = G; i < 16; i++)
#pragma unroll
        for (int j = 0; j < 4; j++) { float v; asm volatile("mov.b32 %0, %1;\n" : "=f"(v) : "f"(acc[i][j])); acc[i][j] = v; }
}
struct Conv {
    uint32_t kw;
    uint32_t wa;
    uint32_t pa, s2;
    uint32_t s8;
    uint32_t id;
    uint32_t lc;
    uint32_t fs;
    uint32_t fl, yo;
    uint32_t yp;
    size_t ycopy;
    uint32_t ps;
    uint64_t d0;
    int warp;
};
struct Pk { uint32_t w[4]; };
__device__ __forceinline__ Pk pk2(const float (&u)[4], const float (&v)[4]) {
    Pk r;
    r.w[0] = pack_f16(u[0], u[1]); r.w[1] = pack_f16(u[2], u[3]); r.w[2] = pack_f16(v[0], v[1]); r.w[3] = pack_f16(v[2], v[3]);
    return r;
}
__device__ __forceinline__ void park(uint32_t a, const Pk& v) {
    asm volatile("stmatrix.sync.aligned.m8n8.x4.trans.shared.b16 [%0], {%1,%2,%3,%4};\n" ::"r"(a), "r"(v.w[0]), "r"(v.w[1]), "r"(v.w[2]), "r"(v.w[3]) : "memory");
}
__device__ __forceinline__ void conv_constants(uint32_t lc, int l) {
    const int d = (l >> 2) - 2 * (l & 3);
    const int e = d + 8, r4 = (e + 1 + ((e >> 2) & 1)) >> 2, p4 = (e + (((e - 1) >> 2) & 1)) >> 2;
    const uint32_t s2 = r4 == p4 ? 0x1010u : 0x3210u;
    sts64(lc + l * 8, KW_P + ((r4 - 5) >> 1) * 16 + ((r4 - 5) & 1) * 4, s2 | ((d < 0 ? s2 : 0x7654u) << 16));
    const int lo = (d >= 4) - (d < -3), ho = (d >= 5) - (d < -2), le = (d > 4) - (d < -4), he = (d > 5) - (d < -3);
    sts32(lc + 512 + l * 8, (0x5454u + lo * 0x22 + ho * 0x2200) | ((0x3232u + le * 0x22 + he * 0x2200) << 16));
    const int cc = l >> 2, j = l & 3;
    sts64(lc + 256 + l * 8, (j >> 1) * PL_HALF + (16 + cc) * 16 + (j & 1) * 8, (cc >> 1) * (DM * 64) + (cc & 1) * 32 + j * 8);
}
__device__ __forceinline__ void conv_selectors4(Conv& c) {
    const uint2 v = lds64(c.lc + lane_v() * 8);
    c.pa = v.x; c.s2 = v.y;
}
__device__ __forceinline__ void conv_selectors8(Conv& c) { c.s8 = lds32(c.lc + 512 + lane_v() * 8); }
template <int G, int I0, int I1>
__device__ __forceinline__ void conv_load(const Conv& c, uint32_t (&q)[9]) {
    const int wq = c.warp & 3;
    if (G < 2) {
#pragma unroll
        for (int i = I0; i < I1; i++) q[i] = lds32(c.wa + G * 512 + i * 16);
    } else if (G < 4) {
        const uint32_t a = (G == 2 && wq == 0) ? c.wa + 1024 : c.pa + c.kw + wq * 128 + (G < 2 ? 0 : G - 2) * 512;
#pragma unroll
        for (int i = I0; i < I1; i++) q[i] = lds32(a + i * 16);
    } else {
        const uint4 u = lds128(c.kw + KW_H + (G < 4 ? 0 : G - 4) * 64 + wq * 16);
        const uint2 v = lds64(c.kw + KW_H + (G < 4 ? 0 : G - 4) * 64 + wq * 16 + 16);
        q[0] = u.x; q[1] = u.y; q[2] = u.z; q[3] = u.w; q[4] = v.x; q[5] = v.y;
        if (G == 4 && wq == 0) { q[6] = lds32(c.pa + c.kw + 1024); q[7] = lds32(c.pa + c.kw + 1040); }
    }
}
template <int G, int J0, int J1>
__device__ __forceinline__ void conv_frag(const Conv& c, const uint32_t (&q)[9], uint32_t* a, const Pk& dp) {
    const uint32_t dep = dp.w[0];
    if (G < 4) {
        const uint32_t s = (G < 2 || (G == 2 && (c.warp & 3) == 0)) ? c.id : c.s2;
#pragma unroll
        for (int j = J0; j < J1; j++) {
            uint32_t* o = a + 4 * (j - J0);
            o[0] = prmt_v(q[2 * j + 1], dp.w[0], s); o[1] = prmt_v(q[2 * j + 2], dp.w[1], s); o[2] = prmt_v(q[2 * j], dp.w[2], s); o[3] = prmt_v(q[2 * j + 1], dp.w[3], s);
        }
    } else {
        const uint32_t so = prmt_v(c.s8, dep, c.id), se = prmt_v(c.s8, dep, c.id + 0x22);
#pragma unroll
        for (int j = J0; j < J1; j++) {
            uint32_t* o = a + 4 * (j - J0);
            o[0] = prmt_v(q[j + 1], q[j + 2], se); o[1] = prmt_v(q[j + 1], q[j + 2], so); o[2] = prmt_v(q[j], q[j + 1], so);
            if (G == 4 && j == 0 && (c.warp & 3) == 0) {
                o[2] = prmt_v(q[6], dep, c.s2);
                o[0] = prmt_v(q[7], o[0], c.s2 >> 16);
            }
            o[3] = mov_v(o[0]);
        }
    }
}
template <int G, int J0, int J1>
__device__ __forceinline__ void conv_frag(const Conv& c, const uint32_t (&q)[9], uint32_t* a, float depf) {
    const uint32_t d = __float_as_uint(depf);
    conv_frag<G, J0, J1>(c, q, a, Pk{{d, d, d, d}});
}
template <int G, int T, int J0, int J1>
__device__ __forceinline__ void conv_mma(float (&acc)[16][4], const Conv& c, const uint32_t* a) {
#pragma unroll
    for (int j = J0; j < J1; j++) wg_mma<T>(acc, a + 4 * (j - J0), c.d0 - 8 * (2 * G - T) - j);
}
__device__ __forceinline__ float h_lo(uint32_t w) { return __half2float(__ushort_as_half((unsigned short)(w & 0xffffu))); }
__device__ __forceinline__ float h_hi(uint32_t w) { return __half2float(__ushort_as_half((unsigned short)(w >> 16))); }
__device__ __forceinline__ void flush_setup(Conv& c) {
    const uint2 v = lds64(c.lc + 256 + lane_v() * 8);
    c.fl = v.x; c.yo = v.y;
}
template <int Q>
__device__ __forceinline__ void flush_load(const Conv& c, uint32_t pl, uint2 (&f)[4]) {
#pragma unroll
    for (int w = 0; w < 4; w++) f[w] = lds64(c.fl + pl + (Q & 1) * 512 + w * (PLW_B - 64));
}
template <int Q>
__device__ __forceinline__ void flush_load_first(const Conv& c, uint32_t pl, uint2 (&f)[4], float depf) {
    const uint32_t p = prmt_v(c.fl, __float_as_uint(depf), c.id) + pl + (Q & 1) * 512;
#define LDV64(d, a) asm volatile("ld.volatile.shared.v2.u32 {%0,%1}, [%2];\n" : "=r"(d.x), "=r"(d.y) : "r"(a) : "memory")
    LDV64(f[0], p); LDV64(f[1], p + (PLW_B - 64)); LDV64(f[2], p + 2 * (PLW_B - 64)); LDV64(f[3], p + 3 * (PLW_B - 64));
}
#define FDEP __uint_as_float(f[3].y)
template <int Q, int mode>
__device__ __forceinline__ void conv_flush(const Conv& c, const uint2 (&f)[4], unsigned char* gy, uint32_t rx) {
    const uint32_t a0 = hadd2(f[0].x, f[1].x), a1 = hadd2(f[2].x, f[3].x), b0 = hadd2(f[0].y, f[1].y), b1 = hadd2(f[2].y, f[3].y);
    if (Q > 0 && mode == 1) {
        const uint32_t ra = rx + 16 + (Q > 0 ? Q - 1 : 0) * 1024 + (c.warp & 3) * 256 + lane_v() * 8;
        asm volatile("st.async.shared::cluster.mbarrier::complete_tx::bytes.v2.b32 [%0], {%1,%2}, [%3];\n"
                     ::"r"(ra ^ 0x1000000u), "r"(hadd2(a0, a1)), "r"(hadd2(b0, b1)), "r"((rx + (Q > 1 ? 8 : 0)) ^ 0x1000000u) : "memory");
        return;
    }
    float v0 = h_lo(a0) + h_lo(a1), v1 = h_hi(a0) + h_hi(a1), v2 = h_lo(b0) + h_lo(b1), v3 = h_hi(b0) + h_hi(b1);
    if (Q > 0 && mode == 2) {
        const uint2 o = lds64(rx + 16 + (Q > 0 ? Q - 1 : 0) * 1024 + (c.warp & 3) * 256 + lane_v() * 8);
        v0 += h_lo(o.x); v1 += h_hi(o.x); v2 += h_lo(o.y); v3 += h_hi(o.y);
    }
    const uint32_t lo = hmul2_bf(pack_bf16(v0, v1), c.fs), hi = hmul2_bf(pack_bf16(v2, v3), c.fs);
    stg64(gy + Q * 32 * DM * 32 + (c.yo + (Q < YQ ? c.yp : 0u)), nzw(lo), nzw(hi));
}
template <int I, bool S = false> struct IC { static constexpr int value = I; static constexpr bool shared = S; };
template <class T> __device__ constexpr bool wg_is4() { return T::shared; }
#define SLOT(n) (c.ps + (2 + ((n) & 7)) * 128)
#define GO() do { wg_commit(); __syncwarp(); } while (0)
#define DEP acc[15][3]
template <class FG, class FP, class FN>
__device__ __forceinline__ void conv_head(Conv& c, float (&acc)[16][4], uint32_t (&q)[9], uint32_t (&r)[9], uint32_t* a, FG fg, FP pre, FN next) {
    c.id = 0x3210u + (c.warp >> 8);
    pre();
    conv_load<0, 0, 9>(c, q);
    conv_frag<0, 0, 1>(c, q, a, 0.f);
    wg_fence(); wg_first<0>(acc, a, c.d0); GO();
    park(c.ps, Pk{{0u, 0u, 0u, 0u}});
    wg_wait0();
    conv_frag<0, 1, 2>(c, q, a, DEP);
    wg_fence(); conv_mma<0, 0, 1, 2>(acc, c, a); GO();
    fg(IC<0>());
    wg_wait0();
    conv_frag<0, 2, 3>(c, q, a, DEP);
    wg_fence(); conv_mma<0, 0, 2, 3>(acc, c, a); GO();
    conv_load<1, 0, 5>(c, r);
    wg_wait0();
    conv_frag<0, 3, 4>(c, q, a, DEP);
    wg_fence(); conv_mma<0, 0, 3, 4>(acc, c, a); GO();
    conv_load<1, 5, 9>(c, r);
    fg(IC<1>());
    wg_wait0();
    const Pk k = pk2(acc[0], acc[1]);
    conv_rename<2>(acc);
    conv_frag<1, 0, 2>(c, r, a, k);
    wg_fence(); conv_mma<1, 2, 0, 2>(acc, c, a); GO();
    park(SLOT(0), k);
    next(IC<0>());
    fg(IC<2>());
    wg_wait0();
    conv_frag<1, 2, 4>(c, r, a, DEP);
    wg_fence(); conv_mma<1, 2, 2, 4>(acc, c, a); GO();
    next(IC<1>());
    fg(IC<3>());
    wg_wait0();
}
template <class FG, class FP>
__device__ __forceinline__ void conv_run(Conv& c, uint32_t pl, unsigned char* gy, FG fg, FP pre) {
    float acc[16][4];
    uint32_t q[9], r[9], a[32];
    uint2 f[4];
    const int bid = 1 + (c.warp >> 2);
    conv_head(c, acc, q, r, a, fg, pre, [&](auto i) { if (decltype(i)::value == 0) conv_selectors4(c); else conv_load<2, 0, 9>(c, q); });
    Pk k = pk2(acc[2], acc[3]);
    conv_rename<4>(acc);
    conv_frag<2, 0, 4>(c, q, a, k);
    wg_fence(); conv_mma<2, 4, 0, 4>(acc, c, a); GO();
    park(SLOT(2), k);
    conv_load<3, 0, 9>(c, q);
    flush_setup(c);
    bar_sync(bid, 128);
    fg(IC<4>());
    wg_wait0();
    conv_rename<6>(acc);
    if (F0) { flush_load_first<0>(c, pl, f, DEP); conv_frag<3, 0, 4>(c, q, a, FDEP); }
    else conv_frag<3, 0, 4>(c, q, a, DEP);
    wg_fence(); conv_mma<3, 6, 0, 4>(acc, c, a); GO();
    park(SLOT(4), pk2(acc[4], acc[5]));
    conv_load<4, 0, 9>(c, q);
    conv_selectors8(c);
    if (!F0) flush_load<0>(c, pl, f);
    conv_flush<0, 0>(c, f, gy, 0u);
    fg(IC<5>());
    wg_wait0();
    conv_rename<8>(acc);
    conv_frag<4, 0, 4>(c, q, a, DEP);
    wg_fence(); conv_mma<4, 8, 0, 4>(acc, c, a); GO();
    k = pk2(acc[6], acc[7]);
    park(SLOT(6), k);
    conv_load<5, 0, 9>(c, q);
    bar_sync(bid, 128);
    park(c.ps, k);
    fg(IC<6>());
    wg_wait0();
    conv_rename<10>(acc);
    flush_load_first<1>(c, pl, f, DEP);
    conv_frag<5, 0, 4>(c, q, a, FDEP);
    wg_fence(); conv_mma<5, 10, 0, 4>(acc, c, a); GO();
    park(SLOT(8), pk2(acc[8], acc[9]));
    conv_load<6, 0, 9>(c, q); conv_load<7, 0, 9>(c, r);
    conv_flush<1, 0>(c, f, gy, 0u);
    fg(IC<7>());
    wg_wait0();
    conv_rename<12>(acc);
    conv_frag<6, 0, 4>(c, q, a, DEP); conv_frag<7, 0, 4>(c, r, a + 16, DEP);
    wg_fence(); conv_mma<6, 12, 0, 4>(acc, c, a); conv_mma<7, 12, 0, 4>(acc, c, a + 16); GO();
    park(SLOT(10), pk2(acc[10], acc[11]));
    bar_sync(bid, 128);
    flush_load<2>(c, pl, f);
    conv_flush<2, 0>(c, f, gy, 0u);
    fg(IC<8>());
    if (c.id == 0) TRAP();
    wg_wait0();
    park(SLOT(12), pk2(acc[12], acc[13])); park(SLOT(14), pk2(acc[14], acc[15]));
    bar_sync(bid, 128);
    flush_load<3>(c, pl, f);
    conv_flush<3, 0>(c, f, gy, 0u);
}
template <class FG>
__device__ __forceinline__ void conv_outer(Conv& c, uint32_t pl, unsigned char* gy, uint32_t rx, FG fg) {
    float acc[16][4];
    uint32_t q[9], r[9], a[32];
    uint2 f[4], f2[4];
    const int bid = 1 + (c.warp >> 2);
    conv_head(c, acc, q, r, a, [&](auto gi) { if (decltype(gi)::value == 2) fg(IC<2, true>()); }, [&]() {}, [&](auto i) { if (decltype(i)::value == 0) conv_selectors8(c); else conv_load<6, 0, 9>(c, q); });
    park(SLOT(2), pk2(acc[2], acc[3])); park(SLOT(4), pk2(acc[4], acc[5]));
    const Pk k = pk2(acc[6], acc[7]);
    park(SLOT(6), k);
    conv_load<7, 0, 9>(c, r);
    conv_rename<12>(acc);
    conv_frag<6, 0, 4>(c, q, a, __uint_as_float(k.w[3])); conv_frag<7, 0, 4>(c, r, a + 16, __uint_as_float(k.w[3]));
    wg_fence(); conv_mma<6, 12, 0, 4>(acc, c, a); conv_mma<7, 12, 0, 4>(acc, c, a + 16); GO();
    flush_setup(c);
    bar_sync(bid, 128);
    flush_load<0>(c, pl, f); flush_load<1>(c, pl, f2);
    conv_flush<1, 1>(c, f2, gy, rx);
    conv_flush<0, 1>(c, f, gy, rx);
    wg_wait0();
    bar_sync(bid, 128);
    park(c.ps, k); park(SLOT(8), pk2(acc[8], acc[9])); park(SLOT(10), pk2(acc[10], acc[11]));
    park(SLOT(12), pk2(acc[12], acc[13])); park(SLOT(14), pk2(acc[14], acc[15]));
    bar_sync(bid, 128);
    flush_load<2>(c, pl, f); flush_load<3>(c, pl, f2);
    conv_flush<2, 1>(c, f, gy, rx);
    conv_flush<3, 1>(c, f2, gy, rx);
}
template <class FG>
__device__ __forceinline__ void conv_inner(Conv& c, uint32_t pl, unsigned char* gy, uint32_t rx, FG fg) {
    float acc[16][4];
    uint32_t q[9], a[16];
    uint2 f[4], f2[4];
    const int bid = 1 + (c.warp >> 2);
    c.id = 0x3210u + (c.warp >> 8);
    conv_selectors4(c);
    conv_load<2, 0, 9>(c, q);
    conv_frag<2, 0, 4>(c, q, a, 0.f);
    wg_fence(); wg_first<4>(acc, a, c.d0); conv_mma<2, 4, 1, 4>(acc, c, a + 4); GO();
    conv_load<3, 0, 9>(c, q);
    park(SLOT(2), Pk{{0u, 0u, 0u, 0u}});
    fg(IC<2, true>());
    wg_wait0();
    conv_rename<6>(acc);
    conv_frag<3, 0, 4>(c, q, a, DEP);
    wg_fence(); conv_mma<3, 6, 0, 4>(acc, c, a); GO();
    park(SLOT(4), pk2(acc[4], acc[5]));
    conv_load<4, 0, 9>(c, q);
    conv_selectors8(c);
    wg_wait0();
    conv_rename<8>(acc);
    conv_frag<4, 0, 4>(c, q, a, DEP);
    wg_fence(); conv_mma<4, 8, 0, 4>(acc, c, a); GO();
    const Pk k = pk2(acc[6], acc[7]);
    park(SLOT(6), k); park(c.ps, k);
    conv_load<5, 0, 9>(c, q);
    flush_setup(c);
    wg_wait0();
    conv_rename<10>(acc);
    conv_frag<5, 0, 4>(c, q, a, DEP);
    wg_fence(); conv_mma<5, 10, 0, 4>(acc, c, a); GO();
    park(SLOT(8), pk2(acc[8], acc[9]));
    bar_sync(bid, 128);
    flush_load<1>(c, pl, f);
    mbar_wait(rx);
    conv_flush<1, 2>(c, f, gy, rx);
    wg_wait0();
    bar_sync(bid, 128);
    park(SLOT(10), pk2(acc[10], acc[11])); park(SLOT(12), pk2(acc[12], acc[13])); park(SLOT(14), pk2(acc[14], acc[15]));
    bar_sync(bid, 128);
    flush_load<3>(c, pl, f); flush_load<2>(c, pl, f2);
    mbar_wait(rx + 8);
    conv_flush<3, 2>(c, f, gy, rx);
    conv_flush<2, 2>(c, f2, gy, rx);
}
#undef SLOT
#undef GO
#undef DEP
template <int U0, int U1>
__device__ __forceinline__ void weight_units(uint32_t sb, const CUtensorMap* tg, const CUtensorMap* tu, const CUtensorMap* td, bool w) {
    if (U1 > U0 && w && elect_one()) {
#pragma unroll
        for (int i = U0; i < U1; i++) {
            if (i < 12) tma_2d(sb + SM_WG + i * 6912, i < 6 ? tg : tu, 72 * (blockIdx.x >> 1), 288 * (blockIdx.x & 1) + (i % 6) * 48, sb + SM_MISC + 328);
            else tma_2d(sb + SM_WD + (i - 12) * 4736, td, 144 * (blockIdx.x & 1), 72 * (blockIdx.x >> 1) + 8 * (i - 12), sb + SM_MISC + 336);
        }
    }
}
#define WS 2110121111122004100
__device__ constexpr int wsched(int i) {
    unsigned long long v = WS;
    int n = 0;
    for (int k = 19; k >= 1; k--) { if (k < i) n += (int)(v % 10); v /= 10; }
    return n;
}
static_assert(wsched(20) == 21 && wsched(6) <= 7 && wsched(11) <= 12 && wsched(13) <= 14 && wsched(16) <= 17 && wsched(16) == wsched(15) && wsched(19) == 21, "");
#define WANY(i) (wsched((i) + 1) > wsched(i))
#define WPOINT(i, w) do { weight_units<wsched(i), wsched(i + 1)>(sb, &tm_g, &tm_u, &tm_d, w); } while (0)

__global__ void __launch_bounds__(NTHR, 1) __cluster_dims__(2, 1, 1)
fused_kernel(const Params p, const __grid_constant__ CUtensorMap tm_g, const __grid_constant__ CUtensorMap tm_u, const __grid_constant__ CUtensorMap tm_d, const __grid_constant__ CUtensorMap tm_x) {
    extern __shared__ __align__(1024) unsigned char smem[];
    const uint32_t sb = smem_u32(smem);
    const int tid = threadIdx.x, warp = __shfl_sync(0xffffffffu, tid >> 5, 0), lane = tid & 31;
    const int b = blockIdx.x, P = b >> 1, odd = b & 1;
    const int g = lane >> 2, t = lane & 3;
    const int wg = warp >> 2, t128 = tid & 127;
    const uint32_t s_stat = sb + SM_MISC;
    const uint32_t s_key = sb + SM_MISC + 128;
    const uint32_t s_rank = sb + SM_MISC + 256;
    const uint32_t s_k16 = sb + SM_MISC + 192;
    const uint32_t s_cnt = sb + SM_MISC + 320;
    const uint32_t bar_w = sb + SM_MISC + 328, bar_d = bar_w + 8, bar_g = bar_w + 16, bar_x = bar_w + 24, bar_v = bar_w + 32, bar_s = bar_w + 40, bar_h = bar_w + 48;
    STAMP(0);

    const int ch = wg < 4 ? 4 * b + wg : 512 + P;
    const uint32_t mo = tid < 512 ? 512 * b + tid : 65536 + 128 * P + t128, mq = (mo & ~127u) + 4 * lane;
    const uint32_t pl = ldo16(p.lar + mo), pa2 = ldo16(p.aim + mo), ldt = ldo16(p.ldt + (mo >> 7));
    const uint32_t pc = ldo16(p.cre + mo), pi = ldo16(p.cim + mo);
    const uint2 call_re = ldo64(p.cre + mq), call_im = ldo64(p.cim + mq);
    const uint32_t epl = ld_poll32(p.s->hint + (b & 7) * 32 + 1);
    if (wg < 4) {
        bar_arrive(0, NWRK);
        asm volatile("barrier.cluster.arrive.relaxed.aligned;\n" ::: "memory");
    } else {
        const int o = (4 * (warp & 3) + (g >> 1)) * 1152 + (g & 1) * 576 + t * 16;
        sts128(sb + SM_Z2 + t128 * 16, 0u, 0u, 0u, 0u); sts128(sb + SM_Z2 + 2048 + t128 * 16, 0u, 0u, 0u, 0u);
        if (warp == 16) sts128(sb + SM_Z2 + 4096 + lane * 16, 0u, 0u, 0u, 0u);
        fence_async();
        bar_sync(0, NWRK);
        STAMP(9);
#pragma unroll
        for (int c = 0; c < 9; c++)
            asm volatile("cp.async.cg.shared.global [%0], [%1], 16;\n" ::"r"(sb + SM_XT + o + c * 64), "l"(reinterpret_cast<const char*>(p.x) + b * 18432 + o + c * 64) : "memory");
        asm volatile("cp.async.commit_group;\n" ::: "memory");
        if (elect_one()) {
            mbar_init(bar_h + 8 * (warp & 3), 1);
            if (warp == 19) {
                mbar_init(bar_x, 1); mbar_init(bar_w, 1);
                mbar_expect(bar_x, 32768); mbar_expect(bar_w, 82944);
#pragma unroll
                for (int i = YQ; i < 4; i++) bulk_s2g(reinterpret_cast<unsigned char*>(p.s->y) + 32 * i * 18432 + b * 4608, sb + SM_Z2, 4608);
            } else if (warp == 18) {
                mbar_init(bar_s, 1); mbar_init(bar_v, 2); mbar_init(bar_d, 1); mbar_init(bar_g, 1); mbar_init(sb + SM_RX, 1); mbar_init(sb + SM_RX + 8, 1);
                mbar_expect(bar_v, 2 * 1152); mbar_expect(bar_d, 72 * WD_PITCH); mbar_expect(bar_g, 4608); mbar_expect(sb + SM_RX, 1024); mbar_expect(sb + SM_RX + 8, 2048);
            }
            asm volatile("fence.mbarrier_init.release.cluster;\n" ::: "memory");
        }
        __syncwarp();
        asm volatile("barrier.cluster.arrive.relaxed.aligned;\n" ::: "memory");
        if (warp == 19) {
            asm volatile("barrier.cluster.wait.aligned;\n" ::: "memory");
            if (elect_one()) tma_4d_mc(sb + SM_XC + odd * 16384, &tm_x, 8 * P, 2 * odd, bar_x);
            __syncwarp();
        }
        {
            if (!(g & 1) && t == (g >> 1)) *reinterpret_cast<volatile uint32_t*>(p.s->stat + 16 * b + 4 * (warp & 3) + t) = 0u;
            if (warp < 18) {
                unsigned char* const ud = reinterpret_cast<unsigned char*>(p.s->uT) + (size_t)(8 * (warp & 1) + 2 * (g >> 1)) * 16384 + b * 128 + (g & 1) * 32 + t * 8;
#pragma unroll
                for (int k = 0; k < 4; k++) *reinterpret_cast<volatile unsigned long long*>(ud + (k >> 1) * 16384 + (k & 1) * 64) = 0ull;
            }
        }
    }
    const uint32_t kw = sb + SM_KW + wg * KW_B;
    const uint32_t tb = table_buf(sb, warp), t5 = sb + SM_WD + warp * 512;
    STAMP(29);
    const float dt = exp_bf(bf_lo(ldt));
    const uint32_t ep = __reduce_or_sync(0xffffffffu, epl);
    auto stats = [&]() {
        const int wq = warp & 3;
        const uint32_t xa = sb + SM_XT + (4 * wq + (g >> 1)) * 1152 + (g & 1) * 576 + t * 16;
        const bool own = !(g & 1) && t == (g >> 1);
        float d[4][4] = {};
        asm volatile("cp.async.wait_group 0;\n" ::: "memory");
        STAMP(26);
        uint4 v[9];
#pragma unroll
        for (int c = 0; c < 9; c++) v[c] = lds128(xa + c * 64);
#pragma unroll
        for (int c = 0; c < 9; c++) {
            mma_bf16(d[2 * (c & 1)], v[c].x, 0x3f803f80u, v[c].y, 0x3f803f80u, v[c].x, v[c].y);
            mma_bf16(d[2 * (c & 1) + 1], v[c].z, 0x3f803f80u, v[c].w, 0x3f803f80u, v[c].z, v[c].w);
        }
        STAMP(27);
        float sm = (g & 1) ? (d[0][3] + d[1][3]) + (d[2][3] + d[3][3]) : (d[0][2] + d[1][2]) + (d[2][2] + d[3][2]);
        float sq = (g & 1) ? (d[0][1] + d[1][1]) + (d[2][1] + d[3][1]) : (d[0][0] + d[1][0]) + (d[2][0] + d[3][0]);
        sm += __shfl_xor_sync(0xffffffffu, sm, 4); sq += __shfl_xor_sync(0xffffffffu, sq, 4);
        if (lane == 0) mbar_arrive(bar_h + 8 * wq);
        float mb, sd;
        ln_stats(sm, sq, mb, sd);
        if (own) p.s->stat[16 * b + 4 * wq + t] = (__float_as_uint(mb) >> 16) | (__float_as_uint(sd) & 0x7fff0000u) | (ep << 31);
        STAMPX(22);
        if (own) stat_store(s_stat + (2 * wq + (t & 1) + 8 * (t >> 1)) * 8, mb, rcp_approx(sd), 0u);
        if (wq == 3) asm volatile("cp.async.bulk.wait_group 0;\n" ::: "memory");
        bar_sync(5, 128);
        STAMP(28);
        uint32_t now;
        asm volatile("mov.u32 %0, %%clock;" : "=r"(now) :: "memory");
        if (wq == 2) {
            conv_constants(sb + SM_LC, lane);
            __syncwarp();
            if (lane < 8) p.s->key3[8 * b + lane] = ep & 1u;
            if (lane == 0) {
                sts64(s_cnt, now, ep);
                mbar_arrive(bar_s);
                bulk_g2s(sb + SM_XT + 16 * 1152, p.dsk, 1152, bar_v);
                bulk_g2s(sb + SM_XT + 17 * 1152, p.wr, 1152, bar_v);
            }
            __syncwarp();
        }
        WPOINT(1, wq == 3);
        if (wq < 2) {
            unsigned char* const ud = reinterpret_cast<unsigned char*>(p.s->uT) + (size_t)(8 * wq + 2 * (g >> 1)) * 16384 + b * 128 + (g & 1) * 32 + t * 8;
            const uint32_t utag = (ep % 7u + 1u) * 0x10001u;
            uint32_t U[2][4];
#pragma unroll
            for (int hf = 0; hf < 2; hf++) {
                const uint2 st = lds64(s_stat + (g + 8 * hf) * 8);
                const uint4 xu = lds128(sb + SM_XT + (TOK(g) + 2 * hf) * 1152 + warp * 64 + t * 16);
                const uint32_t X[4] = {xu.x, xu.y, xu.z, xu.w};
#pragma unroll
                for (int k = 0; k < 4; k++) {
                    const uint32_t u = ln_apply(X[k], STAT_M(st), STAT_H(st), STAT_L(st));
                    U[hf][k] = movm((pack_f16(bf_lo(u), bf_hi(u)) & 0xfff8fff8u) | utag);
                }
            }
#pragma unroll
            for (int k = 0; k < 4; k++) stg64(ud + (k >> 1) * 16384 + (k & 1) * 64, U[0][k], U[1][k]);
        }
    };
    STAMP(1);
    if (wg < 4) { STAMPX(16); }
    KGen kg;
    kgen_setup(kg, bf_lo(pl), bf_lo(pa2), dt);
    kgen_rows(kg, tb, lane);
    STAMP(2);
    const int E = min(max(c_exponent(call_re, call_im, dt) - 243, -120), 120);
    kgen_chain(kg, pc, pi, dt * __uint_as_float((uint32_t)(128 - E) << 23));
    STAMP(3);
    kgen_cols(kg, tb, t5, lane);
    STAMP(4);
    if (wg == 4) stats();
    if (warp != 19) asm volatile("barrier.cluster.wait.aligned;\n" ::: "memory");
    if (wg < 4) { STAMPX(17); }
    if (t128 < 2 * UPAD) sts128(sb + SM_U + wg * USLOT_B + (t128 & 1) * ULO_B + (t128 >> 1) * 16, 0u, 0u, 0u, 0u);
    if (t128 >= 124) sts128(kw + (t128 & 1) * 16 + (t128 & 2) * (KW_PL / 2), 0u, 0u, 0u, 0u);
    if (warp < 15) sts128(sb + SM_Z2 + 4608 + tid * 16, 0u, 0u, 0u, 0u);
    uint32_t co, cn, cd;
    combine_setup(sb, warp, lane, kw, co, cn, cd);
    co = pin(co); cn = pin(cn); cd = pin(cd);
    const uint4* const usrc = reinterpret_cast<const uint4*>(p.s->stat) + pin(wg < 4 ? tid : 512 + (P >> 2) * 1024 + (t128 >> 1) * 8 + (P & 3) * 2 + (t128 & 1));
    if (wg < 4) mbar_wait(bar_h + 8 * (warp & 3));
    if (wg < 4) { STAMPX(19); }
    uint32_t trel;
    asm volatile("mov.u32 %0, %%clock;" : "=r"(trel) :: "memory");
    kgen_mma(kg, tb, t5, lane);
    if (wg < 4) { STAMPX(20); }
    STAMP(5);
    uint4 uv0, uv1;
    auto first_poll = [&](uint32_t dly) {
        mbar_wait(bar_s);
        const uint32_t t0 = lds32(s_cnt);
        uint32_t now;
        do { asm volatile("mov.u32 %0, %%clock;" : "=r"(now) :: "memory"); } while (now - t0 < dly);
        uv0 = ld_poll(usrc);
    };
    if (wg == 4) { first_poll(UDLY); uv1 = ld_poll(usrc + 512); }
    WPOINT(2, warp == 19);
    auto stat_poll = [&]() {
        uint32_t now;
        do { asm volatile("mov.u32 %0, %%clock;" : "=r"(now) :: "memory"); } while (now - trel < SDLY);
        uv0 = ld_poll(usrc);
    };
    bar_sync(1 + wg, 128);
    if (wg < 4) { STAMPX(21); }
    kgen_combine(warp & 3, lane, co, cn, cd);
    STAMP(6);
    if (wg < 4) { STAMPX(18); }
    WPOINT(3, warp == 19);
    if (wg < 4) stat_poll();
    {
        const int wq = warp & 3;
        Conv c;
        const uint32_t pln = sb + SM_PL + wg * PL_B;
        const int e = g - 2 * t + 7;
        c.kw = kw; c.wa = pin(kw + ((e >> 2) & 1) * KW_PL + (8 * wq + (e >> 3)) * 16 + (e & 3) * 4);
        c.ps = mov_v(pln + wq * PLW_B + ((lane >> 3) & 1) * PL_HALF + ((lane >> 4) * 8 + (lane & 7)) * 16); c.warp = warp;
        c.lc = sb + SM_LC; c.fs = (uint32_t)(127 + E) * 0x800080u; c.yp = (ep & 1u) * (NCTA * 18432u);
        c.d0 = ((uint64_t)(ULO_B >> 4) << 16) | ((uint64_t)(128 >> 4) << 32) | (uint64_t)(((sb + SM_U + wg * USLOT_B + UPAD * 16) & 0x3FFFF) >> 4);
        unsigned char* gy = reinterpret_cast<unsigned char*>(p.s->y) + ((size_t)(4 * wq) * DM + ch) * 64;
        auto hook = [&](auto gi) {
                     constexpr int G = decltype(gi)::value;
                     if (G == (wg_is4<decltype(gi)>() ? 2 : 5)) asm volatile("barrier.cluster.wait.aligned;\n" ::: "memory");
                     if (!wg_is4<decltype(gi)>() && G == 1) mbar_wait(bar_s);
                     if (!wg_is4<decltype(gi)>() && (G == 0 || G == 2) && warp == HW && elect_one()) {
                         unsigned char* const sc = reinterpret_cast<unsigned char*>(p.s);
                         if (G == 0) {
                             if (b < 96) bulk_s2g_nc(sc + offsetof(Scratch, part) + b * 12288, sb + SM_Z2, 12288);
                             bulk_s2g(sc + offsetof(Scratch, rows) + (127 - b) * 4608, sb + SM_Z2, 4608);
                         }
                         if (G == 2) {
                             if (YQ == 3) bulk_s2g_nc(sc + offsetof(Scratch, y) + (NCTA * 18432u - c.yp) + b * 13824 + 6912, sb + SM_Z2, 6912);
                             if (YQ) bulk_s2g(sc + offsetof(Scratch, y) + (NCTA * 18432u - c.yp) + b * (4608 * YQ), sb + SM_Z2, YQ == 3 ? 6912 : 4608 * YQ);
                         }
                     }
                     if (!wg_is4<decltype(gi)>()) WPOINT(6 + G, warp == (G >= 7 ? HW : 4 * (G % 3) + 1));
                     if (!wg_is4<decltype(gi)>() && G == 6 && warp == HW) {
                         asm volatile("cp.async.bulk.wait_group 0;\n" ::: "memory");
                         __syncwarp();
                         if (elect_one()) mbar_arrive(bar_v);
                     }
                 };
        if (wg < 4) {
            asm volatile("barrier.cluster.arrive.relaxed.aligned;\n" ::: "memory");
            conv_run(c, pln + wq * 128, gy, hook, [&]() {
                STAMPX(23);
                mbar_wait(bar_x);
                STAMPX(24);
                uint2 xc[4];
                uint32_t xw[4][2];
#pragma unroll
                for (int j = 0; j < 4; j++) xc[j] = lds64(sb + SM_XC + wg * 8192 + j * 2048 + t128 * 16 + odd * 8);
#pragma unroll
                for (int i = 0; i < 8; i++) {
                    const int k = i >> 1, h = i & 1;
                    xw[k][h] = prmt_v(k < 2 ? xc[2 * h].x : xc[2 * h].y, k < 2 ? xc[2 * h + 1].x : xc[2 * h + 1].y, (k & 1) ? 0x7632 : 0x5410);
                }
                const uint32_t ub = mov_v(sb + SM_U + UPAD * 16 + ((tid >> 1) & 1) * ULO_B + (tid >> 2) * 16 + (tid & 1) * 8), tag = ep << 31;
                int it = 0;
                while (min(min((int)(uv0.x ^ tag), (int)(uv0.y ^ tag)), min((int)(uv0.z ^ tag), (int)(uv0.w ^ tag))) < 0x10000) {
                    if (++it > SPIN_LIMIT) TRAP();
                    uv0 = ld_poll(usrc);
                }
                STAMP(8);
                STAMPX(26);
                const float r0 = rcp_approx(fabsf(bf_hi(uv0.x))), r1 = rcp_approx(fabsf(bf_hi(uv0.y))), r2 = rcp_approx(fabsf(bf_hi(uv0.z))), r3 = rcp_approx(fabsf(bf_hi(uv0.w)));
                const uint32_t m[2] = {__byte_perm(uv0.x, uv0.y, 0x5410), __byte_perm(uv0.z, uv0.w, 0x5410)};
                const uint32_t rh[2] = {pack_bf16(r0, r1), pack_bf16(r2, r3)};
                const uint32_t rl[2] = {pack_bf16(r0 - bf_lo(rh[0]), r1 - bf_hi(rh[0])), pack_bf16(r2 - bf_lo(rh[1]), r3 - bf_hi(rh[1]))};
#pragma unroll
                for (int k = 0; k < 4; k++) {
                    const uint32_t u0 = ln_apply(xw[k][0], m[0], rh[0], rl[0]), u1 = ln_apply(xw[k][1], m[1], rh[1], rl[1]);
                    sts64(ub + k * USLOT_B, pack_f16(bf_lo(u0), bf_hi(u0)), pack_f16(bf_lo(u1), bf_hi(u1)));
                }
                STAMPX(29);
                fence_async();
                bar_sync(14, 512);
                STAMP(7);
            });
        } else {
            auto stage = [&]() {
                const uint32_t tag = (ep % 7u + 1u) * 0x10001u;
                int it = 0;
                WPOINT(4, warp == 19);
                while (true) {
                    uv0.x ^= tag; uv0.y ^= tag; uv0.z ^= tag; uv0.w ^= tag; uv1.x ^= tag; uv1.y ^= tag; uv1.z ^= tag; uv1.w ^= tag;
                    if ((((uv0.x | uv0.y | uv0.z) | (uv0.w | uv1.x | uv1.y) | (uv1.z | uv1.w)) & 0x70007u) == 0) break;
                    if (++it > SPIN_LIMIT) TRAP();
                    uv0 = ld_poll(usrc); uv1 = ld_poll(usrc + 512);
                }
                STAMP(8);
                const uint32_t ub = sb + SM_U + UPAD * 16 + 4 * USLOT_B + (t128 & 1) * ULO_B + (t128 >> 1) * 16;
                sts128(ub, uv0.x, uv0.y, uv0.z, uv0.w);
                sts128(ub + 1024, uv1.x, uv1.y, uv1.z, uv1.w);
                fence_async();
                asm volatile("barrier.cluster.arrive.relaxed.aligned;\n" ::: "memory");
                bar_sync(5, 128);
                WPOINT(5, warp == 19);
                STAMP(7);
            };
            stage();
            if (odd) conv_inner(c, pln + wq * 128, gy, sb + SM_RX, hook);
            else conv_outer(c, pln + wq * 128, gy, sb + SM_RX, hook);
        }
        STAMP(10);
    }
    {
    const int lane = lane_v(), tid = 32 * warp + lane, g = lane >> 2, t = lane & 3;
    const uint32_t par = ~ep & 1u;
    bar_sync(0, NWRK);
    STAMP(11);
    uint32_t H[2][4] = {}, U2[2][4] = {};
    auto publish = [&](bool hi, int slot) {
        uint4* rowp = reinterpret_cast<uint4*>(p.s->rows) + slot * 144 + warp * 4 + t;
        stg128(rowp, nzw(hi ? U2[1][0] : U2[0][0]), nzw(hi ? U2[1][1] : U2[0][1]), nzw(hi ? U2[1][2] : U2[0][2]), nzw(hi ? U2[1][3] : U2[0][3]));
        stg128(rowp + 72, nzw(hi ? H[1][0] : H[0][0]), nzw(hi ? H[1][1] : H[0][1]), nzw(hi ? H[1][2] : H[0][2]), nzw(hi ? H[1][3] : H[0][3]));
    };
#define KTOK(k) (int)(((~(k) >> 5) & 0x7f0u) | (((k) >> 1) & 15u))
#define KLATE(k) (((k) & 0x1e0u) < 0xe0u)
#define KSLOT(k, s) (KLATE(k) ? 2 * NCTA + (s) : (int)(((k) >> 8) & 0xffu))
    const uint4* const rsrc = reinterpret_cast<const uint4*>(p.s->rows) + 36 * odd;
    auto gather = [&](uint32_t mine) {
        int it = 0;
        uint32_t mn;
        do {
            mn = 1;
#pragma unroll 1
            for (int r = 0; r < 9; r++) {
                const uint32_t k = __shfl_sync(0xffffffffu, mine, r < 8 ? 4 * r : lane);
                const int row = r < 8 ? r : g, c = r < 8 ? lane : 32 + t;
                asm volatile("cp.async.cg.shared.global [%0], [%1], 16;\n" ::"r"(sb + SM_XS + row * XS_PITCH + c * 16), "l"(rsrc + KSLOT(k, row) * 144 + c) : "memory");
            }
            asm volatile("cp.async.wait_all;\n" ::: "memory");
#pragma unroll 1
            for (int r = 0; r < 9; r++) mn = min(mn, min4(lds128(sb + SM_XS + (r < 8 ? r * XS_PITCH + lane * 16 : g * XS_PITCH + (32 + t) * 16))));
            if (++it > SPIN_LIMIT) TRAP();
        } while (__any_sync(0xffffffffu, mn == 0));
    };
    auto late_rows = [&](auto role) {
        if (decltype(role)::value == 1) {
            int it = 0;
#pragma unroll 1
            for (int i = 0; i < 8; i++) {
                uint4 k;
                do { k = ld_poll(reinterpret_cast<const uint4*>(p.s->key) + 32 * i + lane); if (++it > SPIN_LIMIT) TRAP(); } while (((k.x ^ par) | (k.y ^ par) | (k.z ^ par) | (k.w ^ par)) & 1u);
                sts128(sb + SM_KEYS + (32 * i + lane) * 16, k.x, k.y, k.z, k.w);
            }
            uint32_t m = 0xffffffffu;
#pragma unroll 1
            for (int r = 0; r < 8; r++) {
                uint32_t c = 0;
#pragma unroll 2
                for (int i = 0; i < 8; i++) {
                    const uint4 k = lds128(sb + SM_KEYS + (32 * i + lane) * 16);
                    c = max(max(c, k.x < m ? k.x : 0u), max(k.y < m ? k.y : 0u, max(k.z < m ? k.z : 0u, k.w < m ? k.w : 0u)));
                }
                m = __reduce_max_sync(0xffffffffu, c);
                if (lane == 0) sts32(s_key + r * 4, m);
            }
        }
        bar_sync(0, NWRK);
        const uint32_t kk = lds32(s_key + (lane & 7) * 4), ep = lds32(s_cnt + 4);
        const bool own = KLATE(kk) && (KTOK(kk) >> 4) == b;
        uint32_t todo = __ballot_sync(0xffffffffu, own) & 0xffu;
        if (decltype(role)::value == 0 && todo) {
#pragma unroll
            for (int hf = 0; hf < 2; hf++) {
                const uint4 h = lds128(sb + SM_U + hf * 9216 + tid * 16);
                const uint2 st = lds64(s_stat + (g + 8 * hf) * 8);
                H[hf][0] = h.x; H[hf][1] = h.y; H[hf][2] = h.z; H[hf][3] = h.w;
#pragma unroll
                for (int k = 0; k < 4; k++) U2[hf][k] = ln_apply(H[hf][k], STAT_M(st), STAT_H(st), STAT_L(st));
            }
#pragma unroll 1
            while (todo) {
                const int s = __ffs(todo) - 1, tk = KTOK(__shfl_sync(0xffffffffu, kk, s));
                todo &= todo - 1;
                if ((tk & 13) == TOK(g)) publish(tk & 2, 2 * NCTA + s);
            }
            __threadfence();
        }
        bar_sync(0, NWRK);
        if (decltype(role)::value == 1) {
            if (lane < NSEL && own) *reinterpret_cast<volatile unsigned*>(p.s->flag + lane) = ep + 1u;
            int it = 0;
            while (__any_sync(0xffffffffu, KLATE(kk) && ld_acquire32(p.s->flag + (lane & 7)) != ep + 1u)) { if (++it > SPIN_LIMIT) TRAP(); }
            gather(__shfl_sync(0xffffffffu, kk, g));
        }
        bar_sync(0, NWRK);
    };
    if (warp < 18) {
        const unsigned char* ys = reinterpret_cast<const unsigned char*>(p.s->y) + (b < 32 * YQ ? (par ^ 1u) * (NCTA * 18432u) : 0u) +
                                  ((P * DM + 32 * warp + 8 * (g >> 1) + (g & 1)) * 64 + odd * 32 + t * 8);
        mbar_wait(bar_v);
        const uint32_t xa = sb + SM_XT + warp * 64 + t * 16;
        const uint4 x0 = lds128(xa + TOK(g) * 1152), x1 = lds128(xa + (TOK(g) + 2) * 1152), dk = lds128(xa + 16 * 1152);
        uint4 wr = make_uint4(0u, 0u, 0u, 0u);
        if (g == 0) wr = lds128(xa + 17 * 1152);
        uint2 yv[4];
        const uint32_t Z[2][4] = {{x0.x, x0.y, x0.z, x0.w}, {x1.x, x1.y, x1.z, x1.w}}, D4[4] = {dk.x, dk.y, dk.z, dk.w};
#pragma unroll
        for (int hf = 0; hf < 2; hf++) {
            const uint2 st = lds64(s_stat + (g + 8 * hf) * 8);
#pragma unroll
            for (int k = 0; k < 4; k++) U2[hf][k] = hmul2_bf(ln_apply(Z[hf][k], STAT_M(st), STAT_H(st), STAT_L(st)), D4[k]);
        }
        const uint32_t la = pin(sb + SM_LNP + (g * 20 + warp) * 4);
        {
            const unsigned char* y1 = ys + (U2[0][0] & U2[1][2] & (warp >> 8));
#pragma unroll
            for (int k = 0; k < 4; k++) yv[k] = ld_poll64(y1 + k * 128);
        }
        int it = 0;
        float d[2][4];
        while (true) {
            const uint32_t mn = min3(min3(yv[0].x, yv[0].y, yv[1].x), min3(yv[1].y, yv[2].x, yv[2].y), min(yv[3].x, yv[3].y));
#pragma unroll
            for (int k = 0; k < 4; k++) {
                H[0][k] = hadd2_bf(Z[0][k], hadd2_bf(movm(yv[k].x), U2[0][k]));
                H[1][k] = hadd2_bf(Z[1][k], hadd2_bf(movm(yv[k].y), U2[1][k]));
            }
            ln_partial(H, d);
            if (!__any_sync(0xffffffffu, mn == 0)) break;
            if (++it > SPIN_LIMIT) TRAP();
#pragma unroll
            for (int k = 0; k < 4; k++) yv[k] = ld_poll64(ys + k * 128);
        }
        STAMP(12);
        {
            const float s0 = (g & 1) ? d[0][3] : d[0][2], s1 = (g & 1) ? d[1][3] : d[1][2];
            const float q0 = (g & 1) ? d[0][1] : d[0][0], q1 = (g & 1) ? d[1][1] : d[1][0];
            asm volatile("{\n.reg .pred p;\nsetp.eq.u32 p, %5, %6;\n@p st.shared.f32 [%0], %1;\n@p st.shared.f32 [%0 + 640], %2;\n@p st.shared.f32 [%0 + 1280], %3;\n@p st.shared.f32 [%0 + 1920], %4;\n}\n"
                         ::"r"(la), "f"(s0), "f"(s1), "f"(q0), "f"(q1), "r"(t), "r"(g >> 1) : "memory");
        }
        bar_arrive(6, NWRK);
        STAMP(13);
        bar_sync(7, 608);
        STAMP(14);
#pragma unroll
        for (int hf = 0; hf < 2; hf++) {
            const uint2 st = lds64(s_stat + (g + 8 * hf) * 8);
#pragma unroll
            for (int k = 0; k < 4; k++) U2[hf][k] = ln_apply(H[hf][k], STAT_M(st), STAT_H(st), STAT_L(st));
        }
        {
            float cs[4] = {0.f, 0.f, 0.f, 0.f};
            mma_bf16(cs, U2[0][0], U2[1][0], U2[0][1], U2[1][1], wr.x, wr.y);
            mma_bf16(cs, U2[0][2], U2[1][2], U2[0][3], U2[1][3], wr.z, wr.w);
            if (t == 0) { stsf(la + 32 * 80, cs[0]); stsf(la + 40 * 80, cs[2]); }
            bar_arrive(8, 608);
        }
        FIX((uint32_t)warp >> 8);
        uint32_t O[2][4];
#pragma unroll
        for (int hf = 0; hf < 2; hf++)
#pragma unroll
            for (int k = 0; k < 4; k++) { O[hf][k] = hadd2_bf(H[hf][k], U2[hf][k]); H[hf][k] = nzw(H[hf][k]); U2[hf][k] = nzw(U2[hf][k]); }
        unsigned char* rowp = reinterpret_cast<unsigned char*>(p.s->rows) + ((254 - 2 * b) * 2304 + warp * 64 + t * 16);
        FIX(and3(and3(and3(H[0][0], H[0][1], H[0][2]), and3(H[0][3], H[1][0], H[1][1]), and3(H[1][2], H[1][3], U2[0][0])),
                 and3(and3(U2[0][1], U2[0][2], U2[0][3]), and3(U2[1][0], U2[1][1], U2[1][2]), U2[1][3]), (uint32_t)reinterpret_cast<uint64_t>(rowp)));
        bar_sync(9, 608);
        {
            const uint2 best = lds64(s_rank);
#pragma unroll
            for (int hf = 0; hf < 2; hf++) {
                const uint32_t me = 2 * TOK(g) + 4 * hf;
                unsigned char* d = rowp + (best.x == me ? 2304 : 0);
                if (best.x == me || best.y == me) {
                    stg128(d, U2[hf][0], U2[hf][1], U2[hf][2], U2[hf][3]);
                    stg128(d + 1152, H[hf][0], H[hf][1], H[hf][2], H[hf][3]);
                }
            }
        }
        FIX((uint32_t)warp >> 9);
#pragma unroll
        for (int hf = 0; hf < 2; hf++) {
            sts128(sb + SM_OUT + (TOK(g) + 2 * hf) * (DM * 2) + warp * 64 + t * 16, O[hf][0], O[hf][1], O[hf][2], O[hf][3]);
            sts128(sb + SM_U + hf * 9216 + tid * 16, H[hf][0], H[hf][1], H[hf][2], H[hf][3]);
        }
        STAMP(15);
        const int mi = lane >> 3, rr = lane & 7;
        const bool gate = warp < 12 && (warp & 3) != 2;
        const int fj = gate ? 3 * (warp >> 2) + min(warp & 3, 2) : (warp < 12 ? warp >> 2 : warp - 9);
        if (gate) {
            uint32_t W[18][4];
            mbar_wait(bar_w);
            const uint32_t aad = sb + SM_WG + (mi & 1) * SM_WU + (rr + 8 * (mi >> 1)) * W_PITCH + fj * 16;
            const uint32_t bad = pin(sb + SM_XS + rr * XS_PITCH + mi * 16);
            bool rare = warp >> 8;
#pragma unroll 1
            do {
                if (rare) late_rows(IC<0>());
#pragma unroll
                for (int k = 0; k < 18; k++) ldsm_x4_t(W[k][0], W[k][1], W[k][2], W[k][3], aad + k * 16 * W_PITCH);
                if (rare) break;
                fence_async();
                STAMP2(17);
                rare = bar_or(11, NWRK, false);
            } while (rare);
            STAMP2(19);
            float c4[2][4] = {};
#pragma unroll
            for (int k = 0; k < 18; k += 2) {
                uint32_t b0, b1, b2, b3;
                ldsm_x4(b0, b1, b2, b3, bad + k * 32);
                mma_bf16(c4[0], W[k][0], W[k][1], W[k][2], W[k][3], b0, b1);
                mma_bf16(c4[1], W[k + 1][0], W[k + 1][1], W[k + 1][2], W[k + 1][3], b2, b3);
            }
            const uint32_t ex = sb + SM_EX + (32 * fj + lane) * 16;
            const float e0 = c4[0][0] + c4[1][0], e1 = c4[0][1] + c4[1][1], e2 = c4[0][2] + c4[1][2], e3 = c4[0][3] + c4[1][3];
            asm volatile("st.async.shared::cluster.mbarrier::complete_tx::bytes.v4.f32 [%0], {%1,%2,%3,%4}, [%5];\n"
                         ::"r"(ex ^ 0x1000000u), "f"(e0), "f"(e1), "f"(e2), "f"(e3), "r"(bar_g ^ 0x1000000u) : "memory");
            STAMP2(20);
            mbar_wait(bar_g);
            const uint4 o = lds128(ex);
            const uint32_t G = pack_bf16(e0 + __uint_as_float(o.x), e1 + __uint_as_float(o.y)), U = pack_bf16(e2 + __uint_as_float(o.z), e3 + __uint_as_float(o.w));
            sts32(sb + SM_GU + (32 * fj + lane) * 4, hmul2_bf(pack_bf16(bf_lo(G) * sigmoid_f(bf_lo(G)), bf_hi(G) * sigmoid_f(bf_hi(G))), U));
            bar_arrive(13, NWRK);
        } else {
            uint32_t W[2][18];
            auto load_wd = [&]() {
                mbar_wait(bar_d);
                const uint32_t base = sb + SM_WD + (4 * fj + (mi & 1)) * 16 + rr * WD_PITCH;
#pragma unroll
                for (int j = 0; j < 2; j++) {
#pragma unroll
                    for (int k = 0; k < 4; k++) ldsm_x4_t(W[j][4 * k], W[j][4 * k + 1], W[j][4 * k + 2], W[j][4 * k + 3], base + j * 32 + (k * 16 + 8 * (mi >> 1)) * WD_PITCH);
                    ldsm_x2_t(W[j][16], W[j][17], base + j * 32 + 64 * WD_PITCH);
                }
            };
            const uint32_t po = pin((((8 * (18 * odd + 2 * fj) + g) * 64 + P) * 16 + t * 4) * 4);
            fence_async();
            STAMP2(17);
            if (bar_or(11, NWRK, false)) late_rows(IC<0>());
            delay(DDLY); load_wd();
            bar_sync(13, NWRK);
            STAMP2(21);
            uint32_t gb[9];
            ldsm_x4_t(gb[0], gb[1], gb[2], gb[3], sb + SM_GU + lane * 16);
            ldsm_x4_t(gb[4], gb[5], gb[6], gb[7], sb + SM_GU + 512 + lane * 16);
            ldsm_x1_t(gb[8], sb + SM_GU + 1024 + lane * 16);
            float c4[2][4] = {}, d4[2][4] = {};
#pragma unroll
            for (int k = 0; k < 4; k += 2)
#pragma unroll
                for (int j = 0; j < 2; j++) {
                    mma_bf16(c4[j], W[j][4 * k], W[j][4 * k + 1], W[j][4 * k + 2], W[j][4 * k + 3], gb[2 * k], gb[2 * k + 1]);
                    mma_bf16(d4[j], W[j][4 * k + 4], W[j][4 * k + 5], W[j][4 * k + 6], W[j][4 * k + 7], gb[2 * k + 2], gb[2 * k + 3]);
                }
#pragma unroll
            for (int j = 0; j < 2; j++) mma_bf16_k8(c4[j], W[j][16], W[j][17], gb[8]);
#pragma unroll
            for (int j = 0; j < 2; j++)
                stg128(reinterpret_cast<unsigned char*>(p.s->part) + po + j * 32768, __float_as_uint(c4[j][0] + d4[j][0]) | 1u, __float_as_uint(c4[j][1] + d4[j][1]) | 1u,
                       __float_as_uint(c4[j][2] + d4[j][2]) | 1u, __float_as_uint(c4[j][3] + d4[j][3]) | 1u);
        }
        STAMP2(22);
    } else if (warp == 18) {
        const uint4* const ksrc = reinterpret_cast<const uint4*>(p.s->key3) + pin(2 * lane);
        const int row = (g >> 1) + 4 * (g & 1);
        const uint32_t ro = pin(640 * odd + t * 16), xd = pin(sb + SM_XS + row * XS_PITCH + t * 16 + (odd ? 0 : 512));
        const uint32_t xe = pin(sb + SM_XS + (g >> 1) * XS_PITCH + (lane & 7) * 16 + 64 * odd);
        const uint32_t sa = pin(sb + SM_LNP + lane * 80);
        const uint32_t klo = pin((uint32_t)(127 - b) << 9 | (uint32_t)(15 - ROWTOK(lane & 15)) << 1 | par), ra = pin(sb + SM_LNP + (32 + (lane & 15)) * 80);
        uint4* const kdst = reinterpret_cast<uint4*>(p.s->key3) + pin((lane >> 1) * 2 * NCTA + 2 * b + (lane & 1));
        FIX(ra);
        bar_sync(6, NWRK);
        {
            float mb, rc;
            ln_finish(sum18(sa), lane, mb, rc);
            if (lane < 16) stat_store(s_stat + lane * 8, mb, rc, 0u);
        }
        bar_arrive(7, 608);
        bar_sync(8, 608);
        uint32_t t0;
        {
            const uint32_t bits = __float_as_uint(rbf(sum18(ra)));
            const uint32_t me = ((bits ^ ((uint32_t)((int)bits >> 31) | 0x80000000u)) & 0xffff0000u) | klo;
            const uint32_t k0 = __reduce_max_sync(0xffffffffu, me), k1 = __reduce_max_sync(0xffffffffu, me == k0 ? 0u : me);
            const uint32_t k2 = __reduce_max_sync(0xffffffffu, me >= k1 ? 0u : me);
            if (lane < 2) stg128(kdst, k0 ^ 0x11eu, k1 ^ 0xfeu, k2 ^ 0xdeu, par);
            asm volatile("mov.u32 %0, %%clock;" : "=r"(t0) :: "memory");
            STAMPW(23);
            if (lane == 0) sts64(s_rank, ~k0 & 30u, ~k1 & 30u);
            bar_arrive(9, 608);
            sts32(s_k16 + (lane & 15) * 4, me);
            __syncwarp();
            const uint4 v = lds128(s_k16 + (lane & 16) * 2), w = lds128(s_k16 + (lane & 16) * 2 + 16);
            int rank = ((v.x > me) + (v.y > me)) + ((v.z > me) + (v.w > me)) + (((w.x > me) + (w.y > me)) + ((w.z > me) + (w.w > me)));
            rank += __shfl_xor_sync(0xffffffffu, rank, 16);
            if (lane < 16 && rank < 8) p.s->key[8 * b + rank] = (me ^ 0x1eu) | ((8 - rank) << 5);
        }
        uint4 kq[4];
        uint32_t u[4], mine = 0, m;
        int it = 0;
        { uint32_t now; do { asm volatile("mov.u32 %0, %%clock;" : "=r"(now) :: "memory"); } while (now - t0 < KDLY); }
        do {
#pragma unroll
            for (int i = 0; i < 4; i++) kq[i] = ld_poll(ksrc + 64 * i);
            if (++it > SPIN_LIMIT) TRAP();
            uint32_t S[2][4];
#pragma unroll
            for (int i = 0; i < 2; i++) {
                const uint4 &c = kq[2 * i], &d = kq[2 * i + 1];
                const uint32_t m1 = min(c.x, d.x), m2 = max(c.y, d.y);
                S[i][0] = max(c.x, d.x); S[i][1] = max(m1, m2); S[i][2] = min(m1, m2); S[i][3] = min(c.y, d.y);
            }
            const uint32_t a0 = max(S[0][0], S[1][3]), a1 = max(S[0][1], S[1][2]), a2 = max(S[0][2], S[1][1]), a3 = max(S[0][3], S[1][0]);
            const uint32_t b0 = max(a0, a2), b2 = min(a0, a2), b1 = max(a1, a3), b3 = min(a1, a3);
            u[0] = max(b0, b1); u[1] = min(b0, b1); u[2] = max(b2, b3); u[3] = min(b2, b3);
            const uint32_t bad = or3(or3(xor_or(kq[0].x, kq[0].y, par), xor_or(kq[0].z, kq[1].x, par), xor_or(kq[1].y, kq[1].z, par)),
                                     xor_or(kq[2].x, kq[2].y, par), xor_or(kq[2].z, kq[3].x, par)) | xor_or(kq[3].y, kq[3].z, par);
            m = __reduce_max_sync(0xffffffffu, u[0] | (uint32_t)((int)(bad << 31) >> 31));
        } while (m == 0xffffffffu);
        STAMPW(16);
#pragma unroll
        for (int r = 0; r < 8; r++) {
            if (r) m = __reduce_max_sync(0xffffffffu, u[0]);
            if (u[0] == m) { u[0] = u[1]; u[1] = u[2]; u[2] = u[3]; u[3] = 0; }
            if (row == r) mine = m;
        }
        uint4 v[9];
        const uint32_t o0 = __byte_perm(mine, 0, 0x4441) * 2304u, o1 = __shfl_xor_sync(0xffffffffu, o0, 4);
        const unsigned char* const rA = reinterpret_cast<const unsigned char*>(p.s->rows) + (((g & 1) ? o1 : o0) + ro + (g & 1) * 64);
        const unsigned char* const rb = reinterpret_cast<const unsigned char*>(p.s->rows) + (((g & 1) ? o0 : o1) + ro + (g & 1) * 64);
        const unsigned char* const rc = reinterpret_cast<const unsigned char*>(p.s->rows) + (o0 + ro + (odd ? -64 : 512));
#pragma unroll
        for (int i = 0; i < 4; i++) { v[i] = ld_poll(rA + i * 128); v[4 + i] = ld_poll(rb + i * 128); }
        v[8] = ld_poll(rc);
        const bool again = u[0] == 0 || max(max(kq[0].z, kq[1].z), max(kq[2].z, kq[3].z)) > m;
        if (t == 0) sts32(s_key + row * 4, mine);
#pragma unroll
        for (int i = 0; i < 9; i++) sts128(i < 8 ? xe + (i >> 2) * 4 * XS_PITCH + (i & 3) * 128 : xd, v[i].x, v[i].y, v[i].z, v[i].w);
        uint32_t mn, m3[3];
        m3[0] = m3[1] = m3[2] = 1u;
#pragma unroll
        for (int i = 0; i < 9; i++) m3[i % 3] = min3(min3(m3[i % 3], v[i].x, v[i].y), v[i].z, v[i].w);
        mn = min3(m3[0], m3[1], m3[2]);
        STAMPW(18);
        if (bar_or(11, NWRK, again || mn == 0)) late_rows(IC<1>());
    } else {
        bar_sync(6, NWRK);
        WPOINT(16, true);
        if (WANY(17) || WANY(18)) delay(WDLY);
        WPOINT(17, true);
        if (WANY(18)) delay(WDLY);
        WPOINT(18, true);
        if (bar_or(11, NWRK, false)) late_rows(IC<2>());
        const int tk = KTOK(lds32(s_key + (lane & 7) * 4));
        const uint32_t sel = __reduce_or_sync(0xffffffffu, (tk >> 4) == b ? 1u << (tk & 15) : 0u);
        if (sel ? lane < 16 && !((sel >> lane) & 1u) : lane == 0) bulk_s2g(p.out + (size_t)(16 * b + lane) * DM, sb + SM_OUT + lane * (DM * 2), sel ? DM * 2 : 16 * DM * 2);
        __syncwarp();
    }
    if (warp == 8 || warp >= 18) {
        const int grp = 3 * b + (warp == 8 ? 0 : warp - 17), fsl = 2 * t + ((lane >> 3) & 1), fc = 16 * (grp >> 3) + (grp & 7) + 8 * (lane >> 4);
        const uint32_t fk = lds32(s_key + fsl * 4);
        float hv = 0.f, u2 = 0.f;
        int it = 0;
        if (b < 96) {
            const uint32_t* const fsrc = p.s->rows + KSLOT(fk, fsl) * DM + (fc >> 1);
            uint32_t hw, uw;
            do { hw = ld_poll32(fsrc + 288); uw = ld_poll32(fsrc); if (++it > SPIN_LIMIT) TRAP(); } while (!hw || !uw);
            hv = (fc & 1) ? bf_hi(hw) : bf_lo(hw); u2 = (fc & 1) ? bf_hi(uw) : bf_lo(uw);
        }
        const float rs = rbf(sigmoid_f(__uint_as_float((fk ^ ((uint32_t)((int)~fk >> 31) | 0x80000000u)) & 0xffff0000u)));
        const uint32_t dof = pin(KTOK(fk) * DM + fc), so = pin(grp * 256 + lane);
        if (warp > 17) bar_sync(13, NWRK);
        if (b < 96) {
            delay(warp > 17 ? FDLY : FDLY2);
            const uint4* src = reinterpret_cast<const uint4*>(p.s->part) + so;
            float s0, s1, s2, s3;
            uint32_t ok;
            do {
                uint4 a[8];
#pragma unroll
                for (int i = 0; i < 8; i++) a[i] = ld_poll(src + 32 * i);
                if (++it > SPIN_LIMIT) TRAP();
#define A4(i) and3(and3(a[i].x, a[i].y, a[i].z), and3(a[i].w, a[i + 1].x, a[i + 1].y), a[i + 1].z & a[i + 1].w)
#define S8(f) (((__uint_as_float(a[0].f) + __uint_as_float(a[1].f)) + (__uint_as_float(a[2].f) + __uint_as_float(a[3].f))) + \
               ((__uint_as_float(a[4].f) + __uint_as_float(a[5].f)) + (__uint_as_float(a[6].f) + __uint_as_float(a[7].f))))
                ok = and3(A4(0), A4(2), and3(A4(4), A4(6), 1u));
                s0 = S8(x); s1 = S8(y); s2 = S8(z); s3 = S8(w);
                asm volatile("" : "+f"(s0), "+f"(s1), "+f"(s2), "+f"(s3));
#undef A4
#undef S8
            } while (__any_sync(0xffffffffu, !ok));
            STAMP2(24);
            const bool up = lane & 16, od = lane & 8;
            const float r0 = (up ? s2 : s0) + __shfl_xor_sync(0xffffffffu, up ? s0 : s2, 16), r1 = (up ? s3 : s1) + __shfl_xor_sync(0xffffffffu, up ? s1 : s3, 16);
            float y = (od ? r1 : r0) + __shfl_xor_sync(0xffffffffu, od ? r0 : r1, 8);
            y += __shfl_xor_sync(0xffffffffu, y, 4);
            p.out[dof] = __float2bfloat16_rn(hv + rbf(u2 + rbf(rbf(y) * rs)));
        }
    }
    if (warp == 19) asm volatile("cp.async.bulk.wait_group.read 0;\n" ::: "memory");
    if (b == 0 && tid < 8) *reinterpret_cast<volatile unsigned*>(p.s->hint + tid * 32 + 1) = lds32(s_cnt + 4) + 1u;
    STAMP(25);
    }
}

typedef CUresult (*PFN_tmEncode)(CUtensorMap*, CUtensorMapDataType, cuuint32_t, void*, const cuuint64_t*, const cuuint64_t*, const cuuint32_t*,
                                 const cuuint32_t*, CUtensorMapInterleave, CUtensorMapSwizzle, CUtensorMapL2promotion, CUtensorMapFloatOOBfill);

extern "C" void kernel_launch(void* const* d_in, const int* in_sizes, int n_in, void* d_out, int out_size) {
    Params p;
    p.x = (const bf16*)d_in[0];
    p.lar = (const bf16*)d_in[1];
    p.aim = (const bf16*)d_in[2];
    p.cre = (const bf16*)d_in[3];
    p.cim = (const bf16*)d_in[4];
    p.ldt = (const bf16*)d_in[5];
    p.dsk = (const bf16*)d_in[6];
    p.wr = (const bf16*)d_in[8];
    p.out = (bf16*)d_out;
    static PFN_tmEncode enc = nullptr;
    static void* scratch = nullptr;
    if (!enc) {
        cudaFuncSetAttribute(fused_kernel, cudaFuncAttributeMaxDynamicSharedMemorySize, SMEM_TOTAL);
        void* fn = nullptr;
        cudaDriverEntryPointQueryResult qr;
        cudaGetDriverEntryPoint("cuTensorMapEncodeTiled", &fn, cudaEnableDefault, &qr);
        enc = (PFN_tmEncode)fn;
        cudaGetSymbolAddress(&scratch, g_scratch);
    }
    p.s = (Scratch*)scratch;
    CUtensorMap tm_g, tm_u, tm_d, tm_x;
    const cuuint64_t dims[2] = {FF, DM}, strides[1] = {FF * 2};
    const cuuint32_t box[2] = {72, 48}, es[2] = {1, 1};
    enc(&tm_g, CU_TENSOR_MAP_DATA_TYPE_BFLOAT16, 2, d_in[9], dims, strides, box, es, CU_TENSOR_MAP_INTERLEAVE_NONE, CU_TENSOR_MAP_SWIZZLE_NONE,
        CU_TENSOR_MAP_L2_PROMOTION_NONE, CU_TENSOR_MAP_FLOAT_OOB_FILL_NONE);
    enc(&tm_u, CU_TENSOR_MAP_DATA_TYPE_BFLOAT16, 2, d_in[10], dims, strides, box, es, CU_TENSOR_MAP_INTERLEAVE_NONE, CU_TENSOR_MAP_SWIZZLE_NONE,
        CU_TENSOR_MAP_L2_PROMOTION_NONE, CU_TENSOR_MAP_FLOAT_OOB_FILL_NONE);
    const cuuint64_t ddims[2] = {DM / 2, FF}, dstrides[1] = {DM * 2};
    const cuuint32_t dbox[2] = {WD_PITCH / 4, 8};
    enc(&tm_d, CU_TENSOR_MAP_DATA_TYPE_UINT32, 2, d_in[11], ddims, dstrides, dbox, es, CU_TENSOR_MAP_INTERLEAVE_NONE, CU_TENSOR_MAP_SWIZZLE_NONE,
        CU_TENSOR_MAP_L2_PROMOTION_L2_128B, CU_TENSOR_MAP_FLOAT_OOB_FILL_NONE);
    const cuuint64_t xdims[4] = {DM, 128, 4, 4}, xstrides[3] = {DM * 8, DM * 2, DM * 1024};
    const cuuint32_t xbox[4] = {8, 128, 4, 2}, xes[4] = {1, 1, 1, 1};
    enc(&tm_x, CU_TENSOR_MAP_DATA_TYPE_BFLOAT16, 4, d_in[0], xdims, xstrides, xbox, xes, CU_TENSOR_MAP_INTERLEAVE_NONE, CU_TENSOR_MAP_SWIZZLE_NONE,
        CU_TENSOR_MAP_L2_PROMOTION_NONE, CU_TENSOR_MAP_FLOAT_OOB_FILL_NONE);
    fused_kernel<<<NCTA, NTHR, SMEM_TOTAL>>>(p, tm_g, tm_u, tm_d, tm_x);
}
```

```cpp
#include <cuda_runtime.h>
#include <cuda.h>
#include <cuda_fp16.h>
#include <cuda_bf16.h>
#include <stdint.h>

#define LSEQ 2048
#define DM 576
#define NST 128
#define FF 4608
#define NSEL 8
#define NCTA 128
#define NTHR 640
#define NWRK 640

typedef __nv_bfloat16 bf16;

#define SM_WG 0
#define SM_WU 41472
#define SM_XC (82944 - 32768)
#define SM_WD 82944
#define W_PITCH 144
#define WD_PITCH 592
#define SM_Z2 (SM_WD + 10240)
#define SM_XT (SM_PL - 18 * 1152)
#define SM_PL (SM_WD + 46080)
#define PL_HALF 1344
#define PLW_B 2624
#define PL_B (4 * PLW_B)
#define SM_U (SM_PL + 5 * PL_B)
#define UPAD 20
#define ULO_B ((UPAD + 128) * 16)
#define USLOT_B (2 * ULO_B)
#define SM_KW (SM_U + 5 * USLOT_B)
#define KW_B 3712
#define KW_PL 1216
#define KW_P 2400
#define KW_H 3440
#define SM_MISC (SM_KW + 5 * KW_B)
#define SM_LC (SM_MISC + 416)
#define SM_LNP (SM_LC + 768)
#define SM_RX (SM_LNP + 3840)
#define SMEM_TOTAL (SM_RX + 3088)
#define TBW PLW_B
#define SM_OUT SM_PL
#define SM_XS (SM_PL + 18432)
#define XS_PITCH 592
#define SM_GU (SM_PL + 23296)
#define SM_EX (SM_PL + 24576)

struct __align__(128) Scratch {
    unsigned hint[8 * 32];
    unsigned flag[32];
    uint32_t key3[NCTA * 8];
    uint32_t key[NCTA * 8];
    uint32_t stat[LSEQ];
    uint32_t uT[64 * (LSEQ / 2)];
    uint32_t y[(NCTA + 96) * DM * 8];
    uint32_t part[288 * 64 * 16];
    uint32_t rows[(2 * NCTA + NSEL) * DM];
};
__device__ Scratch g_scratch;
#define STAMP(i)
#define STAMPX(i)
#define STAMPY(i)

__device__ __forceinline__ float rbf(float x) {
    uint32_t r;
    asm("cvt.rn.bf16x2.f32 %0, %1, %2;\n" : "=r"(r) : "f"(x), "f"(0.f));
    return __uint_as_float(r);
}
__device__ __forceinline__ uint32_t pack_bf16(float lo, float hi) {
    uint32_t r;
    asm("cvt.rn.bf16x2.f32 %0, %1, %2;\n" : "=r"(r) : "f"(hi), "f"(lo));
    return r;
}
__device__ __forceinline__ uint32_t pack_f16(float lo, float hi) {
    uint32_t r;
    asm("cvt.rn.f16x2.f32 %0, %1, %2;\n" : "=r"(r) : "f"(hi), "f"(lo));
    return r;
}
__device__ __forceinline__ float bf_lo(uint32_t w) { return __uint_as_float(w << 16); }
__device__ __forceinline__ float bf_hi(uint32_t w) { return __uint_as_float(w & 0xffff0000u); }
__device__ __forceinline__ uint32_t hadd2_bf(uint32_t a, uint32_t b) {
    __nv_bfloat162 r = __hadd2_rn(*reinterpret_cast<__nv_bfloat162*>(&a), *reinterpret_cast<__nv_bfloat162*>(&b));
    return *reinterpret_cast<uint32_t*>(&r);
}
__device__ __forceinline__ uint32_t hsub2_bf(uint32_t a, uint32_t b) {
    __nv_bfloat162 r = __hsub2_rn(*reinterpret_cast<__nv_bfloat162*>(&a), *reinterpret_cast<__nv_bfloat162*>(&b));
    return *reinterpret_cast<uint32_t*>(&r);
}
__device__ __forceinline__ uint32_t hmul2_bf(uint32_t a, uint32_t b) {
    __nv_bfloat162 r = __hmul2_rn(*reinterpret_cast<__nv_bfloat162*>(&a), *reinterpret_cast<__nv_bfloat162*>(&b));
    return *reinterpret_cast<uint32_t*>(&r);
}
__device__ __forceinline__ uint32_t hfma2_bf(uint32_t a, uint32_t b, uint32_t c) { uint32_t r; asm("fma.rn.bf16x2 %0, %1, %2, %3;\n" : "=r"(r) : "r"(a), "r"(b), "r"(c)); return r; }
__device__ __forceinline__ uint32_t hmul2(uint32_t a, uint32_t b) { uint32_t r; asm("mul.rn.f16x2 %0, %1, %2;\n" : "=r"(r) : "r"(a), "r"(b)); return r; }
__device__ __forceinline__ uint32_t hadd2(uint32_t a, uint32_t b) { uint32_t r; asm("add.rn.f16x2 %0, %1, %2;\n" : "=r"(r) : "r"(a), "r"(b)); return r; }
__device__ __forceinline__ uint32_t hfma2(uint32_t a, uint32_t b, uint32_t c) { uint32_t r; asm("fma.rn.f16x2 %0, %1, %2, %3;\n" : "=r"(r) : "r"(a), "r"(b), "r"(c)); return r; }
__device__ __forceinline__ uint32_t hfms2(uint32_t a, uint32_t b, uint32_t c) {
    uint32_t r;
    asm("{\n.reg .b32 n;\nneg.f16x2 n, %2;\nfma.rn.f16x2 %0, %1, n, %3;\n}\n" : "=r"(r) : "r"(a), "r"(b), "r"(c));
    return r;
}
__device__ __forceinline__ uint32_t nzw(uint32_t w) { uint32_t r; asm("max.u32 %0, %1, 1;\n" : "=r"(r) : "r"(w)); return r; }
__device__ __forceinline__ uint32_t smem_u32(const void* p) { return (uint32_t)__cvta_generic_to_shared(p); }
__device__ __forceinline__ uint32_t lds32(uint32_t addr) {
    uint32_t v;
    asm volatile("ld.shared.u32 %0, [%1];\n" : "=r"(v) : "r"(addr) : "memory");
    return v;
}
__device__ __forceinline__ uint32_t lds16(uint32_t addr) {
    unsigned short v;
    asm volatile("ld.shared.u16 %0, [%1];\n" : "=h"(v) : "r"(addr) : "memory");
    return v;
}
__device__ __forceinline__ uint2 lds64(uint32_t addr) {
    uint2 v;
    asm volatile("ld.shared.v2.u32 {%0,%1}, [%2];\n" : "=r"(v.x), "=r"(v.y) : "r"(addr) : "memory");
    return v;
}
__device__ __forceinline__ uint4 lds128(uint32_t addr) {
    uint4 v;
    asm volatile("ld.shared.v4.u32 {%0,%1,%2,%3}, [%4];\n" : "=r"(v.x), "=r"(v.y), "=r"(v.z), "=r"(v.w) : "r"(addr) : "memory");
    return v;
}
__device__ __forceinline__ void sts32(uint32_t addr, uint32_t v) { asm volatile("st.shared.u32 [%0], %1;\n" ::"r"(addr), "r"(v) : "memory"); }
__device__ __forceinline__ void sts16(uint32_t addr, uint32_t v) { asm volatile("st.shared.u16 [%0], %1;\n" ::"r"(addr), "h"((unsigned short)v) : "memory"); }
__device__ __forceinline__ void stsf(uint32_t addr, float v) { sts32(addr, __float_as_uint(v)); }
__device__ __forceinline__ void sts64(uint32_t addr, uint32_t a, uint32_t b) { asm volatile("st.shared.v2.u32 [%0], {%1,%2};\n" ::"r"(addr), "r"(a), "r"(b) : "memory"); }
__device__ __forceinline__ void sts128(uint32_t addr, uint32_t a, uint32_t b, uint32_t c, uint32_t d) {
    asm volatile("st.shared.v4.u32 [%0], {%1,%2,%3,%4};\n" ::"r"(addr), "r"(a), "r"(b), "r"(c), "r"(d) : "memory");
}
__device__ __forceinline__ void ldsm_x4(uint32_t& r0, uint32_t& r1, uint32_t& r2, uint32_t& r3, uint32_t addr) {
    asm volatile("ldmatrix.sync.aligned.m8n8.x4.shared.b16 {%0,%1,%2,%3}, [%4];\n"
                 : "=r"(r0), "=r"(r1), "=r"(r2), "=r"(r3) : "r"(addr) : "memory");
}
__device__ __forceinline__ void ldsm_x4_t(uint32_t& r0, uint32_t& r1, uint32_t& r2, uint32_t& r3, uint32_t addr) {
    asm volatile("ldmatrix.sync.aligned.m8n8.x4.trans.shared.b16 {%0,%1,%2,%3}, [%4];\n"
                 : "=r"(r0), "=r"(r1), "=r"(r2), "=r"(r3) : "r"(addr) : "memory");
}
__device__ __forceinline__ void ldsm_x2_t(uint32_t& r0, uint32_t& r1, uint32_t addr) {
    asm volatile("ldmatrix.sync.aligned.m8n8.x2.trans.shared.b16 {%0,%1}, [%2];\n" : "=r"(r0), "=r"(r1) : "r"(addr) : "memory");
}
__device__ __forceinline__ void ldsm_x1_t(uint32_t& r0, uint32_t addr) {
    asm volatile("ldmatrix.sync.aligned.m8n8.x1.trans.shared.b16 {%0}, [%1];\n" : "=r"(r0) : "r"(addr) : "memory");
}
__device__ __forceinline__ void stsm_x4(uint32_t addr, uint32_t r0, uint32_t r1, uint32_t r2, uint32_t r3) {
    asm volatile("stmatrix.sync.aligned.m8n8.x4.shared.b16 [%0], {%1,%2,%3,%4};\n" ::"r"(addr), "r"(r0), "r"(r1), "r"(r2), "r"(r3) : "memory");
}
__device__ __forceinline__ void stsm_x4_t(uint32_t addr, uint32_t r0, uint32_t r1, uint32_t r2, uint32_t r3) {
    asm volatile("stmatrix.sync.aligned.m8n8.x4.trans.shared.b16 [%0], {%1,%2,%3,%4};\n" ::"r"(addr), "r"(r0), "r"(r1), "r"(r2), "r"(r3) : "memory");
}
__device__ __forceinline__ uint32_t movm(uint32_t a) {
    uint32_t d;
    asm volatile("movmatrix.sync.aligned.m8n8.trans.b16 %0, %1;\n" : "=r"(d) : "r"(a));
    return d;
}
__device__ __forceinline__ void mma_f16(float (&c)[4], uint32_t a0, uint32_t a1, uint32_t a2, uint32_t a3, uint32_t b0, uint32_t b1) {
    asm volatile(
        "mma.sync.aligned.m16n8k16.row.col.f32.f16.f16.f32 {%0,%1,%2,%3}, {%4,%5,%6,%7}, {%8,%9}, {%0,%1,%2,%3};\n"
        : "+f"(c[0]), "+f"(c[1]), "+f"(c[2]), "+f"(c[3])
        : "r"(a0), "r"(a1), "r"(a2), "r"(a3), "r"(b0), "r"(b1));
}
__device__ __forceinline__ void mma_bf16(float (&c)[4], uint32_t a0, uint32_t a1, uint32_t a2, uint32_t a3, uint32_t b0, uint32_t b1) {
    asm volatile(
        "mma.sync.aligned.m16n8k16.row.col.f32.bf16.bf16.f32 {%0,%1,%2,%3}, {%4,%5,%6,%7}, {%8,%9}, {%0,%1,%2,%3};\n"
        : "+f"(c[0]), "+f"(c[1]), "+f"(c[2]), "+f"(c[3])
        : "r"(a0), "r"(a1), "r"(a2), "r"(a3), "r"(b0), "r"(b1));
}
__device__ __forceinline__ void mma_bf16_k8(float (&c)[4], uint32_t a0, uint32_t a1, uint32_t b0) {
    asm volatile("mma.sync.aligned.m16n8k8.row.col.f32.bf16.bf16.f32 {%0,%1,%2,%3}, {%4,%5}, {%6}, {%0,%1,%2,%3};\n"
                 : "+f"(c[0]), "+f"(c[1]), "+f"(c[2]), "+f"(c[3]) : "r"(a0), "r"(a1), "r"(b0));
}
__device__ __forceinline__ void bar_sync(int id, int n) { asm volatile("bar.sync %0, %1;\n" ::"r"(id), "r"(n) : "memory"); }
__device__ __forceinline__ void bar_arrive(int id, int n) { asm volatile("bar.arrive %0, %1;\n" ::"r"(id), "r"(n) : "memory"); }
__device__ __forceinline__ bool bar_or(int id, int n, bool v) {
    uint32_t r;
    asm volatile("{\n.reg .pred p, q;\nsetp.ne.u32 p, %3, 0;\nbar.red.or.pred q, %1, %2, p;\nselp.u32 %0, 1, 0, q;\n}\n" : "=r"(r) : "r"(id), "r"(n), "r"((uint32_t)v) : "memory");
    return r;
}
__device__ __forceinline__ uint32_t and3(uint32_t a, uint32_t b, uint32_t c) { uint32_t r; asm("lop3.b32 %0, %1, %2, %3, 0x80;\n" : "=r"(r) : "r"(a), "r"(b), "r"(c)); return r; }
__device__ __forceinline__ uint32_t or3(uint32_t a, uint32_t b, uint32_t c) { uint32_t r; asm("lop3.b32 %0, %1, %2, %3, 0xfe;\n" : "=r"(r) : "r"(a), "r"(b), "r"(c)); return r; }
__device__ __forceinline__ uint32_t min3(uint32_t a, uint32_t b, uint32_t c) { uint32_t r; asm("{\n.reg .u32 t;\nmin.u32 t, %2, %3;\nmin.u32 %0, %1, t;\n}\n" : "=r"(r) : "r"(a), "r"(b), "r"(c)); return r; }
__device__ __forceinline__ uint32_t xor_or(uint32_t a, uint32_t b, uint32_t c) { uint32_t r; asm("lop3.b32 %0, %1, %2, %3, 0x7e;\n" : "=r"(r) : "r"(a), "r"(b), "r"(c)); return r; }
__device__ __forceinline__ uint32_t pin(uint32_t v) { uint32_t r; asm volatile("shfl.sync.bfly.b32 %0, %1, 0, 0x1f, 0xffffffff;\n" : "=r"(r) : "r"(v) : "memory"); return r; }
__device__ __forceinline__ uint4 ld_poll(const void* p) {
    uint4 v;
    asm volatile("ld.relaxed.gpu.global.v4.u32 {%0,%1,%2,%3}, [%4];\n" : "=r"(v.x), "=r"(v.y), "=r"(v.z), "=r"(v.w) : "l"(p) : "memory");
    return v;
}
__device__ __forceinline__ uint2 ld_poll64(const void* p) {
    uint2 v;
    asm volatile("ld.relaxed.gpu.global.v2.u32 {%0,%1}, [%2];\n" : "=r"(v.x), "=r"(v.y) : "l"(p) : "memory");
    return v;
}
__device__ __forceinline__ uint32_t ld_poll32(const void* p) {
    uint32_t v;
    asm volatile("ld.relaxed.gpu.global.u32 %0, [%1];\n" : "=r"(v) : "l"(p) : "memory");
    return v;
}
__device__ __forceinline__ uint32_t ld_acquire32(const void* p) {
    uint32_t v;
    asm volatile("ld.acquire.gpu.global.u32 %0, [%1];\n" : "=r"(v) : "l"(p) : "memory");
    return v;
}
__device__ __forceinline__ uint2 ldo64(const void* p) {
    uint2 v;
    asm volatile("ld.relaxed.cta.global.v2.u32 {%0,%1}, [%2];\n" : "=r"(v.x), "=r"(v.y) : "l"(p) : "memory");
    return v;
}
__device__ __forceinline__ uint32_t ldo16(const void* p) {
    uint32_t v;
    asm volatile("ld.relaxed.cta.global.u16 %0, [%1];\n" : "=r"(v) : "l"(p) : "memory");
    return v;
}
__device__ __forceinline__ void stg128(void* p, uint32_t a, uint32_t b, uint32_t c, uint32_t d) {
    asm volatile("st.global.v4.u32 [%0], {%1,%2,%3,%4};\n" ::"l"(p), "r"(a), "r"(b), "r"(c), "r"(d) : "memory");
}
__device__ __forceinline__ void stg64(void* p, uint32_t a, uint32_t b) { asm volatile("st.global.v2.u32 [%0], {%1,%2};\n" ::"l"(p), "r"(a), "r"(b) : "memory"); }
__device__ __forceinline__ uint32_t min4(const uint4& v) { return min(min(v.x, v.y), min(v.z, v.w)); }
#define SPIN_LIMIT (1 << 21)
#define TRAP() __trap()
__device__ __forceinline__ void mbar_init(uint32_t bar, uint32_t cnt) { asm volatile("mbarrier.init.shared::cta.b64 [%0], %1;\n" ::"r"(bar), "r"(cnt) : "memory"); }
__device__ __forceinline__ void mbar_expect(uint32_t bar, uint32_t bytes) {
    asm volatile("mbarrier.arrive.expect_tx.shared::cta.b64 _, [%0], %1;\n" ::"r"(bar), "r"(bytes) : "memory");
}
__device__ __forceinline__ void mbar_arrive(uint32_t bar) { asm volatile("mbarrier.arrive.shared::cta.b64 _, [%0];\n" ::"r"(bar) : "memory"); }
__device__ __forceinline__ void mbar_wait(uint32_t bar) {
    asm volatile(
        "{\n.reg .pred p;\n"
        "W_%=:\n"
        "mbarrier.try_wait.parity.shared::cta.b64 p, [%0], 0;\n"
        "@!p bra W_%=;\n}\n" ::"r"(bar) : "memory");
}
__device__ __forceinline__ void bulk_g2s(uint32_t dst, const void* src, uint32_t bytes, uint32_t bar) {
    asm volatile("cp.async.bulk.shared::cluster.global.mbarrier::complete_tx::bytes [%0], [%1], %2, [%3];\n" ::"r"(dst), "l"(src), "r"(bytes), "r"(bar) : "memory");
}
__device__ __forceinline__ void bulk_s2g(void* dst, uint32_t src, uint32_t bytes) {
    asm volatile("cp.async.bulk.global.shared::cta.bulk_group [%0], [%1], %2;\ncp.async.bulk.commit_group;\n" ::"l"(dst), "r"(src), "r"(bytes) : "memory");
}
__device__ __forceinline__ void bulk_s2g_nc(void* dst, uint32_t src, uint32_t bytes) {
    asm volatile("cp.async.bulk.global.shared::cta.bulk_group [%0], [%1], %2;\n" ::"l"(dst), "r"(src), "r"(bytes) : "memory");
}
__device__ __forceinline__ void tma_2d(uint32_t dst, const CUtensorMap* tm, int c0, int c1, uint32_t bar) {
    asm volatile("cp.async.bulk.tensor.2d.shared::cluster.global.mbarrier::complete_tx::bytes [%0], [%1, {%3, %4}], [%2];\n"
                 ::"r"(dst), "l"(tm), "r"(bar), "r"(c0), "r"(c1) : "memory");
}
__device__ __forceinline__ void tma_4d_mc(uint32_t dst, const CUtensorMap* tm, int c0, int c3, uint32_t bar) {
    asm volatile("cp.async.bulk.tensor.4d.shared::cluster.global.mbarrier::complete_tx::bytes.multicast::cluster [%0], [%1, {%3, %4, %4, %5}], [%2], %6;\n"
                 ::"r"(dst), "l"(tm), "r"(bar), "r"(c0), "r"(0), "r"(c3), "h"((unsigned short)3) : "memory");
}
__device__ __forceinline__ bool elect_one() {
    uint32_t r;
    asm volatile("{\n.reg .pred p;\nelect.sync _|p, 0xffffffff;\nselp.u32 %0, 1, 0, p;\n}\n" : "=r"(r));
    return r;
}
__device__ __forceinline__ void delay(uint32_t clks) {
    uint32_t t0, t1;
    asm volatile("mov.u32 %0, %%clock;" : "=r"(t0) :: "memory");
    do { asm volatile("mov.u32 %0, %%clock;" : "=r"(t1) :: "memory"); } while (t1 - t0 < clks);
}
__device__ __forceinline__ void fence_async() { asm volatile("fence.proxy.async.shared::cta;\n" ::: "memory"); }

__device__ __forceinline__ float2 cmul(float2 a, float2 b) {
    return make_float2(fmaf(a.x, b.x, -a.y * b.y), fmaf(a.x, b.y, a.y * b.x));
}
__device__ __forceinline__ float2 csq(float2 a) {
    float p = a.x * a.y;
    return make_float2(fmaf(a.x, a.x, -a.y * a.y), p + p);
}
__device__ __forceinline__ float ex2_approx(float x) { float r; asm("ex2.approx.ftz.f32 %0, %1;\n" : "=f"(r) : "f"(x)); return r; }
__device__ __forceinline__ float exp_bf(float x) { return rbf(ex2_approx(__fmul_ru(x, 1.4426950408889634f))); }
__device__ __forceinline__ float2 cexp_e(float lr2, float li, float e) {
    const float m = ex2_approx(lr2 * e);
    return make_float2(m * __cosf(li * e), m * __sinf(li * e));
}
__device__ __forceinline__ float rcp_approx(float x) { float r; asm("rcp.approx.ftz.f32 %0, %1;\n" : "=f"(r) : "f"(x)); return r; }
__device__ __forceinline__ float sigmoid_f(float x) { return rcp_approx(1.0f + ex2_approx(x * -1.4426950408889634f)); }
__device__ __forceinline__ float sqrt_approx(float x) { float r; asm("sqrt.approx.ftz.f32 %0, %1;\n" : "=f"(r) : "f"(x)); return r; }

__device__ __forceinline__ void wg_fence() { asm volatile("wgmma.fence.sync.aligned;\n" ::: "memory"); }
__device__ __forceinline__ void wg_commit() { asm volatile("wgmma.commit_group.sync.aligned;\n" ::: "memory"); }
__device__ __forceinline__ void wg_wait0() { asm volatile("wgmma.wait_group.sync.aligned 0;\n" ::: "memory"); }
template <int T> __device__ __forceinline__ void wg_mma(float (&acc)[16][4], const uint32_t* a, uint64_t desc);
template <int T> __device__ __forceinline__ void wg_first(float (&acc)[16][4], const uint32_t* a, uint64_t desc);
template <> __device__ __forceinline__ void wg_mma<0>(float (&acc)[16][4], const uint32_t* a, uint64_t desc) {
    asm volatile("wgmma.mma_async.sync.aligned.m64n128k16.f32.f16.f16 {%0,%1,%2,%3,%4,%5,%6,%7,%8,%9,%10,%11,%12,%13,%14,%15,%16,%17,%18,%19,%20,%21,%22,%23,%24,%25,%26,%27,%28,%29,%30,%31,%32,%33,%34,%35,%36,%37,%38,%39,%40,%41,%42,%43,%44,%45,%46,%47,%48,%49,%50,%51,%52,%53,%54,%55,%56,%57,%58,%59,%60,%61,%62,%63}, {%64,%65,%66,%67}, %68, 1, 1, 1, 0;\n"
                 : "+f"(acc[0][0]), "+f"(acc[0][1]), "+f"(acc[0][2]), "+f"(acc[0][3]), "+f"(acc[1][0]), "+f"(acc[1][1]), "+f"(acc[1][2]), "+f"(acc[1][3]), "+f"(acc[2][0]), "+f"(acc[2][1]), "+f"(acc[2][2]), "+f"(acc[2][3]), "+f"(acc[3][0]), "+f"(acc[3][1]), "+f"(acc[3][2]), "+f"(acc[3][3]), "+f"(acc[4][0]), "+f"(acc[4][1]), "+f"(acc[4][2]), "+f"(acc[4][3]), "+f"(acc[5][0]), "+f"(acc[5][1]), "+f"(acc[5][2]), "+f"(acc[5][3]), "+f"(acc[6][0]), "+f"(acc[6][1]), "+f"(acc[6][2]), "+f"(acc[6][3]), "+f"(acc[7][0]), "+f"(acc[7][1]), "+f"(acc[7][2]), "+f"(acc[7][3]), "+f"(acc[8][0]), "+f"(acc[8][1]), "+f"(acc[8][2]), "+f"(acc[8][3]), "+f"(acc[9][0]), "+f"(acc[9][1]), "+f"(acc[9][2]), "+f"(acc[9][3]), "+f"(acc[10][0]), "+f"(acc[10][1]), "+f"(acc[10][2]), "+f"(acc[10][3]), "+f"(acc[11][0]), "+f"(acc[11][1]), "+f"(acc[11][2]), "+f"(acc[11][3]), "+f"(acc[12][0]), "+f"(acc[12][1]), "+f"(acc[12][2]), "+f"(acc[12][3]), "+f"(acc[13][0]), "+f"(acc[13][1]), "+f"(acc[13][2]), "+f"(acc[13][3]), "+f"(acc[14][0]), "+f"(acc[14][1]), "+f"(acc[14][2]), "+f"(acc[14][3]), "+f"(acc[15][0]), "+f"(acc[15][1]), "+f"(acc[15][2]), "+f"(acc[15][3])
                 : "r"(a[0]), "r"(a[1]), "r"(a[2]), "r"(a[3]), "l"(desc));
}
template <> __device__ __forceinline__ void wg_mma<2>(float (&acc)[16][4], const uint32_t* a, uint64_t desc) {
    asm volatile("wgmma.mma_async.sync.aligned.m64n112k16.f32.f16.f16 {%0,%1,%2,%3,%4,%5,%6,%7,%8,%9,%10,%11,%12,%13,%14,%15,%16,%17,%18,%19,%20,%21,%22,%23,%24,%25,%26,%27,%28,%29,%30,%31,%32,%33,%34,%35,%36,%37,%38,%39,%40,%41,%42,%43,%44,%45,%46,%47,%48,%49,%50,%51,%52,%53,%54,%55}, {%56,%57,%58,%59}, %60, 1, 1, 1, 0;\n"
                 : "+f"(acc[2][0]), "+f"(acc[2][1]), "+f"(acc[2][2]), "+f"(acc[2][3]), "+f"(acc[3][0]), "+f"(acc[3][1]), "+f"(acc[3][2]), "+f"(acc[3][3]), "+f"(acc[4][0]), "+f"(acc[4][1]), "+f"(acc[4][2]), "+f"(acc[4][3]), "+f"(acc[5][0]), "+f"(acc[5][1]), "+f"(acc[5][2]), "+f"(acc[5][3]), "+f"(acc[6][0]), "+f"(acc[6][1]), "+f"(acc[6][2]), "+f"(acc[6][3]), "+f"(acc[7][0]), "+f"(acc[7][1]), "+f"(acc[7][2]), "+f"(acc[7][3]), "+f"(acc[8][0]), "+f"(acc[8][1]), "+f"(acc[8][2]), "+f"(acc[8][3]), "+f"(acc[9][0]), "+f"(acc[9][1]), "+f"(acc[9][2]), "+f"(acc[9][3]), "+f"(acc[10][0]), "+f"(acc[10][1]), "+f"(acc[10][2]), "+f"(acc[10][3]), "+f"(acc[11][0]), "+f"(acc[11][1]), "+f"(acc[11][2]), "+f"(acc[11][3]), "+f"(acc[12][0]), "+f"(acc[12][1]), "+f"(acc[12][2]), "+f"(acc[12][3]), "+f"(acc[13][0]), "+f"(acc[13][1]), "+f"(acc[13][2]), "+f"(acc[13][3]), "+f"(acc[14][0]), "+f"(acc[14][1]), "+f"(acc[14][2]), "+f"(acc[14][3]), "+f"(acc[15][0]), "+f"(acc[15][1]), "+f"(acc[15][2]), "+f"(acc[15][3])
                 : "r"(a[0]), "r"(a[1]), "r"(a[2]), "r"(a[3]), "l"(desc));
}
template <> __device__ __forceinline__ void wg_mma<4>(float (&acc)[16][4], const uint32_t* a, uint64_t desc) {
    asm volatile("wgmma.mma_async.sync.aligned.m64n96k16.f32.f16.f16 {%0,%1,%2,%3,%4,%5,%6,%7,%8,%9,%10,%11,%12,%13,%14,%15,%16,%17,%18,%19,%20,%21,%22,%23,%24,%25,%26,%27,%28,%29,%30,%31,%32,%33,%34,%35,%36,%37,%38,%39,%40,%41,%42,%43,%44,%45,%46,%47}, {%48,%49,%50,%51}, %52, 1, 1, 1, 0;\n"
                 : "+f"(acc[4][0]), "+f"(acc[4][1]), "+f"(acc[4][2]), "+f"(acc[4][3]), "+f"(acc[5][0]), "+f"(acc[5][1]), "+f"(acc[5][2]), "+f"(acc[5][3]), "+f"(acc[6][0]), "+f"(acc[6][1]), "+f"(acc[6][2]), "+f"(acc[6][3]), "+f"(acc[7][0]), "+f"(acc[7][1]), "+f"(acc[7][2]), "+f"(acc[7][3]), "+f"(acc[8][0]), "+f"(acc[8][1]), "+f"(acc[8][2]), "+f"(acc[8][3]), "+f"(acc[9][0]), "+f"(acc[9][1]), "+f"(acc[9][2]), "+f"(acc[9][3]), "+f"(acc[10][0]), "+f"(acc[10][1]), "+f"(acc[10][2]), "+f"(acc[10][3]), "+f"(acc[11][0]), "+f"(acc[11][1]), "+f"(acc[11][2]), "+f"(acc[11][3]), "+f"(acc[12][0]), "+f"(acc[12][1]), "+f"(acc[12][2]), "+f"(acc[12][3]), "+f"(acc[13][0]), "+f"(acc[13][1]), "+f"(acc[13][2]), "+f"(acc[13][3]), "+f"(acc[14][0]), "+f"(acc[14][1]), "+f"(acc[14][2]), "+f"(acc[14][3]), "+f"(acc[15][0]), "+f"(acc[15][1]), "+f"(acc[15][2]), "+f"(acc[15][3])
                 : "r"(a[0]), "r"(a[1]), "r"(a[2]), "r"(a[3]), "l"(desc));
}
template <> __device__ __forceinline__ void wg_mma<6>(float (&acc)[16][4], const uint32_t* a, uint64_t desc) {
    asm volatile("wgmma.mma_async.sync.aligned.m64n80k16.f32.f16.f16 {%0,%1,%2,%3,%4,%5,%6,%7,%8,%9,%10,%11,%12,%13,%14,%15,%16,%17,%18,%19,%20,%21,%22,%23,%24,%25,%26,%27,%28,%29,%30,%31,%32,%33,%34,%35,%36,%37,%38,%39}, {%40,%41,%42,%43}, %44, 1, 1, 1, 0;\n"
                 : "+f"(acc[6][0]), "+f"(acc[6][1]), "+f"(acc[6][2]), "+f"(acc[6][3]), "+f"(acc[7][0]), "+f"(acc[7][1]), "+f"(acc[7][2]), "+f"(acc[7][3]), "+f"(acc[8][0]), "+f"(acc[8][1]), "+f"(acc[8][2]), "+f"(acc[8][3]), "+f"(acc[9][0]), "+f"(acc[9][1]), "+f"(acc[9][2]), "+f"(acc[9][3]), "+f"(acc[10][0]), "+f"(acc[10][1]), "+f"(acc[10][2]), "+f"(acc[10][3]), "+f"(acc[11][0]), "+f"(acc[11][1]), "+f"(acc[11][2]), "+f"(acc[11][3]), "+f"(acc[12][0]), "+f"(acc[12][1]), "+f"(acc[12][2]), "+f"(acc[12][3]), "+f"(acc[13][0]), "+f"(acc[13][1]), "+f"(acc[13][2]), "+f"(acc[13][3]), "+f"(acc[14][0]), "+f"(acc[14][1]), "+f"(acc[14][2]), "+f"(acc[14][3]), "+f"(acc[15][0]), "+f"(acc[15][1]), "+f"(acc[15][2]), "+f"(acc[15][3])
                 : "r"(a[0]), "r"(a[1]), "r"(a[2]), "r"(a[3]), "l"(desc));
}
template <> __device__ __forceinline__ void wg_mma<8>(float (&acc)[16][4], const uint32_t* a, uint64_t desc) {
    asm volatile("wgmma.mma_async.sync.aligned.m64n64k16.f32.f16.f16 {%0,%1,%2,%3,%4,%5,%6,%7,%8,%9,%10,%11,%12,%13,%14,%15,%16,%17,%18,%19,%20,%21,%22,%23,%24,%25,%26,%27,%28,%29,%30,%31}, {%32,%33,%34,%35}, %36, 1, 1, 1, 0;\n"
                 : "+f"(acc[8][0]), "+f"(acc[8][1]), "+f"(acc[8][2]), "+f"(acc[8][3]), "+f"(acc[9][0]), "+f"(acc[9][1]), "+f"(acc[9][2]), "+f"(acc[9][3]), "+f"(acc[10][0]), "+f"(acc[10][1]), "+f"(acc[10][2]), "+f"(acc[10][3]), "+f"(acc[11][0]), "+f"(acc[11][1]), "+f"(acc[11][2]), "+f"(acc[11][3]), "+f"(acc[12][0]), "+f"(acc[12][1]), "+f"(acc[12][2]), "+f"(acc[12][3]), "+f"(acc[13][0]), "+f"(acc[13][1]), "+f"(acc[13][2]), "+f"(acc[13][3]), "+f"(acc[14][0]), "+f"(acc[14][1]), "+f"(acc[14][2]), "+f"(acc[14][3]), "+f"(acc[15][0]), "+f"(acc[15][1]), "+f"(acc[15][2]), "+f"(acc[15][3])
                 : "r"(a[0]), "r"(a[1]), "r"(a[2]), "r"(a[3]), "l"(desc));
}
template <> __device__ __forceinline__ void wg_mma<10>(float (&acc)[16][4], const uint32_t* a, uint64_t desc) {
    asm volatile("wgmma.mma_async.sync.aligned.m64n48k16.f32.f16.f16 {%0,%1,%2,%3,%4,%5,%6,%7,%8,%9,%10,%11,%12,%13,%14,%15,%16,%17,%18,%19,%20,%21,%22,%23}, {%24,%25,%26,%27}, %28, 1, 1, 1, 0;\n"
                 : "+f"(acc[10][0]), "+f"(acc[10][1]), "+f"(acc[10][2]), "+f"(acc[10][3]), "+f"(acc[11][0]), "+f"(acc[11][1]), "+f"(acc[11][2]), "+f"(acc[11][3]), "+f"(acc[12][0]), "+f"(acc[12][1]), "+f"(acc[12][2]), "+f"(acc[12][3]), "+f"(acc[13][0]), "+f"(acc[13][1]), "+f"(acc[13][2]), "+f"(acc[13][3]), "+f"(acc[14][0]), "+f"(acc[14][1]), "+f"(acc[14][2]), "+f"(acc[14][3]), "+f"(acc[15][0]), "+f"(acc[15][1]), "+f"(acc[15][2]), "+f"(acc[15][3])
                 : "r"(a[0]), "r"(a[1]), "r"(a[2]), "r"(a[3]), "l"(desc));
}
template <> __device__ __forceinline__ void wg_mma<12>(float (&acc)[16][4], const uint32_t* a, uint64_t desc) {
    asm volatile("wgmma.mma_async.sync.aligned.m64n32k16.f32.f16.f16 {%0,%1,%2,%3,%4,%5,%6,%7,%8,%9,%10,%11,%12,%13,%14,%15}, {%16,%17,%18,%19}, %20, 1, 1, 1, 0;\n"
                 : "+f"(acc[12][0]), "+f"(acc[12][1]), "+f"(acc[12][2]), "+f"(acc[12][3]), "+f"(acc[13][0]), "+f"(acc[13][1]), "+f"(acc[13][2]), "+f"(acc[13][3]), "+f"(acc[14][0]), "+f"(acc[14][1]), "+f"(acc[14][2]), "+f"(acc[14][3]), "+f"(acc[15][0]), "+f"(acc[15][1]), "+f"(acc[15][2]), "+f"(acc[15][3])
                 : "r"(a[0]), "r"(a[1]), "r"(a[2]), "r"(a[3]), "l"(desc));
}
template <> __device__ __forceinline__ void wg_mma<14>(float (&acc)[16][4], const uint32_t* a, uint64_t desc) {
    asm volatile("wgmma.mma_async.sync.aligned.m64n16k16.f32.f16.f16 {%0,%1,%2,%3,%4,%5,%6,%7}, {%8,%9,%10,%11}, %12, 1, 1, 1, 0;\n"
                 : "+f"(acc[14][0]), "+f"(acc[14][1]), "+f"(acc[14][2]), "+f"(acc[14][3]), "+f"(acc[15][0]), "+f"(acc[15][1]), "+f"(acc[15][2]), "+f"(acc[15][3])
                 : "r"(a[0]), "r"(a[1]), "r"(a[2]), "r"(a[3]), "l"(desc));
}
template <> __device__ __forceinline__ void wg_first<0>(float (&acc)[16][4], const uint32_t* a, uint64_t desc) {
    asm volatile("wgmma.mma_async.sync.aligned.m64n128k16.f32.f16.f16 {%0,%1,%2,%3,%4,%5,%6,%7,%8,%9,%10,%11,%12,%13,%14,%15,%16,%17,%18,%19,%20,%21,%22,%23,%24,%25,%26,%27,%28,%29,%30,%31,%32,%33,%34,%35,%36,%37,%38,%39,%40,%41,%42,%43,%44,%45,%46,%47,%48,%49,%50,%51,%52,%53,%54,%55,%56,%57,%58,%59,%60,%61,%62,%63}, {%64,%65,%66,%67}, %68, 0, 1, 1, 0;\n"
                 : "=f"(acc[0][0]), "=f"(acc[0][1]), "=f"(acc[0][2]), "=f"(acc[0][3]), "=f"(acc[1][0]), "=f"(acc[1][1]), "=f"(acc[1][2]), "=f"(acc[1][3]), "=f"(acc[2][0]), "=f"(acc[2][1]), "=f"(acc[2][2]), "=f"(acc[2][3]), "=f"(acc[3][0]), "=f"(acc[3][1]), "=f"(acc[3][2]), "=f"(acc[3][3]), "=f"(acc[4][0]), "=f"(acc[4][1]), "=f"(acc[4][2]), "=f"(acc[4][3]), "=f"(acc[5][0]), "=f"(acc[5][1]), "=f"(acc[5][2]), "=f"(acc[5][3]), "=f"(acc[6][0]), "=f"(acc[6][1]), "=f"(acc[6][2]), "=f"(acc[6][3]), "=f"(acc[7][0]), "=f"(acc[7][1]), "=f"(acc[7][2]), "=f"(acc[7][3]), "=f"(acc[8][0]), "=f"(acc[8][1]), "=f"(acc[8][2]), "=f"(acc[8][3]), "=f"(acc[9][0]), "=f"(acc[9][1]), "=f"(acc[9][2]), "=f"(acc[9][3]), "=f"(acc[10][0]), "=f"(acc[10][1]), "=f"(acc[10][2]), "=f"(acc[10][3]), "=f"(acc[11][0]), "=f"(acc[11][1]), "=f"(acc[11][2]), "=f"(acc[11][3]), "=f"(acc[12][0]), "=f"(acc[12][1]), "=f"(acc[12][2]), "=f"(acc[12][3]), "=f"(acc[13][0]), "=f"(acc[13][1]), "=f"(acc[13][2]), "=f"(acc[13][3]), "=f"(acc[14][0]), "=f"(acc[14][1]), "=f"(acc[14][2]), "=f"(acc[14][3]), "=f"(acc[15][0]), "=f"(acc[15][1]), "=f"(acc[15][2]), "=f"(acc[15][3])
                 : "r"(a[0]), "r"(a[1]), "r"(a[2]), "r"(a[3]), "l"(desc));
}
template <> __device__ __forceinline__ void wg_first<4>(float (&acc)[16][4], const uint32_t* a, uint64_t desc) {
    asm volatile("wgmma.mma_async.sync.aligned.m64n96k16.f32.f16.f16 {%0,%1,%2,%3,%4,%5,%6,%7,%8,%9,%10,%11,%12,%13,%14,%15,%16,%17,%18,%19,%20,%21,%22,%23,%24,%25,%26,%27,%28,%29,%30,%31,%32,%33,%34,%35,%36,%37,%38,%39,%40,%41,%42,%43,%44,%45,%46,%47}, {%48,%49,%50,%51}, %52, 0, 1, 1, 0;\n"
                 : "=f"(acc[4][0]), "=f"(acc[4][1]), "=f"(acc[4][2]), "=f"(acc[4][3]), "=f"(acc[5][0]), "=f"(acc[5][1]), "=f"(acc[5][2]), "=f"(acc[5][3]), "=f"(acc[6][0]), "=f"(acc[6][1]), "=f"(acc[6][2]), "=f"(acc[6][3]), "=f"(acc[7][0]), "=f"(acc[7][1]), "=f"(acc[7][2]), "=f"(acc[7][3]), "=f"(acc[8][0]), "=f"(acc[8][1]), "=f"(acc[8][2]), "=f"(acc[8][3]), "=f"(acc[9][0]), "=f"(acc[9][1]), "=f"(acc[9][2]), "=f"(acc[9][3]), "=f"(acc[10][0]), "=f"(acc[10][1]), "=f"(acc[10][2]), "=f"(acc[10][3]), "=f"(acc[11][0]), "=f"(acc[11][1]), "=f"(acc[11][2]), "=f"(acc[11][3]), "=f"(acc[12][0]), "=f"(acc[12][1]), "=f"(acc[12][2]), "=f"(acc[12][3]), "=f"(acc[13][0]), "=f"(acc[13][1]), "=f"(acc[13][2]), "=f"(acc[13][3]), "=f"(acc[14][0]), "=f"(acc[14][1]), "=f"(acc[14][2]), "=f"(acc[14][3]), "=f"(acc[15][0]), "=f"(acc[15][1]), "=f"(acc[15][2]), "=f"(acc[15][3])
                 : "r"(a[0]), "r"(a[1]), "r"(a[2]), "r"(a[3]), "l"(desc));
}

#define SDLY 1300
#define UDLY 1400
#define KDLY 850
#define FDLY 1000
#define FDLY2 400
#define DDLY 300
#define WDLY 500
#define HW 15
#define FIX(v) do { if ((v) == 1u) TRAP(); } while (0)
#define STAMPW(i) STAMPY(i)
#define STAMP2(i) STAMP(i)
#undef STAMPX
#define STAMPX(i)
struct Params {
    const bf16 *x, *lar, *aim, *cre, *cim, *ldt, *dsk;
    Scratch* s;
    const bf16* wr;
    bf16* out;
};

#define TOK(g) (2 * (g) - ((g) & 1))
#define ROWTOK(r) (TOK((r) & 7) + (((r) >> 2) & 2))
__device__ __forceinline__ void ln_partial(const uint32_t (&H)[2][4], float (&d)[2][4]) {
#pragma unroll
    for (int i = 0; i < 8; i++) d[i >> 2][i & 3] = 0.f;
#pragma unroll
    for (int k = 0; k < 4; k++)
#pragma unroll
        for (int hf = 0; hf < 2; hf++) mma_bf16_k8(d[hf], H[hf][k], 0x3f803f80u, H[hf][k]);
}
__device__ __forceinline__ float sum18(uint32_t a) {
    const uint4 p = lds128(a), q = lds128(a + 16), r = lds128(a + 32), s = lds128(a + 48);
    const uint2 u = lds64(a + 64);
#define F(x) __uint_as_float(x)
    return (((F(p.x) + F(p.y)) + (F(p.z) + F(p.w))) + ((F(q.x) + F(q.y)) + (F(q.z) + F(q.w)))) +
           (((F(r.x) + F(r.y)) + (F(r.z) + F(r.w))) + ((F(s.x) + F(s.y)) + (F(s.z) + F(s.w))) + (F(u.x) + F(u.y)));
#undef F
}
__device__ __forceinline__ void ln_stats(float sm, float sq, float& mb, float& sd) {
    const float m0 = sm * (1.0f / 576.0f);
    const float mean = fmaf(fmaf(-m0, 576.0f, sm), 1.0f / 576.0f, m0);
    const float var = fmaxf(fmaf(-mean, mean, sq * (1.0f / 576.0f)), 0.f);
    mb = rbf(mean);
    sd = rbf(sqrt_approx(rbf(rbf(var) + 1e-5f)));
}
__device__ __forceinline__ void ln_finish(float v, int lane, float& mb, float& rc) {
    const float o = __shfl_xor_sync(0xffffffffu, v, 16);
    float sd;
    ln_stats(lane < 16 ? v : o, lane < 16 ? o : v, mb, sd);
    rc = rcp_approx(sd);
}
__device__ __forceinline__ uint32_t ln_apply(uint32_t w, uint32_t m2, uint32_t rh, uint32_t rl) {
    const uint32_t d = hsub2_bf(w, m2);
    return hfma2_bf(d, rh, hmul2_bf(d, rl));
}
__device__ __forceinline__ void stat_store(uint32_t a, float mb, float rc, uint32_t extra) {
    const float rh = rbf(rc);
    sts64(a, (__float_as_uint(mb) >> 16) | (extra << 16), pack_bf16(rh, rc - rh));
}
#define STAT_M(s) __byte_perm((s).x, (s).x, 0x1010)
#define STAT_H(s) __byte_perm((s).y, (s).y, 0x1010)
#define STAT_L(s) __byte_perm((s).y, (s).y, 0x3232)

__device__ __forceinline__ void hcmul(uint32_t re, uint32_t im, uint32_t zx, uint32_t zy, uint32_t& ore, uint32_t& oim) {
    ore = hfms2(im, zy, hmul2(re, zx));
    oim = hfma2(re, zy, hmul2(im, zx));
}

struct KGen {
    uint32_t A[2][4][4];
    float2 z1, z8, z64, z128, T[9];
};
__device__ __forceinline__ void kgen_setup(KGen& k, float lar, float aim, float dt) {
    const float lr2 = -(exp_bf(lar) * dt) * 1.4426950408889634f, li = aim * dt;
    k.z1 = cexp_e(lr2, li, 1.0f);
    k.z8 = cexp_e(lr2, li, 8.0f);
    k.z64 = cexp_e(lr2, li, 64.0f);
}
__device__ __forceinline__ void kgen_rows(KGen& k, uint32_t tb, int lane) {
    const float2 z8 = k.z8, z64 = k.z64;
    const uint32_t row = tb + lane * 16;
    k.z128 = csq(z64);
    const float2 z16 = csq(z8), z24 = cmul(z16, z8), z32 = csq(z16), z40 = cmul(z32, z8), z48 = csq(z24), z56 = cmul(z32, z24);
    uint32_t re[4], im[4], a[4], b[4];
    re[0] = pack_f16(1.0f, z8.x); im[0] = pack_f16(0.0f, z8.y);
    re[1] = pack_f16(z16.x, z24.x); im[1] = pack_f16(z16.y, z24.y);
    re[2] = pack_f16(z32.x, z40.x); im[2] = pack_f16(z32.y, z40.y);
    re[3] = pack_f16(z48.x, z56.x); im[3] = pack_f16(z48.y, z56.y);
    sts128(row, re[0], re[1], re[2], re[3]);
    sts128(row + 1024, im[0], im[1], im[2], im[3]);
    const uint32_t zx = pack_f16(z64.x, z64.x), zy = pack_f16(z64.y, z64.y), zw = pack_f16(k.z128.x, k.z128.y);
#pragma unroll
    for (int j = 0; j < 4; j++) hcmul(re[j], im[j], zx, zy, a[j], b[j]);
    sts128(row + 512, a[0], a[1], a[2], a[3]);
    sts128(row + 1536, b[0], b[1], b[2], b[3]);
    const int mi = lane >> 3;
    const uint32_t zd = tb + 2048 + mi * 16;
    sts16(tb + 2048 + lane * 2, zw); sts16(tb + 2112 + lane * 2, zw >> 16);
    __syncwarp();
    const uint32_t ad = tb + (lane & 7) * 16 + mi * 512;
    ldsm_x4(a[0], a[1], a[2], a[3], zd);
    ldsm_x4(b[0], b[1], b[2], b[3], zd + 64);
#pragma unroll
    for (int ks = 0; ks < 4; ks++) {
        ldsm_x4_t(k.A[0][ks][0], k.A[0][ks][1], k.A[0][ks][2], k.A[0][ks][3], ad + ks * 128);
        hcmul(k.A[0][ks][0], k.A[0][ks][2], a[ks], b[ks], k.A[1][ks][0], k.A[1][ks][2]);
        hcmul(k.A[0][ks][1], k.A[0][ks][3], a[ks], b[ks], k.A[1][ks][1], k.A[1][ks][3]);
    }
}
__device__ __forceinline__ void kgen_chain(KGen& k, uint32_t cr, uint32_t ci, float cs) {
    k.T[0] = make_float2(bf_lo(cr) * cs, -bf_lo(ci) * cs);
    const float2 y1 = make_float2(k.z1.x, -k.z1.y);
#pragma unroll
    for (int c = 1; c < 8; c++) k.T[c] = cmul(k.T[c - 1], y1);
    k.T[8] = cmul(k.T[0], make_float2(k.z8.x, -k.z8.y));
}
__device__ __forceinline__ void kgen_cols(KGen& k, uint32_t tb, uint32_t t5, int lane) {
    const uint32_t row = tb + lane * 16;
    const float2 (&T)[9] = k.T;
    const float2 y128 = make_float2(k.z128.x, -k.z128.y);
    const float2 y256 = csq(y128), y512 = csq(y256), y768 = cmul(y512, y256), y1024 = csq(y512);
    const float2 c1032 = cmul(T[8], y1024);
    __syncwarp();
    sts128(row, pack_f16(T[0].x, T[1].x), pack_f16(T[2].x, T[3].x), pack_f16(T[4].x, T[5].x), pack_f16(T[6].x, T[7].x));
    sts128(row + 512, pack_f16(T[0].y, T[1].y), pack_f16(T[2].y, T[3].y), pack_f16(T[4].y, T[5].y), pack_f16(T[6].y, T[7].y));
    uint32_t a[4], b[4];
    {
        const uint32_t zx = pack_f16(y256.x, y256.x), zy = pack_f16(y256.y, y256.y);
        hcmul(pack_f16(T[0].x, T[2].x), pack_f16(T[0].y, T[2].y), zx, zy, a[0], b[0]);
        hcmul(pack_f16(T[4].x, T[6].x), pack_f16(T[4].y, T[6].y), zx, zy, a[1], b[1]);
        const uint32_t r04 = pack_f16(T[0].x, T[4].x), i04 = pack_f16(T[0].y, T[4].y);
        hcmul(r04, i04, pack_f16(y512.x, y512.x), pack_f16(y512.y, y512.y), a[2], b[2]);
        hcmul(r04, i04, pack_f16(y768.x, y768.x), pack_f16(y768.y, y768.y), a[3], b[3]);
    }
    sts128(row + 1024, a[0], a[1], a[2], a[3]);
    sts128(row + 1536, b[0], b[1], b[2], b[3]);
    {
        const uint32_t r0 = pack_f16(1.0f, y256.x), i0 = pack_f16(0.0f, y256.y), r1 = pack_f16(y512.x, y768.x), i1 = pack_f16(y512.y, y768.y);
        const uint32_t zx = pack_f16(T[8].x, T[8].x), zy = pack_f16(T[8].y, T[8].y), wx = pack_f16(c1032.x, c1032.x), wy = pack_f16(c1032.y, c1032.y);
        hcmul(r0, i0, zx, zy, a[0], b[0]); hcmul(r1, i1, zx, zy, a[1], b[1]);
        hcmul(r0, i0, wx, wy, a[2], b[2]); hcmul(r1, i1, wx, wy, a[3], b[3]);
    }
    sts128(row + 2048, a[0], a[1], a[2], a[3]);
    sts128(t5 + lane * 16, b[0], b[1], b[2], b[3]);
}
__device__ __forceinline__ void kgen_mma(const KGen& k, uint32_t tb, uint32_t t5, int lane) {
    __syncwarp();
    float acc[2][3][4];
#pragma unroll
    for (int i = 0; i < 6; i++)
#pragma unroll
        for (int j = 0; j < 4; j++) acc[i / 3][i % 3][j] = 0.f;
    const int mi = lane >> 3;
    const uint32_t ro = ((lane & 7) + 8 * (mi >> 1)) * 16, bd = tb + ro + (mi & 1) * 512, b2 = ro + ((mi & 1) ? t5 : tb + 2048);
#pragma unroll
    for (int kp = 0; kp < 2; kp++)
#pragma unroll
        for (int j = 0; j < 3; j++) {
            uint32_t b[4];
            ldsm_x4_t(b[0], b[1], b[2], b[3], (j < 2 ? bd + j * 1024 : b2) + kp * 256);
#pragma unroll
            for (int h = 0; h < 2; h++)
#pragma unroll
                for (int m = 0; m < 2; m++) {
                    const uint32_t (&A)[4] = k.A[m][2 * kp + h];
                    mma_f16(acc[m][j], A[0], A[1], A[2], A[3], b[2 * h], b[2 * h + 1]);
                }
        }
    __syncwarp();
#define PK(j) pack_f16(acc[0][j][0], acc[0][j][1]), pack_f16(acc[0][j][2], acc[0][j][3]), pack_f16(acc[1][j][0], acc[1][j][1]), pack_f16(acc[1][j][2], acc[1][j][3])
    stsm_x4(tb + lane * 16, PK(0));
    stsm_x4(tb + 512 + lane * 16, PK(1));
    stsm_x4_t(tb + 1024 + (lane & 7) * 80 + mi * 16, PK(2));
#undef PK
}
__device__ __forceinline__ uint32_t table_buf(uint32_t sb, int warp) { return sb + SM_PL + warp * TBW; }

__device__ __forceinline__ uint4 lds16x4(uint32_t a) { return make_uint4(lds16(a), lds16(a + TBW), lds16(a + 2 * TBW), lds16(a + 3 * TBW)); }
__device__ __forceinline__ void combine_setup(uint32_t sb, int warp, int lane, uint32_t kw, uint32_t& o, uint32_t& n, uint32_t& d) {
    const int wq = warp & 3;
    const uint32_t a = table_buf(sb, warp & ~3);
    o = wq == 3 ? a + 1024 + 320 + (lane >> 3) * 80 + (lane & 7) * 8 : a + (wq ? 504 + wq * 8 : 0) + lane * 16;
    n = a + 1024 + wq * 80 + lane * 2;
    d = wq < 3 ? kw + (wq == 2 ? KW_P : 32 + wq * 512) + lane * 16 : kw + KW_H + 8 + lane * 8;
}
__device__ __forceinline__ void kgen_combine(int wq, int lane, uint32_t o, uint32_t na, uint32_t d) {
#define S4(f) hadd2(hadd2(u.f, v.f), hadd2(w.f, x.f))
#define H4(v) hadd2(hadd2(v.x, v.y), hadd2(v.z, v.w))
#define BP __byte_perm
    if (wq == 0) {
        const uint4 u = lds128(o), v = lds128(o + TBW), w = lds128(o + 2 * TBW), x = lds128(o + 3 * TBW), nn = lds16x4(na);
        const uint32_t n = H4(nn), k0 = S4(x), k2 = S4(y), k4 = S4(z), k6 = S4(w);
        sts128(d, BP(k0, k0, 0x1032), BP(k0, k2, 0x3254), BP(k2, k2, 0x1032), BP(k2, k4, 0x3254));
        sts128(d + KW_PL, BP(k4, k4, 0x1032), BP(k4, k6, 0x3254), BP(k6, k6, 0x1032), BP(k6, n, 0x3254));
        if (lane == 0) sts32(d + KW_PL - 4, k0 & 0xffffu);
    } else {
        const uint2 u = lds64(o), v = lds64(o + TBW), w = lds64(o + 2 * TBW), x = lds64(o + 3 * TBW);
        uint4 nn = make_uint4(0u, 0u, 0u, 0u), mm = nn;
        if (wq < 3) nn = lds16x4(na);
        if (wq == 2) mm = lds16x4(na + 80);
        const uint32_t k0 = S4(x), k2 = S4(y), n = H4(nn), m = H4(mm);
        if (wq == 3) {
            sts64(d, k0, k2);
        } else if (wq == 1) {
            const uint32_t cc = BP(k2, k2, 0x1010);
            sts128(d, BP(k0, k0, 0x1010), BP(k0, k0, 0x1032), BP(k0, k2, 0x3254), cc);
            sts128(d + KW_PL, cc, BP(k2, k2, 0x1032), BP(k2, n, 0x3254), BP(n, n, 0x1010));
        } else {
            const uint32_t w40 = BP(k0, k0, 0x1032), w84 = BP(k0, n, 0x3254), w0 = BP(k0, k0, 0x1010), w4 = BP(k0, k0, 0x3232), w8 = BP(n, n, 0x1010);
            sts64(d, w40, w84);
            sts64(d + 512, BP(k2, k2, 0x1032), BP(k2, m, 0x3254));
            if (lane < 8) { sts128(d - (KW_P - 1056), w0, w0, w40, w4); sts128(d - (KW_P - 1056 - KW_PL), w4, w84, w8, w8); }
            if (lane == 31) sts16(d + (KW_H + 6 - KW_P - 496), m);
        }
    }
#undef S4
#undef H4
#undef BP
}

__device__ __forceinline__ int c_exponent(const uint2& r, const uint2& i, float dt) {
    const uint32_t mx = __vmaxu2(__vmaxu2(r.x & 0x7fff7fffu, r.y & 0x7fff7fffu), __vmaxu2(i.x & 0x7fff7fffu, i.y & 0x7fff7fffu));
    return __reduce_max_sync(0xffffffffu, max(mx, mx << 16) + (__float_as_uint(dt) & 0x7f800000u)) >> 23;
}

__device__ __forceinline__ int lane_v() { int l; asm volatile("mov.u32 %0, %%laneid;" : "=r"(l)); return l; }
__device__ __forceinline__ uint32_t prmt_v(uint32_t a, uint32_t b, uint32_t s) { uint32_t d; asm volatile("prmt.b32 %0, %1, %2, %3;\n" : "=r"(d) : "r"(a), "r"(b), "r"(s)); return d; }
__device__ __forceinline__ uint32_t mov_v(uint32_t a) { uint32_t d; asm volatile("mov.b32 %0, %1;\n" : "=r"(d) : "r"(a)); return d; }
template <int G>
__device__ __forceinline__ void conv_rename(float (&acc)[16][4]) {
#pragma unroll
    for (int i = G; i < 16; i++)
#pragma unroll
        for (int j = 0; j < 4; j++) { float v; asm volatile("mov.b32 %0, %1;\n" : "=f"(v) : "f"(acc[i][j])); acc[i][j] = v; }
}
struct Conv {
    uint32_t kw;
    uint32_t wa;
    uint32_t pa, s2;
    uint32_t s8;
    uint32_t id;
    uint32_t lc;
    uint32_t fs;
    uint32_t fl, yo;
    uint32_t yp;
    size_t ycopy;
    uint32_t ps;
    uint64_t d0;
    int warp;
};
struct Pk { uint32_t w[4]; };
__device__ __forceinline__ Pk pk2(const float (&u)[4], const float (&v)[4]) {
    Pk r;
    r.w[0] = pack_f16(u[0], u[1]); r.w[1] = pack_f16(u[2], u[3]); r.w[2] = pack_f16(v[0], v[1]); r.w[3] = pack_f16(v[2], v[3]);
    return r;
}
__device__ __forceinline__ void park(uint32_t a, const Pk& v) {
    asm volatile("stmatrix.sync.aligned.m8n8.x4.trans.shared.b16 [%0], {%1,%2,%3,%4};\n" ::"r"(a), "r"(v.w[0]), "r"(v.w[1]), "r"(v.w[2]), "r"(v.w[3]) : "memory");
}
__device__ __forceinline__ void conv_constants(uint32_t lc, int l) {
    const int d = (l >> 2) - 2 * (l & 3);
    const int e = d + 8, r4 = (e + 1 + ((e >> 2) & 1)) >> 2, p4 = (e + (((e - 1) >> 2) & 1)) >> 2;
    const uint32_t s2 = r4 == p4 ? 0x1010u : 0x3210u;
    sts64(lc + l * 8, KW_P + ((r4 - 5) >> 1) * 16 + ((r4 - 5) & 1) * 4, s2 | ((d < 0 ? s2 : 0x7654u) << 16));
    const int lo = (d >= 4) - (d < -3), ho = (d >= 5) - (d < -2), le = (d > 4) - (d < -4), he = (d > 5) - (d < -3);
    sts32(lc + 512 + l * 8, (0x5454u + lo * 0x22 + ho * 0x2200) | ((0x3232u + le * 0x22 + he * 0x2200) << 16));
    const int cc = l >> 2, j = l & 3;
    sts64(lc + 256 + l * 8, (j >> 1) * PL_HALF + (16 + cc) * 16 + (j & 1) * 8, (cc >> 1) * (DM * 64) + (cc & 1) * 32 + j * 8);
}
__device__ __forceinline__ void conv_selectors4(Conv& c) {
    const uint2 v = lds64(c.lc + lane_v() * 8);
    c.pa = v.x; c.s2 = v.y;
}
__device__ __forceinline__ void conv_selectors8(Conv& c) { c.s8 = lds32(c.lc + 512 + lane_v() * 8); }
template <int G, int I0, int I1>
__device__ __forceinline__ void conv_load(const Conv& c, uint32_t (&q)[9]) {
    const int wq = c.warp & 3;
    if (G < 2) {
#pragma unroll
        for (int i = I0; i < I1; i++) q[i] = lds32(c.wa + G * 512 + i * 16);
    } else if (G < 4) {
        const uint32_t a = (G == 2 && wq == 0) ? c.wa + 1024 : c.pa + c.kw + wq * 128 + (G < 2 ? 0 : G - 2) * 512;
#pragma unroll
        for (int i = I0; i < I1; i++) q[i] = lds32(a + i * 16);
    } else {
        const uint4 u = lds128(c.kw + KW_H + (G < 4 ? 0 : G - 4) * 64 + wq * 16);
        const uint2 v = lds64(c.kw + KW_H + (G < 4 ? 0 : G - 4) * 64 + wq * 16 + 16);
        q[0] = u.x; q[1] = u.y; q[2] = u.z; q[3] = u.w; q[4] = v.x; q[5] = v.y;
        if (G == 4 && wq == 0) { q[6] = lds32(c.pa + c.kw + 1024); q[7] = lds32(c.pa + c.kw + 1040); }
    }
}
template <int G, int J0, int J1>
__device__ __forceinline__ void conv_frag(const Conv& c, const uint32_t (&q)[9], uint32_t* a, const Pk& dp) {
    const uint32_t dep = dp.w[0];
    if (G < 4) {
        const uint32_t s = (G < 2 || (G == 2 && (c.warp & 3) == 0)) ? c.id : c.s2;
#pragma unroll
        for (int j = J0; j < J1; j++) {
            uint32_t* o = a + 4 * (j - J0);
            o[0] = prmt_v(q[2 * j + 1], dp.w[0], s); o[1] = prmt_v(q[2 * j + 2], dp.w[1], s); o[2] = prmt_v(q[2 * j], dp.w[2], s); o[3] = prmt_v(q[2 * j + 1], dp.w[3], s);
        }
    } else {
        const uint32_t so = prmt_v(c.s8, dep, c.id), se = prmt_v(c.s8, dep, c.id + 0x22);
#pragma unroll
        for (int j = J0; j < J1; j++) {
            uint32_t* o = a + 4 * (j - J0);
            o[0] = prmt_v(q[j + 1], q[j + 2], se); o[1] = prmt_v(q[j + 1], q[j + 2], so); o[2] = prmt_v(q[j], q[j + 1], so);
            if (G == 4 && j == 0 && (c.warp & 3) == 0) {
                o[2] = prmt_v(q[6], dep, c.s2);
                o[0] = prmt_v(q[7], o[0], c.s2 >> 16);
            }
            o[3] = mov_v(o[0]);
        }
    }
}
template <int G, int J0, int J1>
__device__ __forceinline__ void conv_frag(const Conv& c, const uint32_t (&q)[9], uint32_t* a, float depf) {
    const uint32_t d = __float_as_uint(depf);
    conv_frag<G, J0, J1>(c, q, a, Pk{{d, d, d, d}});
}
template <int G, int T, int J0, int J1>
__device__ __forceinline__ void conv_mma(float (&acc)[16][4], const Conv& c, const uint32_t* a) {
#pragma unroll
    for (int j = J0; j < J1; j++) wg_mma<T>(acc, a + 4 * (j - J0), c.d0 - 8 * (2 * G - T) - j);
}
__device__ __forceinline__ float h_lo(uint32_t w) { return __half2float(__ushort_as_half((unsigned short)(w & 0xffffu))); }
__device__ __forceinline__ float h_hi(uint32_t w) { return __half2float(__ushort_as_half((unsigned short)(w >> 16))); }
__device__ __forceinline__ void flush_setup(Conv& c) {
    const uint2 v = lds64(c.lc + 256 + lane_v() * 8);
    c.fl = v.x; c.yo = v.y;
}
template <int Q>
__device__ __forceinline__ void flush_load(const Conv& c, uint32_t pl, uint2 (&f)[4]) {
#pragma unroll
    for (int w = 0; w < 4; w++) f[w] = lds64(c.fl + pl + (Q & 1) * 512 + w * (PLW_B - 64));
}
template <int Q>
__device__ __forceinline__ void flush_load_first(const Conv& c, uint32_t pl, uint2 (&f)[4], float depf) {
    const uint32_t p = prmt_v(c.fl, __float_as_uint(depf), c.id) + pl + (Q & 1) * 512;
#define LDV64(d, a) asm volatile("ld.volatile.shared.v2.u32 {%0,%1}, [%2];\n" : "=r"(d.x), "=r"(d.y) : "r"(a) : "memory")
    LDV64(f[0], p); LDV64(f[1], p + (PLW_B - 64)); LDV64(f[2], p + 2 * (PLW_B - 64)); LDV64(f[3], p + 3 * (PLW_B - 64));
}
#define FDEP __uint_as_float(f[3].y)
template <int Q, int mode>
__device__ __forceinline__ void conv_flush(const Conv& c, const uint2 (&f)[4], unsigned char* gy, uint32_t rx) {
    const uint32_t a0 = hadd2(f[0].x, f[1].x), a1 = hadd2(f[2].x, f[3].x), b0 = hadd2(f[0].y, f[1].y), b1 = hadd2(f[2].y, f[3].y);
    if (Q > 0 && mode == 1) {
        const uint32_t ra = rx + 16 + (Q > 0 ? Q - 1 : 0) * 1024 + (c.warp & 3) * 256 + lane_v() * 8;
        asm volatile("st.async.shared::cluster.mbarrier::complete_tx::bytes.v2.b32 [%0], {%1,%2}, [%3];\n"
                     ::"r"(ra ^ 0x1000000u), "r"(hadd2(a0, a1)), "r"(hadd2(b0, b1)), "r"((rx + (Q > 1 ? 8 : 0)) ^ 0x1000000u) : "memory");
        return;
    }
    float v0 = h_lo(a0) + h_lo(a1), v1 = h_hi(a0) + h_hi(a1), v2 = h_lo(b0) + h_lo(b1), v3 = h_hi(b0) + h_hi(b1);
    if (Q > 0 && mode == 2) {
        const uint2 o = lds64(rx + 16 + (Q > 0 ? Q - 1 : 0) * 1024 + (c.warp & 3) * 256 + lane_v() * 8);
        v0 += h_lo(o.x); v1 += h_hi(o.x); v2 += h_lo(o.y); v3 += h_hi(o.y);
    }
    const uint32_t lo = hmul2_bf(pack_bf16(v0, v1), c.fs), hi = hmul2_bf(pack_bf16(v2, v3), c.fs);
    stg64(gy + Q * 32 * DM * 32 + (c.yo + (Q < 2 ? c.yp : 0u)), nzw(lo), nzw(hi));
}
template <int I, bool S = false> struct IC { static constexpr int value = I; static constexpr bool shared = S; };
template <class T> __device__ constexpr bool wg_is4() { return T::shared; }
#define SLOT(n) (c.ps + (2 + ((n) & 7)) * 128)
#define GO() do { wg_commit(); __syncwarp(); } while (0)
#define DEP acc[15][3]
template <class FG, class FP, class FN>
__device__ __forceinline__ void conv_head(Conv& c, float (&acc)[16][4], uint32_t (&q)[9], uint32_t (&r)[9], uint32_t* a, FG fg, FP pre, FN next) {
    c.id = 0x3210u + (c.warp >> 8);
    pre();
    conv_load<0, 0, 9>(c, q);
    conv_frag<0, 0, 1>(c, q, a, 0.f);
    wg_fence(); wg_first<0>(acc, a, c.d0); GO();
    park(c.ps, Pk{{0u, 0u, 0u, 0u}});
    wg_wait0();
    conv_frag<0, 1, 2>(c, q, a, DEP);
    wg_fence(); conv_mma<0, 0, 1, 2>(acc, c, a); GO();
    fg(IC<0>());
    wg_wait0();
    conv_frag<0, 2, 3>(c, q, a, DEP);
    wg_fence(); conv_mma<0, 0, 2, 3>(acc, c, a); GO();
    conv_load<1, 0, 5>(c, r);
    wg_wait0();
    conv_frag<0, 3, 4>(c, q, a, DEP);
    wg_fence(); conv_mma<0, 0, 3, 4>(acc, c, a); GO();
    conv_load<1, 5, 9>(c, r);
    fg(IC<1>());
    wg_wait0();
    const Pk k = pk2(acc[0], acc[1]);
    conv_rename<2>(acc);
    conv_frag<1, 0, 2>(c, r, a, k);
    wg_fence(); conv_mma<1, 2, 0, 2>(acc, c, a); GO();
    park(SLOT(0), k);
    next(IC<0>());
    fg(IC<2>());
    wg_wait0();
    conv_frag<1, 2, 4>(c, r, a, DEP);
    wg_fence(); conv_mma<1, 2, 2, 4>(acc, c, a); GO();
    next(IC<1>());
    fg(IC<3>());
    wg_wait0();
}
template <class FG, class FP>
__device__ __forceinline__ void conv_run(Conv& c, uint32_t pl, unsigned char* gy, FG fg, FP pre) {
    float acc[16][4];
    uint32_t q[9], r[9], a[32];
    uint2 f[4];
    const int bid = 1 + (c.warp >> 2);
    conv_head(c, acc, q, r, a, fg, pre, [&](auto i) { if (decltype(i)::value == 0) conv_selectors4(c); else conv_load<2, 0, 9>(c, q); });
    Pk k = pk2(acc[2], acc[3]);
    conv_rename<4>(acc);
    conv_frag<2, 0, 4>(c, q, a, k);
    wg_fence(); conv_mma<2, 4, 0, 4>(acc, c, a); GO();
    park(SLOT(2), k);
    conv_load<3, 0, 9>(c, q);
    flush_setup(c);
    bar_sync(bid, 128);
    fg(IC<4>());
    wg_wait0();
    conv_rename<6>(acc);
    conv_frag<3, 0, 4>(c, q, a, DEP);
    wg_fence(); conv_mma<3, 6, 0, 4>(acc, c, a); GO();
    park(SLOT(4), pk2(acc[4], acc[5]));
    conv_load<4, 0, 9>(c, q);
    conv_selectors8(c);
    flush_load<0>(c, pl, f);
    conv_flush<0, 0>(c, f, gy, 0u);
    fg(IC<5>());
    wg_wait0();
    conv_rename<8>(acc);
    conv_frag<4, 0, 4>(c, q, a, DEP);
    wg_fence(); conv_mma<4, 8, 0, 4>(acc, c, a); GO();
    k = pk2(acc[6], acc[7]);
    park(SLOT(6), k);
    conv_load<5, 0, 9>(c, q);
    bar_sync(bid, 128);
    park(c.ps, k);
    fg(IC<6>());
    wg_wait0();
    conv_rename<10>(acc);
    flush_load_first<1>(c, pl, f, DEP);
    conv_frag<5, 0, 4>(c, q, a, FDEP);
    wg_fence(); conv_mma<5, 10, 0, 4>(acc, c, a); GO();
    park(SLOT(8), pk2(acc[8], acc[9]));
    conv_load<6, 0, 9>(c, q); conv_load<7, 0, 9>(c, r);
    conv_flush<1, 0>(c, f, gy, 0u);
    fg(IC<7>());
    wg_wait0();
    conv_rename<12>(acc);
    conv_frag<6, 0, 4>(c, q, a, DEP); conv_frag<7, 0, 4>(c, r, a + 16, DEP);
    wg_fence(); conv_mma<6, 12, 0, 4>(acc, c, a); conv_mma<7, 12, 0, 4>(acc, c, a + 16); GO();
    park(SLOT(10), pk2(acc[10], acc[11]));
    bar_sync(bid, 128);
    flush_load<2>(c, pl, f);
    conv_flush<2, 0>(c, f, gy, 0u);
    fg(IC<8>());
    if (c.id == 0) TRAP();
    wg_wait0();
    park(SLOT(12), pk2(acc[12], acc[13])); park(SLOT(14), pk2(acc[14], acc[15]));
    bar_sync(bid, 128);
    flush_load<3>(c, pl, f);
    conv_flush<3, 0>(c, f, gy, 0u);
}
template <class FG>
__device__ __forceinline__ void conv_outer(Conv& c, uint32_t pl, unsigned char* gy, uint32_t rx, FG fg) {
    float acc[16][4];
    uint32_t q[9], r[9], a[32];
    uint2 f[4], f2[4];
    const int bid = 1 + (c.warp >> 2);
    conv_head(c, acc, q, r, a, [&](auto gi) { if (decltype(gi)::value == 2) fg(IC<2, true>()); }, [&]() {}, [&](auto i) { if (decltype(i)::value == 0) conv_selectors8(c); else conv_load<6, 0, 9>(c, q); });
    park(SLOT(2), pk2(acc[2], acc[3])); park(SLOT(4), pk2(acc[4], acc[5]));
    const Pk k = pk2(acc[6], acc[7]);
    park(SLOT(6), k);
    conv_load<7, 0, 9>(c, r);
    conv_rename<12>(acc);
    conv_frag<6, 0, 4>(c, q, a, __uint_as_float(k.w[3])); conv_frag<7, 0, 4>(c, r, a + 16, __uint_as_float(k.w[3]));
    wg_fence(); conv_mma<6, 12, 0, 4>(acc, c, a); conv_mma<7, 12, 0, 4>(acc, c, a + 16); GO();
    flush_setup(c);
    bar_sync(bid, 128);
    flush_load<0>(c, pl, f); flush_load<1>(c, pl, f2);
    conv_flush<1, 1>(c, f2, gy, rx);
    conv_flush<0, 1>(c, f, gy, rx);
    wg_wait0();
    bar_sync(bid, 128);
    park(c.ps, k); park(SLOT(8), pk2(acc[8], acc[9])); park(SLOT(10), pk2(acc[10], acc[11]));
    park(SLOT(12), pk2(acc[12], acc[13])); park(SLOT(14), pk2(acc[14], acc[15]));
    bar_sync(bid, 128);
    flush_load<2>(c, pl, f); flush_load<3>(c, pl, f2);
    conv_flush<2, 1>(c, f, gy, rx);
    conv_flush<3, 1>(c, f2, gy, rx);
}
template <class FG>
__device__ __forceinline__ void conv_inner(Conv& c, uint32_t pl, unsigned char* gy, uint32_t rx, FG fg) {
    float acc[16][4];
    uint32_t q[9], a[16];
    uint2 f[4], f2[4];
    const int bid = 1 + (c.warp >> 2);
    c.id = 0x3210u + (c.warp >> 8);
    conv_selectors4(c);
    conv_load<2, 0, 9>(c, q);
    conv_frag<2, 0, 4>(c, q, a, 0.f);
    wg_fence(); wg_first<4>(acc, a, c.d0); conv_mma<2, 4, 1, 4>(acc, c, a + 4); GO();
    conv_load<3, 0, 9>(c, q);
    park(SLOT(2), Pk{{0u, 0u, 0u, 0u}});
    fg(IC<2, true>());
    wg_wait0();
    conv_rename<6>(acc);
    conv_frag<3, 0, 4>(c, q, a, DEP);
    wg_fence(); conv_mma<3, 6, 0, 4>(acc, c, a); GO();
    park(SLOT(4), pk2(acc[4], acc[5]));
    conv_load<4, 0, 9>(c, q);
    conv_selectors8(c);
    wg_wait0();
    conv_rename<8>(acc);
    conv_frag<4, 0, 4>(c, q, a, DEP);
    wg_fence(); conv_mma<4, 8, 0, 4>(acc, c, a); GO();
    const Pk k = pk2(acc[6], acc[7]);
    park(SLOT(6), k); park(c.ps, k);
    conv_load<5, 0, 9>(c, q);
    flush_setup(c);
    wg_wait0();
    conv_rename<10>(acc);
    conv_frag<5, 0, 4>(c, q, a, DEP);
    wg_fence(); conv_mma<5, 10, 0, 4>(acc, c, a); GO();
    park(SLOT(8), pk2(acc[8], acc[9]));
    bar_sync(bid, 128);
    flush_load<1>(c, pl, f);
    mbar_wait(rx);
    conv_flush<1, 2>(c, f, gy, rx);
    wg_wait0();
    bar_sync(bid, 128);
    park(SLOT(10), pk2(acc[10], acc[11])); park(SLOT(12), pk2(acc[12], acc[13])); park(SLOT(14), pk2(acc[14], acc[15]));
    bar_sync(bid, 128);
    flush_load<3>(c, pl, f); flush_load<2>(c, pl, f2);
    mbar_wait(rx + 8);
    conv_flush<3, 2>(c, f, gy, rx);
    conv_flush<2, 2>(c, f2, gy, rx);
}
#undef SLOT
#undef GO
#undef DEP
template <int U0, int U1>
__device__ __forceinline__ void weight_units(uint32_t sb, const CUtensorMap* tg, const CUtensorMap* tu, const CUtensorMap* td, bool w) {
    if (U1 > U0 && w && elect_one()) {
#pragma unroll
        for (int i = U0; i < U1; i++) {
            if (i < 12) tma_2d(sb + SM_WG + i * 6912, i < 6 ? tg : tu, 72 * (blockIdx.x >> 1), 288 * (blockIdx.x & 1) + (i % 6) * 48, sb + SM_MISC + 328);
            else tma_2d(sb + SM_WD + (i - 12) * 4736, td, 144 * (blockIdx.x & 1), 72 * (blockIdx.x >> 1) + 8 * (i - 12), sb + SM_MISC + 336);
        }
    }
}
#define WS 2110121111122004100
__device__ constexpr int wsched(int i) {
    unsigned long long v = WS;
    int n = 0;
    for (int k = 19; k >= 1; k--) { if (k < i) n += (int)(v % 10); v /= 10; }
    return n;
}
static_assert(wsched(20) == 21 && wsched(6) <= 7 && wsched(11) <= 12 && wsched(13) <= 14 && wsched(16) <= 17 && wsched(16) == wsched(15) && wsched(19) == 21, "");
#define WANY(i) (wsched((i) + 1) > wsched(i))
#define WPOINT(i, w) do { weight_units<wsched(i), wsched(i + 1)>(sb, &tm_g, &tm_u, &tm_d, w); } while (0)

__global__ void __launch_bounds__(NTHR, 1) __cluster_dims__(2, 1, 1)
fused_kernel(const Params p, const __grid_constant__ CUtensorMap tm_g, const __grid_constant__ CUtensorMap tm_u, const __grid_constant__ CUtensorMap tm_d, const __grid_constant__ CUtensorMap tm_x) {
    extern __shared__ __align__(1024) unsigned char smem[];
    const uint32_t sb = smem_u32(smem);
    const int tid = threadIdx.x, warp = __shfl_sync(0xffffffffu, tid >> 5, 0), lane = tid & 31;
    const int b = blockIdx.x, P = b >> 1, odd = b & 1;
    const int g = lane >> 2, t = lane & 3;
    const int wg = warp >> 2, t128 = tid & 127;
    const uint32_t s_stat = sb + SM_MISC;
    const uint32_t s_key = sb + SM_MISC + 128;
    const uint32_t s_rank = sb + SM_MISC + 256;
    const uint32_t s_k16 = sb + SM_MISC + 192;
    const uint32_t s_cnt = sb + SM_MISC + 320;
    const uint32_t bar_w = sb + SM_MISC + 328, bar_d = bar_w + 8, bar_g = bar_w + 16, bar_x = bar_w + 24, bar_v = bar_w + 32, bar_s = bar_w + 40, bar_h = bar_w + 48;
    STAMP(0);

    const int ch = wg < 4 ? 4 * b + wg : 512 + P;
    const uint32_t mo = tid < 512 ? 512 * b + tid : 65536 + 128 * P + t128, mq = (mo & ~127u) + 4 * lane;
    const uint32_t pl = ldo16(p.lar + mo), pa2 = ldo16(p.aim + mo), ldt = ldo16(p.ldt + (mo >> 7));
    const uint32_t pc = ldo16(p.cre + mo), pi = ldo16(p.cim + mo);
    const uint2 call_re = ldo64(p.cre + mq), call_im = ldo64(p.cim + mq);
    const uint32_t epl = ld_poll32(p.s->hint + (b & 7) * 32 + 1);
    if (wg < 4) {
        bar_arrive(0, NWRK);
        asm volatile("barrier.cluster.arrive.relaxed.aligned;\n" ::: "memory");
    } else {
        const int o = (4 * (warp & 3) + (g >> 1)) * 1152 + (g & 1) * 576 + t * 16;
        sts128(sb + SM_Z2 + t128 * 16, 0u, 0u, 0u, 0u); sts128(sb + SM_Z2 + 2048 + t128 * 16, 0u, 0u, 0u, 0u);
        if (warp == 16) sts128(sb + SM_Z2 + 4096 + lane * 16, 0u, 0u, 0u, 0u);
        fence_async();
        bar_sync(0, NWRK);
        STAMP(9);
#pragma unroll
        for (int c = 0; c < 9; c++)
            asm volatile("cp.async.cg.shared.global [%0], [%1], 16;\n" ::"r"(sb + SM_XT + o + c * 64), "l"(reinterpret_cast<const char*>(p.x) + b * 18432 + o + c * 64) : "memory");
        asm volatile("cp.async.commit_group;\n" ::: "memory");
        if (elect_one()) {
            mbar_init(bar_h + 8 * (warp & 3), 1);
            if (warp == 19) {
                mbar_init(bar_x, 1); mbar_init(bar_w, 1);
                mbar_expect(bar_x, 32768); mbar_expect(bar_w, 82944);
#pragma unroll
                for (int i = 2; i < 4; i++) bulk_s2g(reinterpret_cast<unsigned char*>(p.s->y) + 32 * i * 18432 + b * 4608, sb + SM_Z2, 4608);
            } else if (warp == 18) {
                mbar_init(bar_s, 1); mbar_init(bar_v, 2); mbar_init(bar_d, 1); mbar_init(bar_g, 1); mbar_init(sb + SM_RX, 1); mbar_init(sb + SM_RX + 8, 1);
                mbar_expect(bar_v, 2 * 1152); mbar_expect(bar_d, 72 * WD_PITCH); mbar_expect(bar_g, 4608); mbar_expect(sb + SM_RX, 1024); mbar_expect(sb + SM_RX + 8, 2048);
            }
            asm volatile("fence.mbarrier_init.release.cluster;\n" ::: "memory");
        }
        __syncwarp();
        asm volatile("barrier.cluster.arrive.relaxed.aligned;\n" ::: "memory");
        if (warp == 19) {
            asm volatile("barrier.cluster.wait.aligned;\n" ::: "memory");
            if (elect_one()) tma_4d_mc(sb + SM_XC + odd * 16384, &tm_x, 8 * P, 2 * odd, bar_x);
            __syncwarp();
        }
        {
            if (!(g & 1) && t == (g >> 1)) *reinterpret_cast<volatile uint32_t*>(p.s->stat + 16 * b + 4 * (warp & 3) + t) = 0u;
            if (warp < 18) {
                unsigned char* const ud = reinterpret_cast<unsigned char*>(p.s->uT) + (size_t)(8 * (warp & 1) + 2 * (g >> 1)) * 16384 + b * 128 + (g & 1) * 32 + t * 8;
#pragma unroll
                for (int k = 0; k < 4; k++) *reinterpret_cast<volatile unsigned long long*>(ud + (k >> 1) * 16384 + (k & 1) * 64) = 0ull;
            }
        }
    }
    const uint32_t kw = sb + SM_KW + wg * KW_B;
    const uint32_t tb = table_buf(sb, warp), t5 = sb + SM_WD + warp * 512;
    STAMP(29);
    const float dt = exp_bf(bf_lo(ldt));
    const uint32_t ep = __reduce_or_sync(0xffffffffu, epl);
    auto stats = [&]() {
        const int wq = warp & 3;
        const uint32_t xa = sb + SM_XT + (4 * wq + (g >> 1)) * 1152 + (g & 1) * 576 + t * 16;
        const bool own = !(g & 1) && t == (g >> 1);
        float d[4][4] = {};
        asm volatile("cp.async.wait_group 0;\n" ::: "memory");
        STAMP(26);
        uint4 v[9];
#pragma unroll
        for (int c = 0; c < 9; c++) v[c] = lds128(xa + c * 64);
#pragma unroll
        for (int c = 0; c < 9; c++) {
            mma_bf16(d[2 * (c & 1)], v[c].x, 0x3f803f80u, v[c].y, 0x3f803f80u, v[c].x, v[c].y);
            mma_bf16(d[2 * (c & 1) + 1], v[c].z, 0x3f803f80u, v[c].w, 0x3f803f80u, v[c].z, v[c].w);
        }
        STAMP(27);
        float sm = (g & 1) ? (d[0][3] + d[1][3]) + (d[2][3] + d[3][3]) : (d[0][2] + d[1][2]) + (d[2][2] + d[3][2]);
        float sq = (g & 1) ? (d[0][1] + d[1][1]) + (d[2][1] + d[3][1]) : (d[0][0] + d[1][0]) + (d[2][0] + d[3][0]);
        sm += __shfl_xor_sync(0xffffffffu, sm, 4); sq += __shfl_xor_sync(0xffffffffu, sq, 4);
        if (lane == 0) mbar_arrive(bar_h + 8 * wq);
        float mb, sd;
        ln_stats(sm, sq, mb, sd);
        if (own) p.s->stat[16 * b + 4 * wq + t] = (__float_as_uint(mb) >> 16) | (__float_as_uint(sd) & 0x7fff0000u) | (ep << 31);
        STAMPX(22);
        if (own) stat_store(s_stat + (2 * wq + (t & 1) + 8 * (t >> 1)) * 8, mb, rcp_approx(sd), 0u);
        if (wq == 3) asm volatile("cp.async.bulk.wait_group 0;\n" ::: "memory");
        bar_sync(5, 128);
        STAMP(28);
        uint32_t now;
        asm volatile("mov.u32 %0, %%clock;" : "=r"(now) :: "memory");
        if (wq == 2) {
            conv_constants(sb + SM_LC, lane);
            __syncwarp();
            if (lane < 8) p.s->key3[8 * b + lane] = ep & 1u;
            if (lane == 0) {
                sts64(s_cnt, now, ep);
                mbar_arrive(bar_s);
                bulk_g2s(sb + SM_XT + 16 * 1152, p.dsk, 1152, bar_v);
                bulk_g2s(sb + SM_XT + 17 * 1152, p.wr, 1152, bar_v);
            }
            __syncwarp();
        }
        WPOINT(1, wq == 3);
        if (wq < 2) {
            unsigned char* const ud = reinterpret_cast<unsigned char*>(p.s->uT) + (size_t)(8 * wq + 2 * (g >> 1)) * 16384 + b * 128 + (g & 1) * 32 + t * 8;
            const uint32_t utag = (ep % 7u + 1u) * 0x10001u;
            uint32_t U[2][4];
#pragma unroll
            for (int hf = 0; hf < 2; hf++) {
                const uint2 st = lds64(s_stat + (g + 8 * hf) * 8);
                const uint4 xu = lds128(sb + SM_XT + (TOK(g) + 2 * hf) * 1152 + warp * 64 + t * 16);
                const uint32_t X[4] = {xu.x, xu.y, xu.z, xu.w};
#pragma unroll
                for (int k = 0; k < 4; k++) {
                    const uint32_t u = ln_apply(X[k], STAT_M(st), STAT_H(st), STAT_L(st));
                    U[hf][k] = movm((pack_f16(bf_lo(u), bf_hi(u)) & 0xfff8fff8u) | utag);
                }
            }
#pragma unroll
            for (int k = 0; k < 4; k++) stg64(ud + (k >> 1) * 16384 + (k & 1) * 64, U[0][k], U[1][k]);
        }
    };
    STAMP(1);
    if (wg < 4) { STAMPX(16); }
    KGen kg;
    kgen_setup(kg, bf_lo(pl), bf_lo(pa2), dt);
    kgen_rows(kg, tb, lane);
    STAMP(2);
    const int E = min(max(c_exponent(call_re, call_im, dt) - 243, -120), 120);
    kgen_chain(kg, pc, pi, dt * __uint_as_float((uint32_t)(128 - E) << 23));
    STAMP(3);
    kgen_cols(kg, tb, t5, lane);
    STAMP(4);
    if (wg == 4) stats();
    if (warp != 19) asm volatile("barrier.cluster.wait.aligned;\n" ::: "memory");
    if (wg < 4) { STAMPX(17); }
    if (t128 < 2 * UPAD) sts128(sb + SM_U + wg * USLOT_B + (t128 & 1) * ULO_B + (t128 >> 1) * 16, 0u, 0u, 0u, 0u);
    if (t128 >= 124) sts128(kw + (t128 & 1) * 16 + (t128 & 2) * (KW_PL / 2), 0u, 0u, 0u, 0u);
    if (warp < 15) sts128(sb + SM_Z2 + 4608 + tid * 16, 0u, 0u, 0u, 0u);
    uint32_t co, cn, cd;
    combine_setup(sb, warp, lane, kw, co, cn, cd);
    co = pin(co); cn = pin(cn); cd = pin(cd);
    const uint4* const usrc = reinterpret_cast<const uint4*>(p.s->stat) + pin(wg < 4 ? tid : 512 + (P >> 2) * 1024 + (t128 >> 1) * 8 + (P & 3) * 2 + (t128 & 1));
    if (wg < 4) mbar_wait(bar_h + 8 * (warp & 3));
    if (wg < 4) { STAMPX(19); }
    uint32_t trel;
    asm volatile("mov.u32 %0, %%clock;" : "=r"(trel) :: "memory");
    kgen_mma(kg, tb, t5, lane);
    if (wg < 4) { STAMPX(20); }
    STAMP(5);
    uint4 uv0, uv1;
    auto first_poll = [&](uint32_t dly) {
        mbar_wait(bar_s);
        const uint32_t t0 = lds32(s_cnt);
        uint32_t now;
        do { asm volatile("mov.u32 %0, %%clock;" : "=r"(now) :: "memory"); } while (now - t0 < dly);
        uv0 = ld_poll(usrc);
    };
    if (wg == 4) { first_poll(UDLY); uv1 = ld_poll(usrc + 512); }
    WPOINT(2, warp == 19);
    auto stat_poll = [&]() {
        uint32_t now;
        do { asm volatile("mov.u32 %0, %%clock;" : "=r"(now) :: "memory"); } while (now - trel < SDLY);
        uv0 = ld_poll(usrc);
    };
    bar_sync(1 + wg, 128);
    if (wg < 4) { STAMPX(21); }
    kgen_combine(warp & 3, lane, co, cn, cd);
    STAMP(6);
    if (wg < 4) { STAMPX(18); }
    WPOINT(3, warp == 19);
    if (wg < 4) stat_poll();
    {
        const int wq = warp & 3;
        Conv c;
        const uint32_t pln = sb + SM_PL + wg * PL_B;
        const int e = g - 2 * t + 7;
        c.kw = kw; c.wa = pin(kw + ((e >> 2) & 1) * KW_PL + (8 * wq + (e >> 3)) * 16 + (e & 3) * 4);
        c.ps = mov_v(pln + wq * PLW_B + ((lane >> 3) & 1) * PL_HALF + ((lane >> 4) * 8 + (lane & 7)) * 16); c.warp = warp;
        c.lc = sb + SM_LC; c.fs = (uint32_t)(127 + E) * 0x800080u; c.yp = (ep & 1u) * (NCTA * 18432u);
        c.d0 = ((uint64_t)(ULO_B >> 4) << 16) | ((uint64_t)(128 >> 4) << 32) | (uint64_t)(((sb + SM_U + wg * USLOT_B + UPAD * 16) & 0x3FFFF) >> 4);
        unsigned char* gy = reinterpret_cast<unsigned char*>(p.s->y) + ((size_t)(4 * wq) * DM + ch) * 64;
        auto hook = [&](auto gi) {
                     constexpr int G = decltype(gi)::value;
                     if (G == (wg_is4<decltype(gi)>() ? 2 : 5)) asm volatile("barrier.cluster.wait.aligned;\n" ::: "memory");
                     if (!wg_is4<decltype(gi)>() && G == 1) mbar_wait(bar_s);
                     if (!wg_is4<decltype(gi)>() && (G == 0 || G == 2) && warp == HW && elect_one()) {
                         unsigned char* const sc = reinterpret_cast<unsigned char*>(p.s);
                         if (G == 0) {
                             if (b < 96) bulk_s2g_nc(sc + offsetof(Scratch, part) + b * 12288, sb + SM_Z2, 12288);
                             bulk_s2g(sc + offsetof(Scratch, rows) + (127 - b) * 4608, sb + SM_Z2, 4608);
                         }
                         if (G == 2) {
                             bulk_s2g(sc + offsetof(Scratch, y) + (NCTA * 18432u - c.yp) + b * 9216, sb + SM_Z2, 9216);
                         }
                     }
                     if (!wg_is4<decltype(gi)>()) WPOINT(6 + G, warp == (G >= 7 ? HW : 4 * (G % 3) + 1));
                     if (!wg_is4<decltype(gi)>() && G == 6 && warp == HW) {
                         asm volatile("cp.async.bulk.wait_group 0;\n" ::: "memory");
                         __syncwarp();
                         if (elect_one()) mbar_arrive(bar_v);
                     }
                 };
        if (wg < 4) {
            asm volatile("barrier.cluster.arrive.relaxed.aligned;\n" ::: "memory");
            conv_run(c, pln + wq * 128, gy, hook, [&]() {
                STAMPX(23);
                mbar_wait(bar_x);
                STAMPX(24);
                uint2 xc[4];
                uint32_t xw[4][2];
#pragma unroll
                for (int j = 0; j < 4; j++) xc[j] = lds64(sb + SM_XC + wg * 8192 + j * 2048 + t128 * 16 + odd * 8);
#pragma unroll
                for (int i = 0; i < 8; i++) {
                    const int k = i >> 1, h = i & 1;
                    xw[k][h] = prmt_v(k < 2 ? xc[2 * h].x : xc[2 * h].y, k < 2 ? xc[2 * h + 1].x : xc[2 * h + 1].y, (k & 1) ? 0x7632 : 0x5410);
                }
                const uint32_t ub = mov_v(sb + SM_U + UPAD * 16 + ((tid >> 1) & 1) * ULO_B + (tid >> 2) * 16 + (tid & 1) * 8), tag = ep << 31;
                int it = 0;
                while (min(min((int)(uv0.x ^ tag), (int)(uv0.y ^ tag)), min((int)(uv0.z ^ tag), (int)(uv0.w ^ tag))) < 0x10000) {
                    if (++it > SPIN_LIMIT) TRAP();
                    uv0 = ld_poll(usrc);
                }
                STAMP(8);
                STAMPX(26);
                const float r0 = rcp_approx(fabsf(bf_hi(uv0.x))), r1 = rcp_approx(fabsf(bf_hi(uv0.y))), r2 = rcp_approx(fabsf(bf_hi(uv0.z))), r3 = rcp_approx(fabsf(bf_hi(uv0.w)));
                const uint32_t m[2] = {__byte_perm(uv0.x, uv0.y, 0x5410), __byte_perm(uv0.z, uv0.w, 0x5410)};
                const uint32_t rh[2] = {pack_bf16(r0, r1), pack_bf16(r2, r3)};
                const uint32_t rl[2] = {pack_bf16(r0 - bf_lo(rh[0]), r1 - bf_hi(rh[0])), pack_bf16(r2 - bf_lo(rh[1]), r3 - bf_hi(rh[1]))};
#pragma unroll
                for (int k = 0; k < 4; k++) {
                    const uint32_t u0 = ln_apply(xw[k][0], m[0], rh[0], rl[0]), u1 = ln_apply(xw[k][1], m[1], rh[1], rl[1]);
                    sts64(ub + k * USLOT_B, pack_f16(bf_lo(u0), bf_hi(u0)), pack_f16(bf_lo(u1), bf_hi(u1)));
                }
                STAMPX(29);
                fence_async();
                bar_sync(14, 512);
                STAMP(7);
            });
        } else {
            auto stage = [&]() {
                const uint32_t tag = (ep % 7u + 1u) * 0x10001u;
                int it = 0;
                WPOINT(4, warp == 19);
                while (true) {
                    uv0.x ^= tag; uv0.y ^= tag; uv0.z ^= tag; uv0.w ^= tag; uv1.x ^= tag; uv1.y ^= tag; uv1.z ^= tag; uv1.w ^= tag;
                    if ((((uv0.x | uv0.y | uv0.z) | (uv0.w | uv1.x | uv1.y) | (uv1.z | uv1.w)) & 0x70007u) == 0) break;
                    if (++it > SPIN_LIMIT) TRAP();
                    uv0 = ld_poll(usrc); uv1 = ld_poll(usrc + 512);
                }
                STAMP(8);
                const uint32_t ub = sb + SM_U + UPAD * 16 + 4 * USLOT_B + (t128 & 1) * ULO_B + (t128 >> 1) * 16;
                sts128(ub, uv0.x, uv0.y, uv0.z, uv0.w);
                sts128(ub + 1024, uv1.x, uv1.y, uv1.z, uv1.w);
                fence_async();
                asm volatile("barrier.cluster.arrive.relaxed.aligned;\n" ::: "memory");
                bar_sync(5, 128);
                WPOINT(5, warp == 19);
                STAMP(7);
            };
            stage();
            if (odd) conv_inner(c, pln + wq * 128, gy, sb + SM_RX, hook);
            else conv_outer(c, pln + wq * 128, gy, sb + SM_RX, hook);
        }
        STAMP(10);
    }
    {
    const int lane = lane_v(), tid = 32 * warp + lane, g = lane >> 2, t = lane & 3;
    const uint32_t par = ~ep & 1u;
    bar_sync(0, NWRK);
    STAMP(11);
    uint32_t H[2][4] = {}, U2[2][4] = {};
    auto publish = [&](bool hi, int slot) {
        uint4* rowp = reinterpret_cast<uint4*>(p.s->rows) + slot * 144 + warp * 4 + t;
        stg128(rowp, nzw(hi ? U2[1][0] : U2[0][0]), nzw(hi ? U2[1][1] : U2[0][1]), nzw(hi ? U2[1][2] : U2[0][2]), nzw(hi ? U2[1][3] : U2[0][3]));
        stg128(rowp + 72, nzw(hi ? H[1][0] : H[0][0]), nzw(hi ? H[1][1] : H[0][1]), nzw(hi ? H[1][2] : H[0][2]), nzw(hi ? H[1][3] : H[0][3]));
    };
#define KTOK(k) (int)(((~(k) >> 5) & 0x7f0u) | (((k) >> 1) & 15u))
#define KLATE(k) (((k) & 0x1e0u) < 0xe0u)
#define KSLOT(k, s) (KLATE(k) ? 2 * NCTA + (s) : (int)(((k) >> 8) & 0xffu))
    const uint4* const rsrc = reinterpret_cast<const uint4*>(p.s->rows) + 36 * odd;
    auto gather = [&](uint32_t mine) {
        int it = 0;
        uint32_t mn;
        do {
            mn = 1;
#pragma unroll 1
            for (int r = 0; r < 9; r++) {
                const uint32_t k = __shfl_sync(0xffffffffu, mine, r < 8 ? 4 * r : lane);
                const int row = r < 8 ? r : g, c = r < 8 ? lane : 32 + t;
                asm volatile("cp.async.cg.shared.global [%0], [%1], 16;\n" ::"r"(sb + SM_XS + row * XS_PITCH + c * 16), "l"(rsrc + KSLOT(k, row) * 144 + c) : "memory");
            }
            asm volatile("cp.async.wait_all;\n" ::: "memory");
#pragma unroll 1
            for (int r = 0; r < 9; r++) mn = min(mn, min4(lds128(sb + SM_XS + (r < 8 ? r * XS_PITCH + lane * 16 : g * XS_PITCH + (32 + t) * 16))));
            if (++it > SPIN_LIMIT) TRAP();
        } while (__any_sync(0xffffffffu, mn == 0));
    };
    auto late_rows = [&](auto role) {
        if (decltype(role)::value == 1) {
            int it = 0;
            uint4 k[8];
            uint32_t bad;
            do {
                bad = 0;
#pragma unroll
                for (int i = 0; i < 8; i++) k[i] = ld_poll(reinterpret_cast<const uint4*>(p.s->key) + 32 * i + lane);
#pragma unroll
                for (int i = 0; i < 8; i++) bad = or3(bad, xor_or(k[i].x, k[i].y, par), xor_or(k[i].z, k[i].w, par));
                if (++it > SPIN_LIMIT) TRAP();
            } while (__any_sync(0xffffffffu, bad & 1u));
#pragma unroll 1
            for (int r = 0; r < 8; r++) {
                uint32_t c = 0;
#pragma unroll
                for (int i = 0; i < 8; i++) c = max(c, k[i].x);
                const uint32_t m = __reduce_max_sync(0xffffffffu, c);
#pragma unroll
                for (int i = 0; i < 8; i++) if (k[i].x == m) k[i] = make_uint4(k[i].y, k[i].z, k[i].w, 0u);
                if (lane == 0) sts32(s_key + r * 4, m);
            }
        }
        bar_sync(0, NWRK);
        const uint32_t kk = lds32(s_key + (lane & 7) * 4), ep = lds32(s_cnt + 4);
        const bool own = KLATE(kk) && (KTOK(kk) >> 4) == b;
        uint32_t todo = __ballot_sync(0xffffffffu, own) & 0xffu;
        if (decltype(role)::value == 0 && todo) {
#pragma unroll
            for (int hf = 0; hf < 2; hf++) {
                const uint4 h = lds128(sb + SM_U + hf * 9216 + tid * 16);
                const uint2 st = lds64(s_stat + (g + 8 * hf) * 8);
                H[hf][0] = h.x; H[hf][1] = h.y; H[hf][2] = h.z; H[hf][3] = h.w;
#pragma unroll
                for (int k = 0; k < 4; k++) U2[hf][k] = ln_apply(H[hf][k], STAT_M(st), STAT_H(st), STAT_L(st));
            }
#pragma unroll 1
            while (todo) {
                const int s = __ffs(todo) - 1, tk = KTOK(__shfl_sync(0xffffffffu, kk, s));
                todo &= todo - 1;
                if ((tk & 13) == TOK(g)) publish(tk & 2, 2 * NCTA + s);
            }
            __threadfence();
        }
        bar_sync(0, NWRK);
        if (decltype(role)::value == 1) {
            if (lane < NSEL && own) *reinterpret_cast<volatile unsigned*>(p.s->flag + lane) = ep + 1u;
            int it = 0;
            while (__any_sync(0xffffffffu, KLATE(kk) && ld_acquire32(p.s->flag + (lane & 7)) != ep + 1u)) { if (++it > SPIN_LIMIT) TRAP(); }
            gather(__shfl_sync(0xffffffffu, kk, g));
        }
        bar_sync(0, NWRK);
    };
    if (warp < 18) {
        const unsigned char* ys = reinterpret_cast<const unsigned char*>(p.s->y) + (b < 64 ? (par ^ 1u) * (NCTA * 18432u) : 0u) +
                                  ((P * DM + 32 * warp + 8 * (g >> 1) + (g & 1)) * 64 + odd * 32 + t * 8);
        mbar_wait(bar_v);
        const uint32_t xa = sb + SM_XT + warp * 64 + t * 16;
        const uint4 x0 = lds128(xa + TOK(g) * 1152), x1 = lds128(xa + (TOK(g) + 2) * 1152), dk = lds128(xa + 16 * 1152);
        uint4 wr = make_uint4(0u, 0u, 0u, 0u);
        if (g == 0) wr = lds128(xa + 17 * 1152);
        uint2 yv[4];
        const uint32_t Z[2][4] = {{x0.x, x0.y, x0.z, x0.w}, {x1.x, x1.y, x1.z, x1.w}}, D4[4] = {dk.x, dk.y, dk.z, dk.w};
#pragma unroll
        for (int hf = 0; hf < 2; hf++) {
            const uint2 st = lds64(s_stat + (g + 8 * hf) * 8);
#pragma unroll
            for (int k = 0; k < 4; k++) U2[hf][k] = hmul2_bf(ln_apply(Z[hf][k], STAT_M(st), STAT_H(st), STAT_L(st)), D4[k]);
        }
        const uint32_t la = pin(sb + SM_LNP + (g * 20 + warp) * 4);
        {
            const unsigned char* y1 = ys + (U2[0][0] & U2[1][2] & (warp >> 8));
#pragma unroll
            for (int k = 0; k < 4; k++) yv[k] = ld_poll64(y1 + k * 128);
        }
        int it = 0;
        float d[2][4];
        while (true) {
            const uint32_t mn = min3(min3(yv[0].x, yv[0].y, yv[1].x), min3(yv[1].y, yv[2].x, yv[2].y), min(yv[3].x, yv[3].y));
#pragma unroll
            for (int k = 0; k < 4; k++) {
                H[0][k] = hadd2_bf(Z[0][k], hadd2_bf(movm(yv[k].x), U2[0][k]));
                H[1][k] = hadd2_bf(Z[1][k], hadd2_bf(movm(yv[k].y), U2[1][k]));
            }
            ln_partial(H, d);
            if (!__any_sync(0xffffffffu, mn == 0)) break;
            if (++it > SPIN_LIMIT) TRAP();
#pragma unroll
            for (int k = 0; k < 4; k++) yv[k] = ld_poll64(ys + k * 128);
        }
        STAMP(12);
        {
            const float s0 = (g & 1) ? d[0][3] : d[0][2], s1 = (g & 1) ? d[1][3] : d[1][2];
            const float q0 = (g & 1) ? d[0][1] : d[0][0], q1 = (g & 1) ? d[1][1] : d[1][0];
            asm volatile("{\n.reg .pred p;\nsetp.eq.u32 p, %5, %6;\n@p st.shared.f32 [%0], %1;\n@p st.shared.f32 [%0 + 640], %2;\n@p st.shared.f32 [%0 + 1280], %3;\n@p st.shared.f32 [%0 + 1920], %4;\n}\n"
                         ::"r"(la), "f"(s0), "f"(s1), "f"(q0), "f"(q1), "r"(t), "r"(g >> 1) : "memory");
        }
        bar_arrive(6, NWRK);
        STAMP(13);
        bar_sync(7, 608);
        STAMP(14);
#pragma unroll
        for (int hf = 0; hf < 2; hf++) {
            const uint2 st = lds64(s_stat + (g + 8 * hf) * 8);
#pragma unroll
            for (int k = 0; k < 4; k++) U2[hf][k] = ln_apply(H[hf][k], STAT_M(st), STAT_H(st), STAT_L(st));
        }
        {
            float cs[4] = {0.f, 0.f, 0.f, 0.f};
            mma_bf16(cs, U2[0][0], U2[1][0], U2[0][1], U2[1][1], wr.x, wr.y);
            mma_bf16(cs, U2[0][2], U2[1][2], U2[0][3], U2[1][3], wr.z, wr.w);
            if (t == 0) { stsf(la + 32 * 80, cs[0]); stsf(la + 40 * 80, cs[2]); }
            bar_arrive(8, 608);
        }
        FIX((uint32_t)warp >> 8);
        uint32_t O[2][4];
#pragma unroll
        for (int hf = 0; hf < 2; hf++)
#pragma unroll
            for (int k = 0; k < 4; k++) { O[hf][k] = hadd2_bf(H[hf][k], U2[hf][k]); H[hf][k] = nzw(H[hf][k]); U2[hf][k] = nzw(U2[hf][k]); }
        unsigned char* rowp = reinterpret_cast<unsigned char*>(p.s->rows) + ((254 - 2 * b) * 2304 + warp * 64 + t * 16);
        FIX(and3(and3(and3(H[0][0], H[0][1], H[0][2]), and3(H[0][3], H[1][0], H[1][1]), and3(H[1][2], H[1][3], U2[0][0])),
                 and3(and3(U2[0][1], U2[0][2], U2[0][3]), and3(U2[1][0], U2[1][1], U2[1][2]), U2[1][3]), (uint32_t)reinterpret_cast<uint64_t>(rowp)));
        bar_sync(9, 608);
        {
            const uint2 best = lds64(s_rank);
#pragma unroll
            for (int hf = 0; hf < 2; hf++) {
                const uint32_t me = 2 * TOK(g) + 4 * hf;
                unsigned char* d = rowp + (best.x == me ? 2304 : 0);
                if (best.x == me || best.y == me) {
                    stg128(d, U2[hf][0], U2[hf][1], U2[hf][2], U2[hf][3]);
                    stg128(d + 1152, H[hf][0], H[hf][1], H[hf][2], H[hf][3]);
                }
            }
        }
        FIX((uint32_t)warp >> 9);
#pragma unroll
        for (int hf = 0; hf < 2; hf++) {
            sts128(sb + SM_OUT + (TOK(g) + 2 * hf) * (DM * 2) + warp * 64 + t * 16, O[hf][0], O[hf][1], O[hf][2], O[hf][3]);
            sts128(sb + SM_U + hf * 9216 + tid * 16, H[hf][0], H[hf][1], H[hf][2], H[hf][3]);
        }
        STAMP(15);
        const int mi = lane >> 3, rr = lane & 7;
        const bool gate = warp < 12 && (warp & 3) != 2;
        const int fj = gate ? 3 * (warp >> 2) + min(warp & 3, 2) : (warp < 12 ? warp >> 2 : warp - 9);
        if (gate) {
            uint32_t W[18][4];
            mbar_wait(bar_w);
            const uint32_t aad = sb + SM_WG + (mi & 1) * SM_WU + (rr + 8 * (mi >> 1)) * W_PITCH + fj * 16;
            const uint32_t bad = pin(sb + SM_XS + rr * XS_PITCH + mi * 16);
            bool rare = warp >> 8;
#pragma unroll 1
            do {
                if (rare) late_rows(IC<0>());
#pragma unroll
                for (int k = 0; k < 18; k++) ldsm_x4_t(W[k][0], W[k][1], W[k][2], W[k][3], aad + k * 16 * W_PITCH);
                if (rare) break;
                fence_async();
                STAMP2(17);
                rare = bar_or(11, NWRK, false);
            } while (rare);
            STAMP2(19);
            float c4[2][4] = {};
#pragma unroll
            for (int k = 0; k < 18; k += 2) {
                uint32_t b0, b1, b2, b3;
                ldsm_x4(b0, b1, b2, b3, bad + k * 32);
                mma_bf16(c4[0], W[k][0], W[k][1], W[k][2], W[k][3], b0, b1);
                mma_bf16(c4[1], W[k + 1][0], W[k + 1][1], W[k + 1][2], W[k + 1][3], b2, b3);
            }
            const uint32_t ex = sb + SM_EX + (32 * fj + lane) * 16;
            const float e0 = c4[0][0] + c4[1][0], e1 = c4[0][1] + c4[1][1], e2 = c4[0][2] + c4[1][2], e3 = c4[0][3] + c4[1][3];
            asm volatile("st.async.shared::cluster.mbarrier::complete_tx::bytes.v4.f32 [%0], {%1,%2,%3,%4}, [%5];\n"
                         ::"r"(ex ^ 0x1000000u), "f"(e0), "f"(e1), "f"(e2), "f"(e3), "r"(bar_g ^ 0x1000000u) : "memory");
            STAMP2(20);
            mbar_wait(bar_g);
            const uint4 o = lds128(ex);
            const uint32_t G = pack_bf16(e0 + __uint_as_float(o.x), e1 + __uint_as_float(o.y)), U = pack_bf16(e2 + __uint_as_float(o.z), e3 + __uint_as_float(o.w));
            sts32(sb + SM_GU + (32 * fj + lane) * 4, hmul2_bf(pack_bf16(bf_lo(G) * sigmoid_f(bf_lo(G)), bf_hi(G) * sigmoid_f(bf_hi(G))), U));
            bar_arrive(13, NWRK);
        } else {
            uint32_t W[2][18];
            auto load_wd = [&]() {
                mbar_wait(bar_d);
                const uint32_t base = sb + SM_WD + (4 * fj + (mi & 1)) * 16 + rr * WD_PITCH;
#pragma unroll
                for (int j = 0; j < 2; j++) {
#pragma unroll
                    for (int k = 0; k < 4; k++) ldsm_x4_t(W[j][4 * k], W[j][4 * k + 1], W[j][4 * k + 2], W[j][4 * k + 3], base + j * 32 + (k * 16 + 8 * (mi >> 1)) * WD_PITCH);
                    ldsm_x2_t(W[j][16], W[j][17], base + j * 32 + 64 * WD_PITCH);
                }
            };
            const uint32_t po = pin((((8 * (18 * odd + 2 * fj) + g) * 64 + P) * 16 + t * 4) * 4);
            fence_async();
            STAMP2(17);
            if (bar_or(11, NWRK, false)) late_rows(IC<0>());
            delay(DDLY); load_wd();
            bar_sync(13, NWRK);
            STAMP2(21);
            uint32_t gb[9];
            ldsm_x4_t(gb[0], gb[1], gb[2], gb[3], sb + SM_GU + lane * 16);
            ldsm_x4_t(gb[4], gb[5], gb[6], gb[7], sb + SM_GU + 512 + lane * 16);
            ldsm_x1_t(gb[8], sb + SM_GU + 1024 + lane * 16);
            float c4[2][4] = {}, d4[2][4] = {};
#pragma unroll
            for (int k = 0; k < 4; k += 2)
#pragma unroll
                for (int j = 0; j < 2; j++) {
                    mma_bf16(c4[j], W[j][4 * k], W[j][4 * k + 1], W[j][4 * k + 2], W[j][4 * k + 3], gb[2 * k], gb[2 * k + 1]);
                    mma_bf16(d4[j], W[j][4 * k + 4], W[j][4 * k + 5], W[j][4 * k + 6], W[j][4 * k + 7], gb[2 * k + 2], gb[2 * k + 3]);
                }
#pragma unroll
            for (int j = 0; j < 2; j++) mma_bf16_k8(c4[j], W[j][16], W[j][17], gb[8]);
#pragma unroll
            for (int j = 0; j < 2; j++)
                stg128(reinterpret_cast<unsigned char*>(p.s->part) + po + j * 32768, __float_as_uint(c4[j][0] + d4[j][0]) | 1u, __float_as_uint(c4[j][1] + d4[j][1]) | 1u,
                       __float_as_uint(c4[j][2] + d4[j][2]) | 1u, __float_as_uint(c4[j][3] + d4[j][3]) | 1u);
        }
        STAMP2(22);
    } else if (warp == 18) {
        const uint4* const ksrc = reinterpret_cast<const uint4*>(p.s->key3) + pin(2 * lane);
        const int row = (g >> 1) + 4 * (g & 1);
        const uint32_t ro = pin(640 * odd + t * 16), xd = pin(sb + SM_XS + row * XS_PITCH + t * 16 + (odd ? 0 : 512));
        const uint32_t xe = pin(sb + SM_XS + (g >> 1) * XS_PITCH + (lane & 7) * 16 + 64 * odd);
        const uint32_t sa = pin(sb + SM_LNP + lane * 80);
        const uint32_t klo = pin((uint32_t)(127 - b) << 9 | (uint32_t)(15 - ROWTOK(lane & 15)) << 1 | par), ra = pin(sb + SM_LNP + (32 + (lane & 15)) * 80);
        uint4* const kdst = reinterpret_cast<uint4*>(p.s->key3) + pin((lane >> 1) * 2 * NCTA + 2 * b + (lane & 1));
        FIX(ra);
        bar_sync(6, NWRK);
        {
            float mb, rc;
            ln_finish(sum18(sa), lane, mb, rc);
            if (lane < 16) stat_store(s_stat + lane * 8, mb, rc, 0u);
        }
        bar_arrive(7, 608);
        bar_sync(8, 608);
        uint32_t t0;
        {
            const uint32_t bits = __float_as_uint(rbf(sum18(ra)));
            const uint32_t me = ((bits ^ ((uint32_t)((int)bits >> 31) | 0x80000000u)) & 0xffff0000u) | klo;
            const uint32_t k0 = __reduce_max_sync(0xffffffffu, me), k1 = __reduce_max_sync(0xffffffffu, me == k0 ? 0u : me);
            const uint32_t k2 = __reduce_max_sync(0xffffffffu, me >= k1 ? 0u : me);
            if (lane < 2) stg128(kdst, k0 ^ 0x11eu, k1 ^ 0xfeu, k2 ^ 0xdeu, par);
            asm volatile("mov.u32 %0, %%clock;" : "=r"(t0) :: "memory");
            STAMPW(23);
            if (lane == 0) sts64(s_rank, ~k0 & 30u, ~k1 & 30u);
            bar_arrive(9, 608);
            sts32(s_k16 + (lane & 15) * 4, me);
            __syncwarp();
            const uint4 v = lds128(s_k16 + (lane & 16) * 2), w = lds128(s_k16 + (lane & 16) * 2 + 16);
            int rank = ((v.x > me) + (v.y > me)) + ((v.z > me) + (v.w > me)) + (((w.x > me) + (w.y > me)) + ((w.z > me) + (w.w > me)));
            rank += __shfl_xor_sync(0xffffffffu, rank, 16);
            if (lane < 16 && rank < 8) p.s->key[8 * b + rank] = (me ^ 0x1eu) | ((8 - rank) << 5);
        }
        uint4 kq[4];
        uint32_t u[4], mine = 0, m;
        int it = 0;
        { uint32_t now; do { asm volatile("mov.u32 %0, %%clock;" : "=r"(now) :: "memory"); } while (now - t0 < KDLY); }
        do {
#pragma unroll
            for (int i = 0; i < 4; i++) kq[i] = ld_poll(ksrc + 64 * i);
            if (++it > SPIN_LIMIT) TRAP();
            uint32_t S[2][4];
#pragma unroll
            for (int i = 0; i < 2; i++) {
                const uint4 &c = kq[2 * i], &d = kq[2 * i + 1];
                const uint32_t m1 = min(c.x, d.x), m2 = max(c.y, d.y);
                S[i][0] = max(c.x, d.x); S[i][1] = max(m1, m2); S[i][2] = min(m1, m2); S[i][3] = min(c.y, d.y);
            }
            const uint32_t a0 = max(S[0][0], S[1][3]), a1 = max(S[0][1], S[1][2]), a2 = max(S[0][2], S[1][1]), a3 = max(S[0][3], S[1][0]);
            const uint32_t b0 = max(a0, a2), b2 = min(a0, a2), b1 = max(a1, a3), b3 = min(a1, a3);
            u[0] = max(b0, b1); u[1] = min(b0, b1); u[2] = max(b2, b3); u[3] = min(b2, b3);
            const uint32_t bad = or3(or3(xor_or(kq[0].x, kq[0].y, par), xor_or(kq[0].z, kq[1].x, par), xor_or(kq[1].y, kq[1].z, par)),
                                     xor_or(kq[2].x, kq[2].y, par), xor_or(kq[2].z, kq[3].x, par)) | xor_or(kq[3].y, kq[3].z, par);
            m = __reduce_max_sync(0xffffffffu, u[0] | (uint32_t)((int)(bad << 31) >> 31));
        } while (m == 0xffffffffu);
        STAMPW(16);
#pragma unroll
        for (int r = 0; r < 8; r++) {
            if (r) m = __reduce_max_sync(0xffffffffu, u[0]);
            if (u[0] == m) { u[0] = u[1]; u[1] = u[2]; u[2] = u[3]; u[3] = 0; }
            if (row == r) mine = m;
        }
        uint4 v[9];
        const uint32_t o0 = __byte_perm(mine, 0, 0x4441) * 2304u, o1 = __shfl_xor_sync(0xffffffffu, o0, 4);
        const unsigned char* const rA = reinterpret_cast<const unsigned char*>(p.s->rows) + (((g & 1) ? o1 : o0) + ro + (g & 1) * 64);
        const unsigned char* const rb = reinterpret_cast<const unsigned char*>(p.s->rows) + (((g & 1) ? o0 : o1) + ro + (g & 1) * 64);
        const unsigned char* const rc = reinterpret_cast<const unsigned char*>(p.s->rows) + (o0 + ro + (odd ? -64 : 512));
#pragma unroll
        for (int i = 0; i < 4; i++) { v[i] = ld_poll(rA + i * 128); v[4 + i] = ld_poll(rb + i * 128); }
        v[8] = ld_poll(rc);
        const bool again = u[0] == 0 || max(max(kq[0].z, kq[1].z), max(kq[2].z, kq[3].z)) > m;
        if (t == 0) sts32(s_key + row * 4, mine);
#pragma unroll
        for (int i = 0; i < 9; i++) sts128(i < 8 ? xe + (i >> 2) * 4 * XS_PITCH + (i & 3) * 128 : xd, v[i].x, v[i].y, v[i].z, v[i].w);
        uint32_t mn, m3[3];
        m3[0] = m3[1] = m3[2] = 1u;
#pragma unroll
        for (int i = 0; i < 9; i++) m3[i % 3] = min3(min3(m3[i % 3], v[i].x, v[i].y), v[i].z, v[i].w);
        mn = min3(m3[0], m3[1], m3[2]);
        STAMPW(18);
        if (bar_or(11, NWRK, again || mn == 0)) late_rows(IC<1>());
    } else {
        bar_sync(6, NWRK);
        WPOINT(16, true);
        if (WANY(17) || WANY(18)) delay(WDLY);
        WPOINT(17, true);
        if (WANY(18)) delay(WDLY);
        WPOINT(18, true);
        if (bar_or(11, NWRK, false)) late_rows(IC<2>());
        const int tk = KTOK(lds32(s_key + (lane & 7) * 4));
        const uint32_t sel = __reduce_or_sync(0xffffffffu, (tk >> 4) == b ? 1u << (tk & 15) : 0u);
        if (sel ? lane < 16 && !((sel >> lane) & 1u) : lane == 0) bulk_s2g(p.out + (size_t)(16 * b + lane) * DM, sb + SM_OUT + lane * (DM * 2), sel ? DM * 2 : 16 * DM * 2);
        __syncwarp();
    }
    if (warp == 8 || warp >= 18) {
        const int grp = 3 * b + (warp == 8 ? 0 : warp - 17), fsl = 2 * t + ((lane >> 3) & 1), fc = 16 * (grp >> 3) + (grp & 7) + 8 * (lane >> 4);
        const uint32_t fk = lds32(s_key + fsl * 4);
        float hv = 0.f, u2 = 0.f;
        int it = 0;
        if (b < 96) {
            const uint32_t* const fsrc = p.s->rows + KSLOT(fk, fsl) * DM + (fc >> 1);
            uint32_t hw, uw;
            do { hw = ld_poll32(fsrc + 288); uw = ld_poll32(fsrc); if (++it > SPIN_LIMIT) TRAP(); } while (!hw || !uw);
            hv = (fc & 1) ? bf_hi(hw) : bf_lo(hw); u2 = (fc & 1) ? bf_hi(uw) : bf_lo(uw);
        }
        const float rs = rbf(sigmoid_f(__uint_as_float((fk ^ ((uint32_t)((int)~fk >> 31) | 0x80000000u)) & 0xffff0000u)));
        const uint32_t dof = pin(KTOK(fk) * DM + fc), so = pin(grp * 256 + lane);
        if (warp > 17) bar_sync(13, NWRK);
        if (b < 96) {
            delay(warp > 17 ? FDLY : FDLY2);
            const uint4* src = reinterpret_cast<const uint4*>(p.s->part) + so;
            float s0, s1, s2, s3;
            uint32_t ok;
            do {
                uint4 a[8];
#pragma unroll
                for (int i = 0; i < 8; i++) a[i] = ld_poll(src + 32 * i);
                if (++it > SPIN_LIMIT) TRAP();
#define A4(i) and3(and3(a[i].x, a[i].y, a[i].z), and3(a[i].w, a[i + 1].x, a[i + 1].y), a[i + 1].z & a[i + 1].w)
#define S8(f) (((__uint_as_float(a[0].f) + __uint_as_float(a[1].f)) + (__uint_as_float(a[2].f) + __uint_as_float(a[3].f))) + \
               ((__uint_as_float(a[4].f) + __uint_as_float(a[5].f)) + (__uint_as_float(a[6].f) + __uint_as_float(a[7].f))))
                ok = and3(A4(0), A4(2), and3(A4(4), A4(6), 1u));
                s0 = S8(x); s1 = S8(y); s2 = S8(z); s3 = S8(w);
                asm volatile("" : "+f"(s0), "+f"(s1), "+f"(s2), "+f"(s3));
#undef A4
#undef S8
            } while (__any_sync(0xffffffffu, !ok));
            STAMP2(24);
            const bool up = lane & 16, od = lane & 8;
            const float r0 = (up ? s2 : s0) + __shfl_xor_sync(0xffffffffu, up ? s0 : s2, 16), r1 = (up ? s3 : s1) + __shfl_xor_sync(0xffffffffu, up ? s1 : s3, 16);
            float y = (od ? r1 : r0) + __shfl_xor_sync(0xffffffffu, od ? r0 : r1, 8);
            y += __shfl_xor_sync(0xffffffffu, y, 4);
            p.out[dof] = __float2bfloat16_rn(hv + rbf(u2 + rbf(rbf(y) * rs)));
        }
    }
    if (warp == 19) asm volatile("cp.async.bulk.wait_group.read 0;\n" ::: "memory");
    if (b == 0 && tid < 8) *reinterpret_cast<volatile unsigned*>(p.s->hint + tid * 32 + 1) = lds32(s_cnt + 4) + 1u;
    STAMP(25);
    }
}

typedef CUresult (*PFN_tmEncode)(CUtensorMap*, CUtensorMapDataType, cuuint32_t, void*, const cuuint64_t*, const cuuint64_t*, const cuuint32_t*,
                                 const cuuint32_t*, CUtensorMapInterleave, CUtensorMapSwizzle, CUtensorMapL2promotion, CUtensorMapFloatOOBfill);

extern "C" void kernel_launch(void* const* d_in, const int* in_sizes, int n_in, void* d_out, int out_size) {
    Params p;
    p.x = (const bf16*)d_in[0];
    p.lar = (const bf16*)d_in[1];
    p.aim = (const bf16*)d_in[2];
    p.cre = (const bf16*)d_in[3];
    p.cim = (const bf16*)d_in[4];
    p.ldt = (const bf16*)d_in[5];
    p.dsk = (const bf16*)d_in[6];
    p.wr = (const bf16*)d_in[8];
    p.out = (bf16*)d_out;
    static PFN_tmEncode enc = nullptr;
    static void* scratch = nullptr;
    if (!enc) {
        cudaFuncSetAttribute(fused_kernel, cudaFuncAttributeMaxDynamicSharedMemorySize, SMEM_TOTAL);
        void* fn = nullptr;
        cudaDriverEntryPointQueryResult qr;
        cudaGetDriverEntryPoint("cuTensorMapEncodeTiled", &fn, cudaEnableDefault, &qr);
        enc = (PFN_tmEncode)fn;
        cudaGetSymbolAddress(&scratch, g_scratch);
    }
    p.s = (Scratch*)scratch;
    CUtensorMap tm_g, tm_u, tm_d, tm_x;
    const cuuint64_t dims[2] = {FF, DM}, strides[1] = {FF * 2};
    const cuuint32_t box[2] = {72, 48}, es[2] = {1, 1};
    enc(&tm_g, CU_TENSOR_MAP_DATA_TYPE_BFLOAT16, 2, d_in[9], dims, strides, box, es, CU_TENSOR_MAP_INTERLEAVE_NONE, CU_TENSOR_MAP_SWIZZLE_NONE,
        CU_TENSOR_MAP_L2_PROMOTION_NONE, CU_TENSOR_MAP_FLOAT_OOB_FILL_NONE);
    enc(&tm_u, CU_TENSOR_MAP_DATA_TYPE_BFLOAT16, 2, d_in[10], dims, strides, box, es, CU_TENSOR_MAP_INTERLEAVE_NONE, CU_TENSOR_MAP_SWIZZLE_NONE,
        CU_TENSOR_MAP_L2_PROMOTION_NONE, CU_TENSOR_MAP_FLOAT_OOB_FILL_NONE);
    const cuuint64_t ddims[2] = {DM / 2, FF}, dstrides[1] = {DM * 2};
    const cuuint32_t dbox[2] = {WD_PITCH / 4, 8};
    enc(&tm_d, CU_TENSOR_MAP_DATA_TYPE_UINT32, 2, d_in[11], ddims, dstrides, dbox, es, CU_TENSOR_MAP_INTERLEAVE_NONE, CU_TENSOR_MAP_SWIZZLE_NONE,
        CU_TENSOR_MAP_L2_PROMOTION_L2_128B, CU_TENSOR_MAP_FLOAT_OOB_FILL_NONE);
    const cuuint64_t xdims[4] = {DM, 128, 4, 4}, xstrides[3] = {DM * 8, DM * 2, DM * 1024};
    const cuuint32_t xbox[4] = {8, 128, 4, 2}, xes[4] = {1, 1, 1, 1};
    enc(&tm_x, CU_TENSOR_MAP_DATA_TYPE_BFLOAT16, 4, d_in[0], xdims, xstrides, xbox, xes, CU_TENSOR_MAP_INTERLEAVE_NONE, CU_TENSOR_MAP_SWIZZLE_NONE,
        CU_TENSOR_MAP_L2_PROMOTION_NONE, CU_TENSOR_MAP_FLOAT_OOB_FILL_NONE);
    fused_kernel<<<NCTA, NTHR, SMEM_TOTAL>>>(p, tm_g, tm_u, tm_d, tm_x);
}
```

```cpp
#include <cuda_runtime.h>
#include <cuda.h>
#include <cuda_fp16.h>
#include <cuda_bf16.h>
#include <stdint.h>

#define LSEQ 2048
#define DM 576
#define NST 128
#define FF 4608
#define NSEL 8
#define NCTA 128
#define NTHR 640
#define NWRK 640

typedef __nv_bfloat16 bf16;

#define SM_WG 0
#define SM_WU 41472
#define SM_XC (82944 - 32768)
#define SM_WD 82944
#define W_PITCH 144
#define WD_PITCH 592
#define SM_Z2 (SM_WD + 10240)
#define SM_XT (SM_PL - 18 * 1152)
#define SM_PL (SM_WD + 46080)
#define PL_HALF 1344
#define PLW_B 2624
#define PL_B (4 * PLW_B)
#define SM_U (SM_PL + 5 * PL_B)
#define UPAD 20
#define ULO_B ((UPAD + 128) * 16)
#define USLOT_B (2 * ULO_B)
#define SM_KW (SM_U + 5 * USLOT_B)
#define KW_B 3712
#define KW_PL 1216
#define KW_P 2400
#define KW_H 3440
#define SM_MISC (SM_KW + 5 * KW_B)
#define SM_LC (SM_MISC + 416)
#define SM_LNP (SM_LC + 768)
#define SM_RX (SM_LNP + 3840)
#define SMEM_TOTAL (SM_RX + 3088)
#define TBW PLW_B
#define SM_OUT SM_PL
#define SM_XS (SM_PL + 18432)
#define XS_PITCH 592
#define SM_GU (SM_PL + 23296)
#define SM_EX (SM_PL + 24576)

struct __align__(128) Scratch {
    unsigned hint[8 * 32];
    unsigned flag[32];
    uint32_t key3[NCTA * 8];
    uint32_t key[NCTA * 8];
    uint32_t stat[LSEQ];
    uint32_t uT[64 * (LSEQ / 2)];
    uint32_t y[(NCTA + 96) * DM * 8];
    uint32_t part[288 * 64 * 8];
    uint32_t rows[(2 * NCTA + NSEL) * DM];
};
__device__ Scratch g_scratch;
#define STAMP(i)
#define STAMPX(i)
#define STAMPY(i)

__device__ __forceinline__ float rbf(float x) {
    uint32_t r;
    asm("cvt.rn.bf16x2.f32 %0, %1, %2;\n" : "=r"(r) : "f"(x), "f"(0.f));
    return __uint_as_float(r);
}
__device__ __forceinline__ uint32_t pack_bf16(float lo, float hi) {
    uint32_t r;
    asm("cvt.rn.bf16x2.f32 %0, %1, %2;\n" : "=r"(r) : "f"(hi), "f"(lo));
    return r;
}
__device__ __forceinline__ uint32_t pack_f16(float lo, float hi) {
    uint32_t r;
    asm("cvt.rn.f16x2.f32 %0, %1, %2;\n" : "=r"(r) : "f"(hi), "f"(lo));
    return r;
}
__device__ __forceinline__ float bf_lo(uint32_t w) { return __uint_as_float(w << 16); }
__device__ __forceinline__ float bf_hi(uint32_t w) { return __uint_as_float(w & 0xffff0000u); }
__device__ __forceinline__ uint32_t hadd2_bf(uint32_t a, uint32_t b) {
    __nv_bfloat162 r = __hadd2_rn(*reinterpret_cast<__nv_bfloat162*>(&a), *reinterpret_cast<__nv_bfloat162*>(&b));
    return *reinterpret_cast<uint32_t*>(&r);
}
__device__ __forceinline__ uint32_t hsub2_bf(uint32_t a, uint32_t b) {
    __nv_bfloat162 r = __hsub2_rn(*reinterpret_cast<__nv_bfloat162*>(&a), *reinterpret_cast<__nv_bfloat162*>(&b));
    return *reinterpret_cast<uint32_t*>(&r);
}
__device__ __forceinline__ uint32_t hmul2_bf(uint32_t a, uint32_t b) {
    __nv_bfloat162 r = __hmul2_rn(*reinterpret_cast<__nv_bfloat162*>(&a), *reinterpret_cast<__nv_bfloat162*>(&b));
    return *reinterpret_cast<uint32_t*>(&r);
}
__device__ __forceinline__ uint32_t hfma2_bf(uint32_t a, uint32_t b, uint32_t c) { uint32_t r; asm("fma.rn.bf16x2 %0, %1, %2, %3;\n" : "=r"(r) : "r"(a), "r"(b), "r"(c)); return r; }
__device__ __forceinline__ uint32_t hmul2(uint32_t a, uint32_t b) { uint32_t r; asm("mul.rn.f16x2 %0, %1, %2;\n" : "=r"(r) : "r"(a), "r"(b)); return r; }
__device__ __forceinline__ uint32_t hadd2(uint32_t a, uint32_t b) { uint32_t r; asm("add.rn.f16x2 %0, %1, %2;\n" : "=r"(r) : "r"(a), "r"(b)); return r; }
__device__ __forceinline__ uint32_t hfma2(uint32_t a, uint32_t b, uint32_t c) { uint32_t r; asm("fma.rn.f16x2 %0, %1, %2, %3;\n" : "=r"(r) : "r"(a), "r"(b), "r"(c)); return r; }
__device__ __forceinline__ uint32_t hfms2(uint32_t a, uint32_t b, uint32_t c) {
    uint32_t r;
    asm("{\n.reg .b32 n;\nneg.f16x2 n, %2;\nfma.rn.f16x2 %0, %1, n, %3;\n}\n" : "=r"(r) : "r"(a), "r"(b), "r"(c));
    return r;
}
__device__ __forceinline__ uint32_t nzw(uint32_t w) { uint32_t r; asm("max.u32 %0, %1, 1;\n" : "=r"(r) : "r"(w)); return r; }
__device__ __forceinline__ uint32_t smem_u32(const void* p) { return (uint32_t)__cvta_generic_to_shared(p); }
__device__ __forceinline__ uint32_t lds32(uint32_t addr) {
    uint32_t v;
    asm volatile("ld.shared.u32 %0, [%1];\n" : "=r"(v) : "r"(addr) : "memory");
    return v;
}
__device__ __forceinline__ uint32_t lds16(uint32_t addr) {
    unsigned short v;
    asm volatile("ld.shared.u16 %0, [%1];\n" : "=h"(v) : "r"(addr) : "memory");
    return v;
}
__device__ __forceinline__ uint2 lds64(uint32_t addr) {
    uint2 v;
    asm volatile("ld.shared.v2.u32 {%0,%1}, [%2];\n" : "=r"(v.x), "=r"(v.y) : "r"(addr) : "memory");
    return v;
}
__device__ __forceinline__ uint4 lds128(uint32_t addr) {
    uint4 v;
    asm volatile("ld.shared.v4.u32 {%0,%1,%2,%3}, [%4];\n" : "=r"(v.x), "=r"(v.y), "=r"(v.z), "=r"(v.w) : "r"(addr) : "memory");
    return v;
}
__device__ __forceinline__ void sts32(uint32_t addr, uint32_t v) { asm volatile("st.shared.u32 [%0], %1;\n" ::"r"(addr), "r"(v) : "memory"); }
__device__ __forceinline__ void sts16(uint32_t addr, uint32_t v) { asm volatile("st.shared.u16 [%0], %1;\n" ::"r"(addr), "h"((unsigned short)v) : "memory"); }
__device__ __forceinline__ void stsf(uint32_t addr, float v) { sts32(addr, __float_as_uint(v)); }
__device__ __forceinline__ void sts64(uint32_t addr, uint32_t a, uint32_t b) { asm volatile("st.shared.v2.u32 [%0], {%1,%2};\n" ::"r"(addr), "r"(a), "r"(b) : "memory"); }
__device__ __forceinline__ void sts128(uint32_t addr, uint32_t a, uint32_t b, uint32_t c, uint32_t d) {
    asm volatile("st.shared.v4.u32 [%0], {%1,%2,%3,%4};\n" ::"r"(addr), "r"(a), "r"(b), "r"(c), "r"(d) : "memory");
}
__device__ __forceinline__ void ldsm_x4(uint32_t& r0, uint32_t& r1, uint32_t& r2, uint32_t& r3, uint32_t addr) {
    asm volatile("ldmatrix.sync.aligned.m8n8.x4.shared.b16 {%0,%1,%2,%3}, [%4];\n"
                 : "=r"(r0), "=r"(r1), "=r"(r2), "=r"(r3) : "r"(addr) : "memory");
}
__device__ __forceinline__ void ldsm_x4_t(uint32_t& r0, uint32_t& r1, uint32_t& r2, uint32_t& r3, uint32_t addr) {
    asm volatile("ldmatrix.sync.aligned.m8n8.x4.trans.shared.b16 {%0,%1,%2,%3}, [%4];\n"
                 : "=r"(r0), "=r"(r1), "=r"(r2), "=r"(r3) : "r"(addr) : "memory");
}
__device__ __forceinline__ void ldsm_x2_t(uint32_t& r0, uint32_t& r1, uint32_t addr) {
    asm volatile("ldmatrix.sync.aligned.m8n8.x2.trans.shared.b16 {%0,%1}, [%2];\n" : "=r"(r0), "=r"(r1) : "r"(addr) : "memory");
}
__device__ __forceinline__ void ldsm_x1_t(uint32_t& r0, uint32_t addr) {
    asm volatile("ldmatrix.sync.aligned.m8n8.x1.trans.shared.b16 {%0}, [%1];\n" : "=r"(r0) : "r"(addr) : "memory");
}
__device__ __forceinline__ void stsm_x4(uint32_t addr, uint32_t r0, uint32_t r1, uint32_t r2, uint32_t r3) {
    asm volatile("stmatrix.sync.aligned.m8n8.x4.shared.b16 [%0], {%1,%2,%3,%4};\n" ::"r"(addr), "r"(r0), "r"(r1), "r"(r2), "r"(r3) : "memory");
}
__device__ __forceinline__ void stsm_x4_t(uint32_t addr, uint32_t r0, uint32_t r1, uint32_t r2, uint32_t r3) {
    asm volatile("stmatrix.sync.aligned.m8n8.x4.trans.shared.b16 [%0], {%1,%2,%3,%4};\n" ::"r"(addr), "r"(r0), "r"(r1), "r"(r2), "r"(r3) : "memory");
}
__device__ __forceinline__ uint32_t movm(uint32_t a) {
    uint32_t d;
    asm volatile("movmatrix.sync.aligned.m8n8.trans.b16 %0, %1;\n" : "=r"(d) : "r"(a));
    return d;
}
__device__ __forceinline__ void mma_f16(float (&c)[4], uint32_t a0, uint32_t a1, uint32_t a2, uint32_t a3, uint32_t b0, uint32_t b1) {
    asm volatile(
        "mma.sync.aligned.m16n8k16.row.col.f32.f16.f16.f32 {%0,%1,%2,%3}, {%4,%5,%6,%7}, {%8,%9}, {%0,%1,%2,%3};\n"
        : "+f"(c[0]), "+f"(c[1]), "+f"(c[2]), "+f"(c[3])
        : "r"(a0), "r"(a1), "r"(a2), "r"(a3), "r"(b0), "r"(b1));
}
__device__ __forceinline__ void mma_bf16(float (&c)[4], uint32_t a0, uint32_t a1, uint32_t a2, uint32_t a3, uint32_t b0, uint32_t b1) {
    asm volatile(
        "mma.sync.aligned.m16n8k16.row.col.f32.bf16.bf16.f32 {%0,%1,%2,%3}, {%4,%5,%6,%7}, {%8,%9}, {%0,%1,%2,%3};\n"
        : "+f"(c[0]), "+f"(c[1]), "+f"(c[2]), "+f"(c[3])
        : "r"(a0), "r"(a1), "r"(a2), "r"(a3), "r"(b0), "r"(b1));
}
__device__ __forceinline__ void mma_bf16_k8(float (&c)[4], uint32_t a0, uint32_t a1, uint32_t b0) {
    asm volatile("mma.sync.aligned.m16n8k8.row.col.f32.bf16.bf16.f32 {%0,%1,%2,%3}, {%4,%5}, {%6}, {%0,%1,%2,%3};\n"
                 : "+f"(c[0]), "+f"(c[1]), "+f"(c[2]), "+f"(c[3]) : "r"(a0), "r"(a1), "r"(b0));
}
__device__ __forceinline__ void bar_sync(int id, int n) { asm volatile("bar.sync %0, %1;\n" ::"r"(id), "r"(n) : "memory"); }
__device__ __forceinline__ void bar_arrive(int id, int n) { asm volatile("bar.arrive %0, %1;\n" ::"r"(id), "r"(n) : "memory"); }
__device__ __forceinline__ bool bar_or(int id, int n, bool v) {
    uint32_t r;
    asm volatile("{\n.reg .pred p, q;\nsetp.ne.u32 p, %3, 0;\nbar.red.or.pred q, %1, %2, p;\nselp.u32 %0, 1, 0, q;\n}\n" : "=r"(r) : "r"(id), "r"(n), "r"((uint32_t)v) : "memory");
    return r;
}
__device__ __forceinline__ uint32_t and3(uint32_t a, uint32_t b, uint32_t c) { uint32_t r; asm("lop3.b32 %0, %1, %2, %3, 0x80;\n" : "=r"(r) : "r"(a), "r"(b), "r"(c)); return r; }
__device__ __forceinline__ uint32_t or3(uint32_t a, uint32_t b, uint32_t c) { uint32_t r; asm("lop3.b32 %0, %1, %2, %3, 0xfe;\n" : "=r"(r) : "r"(a), "r"(b), "r"(c)); return r; }
__device__ __forceinline__ uint32_t min3(uint32_t a, uint32_t b, uint32_t c) { uint32_t r; asm("{\n.reg .u32 t;\nmin.u32 t, %2, %3;\nmin.u32 %0, %1, t;\n}\n" : "=r"(r) : "r"(a), "r"(b), "r"(c)); return r; }
__device__ __forceinline__ uint32_t xor_or(uint32_t a, uint32_t b, uint32_t c) { uint32_t r; asm("lop3.b32 %0, %1, %2, %3, 0x7e;\n" : "=r"(r) : "r"(a), "r"(b), "r"(c)); return r; }
__device__ __forceinline__ uint32_t pin(uint32_t v) { uint32_t r; asm volatile("shfl.sync.bfly.b32 %0, %1, 0, 0x1f, 0xffffffff;\n" : "=r"(r) : "r"(v) : "memory"); return r; }
__device__ __forceinline__ uint4 ld_poll(const void* p) {
    uint4 v;
    asm volatile("ld.relaxed.gpu.global.v4.u32 {%0,%1,%2,%3}, [%4];\n" : "=r"(v.x), "=r"(v.y), "=r"(v.z), "=r"(v.w) : "l"(p) : "memory");
    return v;
}
__device__ __forceinline__ uint2 ld_poll64(const void* p) {
    uint2 v;
    asm volatile("ld.relaxed.gpu.global.v2.u32 {%0,%1}, [%2];\n" : "=r"(v.x), "=r"(v.y) : "l"(p) : "memory");
    return v;
}
__device__ __forceinline__ uint32_t ld_poll32(const void* p) {
    uint32_t v;
    asm volatile("ld.relaxed.gpu.global.u32 %0, [%1];\n" : "=r"(v) : "l"(p) : "memory");
    return v;
}
__device__ __forceinline__ uint32_t ld_acquire32(const void* p) {
    uint32_t v;
    asm volatile("ld.acquire.gpu.global.u32 %0, [%1];\n" : "=r"(v) : "l"(p) : "memory");
    return v;
}
__device__ __forceinline__ uint2 ldo64(const void* p) {
    uint2 v;
    asm volatile("ld.relaxed.cta.global.v2.u32 {%0,%1}, [%2];\n" : "=r"(v.x), "=r"(v.y) : "l"(p) : "memory");
    return v;
}
__device__ __forceinline__ uint32_t ldo16(const void* p) {
    uint32_t v;
    asm volatile("ld.relaxed.cta.global.u16 %0, [%1];\n" : "=r"(v) : "l"(p) : "memory");
    return v;
}
__device__ __forceinline__ void stg128(void* p, uint32_t a, uint32_t b, uint32_t c, uint32_t d) {
    asm volatile("st.global.v4.u32 [%0], {%1,%2,%3,%4};\n" ::"l"(p), "r"(a), "r"(b), "r"(c), "r"(d) : "memory");
}
__device__ __forceinline__ void stg64(void* p, uint32_t a, uint32_t b) { asm volatile("st.global.v2.u32 [%0], {%1,%2};\n" ::"l"(p), "r"(a), "r"(b) : "memory"); }
__device__ __forceinline__ uint32_t min4(const uint4& v) { return min(min(v.x, v.y), min(v.z, v.w)); }
#define SPIN_LIMIT (1 << 21)
#define TRAP() __trap()
__device__ __forceinline__ void mbar_init(uint32_t bar, uint32_t cnt) { asm volatile("mbarrier.init.shared::cta.b64 [%0], %1;\n" ::"r"(bar), "r"(cnt) : "memory"); }
__device__ __forceinline__ void mbar_expect(uint32_t bar, uint32_t bytes) {
    asm volatile("mbarrier.arrive.expect_tx.shared::cta.b64 _, [%0], %1;\n" ::"r"(bar), "r"(bytes) : "memory");
}
__device__ __forceinline__ void mbar_arrive(uint32_t bar) { asm volatile("mbarrier.arrive.shared::cta.b64 _, [%0];\n" ::"r"(bar) : "memory"); }
__device__ __forceinline__ void mbar_wait(uint32_t bar) {
    asm volatile(
        "{\n.reg .pred p;\n"
        "W_%=:\n"
        "mbarrier.try_wait.parity.shared::cta.b64 p, [%0], 0;\n"
        "@!p bra W_%=;\n}\n" ::"r"(bar) : "memory");
}
__device__ __forceinline__ void bulk_g2s(uint32_t dst, const void* src, uint32_t bytes, uint32_t bar) {
    asm volatile("cp.async.bulk.shared::cluster.global.mbarrier::complete_tx::bytes [%0], [%1], %2, [%3];\n" ::"r"(dst), "l"(src), "r"(bytes), "r"(bar) : "memory");
}
__device__ __forceinline__ void bulk_s2g(void* dst, uint32_t src, uint32_t bytes) {
    asm volatile("cp.async.bulk.global.shared::cta.bulk_group [%0], [%1], %2;\ncp.async.bulk.commit_group;\n" ::"l"(dst), "r"(src), "r"(bytes) : "memory");
}
__device__ __forceinline__ void bulk_s2g_nc(void* dst, uint32_t src, uint32_t bytes) {
    asm volatile("cp.async.bulk.global.shared::cta.bulk_group [%0], [%1], %2;\n" ::"l"(dst), "r"(src), "r"(bytes) : "memory");
}
__device__ __forceinline__ void tma_2d(uint32_t dst, const CUtensorMap* tm, int c0, int c1, uint32_t bar) {
    asm volatile("cp.async.bulk.tensor.2d.shared::cluster.global.mbarrier::complete_tx::bytes [%0], [%1, {%3, %4}], [%2];\n"
                 ::"r"(dst), "l"(tm), "r"(bar), "r"(c0), "r"(c1) : "memory");
}
__device__ __forceinline__ void tma_4d_mc(uint32_t dst, const CUtensorMap* tm, int c0, int c3, uint32_t bar) {
    asm volatile("cp.async.bulk.tensor.4d.shared::cluster.global.mbarrier::complete_tx::bytes.multicast::cluster [%0], [%1, {%3, %4, %4, %5}], [%2], %6;\n"
                 ::"r"(dst), "l"(tm), "r"(bar), "r"(c0), "r"(0), "r"(c3), "h"((unsigned short)3) : "memory");
}
__device__ __forceinline__ bool elect_one() {
    uint32_t r;
    asm volatile("{\n.reg .pred p;\nelect.sync _|p, 0xffffffff;\nselp.u32 %0, 1, 0, p;\n}\n" : "=r"(r));
    return r;
}
__device__ __forceinline__ void delay(uint32_t clks) {
    uint32_t t0, t1;
    asm volatile("mov.u32 %0, %%clock;" : "=r"(t0) :: "memory");
    do { asm volatile("mov.u32 %0, %%clock;" : "=r"(t1) :: "memory"); } while (t1 - t0 < clks);
}
__device__ __forceinline__ void fence_async() { asm volatile("fence.proxy.async.shared::cta;\n" ::: "memory"); }

__device__ __forceinline__ float2 cmul(float2 a, float2 b) {
    return make_float2(fmaf(a.x, b.x, -a.y * b.y), fmaf(a.x, b.y, a.y * b.x));
}
__device__ __forceinline__ float2 csq(float2 a) {
    float p = a.x * a.y;
    return make_float2(fmaf(a.x, a.x, -a.y * a.y), p + p);
}
__device__ __forceinline__ float ex2_approx(float x) { float r; asm("ex2.approx.ftz.f32 %0, %1;\n" : "=f"(r) : "f"(x)); return r; }
__device__ __forceinline__ float exp_bf(float x) { return rbf(ex2_approx(__fmul_ru(x, 1.4426950408889634f))); }
__device__ __forceinline__ float2 cexp_e(float lr2, float li, float e) {
    const float m = ex2_approx(lr2 * e);
    return make_float2(m * __cosf(li * e), m * __sinf(li * e));
}
__device__ __forceinline__ float rcp_approx(float x) { float r; asm("rcp.approx.ftz.f32 %0, %1;\n" : "=f"(r) : "f"(x)); return r; }
__device__ __forceinline__ float sigmoid_f(float x) { return rcp_approx(1.0f + ex2_approx(x * -1.4426950408889634f)); }
__device__ __forceinline__ float sqrt_approx(float x) { float r; asm("sqrt.approx.ftz.f32 %0, %1;\n" : "=f"(r) : "f"(x)); return r; }

__device__ __forceinline__ void wg_fence() { asm volatile("wgmma.fence.sync.aligned;\n" ::: "memory"); }
__device__ __forceinline__ void wg_commit() { asm volatile("wgmma.commit_group.sync.aligned;\n" ::: "memory"); }
__device__ __forceinline__ void wg_wait0() { asm volatile("wgmma.wait_group.sync.aligned 0;\n" ::: "memory"); }
template <int T> __device__ __forceinline__ void wg_mma(float (&acc)[16][4], const uint32_t* a, uint64_t desc);
template <int T> __device__ __forceinline__ void wg_first(float (&acc)[16][4], const uint32_t* a, uint64_t desc);
template <> __device__ __forceinline__ void wg_mma<0>(float (&acc)[16][4], const uint32_t* a, uint64_t desc) {
    asm volatile("wgmma.mma_async.sync.aligned.m64n128k16.f32.f16.f16 {%0,%1,%2,%3,%4,%5,%6,%7,%8,%9,%10,%11,%12,%13,%14,%15,%16,%17,%18,%19,%20,%21,%22,%23,%24,%25,%26,%27,%28,%29,%30,%31,%32,%33,%34,%35,%36,%37,%38,%39,%40,%41,%42,%43,%44,%45,%46,%47,%48,%49,%50,%51,%52,%53,%54,%55,%56,%57,%58,%59,%60,%61,%62,%63}, {%64,%65,%66,%67}, %68, 1, 1, 1, 0;\n"
                 : "+f"(acc[0][0]), "+f"(acc[0][1]), "+f"(acc[0][2]), "+f"(acc[0][3]), "+f"(acc[1][0]), "+f"(acc[1][1]), "+f"(acc[1][2]), "+f"(acc[1][3]), "+f"(acc[2][0]), "+f"(acc[2][1]), "+f"(acc[2][2]), "+f"(acc[2][3]), "+f"(acc[3][0]), "+f"(acc[3][1]), "+f"(acc[3][2]), "+f"(acc[3][3]), "+f"(acc[4][0]), "+f"(acc[4][1]), "+f"(acc[4][2]), "+f"(acc[4][3]), "+f"(acc[5][0]), "+f"(acc[5][1]), "+f"(acc[5][2]), "+f"(acc[5][3]), "+f"(acc[6][0]), "+f"(acc[6][1]), "+f"(acc[6][2]), "+f"(acc[6][3]), "+f"(acc[7][0]), "+f"(acc[7][1]), "+f"(acc[7][2]), "+f"(acc[7][3]), "+f"(acc[8][0]), "+f"(acc[8][1]), "+f"(acc[8][2]), "+f"(acc[8][3]), "+f"(acc[9][0]), "+f"(acc[9][1]), "+f"(acc[9][2]), "+f"(acc[9][3]), "+f"(acc[10][0]), "+f"(acc[10][1]), "+f"(acc[10][2]), "+f"(acc[10][3]), "+f"(acc[11][0]), "+f"(acc[11][1]), "+f"(acc[11][2]), "+f"(acc[11][3]), "+f"(acc[12][0]), "+f"(acc[12][1]), "+f"(acc[12][2]), "+f"(acc[12][3]), "+f"(acc[13][0]), "+f"(acc[13][1]), "+f"(acc[13][2]), "+f"(acc[13][3]), "+f"(acc[14][0]), "+f"(acc[14][1]), "+f"(acc[14][2]), "+f"(acc[14][3]), "+f"(acc[15][0]), "+f"(acc[15][1]), "+f"(acc[15][2]), "+f"(acc[15][3])
                 : "r"(a[0]), "r"(a[1]), "r"(a[2]), "r"(a[3]), "l"(desc));
}
template <> __device__ __forceinline__ void wg_mma<2>(float (&acc)[16][4], const uint32_t* a, uint64_t desc) {
    asm volatile("wgmma.mma_async.sync.aligned.m64n112k16.f32.f16.f16 {%0,%1,%2,%3,%4,%5,%6,%7,%8,%9,%10,%11,%12,%13,%14,%15,%16,%17,%18,%19,%20,%21,%22,%23,%24,%25,%26,%27,%28,%29,%30,%31,%32,%33,%34,%35,%36,%37,%38,%39,%40,%41,%42,%43,%44,%45,%46,%47,%48,%49,%50,%51,%52,%53,%54,%55}, {%56,%57,%58,%59}, %60, 1, 1, 1, 0;\n"
                 : "+f"(acc[2][0]), "+f"(acc[2][1]), "+f"(acc[2][2]), "+f"(acc[2][3]), "+f"(acc[3][0]), "+f"(acc[3][1]), "+f"(acc[3][2]), "+f"(acc[3][3]), "+f"(acc[4][0]), "+f"(acc[4][1]), "+f"(acc[4][2]), "+f"(acc[4][3]), "+f"(acc[5][0]), "+f"(acc[5][1]), "+f"(acc[5][2]), "+f"(acc[5][3]), "+f"(acc[6][0]), "+f"(acc[6][1]), "+f"(acc[6][2]), "+f"(acc[6][3]), "+f"(acc[7][0]), "+f"(acc[7][1]), "+f"(acc[7][2]), "+f"(acc[7][3]), "+f"(acc[8][0]), "+f"(acc[8][1]), "+f"(acc[8][2]), "+f"(acc[8][3]), "+f"(acc[9][0]), "+f"(acc[9][1]), "+f"(acc[9][2]), "+f"(acc[9][3]), "+f"(acc[10][0]), "+f"(acc[10][1]), "+f"(acc[10][2]), "+f"(acc[10][3]), "+f"(acc[11][0]), "+f"(acc[11][1]), "+f"(acc[11][2]), "+f"(acc[11][3]), "+f"(acc[12][0]), "+f"(acc[12][1]), "+f"(acc[12][2]), "+f"(acc[12][3]), "+f"(acc[13][0]), "+f"(acc[13][1]), "+f"(acc[13][2]), "+f"(acc[13][3]), "+f"(acc[14][0]), "+f"(acc[14][1]), "+f"(acc[14][2]), "+f"(acc[14][3]), "+f"(acc[15][0]), "+f"(acc[15][1]), "+f"(acc[15][2]), "+f"(acc[15][3])
                 : "r"(a[0]), "r"(a[1]), "r"(a[2]), "r"(a[3]), "l"(desc));
}
template <> __device__ __forceinline__ void wg_mma<4>(float (&acc)[16][4], const uint32_t* a, uint64_t desc) {
    asm volatile("wgmma.mma_async.sync.aligned.m64n96k16.f32.f16.f16 {%0,%1,%2,%3,%4,%5,%6,%7,%8,%9,%10,%11,%12,%13,%14,%15,%16,%17,%18,%19,%20,%21,%22,%23,%24,%25,%26,%27,%28,%29,%30,%31,%32,%33,%34,%35,%36,%37,%38,%39,%40,%41,%42,%43,%44,%45,%46,%47}, {%48,%49,%50,%51}, %52, 1, 1, 1, 0;\n"
                 : "+f"(acc[4][0]), "+f"(acc[4][1]), "+f"(acc[4][2]), "+f"(acc[4][3]), "+f"(acc[5][0]), "+f"(acc[5][1]), "+f"(acc[5][2]), "+f"(acc[5][3]), "+f"(acc[6][0]), "+f"(acc[6][1]), "+f"(acc[6][2]), "+f"(acc[6][3]), "+f"(acc[7][0]), "+f"(acc[7][1]), "+f"(acc[7][2]), "+f"(acc[7][3]), "+f"(acc[8][0]), "+f"(acc[8][1]), "+f"(acc[8][2]), "+f"(acc[8][3]), "+f"(acc[9][0]), "+f"(acc[9][1]), "+f"(acc[9][2]), "+f"(acc[9][3]), "+f"(acc[10][0]), "+f"(acc[10][1]), "+f"(acc[10][2]), "+f"(acc[10][3]), "+f"(acc[11][0]), "+f"(acc[11][1]), "+f"(acc[11][2]), "+f"(acc[11][3]), "+f"(acc[12][0]), "+f"(acc[12][1]), "+f"(acc[12][2]), "+f"(acc[12][3]), "+f"(acc[13][0]), "+f"(acc[13][1]), "+f"(acc[13][2]), "+f"(acc[13][3]), "+f"(acc[14][0]), "+f"(acc[14][1]), "+f"(acc[14][2]), "+f"(acc[14][3]), "+f"(acc[15][0]), "+f"(acc[15][1]), "+f"(acc[15][2]), "+f"(acc[15][3])
                 : "r"(a[0]), "r"(a[1]), "r"(a[2]), "r"(a[3]), "l"(desc));
}
template <> __device__ __forceinline__ void wg_mma<6>(float (&acc)[16][4], const uint32_t* a, uint64_t desc) {
    asm volatile("wgmma.mma_async.sync.aligned.m64n80k16.f32.f16.f16 {%0,%1,%2,%3,%4,%5,%6,%7,%8,%9,%10,%11,%12,%13,%14,%15,%16,%17,%18,%19,%20,%21,%22,%23,%24,%25,%26,%27,%28,%29,%30,%31,%32,%33,%34,%35,%36,%37,%38,%39}, {%40,%41,%42,%43}, %44, 1, 1, 1, 0;\n"
                 : "+f"(acc[6][0]), "+f"(acc[6][1]), "+f"(acc[6][2]), "+f"(acc[6][3]), "+f"(acc[7][0]), "+f"(acc[7][1]), "+f"(acc[7][2]), "+f"(acc[7][3]), "+f"(acc[8][0]), "+f"(acc[8][1]), "+f"(acc[8][2]), "+f"(acc[8][3]), "+f"(acc[9][0]), "+f"(acc[9][1]), "+f"(acc[9][2]), "+f"(acc[9][3]), "+f"(acc[10][0]), "+f"(acc[10][1]), "+f"(acc[10][2]), "+f"(acc[10][3]), "+f"(acc[11][0]), "+f"(acc[11][1]), "+f"(acc[11][2]), "+f"(acc[11][3]), "+f"(acc[12][0]), "+f"(acc[12][1]), "+f"(acc[12][2]), "+f"(acc[12][3]), "+f"(acc[13][0]), "+f"(acc[13][1]), "+f"(acc[13][2]), "+f"(acc[13][3]), "+f"(acc[14][0]), "+f"(acc[14][1]), "+f"(acc[14][2]), "+f"(acc[14][3]), "+f"(acc[15][0]), "+f"(acc[15][1]), "+f"(acc[15][2]), "+f"(acc[15][3])
                 : "r"(a[0]), "r"(a[1]), "r"(a[2]), "r"(a[3]), "l"(desc));
}
template <> __device__ __forceinline__ void wg_mma<8>(float (&acc)[16][4], const uint32_t* a, uint64_t desc) {
    asm volatile("wgmma.mma_async.sync.aligned.m64n64k16.f32.f16.f16 {%0,%1,%2,%3,%4,%5,%6,%7,%8,%9,%10,%11,%12,%13,%14,%15,%16,%17,%18,%19,%20,%21,%22,%23,%24,%25,%26,%27,%28,%29,%30,%31}, {%32,%33,%34,%35}, %36, 1, 1, 1, 0;\n"
                 : "+f"(acc[8][0]), "+f"(acc[8][1]), "+f"(acc[8][2]), "+f"(acc[8][3]), "+f"(acc[9][0]), "+f"(acc[9][1]), "+f"(acc[9][2]), "+f"(acc[9][3]), "+f"(acc[10][0]), "+f"(acc[10][1]), "+f"(acc[10][2]), "+f"(acc[10][3]), "+f"(acc[11][0]), "+f"(acc[11][1]), "+f"(acc[11][2]), "+f"(acc[11][3]), "+f"(acc[12][0]), "+f"(acc[12][1]), "+f"(acc[12][2]), "+f"(acc[12][3]), "+f"(acc[13][0]), "+f"(acc[13][1]), "+f"(acc[13][2]), "+f"(acc[13][3]), "+f"(acc[14][0]), "+f"(acc[14][1]), "+f"(acc[14][2]), "+f"(acc[14][3]), "+f"(acc[15][0]), "+f"(acc[15][1]), "+f"(acc[15][2]), "+f"(acc[15][3])
                 : "r"(a[0]), "r"(a[1]), "r"(a[2]), "r"(a[3]), "l"(desc));
}
template <> __device__ __forceinline__ void wg_mma<10>(float (&acc)[16][4], const uint32_t* a, uint64_t desc) {
    asm volatile("wgmma.mma_async.sync.aligned.m64n48k16.f32.f16.f16 {%0,%1,%2,%3,%4,%5,%6,%7,%8,%9,%10,%11,%12,%13,%14,%15,%16,%17,%18,%19,%20,%21,%22,%23}, {%24,%25,%26,%27}, %28, 1, 1, 1, 0;\n"
                 : "+f"(acc[10][0]), "+f"(acc[10][1]), "+f"(acc[10][2]), "+f"(acc[10][3]), "+f"(acc[11][0]), "+f"(acc[11][1]), "+f"(acc[11][2]), "+f"(acc[11][3]), "+f"(acc[12][0]), "+f"(acc[12][1]), "+f"(acc[12][2]), "+f"(acc[12][3]), "+f"(acc[13][0]), "+f"(acc[13][1]), "+f"(acc[13][2]), "+f"(acc[13][3]), "+f"(acc[14][0]), "+f"(acc[14][1]), "+f"(acc[14][2]), "+f"(acc[14][3]), "+f"(acc[15][0]), "+f"(acc[15][1]), "+f"(acc[15][2]), "+f"(acc[15][3])
                 : "r"(a[0]), "r"(a[1]), "r"(a[2]), "r"(a[3]), "l"(desc));
}
template <> __device__ __forceinline__ void wg_mma<12>(float (&acc)[16][4], const uint32_t* a, uint64_t desc) {
    asm volatile("wgmma.mma_async.sync.aligned.m64n32k16.f32.f16.f16 {%0,%1,%2,%3,%4,%5,%6,%7,%8,%9,%10,%11,%12,%13,%14,%15}, {%16,%17,%18,%19}, %20, 1, 1, 1, 0;\n"
                 : "+f"(acc[12][0]), "+f"(acc[12][1]), "+f"(acc[12][2]), "+f"(acc[12][3]), "+f"(acc[13][0]), "+f"(acc[13][1]), "+f"(acc[13][2]), "+f"(acc[13][3]), "+f"(acc[14][0]), "+f"(acc[14][1]), "+f"(acc[14][2]), "+f"(acc[14][3]), "+f"(acc[15][0]), "+f"(acc[15][1]), "+f"(acc[15][2]), "+f"(acc[15][3])
                 : "r"(a[0]), "r"(a[1]), "r"(a[2]), "r"(a[3]), "l"(desc));
}
template <> __device__ __forceinline__ void wg_mma<14>(float (&acc)[16][4], const uint32_t* a, uint64_t desc) {
    asm volatile("wgmma.mma_async.sync.aligned.m64n16k16.f32.f16.f16 {%0,%1,%2,%3,%4,%5,%6,%7}, {%8,%9,%10,%11}, %12, 1, 1, 1, 0;\n"
                 : "+f"(acc[14][0]), "+f"(acc[14][1]), "+f"(acc[14][2]), "+f"(acc[14][3]), "+f"(acc[15][0]), "+f"(acc[15][1]), "+f"(acc[15][2]), "+f"(acc[15][3])
                 : "r"(a[0]), "r"(a[1]), "r"(a[2]), "r"(a[3]), "l"(desc));
}
template <> __device__ __forceinline__ void wg_first<0>(float (&acc)[16][4], const uint32_t* a, uint64_t desc) {
    asm volatile("wgmma.mma_async.sync.aligned.m64n128k16.f32.f16.f16 {%0,%1,%2,%3,%4,%5,%6,%7,%8,%9,%10,%11,%12,%13,%14,%15,%16,%17,%18,%19,%20,%21,%22,%23,%24,%25,%26,%27,%28,%29,%30,%31,%32,%33,%34,%35,%36,%37,%38,%39,%40,%41,%42,%43,%44,%45,%46,%47,%48,%49,%50,%51,%52,%53,%54,%55,%56,%57,%58,%59,%60,%61,%62,%63}, {%64,%65,%66,%67}, %68, 0, 1, 1, 0;\n"
                 : "=f"(acc[0][0]), "=f"(acc[0][1]), "=f"(acc[0][2]), "=f"(acc[0][3]), "=f"(acc[1][0]), "=f"(acc[1][1]), "=f"(acc[1][2]), "=f"(acc[1][3]), "=f"(acc[2][0]), "=f"(acc[2][1]), "=f"(acc[2][2]), "=f"(acc[2][3]), "=f"(acc[3][0]), "=f"(acc[3][1]), "=f"(acc[3][2]), "=f"(acc[3][3]), "=f"(acc[4][0]), "=f"(acc[4][1]), "=f"(acc[4][2]), "=f"(acc[4][3]), "=f"(acc[5][0]), "=f"(acc[5][1]), "=f"(acc[5][2]), "=f"(acc[5][3]), "=f"(acc[6][0]), "=f"(acc[6][1]), "=f"(acc[6][2]), "=f"(acc[6][3]), "=f"(acc[7][0]), "=f"(acc[7][1]), "=f"(acc[7][2]), "=f"(acc[7][3]), "=f"(acc[8][0]), "=f"(acc[8][1]), "=f"(acc[8][2]), "=f"(acc[8][3]), "=f"(acc[9][0]), "=f"(acc[9][1]), "=f"(acc[9][2]), "=f"(acc[9][3]), "=f"(acc[10][0]), "=f"(acc[10][1]), "=f"(acc[10][2]), "=f"(acc[10][3]), "=f"(acc[11][0]), "=f"(acc[11][1]), "=f"(acc[11][2]), "=f"(acc[11][3]), "=f"(acc[12][0]), "=f"(acc[12][1]), "=f"(acc[12][2]), "=f"(acc[12][3]), "=f"(acc[13][0]), "=f"(acc[13][1]), "=f"(acc[13][2]), "=f"(acc[13][3]), "=f"(acc[14][0]), "=f"(acc[14][1]), "=f"(acc[14][2]), "=f"(acc[14][3]), "=f"(acc[15][0]), "=f"(acc[15][1]), "=f"(acc[15][2]), "=f"(acc[15][3])
                 : "r"(a[0]), "r"(a[1]), "r"(a[2]), "r"(a[3]), "l"(desc));
}
template <> __device__ __forceinline__ void wg_first<4>(float (&acc)[16][4], const uint32_t* a, uint64_t desc) {
    asm volatile("wgmma.mma_async.sync.aligned.m64n96k16.f32.f16.f16 {%0,%1,%2,%3,%4,%5,%6,%7,%8,%9,%10,%11,%12,%13,%14,%15,%16,%17,%18,%19,%20,%21,%22,%23,%24,%25,%26,%27,%28,%29,%30,%31,%32,%33,%34,%35,%36,%37,%38,%39,%40,%41,%42,%43,%44,%45,%46,%47}, {%48,%49,%50,%51}, %52, 0, 1, 1, 0;\n"
                 : "=f"(acc[4][0]), "=f"(acc[4][1]), "=f"(acc[4][2]), "=f"(acc[4][3]), "=f"(acc[5][0]), "=f"(acc[5][1]), "=f"(acc[5][2]), "=f"(acc[5][3]), "=f"(acc[6][0]), "=f"(acc[6][1]), "=f"(acc[6][2]), "=f"(acc[6][3]), "=f"(acc[7][0]), "=f"(acc[7][1]), "=f"(acc[7][2]), "=f"(acc[7][3]), "=f"(acc[8][0]), "=f"(acc[8][1]), "=f"(acc[8][2]), "=f"(acc[8][3]), "=f"(acc[9][0]), "=f"(acc[9][1]), "=f"(acc[9][2]), "=f"(acc[9][3]), "=f"(acc[10][0]), "=f"(acc[10][1]), "=f"(acc[10][2]), "=f"(acc[10][3]), "=f"(acc[11][0]), "=f"(acc[11][1]), "=f"(acc[11][2]), "=f"(acc[11][3]), "=f"(acc[12][0]), "=f"(acc[12][1]), "=f"(acc[12][2]), "=f"(acc[12][3]), "=f"(acc[13][0]), "=f"(acc[13][1]), "=f"(acc[13][2]), "=f"(acc[13][3]), "=f"(acc[14][0]), "=f"(acc[14][1]), "=f"(acc[14][2]), "=f"(acc[14][3]), "=f"(acc[15][0]), "=f"(acc[15][1]), "=f"(acc[15][2]), "=f"(acc[15][3])
                 : "r"(a[0]), "r"(a[1]), "r"(a[2]), "r"(a[3]), "l"(desc));
}

#define SDLY 1300
#define UDLY 1400
#define KDLY 850
#define FDLY 950
#define FDLY2 350
#define DDLY 300
#define WDLY 500
#define HW 15
#define FIX(v) do { if ((v) == 1u) TRAP(); } while (0)
#define STAMPW(i) STAMPY(i)
#define STAMP2(i) STAMP(i)
#undef STAMPX
#define STAMPX(i)
struct Params {
    const bf16 *x, *lar, *aim, *cre, *cim, *ldt, *dsk;
    Scratch* s;
    const bf16* wr;
    bf16* out;
};

#define TOK(g) (2 * (g) - ((g) & 1))
#define ROWTOK(r) (TOK((r) & 7) + (((r) >> 2) & 2))
__device__ __forceinline__ void ln_partial(const uint32_t (&H)[2][4], float (&d)[2][4]) {
#pragma unroll
    for (int i = 0; i < 8; i++) d[i >> 2][i & 3] = 0.f;
#pragma unroll
    for (int k = 0; k < 4; k++)
#pragma unroll
        for (int hf = 0; hf < 2; hf++) mma_bf16_k8(d[hf], H[hf][k], 0x3f803f80u, H[hf][k]);
}
__device__ __forceinline__ float sum18(uint32_t a) {
    const uint4 p = lds128(a), q = lds128(a + 16), r = lds128(a + 32), s = lds128(a + 48);
    const uint2 u = lds64(a + 64);
#define F(x) __uint_as_float(x)
    return (((F(p.x) + F(p.y)) + (F(p.z) + F(p.w))) + ((F(q.x) + F(q.y)) + (F(q.z) + F(q.w)))) +
           (((F(r.x) + F(r.y)) + (F(r.z) + F(r.w))) + ((F(s.x) + F(s.y)) + (F(s.z) + F(s.w))) + (F(u.x) + F(u.y)));
#undef F
}
__device__ __forceinline__ void ln_stats(float sm, float sq, float& mb, float& sd) {
    const float m0 = sm * (1.0f / 576.0f);
    const float mean = fmaf(fmaf(-m0, 576.0f, sm), 1.0f / 576.0f, m0);
    const float var = fmaxf(fmaf(-mean, mean, sq * (1.0f / 576.0f)), 0.f);
    mb = rbf(mean);
    sd = rbf(sqrt_approx(rbf(rbf(var) + 1e-5f)));
}
__device__ __forceinline__ void ln_finish(float v, int lane, float& mb, float& rc) {
    const float o = __shfl_xor_sync(0xffffffffu, v, 16);
    float sd;
    ln_stats(lane < 16 ? v : o, lane < 16 ? o : v, mb, sd);
    rc = rcp_approx(sd);
}
__device__ __forceinline__ uint32_t ln_apply(uint32_t w, uint32_t m2, uint32_t rh, uint32_t rl) {
    const uint32_t d = hsub2_bf(w, m2);
    return hfma2_bf(d, rh, hmul2_bf(d, rl));
}
__device__ __forceinline__ void stat_store(uint32_t a, float mb, float rc, uint32_t extra) {
    const float rh = rbf(rc);
    sts64(a, (__float_as_uint(mb) >> 16) | (extra << 16), pack_bf16(rh, rc - rh));
}
#define STAT_M(s) __byte_perm((s).x, (s).x, 0x1010)
#define STAT_H(s) __byte_perm((s).y, (s).y, 0x1010)
#define STAT_L(s) __byte_perm((s).y, (s).y, 0x3232)

__device__ __forceinline__ void hcmul(uint32_t re, uint32_t im, uint32_t zx, uint32_t zy, uint32_t& ore, uint32_t& oim) {
    ore = hfms2(im, zy, hmul2(re, zx));
    oim = hfma2(re, zy, hmul2(im, zx));
}

struct KGen {
    uint32_t A[2][4][4];
    float2 z1, z8, z64, z128, T[9];
};
__device__ __forceinline__ void kgen_setup(KGen& k, float lar, float aim, float dt) {
    const float lr2 = -(exp_bf(lar) * dt) * 1.4426950408889634f, li = aim * dt;
    k.z1 = cexp_e(lr2, li, 1.0f);
    k.z8 = cexp_e(lr2, li, 8.0f);
    k.z64 = cexp_e(lr2, li, 64.0f);
}
__device__ __forceinline__ void kgen_rows(KGen& k, uint32_t tb, int lane) {
    const float2 z8 = k.z8, z64 = k.z64;
    const uint32_t row = tb + lane * 16;
    k.z128 = csq(z64);
    const float2 z16 = csq(z8), z24 = cmul(z16, z8), z32 = csq(z16), z40 = cmul(z32, z8), z48 = csq(z24), z56 = cmul(z32, z24);
    uint32_t re[4], im[4], a[4], b[4];
    re[0] = pack_f16(1.0f, z8.x); im[0] = pack_f16(0.0f, z8.y);
    re[1] = pack_f16(z16.x, z24.x); im[1] = pack_f16(z16.y, z24.y);
    re[2] = pack_f16(z32.x, z40.x); im[2] = pack_f16(z32.y, z40.y);
    re[3] = pack_f16(z48.x, z56.x); im[3] = pack_f16(z48.y, z56.y);
    sts128(row, re[0], re[1], re[2], re[3]);
    sts128(row + 1024, im[0], im[1], im[2], im[3]);
    const uint32_t zx = pack_f16(z64.x, z64.x), zy = pack_f16(z64.y, z64.y), zw = pack_f16(k.z128.x, k.z128.y);
#pragma unroll
    for (int j = 0; j < 4; j++) hcmul(re[j], im[j], zx, zy, a[j], b[j]);
    sts128(row + 512, a[0], a[1], a[2], a[3]);
    sts128(row + 1536, b[0], b[1], b[2], b[3]);
    const int mi = lane >> 3;
    const uint32_t zd = tb + 2048 + mi * 16;
    sts16(tb + 2048 + lane * 2, zw); sts16(tb + 2112 + lane * 2, zw >> 16);
    __syncwarp();
    const uint32_t ad = tb + (lane & 7) * 16 + mi * 512;
    ldsm_x4(a[0], a[1], a[2], a[3], zd);
    ldsm_x4(b[0], b[1], b[2], b[3], zd + 64);
#pragma unroll
    for (int ks = 0; ks < 4; ks++) {
        ldsm_x4_t(k.A[0][ks][0], k.A[0][ks][1], k.A[0][ks][2], k.A[0][ks][3], ad + ks * 128);
        hcmul(k.A[0][ks][0], k.A[0][ks][2], a[ks], b[ks], k.A[1][ks][0], k.A[1][ks][2]);
        hcmul(k.A[0][ks][1], k.A[0][ks][3], a[ks], b[ks], k.A[1][ks][1], k.A[1][ks][3]);
    }
}
__device__ __forceinline__ void kgen_chain(KGen& k, uint32_t cr, uint32_t ci, float cs) {
    k.T[0] = make_float2(bf_lo(cr) * cs, -bf_lo(ci) * cs);
    const float2 y1 = make_float2(k.z1.x, -k.z1.y);
#pragma unroll
    for (int c = 1; c < 8; c++) k.T[c] = cmul(k.T[c - 1], y1);
    k.T[8] = cmul(k.T[0], make_float2(k.z8.x, -k.z8.y));
}
__device__ __forceinline__ void kgen_cols(KGen& k, uint32_t tb, uint32_t t5, int lane) {
    const uint32_t row = tb + lane * 16;
    const float2 (&T)[9] = k.T;
    const float2 y128 = make_float2(k.z128.x, -k.z128.y);
    const float2 y256 = csq(y128), y512 = csq(y256), y768 = cmul(y512, y256), y1024 = csq(y512);
    const float2 c1032 = cmul(T[8], y1024);
    __syncwarp();
    sts128(row, pack_f16(T[0].x, T[1].x), pack_f16(T[2].x, T[3].x), pack_f16(T[4].x, T[5].x), pack_f16(T[6].x, T[7].x));
    sts128(row + 512, pack_f16(T[0].y, T[1].y), pack_f16(T[2].y, T[3].y), pack_f16(T[4].y, T[5].y), pack_f16(T[6].y, T[7].y));
    uint32_t a[4], b[4];
    {
        const uint32_t zx = pack_f16(y256.x, y256.x), zy = pack_f16(y256.y, y256.y);
        hcmul(pack_f16(T[0].x, T[2].x), pack_f16(T[0].y, T[2].y), zx, zy, a[0], b[0]);
        hcmul(pack_f16(T[4].x, T[6].x), pack_f16(T[4].y, T[6].y), zx, zy, a[1], b[1]);
        const uint32_t r04 = pack_f16(T[0].x, T[4].x), i04 = pack_f16(T[0].y, T[4].y);
        hcmul(r04, i04, pack_f16(y512.x, y512.x), pack_f16(y512.y, y512.y), a[2], b[2]);
        hcmul(r04, i04, pack_f16(y768.x, y768.x), pack_f16(y768.y, y768.y), a[3], b[3]);
    }
    sts128(row + 1024, a[0], a[1], a[2], a[3]);
    sts128(row + 1536, b[0], b[1], b[2], b[3]);
    {
        const uint32_t r0 = pack_f16(1.0f, y256.x), i0 = pack_f16(0.0f, y256.y), r1 = pack_f16(y512.x, y768.x), i1 = pack_f16(y512.y, y768.y);
        const uint32_t zx = pack_f16(T[8].x, T[8].x), zy = pack_f16(T[8].y, T[8].y), wx = pack_f16(c1032.x, c1032.x), wy = pack_f16(c1032.y, c1032.y);
        hcmul(r0, i0, zx, zy, a[0], b[0]); hcmul(r1, i1, zx, zy, a[1], b[1]);
        hcmul(r0, i0, wx, wy, a[2], b[2]); hcmul(r1, i1, wx, wy, a[3], b[3]);
    }
    sts128(row + 2048, a[0], a[1], a[2], a[3]);
    sts128(t5 + lane * 16, b[0], b[1], b[2], b[3]);
}
__device__ __forceinline__ void kgen_mma(const KGen& k, uint32_t tb, uint32_t t5, int lane) {
    __syncwarp();
    float acc[2][3][4];
#pragma unroll
    for (int i = 0; i < 6; i++)
#pragma unroll
        for (int j = 0; j < 4; j++) acc[i / 3][i % 3][j] = 0.f;
    const int mi = lane >> 3;
    const uint32_t ro = ((lane & 7) + 8 * (mi >> 1)) * 16, bd = tb + ro + (mi & 1) * 512, b2 = ro + ((mi & 1) ? t5 : tb + 2048);
#pragma unroll
    for (int kp = 0; kp < 2; kp++)
#pragma unroll
        for (int j = 0; j < 3; j++) {
            uint32_t b[4];
            ldsm_x4_t(b[0], b[1], b[2], b[3], (j < 2 ? bd + j * 1024 : b2) + kp * 256);
#pragma unroll
            for (int h = 0; h < 2; h++)
#pragma unroll
                for (int m = 0; m < 2; m++) {
                    const uint32_t (&A)[4] = k.A[m][2 * kp + h];
                    mma_f16(acc[m][j], A[0], A[1], A[2], A[3], b[2 * h], b[2 * h + 1]);
                }
        }
    __syncwarp();
#define PK(j) pack_f16(acc[0][j][0], acc[0][j][1]), pack_f16(acc[0][j][2], acc[0][j][3]), pack_f16(acc[1][j][0], acc[1][j][1]), pack_f16(acc[1][j][2], acc[1][j][3])
    stsm_x4(tb + lane * 16, PK(0));
    stsm_x4(tb + 512 + lane * 16, PK(1));
    stsm_x4_t(tb + 1024 + (lane & 7) * 80 + mi * 16, PK(2));
#undef PK
}
__device__ __forceinline__ uint32_t table_buf(uint32_t sb, int warp) { return sb + SM_PL + warp * TBW; }

__device__ __forceinline__ uint4 lds16x4(uint32_t a) { return make_uint4(lds16(a), lds16(a + TBW), lds16(a + 2 * TBW), lds16(a + 3 * TBW)); }
__device__ __forceinline__ void combine_setup(uint32_t sb, int warp, int lane, uint32_t kw, uint32_t& o, uint32_t& n, uint32_t& d) {
    const int wq = warp & 3;
    const uint32_t a = table_buf(sb, warp & ~3);
    o = wq == 3 ? a + 1024 + 320 + (lane >> 3) * 80 + (lane & 7) * 8 : a + (wq ? 504 + wq * 8 : 0) + lane * 16;
    n = a + 1024 + wq * 80 + lane * 2;
    d = wq < 3 ? kw + (wq == 2 ? KW_P : 32 + wq * 512) + lane * 16 : kw + KW_H + 8 + lane * 8;
}
__device__ __forceinline__ void kgen_combine(int wq, int lane, uint32_t o, uint32_t na, uint32_t d) {
#define S4(f) hadd2(hadd2(u.f, v.f), hadd2(w.f, x.f))
#define H4(v) hadd2(hadd2(v.x, v.y), hadd2(v.z, v.w))
#define BP __byte_perm
    if (wq == 0) {
        const uint4 u = lds128(o), v = lds128(o + TBW), w = lds128(o + 2 * TBW), x = lds128(o + 3 * TBW), nn = lds16x4(na);
        const uint32_t n = H4(nn), k0 = S4(x), k2 = S4(y), k4 = S4(z), k6 = S4(w);
        sts128(d, BP(k0, k0, 0x1032), BP(k0, k2, 0x3254), BP(k2, k2, 0x1032), BP(k2, k4, 0x3254));
        sts128(d + KW_PL, BP(k4, k4, 0x1032), BP(k4, k6, 0x3254), BP(k6, k6, 0x1032), BP(k6, n, 0x3254));
        if (lane == 0) sts32(d + KW_PL - 4, k0 & 0xffffu);
    } else {
        const uint2 u = lds64(o), v = lds64(o + TBW), w = lds64(o + 2 * TBW), x = lds64(o + 3 * TBW);
        uint4 nn = make_uint4(0u, 0u, 0u, 0u), mm = nn;
        if (wq < 3) nn = lds16x4(na);
        if (wq == 2) mm = lds16x4(na + 80);
        const uint32_t k0 = S4(x), k2 = S4(y), n = H4(nn), m = H4(mm);
        if (wq == 3) {
            sts64(d, k0, k2);
        } else if (wq == 1) {
            const uint32_t cc = BP(k2, k2, 0x1010);
            sts128(d, BP(k0, k0, 0x1010), BP(k0, k0, 0x1032), BP(k0, k2, 0x3254), cc);
            sts128(d + KW_PL, cc, BP(k2, k2, 0x1032), BP(k2, n, 0x3254), BP(n, n, 0x1010));
        } else {
            const uint32_t w40 = BP(k0, k0, 0x1032), w84 = BP(k0, n, 0x3254), w0 = BP(k0, k0, 0x1010), w4 = BP(k0, k0, 0x3232), w8 = BP(n, n, 0x1010);
            sts64(d, w40, w84);
            sts64(d + 512, BP(k2, k2, 0x1032), BP(k2, m, 0x3254));
            if (lane < 8) { sts128(d - (KW_P - 1056), w0, w0, w40, w4); sts128(d - (KW_P - 1056 - KW_PL), w4, w84, w8, w8); }
            if (lane == 31) sts16(d + (KW_H + 6 - KW_P - 496), m);
        }
    }
#undef S4
#undef H4
#undef BP
}

__device__ __forceinline__ int c_exponent(const uint2& r, const uint2& i, float dt) {
    const uint32_t mx = __vmaxu2(__vmaxu2(r.x & 0x7fff7fffu, r.y & 0x7fff7fffu), __vmaxu2(i.x & 0x7fff7fffu, i.y & 0x7fff7fffu));
    return __reduce_max_sync(0xffffffffu, max(mx, mx << 16) + (__float_as_uint(dt) & 0x7f800000u)) >> 23;
}

__device__ __forceinline__ int lane_v() { int l; asm volatile("mov.u32 %0, %%laneid;" : "=r"(l)); return l; }
__device__ __forceinline__ uint32_t prmt_v(uint32_t a, uint32_t b, uint32_t s) { uint32_t d; asm volatile("prmt.b32 %0, %1, %2, %3;\n" : "=r"(d) : "r"(a), "r"(b), "r"(s)); return d; }
__device__ __forceinline__ uint32_t mov_v(uint32_t a) { uint32_t d; asm volatile("mov.b32 %0, %1;\n" : "=r"(d) : "r"(a)); return d; }
template <int G>
__device__ __forceinline__ void conv_rename(float (&acc)[16][4]) {
#pragma unroll
    for (int i = G; i < 16; i++)
#pragma unroll
        for (int j = 0; j < 4; j++) { float v; asm volatile("mov.b32 %0, %1;\n" : "=f"(v) : "f"(acc[i][j])); acc[i][j] = v; }
}
struct Conv {
    uint32_t kw;
    uint32_t wa;
    uint32_t pa, s2;
    uint32_t s8;
    uint32_t id;
    uint32_t lc;
    uint32_t fs;
    uint32_t fl, yo;
    uint32_t yp;
    size_t ycopy;
    uint32_t ps;
    uint64_t d0;
    int warp;
};
struct Pk { uint32_t w[4]; };
__device__ __forceinline__ Pk pk2(const float (&u)[4], const float (&v)[4]) {
    Pk r;
    r.w[0] = pack_f16(u[0], u[1]); r.w[1] = pack_f16(u[2], u[3]); r.w[2] = pack_f16(v[0], v[1]); r.w[3] = pack_f16(v[2], v[3]);
    return r;
}
__device__ __forceinline__ void park(uint32_t a, const Pk& v) {
    asm volatile("stmatrix.sync.aligned.m8n8.x4.trans.shared.b16 [%0], {%1,%2,%3,%4};\n" ::"r"(a), "r"(v.w[0]), "r"(v.w[1]), "r"(v.w[2]), "r"(v.w[3]) : "memory");
}
__device__ __forceinline__ void conv_constants(uint32_t lc, int l) {
    const int d = (l >> 2) - 2 * (l & 3);
    const int e = d + 8, r4 = (e + 1 + ((e >> 2) & 1)) >> 2, p4 = (e + (((e - 1) >> 2) & 1)) >> 2;
    const uint32_t s2 = r4 == p4 ? 0x1010u : 0x3210u;
    sts64(lc + l * 8, KW_P + ((r4 - 5) >> 1) * 16 + ((r4 - 5) & 1) * 4, s2 | ((d < 0 ? s2 : 0x7654u) << 16));
    const int lo = (d >= 4) - (d < -3), ho = (d >= 5) - (d < -2), le = (d > 4) - (d < -4), he = (d > 5) - (d < -3);
    sts32(lc + 512 + l * 8, (0x5454u + lo * 0x22 + ho * 0x2200) | ((0x3232u + le * 0x22 + he * 0x2200) << 16));
    const int cc = l >> 2, j = l & 3;
    sts64(lc + 256 + l * 8, (j >> 1) * PL_HALF + (16 + cc) * 16 + (j & 1) * 8, (cc >> 1) * (DM * 64) + (cc & 1) * 32 + j * 8);
}
__device__ __forceinline__ void conv_selectors4(Conv& c) {
    const uint2 v = lds64(c.lc + lane_v() * 8);
    c.pa = v.x; c.s2 = v.y;
}
__device__ __forceinline__ void conv_selectors8(Conv& c) { c.s8 = lds32(c.lc + 512 + lane_v() * 8); }
template <int G, int I0, int I1>
__device__ __forceinline__ void conv_load(const Conv& c, uint32_t (&q)[9]) {
    const int wq = c.warp & 3;
    if (G < 2) {
#pragma unroll
        for (int i = I0; i < I1; i++) q[i] = lds32(c.wa + G * 512 + i * 16);
    } else if (G < 4) {
        const uint32_t a = (G == 2 && wq == 0) ? c.wa + 1024 : c.pa + c.kw + wq * 128 + (G < 2 ? 0 : G - 2) * 512;
#pragma unroll
        for (int i = I0; i < I1; i++) q[i] = lds32(a + i * 16);
    } else {
        const uint4 u = lds128(c.kw + KW_H + (G < 4 ? 0 : G - 4) * 64 + wq * 16);
        const uint2 v = lds64(c.kw + KW_H + (G < 4 ? 0 : G - 4) * 64 + wq * 16 + 16);
        q[0] = u.x; q[1] = u.y; q[2] = u.z; q[3] = u.w; q[4] = v.x; q[5] = v.y;
        if (G == 4 && wq == 0) { q[6] = lds32(c.pa + c.kw + 1024); q[7] = lds32(c.pa + c.kw + 1040); }
    }
}
template <int G, int J0, int J1>
__device__ __forceinline__ void conv_frag(const Conv& c, const uint32_t (&q)[9], uint32_t* a, const Pk& dp) {
    const uint32_t dep = dp.w[0];
    if (G < 4) {
        const uint32_t s = (G < 2 || (G == 2 && (c.warp & 3) == 0)) ? c.id : c.s2;
#pragma unroll
        for (int j = J0; j < J1; j++) {
            uint32_t* o = a + 4 * (j - J0);
            o[0] = prmt_v(q[2 * j + 1], dp.w[0], s); o[1] = prmt_v(q[2 * j + 2], dp.w[1], s); o[2] = prmt_v(q[2 * j], dp.w[2], s); o[3] = prmt_v(q[2 * j + 1], dp.w[3], s);
        }
    } else {
        const uint32_t so = prmt_v(c.s8, dep, c.id), se = prmt_v(c.s8, dep, c.id + 0x22);
#pragma unroll
        for (int j = J0; j < J1; j++) {
            uint32_t* o = a + 4 * (j - J0);
            o[0] = prmt_v(q[j + 1], q[j + 2], se); o[1] = prmt_v(q[j + 1], q[j + 2], so); o[2] = prmt_v(q[j], q[j + 1], so);
            if (G == 4 && j == 0 && (c.warp & 3) == 0) {
                o[2] = prmt_v(q[6], dep, c.s2);
                o[0] = prmt_v(q[7], o[0], c.s2 >> 16);
            }
            o[3] = mov_v(o[0]);
        }
    }
}
template <int G, int J0, int J1>
__device__ __forceinline__ void conv_frag(const Conv& c, const uint32_t (&q)[9], uint32_t* a, float depf) {
    const uint32_t d = __float_as_uint(depf);
    conv_frag<G, J0, J1>(c, q, a, Pk{{d, d, d, d}});
}
template <int G, int T, int J0, int J1>
__device__ __forceinline__ void conv_mma(float (&acc)[16][4], const Conv& c, const uint32_t* a) {
#pragma unroll
    for (int j = J0; j < J1; j++) wg_mma<T>(acc, a + 4 * (j - J0), c.d0 - 8 * (2 * G - T) - j);
}
__device__ __forceinline__ float h_lo(uint32_t w) { return __half2float(__ushort_as_half((unsigned short)(w & 0xffffu))); }
__device__ __forceinline__ float h_hi(uint32_t w) { return __half2float(__ushort_as_half((unsigned short)(w >> 16))); }
__device__ __forceinline__ void flush_setup(Conv& c) {
    const uint2 v = lds64(c.lc + 256 + lane_v() * 8);
    c.fl = v.x; c.yo = v.y;
}
template <int Q>
__device__ __forceinline__ void flush_load(const Conv& c, uint32_t pl, uint2 (&f)[4]) {
#pragma unroll
    for (int w = 0; w < 4; w++) f[w] = lds64(c.fl + pl + (Q & 1) * 512 + w * (PLW_B - 64));
}
template <int Q>
__device__ __forceinline__ void flush_load_first(const Conv& c, uint32_t pl, uint2 (&f)[4], float depf) {
    const uint32_t p = prmt_v(c.fl, __float_as_uint(depf), c.id) + pl + (Q & 1) * 512;
#define LDV64(d, a) asm volatile("ld.volatile.shared.v2.u32 {%0,%1}, [%2];\n" : "=r"(d.x), "=r"(d.y) : "r"(a) : "memory")
    LDV64(f[0], p); LDV64(f[1], p + (PLW_B - 64)); LDV64(f[2], p + 2 * (PLW_B - 64)); LDV64(f[3], p + 3 * (PLW_B - 64));
}
#define FDEP __uint_as_float(f[3].y)
template <int Q, int mode>
__device__ __forceinline__ void conv_flush(const Conv& c, const uint2 (&f)[4], unsigned char* gy, uint32_t rx) {
    const uint32_t a0 = hadd2(f[0].x, f[1].x), a1 = hadd2(f[2].x, f[3].x), b0 = hadd2(f[0].y, f[1].y), b1 = hadd2(f[2].y, f[3].y);
    if (Q > 0 && mode == 1) {
        const uint32_t ra = rx + 16 + (Q > 0 ? Q - 1 : 0) * 1024 + (c.warp & 3) * 256 + lane_v() * 8;
        asm volatile("st.async.shared::cluster.mbarrier::complete_tx::bytes.v2.b32 [%0], {%1,%2}, [%3];\n"
                     ::"r"(ra ^ 0x1000000u), "r"(hadd2(a0, a1)), "r"(hadd2(b0, b1)), "r"((rx + (Q > 1 ? 8 : 0)) ^ 0x1000000u) : "memory");
        return;
    }
    float v0 = h_lo(a0) + h_lo(a1), v1 = h_hi(a0) + h_hi(a1), v2 = h_lo(b0) + h_lo(b1), v3 = h_hi(b0) + h_hi(b1);
    if (Q > 0 && mode == 2) {
        const uint2 o = lds64(rx + 16 + (Q > 0 ? Q - 1 : 0) * 1024 + (c.warp & 3) * 256 + lane_v() * 8);
        v0 += h_lo(o.x); v1 += h_hi(o.x); v2 += h_lo(o.y); v3 += h_hi(o.y);
    }
    const uint32_t lo = hmul2_bf(pack_bf16(v0, v1), c.fs), hi = hmul2_bf(pack_bf16(v2, v3), c.fs);
    stg64(gy + Q * 32 * DM * 32 + (c.yo + (Q < 2 ? c.yp : 0u)), nzw(lo), nzw(hi));
}
template <int I, bool S = false> struct IC { static constexpr int value = I; static constexpr bool shared = S; };
template <class T> __device__ constexpr bool wg_is4() { return T::shared; }
#define SLOT(n) (c.ps + (2 + ((n) & 7)) * 128)
#define GO() do { wg_commit(); __syncwarp(); } while (0)
#define DEP acc[15][3]
template <class FG, class FP, class FN>
__device__ __forceinline__ void conv_head(Conv& c, float (&acc)[16][4], uint32_t (&q)[9], uint32_t (&r)[9], uint32_t* a, FG fg, FP pre, FN next) {
    c.id = 0x3210u + (c.warp >> 8);
    pre();
    conv_load<0, 0, 9>(c, q);
    conv_frag<0, 0, 1>(c, q, a, 0.f);
    wg_fence(); wg_first<0>(acc, a, c.d0); GO();
    park(c.ps, Pk{{0u, 0u, 0u, 0u}});
    wg_wait0();
    conv_frag<0, 1, 2>(c, q, a, DEP);
    wg_fence(); conv_mma<0, 0, 1, 2>(acc, c, a); GO();
    fg(IC<0>());
    wg_wait0();
    conv_frag<0, 2, 3>(c, q, a, DEP);
    wg_fence(); conv_mma<0, 0, 2, 3>(acc, c, a); GO();
    conv_load<1, 0, 5>(c, r);
    wg_wait0();
    conv_frag<0, 3, 4>(c, q, a, DEP);
    wg_fence(); conv_mma<0, 0, 3, 4>(acc, c, a); GO();
    conv_load<1, 5, 9>(c, r);
    fg(IC<1>());
    wg_wait0();
    const Pk k = pk2(acc[0], acc[1]);
    conv_rename<2>(acc);
    conv_frag<1, 0, 2>(c, r, a, k);
    wg_fence(); conv_mma<1, 2, 0, 2>(acc, c, a); GO();
    park(SLOT(0), k);
    next(IC<0>());
    fg(IC<2>());
    wg_wait0();
    conv_frag<1, 2, 4>(c, r, a, DEP);
    wg_fence(); conv_mma<1, 2, 2, 4>(acc, c, a); GO();
    next(IC<1>());
    fg(IC<3>());
    wg_wait0();
}
template <class FG, class FP>
__device__ __forceinline__ void conv_run(Conv& c, uint32_t pl, unsigned char* gy, FG fg, FP pre) {
    float acc[16][4];
    uint32_t q[9], r[9], a[32];
    uint2 f[4];
    const int bid = 1 + (c.warp >> 2);
    conv_head(c, acc, q, r, a, fg, pre, [&](auto i) { if (decltype(i)::value == 0) conv_selectors4(c); else conv_load<2, 0, 9>(c, q); });
    Pk k = pk2(acc[2], acc[3]);
    conv_rename<4>(acc);
    conv_frag<2, 0, 4>(c, q, a, k);
    wg_fence(); conv_mma<2, 4, 0, 4>(acc, c, a); GO();
    park(SLOT(2), k);
    conv_load<3, 0, 9>(c, q);
    flush_setup(c);
    bar_sync(bid, 128);
    fg(IC<4>());
    wg_wait0();
    conv_rename<6>(acc);
    conv_frag<3, 0, 4>(c, q, a, DEP);
    wg_fence(); conv_mma<3, 6, 0, 4>(acc, c, a); GO();
    park(SLOT(4), pk2(acc[4], acc[5]));
    conv_load<4, 0, 9>(c, q);
    conv_selectors8(c);
    flush_load<0>(c, pl, f);
    conv_flush<0, 0>(c, f, gy, 0u);
    fg(IC<5>());
    wg_wait0();
    conv_rename<8>(acc);
    conv_frag<4, 0, 4>(c, q, a, DEP);
    wg_fence(); conv_mma<4, 8, 0, 4>(acc, c, a); GO();
    k = pk2(acc[6], acc[7]);
    park(SLOT(6), k);
    conv_load<5, 0, 9>(c, q);
    bar_sync(bid, 128);
    park(c.ps, k);
    fg(IC<6>());
    wg_wait0();
    conv_rename<10>(acc);
    flush_load_first<1>(c, pl, f, DEP);
    conv_frag<5, 0, 4>(c, q, a, FDEP);
    wg_fence(); conv_mma<5, 10, 0, 4>(acc, c, a); GO();
    park(SLOT(8), pk2(acc[8], acc[9]));
    conv_load<6, 0, 9>(c, q); conv_load<7, 0, 9>(c, r);
    conv_flush<1, 0>(c, f, gy, 0u);
    fg(IC<7>());
    wg_wait0();
    conv_rename<12>(acc);
    conv_frag<6, 0, 4>(c, q, a, DEP); conv_frag<7, 0, 4>(c, r, a + 16, DEP);
    wg_fence(); conv_mma<6, 12, 0, 4>(acc, c, a); conv_mma<7, 12, 0, 4>(acc, c, a + 16); GO();
    park(SLOT(10), pk2(acc[10], acc[11]));
    bar_sync(bid, 128);
    flush_load<2>(c, pl, f);
    conv_flush<2, 0>(c, f, gy, 0u);
    fg(IC<8>());
    if (c.id == 0) TRAP();
    wg_wait0();
    park(SLOT(12), pk2(acc[12], acc[13])); park(SLOT(14), pk2(acc[14], acc[15]));
    bar_sync(bid, 128);
    flush_load<3>(c, pl, f);
    conv_flush<3, 0>(c, f, gy, 0u);
}
template <class FG>
__device__ __forceinline__ void conv_outer(Conv& c, uint32_t pl, unsigned char* gy, uint32_t rx, FG fg) {
    float acc[16][4];
    uint32_t q[9], r[9], a[32];
    uint2 f[4], f2[4];
    const int bid = 1 + (c.warp >> 2);
    conv_head(c, acc, q, r, a, [&](auto gi) { if (decltype(gi)::value == 2) fg(IC<2, true>()); }, [&]() {}, [&](auto i) { if (decltype(i)::value == 0) conv_selectors8(c); else conv_load<6, 0, 9>(c, q); });
    park(SLOT(2), pk2(acc[2], acc[3])); park(SLOT(4), pk2(acc[4], acc[5]));
    const Pk k = pk2(acc[6], acc[7]);
    park(SLOT(6), k);
    conv_load<7, 0, 9>(c, r);
    conv_rename<12>(acc);
    conv_frag<6, 0, 4>(c, q, a, __uint_as_float(k.w[3])); conv_frag<7, 0, 4>(c, r, a + 16, __uint_as_float(k.w[3]));
    wg_fence(); conv_mma<6, 12, 0, 4>(acc, c, a); conv_mma<7, 12, 0, 4>(acc, c, a + 16); GO();
    flush_setup(c);
    bar_sync(bid, 128);
    flush_load<0>(c, pl, f); flush_load<1>(c, pl, f2);
    conv_flush<1, 1>(c, f2, gy, rx);
    conv_flush<0, 1>(c, f, gy, rx);
    wg_wait0();
    bar_sync(bid, 128);
    park(c.ps, k); park(SLOT(8), pk2(acc[8], acc[9])); park(SLOT(10), pk2(acc[10], acc[11]));
    park(SLOT(12), pk2(acc[12], acc[13])); park(SLOT(14), pk2(acc[14], acc[15]));
    bar_sync(bid, 128);
    flush_load<2>(c, pl, f); flush_load<3>(c, pl, f2);
    conv_flush<2, 1>(c, f, gy, rx);
    conv_flush<3, 1>(c, f2, gy, rx);
}
template <class FG>
__device__ __forceinline__ void conv_inner(Conv& c, uint32_t pl, unsigned char* gy, uint32_t rx, FG fg) {
    float acc[16][4];
    uint32_t q[9], a[16];
    uint2 f[4], f2[4];
    const int bid = 1 + (c.warp >> 2);
    c.id = 0x3210u + (c.warp >> 8);
    conv_selectors4(c);
    conv_load<2, 0, 9>(c, q);
    conv_frag<2, 0, 4>(c, q, a, 0.f);
    wg_fence(); wg_first<4>(acc, a, c.d0); conv_mma<2, 4, 1, 4>(acc, c, a + 4); GO();
    conv_load<3, 0, 9>(c, q);
    park(SLOT(2), Pk{{0u, 0u, 0u, 0u}});
    fg(IC<2, true>());
    wg_wait0();
    conv_rename<6>(acc);
    conv_frag<3, 0, 4>(c, q, a, DEP);
    wg_fence(); conv_mma<3, 6, 0, 4>(acc, c, a); GO();
    park(SLOT(4), pk2(acc[4], acc[5]));
    conv_load<4, 0, 9>(c, q);
    conv_selectors8(c);
    wg_wait0();
    conv_rename<8>(acc);
    conv_frag<4, 0, 4>(c, q, a, DEP);
    wg_fence(); conv_mma<4, 8, 0, 4>(acc, c, a); GO();
    const Pk k = pk2(acc[6], acc[7]);
    park(SLOT(6), k); park(c.ps, k);
    conv_load<5, 0, 9>(c, q);
    flush_setup(c);
    wg_wait0();
    conv_rename<10>(acc);
    conv_frag<5, 0, 4>(c, q, a, DEP);
    wg_fence(); conv_mma<5, 10, 0, 4>(acc, c, a); GO();
    park(SLOT(8), pk2(acc[8], acc[9]));
    bar_sync(bid, 128);
    flush_load<1>(c, pl, f);
    mbar_wait(rx);
    conv_flush<1, 2>(c, f, gy, rx);
    wg_wait0();
    bar_sync(bid, 128);
    park(SLOT(10), pk2(acc[10], acc[11])); park(SLOT(12), pk2(acc[12], acc[13])); park(SLOT(14), pk2(acc[14], acc[15]));
    bar_sync(bid, 128);
    flush_load<3>(c, pl, f); flush_load<2>(c, pl, f2);
    mbar_wait(rx + 8);
    conv_flush<3, 2>(c, f, gy, rx);
    conv_flush<2, 2>(c, f2, gy, rx);
}
#undef SLOT
#undef GO
#undef DEP
template <int U0, int U1>
__device__ __forceinline__ void weight_units(uint32_t sb, const CUtensorMap* tg, const CUtensorMap* tu, const CUtensorMap* td, bool w) {
    if (U1 > U0 && w && elect_one()) {
#pragma unroll
        for (int i = U0; i < U1; i++) {
            if (i < 12) tma_2d(sb + SM_WG + i * 6912, i < 6 ? tg : tu, 72 * (blockIdx.x >> 1), 288 * (blockIdx.x & 1) + (i % 6) * 48, sb + SM_MISC + 328);
            else tma_2d(sb + SM_WD + (i - 12) * 4736, td, 144 * (blockIdx.x & 1), 72 * (blockIdx.x >> 1) + 8 * (i - 12), sb + SM_MISC + 336);
        }
    }
}
#define WS 2110121111122004100
__device__ constexpr int wsched(int i) {
    unsigned long long v = WS;
    int n = 0;
    for (int k = 19; k >= 1; k--) { if (k < i) n += (int)(v % 10); v /= 10; }
    return n;
}
static_assert(wsched(20) == 21 && wsched(6) <= 7 && wsched(11) <= 12 && wsched(13) <= 14 && wsched(16) <= 17 && wsched(16) == wsched(15) && wsched(19) == 21, "");
#define WANY(i) (wsched((i) + 1) > wsched(i))
#define WPOINT(i, w) do { weight_units<wsched(i), wsched(i + 1)>(sb, &tm_g, &tm_u, &tm_d, w); } while (0)

__global__ void __launch_bounds__(NTHR, 1) __cluster_dims__(2, 1, 1)
fused_kernel(const Params p, const __grid_constant__ CUtensorMap tm_g, const __grid_constant__ CUtensorMap tm_u, const __grid_constant__ CUtensorMap tm_d, const __grid_constant__ CUtensorMap tm_x) {
    extern __shared__ __align__(1024) unsigned char smem[];
    const uint32_t sb = smem_u32(smem);
    const int tid = threadIdx.x, warp = __shfl_sync(0xffffffffu, tid >> 5, 0), lane = tid & 31;
    const int b = blockIdx.x, P = b >> 1, odd = b & 1;
    const int g = lane >> 2, t = lane & 3;
    const int wg = warp >> 2, t128 = tid & 127;
    const uint32_t s_stat = sb + SM_MISC;
    const uint32_t s_key = sb + SM_MISC + 128;
    const uint32_t s_rank = sb + SM_MISC + 256;
    const uint32_t s_k16 = sb + SM_MISC + 192;
    const uint32_t s_cnt = sb + SM_MISC + 320;
    const uint32_t bar_w = sb + SM_MISC + 328, bar_d = bar_w + 8, bar_g = bar_w + 16, bar_x = bar_w + 24, bar_v = bar_w + 32, bar_s = bar_w + 40, bar_h = bar_w + 48;
    STAMP(0);

    const int ch = wg < 4 ? 4 * b + wg : 512 + P;
    const uint32_t mo = tid < 512 ? 512 * b + tid : 65536 + 128 * P + t128, mq = (mo & ~127u) + 4 * lane;
    const uint32_t pl = ldo16(p.lar + mo), pa2 = ldo16(p.aim + mo), ldt = ldo16(p.ldt + (mo >> 7));
    const uint32_t pc = ldo16(p.cre + mo), pi = ldo16(p.cim + mo);
    const uint2 call_re = ldo64(p.cre + mq), call_im = ldo64(p.cim + mq);
    const uint32_t epl = ld_poll32(p.s->hint + (b & 7) * 32 + 1);
    if (wg < 4) {
        bar_arrive(0, NWRK);
        asm volatile("barrier.cluster.arrive.relaxed.aligned;\n" ::: "memory");
    } else {
        const int o = (4 * (warp & 3) + (g >> 1)) * 1152 + (g & 1) * 576 + t * 16;
        sts128(sb + SM_Z2 + t128 * 16, 0u, 0u, 0u, 0u); sts128(sb + SM_Z2 + 2048 + t128 * 16, 0u, 0u, 0u, 0u);
        if (warp == 16) sts128(sb + SM_Z2 + 4096 + lane * 16, 0u, 0u, 0u, 0u);
        fence_async();
        bar_sync(0, NWRK);
        STAMP(9);
#pragma unroll
        for (int c = 0; c < 9; c++)
            asm volatile("cp.async.cg.shared.global [%0], [%1], 16;\n" ::"r"(sb + SM_XT + o + c * 64), "l"(reinterpret_cast<const char*>(p.x) + b * 18432 + o + c * 64) : "memory");
        asm volatile("cp.async.commit_group;\n" ::: "memory");
        if (elect_one()) {
            mbar_init(bar_h + 8 * (warp & 3), 1);
            if (warp == 19) {
                mbar_init(bar_x, 1); mbar_init(bar_w, 1);
                mbar_expect(bar_x, 32768); mbar_expect(bar_w, 82944);
#pragma unroll
                for (int i = 2; i < 4; i++) bulk_s2g(reinterpret_cast<unsigned char*>(p.s->y) + 32 * i * 18432 + b * 4608, sb + SM_Z2, 4608);
            } else if (warp == 18) {
                mbar_init(bar_s, 1); mbar_init(bar_v, 2); mbar_init(bar_d, 1); mbar_init(bar_g, 1); mbar_init(sb + SM_RX, 1); mbar_init(sb + SM_RX + 8, 1);
                mbar_expect(bar_v, 2 * 1152); mbar_expect(bar_d, 72 * WD_PITCH); mbar_expect(bar_g, 4608); mbar_expect(sb + SM_RX, 1024); mbar_expect(sb + SM_RX + 8, 2048);
            }
            asm volatile("fence.mbarrier_init.release.cluster;\n" ::: "memory");
        }
        __syncwarp();
        asm volatile("barrier.cluster.arrive.relaxed.aligned;\n" ::: "memory");
        if (warp == 19) {
            asm volatile("barrier.cluster.wait.aligned;\n" ::: "memory");
            if (elect_one()) tma_4d_mc(sb + SM_XC + odd * 16384, &tm_x, 8 * P, 2 * odd, bar_x);
            __syncwarp();
        }
        {
            if (!(g & 1) && t == (g >> 1)) *reinterpret_cast<volatile uint32_t*>(p.s->stat + 16 * b + 4 * (warp & 3) + t) = 0u;
            if (warp < 18) {
                unsigned char* const ud = reinterpret_cast<unsigned char*>(p.s->uT) + (size_t)(8 * (warp & 1) + 2 * (g >> 1)) * 16384 + b * 128 + (g & 1) * 32 + t * 8;
#pragma unroll
                for (int k = 0; k < 4; k++) *reinterpret_cast<volatile unsigned long long*>(ud + (k >> 1) * 16384 + (k & 1) * 64) = 0ull;
            }
        }
    }
    const uint32_t kw = sb + SM_KW + wg * KW_B;
    const uint32_t tb = table_buf(sb, warp), t5 = sb + SM_WD + warp * 512;
    STAMP(29);
    const float dt = exp_bf(bf_lo(ldt));
    const uint32_t ep = __reduce_or_sync(0xffffffffu, epl);
    auto stats = [&]() {
        const int wq = warp & 3;
        const uint32_t xa = sb + SM_XT + (4 * wq + (g >> 1)) * 1152 + (g & 1) * 576 + t * 16;
        const bool own = !(g & 1) && t == (g >> 1);
        float d[4][4] = {};
        asm volatile("cp.async.wait_group 0;\n" ::: "memory");
        STAMP(26);
        uint4 v[9];
#pragma unroll
        for (int c = 0; c < 9; c++) v[c] = lds128(xa + c * 64);
#pragma unroll
        for (int c = 0; c < 9; c++) {
            mma_bf16(d[2 * (c & 1)], v[c].x, 0x3f803f80u, v[c].y, 0x3f803f80u, v[c].x, v[c].y);
            mma_bf16(d[2 * (c & 1) + 1], v[c].z, 0x3f803f80u, v[c].w, 0x3f803f80u, v[c].z, v[c].w);
        }
        STAMP(27);
        float sm = (g & 1) ? (d[0][3] + d[1][3]) + (d[2][3] + d[3][3]) : (d[0][2] + d[1][2]) + (d[2][2] + d[3][2]);
        float sq = (g & 1) ? (d[0][1] + d[1][1]) + (d[2][1] + d[3][1]) : (d[0][0] + d[1][0]) + (d[2][0] + d[3][0]);
        sm += __shfl_xor_sync(0xffffffffu, sm, 4); sq += __shfl_xor_sync(0xffffffffu, sq, 4);
        if (lane == 0) mbar_arrive(bar_h + 8 * wq);
        float mb, sd;
        ln_stats(sm, sq, mb, sd);
        if (own) p.s->stat[16 * b + 4 * wq + t] = (__float_as_uint(mb) >> 16) | (__float_as_uint(sd) & 0x7fff0000u) | (ep << 31);
        STAMPX(22);
        if (own) stat_store(s_stat + (2 * wq + (t & 1) + 8 * (t >> 1)) * 8, mb, rcp_approx(sd), 0u);
        if (wq == 3) asm volatile("cp.async.bulk.wait_group 0;\n" ::: "memory");
        bar_sync(5, 128);
        STAMP(28);
        uint32_t now;
        asm volatile("mov.u32 %0, %%clock;" : "=r"(now) :: "memory");
        if (wq == 2) {
            conv_constants(sb + SM_LC, lane);
            __syncwarp();
            if (lane < 8) p.s->key3[8 * b + lane] = ep & 1u;
            if (lane == 0) {
                sts64(s_cnt, now, ep);
                mbar_arrive(bar_s);
                bulk_g2s(sb + SM_XT + 16 * 1152, p.dsk, 1152, bar_v);
                bulk_g2s(sb + SM_XT + 17 * 1152, p.wr, 1152, bar_v);
            }
            __syncwarp();
        }
        WPOINT(1, wq == 3);
        if (wq < 2) {
            unsigned char* const ud = reinterpret_cast<unsigned char*>(p.s->uT) + (size_t)(8 * wq + 2 * (g >> 1)) * 16384 + b * 128 + (g & 1) * 32 + t * 8;
            const uint32_t utag = (ep % 7u + 1u) * 0x10001u;
            uint32_t U[2][4];
#pragma unroll
            for (int hf = 0; hf < 2; hf++) {
                const uint2 st = lds64(s_stat + (g + 8 * hf) * 8);
                const uint4 xu = lds128(sb + SM_XT + (TOK(g) + 2 * hf) * 1152 + warp * 64 + t * 16);
                const uint32_t X[4] = {xu.x, xu.y, xu.z, xu.w};
#pragma unroll
                for (int k = 0; k < 4; k++) {
                    const uint32_t u = ln_apply(X[k], STAT_M(st), STAT_H(st), STAT_L(st));
                    U[hf][k] = movm((pack_f16(bf_lo(u), bf_hi(u)) & 0xfff8fff8u) | utag);
                }
            }
#pragma unroll
            for (int k = 0; k < 4; k++) stg64(ud + (k >> 1) * 16384 + (k & 1) * 64, U[0][k], U[1][k]);
        }
    };
    STAMP(1);
    if (wg < 4) { STAMPX(16); }
    KGen kg;
    kgen_setup(kg, bf_lo(pl), bf_lo(pa2), dt);
    kgen_rows(kg, tb, lane);
    STAMP(2);
    const int E = min(max(c_exponent(call_re, call_im, dt) - 243, -120), 120);
    kgen_chain(kg, pc, pi, dt * __uint_as_float((uint32_t)(128 - E) << 23));
    STAMP(3);
    kgen_cols(kg, tb, t5, lane);
    STAMP(4);
    if (wg == 4) stats();
    if (warp != 19) asm volatile("barrier.cluster.wait.aligned;\n" ::: "memory");
    if (wg < 4) { STAMPX(17); }
    if (t128 < 2 * UPAD) sts128(sb + SM_U + wg * USLOT_B + (t128 & 1) * ULO_B + (t128 >> 1) * 16, 0u, 0u, 0u, 0u);
    if (t128 >= 124) sts128(kw + (t128 & 1) * 16 + (t128 & 2) * (KW_PL / 2), 0u, 0u, 0u, 0u);
    if (warp < 15) sts128(sb + SM_Z2 + 4608 + tid * 16, 0u, 0u, 0u, 0u);
    uint32_t co, cn, cd;
    combine_setup(sb, warp, lane, kw, co, cn, cd);
    co = pin(co); cn = pin(cn); cd = pin(cd);
    const uint4* const usrc = reinterpret_cast<const uint4*>(p.s->stat) + pin(wg < 4 ? tid : 512 + (P >> 2) * 1024 + (t128 >> 1) * 8 + (P & 3) * 2 + (t128 & 1));
    if (wg < 4) mbar_wait(bar_h + 8 * (warp & 3));
    if (wg < 4) { STAMPX(19); }
    uint32_t trel;
    asm volatile("mov.u32 %0, %%clock;" : "=r"(trel) :: "memory");
    kgen_mma(kg, tb, t5, lane);
    if (wg < 4) { STAMPX(20); }
    STAMP(5);
    uint4 uv0, uv1;
    auto first_poll = [&](uint32_t dly) {
        mbar_wait(bar_s);
        const uint32_t t0 = lds32(s_cnt);
        uint32_t now;
        do { asm volatile("mov.u32 %0, %%clock;" : "=r"(now) :: "memory"); } while (now - t0 < dly);
        uv0 = ld_poll(usrc);
    };
    if (wg == 4) { first_poll(UDLY); uv1 = ld_poll(usrc + 512); }
    WPOINT(2, warp == 19);
    auto stat_poll = [&]() {
        uint32_t now;
        do { asm volatile("mov.u32 %0, %%clock;" : "=r"(now) :: "memory"); } while (now - trel < SDLY);
        uv0 = ld_poll(usrc);
    };
    bar_sync(1 + wg, 128);
    if (wg < 4) { STAMPX(21); }
    kgen_combine(warp & 3, lane, co, cn, cd);
    STAMP(6);
    if (wg < 4) { STAMPX(18); }
    WPOINT(3, warp == 19);
    if (wg < 4) stat_poll();
    {
        const int wq = warp & 3;
        Conv c;
        const uint32_t pln = sb + SM_PL + wg * PL_B;
        const int e = g - 2 * t + 7;
        c.kw = kw; c.wa = pin(kw + ((e >> 2) & 1) * KW_PL + (8 * wq + (e >> 3)) * 16 + (e & 3) * 4);
        c.ps = mov_v(pln + wq * PLW_B + ((lane >> 3) & 1) * PL_HALF + ((lane >> 4) * 8 + (lane & 7)) * 16); c.warp = warp;
        c.lc = sb + SM_LC; c.fs = (uint32_t)(127 + E) * 0x800080u; c.yp = (ep & 1u) * (NCTA * 18432u);
        c.d0 = ((uint64_t)(ULO_B >> 4) << 16) | ((uint64_t)(128 >> 4) << 32) | (uint64_t)(((sb + SM_U + wg * USLOT_B + UPAD * 16) & 0x3FFFF) >> 4);
        unsigned char* gy = reinterpret_cast<unsigned char*>(p.s->y) + ((size_t)(4 * wq) * DM + ch) * 64;
        auto hook = [&](auto gi) {
                     constexpr int G = decltype(gi)::value;
                     if (G == (wg_is4<decltype(gi)>() ? 2 : 5)) asm volatile("barrier.cluster.wait.aligned;\n" ::: "memory");
                     if (!wg_is4<decltype(gi)>() && G == 1) mbar_wait(bar_s);
                     if (!wg_is4<decltype(gi)>() && (G == 0 || G == 2) && warp == HW && elect_one()) {
                         unsigned char* const sc = reinterpret_cast<unsigned char*>(p.s);
                         if (G == 0) {
                             if (b < 96) bulk_s2g_nc(sc + offsetof(Scratch, part) + b * 6144, sb + SM_Z2, 6144);
                             bulk_s2g(sc + offsetof(Scratch, rows) + (127 - b) * 4608, sb + SM_Z2, 4608);
                         }
                         if (G == 2) {
                             bulk_s2g(sc + offsetof(Scratch, y) + (NCTA * 18432u - c.yp) + b * 9216, sb + SM_Z2, 9216);
                         }
                     }
                     if (!wg_is4<decltype(gi)>()) WPOINT(6 + G, warp == (G >= 7 ? HW : 4 * (G % 3) + 1));
                     if (!wg_is4<decltype(gi)>() && G == 6 && warp == HW) {
                         asm volatile("cp.async.bulk.wait_group 0;\n" ::: "memory");
                         __syncwarp();
                         if (elect_one()) mbar_arrive(bar_v);
                     }
                 };
        if (wg < 4) {
            asm volatile("barrier.cluster.arrive.relaxed.aligned;\n" ::: "memory");
            conv_run(c, pln + wq * 128, gy, hook, [&]() {
                STAMPX(23);
                mbar_wait(bar_x);
                STAMPX(24);
                uint2 xc[4];
                uint32_t xw[4][2];
#pragma unroll
                for (int j = 0; j < 4; j++) xc[j] = lds64(sb + SM_XC + wg * 8192 + j * 2048 + t128 * 16 + odd * 8);
#pragma unroll
                for (int i = 0; i < 8; i++) {
                    const int k = i >> 1, h = i & 1;
                    xw[k][h] = prmt_v(k < 2 ? xc[2 * h].x : xc[2 * h].y, k < 2 ? xc[2 * h + 1].x : xc[2 * h + 1].y, (k & 1) ? 0x7632 : 0x5410);
                }
                const uint32_t ub = mov_v(sb + SM_U + UPAD * 16 + ((tid >> 1) & 1) * ULO_B + (tid >> 2) * 16 + (tid & 1) * 8), tag = ep << 31;
                int it = 0;
                while (min(min((int)(uv0.x ^ tag), (int)(uv0.y ^ tag)), min((int)(uv0.z ^ tag), (int)(uv0.w ^ tag))) < 0x10000) {
                    if (++it > SPIN_LIMIT) TRAP();
                    uv0 = ld_poll(usrc);
                }
                STAMP(8);
                STAMPX(26);
                const float r0 = rcp_approx(fabsf(bf_hi(uv0.x))), r1 = rcp_approx(fabsf(bf_hi(uv0.y))), r2 = rcp_approx(fabsf(bf_hi(uv0.z))), r3 = rcp_approx(fabsf(bf_hi(uv0.w)));
                const uint32_t m[2] = {__byte_perm(uv0.x, uv0.y, 0x5410), __byte_perm(uv0.z, uv0.w, 0x5410)};
                const uint32_t rh[2] = {pack_bf16(r0, r1), pack_bf16(r2, r3)};
                const uint32_t rl[2] = {pack_bf16(r0 - bf_lo(rh[0]), r1 - bf_hi(rh[0])), pack_bf16(r2 - bf_lo(rh[1]), r3 - bf_hi(rh[1]))};
#pragma unroll
                for (int k = 0; k < 4; k++) {
                    const uint32_t u0 = ln_apply(xw[k][0], m[0], rh[0], rl[0]), u1 = ln_apply(xw[k][1], m[1], rh[1], rl[1]);
                    sts64(ub + k * USLOT_B, pack_f16(bf_lo(u0), bf_hi(u0)), pack_f16(bf_lo(u1), bf_hi(u1)));
                }
                STAMPX(29);
                fence_async();
                bar_sync(14, 512);
                STAMP(7);
            });
        } else {
            auto stage = [&]() {
                const uint32_t tag = (ep % 7u + 1u) * 0x10001u;
                int it = 0;
                WPOINT(4, warp == 19);
                while (true) {
                    uv0.x ^= tag; uv0.y ^= tag; uv0.z ^= tag; uv0.w ^= tag; uv1.x ^= tag; uv1.y ^= tag; uv1.z ^= tag; uv1.w ^= tag;
                    if ((((uv0.x | uv0.y | uv0.z) | (uv0.w | uv1.x | uv1.y) | (uv1.z | uv1.w)) & 0x70007u) == 0) break;
                    if (++it > SPIN_LIMIT) TRAP();
                    uv0 = ld_poll(usrc); uv1 = ld_poll(usrc + 512);
                }
                STAMP(8);
                const uint32_t ub = sb + SM_U + UPAD * 16 + 4 * USLOT_B + (t128 & 1) * ULO_B + (t128 >> 1) * 16;
                sts128(ub, uv0.x, uv0.y, uv0.z, uv0.w);
                sts128(ub + 1024, uv1.x, uv1.y, uv1.z, uv1.w);
                fence_async();
                asm volatile("barrier.cluster.arrive.relaxed.aligned;\n" ::: "memory");
                bar_sync(5, 128);
                WPOINT(5, warp == 19);
                STAMP(7);
            };
            stage();
            if (odd) conv_inner(c, pln + wq * 128, gy, sb + SM_RX, hook);
            else conv_outer(c, pln + wq * 128, gy, sb + SM_RX, hook);
        }
        STAMP(10);
    }
    {
    const int lane = lane_v(), tid = 32 * warp + lane, g = lane >> 2, t = lane & 3;
    const uint32_t par = ~ep & 1u;
    bar_sync(0, NWRK);
    STAMP(11);
    uint32_t H[2][4] = {}, U2[2][4] = {};
    auto publish = [&](bool hi, int slot) {
        uint4* rowp = reinterpret_cast<uint4*>(p.s->rows) + slot * 144 + warp * 4 + t;
        stg128(rowp, nzw(hi ? U2[1][0] : U2[0][0]), nzw(hi ? U2[1][1] : U2[0][1]), nzw(hi ? U2[1][2] : U2[0][2]), nzw(hi ? U2[1][3] : U2[0][3]));
        stg128(rowp + 72, nzw(hi ? H[1][0] : H[0][0]), nzw(hi ? H[1][1] : H[0][1]), nzw(hi ? H[1][2] : H[0][2]), nzw(hi ? H[1][3] : H[0][3]));
    };
#define KTOK(k) (int)(((~(k) >> 5) & 0x7f0u) | (((k) >> 1) & 15u))
#define KLATE(k) (((k) & 0x1e0u) < 0xe0u)
#define KSLOT(k, s) (KLATE(k) ? 2 * NCTA + (s) : (int)(((k) >> 8) & 0xffu))
    const uint4* const rsrc = reinterpret_cast<const uint4*>(p.s->rows) + 36 * odd;
    auto gather = [&](uint32_t mine) {
        int it = 0;
        uint32_t mn;
        do {
            mn = 1;
#pragma unroll 1
            for (int r = 0; r < 9; r++) {
                const uint32_t k = __shfl_sync(0xffffffffu, mine, r < 8 ? 4 * r : lane);
                const int row = r < 8 ? r : g, c = r < 8 ? lane : 32 + t;
                asm volatile("cp.async.cg.shared.global [%0], [%1], 16;\n" ::"r"(sb + SM_XS + row * XS_PITCH + c * 16), "l"(rsrc + KSLOT(k, row) * 144 + c) : "memory");
            }
            asm volatile("cp.async.wait_all;\n" ::: "memory");
#pragma unroll 1
            for (int r = 0; r < 9; r++) mn = min(mn, min4(lds128(sb + SM_XS + (r < 8 ? r * XS_PITCH + lane * 16 : g * XS_PITCH + (32 + t) * 16))));
            if (++it > SPIN_LIMIT) TRAP();
        } while (__any_sync(0xffffffffu, mn == 0));
    };
    auto late_rows = [&](auto role) {
        if (decltype(role)::value == 1) {
            int it = 0;
            uint4 k[8];
            uint32_t bad;
            do {
                bad = 0;
#pragma unroll
                for (int i = 0; i < 8; i++) k[i] = ld_poll(reinterpret_cast<const uint4*>(p.s->key) + 32 * i + lane);
#pragma unroll
                for (int i = 0; i < 8; i++) bad = or3(bad, xor_or(k[i].x, k[i].y, par), xor_or(k[i].z, k[i].w, par));
                if (++it > SPIN_LIMIT) TRAP();
            } while (__any_sync(0xffffffffu, bad & 1u));
#pragma unroll 1
            for (int r = 0; r < 8; r++) {
                uint32_t c = 0;
#pragma unroll
                for (int i = 0; i < 8; i++) c = max(c, k[i].x);
                const uint32_t m = __reduce_max_sync(0xffffffffu, c);
#pragma unroll
                for (int i = 0; i < 8; i++) if (k[i].x == m) k[i] = make_uint4(k[i].y, k[i].z, k[i].w, 0u);
                if (lane == 0) sts32(s_key + r * 4, m);
            }
        }
        bar_sync(0, NWRK);
        const uint32_t kk = lds32(s_key + (lane & 7) * 4), ep = lds32(s_cnt + 4);
        const bool own = KLATE(kk) && (KTOK(kk) >> 4) == b;
        uint32_t todo = __ballot_sync(0xffffffffu, own) & 0xffu;
        if (decltype(role)::value == 0 && todo) {
#pragma unroll
            for (int hf = 0; hf < 2; hf++) {
                const uint4 h = lds128(sb + SM_U + hf * 9216 + tid * 16);
                const uint2 st = lds64(s_stat + (g + 8 * hf) * 8);
                H[hf][0] = h.x; H[hf][1] = h.y; H[hf][2] = h.z; H[hf][3] = h.w;
#pragma unroll
                for (int k = 0; k < 4; k++) U2[hf][k] = ln_apply(H[hf][k], STAT_M(st), STAT_H(st), STAT_L(st));
            }
#pragma unroll 1
            while (todo) {
                const int s = __ffs(todo) - 1, tk = KTOK(__shfl_sync(0xffffffffu, kk, s));
                todo &= todo - 1;
                if ((tk & 13) == TOK(g)) publish(tk & 2, 2 * NCTA + s);
            }
            __threadfence();
        }
        bar_sync(0, NWRK);
        if (decltype(role)::value == 1) {
            if (lane < NSEL && own) *reinterpret_cast<volatile unsigned*>(p.s->flag + lane) = ep + 1u;
            int it = 0;
            while (__any_sync(0xffffffffu, KLATE(kk) && ld_acquire32(p.s->flag + (lane & 7)) != ep + 1u)) { if (++it > SPIN_LIMIT) TRAP(); }
            gather(__shfl_sync(0xffffffffu, kk, g));
        }
        bar_sync(0, NWRK);
    };
    if (warp < 18) {
        const unsigned char* ys = reinterpret_cast<const unsigned char*>(p.s->y) + (b < 64 ? (par ^ 1u) * (NCTA * 18432u) : 0u) +
                                  ((P * DM + 32 * warp + 8 * (g >> 1) + (g & 1)) * 64 + odd * 32 + t * 8);
        mbar_wait(bar_v);
        const uint32_t xa = sb + SM_XT + warp * 64 + t * 16;
        const uint4 x0 = lds128(xa + TOK(g) * 1152), x1 = lds128(xa + (TOK(g) + 2) * 1152), dk = lds128(xa + 16 * 1152);
        uint4 wr = make_uint4(0u, 0u, 0u, 0u);
        if (g == 0) wr = lds128(xa + 17 * 1152);
        uint2 yv[4];
        const uint32_t Z[2][4] = {{x0.x, x0.y, x0.z, x0.w}, {x1.x, x1.y, x1.z, x1.w}}, D4[4] = {dk.x, dk.y, dk.z, dk.w};
#pragma unroll
        for (int hf = 0; hf < 2; hf++) {
            const uint2 st = lds64(s_stat + (g + 8 * hf) * 8);
#pragma unroll
            for (int k = 0; k < 4; k++) U2[hf][k] = hmul2_bf(ln_apply(Z[hf][k], STAT_M(st), STAT_H(st), STAT_L(st)), D4[k]);
        }
        const uint32_t la = pin(sb + SM_LNP + (g * 20 + warp) * 4);
        {
            const unsigned char* y1 = ys + (U2[0][0] & U2[1][2] & (warp >> 8));
#pragma unroll
            for (int k = 0; k < 4; k++) yv[k] = ld_poll64(y1 + k * 128);
        }
        int it = 0;
        float d[2][4];
        while (true) {
            const uint32_t mn = min3(min3(yv[0].x, yv[0].y, yv[1].x), min3(yv[1].y, yv[2].x, yv[2].y), min(yv[3].x, yv[3].y));
#pragma unroll
            for (int k = 0; k < 4; k++) {
                H[0][k] = hadd2_bf(Z[0][k], hadd2_bf(movm(yv[k].x), U2[0][k]));
                H[1][k] = hadd2_bf(Z[1][k], hadd2_bf(movm(yv[k].y), U2[1][k]));
            }
            ln_partial(H, d);
            if (!__any_sync(0xffffffffu, mn == 0)) break;
            if (++it > SPIN_LIMIT) TRAP();
#pragma unroll
            for (int k = 0; k < 4; k++) yv[k] = ld_poll64(ys + k * 128);
        }
        STAMP(12);
        {
            const float s0 = (g & 1) ? d[0][3] : d[0][2], s1 = (g & 1) ? d[1][3] : d[1][2];
            const float q0 = (g & 1) ? d[0][1] : d[0][0], q1 = (g & 1) ? d[1][1] : d[1][0];
            asm volatile("{\n.reg .pred p;\nsetp.eq.u32 p, %5, %6;\n@p st.shared.f32 [%0], %1;\n@p st.shared.f32 [%0 + 640], %2;\n@p st.shared.f32 [%0 + 1280], %3;\n@p st.shared.f32 [%0 + 1920], %4;\n}\n"
                         ::"r"(la), "f"(s0), "f"(s1), "f"(q0), "f"(q1), "r"(t), "r"(g >> 1) : "memory");
        }
        bar_arrive(6, NWRK);
        STAMP(13);
        bar_sync(7, 608);
        STAMP(14);
#pragma unroll
        for (int hf = 0; hf < 2; hf++) {
            const uint2 st = lds64(s_stat + (g + 8 * hf) * 8);
#pragma unroll
            for (int k = 0; k < 4; k++) U2[hf][k] = ln_apply(H[hf][k], STAT_M(st), STAT_H(st), STAT_L(st));
        }
        {
            float cs[4] = {0.f, 0.f, 0.f, 0.f};
            mma_bf16(cs, U2[0][0], U2[1][0], U2[0][1], U2[1][1], wr.x, wr.y);
            mma_bf16(cs, U2[0][2], U2[1][2], U2[0][3], U2[1][3], wr.z, wr.w);
            if (t == 0) { stsf(la + 32 * 80, cs[0]); stsf(la + 40 * 80, cs[2]); }
            bar_arrive(8, 608);
        }
        FIX((uint32_t)warp >> 8);
        uint32_t O[2][4];
#pragma unroll
        for (int hf = 0; hf < 2; hf++)
#pragma unroll
            for (int k = 0; k < 4; k++) { O[hf][k] = hadd2_bf(H[hf][k], U2[hf][k]); H[hf][k] = nzw(H[hf][k]); U2[hf][k] = nzw(U2[hf][k]); }
        unsigned char* rowp = reinterpret_cast<unsigned char*>(p.s->rows) + ((254 - 2 * b) * 2304 + warp * 64 + t * 16);
        FIX(and3(and3(and3(H[0][0], H[0][1], H[0][2]), and3(H[0][3], H[1][0], H[1][1]), and3(H[1][2], H[1][3], U2[0][0])),
                 and3(and3(U2[0][1], U2[0][2], U2[0][3]), and3(U2[1][0], U2[1][1], U2[1][2]), U2[1][3]), (uint32_t)reinterpret_cast<uint64_t>(rowp)));
        bar_sync(9, 608);
        {
            const uint2 best = lds64(s_rank);
#pragma unroll
            for (int hf = 0; hf < 2; hf++) {
                const uint32_t me = 2 * TOK(g) + 4 * hf;
                unsigned char* d = rowp + (best.x == me ? 2304 : 0);
                if (best.x == me || best.y == me) {
                    stg128(d, U2[hf][0], U2[hf][1], U2[hf][2], U2[hf][3]);
                    stg128(d + 1152, H[hf][0], H[hf][1], H[hf][2], H[hf][3]);
                }
            }
        }
        FIX((uint32_t)warp >> 9);
#pragma unroll
        for (int hf = 0; hf < 2; hf++) {
            sts128(sb + SM_OUT + (TOK(g) + 2 * hf) * (DM * 2) + warp * 64 + t * 16, O[hf][0], O[hf][1], O[hf][2], O[hf][3]);
            sts128(sb + SM_U + hf * 9216 + tid * 16, H[hf][0], H[hf][1], H[hf][2], H[hf][3]);
        }
        STAMP(15);
        const int mi = lane >> 3, rr = lane & 7;
        const bool gate = warp < 12 && (warp & 3) != 2;
        const int fj = gate ? 3 * (warp >> 2) + min(warp & 3, 2) : (warp < 12 ? warp >> 2 : warp - 9);
        if (gate) {
            uint32_t W[18][4];
            mbar_wait(bar_w);
            const uint32_t aad = sb + SM_WG + (mi & 1) * SM_WU + (rr + 8 * (mi >> 1)) * W_PITCH + fj * 16;
            const uint32_t bad = pin(sb + SM_XS + rr * XS_PITCH + mi * 16);
            bool rare = warp >> 8;
#pragma unroll 1
            do {
                if (rare) late_rows(IC<0>());
#pragma unroll
                for (int k = 0; k < 18; k++) ldsm_x4_t(W[k][0], W[k][1], W[k][2], W[k][3], aad + k * 16 * W_PITCH);
                if (rare) break;
                fence_async();
                STAMP2(17);
                rare = bar_or(11, NWRK, false);
            } while (rare);
            STAMP2(19);
            float c4[2][4] = {};
#pragma unroll
            for (int k = 0; k < 18; k += 2) {
                uint32_t b0, b1, b2, b3;
                ldsm_x4(b0, b1, b2, b3, bad + k * 32);
                mma_bf16(c4[0], W[k][0], W[k][1], W[k][2], W[k][3], b0, b1);
                mma_bf16(c4[1], W[k + 1][0], W[k + 1][1], W[k + 1][2], W[k + 1][3], b2, b3);
            }
            const uint32_t ex = sb + SM_EX + (32 * fj + lane) * 16;
            const float e0 = c4[0][0] + c4[1][0], e1 = c4[0][1] + c4[1][1], e2 = c4[0][2] + c4[1][2], e3 = c4[0][3] + c4[1][3];
            asm volatile("st.async.shared::cluster.mbarrier::complete_tx::bytes.v4.f32 [%0], {%1,%2,%3,%4}, [%5];\n"
                         ::"r"(ex ^ 0x1000000u), "f"(e0), "f"(e1), "f"(e2), "f"(e3), "r"(bar_g ^ 0x1000000u) : "memory");
            STAMP2(20);
            mbar_wait(bar_g);
            const uint4 o = lds128(ex);
            const uint32_t G = pack_bf16(e0 + __uint_as_float(o.x), e1 + __uint_as_float(o.y)), U = pack_bf16(e2 + __uint_as_float(o.z), e3 + __uint_as_float(o.w));
            sts32(sb + SM_GU + (32 * fj + lane) * 4, hmul2_bf(pack_bf16(bf_lo(G) * sigmoid_f(bf_lo(G)), bf_hi(G) * sigmoid_f(bf_hi(G))), U));
            bar_arrive(13, NWRK);
        } else {
            uint32_t W[2][18];
            auto load_wd = [&]() {
                mbar_wait(bar_d);
                const uint32_t base = sb + SM_WD + (4 * fj + (mi & 1)) * 16 + rr * WD_PITCH;
#pragma unroll
                for (int j = 0; j < 2; j++) {
#pragma unroll
                    for (int k = 0; k < 4; k++) ldsm_x4_t(W[j][4 * k], W[j][4 * k + 1], W[j][4 * k + 2], W[j][4 * k + 3], base + j * 32 + (k * 16 + 8 * (mi >> 1)) * WD_PITCH);
                    ldsm_x2_t(W[j][16], W[j][17], base + j * 32 + 64 * WD_PITCH);
                }
            };
            const uint32_t po = pin((((8 * (18 * odd + 2 * fj) + g) * 64 + P) * 4 + t) * 8);
            fence_async();
            STAMP2(17);
            if (bar_or(11, NWRK, false)) late_rows(IC<0>());
            delay(DDLY); load_wd();
            bar_sync(13, NWRK);
            STAMP2(21);
            uint32_t gb[9];
            ldsm_x4_t(gb[0], gb[1], gb[2], gb[3], sb + SM_GU + lane * 16);
            ldsm_x4_t(gb[4], gb[5], gb[6], gb[7], sb + SM_GU + 512 + lane * 16);
            ldsm_x1_t(gb[8], sb + SM_GU + 1024 + lane * 16);
            float c4[2][4] = {}, d4[2][4] = {};
#pragma unroll
            for (int k = 0; k < 4; k += 2)
#pragma unroll
                for (int j = 0; j < 2; j++) {
                    mma_bf16(c4[j], W[j][4 * k], W[j][4 * k + 1], W[j][4 * k + 2], W[j][4 * k + 3], gb[2 * k], gb[2 * k + 1]);
                    mma_bf16(d4[j], W[j][4 * k + 4], W[j][4 * k + 5], W[j][4 * k + 6], W[j][4 * k + 7], gb[2 * k + 2], gb[2 * k + 3]);
                }
#pragma unroll
            for (int j = 0; j < 2; j++) mma_bf16_k8(c4[j], W[j][16], W[j][17], gb[8]);
#pragma unroll
            for (int j = 0; j < 2; j++)
                stg64(reinterpret_cast<unsigned char*>(p.s->part) + po + j * 16384, nzw(pack_bf16(c4[j][0] + d4[j][0], c4[j][1] + d4[j][1])), nzw(pack_bf16(c4[j][2] + d4[j][2], c4[j][3] + d4[j][3])));
        }
        STAMP2(22);
    } else if (warp == 18) {
        const uint4* const ksrc = reinterpret_cast<const uint4*>(p.s->key3) + pin(2 * lane);
        const int row = (g >> 1) + 4 * (g & 1);
        const uint32_t ro = pin(640 * odd + t * 16), xd = pin(sb + SM_XS + row * XS_PITCH + t * 16 + (odd ? 0 : 512));
        const uint32_t xe = pin(sb + SM_XS + (g >> 1) * XS_PITCH + (lane & 7) * 16 + 64 * odd);
        const uint32_t sa = pin(sb + SM_LNP + lane * 80);
        const uint32_t klo = pin((uint32_t)(127 - b) << 9 | (uint32_t)(15 - ROWTOK(lane & 15)) << 1 | par), ra = pin(sb + SM_LNP + (32 + (lane & 15)) * 80);
        uint4* const kdst = reinterpret_cast<uint4*>(p.s->key3) + pin((lane >> 1) * 2 * NCTA + 2 * b + (lane & 1));
        FIX(ra);
        bar_sync(6, NWRK);
        {
            float mb, rc;
            ln_finish(sum18(sa), lane, mb, rc);
            if (lane < 16) stat_store(s_stat + lane * 8, mb, rc, 0u);
        }
        bar_arrive(7, 608);
        bar_sync(8, 608);
        uint32_t t0;
        {
            const uint32_t bits = __float_as_uint(rbf(sum18(ra)));
            const uint32_t me = ((bits ^ ((uint32_t)((int)bits >> 31) | 0x80000000u)) & 0xffff0000u) | klo;
            const uint32_t k0 = __reduce_max_sync(0xffffffffu, me), k1 = __reduce_max_sync(0xffffffffu, me == k0 ? 0u : me);
            const uint32_t k2 = __reduce_max_sync(0xffffffffu, me >= k1 ? 0u : me);
            if (lane < 2) stg128(kdst, k0 ^ 0x11eu, k1 ^ 0xfeu, k2 ^ 0xdeu, par);
            asm volatile("mov.u32 %0, %%clock;" : "=r"(t0) :: "memory");
            STAMPW(23);
            if (lane == 0) sts64(s_rank, ~k0 & 30u, ~k1 & 30u);
            bar_arrive(9, 608);
            sts32(s_k16 + (lane & 15) * 4, me);
            __syncwarp();
            const uint4 v = lds128(s_k16 + (lane & 16) * 2), w = lds128(s_k16 + (lane & 16) * 2 + 16);
            int rank = ((v.x > me) + (v.y > me)) + ((v.z > me) + (v.w > me)) + (((w.x > me) + (w.y > me)) + ((w.z > me) + (w.w > me)));
            rank += __shfl_xor_sync(0xffffffffu, rank, 16);
            if (lane < 16 && rank < 8) p.s->key[8 * b + rank] = (me ^ 0x1eu) | ((8 - rank) << 5);
        }
        uint4 kq[4];
        uint32_t u[4], mine = 0, m;
        int it = 0;
        { uint32_t now; do { asm volatile("mov.u32 %0, %%clock;" : "=r"(now) :: "memory"); } while (now - t0 < KDLY); }
        do {
#pragma unroll
            for (int i = 0; i < 4; i++) kq[i] = ld_poll(ksrc + 64 * i);
            if (++it > SPIN_LIMIT) TRAP();
            uint32_t S[2][4];
#pragma unroll
            for (int i = 0; i < 2; i++) {
                const uint4 &c = kq[2 * i], &d = kq[2 * i + 1];
                const uint32_t m1 = min(c.x, d.x), m2 = max(c.y, d.y);
                S[i][0] = max(c.x, d.x); S[i][1] = max(m1, m2); S[i][2] = min(m1, m2); S[i][3] = min(c.y, d.y);
            }
            const uint32_t a0 = max(S[0][0], S[1][3]), a1 = max(S[0][1], S[1][2]), a2 = max(S[0][2], S[1][1]), a3 = max(S[0][3], S[1][0]);
            const uint32_t b0 = max(a0, a2), b2 = min(a0, a2), b1 = max(a1, a3), b3 = min(a1, a3);
            u[0] = max(b0, b1); u[1] = min(b0, b1); u[2] = max(b2, b3); u[3] = min(b2, b3);
            const uint32_t bad = or3(or3(xor_or(kq[0].x, kq[0].y, par), xor_or(kq[0].z, kq[1].x, par), xor_or(kq[1].y, kq[1].z, par)),
                                     xor_or(kq[2].x, kq[2].y, par), xor_or(kq[2].z, kq[3].x, par)) | xor_or(kq[3].y, kq[3].z, par);
            m = __reduce_max_sync(0xffffffffu, u[0] | (uint32_t)((int)(bad << 31) >> 31));
        } while (m == 0xffffffffu);
        STAMPW(16);
#pragma unroll
        for (int r = 0; r < 8; r++) {
            if (r) m = __reduce_max_sync(0xffffffffu, u[0]);
            if (u[0] == m) { u[0] = u[1]; u[1] = u[2]; u[2] = u[3]; u[3] = 0; }
            if (row == r) mine = m;
        }
        uint4 v[9];
        const uint32_t o0 = __byte_perm(mine, 0, 0x4441) * 2304u, o1 = __shfl_xor_sync(0xffffffffu, o0, 4);
        const unsigned char* const rA = reinterpret_cast<const unsigned char*>(p.s->rows) + (((g & 1) ? o1 : o0) + ro + (g & 1) * 64);
        const unsigned char* const rb = reinterpret_cast<const unsigned char*>(p.s->rows) + (((g & 1) ? o0 : o1) + ro + (g & 1) * 64);
        const unsigned char* const rc = reinterpret_cast<const unsigned char*>(p.s->rows) + (o0 + ro + (odd ? -64 : 512));
#pragma unroll
        for (int i = 0; i < 4; i++) { v[i] = ld_poll(rA + i * 128); v[4 + i] = ld_poll(rb + i * 128); }
        v[8] = ld_poll(rc);
        const bool again = u[0] == 0 || max(max(kq[0].z, kq[1].z), max(kq[2].z, kq[3].z)) > m;
        if (t == 0) sts32(s_key + row * 4, mine);
#pragma unroll
        for (int i = 0; i < 9; i++) sts128(i < 8 ? xe + (i >> 2) * 4 * XS_PITCH + (i & 3) * 128 : xd, v[i].x, v[i].y, v[i].z, v[i].w);
        uint32_t mn, m3[3];
        m3[0] = m3[1] = m3[2] = 1u;
#pragma unroll
        for (int i = 0; i < 9; i++) m3[i % 3] = min3(min3(m3[i % 3], v[i].x, v[i].y), v[i].z, v[i].w);
        mn = min3(m3[0], m3[1], m3[2]);
        STAMPW(18);
        if (bar_or(11, NWRK, again || mn == 0)) late_rows(IC<1>());
    } else {
        bar_sync(6, NWRK);
        WPOINT(16, true);
        if (WANY(17) || WANY(18)) delay(WDLY);
        WPOINT(17, true);
        if (WANY(18)) delay(WDLY);
        WPOINT(18, true);
        if (bar_or(11, NWRK, false)) late_rows(IC<2>());
        const int tk = KTOK(lds32(s_key + (lane & 7) * 4));
        const uint32_t sel = __reduce_or_sync(0xffffffffu, (tk >> 4) == b ? 1u << (tk & 15) : 0u);
        if (sel ? lane < 16 && !((sel >> lane) & 1u) : lane == 0) bulk_s2g(p.out + (size_t)(16 * b + lane) * DM, sb + SM_OUT + lane * (DM * 2), sel ? DM * 2 : 16 * DM * 2);
        __syncwarp();
    }
    if (warp == 8 || warp >= 18) {
        const int grp = 3 * b + (warp == 8 ? 0 : warp - 17), fsl = 2 * t + ((lane >> 3) & 1), fc = 16 * (grp >> 3) + (grp & 7) + 8 * (lane >> 4);
        const uint32_t fk = lds32(s_key + fsl * 4);
        float hv = 0.f, u2 = 0.f;
        int it = 0;
        if (b < 96) {
            const uint32_t* const fsrc = p.s->rows + KSLOT(fk, fsl) * DM + (fc >> 1);
            uint32_t hw, uw;
            do { hw = ld_poll32(fsrc + 288); uw = ld_poll32(fsrc); if (++it > SPIN_LIMIT) TRAP(); } while (!hw || !uw);
            hv = (fc & 1) ? bf_hi(hw) : bf_lo(hw); u2 = (fc & 1) ? bf_hi(uw) : bf_lo(uw);
        }
        const float rs = rbf(sigmoid_f(__uint_as_float((fk ^ ((uint32_t)((int)~fk >> 31) | 0x80000000u)) & 0xffff0000u)));
        const uint32_t dof = pin(KTOK(fk) * DM + fc), so = pin(grp * 256 + lane);
        if (warp > 17) bar_sync(13, NWRK);
        if (b < 96) {
            delay(warp > 17 ? FDLY : FDLY2);
            float y;
            uint32_t ok;
            float s0, s1, s2, s3;
            do {
                uint2 a[8];
#pragma unroll
                for (int i = 0; i < 8; i++) a[i] = ld_poll64(reinterpret_cast<const uint2*>(p.s->part) + so + 32 * i);
                if (++it > SPIN_LIMIT) TRAP();
                ok = min3(min3(min3(a[0].x, a[0].y, a[1].x), min3(a[1].y, a[2].x, a[2].y), min3(a[3].x, a[3].y, a[4].x)), min3(min3(a[4].y, a[5].x, a[5].y), min3(a[6].x, a[6].y, a[7].x), a[7].y), 1u);
#define S8(c, f) (((c(a[0].f) + c(a[1].f)) + (c(a[2].f) + c(a[3].f))) + ((c(a[4].f) + c(a[5].f)) + (c(a[6].f) + c(a[7].f))))
                s0 = S8(bf_lo, x); s1 = S8(bf_hi, x); s2 = S8(bf_lo, y); s3 = S8(bf_hi, y);
                asm volatile("" : "+f"(s0), "+f"(s1), "+f"(s2), "+f"(s3));
#undef S8
            } while (__any_sync(0xffffffffu, !ok));
            STAMP2(24);
#define HALVE(u, v, m) (((lane & m) ? v : u) + __shfl_xor_sync(0xffffffffu, (lane & m) ? u : v, m))
            const float r0 = HALVE(s0, s2, 16), r1 = HALVE(s1, s3, 16);
            y = HALVE(r0, r1, 8);
            y += __shfl_xor_sync(0xffffffffu, y, 4);
#undef HALVE
            p.out[dof] = __float2bfloat16_rn(hv + rbf(u2 + rbf(rbf(y) * rs)));
        }
    }
    if (warp == 19) asm volatile("cp.async.bulk.wait_group.read 0;\n" ::: "memory");
    if (b == 0 && tid < 8) *reinterpret_cast<volatile unsigned*>(p.s->hint + tid * 32 + 1) = lds32(s_cnt + 4) + 1u;
    STAMP(25);
    }
}

typedef CUresult (*PFN_tmEncode)(CUtensorMap*, CUtensorMapDataType, cuuint32_t, void*, const cuuint64_t*, const cuuint64_t*, const cuuint32_t*,
                                 const cuuint32_t*, CUtensorMapInterleave, CUtensorMapSwizzle, CUtensorMapL2promotion, CUtensorMapFloatOOBfill);

extern "C" void kernel_launch(void* const* d_in, const int* in_sizes, int n_in, void* d_out, int out_size) {
    Params p;
    p.x = (const bf16*)d_in[0];
    p.lar = (const bf16*)d_in[1];
    p.aim = (const bf16*)d_in[2];
    p.cre = (const bf16*)d_in[3];
    p.cim = (const bf16*)d_in[4];
    p.ldt = (const bf16*)d_in[5];
    p.dsk = (const bf16*)d_in[6];
    p.wr = (const bf16*)d_in[8];
    p.out = (bf16*)d_out;
    static PFN_tmEncode enc = nullptr;
    static void* scratch = nullptr;
    if (!enc) {
        cudaFuncSetAttribute(fused_kernel, cudaFuncAttributeMaxDynamicSharedMemorySize, SMEM_TOTAL);
        void* fn = nullptr;
        cudaDriverEntryPointQueryResult qr;
        cudaGetDriverEntryPoint("cuTensorMapEncodeTiled", &fn, cudaEnableDefault, &qr);
        enc = (PFN_tmEncode)fn;
        cudaGetSymbolAddress(&scratch, g_scratch);
    }
    p.s = (Scratch*)scratch;
    CUtensorMap tm_g, tm_u, tm_d, tm_x;
    const cuuint64_t dims[2] = {FF, DM}, strides[1] = {FF * 2};
    const cuuint32_t box[2] = {72, 48}, es[2] = {1, 1};
    enc(&tm_g, CU_TENSOR_MAP_DATA_TYPE_BFLOAT16, 2, d_in[9], dims, strides, box, es, CU_TENSOR_MAP_INTERLEAVE_NONE, CU_TENSOR_MAP_SWIZZLE_NONE,
        CU_TENSOR_MAP_L2_PROMOTION_NONE, CU_TENSOR_MAP_FLOAT_OOB_FILL_NONE);
    enc(&tm_u, CU_TENSOR_MAP_DATA_TYPE_BFLOAT16, 2, d_in[10], dims, strides, box, es, CU_TENSOR_MAP_INTERLEAVE_NONE, CU_TENSOR_MAP_SWIZZLE_NONE,
        CU_TENSOR_MAP_L2_PROMOTION_NONE, CU_TENSOR_MAP_FLOAT_OOB_FILL_NONE);
    const cuuint64_t ddims[2] = {DM / 2, FF}, dstrides[1] = {DM * 2};
    const cuuint32_t dbox[2] = {WD_PITCH / 4, 8};
    enc(&tm_d, CU_TENSOR_MAP_DATA_TYPE_UINT32, 2, d_in[11], ddims, dstrides, dbox, es, CU_TENSOR_MAP_INTERLEAVE_NONE, CU_TENSOR_MAP_SWIZZLE_NONE,
        CU_TENSOR_MAP_L2_PROMOTION_L2_128B, CU_TENSOR_MAP_FLOAT_OOB_FILL_NONE);
    const cuuint64_t xdims[4] = {DM, 128, 4, 4}, xstrides[3] = {DM * 8, DM * 2, DM * 1024};
    const cuuint32_t xbox[4] = {8, 128, 4, 2}, xes[4] = {1, 1, 1, 1};
    enc(&tm_x, CU_TENSOR_MAP_DATA_TYPE_BFLOAT16, 4, d_in[0], xdims, xstrides, xbox, xes, CU_TENSOR_MAP_INTERLEAVE_NONE, CU_TENSOR_MAP_SWIZZLE_NONE,
        CU_TENSOR_MAP_L2_PROMOTION_NONE, CU_TENSOR_MAP_FLOAT_OOB_FILL_NONE);
    fused_kernel<<<NCTA, NTHR, SMEM_TOTAL>>>(p, tm_g, tm_u, tm_d, tm_x);
}
```

```cpp
#include <cuda_runtime.h>
#include <cuda.h>
#include <cuda_fp16.h>
#include <cuda_bf16.h>
#include <stdint.h>

#define LSEQ 2048
#define DM 576
#define NST 128
#define FF 4608
#define NSEL 8
#define NCTA 128
#define NTHR 640
#define NWRK 640

typedef __nv_bfloat16 bf16;

#define SM_WG 0
#define SM_WU 36864
#define SM_WR 73728
#define SM_XC (82944 - 32768)
#define SM_WD 82944
#define WD_PITCH 592
#define SM_Z2 (SM_WD + 10240)
#define SM_XT (SM_PL - 18 * 1152)
#define SM_PL (SM_WD + 46080)
#define PL_HALF 1344
#define PLW_B 2624
#define PL_B (4 * PLW_B)
#define SM_U (SM_PL + 5 * PL_B)
#define UPAD 20
#define ULO_B ((UPAD + 128) * 16)
#define USLOT_B (2 * ULO_B)
#define SM_KW (SM_U + 5 * USLOT_B)
#define KW_B 3712
#define KW_PL 1216
#define KW_P 2400
#define KW_H 3440
#define SM_MISC (SM_KW + 5 * KW_B)
#define SM_LC (SM_MISC + 416)
#define SM_LNP (SM_LC + 768)
#define SM_RX (SM_LNP + 3840)
#define SMEM_TOTAL (SM_RX + 3088)
#define TBW PLW_B
#define SM_OUT SM_PL
#define SM_XS (SM_PL + 18432)
#define XS_PITCH 592
#define SM_GU (SM_PL + 23296)
#define SM_EX (SM_PL + 24576)

struct __align__(128) Scratch {
    unsigned hint[8 * 32];
    unsigned flag[32];
    uint32_t key3[NCTA * 8];
    uint32_t key[NCTA * 8];
    uint32_t stat[LSEQ];
    uint32_t uT[64 * (LSEQ / 2)];
    uint32_t y[(NCTA + 96) * DM * 8];
    uint32_t part[288 * 64 * 8];
    uint32_t rows[(2 * NCTA + NSEL) * DM];
};
__device__ Scratch g_scratch;
#define STAMP(i)
#define STAMPX(i)
#define STAMPY(i)

__device__ __forceinline__ float rbf(float x) {
    uint32_t r;
    asm("cvt.rn.bf16x2.f32 %0, %1, %2;\n" : "=r"(r) : "f"(x), "f"(0.f));
    return __uint_as_float(r);
}
__device__ __forceinline__ uint32_t pack_bf16(float lo, float hi) {
    uint32_t r;
    asm("cvt.rn.bf16x2.f32 %0, %1, %2;\n" : "=r"(r) : "f"(hi), "f"(lo));
    return r;
}
__device__ __forceinline__ uint32_t pack_f16(float lo, float hi) {
    uint32_t r;
    asm("cvt.rn.f16x2.f32 %0, %1, %2;\n" : "=r"(r) : "f"(hi), "f"(lo));
    return r;
}
__device__ __forceinline__ float bf_lo(uint32_t w) { return __uint_as_float(w << 16); }
__device__ __forceinline__ float bf_hi(uint32_t w) { return __uint_as_float(w & 0xffff0000u); }
__device__ __forceinline__ uint32_t hadd2_bf(uint32_t a, uint32_t b) {
    __nv_bfloat162 r = __hadd2_rn(*reinterpret_cast<__nv_bfloat162*>(&a), *reinterpret_cast<__nv_bfloat162*>(&b));
    return *reinterpret_cast<uint32_t*>(&r);
}
__device__ __forceinline__ uint32_t hsub2_bf(uint32_t a, uint32_t b) {
    __nv_bfloat162 r = __hsub2_rn(*reinterpret_cast<__nv_bfloat162*>(&a), *reinterpret_cast<__nv_bfloat162*>(&b));
    return *reinterpret_cast<uint32_t*>(&r);
}
__device__ __forceinline__ uint32_t hmul2_bf(uint32_t a, uint32_t b) {
    __nv_bfloat162 r = __hmul2_rn(*reinterpret_cast<__nv_bfloat162*>(&a), *reinterpret_cast<__nv_bfloat162*>(&b));
    return *reinterpret_cast<uint32_t*>(&r);
}
__device__ __forceinline__ uint32_t hfma2_bf(uint32_t a, uint32_t b, uint32_t c) { uint32_t r; asm("fma.rn.bf16x2 %0, %1, %2, %3;\n" : "=r"(r) : "r"(a), "r"(b), "r"(c)); return r; }
__device__ __forceinline__ uint32_t hmul2(uint32_t a, uint32_t b) { uint32_t r; asm("mul.rn.f16x2 %0, %1, %2;\n" : "=r"(r) : "r"(a), "r"(b)); return r; }
__device__ __forceinline__ uint32_t hadd2(uint32_t a, uint32_t b) { uint32_t r; asm("add.rn.f16x2 %0, %1, %2;\n" : "=r"(r) : "r"(a), "r"(b)); return r; }
__device__ __forceinline__ uint32_t hfma2(uint32_t a, uint32_t b, uint32_t c) { uint32_t r; asm("fma.rn.f16x2 %0, %1, %2, %3;\n" : "=r"(r) : "r"(a), "r"(b), "r"(c)); return r; }
__device__ __forceinline__ uint32_t hfms2(uint32_t a, uint32_t b, uint32_t c) {
    uint32_t r;
    asm("{\n.reg .b32 n;\nneg.f16x2 n, %2;\nfma.rn.f16x2 %0, %1, n, %3;\n}\n" : "=r"(r) : "r"(a), "r"(b), "r"(c));
    return r;
}
__device__ __forceinline__ uint32_t nzw(uint32_t w) { uint32_t r; asm("max.u32 %0, %1, 1;\n" : "=r"(r) : "r"(w)); return r; }
__device__ __forceinline__ uint32_t smem_u32(const void* p) { return (uint32_t)__cvta_generic_to_shared(p); }
__device__ __forceinline__ uint32_t lds32(uint32_t addr) {
    uint32_t v;
    asm volatile("ld.shared.u32 %0, [%1];\n" : "=r"(v) : "r"(addr) : "memory");
    return v;
}
__device__ __forceinline__ uint32_t lds16(uint32_t addr) {
    unsigned short v;
    asm volatile("ld.shared.u16 %0, [%1];\n" : "=h"(v) : "r"(addr) : "memory");
    return v;
}
__device__ __forceinline__ uint2 lds64(uint32_t addr) {
    uint2 v;
    asm volatile("ld.shared.v2.u32 {%0,%1}, [%2];\n" : "=r"(v.x), "=r"(v.y) : "r"(addr) : "memory");
    return v;
}
__device__ __forceinline__ uint4 lds128(uint32_t addr) {
    uint4 v;
    asm volatile("ld.shared.v4.u32 {%0,%1,%2,%3}, [%4];\n" : "=r"(v.x), "=r"(v.y), "=r"(v.z), "=r"(v.w) : "r"(addr) : "memory");
    return v;
}
__device__ __forceinline__ void sts32(uint32_t addr, uint32_t v) { asm volatile("st.shared.u32 [%0], %1;\n" ::"r"(addr), "r"(v) : "memory"); }
__device__ __forceinline__ void sts16(uint32_t addr, uint32_t v) { asm volatile("st.shared.u16 [%0], %1;\n" ::"r"(addr), "h"((unsigned short)v) : "memory"); }
__device__ __forceinline__ void stsf(uint32_t addr, float v) { sts32(addr, __float_as_uint(v)); }
__device__ __forceinline__ void sts64(uint32_t addr, uint32_t a, uint32_t b) { asm volatile("st.shared.v2.u32 [%0], {%1,%2};\n" ::"r"(addr), "r"(a), "r"(b) : "memory"); }
__device__ __forceinline__ void sts128(uint32_t addr, uint32_t a, uint32_t b, uint32_t c, uint32_t d) {
    asm volatile("st.shared.v4.u32 [%0], {%1,%2,%3,%4};\n" ::"r"(addr), "r"(a), "r"(b), "r"(c), "r"(d) : "memory");
}
__device__ __forceinline__ void ldsm_x4(uint32_t& r0, uint32_t& r1, uint32_t& r2, uint32_t& r3, uint32_t addr) {
    asm volatile("ldmatrix.sync.aligned.m8n8.x4.shared.b16 {%0,%1,%2,%3}, [%4];\n"
                 : "=r"(r0), "=r"(r1), "=r"(r2), "=r"(r3) : "r"(addr) : "memory");
}
__device__ __forceinline__ void ldsm_x4_t(uint32_t& r0, uint32_t& r1, uint32_t& r2, uint32_t& r3, uint32_t addr) {
    asm volatile("ldmatrix.sync.aligned.m8n8.x4.trans.shared.b16 {%0,%1,%2,%3}, [%4];\n"
                 : "=r"(r0), "=r"(r1), "=r"(r2), "=r"(r3) : "r"(addr) : "memory");
}
__device__ __forceinline__ void ldsm_x2_t(uint32_t& r0, uint32_t& r1, uint32_t addr) {
    asm volatile("ldmatrix.sync.aligned.m8n8.x2.trans.shared.b16 {%0,%1}, [%2];\n" : "=r"(r0), "=r"(r1) : "r"(addr) : "memory");
}
__device__ __forceinline__ void ldsm_x1_t(uint32_t& r0, uint32_t addr) {
    asm volatile("ldmatrix.sync.aligned.m8n8.x1.trans.shared.b16 {%0}, [%1];\n" : "=r"(r0) : "r"(addr) : "memory");
}
__device__ __forceinline__ void stsm_x4(uint32_t addr, uint32_t r0, uint32_t r1, uint32_t r2, uint32_t r3) {
    asm volatile("stmatrix.sync.aligned.m8n8.x4.shared.b16 [%0], {%1,%2,%3,%4};\n" ::"r"(addr), "r"(r0), "r"(r1), "r"(r2), "r"(r3) : "memory");
}
__device__ __forceinline__ void stsm_x4_t(uint32_t addr, uint32_t r0, uint32_t r1, uint32_t r2, uint32_t r3) {
    asm volatile("stmatrix.sync.aligned.m8n8.x4.trans.shared.b16 [%0], {%1,%2,%3,%4};\n" ::"r"(addr), "r"(r0), "r"(r1), "r"(r2), "r"(r3) : "memory");
}
__device__ __forceinline__ uint32_t movm(uint32_t a) {
    uint32_t d;
    asm volatile("movmatrix.sync.aligned.m8n8.trans.b16 %0, %1;\n" : "=r"(d) : "r"(a));
    return d;
}
__device__ __forceinline__ void mma_f16(float (&c)[4], uint32_t a0, uint32_t a1, uint32_t a2, uint32_t a3, uint32_t b0, uint32_t b1) {
    asm volatile(
        "mma.sync.aligned.m16n8k16.row.col.f32.f16.f16.f32 {%0,%1,%2,%3}, {%4,%5,%6,%7}, {%8,%9}, {%0,%1,%2,%3};\n"
        : "+f"(c[0]), "+f"(c[1]), "+f"(c[2]), "+f"(c[3])
        : "r"(a0), "r"(a1), "r"(a2), "r"(a3), "r"(b0), "r"(b1));
}
__device__ __forceinline__ void mma_bf16(float (&c)[4], uint32_t a0, uint32_t a1, uint32_t a2, uint32_t a3, uint32_t b0, uint32_t b1) {
    asm volatile(
        "mma.sync.aligned.m16n8k16.row.col.f32.bf16.bf16.f32 {%0,%1,%2,%3}, {%4,%5,%6,%7}, {%8,%9}, {%0,%1,%2,%3};\n"
        : "+f"(c[0]), "+f"(c[1]), "+f"(c[2]), "+f"(c[3])
        : "r"(a0), "r"(a1), "r"(a2), "r"(a3), "r"(b0), "r"(b1));
}
__device__ __forceinline__ void mma_bf16_k8(float (&c)[4], uint32_t a0, uint32_t a1, uint32_t b0) {
    asm volatile("mma.sync.aligned.m16n8k8.row.col.f32.bf16.bf16.f32 {%0,%1,%2,%3}, {%4,%5}, {%6}, {%0,%1,%2,%3};\n"
                 : "+f"(c[0]), "+f"(c[1]), "+f"(c[2]), "+f"(c[3]) : "r"(a0), "r"(a1), "r"(b0));
}
__device__ __forceinline__ void bar_sync(int id, int n) { asm volatile("bar.sync %0, %1;\n" ::"r"(id), "r"(n) : "memory"); }
__device__ __forceinline__ void bar_arrive(int id, int n) { asm volatile("bar.arrive %0, %1;\n" ::"r"(id), "r"(n) : "memory"); }
__device__ __forceinline__ bool bar_or(int id, int n, bool v) {
    uint32_t r;
    asm volatile("{\n.reg .pred p, q;\nsetp.ne.u32 p, %3, 0;\nbar.red.or.pred q, %1, %2, p;\nselp.u32 %0, 1, 0, q;\n}\n" : "=r"(r) : "r"(id), "r"(n), "r"((uint32_t)v) : "memory");
    return r;
}
__device__ __forceinline__ uint32_t and3(uint32_t a, uint32_t b, uint32_t c) { uint32_t r; asm("lop3.b32 %0, %1, %2, %3, 0x80;\n" : "=r"(r) : "r"(a), "r"(b), "r"(c)); return r; }
__device__ __forceinline__ uint32_t or3(uint32_t a, uint32_t b, uint32_t c) { uint32_t r; asm("lop3.b32 %0, %1, %2, %3, 0xfe;\n" : "=r"(r) : "r"(a), "r"(b), "r"(c)); return r; }
__device__ __forceinline__ uint32_t min3(uint32_t a, uint32_t b, uint32_t c) { uint32_t r; asm("{\n.reg .u32 t;\nmin.u32 t, %2, %3;\nmin.u32 %0, %1, t;\n}\n" : "=r"(r) : "r"(a), "r"(b), "r"(c)); return r; }
__device__ __forceinline__ uint32_t xor_or(uint32_t a, uint32_t b, uint32_t c) { uint32_t r; asm("lop3.b32 %0, %1, %2, %3, 0x7e;\n" : "=r"(r) : "r"(a), "r"(b), "r"(c)); return r; }
__device__ __forceinline__ uint32_t pin(uint32_t v) { uint32_t r; asm volatile("shfl.sync.bfly.b32 %0, %1, 0, 0x1f, 0xffffffff;\n" : "=r"(r) : "r"(v) : "memory"); return r; }
__device__ __forceinline__ uint4 ld_poll(const void* p) {
    uint4 v;
    asm volatile("ld.relaxed.gpu.global.v4.u32 {%0,%1,%2,%3}, [%4];\n" : "=r"(v.x), "=r"(v.y), "=r"(v.z), "=r"(v.w) : "l"(p) : "memory");
    return v;
}
__device__ __forceinline__ uint2 ld_poll64(const void* p) {
    uint2 v;
    asm volatile("ld.relaxed.gpu.global.v2.u32 {%0,%1}, [%2];\n" : "=r"(v.x), "=r"(v.y) : "l"(p) : "memory");
    return v;
}
__device__ __forceinline__ uint32_t ld_poll32(const void* p) {
    uint32_t v;
    asm volatile("ld.relaxed.gpu.global.u32 %0, [%1];\n" : "=r"(v) : "l"(p) : "memory");
    return v;
}
__device__ __forceinline__ uint32_t ld_acquire32(const void* p) {
    uint32_t v;
    asm volatile("ld.acquire.gpu.global.u32 %0, [%1];\n" : "=r"(v) : "l"(p) : "memory");
    return v;
}
__device__ __forceinline__ uint2 ldo64(const void* p) {
    uint2 v;
    asm volatile("ld.relaxed.cta.global.v2.u32 {%0,%1}, [%2];\n" : "=r"(v.x), "=r"(v.y) : "l"(p) : "memory");
    return v;
}
__device__ __forceinline__ uint32_t ldo16(const void* p) {
    uint32_t v;
    asm volatile("ld.relaxed.cta.global.u16 %0, [%1];\n" : "=r"(v) : "l"(p) : "memory");
    return v;
}
__device__ __forceinline__ void stg128(void* p, uint32_t a, uint32_t b, uint32_t c, uint32_t d) {
    asm volatile("st.global.v4.u32 [%0], {%1,%2,%3,%4};\n" ::"l"(p), "r"(a), "r"(b), "r"(c), "r"(d) : "memory");
}
__device__ __forceinline__ void stg64(void* p, uint32_t a, uint32_t b) { asm volatile("st.global.v2.u32 [%0], {%1,%2};\n" ::"l"(p), "r"(a), "r"(b) : "memory"); }
__device__ __forceinline__ uint32_t min4(const uint4& v) { return min(min(v.x, v.y), min(v.z, v.w)); }
#define SPIN_LIMIT (1 << 21)
#define TRAP() __trap()
__device__ __forceinline__ void mbar_init(uint32_t bar, uint32_t cnt) { asm volatile("mbarrier.init.shared::cta.b64 [%0], %1;\n" ::"r"(bar), "r"(cnt) : "memory"); }
__device__ __forceinline__ void mbar_expect(uint32_t bar, uint32_t bytes) {
    asm volatile("mbarrier.arrive.expect_tx.shared::cta.b64 _, [%0], %1;\n" ::"r"(bar), "r"(bytes) : "memory");
}
__device__ __forceinline__ void mbar_arrive(uint32_t bar) { asm volatile("mbarrier.arrive.shared::cta.b64 _, [%0];\n" ::"r"(bar) : "memory"); }
__device__ __forceinline__ void mbar_wait(uint32_t bar) {
    asm volatile(
        "{\n.reg .pred p;\n"
        "W_%=:\n"
        "mbarrier.try_wait.parity.shared::cta.b64 p, [%0], 0;\n"
        "@!p bra W_%=;\n}\n" ::"r"(bar) : "memory");
}
__device__ __forceinline__ void bulk_g2s(uint32_t dst, const void* src, uint32_t bytes, uint32_t bar) {
    asm volatile("cp.async.bulk.shared::cluster.global.mbarrier::complete_tx::bytes [%0], [%1], %2, [%3];\n" ::"r"(dst), "l"(src), "r"(bytes), "r"(bar) : "memory");
}
__device__ __forceinline__ void bulk_s2g(void* dst, uint32_t src, uint32_t bytes) {
    asm volatile("cp.async.bulk.global.shared::cta.bulk_group [%0], [%1], %2;\ncp.async.bulk.commit_group;\n" ::"l"(dst), "r"(src), "r"(bytes) : "memory");
}
__device__ __forceinline__ void bulk_s2g_nc(void* dst, uint32_t src, uint32_t bytes) {
    asm volatile("cp.async.bulk.global.shared::cta.bulk_group [%0], [%1], %2;\n" ::"l"(dst), "r"(src), "r"(bytes) : "memory");
}
__device__ __forceinline__ void tma_2d(uint32_t dst, const CUtensorMap* tm, int c0, int c1, uint32_t bar) {
    asm volatile("cp.async.bulk.tensor.2d.shared::cluster.global.mbarrier::complete_tx::bytes [%0], [%1, {%3, %4}], [%2];\n"
                 ::"r"(dst), "l"(tm), "r"(bar), "r"(c0), "r"(c1) : "memory");
}
__device__ __forceinline__ void tma_4d_mc(uint32_t dst, const CUtensorMap* tm, int c0, int c3, uint32_t bar) {
    asm volatile("cp.async.bulk.tensor.4d.shared::cluster.global.mbarrier::complete_tx::bytes.multicast::cluster [%0], [%1, {%3, %4, %4, %5}], [%2], %6;\n"
                 ::"r"(dst), "l"(tm), "r"(bar), "r"(c0), "r"(0), "r"(c3), "h"((unsigned short)3) : "memory");
}
__device__ __forceinline__ bool elect_one() {
    uint32_t r;
    asm volatile("{\n.reg .pred p;\nelect.sync _|p, 0xffffffff;\nselp.u32 %0, 1, 0, p;\n}\n" : "=r"(r));
    return r;
}
__device__ __forceinline__ void delay(uint32_t clks) {
    uint32_t t0, t1;
    asm volatile("mov.u32 %0, %%clock;" : "=r"(t0) :: "memory");
    do { asm volatile("mov.u32 %0, %%clock;" : "=r"(t1) :: "memory"); } while (t1 - t0 < clks);
}
__device__ __forceinline__ void fence_async() { asm volatile("fence.proxy.async.shared::cta;\n" ::: "memory"); }

__device__ __forceinline__ float2 cmul(float2 a, float2 b) {
    return make_float2(fmaf(a.x, b.x, -a.y * b.y), fmaf(a.x, b.y, a.y * b.x));
}
__device__ __forceinline__ float2 csq(float2 a) {
    float p = a.x * a.y;
    return make_float2(fmaf(a.x, a.x, -a.y * a.y), p + p);
}
__device__ __forceinline__ float ex2_approx(float x) { float r; asm("ex2.approx.ftz.f32 %0, %1;\n" : "=f"(r) : "f"(x)); return r; }
__device__ __forceinline__ float exp_bf(float x) { return rbf(ex2_approx(__fmul_ru(x, 1.4426950408889634f))); }
__device__ __forceinline__ float2 cexp_e(float lr2, float li, float e) {
    const float m = ex2_approx(lr2 * e);
    return make_float2(m * __cosf(li * e), m * __sinf(li * e));
}
__device__ __forceinline__ float rcp_approx(float x) { float r; asm("rcp.approx.ftz.f32 %0, %1;\n" : "=f"(r) : "f"(x)); return r; }
__device__ __forceinline__ float sigmoid_f(float x) { return rcp_approx(1.0f + ex2_approx(x * -1.4426950408889634f)); }
__device__ __forceinline__ float sqrt_approx(float x) { float r; asm("sqrt.approx.ftz.f32 %0, %1;\n" : "=f"(r) : "f"(x)); return r; }

__device__ __forceinline__ void wg_fence() { asm volatile("wgmma.fence.sync.aligned;\n" ::: "memory"); }
__device__ __forceinline__ void wg_commit() { asm volatile("wgmma.commit_group.sync.aligned;\n" ::: "memory"); }
__device__ __forceinline__ void wg_wait0() { asm volatile("wgmma.wait_group.sync.aligned 0;\n" ::: "memory"); }
template <int T> __device__ __forceinline__ void wg_mma(float (&acc)[16][4], const uint32_t* a, uint64_t desc);
template <int T> __device__ __forceinline__ void wg_first(float (&acc)[16][4], const uint32_t* a, uint64_t desc);
template <> __device__ __forceinline__ void wg_mma<0>(float (&acc)[16][4], const uint32_t* a, uint64_t desc) {
    asm volatile("wgmma.mma_async.sync.aligned.m64n128k16.f32.f16.f16 {%0,%1,%2,%3,%4,%5,%6,%7,%8,%9,%10,%11,%12,%13,%14,%15,%16,%17,%18,%19,%20,%21,%22,%23,%24,%25,%26,%27,%28,%29,%30,%31,%32,%33,%34,%35,%36,%37,%38,%39,%40,%41,%42,%43,%44,%45,%46,%47,%48,%49,%50,%51,%52,%53,%54,%55,%56,%57,%58,%59,%60,%61,%62,%63}, {%64,%65,%66,%67}, %68, 1, 1, 1, 0;\n"
                 : "+f"(acc[0][0]), "+f"(acc[0][1]), "+f"(acc[0][2]), "+f"(acc[0][3]), "+f"(acc[1][0]), "+f"(acc[1][1]), "+f"(acc[1][2]), "+f"(acc[1][3]), "+f"(acc[2][0]), "+f"(acc[2][1]), "+f"(acc[2][2]), "+f"(acc[2][3]), "+f"(acc[3][0]), "+f"(acc[3][1]), "+f"(acc[3][2]), "+f"(acc[3][3]), "+f"(acc[4][0]), "+f"(acc[4][1]), "+f"(acc[4][2]), "+f"(acc[4][3]), "+f"(acc[5][0]), "+f"(acc[5][1]), "+f"(acc[5][2]), "+f"(acc[5][3]), "+f"(acc[6][0]), "+f"(acc[6][1]), "+f"(acc[6][2]), "+f"(acc[6][3]), "+f"(acc[7][0]), "+f"(acc[7][1]), "+f"(acc[7][2]), "+f"(acc[7][3]), "+f"(acc[8][0]), "+f"(acc[8][1]), "+f"(acc[8][2]), "+f"(acc[8][3]), "+f"(acc[9][0]), "+f"(acc[9][1]), "+f"(acc[9][2]), "+f"(acc[9][3]), "+f"(acc[10][0]), "+f"(acc[10][1]), "+f"(acc[10][2]), "+f"(acc[10][3]), "+f"(acc[11][0]), "+f"(acc[11][1]), "+f"(acc[11][2]), "+f"(acc[11][3]), "+f"(acc[12][0]), "+f"(acc[12][1]), "+f"(acc[12][2]), "+f"(acc[12][3]), "+f"(acc[13][0]), "+f"(acc[13][1]), "+f"(acc[13][2]), "+f"(acc[13][3]), "+f"(acc[14][0]), "+f"(acc[14][1]), "+f"(acc[14][2]), "+f"(acc[14][3]), "+f"(acc[15][0]), "+f"(acc[15][1]), "+f"(acc[15][2]), "+f"(acc[15][3])
                 : "r"(a[0]), "r"(a[1]), "r"(a[2]), "r"(a[3]), "l"(desc));
}
template <> __device__ __forceinline__ void wg_mma<2>(float (&acc)[16][4], const uint32_t* a, uint64_t desc) {
    asm volatile("wgmma.mma_async.sync.aligned.m64n112k16.f32.f16.f16 {%0,%1,%2,%3,%4,%5,%6,%7,%8,%9,%10,%11,%12,%13,%14,%15,%16,%17,%18,%19,%20,%21,%22,%23,%24,%25,%26,%27,%28,%29,%30,%31,%32,%33,%34,%35,%36,%37,%38,%39,%40,%41,%42,%43,%44,%45,%46,%47,%48,%49,%50,%51,%52,%53,%54,%55}, {%56,%57,%58,%59}, %60, 1, 1, 1, 0;\n"
                 : "+f"(acc[2][0]), "+f"(acc[2][1]), "+f"(acc[2][2]), "+f"(acc[2][3]), "+f"(acc[3][0]), "+f"(acc[3][1]), "+f"(acc[3][2]), "+f"(acc[3][3]), "+f"(acc[4][0]), "+f"(acc[4][1]), "+f"(acc[4][2]), "+f"(acc[4][3]), "+f"(acc[5][0]), "+f"(acc[5][1]), "+f"(acc[5][2]), "+f"(acc[5][3]), "+f"(acc[6][0]), "+f"(acc[6][1]), "+f"(acc[6][2]), "+f"(acc[6][3]), "+f"(acc[7][0]), "+f"(acc[7][1]), "+f"(acc[7][2]), "+f"(acc[7][3]), "+f"(acc[8][0]), "+f"(acc[8][1]), "+f"(acc[8][2]), "+f"(acc[8][3]), "+f"(acc[9][0]), "+f"(acc[9][1]), "+f"(acc[9][2]), "+f"(acc[9][3]), "+f"(acc[10][0]), "+f"(acc[10][1]), "+f"(acc[10][2]), "+f"(acc[10][3]), "+f"(acc[11][0]), "+f"(acc[11][1]), "+f"(acc[11][2]), "+f"(acc[11][3]), "+f"(acc[12][0]), "+f"(acc[12][1]), "+f"(acc[12][2]), "+f"(acc[12][3]), "+f"(acc[13][0]), "+f"(acc[13][1]), "+f"(acc[13][2]), "+f"(acc[13][3]), "+f"(acc[14][0]), "+f"(acc[14][1]), "+f"(acc[14][2]), "+f"(acc[14][3]), "+f"(acc[15][0]), "+f"(acc[15][1]), "+f"(acc[15][2]), "+f"(acc[15][3])
                 : "r"(a[0]), "r"(a[1]), "r"(a[2]), "r"(a[3]), "l"(desc));
}
template <> __device__ __forceinline__ void wg_mma<4>(float (&acc)[16][4], const uint32_t* a, uint64_t desc) {
    asm volatile("wgmma.mma_async.sync.aligned.m64n96k16.f32.f16.f16 {%0,%1,%2,%3,%4,%5,%6,%7,%8,%9,%10,%11,%12,%13,%14,%15,%16,%17,%18,%19,%20,%21,%22,%23,%24,%25,%26,%27,%28,%29,%30,%31,%32,%33,%34,%35,%36,%37,%38,%39,%40,%41,%42,%43,%44,%45,%46,%47}, {%48,%49,%50,%51}, %52, 1, 1, 1, 0;\n"
                 : "+f"(acc[4][0]), "+f"(acc[4][1]), "+f"(acc[4][2]), "+f"(acc[4][3]), "+f"(acc[5][0]), "+f"(acc[5][1]), "+f"(acc[5][2]), "+f"(acc[5][3]), "+f"(acc[6][0]), "+f"(acc[6][1]), "+f"(acc[6][2]), "+f"(acc[6][3]), "+f"(acc[7][0]), "+f"(acc[7][1]), "+f"(acc[7][2]), "+f"(acc[7][3]), "+f"(acc[8][0]), "+f"(acc[8][1]), "+f"(acc[8][2]), "+f"(acc[8][3]), "+f"(acc[9][0]), "+f"(acc[9][1]), "+f"(acc[9][2]), "+f"(acc[9][3]), "+f"(acc[10][0]), "+f"(acc[10][1]), "+f"(acc[10][2]), "+f"(acc[10][3]), "+f"(acc[11][0]), "+f"(acc[11][1]), "+f"(acc[11][2]), "+f"(acc[11][3]), "+f"(acc[12][0]), "+f"(acc[12][1]), "+f"(acc[12][2]), "+f"(acc[12][3]), "+f"(acc[13][0]), "+f"(acc[13][1]), "+f"(acc[13][2]), "+f"(acc[13][3]), "+f"(acc[14][0]), "+f"(acc[14][1]), "+f"(acc[14][2]), "+f"(acc[14][3]), "+f"(acc[15][0]), "+f"(acc[15][1]), "+f"(acc[15][2]), "+f"(acc[15][3])
                 : "r"(a[0]), "r"(a[1]), "r"(a[2]), "r"(a[3]), "l"(desc));
}
template <> __device__ __forceinline__ void wg_mma<6>(float (&acc)[16][4], const uint32_t* a, uint64_t desc) {
    asm volatile("wgmma.mma_async.sync.aligned.m64n80k16.f32.f16.f16 {%0,%1,%2,%3,%4,%5,%6,%7,%8,%9,%10,%11,%12,%13,%14,%15,%16,%17,%18,%19,%20,%21,%22,%23,%24,%25,%26,%27,%28,%29,%30,%31,%32,%33,%34,%35,%36,%37,%38,%39}, {%40,%41,%42,%43}, %44, 1, 1, 1, 0;\n"
                 : "+f"(acc[6][0]), "+f"(acc[6][1]), "+f"(acc[6][2]), "+f"(acc[6][3]), "+f"(acc[7][0]), "+f"(acc[7][1]), "+f"(acc[7][2]), "+f"(acc[7][3]), "+f"(acc[8][0]), "+f"(acc[8][1]), "+f"(acc[8][2]), "+f"(acc[8][3]), "+f"(acc[9][0]), "+f"(acc[9][1]), "+f"(acc[9][2]), "+f"(acc[9][3]), "+f"(acc[10][0]), "+f"(acc[10][1]), "+f"(acc[10][2]), "+f"(acc[10][3]), "+f"(acc[11][0]), "+f"(acc[11][1]), "+f"(acc[11][2]), "+f"(acc[11][3]), "+f"(acc[12][0]), "+f"(acc[12][1]), "+f"(acc[12][2]), "+f"(acc[12][3]), "+f"(acc[13][0]), "+f"(acc[13][1]), "+f"(acc[13][2]), "+f"(acc[13][3]), "+f"(acc[14][0]), "+f"(acc[14][1]), "+f"(acc[14][2]), "+f"(acc[14][3]), "+f"(acc[15][0]), "+f"(acc[15][1]), "+f"(acc[15][2]), "+f"(acc[15][3])
                 : "r"(a[0]), "r"(a[1]), "r"(a[2]), "r"(a[3]), "l"(desc));
}
template <> __device__ __forceinline__ void wg_mma<8>(float (&acc)[16][4], const uint32_t* a, uint64_t desc) {
    asm volatile("wgmma.mma_async.sync.aligned.m64n64k16.f32.f16.f16 {%0,%1,%2,%3,%4,%5,%6,%7,%8,%9,%10,%11,%12,%13,%14,%15,%16,%17,%18,%19,%20,%21,%22,%23,%24,%25,%26,%27,%28,%29,%30,%31}, {%32,%33,%34,%35}, %36, 1, 1, 1, 0;\n"
                 : "+f"(acc[8][0]), "+f"(acc[8][1]), "+f"(acc[8][2]), "+f"(acc[8][3]), "+f"(acc[9][0]), "+f"(acc[9][1]), "+f"(acc[9][2]), "+f"(acc[9][3]), "+f"(acc[10][0]), "+f"(acc[10][1]), "+f"(acc[10][2]), "+f"(acc[10][3]), "+f"(acc[11][0]), "+f"(acc[11][1]), "+f"(acc[11][2]), "+f"(acc[11][3]), "+f"(acc[12][0]), "+f"(acc[12][1]), "+f"(acc[12][2]), "+f"(acc[12][3]), "+f"(acc[13][0]), "+f"(acc[13][1]), "+f"(acc[13][2]), "+f"(acc[13][3]), "+f"(acc[14][0]), "+f"(acc[14][1]), "+f"(acc[14][2]), "+f"(acc[14][3]), "+f"(acc[15][0]), "+f"(acc[15][1]), "+f"(acc[15][2]), "+f"(acc[15][3])
                 : "r"(a[0]), "r"(a[1]), "r"(a[2]), "r"(a[3]), "l"(desc));
}
template <> __device__ __forceinline__ void wg_mma<10>(float (&acc)[16][4], const uint32_t* a, uint64_t desc) {
    asm volatile("wgmma.mma_async.sync.aligned.m64n48k16.f32.f16.f16 {%0,%1,%2,%3,%4,%5,%6,%7,%8,%9,%10,%11,%12,%13,%14,%15,%16,%17,%18,%19,%20,%21,%22,%23}, {%24,%25,%26,%27}, %28, 1, 1, 1, 0;\n"
                 : "+f"(acc[10][0]), "+f"(acc[10][1]), "+f"(acc[10][2]), "+f"(acc[10][3]), "+f"(acc[11][0]), "+f"(acc[11][1]), "+f"(acc[11][2]), "+f"(acc[11][3]), "+f"(acc[12][0]), "+f"(acc[12][1]), "+f"(acc[12][2]), "+f"(acc[12][3]), "+f"(acc[13][0]), "+f"(acc[13][1]), "+f"(acc[13][2]), "+f"(acc[13][3]), "+f"(acc[14][0]), "+f"(acc[14][1]), "+f"(acc[14][2]), "+f"(acc[14][3]), "+f"(acc[15][0]), "+f"(acc[15][1]), "+f"(acc[15][2]), "+f"(acc[15][3])
                 : "r"(a[0]), "r"(a[1]), "r"(a[2]), "r"(a[3]), "l"(desc));
}
template <> __device__ __forceinline__ void wg_mma<12>(float (&acc)[16][4], const uint32_t* a, uint64_t desc) {
    asm volatile("wgmma.mma_async.sync.aligned.m64n32k16.f32.f16.f16 {%0,%1,%2,%3,%4,%5,%6,%7,%8,%9,%10,%11,%12,%13,%14,%15}, {%16,%17,%18,%19}, %20, 1, 1, 1, 0;\n"
                 : "+f"(acc[12][0]), "+f"(acc[12][1]), "+f"(acc[12][2]), "+f"(acc[12][3]), "+f"(acc[13][0]), "+f"(acc[13][1]), "+f"(acc[13][2]), "+f"(acc[13][3]), "+f"(acc[14][0]), "+f"(acc[14][1]), "+f"(acc[14][2]), "+f"(acc[14][3]), "+f"(acc[15][0]), "+f"(acc[15][1]), "+f"(acc[15][2]), "+f"(acc[15][3])
                 : "r"(a[0]), "r"(a[1]), "r"(a[2]), "r"(a[3]), "l"(desc));
}
template <> __device__ __forceinline__ void wg_mma<14>(float (&acc)[16][4], const uint32_t* a, uint64_t desc) {
    asm volatile("wgmma.mma_async.sync.aligned.m64n16k16.f32.f16.f16 {%0,%1,%2,%3,%4,%5,%6,%7}, {%8,%9,%10,%11}, %12, 1, 1, 1, 0;\n"
                 : "+f"(acc[14][0]), "+f"(acc[14][1]), "+f"(acc[14][2]), "+f"(acc[14][3]), "+f"(acc[15][0]), "+f"(acc[15][1]), "+f"(acc[15][2]), "+f"(acc[15][3])
                 : "r"(a[0]), "r"(a[1]), "r"(a[2]), "r"(a[3]), "l"(desc));
}
template <> __device__ __forceinline__ void wg_first<0>(float (&acc)[16][4], const uint32_t* a, uint64_t desc) {
    asm volatile("wgmma.mma_async.sync.aligned.m64n128k16.f32.f16.f16 {%0,%1,%2,%3,%4,%5,%6,%7,%8,%9,%10,%11,%12,%13,%14,%15,%16,%17,%18,%19,%20,%21,%22,%23,%24,%25,%26,%27,%28,%29,%30,%31,%32,%33,%34,%35,%36,%37,%38,%39,%40,%41,%42,%43,%44,%45,%46,%47,%48,%49,%50,%51,%52,%53,%54,%55,%56,%57,%58,%59,%60,%61,%62,%63}, {%64,%65,%66,%67}, %68, 0, 1, 1, 0;\n"
                 : "=f"(acc[0][0]), "=f"(acc[0][1]), "=f"(acc[0][2]), "=f"(acc[0][3]), "=f"(acc[1][0]), "=f"(acc[1][1]), "=f"(acc[1][2]), "=f"(acc[1][3]), "=f"(acc[2][0]), "=f"(acc[2][1]), "=f"(acc[2][2]), "=f"(acc[2][3]), "=f"(acc[3][0]), "=f"(acc[3][1]), "=f"(acc[3][2]), "=f"(acc[3][3]), "=f"(acc[4][0]), "=f"(acc[4][1]), "=f"(acc[4][2]), "=f"(acc[4][3]), "=f"(acc[5][0]), "=f"(acc[5][1]), "=f"(acc[5][2]), "=f"(acc[5][3]), "=f"(acc[6][0]), "=f"(acc[6][1]), "=f"(acc[6][2]), "=f"(acc[6][3]), "=f"(acc[7][0]), "=f"(acc[7][1]), "=f"(acc[7][2]), "=f"(acc[7][3]), "=f"(acc[8][0]), "=f"(acc[8][1]), "=f"(acc[8][2]), "=f"(acc[8][3]), "=f"(acc[9][0]), "=f"(acc[9][1]), "=f"(acc[9][2]), "=f"(acc[9][3]), "=f"(acc[10][0]), "=f"(acc[10][1]), "=f"(acc[10][2]), "=f"(acc[10][3]), "=f"(acc[11][0]), "=f"(acc[11][1]), "=f"(acc[11][2]), "=f"(acc[11][3]), "=f"(acc[12][0]), "=f"(acc[12][1]), "=f"(acc[12][2]), "=f"(acc[12][3]), "=f"(acc[13][0]), "=f"(acc[13][1]), "=f"(acc[13][2]), "=f"(acc[13][3]), "=f"(acc[14][0]), "=f"(acc[14][1]), "=f"(acc[14][2]), "=f"(acc[14][3]), "=f"(acc[15][0]), "=f"(acc[15][1]), "=f"(acc[15][2]), "=f"(acc[15][3])
                 : "r"(a[0]), "r"(a[1]), "r"(a[2]), "r"(a[3]), "l"(desc));
}
template <> __device__ __forceinline__ void wg_first<4>(float (&acc)[16][4], const uint32_t* a, uint64_t desc) {
    asm volatile("wgmma.mma_async.sync.aligned.m64n96k16.f32.f16.f16 {%0,%1,%2,%3,%4,%5,%6,%7,%8,%9,%10,%11,%12,%13,%14,%15,%16,%17,%18,%19,%20,%21,%22,%23,%24,%25,%26,%27,%28,%29,%30,%31,%32,%33,%34,%35,%36,%37,%38,%39,%40,%41,%42,%43,%44,%45,%46,%47}, {%48,%49,%50,%51}, %52, 0, 1, 1, 0;\n"
                 : "=f"(acc[4][0]), "=f"(acc[4][1]), "=f"(acc[4][2]), "=f"(acc[4][3]), "=f"(acc[5][0]), "=f"(acc[5][1]), "=f"(acc[5][2]), "=f"(acc[5][3]), "=f"(acc[6][0]), "=f"(acc[6][1]), "=f"(acc[6][2]), "=f"(acc[6][3]), "=f"(acc[7][0]), "=f"(acc[7][1]), "=f"(acc[7][2]), "=f"(acc[7][3]), "=f"(acc[8][0]), "=f"(acc[8][1]), "=f"(acc[8][2]), "=f"(acc[8][3]), "=f"(acc[9][0]), "=f"(acc[9][1]), "=f"(acc[9][2]), "=f"(acc[9][3]), "=f"(acc[10][0]), "=f"(acc[10][1]), "=f"(acc[10][2]), "=f"(acc[10][3]), "=f"(acc[11][0]), "=f"(acc[11][1]), "=f"(acc[11][2]), "=f"(acc[11][3]), "=f"(acc[12][0]), "=f"(acc[12][1]), "=f"(acc[12][2]), "=f"(acc[12][3]), "=f"(acc[13][0]), "=f"(acc[13][1]), "=f"(acc[13][2]), "=f"(acc[13][3]), "=f"(acc[14][0]), "=f"(acc[14][1]), "=f"(acc[14][2]), "=f"(acc[14][3]), "=f"(acc[15][0]), "=f"(acc[15][1]), "=f"(acc[15][2]), "=f"(acc[15][3])
                 : "r"(a[0]), "r"(a[1]), "r"(a[2]), "r"(a[3]), "l"(desc));
}

#define SDLY 1300
#define UDLY 1400
#define KDLY 850
#define FDLY 950
#define FDLY2 350
#define DDLY 300
#define WDLY 500
#define HW 15
#define FIX(v) do { if ((v) == 1u) TRAP(); } while (0)
#define STAMPW(i) STAMPY(i)
#define STAMP2(i) STAMP(i)
#undef STAMPX
#define STAMPX(i)
struct Params {
    const bf16 *x, *lar, *aim, *cre, *cim, *ldt, *dsk;
    Scratch* s;
    const bf16* wr;
    bf16* out;
};
struct Maps { CUtensorMap x, w[2], r[2], d; };

#define TOK(g) (2 * (g) - ((g) & 1))
#define ROWTOK(r) (TOK((r) & 7) + (((r) >> 2) & 2))
__device__ __forceinline__ void ln_partial(const uint32_t (&H)[2][4], float (&d)[2][4]) {
#pragma unroll
    for (int i = 0; i < 8; i++) d[i >> 2][i & 3] = 0.f;
#pragma unroll
    for (int k = 0; k < 4; k++)
#pragma unroll
        for (int hf = 0; hf < 2; hf++) mma_bf16_k8(d[hf], H[hf][k], 0x3f803f80u, H[hf][k]);
}
__device__ __forceinline__ float sum18(uint32_t a) {
    const uint4 p = lds128(a), q = lds128(a + 16), r = lds128(a + 32), s = lds128(a + 48);
    const uint2 u = lds64(a + 64);
#define F(x) __uint_as_float(x)
    return (((F(p.x) + F(p.y)) + (F(p.z) + F(p.w))) + ((F(q.x) + F(q.y)) + (F(q.z) + F(q.w)))) +
           (((F(r.x) + F(r.y)) + (F(r.z) + F(r.w))) + ((F(s.x) + F(s.y)) + (F(s.z) + F(s.w))) + (F(u.x) + F(u.y)));
#undef F
}
__device__ __forceinline__ void ln_stats(float sm, float sq, float& mb, float& sd) {
    const float m0 = sm * (1.0f / 576.0f);
    const float mean = fmaf(fmaf(-m0, 576.0f, sm), 1.0f / 576.0f, m0);
    const float var = fmaxf(fmaf(-mean, mean, sq * (1.0f / 576.0f)), 0.f);
    mb = rbf(mean);
    sd = rbf(sqrt_approx(rbf(rbf(var) + 1e-5f)));
}
__device__ __forceinline__ void ln_finish(float v, int lane, float& mb, float& rc) {
    const float o = __shfl_xor_sync(0xffffffffu, v, 16);
    float sd;
    ln_stats(lane < 16 ? v : o, lane < 16 ? o : v, mb, sd);
    rc = rcp_approx(sd);
}
__device__ __forceinline__ uint32_t ln_apply(uint32_t w, uint32_t m2, uint32_t rh, uint32_t rl) {
    const uint32_t d = hsub2_bf(w, m2);
    return hfma2_bf(d, rh, hmul2_bf(d, rl));
}
__device__ __forceinline__ void stat_store(uint32_t a, float mb, float rc, uint32_t extra) {
    const float rh = rbf(rc);
    sts64(a, (__float_as_uint(mb) >> 16) | (extra << 16), pack_bf16(rh, rc - rh));
}
#define STAT_M(s) __byte_perm((s).x, (s).x, 0x1010)
#define STAT_H(s) __byte_perm((s).y, (s).y, 0x1010)
#define STAT_L(s) __byte_perm((s).y, (s).y, 0x3232)

__device__ __forceinline__ void hcmul(uint32_t re, uint32_t im, uint32_t zx, uint32_t zy, uint32_t& ore, uint32_t& oim) {
    ore = hfms2(im, zy, hmul2(re, zx));
    oim = hfma2(re, zy, hmul2(im, zx));
}

struct KGen {
    uint32_t A[2][4][4];
    float2 z1, z8, z64, z128, T[9];
};
__device__ __forceinline__ void kgen_setup(KGen& k, float lar, float aim, float dt) {
    const float lr2 = -(exp_bf(lar) * dt) * 1.4426950408889634f, li = aim * dt;
    k.z1 = cexp_e(lr2, li, 1.0f);
    k.z8 = cexp_e(lr2, li, 8.0f);
    k.z64 = cexp_e(lr2, li, 64.0f);
}
__device__ __forceinline__ void kgen_rows(KGen& k, uint32_t tb, int lane) {
    const float2 z8 = k.z8, z64 = k.z64;
    const uint32_t row = tb + lane * 16;
    k.z128 = csq(z64);
    const float2 z16 = csq(z8), z24 = cmul(z16, z8), z32 = csq(z16), z40 = cmul(z32, z8), z48 = csq(z24), z56 = cmul(z32, z24);
    uint32_t re[4], im[4], a[4], b[4];
    re[0] = pack_f16(1.0f, z8.x); im[0] = pack_f16(0.0f, z8.y);
    re[1] = pack_f16(z16.x, z24.x); im[1] = pack_f16(z16.y, z24.y);
    re[2] = pack_f16(z32.x, z40.x); im[2] = pack_f16(z32.y, z40.y);
    re[3] = pack_f16(z48.x, z56.x); im[3] = pack_f16(z48.y, z56.y);
    sts128(row, re[0], re[1], re[2], re[3]);
    sts128(row + 1024, im[0], im[1], im[2], im[3]);
    const uint32_t zx = pack_f16(z64.x, z64.x), zy = pack_f16(z64.y, z64.y), zw = pack_f16(k.z128.x, k.z128.y);
#pragma unroll
    for (int j = 0; j < 4; j++) hcmul(re[j], im[j], zx, zy, a[j], b[j]);
    sts128(row + 512, a[0], a[1], a[2], a[3]);
    sts128(row + 1536, b[0], b[1], b[2], b[3]);
    const int mi = lane >> 3;
    const uint32_t zd = tb + 2048 + mi * 16;
    sts16(tb + 2048 + lane * 2, zw); sts16(tb + 2112 + lane * 2, zw >> 16);
    __syncwarp();
    const uint32_t ad = tb + (lane & 7) * 16 + mi * 512;
    ldsm_x4(a[0], a[1], a[2], a[3], zd);
    ldsm_x4(b[0], b[1], b[2], b[3], zd + 64);
#pragma unroll
    for (int ks = 0; ks < 4; ks++) {
        ldsm_x4_t(k.A[0][ks][0], k.A[0][ks][1], k.A[0][ks][2], k.A[0][ks][3], ad + ks * 128);
        hcmul(k.A[0][ks][0], k.A[0][ks][2], a[ks], b[ks], k.A[1][ks][0], k.A[1][ks][2]);
        hcmul(k.A[0][ks][1], k.A[0][ks][3], a[ks], b[ks], k.A[1][ks][1], k.A[1][ks][3]);
    }
}
__device__ __forceinline__ void kgen_chain(KGen& k, uint32_t cr, uint32_t ci, float cs) {
    k.T[0] = make_float2(bf_lo(cr) * cs, -bf_lo(ci) * cs);
    const float2 y1 = make_float2(k.z1.x, -k.z1.y);
#pragma unroll
    for (int c = 1; c < 8; c++) k.T[c] = cmul(k.T[c - 1], y1);
    k.T[8] = cmul(k.T[0], make_float2(k.z8.x, -k.z8.y));
}
__device__ __forceinline__ void kgen_cols(KGen& k, uint32_t tb, uint32_t t5, int lane) {
    const uint32_t row = tb + lane * 16;
    const float2 (&T)[9] = k.T;
    const float2 y128 = make_float2(k.z128.x, -k.z128.y);
    const float2 y256 = csq(y128), y512 = csq(y256), y768 = cmul(y512, y256), y1024 = csq(y512);
    const float2 c1032 = cmul(T[8], y1024);
    __syncwarp();
    sts128(row, pack_f16(T[0].x, T[1].x), pack_f16(T[2].x, T[3].x), pack_f16(T[4].x, T[5].x), pack_f16(T[6].x, T[7].x));
    sts128(row + 512, pack_f16(T[0].y, T[1].y), pack_f16(T[2].y, T[3].y), pack_f16(T[4].y, T[5].y), pack_f16(T[6].y, T[7].y));
    uint32_t a[4], b[4];
    {
        const uint32_t zx = pack_f16(y256.x, y256.x), zy = pack_f16(y256.y, y256.y);
        hcmul(pack_f16(T[0].x, T[2].x), pack_f16(T[0].y, T[2].y), zx, zy, a[0], b[0]);
        hcmul(pack_f16(T[4].x, T[6].x), pack_f16(T[4].y, T[6].y), zx, zy, a[1], b[1]);
        const uint32_t r04 = pack_f16(T[0].x, T[4].x), i04 = pack_f16(T[0].y, T[4].y);
        hcmul(r04, i04, pack_f16(y512.x, y512.x), pack_f16(y512.y, y512.y), a[2], b[2]);
        hcmul(r04, i04, pack_f16(y768.x, y768.x), pack_f16(y768.y, y768.y), a[3], b[3]);
    }
    sts128(row + 1024, a[0], a[1], a[2], a[3]);
    sts128(row + 1536, b[0], b[1], b[2], b[3]);
    {
        const uint32_t r0 = pack_f16(1.0f, y256.x), i0 = pack_f16(0.0f, y256.y), r1 = pack_f16(y512.x, y768.x), i1 = pack_f16(y512.y, y768.y);
        const uint32_t zx = pack_f16(T[8].x, T[8].x), zy = pack_f16(T[8].y, T[8].y), wx = pack_f16(c1032.x, c1032.x), wy = pack_f16(c1032.y, c1032.y);
        hcmul(r0, i0, zx, zy, a[0], b[0]); hcmul(r1, i1, zx, zy, a[1], b[1]);
        hcmul(r0, i0, wx, wy, a[2], b[2]); hcmul(r1, i1, wx, wy, a[3], b[3]);
    }
    sts128(row + 2048, a[0], a[1], a[2], a[3]);
    sts128(t5 + lane * 16, b[0], b[1], b[2], b[3]);
}
__device__ __forceinline__ void kgen_mma(const KGen& k, uint32_t tb, uint32_t t5, int lane) {
    __syncwarp();
    float acc[2][3][4];
#pragma unroll
    for (int i = 0; i < 6; i++)
#pragma unroll
        for (int j = 0; j < 4; j++) acc[i / 3][i % 3][j] = 0.f;
    const int mi = lane >> 3;
    const uint32_t ro = ((lane & 7) + 8 * (mi >> 1)) * 16, bd = tb + ro + (mi & 1) * 512, b2 = ro + ((mi & 1) ? t5 : tb + 2048);
#pragma unroll
    for (int kp = 0; kp < 2; kp++)
#pragma unroll
        for (int j = 0; j < 3; j++) {
            uint32_t b[4];
            ldsm_x4_t(b[0], b[1], b[2], b[3], (j < 2 ? bd + j * 1024 : b2) + kp * 256);
#pragma unroll
            for (int h = 0; h < 2; h++)
#pragma unroll
                for (int m = 0; m < 2; m++) {
                    const uint32_t (&A)[4] = k.A[m][2 * kp + h];
                    mma_f16(acc[m][j], A[0], A[1], A[2], A[3], b[2 * h], b[2 * h + 1]);
                }
        }
    __syncwarp();
#define PK(j) pack_f16(acc[0][j][0], acc[0][j][1]), pack_f16(acc[0][j][2], acc[0][j][3]), pack_f16(acc[1][j][0], acc[1][j][1]), pack_f16(acc[1][j][2], acc[1][j][3])
    stsm_x4(tb + lane * 16, PK(0));
    stsm_x4(tb + 512 + lane * 16, PK(1));
    stsm_x4_t(tb + 1024 + (lane & 7) * 80 + mi * 16, PK(2));
#undef PK
}
__device__ __forceinline__ uint32_t table_buf(uint32_t sb, int warp) { return sb + SM_PL + warp * TBW; }

__device__ __forceinline__ uint4 lds16x4(uint32_t a) { return make_uint4(lds16(a), lds16(a + TBW), lds16(a + 2 * TBW), lds16(a + 3 * TBW)); }
__device__ __forceinline__ void combine_setup(uint32_t sb, int warp, int lane, uint32_t kw, uint32_t& o, uint32_t& n, uint32_t& d) {
    const int wq = warp & 3;
    const uint32_t a = table_buf(sb, warp & ~3);
    o = wq == 3 ? a + 1024 + 320 + (lane >> 3) * 80 + (lane & 7) * 8 : a + (wq ? 504 + wq * 8 : 0) + lane * 16;
    n = a + 1024 + wq * 80 + lane * 2;
    d = wq < 3 ? kw + (wq == 2 ? KW_P : 32 + wq * 512) + lane * 16 : kw + KW_H + 8 + lane * 8;
}
__device__ __forceinline__ void kgen_combine(int wq, int lane, uint32_t o, uint32_t na, uint32_t d) {
#define S4(f) hadd2(hadd2(u.f, v.f), hadd2(w.f, x.f))
#define H4(v) hadd2(hadd2(v.x, v.y), hadd2(v.z, v.w))
#define BP __byte_perm
    if (wq == 0) {
        const uint4 u = lds128(o), v = lds128(o + TBW), w = lds128(o + 2 * TBW), x = lds128(o + 3 * TBW), nn = lds16x4(na);
        const uint32_t n = H4(nn), k0 = S4(x), k2 = S4(y), k4 = S4(z), k6 = S4(w);
        sts128(d, BP(k0, k0, 0x1032), BP(k0, k2, 0x3254), BP(k2, k2, 0x1032), BP(k2, k4, 0x3254));
        sts128(d + KW_PL, BP(k4, k4, 0x1032), BP(k4, k6, 0x3254), BP(k6, k6, 0x1032), BP(k6, n, 0x3254));
        if (lane == 0) sts32(d + KW_PL - 4, k0 & 0xffffu);
    } else {
        const uint2 u = lds64(o), v = lds64(o + TBW), w = lds64(o + 2 * TBW), x = lds64(o + 3 * TBW);
        uint4 nn = make_uint4(0u, 0u, 0u, 0u), mm = nn;
        if (wq < 3) nn = lds16x4(na);
        if (wq == 2) mm = lds16x4(na + 80);
        const uint32_t k0 = S4(x), k2 = S4(y), n = H4(nn), m = H4(mm);
        if (wq == 3) {
            sts64(d, k0, k2);
        } else if (wq == 1) {
            const uint32_t cc = BP(k2, k2, 0x1010);
            sts128(d, BP(k0, k0, 0x1010), BP(k0, k0, 0x1032), BP(k0, k2, 0x3254), cc);
            sts128(d + KW_PL, cc, BP(k2, k2, 0x1032), BP(k2, n, 0x3254), BP(n, n, 0x1010));
        } else {
            const uint32_t w40 = BP(k0, k0, 0x1032), w84 = BP(k0, n, 0x3254), w0 = BP(k0, k0, 0x1010), w4 = BP(k0, k0, 0x3232), w8 = BP(n, n, 0x1010);
            sts64(d, w40, w84);
            sts64(d + 512, BP(k2, k2, 0x1032), BP(k2, m, 0x3254));
            if (lane < 8) { sts128(d - (KW_P - 1056), w0, w0, w40, w4); sts128(d - (KW_P - 1056 - KW_PL), w4, w84, w8, w8); }
            if (lane == 31) sts16(d + (KW_H + 6 - KW_P - 496), m);
        }
    }
#undef S4
#undef H4
#undef BP
}

__device__ __forceinline__ int c_exponent(const uint2& r, const uint2& i, float dt) {
    const uint32_t mx = __vmaxu2(__vmaxu2(r.x & 0x7fff7fffu, r.y & 0x7fff7fffu), __vmaxu2(i.x & 0x7fff7fffu, i.y & 0x7fff7fffu));
    return __reduce_max_sync(0xffffffffu, max(mx, mx << 16) + (__float_as_uint(dt) & 0x7f800000u)) >> 23;
}

__device__ __forceinline__ int lane_v() { int l; asm volatile("mov.u32 %0, %%laneid;" : "=r"(l)); return l; }
__device__ __forceinline__ uint32_t prmt_v(uint32_t a, uint32_t b, uint32_t s) { uint32_t d; asm volatile("prmt.b32 %0, %1, %2, %3;\n" : "=r"(d) : "r"(a), "r"(b), "r"(s)); return d; }
__device__ __forceinline__ uint32_t mov_v(uint32_t a) { uint32_t d; asm volatile("mov.b32 %0, %1;\n" : "=r"(d) : "r"(a)); return d; }
template <int G>
__device__ __forceinline__ void conv_rename(float (&acc)[16][4]) {
#pragma unroll
    for (int i = G; i < 16; i++)
#pragma unroll
        for (int j = 0; j < 4; j++) { float v; asm volatile("mov.b32 %0, %1;\n" : "=f"(v) : "f"(acc[i][j])); acc[i][j] = v; }
}
struct Conv {
    uint32_t kw;
    uint32_t wa;
    uint32_t pa, s2;
    uint32_t s8;
    uint32_t id;
    uint32_t lc;
    uint32_t fs;
    uint32_t fl, yo;
    uint32_t yp;
    size_t ycopy;
    uint32_t ps;
    uint64_t d0;
    int warp;
};
struct Pk { uint32_t w[4]; };
__device__ __forceinline__ Pk pk2(const float (&u)[4], const float (&v)[4]) {
    Pk r;
    r.w[0] = pack_f16(u[0], u[1]); r.w[1] = pack_f16(u[2], u[3]); r.w[2] = pack_f16(v[0], v[1]); r.w[3] = pack_f16(v[2], v[3]);
    return r;
}
__device__ __forceinline__ void park(uint32_t a, const Pk& v) {
    asm volatile("stmatrix.sync.aligned.m8n8.x4.trans.shared.b16 [%0], {%1,%2,%3,%4};\n" ::"r"(a), "r"(v.w[0]), "r"(v.w[1]), "r"(v.w[2]), "r"(v.w[3]) : "memory");
}
__device__ __forceinline__ void conv_constants(uint32_t lc, int l) {
    const int d = (l >> 2) - 2 * (l & 3);
    const int e = d + 8, r4 = (e + 1 + ((e >> 2) & 1)) >> 2, p4 = (e + (((e - 1) >> 2) & 1)) >> 2;
    const uint32_t s2 = r4 == p4 ? 0x1010u : 0x3210u;
    sts64(lc + l * 8, KW_P + ((r4 - 5) >> 1) * 16 + ((r4 - 5) & 1) * 4, s2 | ((d < 0 ? s2 : 0x7654u) << 16));
    const int lo = (d >= 4) - (d < -3), ho = (d >= 5) - (d < -2), le = (d > 4) - (d < -4), he = (d > 5) - (d < -3);
    sts32(lc + 512 + l * 8, (0x5454u + lo * 0x22 + ho * 0x2200) | ((0x3232u + le * 0x22 + he * 0x2200) << 16));
    const int cc = l >> 2, j = l & 3;
    sts64(lc + 256 + l * 8, (j >> 1) * PL_HALF + (16 + cc) * 16 + (j & 1) * 8, (cc >> 1) * (DM * 64) + (cc & 1) * 32 + j * 8);
}
__device__ __forceinline__ void conv_selectors4(Conv& c) {
    const uint2 v = lds64(c.lc + lane_v() * 8);
    c.pa = v.x; c.s2 = v.y;
}
__device__ __forceinline__ void conv_selectors8(Conv& c) { c.s8 = lds32(c.lc + 512 + lane_v() * 8); }
template <int G, int I0, int I1>
__device__ __forceinline__ void conv_load(const Conv& c, uint32_t (&q)[9]) {
    const int wq = c.warp & 3;
    if (G < 2) {
#pragma unroll
        for (int i = I0; i < I1; i++) q[i] = lds32(c.wa + G * 512 + i * 16);
    } else if (G < 4) {
        const uint32_t a = (G == 2 && wq == 0) ? c.wa + 1024 : c.pa + c.kw + wq * 128 + (G < 2 ? 0 : G - 2) * 512;
#pragma unroll
        for (int i = I0; i < I1; i++) q[i] = lds32(a + i * 16);
    } else {
        const uint4 u = lds128(c.kw + KW_H + (G < 4 ? 0 : G - 4) * 64 + wq * 16);
        const uint2 v = lds64(c.kw + KW_H + (G < 4 ? 0 : G - 4) * 64 + wq * 16 + 16);
        q[0] = u.x; q[1] = u.y; q[2] = u.z; q[3] = u.w; q[4] = v.x; q[5] = v.y;
        if (G == 4 && wq == 0) { q[6] = lds32(c.pa + c.kw + 1024); q[7] = lds32(c.pa + c.kw + 1040); }
    }
}
template <int G, int J0, int J1>
__device__ __forceinline__ void conv_frag(const Conv& c, const uint32_t (&q)[9], uint32_t* a, const Pk& dp) {
    const uint32_t dep = dp.w[0];
    if (G < 4) {
        const uint32_t s = (G < 2 || (G == 2 && (c.warp & 3) == 0)) ? c.id : c.s2;
#pragma unroll
        for (int j = J0; j < J1; j++) {
            uint32_t* o = a + 4 * (j - J0);
            o[0] = prmt_v(q[2 * j + 1], dp.w[0], s); o[1] = prmt_v(q[2 * j + 2], dp.w[1], s); o[2] = prmt_v(q[2 * j], dp.w[2], s); o[3] = prmt_v(q[2 * j + 1], dp.w[3], s);
        }
    } else {
        const uint32_t so = prmt_v(c.s8, dep, c.id), se = prmt_v(c.s8, dep, c.id + 0x22);
#pragma unroll
        for (int j = J0; j < J1; j++) {
            uint32_t* o = a + 4 * (j - J0);
            o[0] = prmt_v(q[j + 1], q[j + 2], se); o[1] = prmt_v(q[j + 1], q[j + 2], so); o[2] = prmt_v(q[j], q[j + 1], so);
            if (G == 4 && j == 0 && (c.warp & 3) == 0) {
                o[2] = prmt_v(q[6], dep, c.s2);
                o[0] = prmt_v(q[7], o[0], c.s2 >> 16);
            }
            o[3] = mov_v(o[0]);
        }
    }
}
template <int G, int J0, int J1>
__device__ __forceinline__ void conv_frag(const Conv& c, const uint32_t (&q)[9], uint32_t* a, float depf) {
    const uint32_t d = __float_as_uint(depf);
    conv_frag<G, J0, J1>(c, q, a, Pk{{d, d, d, d}});
}
template <int G, int T, int J0, int J1>
__device__ __forceinline__ void conv_mma(float (&acc)[16][4], const Conv& c, const uint32_t* a) {
#pragma unroll
    for (int j = J0; j < J1; j++) wg_mma<T>(acc, a + 4 * (j - J0), c.d0 - 8 * (2 * G - T) - j);
}
__device__ __forceinline__ float h_lo(uint32_t w) { return __half2float(__ushort_as_half((unsigned short)(w & 0xffffu))); }
__device__ __forceinline__ float h_hi(uint32_t w) { return __half2float(__ushort_as_half((unsigned short)(w >> 16))); }
__device__ __forceinline__ void flush_setup(Conv& c) {
    const uint2 v = lds64(c.lc + 256 + lane_v() * 8);
    c.fl = v.x; c.yo = v.y;
}
template <int Q>
__device__ __forceinline__ void flush_load(const Conv& c, uint32_t pl, uint2 (&f)[4]) {
#pragma unroll
    for (int w = 0; w < 4; w++) f[w] = lds64(c.fl + pl + (Q & 1) * 512 + w * (PLW_B - 64));
}
template <int Q>
__device__ __forceinline__ void flush_load_first(const Conv& c, uint32_t pl, uint2 (&f)[4], float depf) {
    const uint32_t p = prmt_v(c.fl, __float_as_uint(depf), c.id) + pl + (Q & 1) * 512;
#define LDV64(d, a) asm volatile("ld.volatile.shared.v2.u32 {%0,%1}, [%2];\n" : "=r"(d.x), "=r"(d.y) : "r"(a) : "memory")
    LDV64(f[0], p); LDV64(f[1], p + (PLW_B - 64)); LDV64(f[2], p + 2 * (PLW_B - 64)); LDV64(f[3], p + 3 * (PLW_B - 64));
}
#define FDEP __uint_as_float(f[3].y)
template <int Q, int mode>
__device__ __forceinline__ void conv_flush(const Conv& c, const uint2 (&f)[4], unsigned char* gy, uint32_t rx) {
    const uint32_t a0 = hadd2(f[0].x, f[1].x), a1 = hadd2(f[2].x, f[3].x), b0 = hadd2(f[0].y, f[1].y), b1 = hadd2(f[2].y, f[3].y);
    if (Q > 0 && mode == 1) {
        const uint32_t ra = rx + 16 + (Q > 0 ? Q - 1 : 0) * 1024 + (c.warp & 3) * 256 + lane_v() * 8;
        asm volatile("st.async.shared::cluster.mbarrier::complete_tx::bytes.v2.b32 [%0], {%1,%2}, [%3];\n"
                     ::"r"(ra ^ 0x1000000u), "r"(hadd2(a0, a1)), "r"(hadd2(b0, b1)), "r"((rx + (Q > 1 ? 8 : 0)) ^ 0x1000000u) : "memory");
        return;
    }
    float v0 = h_lo(a0) + h_lo(a1), v1 = h_hi(a0) + h_hi(a1), v2 = h_lo(b0) + h_lo(b1), v3 = h_hi(b0) + h_hi(b1);
    if (Q > 0 && mode == 2) {
        const uint2 o = lds64(rx + 16 + (Q > 0 ? Q - 1 : 0) * 1024 + (c.warp & 3) * 256 + lane_v() * 8);
        v0 += h_lo(o.x); v1 += h_hi(o.x); v2 += h_lo(o.y); v3 += h_hi(o.y);
    }
    const uint32_t lo = hmul2_bf(pack_bf16(v0, v1), c.fs), hi = hmul2_bf(pack_bf16(v2, v3), c.fs);
    stg64(gy + Q * 32 * DM * 32 + (c.yo + (Q < 2 ? c.yp : 0u)), nzw(lo), nzw(hi));
}
template <int I, bool S = false> struct IC { static constexpr int value = I; static constexpr bool shared = S; };
template <class T> __device__ constexpr bool wg_is4() { return T::shared; }
#define SLOT(n) (c.ps + (2 + ((n) & 7)) * 128)
#define GO() do { wg_commit(); __syncwarp(); } while (0)
#define DEP acc[15][3]
template <class FG, class FP, class FN>
__device__ __forceinline__ void conv_head(Conv& c, float (&acc)[16][4], uint32_t (&q)[9], uint32_t (&r)[9], uint32_t* a, FG fg, FP pre, FN next) {
    c.id = 0x3210u + (c.warp >> 8);
    pre();
    conv_load<0, 0, 9>(c, q);
    conv_frag<0, 0, 1>(c, q, a, 0.f);
    wg_fence(); wg_first<0>(acc, a, c.d0); GO();
    park(c.ps, Pk{{0u, 0u, 0u, 0u}});
    wg_wait0();
    conv_frag<0, 1, 2>(c, q, a, DEP);
    wg_fence(); conv_mma<0, 0, 1, 2>(acc, c, a); GO();
    fg(IC<0>());
    wg_wait0();
    conv_frag<0, 2, 3>(c, q, a, DEP);
    wg_fence(); conv_mma<0, 0, 2, 3>(acc, c, a); GO();
    conv_load<1, 0, 5>(c, r);
    wg_wait0();
    conv_frag<0, 3, 4>(c, q, a, DEP);
    wg_fence(); conv_mma<0, 0, 3, 4>(acc, c, a); GO();
    conv_load<1, 5, 9>(c, r);
    fg(IC<1>());
    wg_wait0();
    const Pk k = pk2(acc[0], acc[1]);
    conv_rename<2>(acc);
    conv_frag<1, 0, 2>(c, r, a, k);
    wg_fence(); conv_mma<1, 2, 0, 2>(acc, c, a); GO();
    park(SLOT(0), k);
    next(IC<0>());
    fg(IC<2>());
    wg_wait0();
    conv_frag<1, 2, 4>(c, r, a, DEP);
    wg_fence(); conv_mma<1, 2, 2, 4>(acc, c, a); GO();
    next(IC<1>());
    fg(IC<3>());
    wg_wait0();
}
template <class FG, class FP>
__device__ __forceinline__ void conv_run(Conv& c, uint32_t pl, unsigned char* gy, FG fg, FP pre) {
    float acc[16][4];
    uint32_t q[9], r[9], a[32];
    uint2 f[4];
    const int bid = 1 + (c.warp >> 2);
    conv_head(c, acc, q, r, a, fg, pre, [&](auto i) { if (decltype(i)::value == 0) conv_selectors4(c); else conv_load<2, 0, 9>(c, q); });
    Pk k = pk2(acc[2], acc[3]);
    conv_rename<4>(acc);
    conv_frag<2, 0, 4>(c, q, a, k);
    wg_fence(); conv_mma<2, 4, 0, 4>(acc, c, a); GO();
    park(SLOT(2), k);
    conv_load<3, 0, 9>(c, q);
    flush_setup(c);
    bar_sync(bid, 128);
    fg(IC<4>());
    wg_wait0();
    conv_rename<6>(acc);
    conv_frag<3, 0, 4>(c, q, a, DEP);
    wg_fence(); conv_mma<3, 6, 0, 4>(acc, c, a); GO();
    park(SLOT(4), pk2(acc[4], acc[5]));
    conv_load<4, 0, 9>(c, q);
    conv_selectors8(c);
    flush_load<0>(c, pl, f);
    conv_flush<0, 0>(c, f, gy, 0u);
    fg(IC<5>());
    wg_wait0();
    conv_rename<8>(acc);
    conv_frag<4, 0, 4>(c, q, a, DEP);
    wg_fence(); conv_mma<4, 8, 0, 4>(acc, c, a); GO();
    k = pk2(acc[6], acc[7]);
    park(SLOT(6), k);
    conv_load<5, 0, 9>(c, q);
    bar_sync(bid, 128);
    park(c.ps, k);
    fg(IC<6>());
    wg_wait0();
    conv_rename<10>(acc);
    flush_load_first<1>(c, pl, f, DEP);
    conv_frag<5, 0, 4>(c, q, a, FDEP);
    wg_fence(); conv_mma<5, 10, 0, 4>(acc, c, a); GO();
    park(SLOT(8), pk2(acc[8], acc[9]));
    conv_load<6, 0, 9>(c, q); conv_load<7, 0, 9>(c, r);
    conv_flush<1, 0>(c, f, gy, 0u);
    fg(IC<7>());
    wg_wait0();
    conv_rename<12>(acc);
    conv_frag<6, 0, 4>(c, q, a, DEP); conv_frag<7, 0, 4>(c, r, a + 16, DEP);
    wg_fence(); conv_mma<6, 12, 0, 4>(acc, c, a); conv_mma<7, 12, 0, 4>(acc, c, a + 16); GO();
    park(SLOT(10), pk2(acc[10], acc[11]));
    bar_sync(bid, 128);
    flush_load<2>(c, pl, f);
    conv_flush<2, 0>(c, f, gy, 0u);
    fg(IC<8>());
    if (c.id == 0) TRAP();
    wg_wait0();
    park(SLOT(12), pk2(acc[12], acc[13])); park(SLOT(14), pk2(acc[14], acc[15]));
    bar_sync(bid, 128);
    flush_load<3>(c, pl, f);
    conv_flush<3, 0>(c, f, gy, 0u);
}
template <class FG>
__device__ __forceinline__ void conv_outer(Conv& c, uint32_t pl, unsigned char* gy, uint32_t rx, FG fg) {
    float acc[16][4];
    uint32_t q[9], r[9], a[32];
    uint2 f[4], f2[4];
    const int bid = 1 + (c.warp >> 2);
    conv_head(c, acc, q, r, a, [&](auto gi) { if (decltype(gi)::value == 2) fg(IC<2, true>()); }, [&]() {}, [&](auto i) { if (decltype(i)::value == 0) conv_selectors8(c); else conv_load<6, 0, 9>(c, q); });
    park(SLOT(2), pk2(acc[2], acc[3])); park(SLOT(4), pk2(acc[4], acc[5]));
    const Pk k = pk2(acc[6], acc[7]);
    park(SLOT(6), k);
    conv_load<7, 0, 9>(c, r);
    conv_rename<12>(acc);
    conv_frag<6, 0, 4>(c, q, a, __uint_as_float(k.w[3])); conv_frag<7, 0, 4>(c, r, a + 16, __uint_as_float(k.w[3]));
    wg_fence(); conv_mma<6, 12, 0, 4>(acc, c, a); conv_mma<7, 12, 0, 4>(acc, c, a + 16); GO();
    flush_setup(c);
    bar_sync(bid, 128);
    flush_load<0>(c, pl, f); flush_load<1>(c, pl, f2);
    conv_flush<1, 1>(c, f2, gy, rx);
    conv_flush<0, 1>(c, f, gy, rx);
    wg_wait0();
    bar_sync(bid, 128);
    park(c.ps, k); park(SLOT(8), pk2(acc[8], acc[9])); park(SLOT(10), pk2(acc[10], acc[11]));
    park(SLOT(12), pk2(acc[12], acc[13])); park(SLOT(14), pk2(acc[14], acc[15]));
    bar_sync(bid, 128);
    flush_load<2>(c, pl, f); flush_load<3>(c, pl, f2);
    conv_flush<2, 1>(c, f, gy, rx);
    conv_flush<3, 1>(c, f2, gy, rx);
}
template <class FG>
__device__ __forceinline__ void conv_inner(Conv& c, uint32_t pl, unsigned char* gy, uint32_t rx, FG fg) {
    float acc[16][4];
    uint32_t q[9], a[16];
    uint2 f[4], f2[4];
    const int bid = 1 + (c.warp >> 2);
    c.id = 0x3210u + (c.warp >> 8);
    conv_selectors4(c);
    conv_load<2, 0, 9>(c, q);
    conv_frag<2, 0, 4>(c, q, a, 0.f);
    wg_fence(); wg_first<4>(acc, a, c.d0); conv_mma<2, 4, 1, 4>(acc, c, a + 4); GO();
    conv_load<3, 0, 9>(c, q);
    park(SLOT(2), Pk{{0u, 0u, 0u, 0u}});
    fg(IC<2, true>());
    wg_wait0();
    conv_rename<6>(acc);
    conv_frag<3, 0, 4>(c, q, a, DEP);
    wg_fence(); conv_mma<3, 6, 0, 4>(acc, c, a); GO();
    park(SLOT(4), pk2(acc[4], acc[5]));
    conv_load<4, 0, 9>(c, q);
    conv_selectors8(c);
    wg_wait0();
    conv_rename<8>(acc);
    conv_frag<4, 0, 4>(c, q, a, DEP);
    wg_fence(); conv_mma<4, 8, 0, 4>(acc, c, a); GO();
    const Pk k = pk2(acc[6], acc[7]);
    park(SLOT(6), k); park(c.ps, k);
    conv_load<5, 0, 9>(c, q);
    flush_setup(c);
    wg_wait0();
    conv_rename<10>(acc);
    conv_frag<5, 0, 4>(c, q, a, DEP);
    wg_fence(); conv_mma<5, 10, 0, 4>(acc, c, a); GO();
    park(SLOT(8), pk2(acc[8], acc[9]));
    bar_sync(bid, 128);
    flush_load<1>(c, pl, f);
    mbar_wait(rx);
    conv_flush<1, 2>(c, f, gy, rx);
    wg_wait0();
    bar_sync(bid, 128);
    park(SLOT(10), pk2(acc[10], acc[11])); park(SLOT(12), pk2(acc[12], acc[13])); park(SLOT(14), pk2(acc[14], acc[15]));
    bar_sync(bid, 128);
    flush_load<3>(c, pl, f); flush_load<2>(c, pl, f2);
    mbar_wait(rx + 8);
    conv_flush<3, 2>(c, f, gy, rx);
    conv_flush<2, 2>(c, f2, gy, rx);
}
#undef SLOT
#undef GO
#undef DEP
template <int U0, int U1>
__device__ __forceinline__ void weight_units(uint32_t sb, const Maps& tm, bool w) {
    if (U1 > U0 && w && elect_one()) {
#pragma unroll
        for (int i = U0; i < U1; i++) {
            const int P = blockIdx.x >> 1, odd = blockIdx.x & 1;
            if (i < 12) tma_2d(sb + SM_WG + i * 6144, &tm.w[i / 6], 64 * P, 288 * odd + (i % 6) * 48, sb + SM_MISC + 328);
            else tma_2d(sb + SM_WD + (i - 12) * 4736, &tm.d, 144 * odd, i < 20 ? 64 * P + 8 * (i - 12) : 4096 + 8 * P, sb + SM_MISC + 336);
            if (i >= 8 && i < 12) tma_2d(sb + SM_WR + (i - 8) * 2304, &tm.r[(i - 8) >> 1], 4096 + 8 * P, 288 * odd + (i & 1) * 144, sb + SM_MISC + 328);
        }
    }
}
#define WS 2210121111113004000
__device__ constexpr int wsched(int i) {
    unsigned long long v = WS;
    int n = 0;
    for (int k = 19; k >= 1; k--) { if (k < i) n += (int)(v % 10); v /= 10; }
    return n;
}
static_assert(wsched(20) == 21 && wsched(6) <= 8 && wsched(11) <= 12 && wsched(13) <= 14 && wsched(16) <= 17 && wsched(16) == wsched(15) && wsched(19) == 21, "");
#define WANY(i) (wsched((i) + 1) > wsched(i))
#define WPOINT(i, w) do { weight_units<wsched(i), wsched(i + 1)>(sb, tm, w); } while (0)

__global__ void __launch_bounds__(NTHR, 1) __cluster_dims__(2, 1, 1)
fused_kernel(const Params p, const __grid_constant__ Maps tm) {
    extern __shared__ __align__(1024) unsigned char smem[];
    const uint32_t sb = smem_u32(smem);
    const int tid = threadIdx.x, warp = __shfl_sync(0xffffffffu, tid >> 5, 0), lane = tid & 31;
    const int b = blockIdx.x, P = b >> 1, odd = b & 1;
    const int g = lane >> 2, t = lane & 3;
    const int wg = warp >> 2, t128 = tid & 127;
    const uint32_t s_stat = sb + SM_MISC;
    const uint32_t s_key = sb + SM_MISC + 128;
    const uint32_t s_rank = sb + SM_MISC + 256;
    const uint32_t s_k16 = sb + SM_MISC + 192;
    const uint32_t s_cnt = sb + SM_MISC + 320;
    const uint32_t bar_w = sb + SM_MISC + 328, bar_d = bar_w + 8, bar_g = bar_w + 16, bar_x = bar_w + 24, bar_v = bar_w + 32, bar_s = bar_w + 40, bar_h = bar_w + 48;
    STAMP(0);

    const int ch = wg < 4 ? 4 * b + wg : 512 + P;
    const uint32_t mo = tid < 512 ? 512 * b + tid : 65536 + 128 * P + t128, mq = (mo & ~127u) + 4 * lane;
    const uint32_t pl = ldo16(p.lar + mo), pa2 = ldo16(p.aim + mo), ldt = ldo16(p.ldt + (mo >> 7));
    const uint32_t pc = ldo16(p.cre + mo), pi = ldo16(p.cim + mo);
    const uint2 call_re = ldo64(p.cre + mq), call_im = ldo64(p.cim + mq);
    const uint32_t epl = ld_poll32(p.s->hint + (b & 7) * 32 + 1);
    if (wg < 4) {
        bar_arrive(0, NWRK);
        asm volatile("barrier.cluster.arrive.relaxed.aligned;\n" ::: "memory");
    } else {
        const int o = (4 * (warp & 3) + (g >> 1)) * 1152 + (g & 1) * 576 + t * 16;
        sts128(sb + SM_Z2 + t128 * 16, 0u, 0u, 0u, 0u); sts128(sb + SM_Z2 + 2048 + t128 * 16, 0u, 0u, 0u, 0u);
        if (warp == 16) sts128(sb + SM_Z2 + 4096 + lane * 16, 0u, 0u, 0u, 0u);
        fence_async();
        bar_sync(0, NWRK);
        STAMP(9);
#pragma unroll
        for (int c = 0; c < 9; c++)
            asm volatile("cp.async.cg.shared.global [%0], [%1], 16;\n" ::"r"(sb + SM_XT + o + c * 64), "l"(reinterpret_cast<const char*>(p.x) + b * 18432 + o + c * 64) : "memory");
        asm volatile("cp.async.commit_group;\n" ::: "memory");
        if (elect_one()) {
            mbar_init(bar_h + 8 * (warp & 3), 1);
            if (warp == 19) {
                mbar_init(bar_x, 1); mbar_init(bar_w, 1);
                mbar_expect(bar_x, 32768); mbar_expect(bar_w, 82944);
#pragma unroll
                for (int i = 2; i < 4; i++) bulk_s2g(reinterpret_cast<unsigned char*>(p.s->y) + 32 * i * 18432 + b * 4608, sb + SM_Z2, 4608);
            } else if (warp == 18) {
                mbar_init(bar_s, 1); mbar_init(bar_v, 2); mbar_init(bar_d, 1); mbar_init(bar_g, 1); mbar_init(sb + SM_RX, 1); mbar_init(sb + SM_RX + 8, 1);
                mbar_expect(bar_v, 2 * 1152); mbar_expect(bar_d, 72 * WD_PITCH); mbar_expect(bar_g, 4608); mbar_expect(sb + SM_RX, 1024); mbar_expect(sb + SM_RX + 8, 2048);
            }
            asm volatile("fence.mbarrier_init.release.cluster;\n" ::: "memory");
        }
        __syncwarp();
        asm volatile("barrier.cluster.arrive.relaxed.aligned;\n" ::: "memory");
        if (warp == 19) {
            asm volatile("barrier.cluster.wait.aligned;\n" ::: "memory");
            if (elect_one()) tma_4d_mc(sb + SM_XC + odd * 16384, &tm.x, 8 * P, 2 * odd, bar_x);
            __syncwarp();
        }
        {
            if (!(g & 1) && t == (g >> 1)) *reinterpret_cast<volatile uint32_t*>(p.s->stat + 16 * b + 4 * (warp & 3) + t) = 0u;
            if (warp < 18) {
                unsigned char* const ud = reinterpret_cast<unsigned char*>(p.s->uT) + (size_t)(8 * (warp & 1) + 2 * (g >> 1)) * 16384 + b * 128 + (g & 1) * 32 + t * 8;
#pragma unroll
                for (int k = 0; k < 4; k++) *reinterpret_cast<volatile unsigned long long*>(ud + (k >> 1) * 16384 + (k & 1) * 64) = 0ull;
            }
        }
    }
    const uint32_t kw = sb + SM_KW + wg * KW_B;
    const uint32_t tb = table_buf(sb, warp), t5 = sb + SM_WD + warp * 512;
    STAMP(29);
    const float dt = exp_bf(bf_lo(ldt));
    const uint32_t ep = __reduce_or_sync(0xffffffffu, epl);
    auto stats = [&]() {
        const int wq = warp & 3;
        const uint32_t xa = sb + SM_XT + (4 * wq + (g >> 1)) * 1152 + (g & 1) * 576 + t * 16;
        const bool own = !(g & 1) && t == (g >> 1);
        float d[4][4] = {};
        asm volatile("cp.async.wait_group 0;\n" ::: "memory");
        STAMP(26);
        uint4 v[9];
#pragma unroll
        for (int c = 0; c < 9; c++) v[c] = lds128(xa + c * 64);
#pragma unroll
        for (int c = 0; c < 9; c++) {
            mma_bf16(d[2 * (c & 1)], v[c].x, 0x3f803f80u, v[c].y, 0x3f803f80u, v[c].x, v[c].y);
            mma_bf16(d[2 * (c & 1) + 1], v[c].z, 0x3f803f80u, v[c].w, 0x3f803f80u, v[c].z, v[c].w);
        }
        STAMP(27);
        float sm = (g & 1) ? (d[0][3] + d[1][3]) + (d[2][3] + d[3][3]) : (d[0][2] + d[1][2]) + (d[2][2] + d[3][2]);
        float sq = (g & 1) ? (d[0][1] + d[1][1]) + (d[2][1] + d[3][1]) : (d[0][0] + d[1][0]) + (d[2][0] + d[3][0]);
        sm += __shfl_xor_sync(0xffffffffu, sm, 4); sq += __shfl_xor_sync(0xffffffffu, sq, 4);
        if (lane == 0) mbar_arrive(bar_h + 8 * wq);
        float mb, sd;
        ln_stats(sm, sq, mb, sd);
        if (own) p.s->stat[16 * b + 4 * wq + t] = (__float_as_uint(mb) >> 16) | (__float_as_uint(sd) & 0x7fff0000u) | (ep << 31);
        STAMPX(22);
        if (own) stat_store(s_stat + (2 * wq + (t & 1) + 8 * (t >> 1)) * 8, mb, rcp_approx(sd), 0u);
        if (wq == 3) asm volatile("cp.async.bulk.wait_group 0;\n" ::: "memory");
        bar_sync(5, 128);
        STAMP(28);
        uint32_t now;
        asm volatile("mov.u32 %0, %%clock;" : "=r"(now) :: "memory");
        if (wq == 2) {
            conv_constants(sb + SM_LC, lane);
            __syncwarp();
            if (lane < 8) p.s->key3[8 * b + lane] = ep & 1u;
            if (lane == 0) {
                sts64(s_cnt, now, ep);
                mbar_arrive(bar_s);
                bulk_g2s(sb + SM_XT + 16 * 1152, p.dsk, 1152, bar_v);
                bulk_g2s(sb + SM_XT + 17 * 1152, p.wr, 1152, bar_v);
            }
            __syncwarp();
        }
        WPOINT(1, wq == 3);
        if (wq < 2) {
            unsigned char* const ud = reinterpret_cast<unsigned char*>(p.s->uT) + (size_t)(8 * wq + 2 * (g >> 1)) * 16384 + b * 128 + (g & 1) * 32 + t * 8;
            const uint32_t utag = (ep % 7u + 1u) * 0x10001u;
            uint32_t U[2][4];
#pragma unroll
            for (int hf = 0; hf < 2; hf++) {
                const uint2 st = lds64(s_stat + (g + 8 * hf) * 8);
                const uint4 xu = lds128(sb + SM_XT + (TOK(g) + 2 * hf) * 1152 + warp * 64 + t * 16);
                const uint32_t X[4] = {xu.x, xu.y, xu.z, xu.w};
#pragma unroll
                for (int k = 0; k < 4; k++) {
                    const uint32_t u = ln_apply(X[k], STAT_M(st), STAT_H(st), STAT_L(st));
                    U[hf][k] = movm((pack_f16(bf_lo(u), bf_hi(u)) & 0xfff8fff8u) | utag);
                }
            }
#pragma unroll
            for (int k = 0; k < 4; k++) stg64(ud + (k >> 1) * 16384 + (k & 1) * 64, U[0][k], U[1][k]);
        }
    };
    STAMP(1);
    if (wg < 4) { STAMPX(16); }
    KGen kg;
    kgen_setup(kg, bf_lo(pl), bf_lo(pa2), dt);
    kgen_rows(kg, tb, lane);
    STAMP(2);
    const int E = min(max(c_exponent(call_re, call_im, dt) - 243, -120), 120);
    kgen_chain(kg, pc, pi, dt * __uint_as_float((uint32_t)(128 - E) << 23));
    STAMP(3);
    kgen_cols(kg, tb, t5, lane);
    STAMP(4);
    if (wg == 4) stats();
    if (warp != 19) asm volatile("barrier.cluster.wait.aligned;\n" ::: "memory");
    if (wg < 4) { STAMPX(17); }
    if (t128 < 2 * UPAD) sts128(sb + SM_U + wg * USLOT_B + (t128 & 1) * ULO_B + (t128 >> 1) * 16, 0u, 0u, 0u, 0u);
    if (t128 >= 124) sts128(kw + (t128 & 1) * 16 + (t128 & 2) * (KW_PL / 2), 0u, 0u, 0u, 0u);
    if (warp < 15) sts128(sb + SM_Z2 + 4608 + tid * 16, 0u, 0u, 0u, 0u);
    uint32_t co, cn, cd;
    combine_setup(sb, warp, lane, kw, co, cn, cd);
    co = pin(co); cn = pin(cn); cd = pin(cd);
    const uint4* const usrc = reinterpret_cast<const uint4*>(p.s->stat) + pin(wg < 4 ? tid : 512 + (P >> 2) * 1024 + (t128 >> 1) * 8 + (P & 3) * 2 + (t128 & 1));
    if (wg < 4) mbar_wait(bar_h + 8 * (warp & 3));
    if (wg < 4) { STAMPX(19); }
    uint32_t trel;
    asm volatile("mov.u32 %0, %%clock;" : "=r"(trel) :: "memory");
    kgen_mma(kg, tb, t5, lane);
    if (wg < 4) { STAMPX(20); }
    STAMP(5);
    uint4 uv0, uv1;
    auto first_poll = [&](uint32_t dly) {
        mbar_wait(bar_s);
        const uint32_t t0 = lds32(s_cnt);
        uint32_t now;
        do { asm volatile("mov.u32 %0, %%clock;" : "=r"(now) :: "memory"); } while (now - t0 < dly);
        uv0 = ld_poll(usrc);
    };
    if (wg == 4) { first_poll(UDLY); uv1 = ld_poll(usrc + 512); }
    WPOINT(2, warp == 19);
    auto stat_poll = [&]() {
        uint32_t now;
        do { asm volatile("mov.u32 %0, %%clock;" : "=r"(now) :: "memory"); } while (now - trel < SDLY);
        uv0 = ld_poll(usrc);
    };
    bar_sync(1 + wg, 128);
    if (wg < 4) { STAMPX(21); }
    kgen_combine(warp & 3, lane, co, cn, cd);
    STAMP(6);
    if (wg < 4) { STAMPX(18); }
    WPOINT(3, warp == 19);
    if (wg < 4) stat_poll();
    {
        const int wq = warp & 3;
        Conv c;
        const uint32_t pln = sb + SM_PL + wg * PL_B;
        const int e = g - 2 * t + 7;
        c.kw = kw; c.wa = pin(kw + ((e >> 2) & 1) * KW_PL + (8 * wq + (e >> 3)) * 16 + (e & 3) * 4);
        c.ps = mov_v(pln + wq * PLW_B + ((lane >> 3) & 1) * PL_HALF + ((lane >> 4) * 8 + (lane & 7)) * 16); c.warp = warp;
        c.lc = sb + SM_LC; c.fs = (uint32_t)(127 + E) * 0x800080u; c.yp = (ep & 1u) * (NCTA * 18432u);
        c.d0 = ((uint64_t)(ULO_B >> 4) << 16) | ((uint64_t)(128 >> 4) << 32) | (uint64_t)(((sb + SM_U + wg * USLOT_B + UPAD * 16) & 0x3FFFF) >> 4);
        unsigned char* gy = reinterpret_cast<unsigned char*>(p.s->y) + ((size_t)(4 * wq) * DM + ch) * 64;
        auto hook = [&](auto gi) {
                     constexpr int G = decltype(gi)::value;
                     if (G == (wg_is4<decltype(gi)>() ? 2 : 5)) asm volatile("barrier.cluster.wait.aligned;\n" ::: "memory");
                     if (!wg_is4<decltype(gi)>() && G == 1) mbar_wait(bar_s);
                     if (!wg_is4<decltype(gi)>() && (G == 0 || G == 2) && warp == HW && elect_one()) {
                         unsigned char* const sc = reinterpret_cast<unsigned char*>(p.s);
                         if (G == 0) {
                             if (b < 96) bulk_s2g_nc(sc + offsetof(Scratch, part) + b * 6144, sb + SM_Z2, 6144);
                             bulk_s2g(sc + offsetof(Scratch, rows) + (127 - b) * 4608, sb + SM_Z2, 4608);
                         }
                         if (G == 2) {
                             bulk_s2g(sc + offsetof(Scratch, y) + (NCTA * 18432u - c.yp) + b * 9216, sb + SM_Z2, 9216);
                         }
                     }
                     if (!wg_is4<decltype(gi)>()) WPOINT(6 + G, warp == (G >= 7 ? HW : 4 * (G % 3) + 1));
                     if (!wg_is4<decltype(gi)>() && G == 6 && warp == HW) {
                         asm volatile("cp.async.bulk.wait_group 0;\n" ::: "memory");
                         __syncwarp();
                         if (elect_one()) mbar_arrive(bar_v);
                     }
                 };
        if (wg < 4) {
            asm volatile("barrier.cluster.arrive.relaxed.aligned;\n" ::: "memory");
            conv_run(c, pln + wq * 128, gy, hook, [&]() {
                STAMPX(23);
                mbar_wait(bar_x);
                STAMPX(24);
                uint2 xc[4];
                uint32_t xw[4][2];
#pragma unroll
                for (int j = 0; j < 4; j++) xc[j] = lds64(sb + SM_XC + wg * 8192 + j * 2048 + t128 * 16 + odd * 8);
#pragma unroll
                for (int i = 0; i < 8; i++) {
                    const int k = i >> 1, h = i & 1;
                    xw[k][h] = prmt_v(k < 2 ? xc[2 * h].x : xc[2 * h].y, k < 2 ? xc[2 * h + 1].x : xc[2 * h + 1].y, (k & 1) ? 0x7632 : 0x5410);
                }
                const uint32_t ub = mov_v(sb + SM_U + UPAD * 16 + ((tid >> 1) & 1) * ULO_B + (tid >> 2) * 16 + (tid & 1) * 8), tag = ep << 31;
                int it = 0;
                while (min(min((int)(uv0.x ^ tag), (int)(uv0.y ^ tag)), min((int)(uv0.z ^ tag), (int)(uv0.w ^ tag))) < 0x10000) {
                    if (++it > SPIN_LIMIT) TRAP();
                    uv0 = ld_poll(usrc);
                }
                STAMP(8);
                STAMPX(26);
                const float r0 = rcp_approx(fabsf(bf_hi(uv0.x))), r1 = rcp_approx(fabsf(bf_hi(uv0.y))), r2 = rcp_approx(fabsf(bf_hi(uv0.z))), r3 = rcp_approx(fabsf(bf_hi(uv0.w)));
                const uint32_t m[2] = {__byte_perm(uv0.x, uv0.y, 0x5410), __byte_perm(uv0.z, uv0.w, 0x5410)};
                const uint32_t rh[2] = {pack_bf16(r0, r1), pack_bf16(r2, r3)};
                const uint32_t rl[2] = {pack_bf16(r0 - bf_lo(rh[0]), r1 - bf_hi(rh[0])), pack_bf16(r2 - bf_lo(rh[1]), r3 - bf_hi(rh[1]))};
#pragma unroll
                for (int k = 0; k < 4; k++) {
                    const uint32_t u0 = ln_apply(xw[k][0], m[0], rh[0], rl[0]), u1 = ln_apply(xw[k][1], m[1], rh[1], rl[1]);
                    sts64(ub + k * USLOT_B, pack_f16(bf_lo(u0), bf_hi(u0)), pack_f16(bf_lo(u1), bf_hi(u1)));
                }
                STAMPX(29);
                fence_async();
                bar_sync(14, 512);
                STAMP(7);
            });
        } else {
            auto stage = [&]() {
                const uint32_t tag = (ep % 7u + 1u) * 0x10001u;
                int it = 0;
                WPOINT(4, warp == 19);
                while (true) {
                    uv0.x ^= tag; uv0.y ^= tag; uv0.z ^= tag; uv0.w ^= tag; uv1.x ^= tag; uv1.y ^= tag; uv1.z ^= tag; uv1.w ^= tag;
                    if ((((uv0.x | uv0.y | uv0.z) | (uv0.w | uv1.x | uv1.y) | (uv1.z | uv1.w)) & 0x70007u) == 0) break;
                    if (++it > SPIN_LIMIT) TRAP();
                    uv0 = ld_poll(usrc); uv1 = ld_poll(usrc + 512);
                }
                STAMP(8);
                const uint32_t ub = sb + SM_U + UPAD * 16 + 4 * USLOT_B + (t128 & 1) * ULO_B + (t128 >> 1) * 16;
                sts128(ub, uv0.x, uv0.y, uv0.z, uv0.w);
                sts128(ub + 1024, uv1.x, uv1.y, uv1.z, uv1.w);
                fence_async();
                asm volatile("barrier.cluster.arrive.relaxed.aligned;\n" ::: "memory");
                bar_sync(5, 128);
                WPOINT(5, warp == 19);
                STAMP(7);
            };
            stage();
            if (odd) conv_inner(c, pln + wq * 128, gy, sb + SM_RX, hook);
            else conv_outer(c, pln + wq * 128, gy, sb + SM_RX, hook);
        }
        STAMP(10);
    }
    {
    const int lane = lane_v(), tid = 32 * warp + lane, g = lane >> 2, t = lane & 3;
    const uint32_t par = ~ep & 1u;
    bar_sync(0, NWRK);
    STAMP(11);
    uint32_t H[2][4] = {}, U2[2][4] = {};
    auto publish = [&](bool hi, int slot) {
        uint4* rowp = reinterpret_cast<uint4*>(p.s->rows) + slot * 144 + warp * 4 + t;
        stg128(rowp, nzw(hi ? U2[1][0] : U2[0][0]), nzw(hi ? U2[1][1] : U2[0][1]), nzw(hi ? U2[1][2] : U2[0][2]), nzw(hi ? U2[1][3] : U2[0][3]));
        stg128(rowp + 72, nzw(hi ? H[1][0] : H[0][0]), nzw(hi ? H[1][1] : H[0][1]), nzw(hi ? H[1][2] : H[0][2]), nzw(hi ? H[1][3] : H[0][3]));
    };
#define KTOK(k) (int)(((~(k) >> 5) & 0x7f0u) | (((k) >> 1) & 15u))
#define KLATE(k) (((k) & 0x1e0u) < 0xe0u)
#define KSLOT(k, s) (KLATE(k) ? 2 * NCTA + (s) : (int)(((k) >> 8) & 0xffu))
    const uint4* const rsrc = reinterpret_cast<const uint4*>(p.s->rows) + 36 * odd;
    auto gather = [&](uint32_t mine) {
        int it = 0;
        uint32_t mn;
        do {
            mn = 1;
#pragma unroll 1
            for (int r = 0; r < 9; r++) {
                const uint32_t k = __shfl_sync(0xffffffffu, mine, r < 8 ? 4 * r : lane);
                const int row = r < 8 ? r : g, c = r < 8 ? lane : 32 + t;
                asm volatile("cp.async.cg.shared.global [%0], [%1], 16;\n" ::"r"(sb + SM_XS + row * XS_PITCH + c * 16), "l"(rsrc + KSLOT(k, row) * 144 + c) : "memory");
            }
            asm volatile("cp.async.wait_all;\n" ::: "memory");
#pragma unroll 1
            for (int r = 0; r < 9; r++) mn = min(mn, min4(lds128(sb + SM_XS + (r < 8 ? r * XS_PITCH + lane * 16 : g * XS_PITCH + (32 + t) * 16))));
            if (++it > SPIN_LIMIT) TRAP();
        } while (__any_sync(0xffffffffu, mn == 0));
    };
    auto late_rows = [&](auto role) {
        if (decltype(role)::value == 1) {
            int it = 0;
            uint4 k[8];
            uint32_t bad;
            do {
                bad = 0;
#pragma unroll
                for (int i = 0; i < 8; i++) k[i] = ld_poll(reinterpret_cast<const uint4*>(p.s->key) + 32 * i + lane);
#pragma unroll
                for (int i = 0; i < 8; i++) bad = or3(bad, xor_or(k[i].x, k[i].y, par), xor_or(k[i].z, k[i].w, par));
                if (++it > SPIN_LIMIT) TRAP();
            } while (__any_sync(0xffffffffu, bad & 1u));
#pragma unroll 1
            for (int r = 0; r < 8; r++) {
                uint32_t c = 0;
#pragma unroll
                for (int i = 0; i < 8; i++) c = max(c, k[i].x);
                const uint32_t m = __reduce_max_sync(0xffffffffu, c);
#pragma unroll
                for (int i = 0; i < 8; i++) if (k[i].x == m) k[i] = make_uint4(k[i].y, k[i].z, k[i].w, 0u);
                if (lane == 0) sts32(s_key + r * 4, m);
            }
        }
        bar_sync(0, NWRK);
        const uint32_t kk = lds32(s_key + (lane & 7) * 4), ep = lds32(s_cnt + 4);
        const bool own = KLATE(kk) && (KTOK(kk) >> 4) == b;
        uint32_t todo = __ballot_sync(0xffffffffu, own) & 0xffu;
        if (decltype(role)::value == 0 && todo) {
#pragma unroll
            for (int hf = 0; hf < 2; hf++) {
                const uint4 h = lds128(sb + SM_U + hf * 9216 + tid * 16);
                const uint2 st = lds64(s_stat + (g + 8 * hf) * 8);
                H[hf][0] = h.x; H[hf][1] = h.y; H[hf][2] = h.z; H[hf][3] = h.w;
#pragma unroll
                for (int k = 0; k < 4; k++) U2[hf][k] = ln_apply(H[hf][k], STAT_M(st), STAT_H(st), STAT_L(st));
            }
#pragma unroll 1
            while (todo) {
                const int s = __ffs(todo) - 1, tk = KTOK(__shfl_sync(0xffffffffu, kk, s));
                todo &= todo - 1;
                if ((tk & 13) == TOK(g)) publish(tk & 2, 2 * NCTA + s);
            }
            __threadfence();
        }
        bar_sync(0, NWRK);
        if (decltype(role)::value == 1) {
            if (lane < NSEL && own) *reinterpret_cast<volatile unsigned*>(p.s->flag + lane) = ep + 1u;
            int it = 0;
            while (__any_sync(0xffffffffu, KLATE(kk) && ld_acquire32(p.s->flag + (lane & 7)) != ep + 1u)) { if (++it > SPIN_LIMIT) TRAP(); }
            gather(__shfl_sync(0xffffffffu, kk, g));
        }
        bar_sync(0, NWRK);
    };
    if (warp < 18) {
        const unsigned char* ys = reinterpret_cast<const unsigned char*>(p.s->y) + (b < 64 ? (par ^ 1u) * (NCTA * 18432u) : 0u) +
                                  ((P * DM + 32 * warp + 8 * (g >> 1) + (g & 1)) * 64 + odd * 32 + t * 8);
        mbar_wait(bar_v);
        const uint32_t xa = sb + SM_XT + warp * 64 + t * 16;
        const uint4 x0 = lds128(xa + TOK(g) * 1152), x1 = lds128(xa + (TOK(g) + 2) * 1152), dk = lds128(xa + 16 * 1152);
        uint4 wr = make_uint4(0u, 0u, 0u, 0u);
        if (g == 0) wr = lds128(xa + 17 * 1152);
        uint2 yv[4];
        const uint32_t Z[2][4] = {{x0.x, x0.y, x0.z, x0.w}, {x1.x, x1.y, x1.z, x1.w}}, D4[4] = {dk.x, dk.y, dk.z, dk.w};
#pragma unroll
        for (int hf = 0; hf < 2; hf++) {
            const uint2 st = lds64(s_stat + (g + 8 * hf) * 8);
#pragma unroll
            for (int k = 0; k < 4; k++) U2[hf][k] = hmul2_bf(ln_apply(Z[hf][k], STAT_M(st), STAT_H(st), STAT_L(st)), D4[k]);
        }
        const uint32_t la = pin(sb + SM_LNP + (g * 20 + warp) * 4);
        {
            const unsigned char* y1 = ys + (U2[0][0] & U2[1][2] & (warp >> 8));
#pragma unroll
            for (int k = 0; k < 4; k++) yv[k] = ld_poll64(y1 + k * 128);
        }
        int it = 0;
        float d[2][4];
        while (true) {
            const uint32_t mn = min3(min3(yv[0].x, yv[0].y, yv[1].x), min3(yv[1].y, yv[2].x, yv[2].y), min(yv[3].x, yv[3].y));
#pragma unroll
            for (int k = 0; k < 4; k++) {
                H[0][k] = hadd2_bf(Z[0][k], hadd2_bf(movm(yv[k].x), U2[0][k]));
                H[1][k] = hadd2_bf(Z[1][k], hadd2_bf(movm(yv[k].y), U2[1][k]));
            }
            ln_partial(H, d);
            if (!__any_sync(0xffffffffu, mn == 0)) break;
            if (++it > SPIN_LIMIT) TRAP();
#pragma unroll
            for (int k = 0; k < 4; k++) yv[k] = ld_poll64(ys + k * 128);
        }
        STAMP(12);
        {
            const float s0 = (g & 1) ? d[0][3] : d[0][2], s1 = (g & 1) ? d[1][3] : d[1][2];
            const float q0 = (g & 1) ? d[0][1] : d[0][0], q1 = (g & 1) ? d[1][1] : d[1][0];
            asm volatile("{\n.reg .pred p;\nsetp.eq.u32 p, %5, %6;\n@p st.shared.f32 [%0], %1;\n@p st.shared.f32 [%0 + 640], %2;\n@p st.shared.f32 [%0 + 1280], %3;\n@p st.shared.f32 [%0 + 1920], %4;\n}\n"
                         ::"r"(la), "f"(s0), "f"(s1), "f"(q0), "f"(q1), "r"(t), "r"(g >> 1) : "memory");
        }
        bar_arrive(6, NWRK);
        STAMP(13);
        bar_sync(7, 608);
        STAMP(14);
#pragma unroll
        for (int hf = 0; hf < 2; hf++) {
            const uint2 st = lds64(s_stat + (g + 8 * hf) * 8);
#pragma unroll
            for (int k = 0; k < 4; k++) U2[hf][k] = ln_apply(H[hf][k], STAT_M(st), STAT_H(st), STAT_L(st));
        }
        {
            float cs[4] = {0.f, 0.f, 0.f, 0.f};
            mma_bf16(cs, U2[0][0], U2[1][0], U2[0][1], U2[1][1], wr.x, wr.y);
            mma_bf16(cs, U2[0][2], U2[1][2], U2[0][3], U2[1][3], wr.z, wr.w);
            if (t == 0) { stsf(la + 32 * 80, cs[0]); stsf(la + 40 * 80, cs[2]); }
            bar_arrive(8, 608);
        }
        FIX((uint32_t)warp >> 8);
        uint32_t O[2][4];
#pragma unroll
        for (int hf = 0; hf < 2; hf++)
#pragma unroll
            for (int k = 0; k < 4; k++) { O[hf][k] = hadd2_bf(H[hf][k], U2[hf][k]); H[hf][k] = nzw(H[hf][k]); U2[hf][k] = nzw(U2[hf][k]); }
        unsigned char* rowp = reinterpret_cast<unsigned char*>(p.s->rows) + ((254 - 2 * b) * 2304 + warp * 64 + t * 16);
        FIX(and3(and3(and3(H[0][0], H[0][1], H[0][2]), and3(H[0][3], H[1][0], H[1][1]), and3(H[1][2], H[1][3], U2[0][0])),
                 and3(and3(U2[0][1], U2[0][2], U2[0][3]), and3(U2[1][0], U2[1][1], U2[1][2]), U2[1][3]), (uint32_t)reinterpret_cast<uint64_t>(rowp)));
        bar_sync(9, 608);
        {
            const uint2 best = lds64(s_rank);
#pragma unroll
            for (int hf = 0; hf < 2; hf++) {
                const uint32_t me = 2 * TOK(g) + 4 * hf;
                unsigned char* d = rowp + (best.x == me ? 2304 : 0);
                if (best.x == me || best.y == me) {
                    stg128(d, U2[hf][0], U2[hf][1], U2[hf][2], U2[hf][3]);
                    stg128(d + 1152, H[hf][0], H[hf][1], H[hf][2], H[hf][3]);
                }
            }
        }
        FIX((uint32_t)warp >> 9);
#pragma unroll
        for (int hf = 0; hf < 2; hf++) {
            sts128(sb + SM_OUT + (TOK(g) + 2 * hf) * (DM * 2) + warp * 64 + t * 16, O[hf][0], O[hf][1], O[hf][2], O[hf][3]);
            sts128(sb + SM_U + hf * 9216 + tid * 16, H[hf][0], H[hf][1], H[hf][2], H[hf][3]);
        }
        STAMP(15);
        const int mi = lane >> 3, rr = lane & 7;
        const bool gate = warp < 12 && (warp & 3) != 2;
        const int fj = gate ? 3 * (warp >> 2) + min(warp & 3, 2) : (warp < 12 ? warp >> 2 : warp - 9);
        if (gate) {
            uint32_t W[18][4];
            mbar_wait(bar_w);
            const uint32_t aad = fj < 8 ? sb + SM_WG + (mi & 1) * SM_WU + (rr + 8 * (mi >> 1)) * 128 + (fj ^ rr) * 16 : sb + SM_WR + (mi & 1) * 4608 + (rr + 8 * (mi >> 1)) * 16;
            const uint32_t ast = fj < 8 ? 2048 : 256;
            const uint32_t bad = pin(sb + SM_XS + rr * XS_PITCH + mi * 16);
            bool rare = warp >> 8;
#pragma unroll 1
            do {
                if (rare) late_rows(IC<0>());
#pragma unroll
                for (int k = 0; k < 18; k++) ldsm_x4_t(W[k][0], W[k][1], W[k][2], W[k][3], aad + k * ast);
                if (rare) break;
                fence_async();
                STAMP2(17);
                rare = bar_or(11, NWRK, false);
            } while (rare);
            STAMP2(19);
            float c4[2][4] = {};
#pragma unroll
            for (int k = 0; k < 18; k += 2) {
                uint32_t b0, b1, b2, b3;
                ldsm_x4(b0, b1, b2, b3, bad + k * 32);
                mma_bf16(c4[0], W[k][0], W[k][1], W[k][2], W[k][3], b0, b1);
                mma_bf16(c4[1], W[k + 1][0], W[k + 1][1], W[k + 1][2], W[k + 1][3], b2, b3);
            }
            const uint32_t ex = sb + SM_EX + (32 * fj + lane) * 16;
            const float e0 = c4[0][0] + c4[1][0], e1 = c4[0][1] + c4[1][1], e2 = c4[0][2] + c4[1][2], e3 = c4[0][3] + c4[1][3];
            asm volatile("st.async.shared::cluster.mbarrier::complete_tx::bytes.v4.f32 [%0], {%1,%2,%3,%4}, [%5];\n"
                         ::"r"(ex ^ 0x1000000u), "f"(e0), "f"(e1), "f"(e2), "f"(e3), "r"(bar_g ^ 0x1000000u) : "memory");
            STAMP2(20);
            mbar_wait(bar_g);
            const uint4 o = lds128(ex);
            const uint32_t G = pack_bf16(e0 + __uint_as_float(o.x), e1 + __uint_as_float(o.y)), U = pack_bf16(e2 + __uint_as_float(o.z), e3 + __uint_as_float(o.w));
            sts32(sb + SM_GU + (32 * fj + lane) * 4, hmul2_bf(pack_bf16(bf_lo(G) * sigmoid_f(bf_lo(G)), bf_hi(G) * sigmoid_f(bf_hi(G))), U));
            bar_arrive(13, NWRK);
        } else {
            uint32_t W[2][18];
            auto load_wd = [&]() {
                mbar_wait(bar_d);
                const uint32_t base = sb + SM_WD + (4 * fj + (mi & 1)) * 16 + rr * WD_PITCH;
#pragma unroll
                for (int j = 0; j < 2; j++) {
#pragma unroll
                    for (int k = 0; k < 4; k++) ldsm_x4_t(W[j][4 * k], W[j][4 * k + 1], W[j][4 * k + 2], W[j][4 * k + 3], base + j * 32 + (k * 16 + 8 * (mi >> 1)) * WD_PITCH);
                    ldsm_x2_t(W[j][16], W[j][17], base + j * 32 + 64 * WD_PITCH);
                }
            };
            const uint32_t po = pin((((8 * (18 * odd + 2 * fj) + g) * 64 + P) * 4 + t) * 8);
            fence_async();
            STAMP2(17);
            if (bar_or(11, NWRK, false)) late_rows(IC<0>());
            delay(DDLY); load_wd();
            bar_sync(13, NWRK);
            STAMP2(21);
            uint32_t gb[9];
            ldsm_x4_t(gb[0], gb[1], gb[2], gb[3], sb + SM_GU + lane * 16);
            ldsm_x4_t(gb[4], gb[5], gb[6], gb[7], sb + SM_GU + 512 + lane * 16);
            ldsm_x1_t(gb[8], sb + SM_GU + 1024 + lane * 16);
            float c4[2][4] = {}, d4[2][4] = {};
#pragma unroll
            for (int k = 0; k < 4; k += 2)
#pragma unroll
                for (int j = 0; j < 2; j++) {
                    mma_bf16(c4[j], W[j][4 * k], W[j][4 * k + 1], W[j][4 * k + 2], W[j][4 * k + 3], gb[2 * k], gb[2 * k + 1]);
                    mma_bf16(d4[j], W[j][4 * k + 4], W[j][4 * k + 5], W[j][4 * k + 6], W[j][4 * k + 7], gb[2 * k + 2], gb[2 * k + 3]);
                }
#pragma unroll
            for (int j = 0; j < 2; j++) mma_bf16_k8(c4[j], W[j][16], W[j][17], gb[8]);
#pragma unroll
            for (int j = 0; j < 2; j++)
                stg64(reinterpret_cast<unsigned char*>(p.s->part) + po + j * 16384, nzw(pack_bf16(c4[j][0] + d4[j][0], c4[j][1] + d4[j][1])), nzw(pack_bf16(c4[j][2] + d4[j][2], c4[j][3] + d4[j][3])));
        }
        STAMP2(22);
    } else if (warp == 18) {
        const uint4* const ksrc = reinterpret_cast<const uint4*>(p.s->key3) + pin(2 * lane);
        const int row = (g >> 1) + 4 * (g & 1);
        const uint32_t ro = pin(640 * odd + t * 16), xd = pin(sb + SM_XS + row * XS_PITCH + t * 16 + (odd ? 0 : 512));
        const uint32_t xe = pin(sb + SM_XS + (g >> 1) * XS_PITCH + (lane & 7) * 16 + 64 * odd);
        const uint32_t sa = pin(sb + SM_LNP + lane * 80);
        const uint32_t klo = pin((uint32_t)(127 - b) << 9 | (uint32_t)(15 - ROWTOK(lane & 15)) << 1 | par), ra = pin(sb + SM_LNP + (32 + (lane & 15)) * 80);
        uint4* const kdst = reinterpret_cast<uint4*>(p.s->key3) + pin((lane >> 1) * 2 * NCTA + 2 * b + (lane & 1));
        FIX(ra);
        bar_sync(6, NWRK);
        {
            float mb, rc;
            ln_finish(sum18(sa), lane, mb, rc);
            if (lane < 16) stat_store(s_stat + lane * 8, mb, rc, 0u);
        }
        bar_arrive(7, 608);
        bar_sync(8, 608);
        uint32_t t0;
        {
            const uint32_t bits = __float_as_uint(rbf(sum18(ra)));
            const uint32_t me = ((bits ^ ((uint32_t)((int)bits >> 31) | 0x80000000u)) & 0xffff0000u) | klo;
            const uint32_t k0 = __reduce_max_sync(0xffffffffu, me), k1 = __reduce_max_sync(0xffffffffu, me == k0 ? 0u : me);
            const uint32_t k2 = __reduce_max_sync(0xffffffffu, me >= k1 ? 0u : me);
            if (lane < 2) stg128(kdst, k0 ^ 0x11eu, k1 ^ 0xfeu, k2 ^ 0xdeu, par);
            asm volatile("mov.u32 %0, %%clock;" : "=r"(t0) :: "memory");
            STAMPW(23);
            if (lane == 0) sts64(s_rank, ~k0 & 30u, ~k1 & 30u);
            bar_arrive(9, 608);
            sts32(s_k16 + (lane & 15) * 4, me);
            __syncwarp();
            const uint4 v = lds128(s_k16 + (lane & 16) * 2), w = lds128(s_k16 + (lane & 16) * 2 + 16);
            int rank = ((v.x > me) + (v.y > me)) + ((v.z > me) + (v.w > me)) + (((w.x > me) + (w.y > me)) + ((w.z > me) + (w.w > me)));
            rank += __shfl_xor_sync(0xffffffffu, rank, 16);
            if (lane < 16 && rank < 8) p.s->key[8 * b + rank] = (me ^ 0x1eu) | ((8 - rank) << 5);
        }
        uint4 kq[4];
        uint32_t u[4], mine = 0, m;
        int it = 0;
        { uint32_t now; do { asm volatile("mov.u32 %0, %%clock;" : "=r"(now) :: "memory"); } while (now - t0 < KDLY); }
        do {
#pragma unroll
            for (int i = 0; i < 4; i++) kq[i] = ld_poll(ksrc + 64 * i);
            if (++it > SPIN_LIMIT) TRAP();
            uint32_t S[2][4];
#pragma unroll
            for (int i = 0; i < 2; i++) {
                const uint4 &c = kq[2 * i], &d = kq[2 * i + 1];
                const uint32_t m1 = min(c.x, d.x), m2 = max(c.y, d.y);
                S[i][0] = max(c.x, d.x); S[i][1] = max(m1, m2); S[i][2] = min(m1, m2); S[i][3] = min(c.y, d.y);
            }
            const uint32_t a0 = max(S[0][0], S[1][3]), a1 = max(S[0][1], S[1][2]), a2 = max(S[0][2], S[1][1]), a3 = max(S[0][3], S[1][0]);
            const uint32_t b0 = max(a0, a2), b2 = min(a0, a2), b1 = max(a1, a3), b3 = min(a1, a3);
            u[0] = max(b0, b1); u[1] = min(b0, b1); u[2] = max(b2, b3); u[3] = min(b2, b3);
            const uint32_t bad = or3(or3(xor_or(kq[0].x, kq[0].y, par), xor_or(kq[0].z, kq[1].x, par), xor_or(kq[1].y, kq[1].z, par)),
                                     xor_or(kq[2].x, kq[2].y, par), xor_or(kq[2].z, kq[3].x, par)) | xor_or(kq[3].y, kq[3].z, par);
            m = __reduce_max_sync(0xffffffffu, u[0] | (uint32_t)((int)(bad << 31) >> 31));
        } while (m == 0xffffffffu);
        STAMPW(16);
#pragma unroll
        for (int r = 0; r < 8; r++) {
            if (r) m = __reduce_max_sync(0xffffffffu, u[0]);
            if (u[0] == m) { u[0] = u[1]; u[1] = u[2]; u[2] = u[3]; u[3] = 0; }
            if (row == r) mine = m;
        }
        uint4 v[9];
        const uint32_t o0 = __byte_perm(mine, 0, 0x4441) * 2304u, o1 = __shfl_xor_sync(0xffffffffu, o0, 4);
        const unsigned char* const rA = reinterpret_cast<const unsigned char*>(p.s->rows) + (((g & 1) ? o1 : o0) + ro + (g & 1) * 64);
        const unsigned char* const rb = reinterpret_cast<const unsigned char*>(p.s->rows) + (((g & 1) ? o0 : o1) + ro + (g & 1) * 64);
        const unsigned char* const rc = reinterpret_cast<const unsigned char*>(p.s->rows) + (o0 + ro + (odd ? -64 : 512));
#pragma unroll
        for (int i = 0; i < 4; i++) { v[i] = ld_poll(rA + i * 128); v[4 + i] = ld_poll(rb + i * 128); }
        v[8] = ld_poll(rc);
        const bool again = u[0] == 0 || max(max(kq[0].z, kq[1].z), max(kq[2].z, kq[3].z)) > m;
        if (t == 0) sts32(s_key + row * 4, mine);
#pragma unroll
        for (int i = 0; i < 9; i++) sts128(i < 8 ? xe + (i >> 2) * 4 * XS_PITCH + (i & 3) * 128 : xd, v[i].x, v[i].y, v[i].z, v[i].w);
        uint32_t mn, m3[3];
        m3[0] = m3[1] = m3[2] = 1u;
#pragma unroll
        for (int i = 0; i < 9; i++) m3[i % 3] = min3(min3(m3[i % 3], v[i].x, v[i].y), v[i].z, v[i].w);
        mn = min3(m3[0], m3[1], m3[2]);
        STAMPW(18);
        if (bar_or(11, NWRK, again || mn == 0)) late_rows(IC<1>());
    } else {
        bar_sync(6, NWRK);
        WPOINT(16, true);
        if (WANY(17) || WANY(18)) delay(WDLY);
        WPOINT(17, true);
        if (WANY(18)) delay(WDLY);
        WPOINT(18, true);
        if (bar_or(11, NWRK, false)) late_rows(IC<2>());
        const int tk = KTOK(lds32(s_key + (lane & 7) * 4));
        const uint32_t sel = __reduce_or_sync(0xffffffffu, (tk >> 4) == b ? 1u << (tk & 15) : 0u);
        if (sel ? lane < 16 && !((sel >> lane) & 1u) : lane == 0) bulk_s2g(p.out + (size_t)(16 * b + lane) * DM, sb + SM_OUT + lane * (DM * 2), sel ? DM * 2 : 16 * DM * 2);
        __syncwarp();
    }
    if (warp == 8 || warp >= 18) {
        const int grp = 3 * b + (warp == 8 ? 0 : warp - 17), fsl = 2 * t + ((lane >> 3) & 1), fc = 16 * (grp >> 3) + (grp & 7) + 8 * (lane >> 4);
        const uint32_t fk = lds32(s_key + fsl * 4);
        float hv = 0.f, u2 = 0.f;
        int it = 0;
        if (b < 96) {
            const uint32_t* const fsrc = p.s->rows + KSLOT(fk, fsl) * DM + (fc >> 1);
            uint32_t hw, uw;
            do { hw = ld_poll32(fsrc + 288); uw = ld_poll32(fsrc); if (++it > SPIN_LIMIT) TRAP(); } while (!hw || !uw);
            hv = (fc & 1) ? bf_hi(hw) : bf_lo(hw); u2 = (fc & 1) ? bf_hi(uw) : bf_lo(uw);
        }
        const float rs = rbf(sigmoid_f(__uint_as_float((fk ^ ((uint32_t)((int)~fk >> 31) | 0x80000000u)) & 0xffff0000u)));
        const uint32_t dof = pin(KTOK(fk) * DM + fc), so = pin(grp * 256 + lane);
        if (warp > 17) bar_sync(13, NWRK);
        if (b < 96) {
            delay(warp > 17 ? FDLY : FDLY2);
            float y;
            uint32_t ok;
            float s0, s1, s2, s3;
            do {
                uint2 a[8];
#pragma unroll
                for (int i = 0; i < 8; i++) a[i] = ld_poll64(reinterpret_cast<const uint2*>(p.s->part) + so + 32 * i);
                if (++it > SPIN_LIMIT) TRAP();
                ok = min3(min3(min3(a[0].x, a[0].y, a[1].x), min3(a[1].y, a[2].x, a[2].y), min3(a[3].x, a[3].y, a[4].x)), min3(min3(a[4].y, a[5].x, a[5].y), min3(a[6].x, a[6].y, a[7].x), a[7].y), 1u);
#define S8(c, f) (((c(a[0].f) + c(a[1].f)) + (c(a[2].f) + c(a[3].f))) + ((c(a[4].f) + c(a[5].f)) + (c(a[6].f) + c(a[7].f))))
                s0 = S8(bf_lo, x); s1 = S8(bf_hi, x); s2 = S8(bf_lo, y); s3 = S8(bf_hi, y);
                asm volatile("" : "+f"(s0), "+f"(s1), "+f"(s2), "+f"(s3));
#undef S8
            } while (__any_sync(0xffffffffu, !ok));
            STAMP2(24);
#define HALVE(u, v, m) (((lane & m) ? v : u) + __shfl_xor_sync(0xffffffffu, (lane & m) ? u : v, m))
            const float r0 = HALVE(s0, s2, 16), r1 = HALVE(s1, s3, 16);
            y = HALVE(r0, r1, 8);
            y += __shfl_xor_sync(0xffffffffu, y, 4);
#undef HALVE
            p.out[dof] = __float2bfloat16_rn(hv + rbf(u2 + rbf(rbf(y) * rs)));
        }
    }
    if (warp == 19) asm volatile("cp.async.bulk.wait_group.read 0;\n" ::: "memory");
    if (b == 0 && tid < 8) *reinterpret_cast<volatile unsigned*>(p.s->hint + tid * 32 + 1) = lds32(s_cnt + 4) + 1u;
    STAMP(25);
    }
}

typedef CUresult (*PFN_tmEncode)(CUtensorMap*, CUtensorMapDataType, cuuint32_t, void*, const cuuint64_t*, const cuuint64_t*, const cuuint32_t*,
                                 const cuuint32_t*, CUtensorMapInterleave, CUtensorMapSwizzle, CUtensorMapL2promotion, CUtensorMapFloatOOBfill);

extern "C" void kernel_launch(void* const* d_in, const int* in_sizes, int n_in, void* d_out, int out_size) {
    Params p;
    p.x = (const bf16*)d_in[0];
    p.lar = (const bf16*)d_in[1];
    p.aim = (const bf16*)d_in[2];
    p.cre = (const bf16*)d_in[3];
    p.cim = (const bf16*)d_in[4];
    p.ldt = (const bf16*)d_in[5];
    p.dsk = (const bf16*)d_in[6];
    p.wr = (const bf16*)d_in[8];
    p.out = (bf16*)d_out;
    static PFN_tmEncode enc = nullptr;
    static void* scratch = nullptr;
    if (!enc) {
        cudaFuncSetAttribute(fused_kernel, cudaFuncAttributeMaxDynamicSharedMemorySize, SMEM_TOTAL);
        void* fn = nullptr;
        cudaDriverEntryPointQueryResult qr;
        cudaGetDriverEntryPoint("cuTensorMapEncodeTiled", &fn, cudaEnableDefault, &qr);
        enc = (PFN_tmEncode)fn;
        cudaGetSymbolAddress(&scratch, g_scratch);
    }
    p.s = (Scratch*)scratch;
    Maps tm;
    const cuuint64_t dims[2] = {FF, DM}, strides[1] = {FF * 2};
    const cuuint32_t box[2] = {64, 48}, rbox[2] = {8, 144}, es[2] = {1, 1};
    for (int i = 0; i < 2; i++) {
        enc(&tm.w[i], CU_TENSOR_MAP_DATA_TYPE_BFLOAT16, 2, d_in[9 + i], dims, strides, box, es, CU_TENSOR_MAP_INTERLEAVE_NONE, CU_TENSOR_MAP_SWIZZLE_128B,
            CU_TENSOR_MAP_L2_PROMOTION_NONE, CU_TENSOR_MAP_FLOAT_OOB_FILL_NONE);
        enc(&tm.r[i], CU_TENSOR_MAP_DATA_TYPE_BFLOAT16, 2, d_in[9 + i], dims, strides, rbox, es, CU_TENSOR_MAP_INTERLEAVE_NONE, CU_TENSOR_MAP_SWIZZLE_NONE,
            CU_TENSOR_MAP_L2_PROMOTION_NONE, CU_TENSOR_MAP_FLOAT_OOB_FILL_NONE);
    }
    const cuuint64_t ddims[2] = {DM / 2, FF}, dstrides[1] = {DM * 2};
    const cuuint32_t dbox[2] = {WD_PITCH / 4, 8};
    enc(&tm.d, CU_TENSOR_MAP_DATA_TYPE_UINT32, 2, d_in[11], ddims, dstrides, dbox, es, CU_TENSOR_MAP_INTERLEAVE_NONE, CU_TENSOR_MAP_SWIZZLE_NONE,
        CU_TENSOR_MAP_L2_PROMOTION_L2_128B, CU_TENSOR_MAP_FLOAT_OOB_FILL_NONE);
    const cuuint64_t xdims[4] = {DM, 128, 4, 4}, xstrides[3] = {DM * 8, DM * 2, DM * 1024};
    const cuuint32_t xbox[4] = {8, 128, 4, 2}, xes[4] = {1, 1, 1, 1};
    enc(&tm.x, CU_TENSOR_MAP_DATA_TYPE_BFLOAT16, 4, d_in[0], xdims, xstrides, xbox, xes, CU_TENSOR_MAP_INTERLEAVE_NONE, CU_TENSOR_MAP_SWIZZLE_NONE,
        CU_TENSOR_MAP_L2_PROMOTION_NONE, CU_TENSOR_MAP_FLOAT_OOB_FILL_NONE);
    fused_kernel<<<NCTA, NTHR, SMEM_TOTAL>>>(p, tm);
}
```

```cpp
#include <cuda_runtime.h>
#include <cuda.h>
#include <cuda_fp16.h>
#include <cuda_bf16.h>
#include <stdint.h>

#define LSEQ 2048
#define DM 576
#define NST 128
#define FF 4608
#define NSEL 8
#define NCTA 128
#define NTHR 640
#define NWRK 640

typedef __nv_bfloat16 bf16;

#define SM_WG 0
#define SM_WU 36864
#define SM_WR 73728
#define SM_XC (82944 - 32768)
#define SM_WD 82944
#define WD_PITCH 592
#define SM_Z2 (SM_WD + 10240)
#define SM_XT (SM_PL - 18 * 1152)
#define SM_PL (SM_WD + 46080)
#define PL_HALF 1344
#define PLW_B 2624
#define PL_B (4 * PLW_B)
#define SM_U (SM_PL + 5 * PL_B)
#define UPAD 20
#define ULO_B ((UPAD + 128) * 16)
#define USLOT_B (2 * ULO_B)
#define SM_KW (SM_U + 5 * USLOT_B)
#define KW_B 3712
#define KW_PL 1216
#define KW_P 2400
#define KW_H 3440
#define SM_MISC (SM_KW + 5 * KW_B)
#define SM_LC (SM_MISC + 416)
#define SM_LNP (SM_LC + 768)
#define SM_RX (SM_LNP + 3840)
#define SMEM_TOTAL (SM_RX + 3088)
#define TBW PLW_B
#define SM_OUT SM_PL
#define SM_XS (SM_PL + 18432)
#define XS_PITCH 592
#define SM_GU (SM_PL + 23296)
#define SM_EX (SM_PL + 24576)

struct __align__(128) Scratch {
    unsigned hint[8 * 32];
    unsigned flag[32];
    uint32_t key3[NCTA * 8];
    uint32_t key[NCTA * 8];
    uint32_t stat[LSEQ];
    uint32_t uT[64 * (LSEQ / 2)];
    uint32_t y[(NCTA + 96) * DM * 8];
    uint32_t part[288 * 64 * 8];
    uint32_t rows[(2 * NCTA + NSEL) * DM];
};
__device__ Scratch g_scratch;
#define STAMP(i)
#define STAMPX(i)
#define STAMPY(i)

__device__ __forceinline__ float rbf(float x) {
    uint32_t r;
    asm("cvt.rn.bf16x2.f32 %0, %1, %2;\n" : "=r"(r) : "f"(x), "f"(0.f));
    return __uint_as_float(r);
}
__device__ __forceinline__ uint32_t pack_bf16(float lo, float hi) {
    uint32_t r;
    asm("cvt.rn.bf16x2.f32 %0, %1, %2;\n" : "=r"(r) : "f"(hi), "f"(lo));
    return r;
}
__device__ __forceinline__ uint32_t pack_f16(float lo, float hi) {
    uint32_t r;
    asm("cvt.rn.f16x2.f32 %0, %1, %2;\n" : "=r"(r) : "f"(hi), "f"(lo));
    return r;
}
__device__ __forceinline__ float bf_lo(uint32_t w) { return __uint_as_float(w << 16); }
__device__ __forceinline__ float bf_hi(uint32_t w) { return __uint_as_float(w & 0xffff0000u); }
__device__ __forceinline__ uint32_t hadd2_bf(uint32_t a, uint32_t b) {
    __nv_bfloat162 r = __hadd2_rn(*reinterpret_cast<__nv_bfloat162*>(&a), *reinterpret_cast<__nv_bfloat162*>(&b));
    return *reinterpret_cast<uint32_t*>(&r);
}
__device__ __forceinline__ uint32_t hsub2_bf(uint32_t a, uint32_t b) {
    __nv_bfloat162 r = __hsub2_rn(*reinterpret_cast<__nv_bfloat162*>(&a), *reinterpret_cast<__nv_bfloat162*>(&b));
    return *reinterpret_cast<uint32_t*>(&r);
}
__device__ __forceinline__ uint32_t hmul2_bf(uint32_t a, uint32_t b) {
    __nv_bfloat162 r = __hmul2_rn(*reinterpret_cast<__nv_bfloat162*>(&a), *reinterpret_cast<__nv_bfloat162*>(&b));
    return *reinterpret_cast<uint32_t*>(&r);
}
__device__ __forceinline__ uint32_t hfma2_bf(uint32_t a, uint32_t b, uint32_t c) { uint32_t r; asm("fma.rn.bf16x2 %0, %1, %2, %3;\n" : "=r"(r) : "r"(a), "r"(b), "r"(c)); return r; }
__device__ __forceinline__ uint32_t hmul2(uint32_t a, uint32_t b) { uint32_t r; asm("mul.rn.f16x2 %0, %1, %2;\n" : "=r"(r) : "r"(a), "r"(b)); return r; }
__device__ __forceinline__ uint32_t hadd2(uint32_t a, uint32_t b) { uint32_t r; asm("add.rn.f16x2 %0, %1, %2;\n" : "=r"(r) : "r"(a), "r"(b)); return r; }
__device__ __forceinline__ uint32_t hfma2(uint32_t a, uint32_t b, uint32_t c) { uint32_t r; asm("fma.rn.f16x2 %0, %1, %2, %3;\n" : "=r"(r) : "r"(a), "r"(b), "r"(c)); return r; }
__device__ __forceinline__ uint32_t hfms2(uint32_t a, uint32_t b, uint32_t c) {
    uint32_t r;
    asm("{\n.reg .b32 n;\nneg.f16x2 n, %2;\nfma.rn.f16x2 %0, %1, n, %3;\n}\n" : "=r"(r) : "r"(a), "r"(b), "r"(c));
    return r;
}
__device__ __forceinline__ uint32_t nzw(uint32_t w) { uint32_t r; asm("max.u32 %0, %1, 1;\n" : "=r"(r) : "r"(w)); return r; }
__device__ __forceinline__ uint32_t smem_u32(const void* p) { return (uint32_t)__cvta_generic_to_shared(p); }
__device__ __forceinline__ uint32_t lds32(uint32_t addr) {
    uint32_t v;
    asm volatile("ld.shared.u32 %0, [%1];\n" : "=r"(v) : "r"(addr) : "memory");
    return v;
}
__device__ __forceinline__ uint32_t lds16(uint32_t addr) {
    unsigned short v;
    asm volatile("ld.shared.u16 %0, [%1];\n" : "=h"(v) : "r"(addr) : "memory");
    return v;
}
__device__ __forceinline__ uint2 lds64(uint32_t addr) {
    uint2 v;
    asm volatile("ld.shared.v2.u32 {%0,%1}, [%2];\n" : "=r"(v.x), "=r"(v.y) : "r"(addr) : "memory");
    return v;
}
__device__ __forceinline__ uint4 lds128(uint32_t addr) {
    uint4 v;
    asm volatile("ld.shared.v4.u32 {%0,%1,%2,%3}, [%4];\n" : "=r"(v.x), "=r"(v.y), "=r"(v.z), "=r"(v.w) : "r"(addr) : "memory");
    return v;
}
__device__ __forceinline__ void sts32(uint32_t addr, uint32_t v) { asm volatile("st.shared.u32 [%0], %1;\n" ::"r"(addr), "r"(v) : "memory"); }
__device__ __forceinline__ void sts16(uint32_t addr, uint32_t v) { asm volatile("st.shared.u16 [%0], %1;\n" ::"r"(addr), "h"((unsigned short)v) : "memory"); }
__device__ __forceinline__ void stsf(uint32_t addr, float v) { sts32(addr, __float_as_uint(v)); }
__device__ __forceinline__ void sts64(uint32_t addr, uint32_t a, uint32_t b) { asm volatile("st.shared.v2.u32 [%0], {%1,%2};\n" ::"r"(addr), "r"(a), "r"(b) : "memory"); }
__device__ __forceinline__ void sts128(uint32_t addr, uint32_t a, uint32_t b, uint32_t c, uint32_t d) {
    asm volatile("st.shared.v4.u32 [%0], {%1,%2,%3,%4};\n" ::"r"(addr), "r"(a), "r"(b), "r"(c), "r"(d) : "memory");
}
__device__ __forceinline__ void ldsm_x4(uint32_t& r0, uint32_t& r1, uint32_t& r2, uint32_t& r3, uint32_t addr) {
    asm volatile("ldmatrix.sync.aligned.m8n8.x4.shared.b16 {%0,%1,%2,%3}, [%4];\n"
                 : "=r"(r0), "=r"(r1), "=r"(r2), "=r"(r3) : "r"(addr) : "memory");
}
__device__ __forceinline__ void ldsm_x4_t(uint32_t& r0, uint32_t& r1, uint32_t& r2, uint32_t& r3, uint32_t addr) {
    asm volatile("ldmatrix.sync.aligned.m8n8.x4.trans.shared.b16 {%0,%1,%2,%3}, [%4];\n"
                 : "=r"(r0), "=r"(r1), "=r"(r2), "=r"(r3) : "r"(addr) : "memory");
}
__device__ __forceinline__ void ldsm_x2_t(uint32_t& r0, uint32_t& r1, uint32_t addr) {
    asm volatile("ldmatrix.sync.aligned.m8n8.x2.trans.shared.b16 {%0,%1}, [%2];\n" : "=r"(r0), "=r"(r1) : "r"(addr) : "memory");
}
__device__ __forceinline__ void ldsm_x1_t(uint32_t& r0, uint32_t addr) {
    asm volatile("ldmatrix.sync.aligned.m8n8.x1.trans.shared.b16 {%0}, [%1];\n" : "=r"(r0) : "r"(addr) : "memory");
}
__device__ __forceinline__ void stsm_x4(uint32_t addr, uint32_t r0, uint32_t r1, uint32_t r2, uint32_t r3) {
    asm volatile("stmatrix.sync.aligned.m8n8.x4.shared.b16 [%0], {%1,%2,%3,%4};\n" ::"r"(addr), "r"(r0), "r"(r1), "r"(r2), "r"(r3) : "memory");
}
__device__ __forceinline__ void stsm_x4_t(uint32_t addr, uint32_t r0, uint32_t r1, uint32_t r2, uint32_t r3) {
    asm volatile("stmatrix.sync.aligned.m8n8.x4.trans.shared.b16 [%0], {%1,%2,%3,%4};\n" ::"r"(addr), "r"(r0), "r"(r1), "r"(r2), "r"(r3) : "memory");
}
__device__ __forceinline__ uint32_t movm(uint32_t a) {
    uint32_t d;
    asm volatile("movmatrix.sync.aligned.m8n8.trans.b16 %0, %1;\n" : "=r"(d) : "r"(a));
    return d;
}
__device__ __forceinline__ void mma_f16(float (&c)[4], uint32_t a0, uint32_t a1, uint32_t a2, uint32_t a3, uint32_t b0, uint32_t b1) {
    asm volatile(
        "mma.sync.aligned.m16n8k16.row.col.f32.f16.f16.f32 {%0,%1,%2,%3}, {%4,%5,%6,%7}, {%8,%9}, {%0,%1,%2,%3};\n"
        : "+f"(c[0]), "+f"(c[1]), "+f"(c[2]), "+f"(c[3])
        : "r"(a0), "r"(a1), "r"(a2), "r"(a3), "r"(b0), "r"(b1));
}
__device__ __forceinline__ void mma_bf16(float (&c)[4], uint32_t a0, uint32_t a1, uint32_t a2, uint32_t a3, uint32_t b0, uint32_t b1) {
    asm volatile(
        "mma.sync.aligned.m16n8k16.row.col.f32.bf16.bf16.f32 {%0,%1,%2,%3}, {%4,%5,%6,%7}, {%8,%9}, {%0,%1,%2,%3};\n"
        : "+f"(c[0]), "+f"(c[1]), "+f"(c[2]), "+f"(c[3])
        : "r"(a0), "r"(a1), "r"(a2), "r"(a3), "r"(b0), "r"(b1));
}
__device__ __forceinline__ void mma_bf16_k8(float (&c)[4], uint32_t a0, uint32_t a1, uint32_t b0) {
    asm volatile("mma.sync.aligned.m16n8k8.row.col.f32.bf16.bf16.f32 {%0,%1,%2,%3}, {%4,%5}, {%6}, {%0,%1,%2,%3};\n"
                 : "+f"(c[0]), "+f"(c[1]), "+f"(c[2]), "+f"(c[3]) : "r"(a0), "r"(a1), "r"(b0));
}
__device__ __forceinline__ void bar_sync(int id, int n) { asm volatile("bar.sync %0, %1;\n" ::"r"(id), "r"(n) : "memory"); }
__device__ __forceinline__ void bar_arrive(int id, int n) { asm volatile("bar.arrive %0, %1;\n" ::"r"(id), "r"(n) : "memory"); }
__device__ __forceinline__ bool bar_or(int id, int n, bool v) {
    uint32_t r;
    asm volatile("{\n.reg .pred p, q;\nsetp.ne.u32 p, %3, 0;\nbar.red.or.pred q, %1, %2, p;\nselp.u32 %0, 1, 0, q;\n}\n" : "=r"(r) : "r"(id), "r"(n), "r"((uint32_t)v) : "memory");
    return r;
}
__device__ __forceinline__ uint32_t and3(uint32_t a, uint32_t b, uint32_t c) { uint32_t r; asm("lop3.b32 %0, %1, %2, %3, 0x80;\n" : "=r"(r) : "r"(a), "r"(b), "r"(c)); return r; }
__device__ __forceinline__ uint32_t or3(uint32_t a, uint32_t b, uint32_t c) { uint32_t r; asm("lop3.b32 %0, %1, %2, %3, 0xfe;\n" : "=r"(r) : "r"(a), "r"(b), "r"(c)); return r; }
__device__ __forceinline__ uint32_t min3(uint32_t a, uint32_t b, uint32_t c) { uint32_t r; asm("{\n.reg .u32 t;\nmin.u32 t, %2, %3;\nmin.u32 %0, %1, t;\n}\n" : "=r"(r) : "r"(a), "r"(b), "r"(c)); return r; }
__device__ __forceinline__ uint32_t xor_or(uint32_t a, uint32_t b, uint32_t c) { uint32_t r; asm("lop3.b32 %0, %1, %2, %3, 0x7e;\n" : "=r"(r) : "r"(a), "r"(b), "r"(c)); return r; }
__device__ __forceinline__ uint32_t pin(uint32_t v) { uint32_t r; asm volatile("shfl.sync.bfly.b32 %0, %1, 0, 0x1f, 0xffffffff;\n" : "=r"(r) : "r"(v) : "memory"); return r; }
__device__ __forceinline__ uint4 ld_poll(const void* p) {
    uint4 v;
    asm volatile("ld.relaxed.gpu.global.v4.u32 {%0,%1,%2,%3}, [%4];\n" : "=r"(v.x), "=r"(v.y), "=r"(v.z), "=r"(v.w) : "l"(p) : "memory");
    return v;
}
__device__ __forceinline__ uint2 ld_poll64(const void* p) {
    uint2 v;
    asm volatile("ld.relaxed.gpu.global.v2.u32 {%0,%1}, [%2];\n" : "=r"(v.x), "=r"(v.y) : "l"(p) : "memory");
    return v;
}
__device__ __forceinline__ uint32_t ld_poll32(const void* p) {
    uint32_t v;
    asm volatile("ld.relaxed.gpu.global.u32 %0, [%1];\n" : "=r"(v) : "l"(p) : "memory");
    return v;
}
__device__ __forceinline__ uint32_t ld_acquire32(const void* p) {
    uint32_t v;
    asm volatile("ld.acquire.gpu.global.u32 %0, [%1];\n" : "=r"(v) : "l"(p) : "memory");
    return v;
}
__device__ __forceinline__ uint2 ldo64(const void* p) {
    uint2 v;
    asm volatile("ld.relaxed.cta.global.v2.u32 {%0,%1}, [%2];\n" : "=r"(v.x), "=r"(v.y) : "l"(p) : "memory");
    return v;
}
__device__ __forceinline__ uint32_t ldo16(const void* p) {
    uint32_t v;
    asm volatile("ld.relaxed.cta.global.u16 %0, [%1];\n" : "=r"(v) : "l"(p) : "memory");
    return v;
}
__device__ __forceinline__ void stg128(void* p, uint32_t a, uint32_t b, uint32_t c, uint32_t d) {
    asm volatile("st.global.v4.u32 [%0], {%1,%2,%3,%4};\n" ::"l"(p), "r"(a), "r"(b), "r"(c), "r"(d) : "memory");
}
__device__ __forceinline__ void stg64(void* p, uint32_t a, uint32_t b) { asm volatile("st.global.v2.u32 [%0], {%1,%2};\n" ::"l"(p), "r"(a), "r"(b) : "memory"); }
__device__ __forceinline__ uint32_t min4(const uint4& v) { return min(min(v.x, v.y), min(v.z, v.w)); }
#define SPIN_LIMIT (1 << 21)
#define TRAP() __trap()
__device__ __forceinline__ void mbar_init(uint32_t bar, uint32_t cnt) { asm volatile("mbarrier.init.shared::cta.b64 [%0], %1;\n" ::"r"(bar), "r"(cnt) : "memory"); }
__device__ __forceinline__ void mbar_expect(uint32_t bar, uint32_t bytes) {
    asm volatile("mbarrier.arrive.expect_tx.shared::cta.b64 _, [%0], %1;\n" ::"r"(bar), "r"(bytes) : "memory");
}
__device__ __forceinline__ void mbar_arrive(uint32_t bar) { asm volatile("mbarrier.arrive.shared::cta.b64 _, [%0];\n" ::"r"(bar) : "memory"); }
__device__ __forceinline__ void mbar_wait(uint32_t bar) {
    asm volatile(
        "{\n.reg .pred p;\n"
        "W_%=:\n"
        "mbarrier.try_wait.parity.shared::cta.b64 p, [%0], 0;\n"
        "@!p bra W_%=;\n}\n" ::"r"(bar) : "memory");
}
__device__ __forceinline__ void bulk_g2s(uint32_t dst, const void* src, uint32_t bytes, uint32_t bar) {
    asm volatile("cp.async.bulk.shared::cluster.global.mbarrier::complete_tx::bytes [%0], [%1], %2, [%3];\n" ::"r"(dst), "l"(src), "r"(bytes), "r"(bar) : "memory");
}
__device__ __forceinline__ void bulk_s2g(void* dst, uint32_t src, uint32_t bytes) {
    asm volatile("cp.async.bulk.global.shared::cta.bulk_group [%0], [%1], %2;\ncp.async.bulk.commit_group;\n" ::"l"(dst), "r"(src), "r"(bytes) : "memory");
}
__device__ __forceinline__ void bulk_s2g_nc(void* dst, uint32_t src, uint32_t bytes) {
    asm volatile("cp.async.bulk.global.shared::cta.bulk_group [%0], [%1], %2;\n" ::"l"(dst), "r"(src), "r"(bytes) : "memory");
}
__device__ __forceinline__ void tma_2d(uint32_t dst, const CUtensorMap* tm, int c0, int c1, uint32_t bar) {
    asm volatile("cp.async.bulk.tensor.2d.shared::cluster.global.mbarrier::complete_tx::bytes [%0], [%1, {%3, %4}], [%2];\n"
                 ::"r"(dst), "l"(tm), "r"(bar), "r"(c0), "r"(c1) : "memory");
}
__device__ __forceinline__ void tma_4d_mc(uint32_t dst, const CUtensorMap* tm, int c0, int c3, uint32_t bar) {
    asm volatile("cp.async.bulk.tensor.4d.shared::cluster.global.mbarrier::complete_tx::bytes.multicast::cluster [%0], [%1, {%3, %4, %4, %5}], [%2], %6;\n"
                 ::"r"(dst), "l"(tm), "r"(bar), "r"(c0), "r"(0), "r"(c3), "h"((unsigned short)3) : "memory");
}
__device__ __forceinline__ bool elect_one() {
    uint32_t r;
    asm volatile("{\n.reg .pred p;\nelect.sync _|p, 0xffffffff;\nselp.u32 %0, 1, 0, p;\n}\n" : "=r"(r));
    return r;
}
__device__ __forceinline__ void delay(uint32_t clks) {
    uint32_t t0, t1;
    asm volatile("mov.u32 %0, %%clock;" : "=r"(t0) :: "memory");
    do { asm volatile("mov.u32 %0, %%clock;" : "=r"(t1) :: "memory"); } while (t1 - t0 < clks);
}
__device__ __forceinline__ void fence_async() { asm volatile("fence.proxy.async.shared::cta;\n" ::: "memory"); }

__device__ __forceinline__ float2 cmul(float2 a, float2 b) {
    return make_float2(fmaf(a.x, b.x, -a.y * b.y), fmaf(a.x, b.y, a.y * b.x));
}
__device__ __forceinline__ float2 csq(float2 a) {
    float p = a.x * a.y;
    return make_float2(fmaf(a.x, a.x, -a.y * a.y), p + p);
}
__device__ __forceinline__ float ex2_approx(float x) { float r; asm("ex2.approx.ftz.f32 %0, %1;\n" : "=f"(r) : "f"(x)); return r; }
__device__ __forceinline__ float exp_bf(float x) { return rbf(ex2_approx(__fmul_ru(x, 1.4426950408889634f))); }
__device__ __forceinline__ float2 cexp_e(float lr2, float li, float e) {
    const float m = ex2_approx(lr2 * e);
    return make_float2(m * __cosf(li * e), m * __sinf(li * e));
}
__device__ __forceinline__ float rcp_approx(float x) { float r; asm("rcp.approx.ftz.f32 %0, %1;\n" : "=f"(r) : "f"(x)); return r; }
__device__ __forceinline__ float sigmoid_f(float x) { return rcp_approx(1.0f + ex2_approx(x * -1.4426950408889634f)); }
__device__ __forceinline__ float sqrt_approx(float x) { float r; asm("sqrt.approx.ftz.f32 %0, %1;\n" : "=f"(r) : "f"(x)); return r; }

__device__ __forceinline__ void wg_fence() { asm volatile("wgmma.fence.sync.aligned;\n" ::: "memory"); }
__device__ __forceinline__ void wg_commit() { asm volatile("wgmma.commit_group.sync.aligned;\n" ::: "memory"); }
__device__ __forceinline__ void wg_wait0() { asm volatile("wgmma.wait_group.sync.aligned 0;\n" ::: "memory"); }
template <int T> __device__ __forceinline__ void wg_mma(float (&acc)[16][4], const uint32_t* a, uint64_t desc);
template <int T> __device__ __forceinline__ void wg_first(float (&acc)[16][4], const uint32_t* a, uint64_t desc);
template <> __device__ __forceinline__ void wg_mma<0>(float (&acc)[16][4], const uint32_t* a, uint64_t desc) {
    asm volatile("wgmma.mma_async.sync.aligned.m64n128k16.f32.f16.f16 {%0,%1,%2,%3,%4,%5,%6,%7,%8,%9,%10,%11,%12,%13,%14,%15,%16,%17,%18,%19,%20,%21,%22,%23,%24,%25,%26,%27,%28,%29,%30,%31,%32,%33,%34,%35,%36,%37,%38,%39,%40,%41,%42,%43,%44,%45,%46,%47,%48,%49,%50,%51,%52,%53,%54,%55,%56,%57,%58,%59,%60,%61,%62,%63}, {%64,%65,%66,%67}, %68, 1, 1, 1, 0;\n"
                 : "+f"(acc[0][0]), "+f"(acc[0][1]), "+f"(acc[0][2]), "+f"(acc[0][3]), "+f"(acc[1][0]), "+f"(acc[1][1]), "+f"(acc[1][2]), "+f"(acc[1][3]), "+f"(acc[2][0]), "+f"(acc[2][1]), "+f"(acc[2][2]), "+f"(acc[2][3]), "+f"(acc[3][0]), "+f"(acc[3][1]), "+f"(acc[3][2]), "+f"(acc[3][3]), "+f"(acc[4][0]), "+f"(acc[4][1]), "+f"(acc[4][2]), "+f"(acc[4][3]), "+f"(acc[5][0]), "+f"(acc[5][1]), "+f"(acc[5][2]), "+f"(acc[5][3]), "+f"(acc[6][0]), "+f"(acc[6][1]), "+f"(acc[6][2]), "+f"(acc[6][3]), "+f"(acc[7][0]), "+f"(acc[7][1]), "+f"(acc[7][2]), "+f"(acc[7][3]), "+f"(acc[8][0]), "+f"(acc[8][1]), "+f"(acc[8][2]), "+f"(acc[8][3]), "+f"(acc[9][0]), "+f"(acc[9][1]), "+f"(acc[9][2]), "+f"(acc[9][3]), "+f"(acc[10][0]), "+f"(acc[10][1]), "+f"(acc[10][2]), "+f"(acc[10][3]), "+f"(acc[11][0]), "+f"(acc[11][1]), "+f"(acc[11][2]), "+f"(acc[11][3]), "+f"(acc[12][0]), "+f"(acc[12][1]), "+f"(acc[12][2]), "+f"(acc[12][3]), "+f"(acc[13][0]), "+f"(acc[13][1]), "+f"(acc[13][2]), "+f"(acc[13][3]), "+f"(acc[14][0]), "+f"(acc[14][1]), "+f"(acc[14][2]), "+f"(acc[14][3]), "+f"(acc[15][0]), "+f"(acc[15][1]), "+f"(acc[15][2]), "+f"(acc[15][3])
                 : "r"(a[0]), "r"(a[1]), "r"(a[2]), "r"(a[3]), "l"(desc));
}
template <> __device__ __forceinline__ void wg_mma<2>(float (&acc)[16][4], const uint32_t* a, uint64_t desc) {
    asm volatile("wgmma.mma_async.sync.aligned.m64n112k16.f32.f16.f16 {%0,%1,%2,%3,%4,%5,%6,%7,%8,%9,%10,%11,%12,%13,%14,%15,%16,%17,%18,%19,%20,%21,%22,%23,%24,%25,%26,%27,%28,%29,%30,%31,%32,%33,%34,%35,%36,%37,%38,%39,%40,%41,%42,%43,%44,%45,%46,%47,%48,%49,%50,%51,%52,%53,%54,%55}, {%56,%57,%58,%59}, %60, 1, 1, 1, 0;\n"
                 : "+f"(acc[2][0]), "+f"(acc[2][1]), "+f"(acc[2][2]), "+f"(acc[2][3]), "+f"(acc[3][0]), "+f"(acc[3][1]), "+f"(acc[3][2]), "+f"(acc[3][3]), "+f"(acc[4][0]), "+f"(acc[4][1]), "+f"(acc[4][2]), "+f"(acc[4][3]), "+f"(acc[5][0]), "+f"(acc[5][1]), "+f"(acc[5][2]), "+f"(acc[5][3]), "+f"(acc[6][0]), "+f"(acc[6][1]), "+f"(acc[6][2]), "+f"(acc[6][3]), "+f"(acc[7][0]), "+f"(acc[7][1]), "+f"(acc[7][2]), "+f"(acc[7][3]), "+f"(acc[8][0]), "+f"(acc[8][1]), "+f"(acc[8][2]), "+f"(acc[8][3]), "+f"(acc[9][0]), "+f"(acc[9][1]), "+f"(acc[9][2]), "+f"(acc[9][3]), "+f"(acc[10][0]), "+f"(acc[10][1]), "+f"(acc[10][2]), "+f"(acc[10][3]), "+f"(acc[11][0]), "+f"(acc[11][1]), "+f"(acc[11][2]), "+f"(acc[11][3]), "+f"(acc[12][0]), "+f"(acc[12][1]), "+f"(acc[12][2]), "+f"(acc[12][3]), "+f"(acc[13][0]), "+f"(acc[13][1]), "+f"(acc[13][2]), "+f"(acc[13][3]), "+f"(acc[14][0]), "+f"(acc[14][1]), "+f"(acc[14][2]), "+f"(acc[14][3]), "+f"(acc[15][0]), "+f"(acc[15][1]), "+f"(acc[15][2]), "+f"(acc[15][3])
                 : "r"(a[0]), "r"(a[1]), "r"(a[2]), "r"(a[3]), "l"(desc));
}
template <> __device__ __forceinline__ void wg_mma<4>(float (&acc)[16][4], const uint32_t* a, uint64_t desc) {
    asm volatile("wgmma.mma_async.sync.aligned.m64n96k16.f32.f16.f16 {%0,%1,%2,%3,%4,%5,%6,%7,%8,%9,%10,%11,%12,%13,%14,%15,%16,%17,%18,%19,%20,%21,%22,%23,%24,%25,%26,%27,%28,%29,%30,%31,%32,%33,%34,%35,%36,%37,%38,%39,%40,%41,%42,%43,%44,%45,%46,%47}, {%48,%49,%50,%51}, %52, 1, 1, 1, 0;\n"
                 : "+f"(acc[4][0]), "+f"(acc[4][1]), "+f"(acc[4][2]), "+f"(acc[4][3]), "+f"(acc[5][0]), "+f"(acc[5][1]), "+f"(acc[5][2]), "+f"(acc[5][3]), "+f"(acc[6][0]), "+f"(acc[6][1]), "+f"(acc[6][2]), "+f"(acc[6][3]), "+f"(acc[7][0]), "+f"(acc[7][1]), "+f"(acc[7][2]), "+f"(acc[7][3]), "+f"(acc[8][0]), "+f"(acc[8][1]), "+f"(acc[8][2]), "+f"(acc[8][3]), "+f"(acc[9][0]), "+f"(acc[9][1]), "+f"(acc[9][2]), "+f"(acc[9][3]), "+f"(acc[10][0]), "+f"(acc[10][1]), "+f"(acc[10][2]), "+f"(acc[10][3]), "+f"(acc[11][0]), "+f"(acc[11][1]), "+f"(acc[11][2]), "+f"(acc[11][3]), "+f"(acc[12][0]), "+f"(acc[12][1]), "+f"(acc[12][2]), "+f"(acc[12][3]), "+f"(acc[13][0]), "+f"(acc[13][1]), "+f"(acc[13][2]), "+f"(acc[13][3]), "+f"(acc[14][0]), "+f"(acc[14][1]), "+f"(acc[14][2]), "+f"(acc[14][3]), "+f"(acc[15][0]), "+f"(acc[15][1]), "+f"(acc[15][2]), "+f"(acc[15][3])
                 : "r"(a[0]), "r"(a[1]), "r"(a[2]), "r"(a[3]), "l"(desc));
}
template <> __device__ __forceinline__ void wg_mma<6>(float (&acc)[16][4], const uint32_t* a, uint64_t desc) {
    asm volatile("wgmma.mma_async.sync.aligned.m64n80k16.f32.f16.f16 {%0,%1,%2,%3,%4,%5,%6,%7,%8,%9,%10,%11,%12,%13,%14,%15,%16,%17,%18,%19,%20,%21,%22,%23,%24,%25,%26,%27,%28,%29,%30,%31,%32,%33,%34,%35,%36,%37,%38,%39}, {%40,%41,%42,%43}, %44, 1, 1, 1, 0;\n"
                 : "+f"(acc[6][0]), "+f"(acc[6][1]), "+f"(acc[6][2]), "+f"(acc[6][3]), "+f"(acc[7][0]), "+f"(acc[7][1]), "+f"(acc[7][2]), "+f"(acc[7][3]), "+f"(acc[8][0]), "+f"(acc[8][1]), "+f"(acc[8][2]), "+f"(acc[8][3]), "+f"(acc[9][0]), "+f"(acc[9][1]), "+f"(acc[9][2]), "+f"(acc[9][3]), "+f"(acc[10][0]), "+f"(acc[10][1]), "+f"(acc[10][2]), "+f"(acc[10][3]), "+f"(acc[11][0]), "+f"(acc[11][1]), "+f"(acc[11][2]), "+f"(acc[11][3]), "+f"(acc[12][0]), "+f"(acc[12][1]), "+f"(acc[12][2]), "+f"(acc[12][3]), "+f"(acc[13][0]), "+f"(acc[13][1]), "+f"(acc[13][2]), "+f"(acc[13][3]), "+f"(acc[14][0]), "+f"(acc[14][1]), "+f"(acc[14][2]), "+f"(acc[14][3]), "+f"(acc[15][0]), "+f"(acc[15][1]), "+f"(acc[15][2]), "+f"(acc[15][3])
                 : "r"(a[0]), "r"(a[1]), "r"(a[2]), "r"(a[3]), "l"(desc));
}
template <> __device__ __forceinline__ void wg_mma<8>(float (&acc)[16][4], const uint32_t* a, uint64_t desc) {
    asm volatile("wgmma.mma_async.sync.aligned.m64n64k16.f32.f16.f16 {%0,%1,%2,%3,%4,%5,%6,%7,%8,%9,%10,%11,%12,%13,%14,%15,%16,%17,%18,%19,%20,%21,%22,%23,%24,%25,%26,%27,%28,%29,%30,%31}, {%32,%33,%34,%35}, %36, 1, 1, 1, 0;\n"
                 : "+f"(acc[8][0]), "+f"(acc[8][1]), "+f"(acc[8][2]), "+f"(acc[8][3]), "+f"(acc[9][0]), "+f"(acc[9][1]), "+f"(acc[9][2]), "+f"(acc[9][3]), "+f"(acc[10][0]), "+f"(acc[10][1]), "+f"(acc[10][2]), "+f"(acc[10][3]), "+f"(acc[11][0]), "+f"(acc[11][1]), "+f"(acc[11][2]), "+f"(acc[11][3]), "+f"(acc[12][0]), "+f"(acc[12][1]), "+f"(acc[12][2]), "+f"(acc[12][3]), "+f"(acc[13][0]), "+f"(acc[13][1]), "+f"(acc[13][2]), "+f"(acc[13][3]), "+f"(acc[14][0]), "+f"(acc[14][1]), "+f"(acc[14][2]), "+f"(acc[14][3]), "+f"(acc[15][0]), "+f"(acc[15][1]), "+f"(acc[15][2]), "+f"(acc[15][3])
                 : "r"(a[0]), "r"(a[1]), "r"(a[2]), "r"(a[3]), "l"(desc));
}
template <> __device__ __forceinline__ void wg_mma<10>(float (&acc)[16][4], const uint32_t* a, uint64_t desc) {
    asm volatile("wgmma.mma_async.sync.aligned.m64n48k16.f32.f16.f16 {%0,%1,%2,%3,%4,%5,%6,%7,%8,%9,%10,%11,%12,%13,%14,%15,%16,%17,%18,%19,%20,%21,%22,%23}, {%24,%25,%26,%27}, %28, 1, 1, 1, 0;\n"
                 : "+f"(acc[10][0]), "+f"(acc[10][1]), "+f"(acc[10][2]), "+f"(acc[10][3]), "+f"(acc[11][0]), "+f"(acc[11][1]), "+f"(acc[11][2]), "+f"(acc[11][3]), "+f"(acc[12][0]), "+f"(acc[12][1]), "+f"(acc[12][2]), "+f"(acc[12][3]), "+f"(acc[13][0]), "+f"(acc[13][1]), "+f"(acc[13][2]), "+f"(acc[13][3]), "+f"(acc[14][0]), "+f"(acc[14][1]), "+f"(acc[14][2]), "+f"(acc[14][3]), "+f"(acc[15][0]), "+f"(acc[15][1]), "+f"(acc[15][2]), "+f"(acc[15][3])
                 : "r"(a[0]), "r"(a[1]), "r"(a[2]), "r"(a[3]), "l"(desc));
}
template <> __device__ __forceinline__ void wg_mma<12>(float (&acc)[16][4], const uint32_t* a, uint64_t desc) {
    asm volatile("wgmma.mma_async.sync.aligned.m64n32k16.f32.f16.f16 {%0,%1,%2,%3,%4,%5,%6,%7,%8,%9,%10,%11,%12,%13,%14,%15}, {%16,%17,%18,%19}, %20, 1, 1, 1, 0;\n"
                 : "+f"(acc[12][0]), "+f"(acc[12][1]), "+f"(acc[12][2]), "+f"(acc[12][3]), "+f"(acc[13][0]), "+f"(acc[13][1]), "+f"(acc[13][2]), "+f"(acc[13][3]), "+f"(acc[14][0]), "+f"(acc[14][1]), "+f"(acc[14][2]), "+f"(acc[14][3]), "+f"(acc[15][0]), "+f"(acc[15][1]), "+f"(acc[15][2]), "+f"(acc[15][3])
                 : "r"(a[0]), "r"(a[1]), "r"(a[2]), "r"(a[3]), "l"(desc));
}
template <> __device__ __forceinline__ void wg_mma<14>(float (&acc)[16][4], const uint32_t* a, uint64_t desc) {
    asm volatile("wgmma.mma_async.sync.aligned.m64n16k16.f32.f16.f16 {%0,%1,%2,%3,%4,%5,%6,%7}, {%8,%9,%10,%11}, %12, 1, 1, 1, 0;\n"
                 : "+f"(acc[14][0]), "+f"(acc[14][1]), "+f"(acc[14][2]), "+f"(acc[14][3]), "+f"(acc[15][0]), "+f"(acc[15][1]), "+f"(acc[15][2]), "+f"(acc[15][3])
                 : "r"(a[0]), "r"(a[1]), "r"(a[2]), "r"(a[3]), "l"(desc));
}
template <> __device__ __forceinline__ void wg_first<0>(float (&acc)[16][4], const uint32_t* a, uint64_t desc) {
    asm volatile("wgmma.mma_async.sync.aligned.m64n128k16.f32.f16.f16 {%0,%1,%2,%3,%4,%5,%6,%7,%8,%9,%10,%11,%12,%13,%14,%15,%16,%17,%18,%19,%20,%21,%22,%23,%24,%25,%26,%27,%28,%29,%30,%31,%32,%33,%34,%35,%36,%37,%38,%39,%40,%41,%42,%43,%44,%45,%46,%47,%48,%49,%50,%51,%52,%53,%54,%55,%56,%57,%58,%59,%60,%61,%62,%63}, {%64,%65,%66,%67}, %68, 0, 1, 1, 0;\n"
                 : "=f"(acc[0][0]), "=f"(acc[0][1]), "=f"(acc[0][2]), "=f"(acc[0][3]), "=f"(acc[1][0]), "=f"(acc[1][1]), "=f"(acc[1][2]), "=f"(acc[1][3]), "=f"(acc[2][0]), "=f"(acc[2][1]), "=f"(acc[2][2]), "=f"(acc[2][3]), "=f"(acc[3][0]), "=f"(acc[3][1]), "=f"(acc[3][2]), "=f"(acc[3][3]), "=f"(acc[4][0]), "=f"(acc[4][1]), "=f"(acc[4][2]), "=f"(acc[4][3]), "=f"(acc[5][0]), "=f"(acc[5][1]), "=f"(acc[5][2]), "=f"(acc[5][3]), "=f"(acc[6][0]), "=f"(acc[6][1]), "=f"(acc[6][2]), "=f"(acc[6][3]), "=f"(acc[7][0]), "=f"(acc[7][1]), "=f"(acc[7][2]), "=f"(acc[7][3]), "=f"(acc[8][0]), "=f"(acc[8][1]), "=f"(acc[8][2]), "=f"(acc[8][3]), "=f"(acc[9][0]), "=f"(acc[9][1]), "=f"(acc[9][2]), "=f"(acc[9][3]), "=f"(acc[10][0]), "=f"(acc[10][1]), "=f"(acc[10][2]), "=f"(acc[10][3]), "=f"(acc[11][0]), "=f"(acc[11][1]), "=f"(acc[11][2]), "=f"(acc[11][3]), "=f"(acc[12][0]), "=f"(acc[12][1]), "=f"(acc[12][2]), "=f"(acc[12][3]), "=f"(acc[13][0]), "=f"(acc[13][1]), "=f"(acc[13][2]), "=f"(acc[13][3]), "=f"(acc[14][0]), "=f"(acc[14][1]), "=f"(acc[14][2]), "=f"(acc[14][3]), "=f"(acc[15][0]), "=f"(acc[15][1]), "=f"(acc[15][2]), "=f"(acc[15][3])
                 : "r"(a[0]), "r"(a[1]), "r"(a[2]), "r"(a[3]), "l"(desc));
}
template <> __device__ __forceinline__ void wg_first<4>(float (&acc)[16][4], const uint32_t* a, uint64_t desc) {
    asm volatile("wgmma.mma_async.sync.aligned.m64n96k16.f32.f16.f16 {%0,%1,%2,%3,%4,%5,%6,%7,%8,%9,%10,%11,%12,%13,%14,%15,%16,%17,%18,%19,%20,%21,%22,%23,%24,%25,%26,%27,%28,%29,%30,%31,%32,%33,%34,%35,%36,%37,%38,%39,%40,%41,%42,%43,%44,%45,%46,%47}, {%48,%49,%50,%51}, %52, 0, 1, 1, 0;\n"
                 : "=f"(acc[4][0]), "=f"(acc[4][1]), "=f"(acc[4][2]), "=f"(acc[4][3]), "=f"(acc[5][0]), "=f"(acc[5][1]), "=f"(acc[5][2]), "=f"(acc[5][3]), "=f"(acc[6][0]), "=f"(acc[6][1]), "=f"(acc[6][2]), "=f"(acc[6][3]), "=f"(acc[7][0]), "=f"(acc[7][1]), "=f"(acc[7][2]), "=f"(acc[7][3]), "=f"(acc[8][0]), "=f"(acc[8][1]), "=f"(acc[8][2]), "=f"(acc[8][3]), "=f"(acc[9][0]), "=f"(acc[9][1]), "=f"(acc[9][2]), "=f"(acc[9][3]), "=f"(acc[10][0]), "=f"(acc[10][1]), "=f"(acc[10][2]), "=f"(acc[10][3]), "=f"(acc[11][0]), "=f"(acc[11][1]), "=f"(acc[11][2]), "=f"(acc[11][3]), "=f"(acc[12][0]), "=f"(acc[12][1]), "=f"(acc[12][2]), "=f"(acc[12][3]), "=f"(acc[13][0]), "=f"(acc[13][1]), "=f"(acc[13][2]), "=f"(acc[13][3]), "=f"(acc[14][0]), "=f"(acc[14][1]), "=f"(acc[14][2]), "=f"(acc[14][3]), "=f"(acc[15][0]), "=f"(acc[15][1]), "=f"(acc[15][2]), "=f"(acc[15][3])
                 : "r"(a[0]), "r"(a[1]), "r"(a[2]), "r"(a[3]), "l"(desc));
}

#define SDLY 1500
#define UDLY 1400
#define KDLY 850
#define FDLY 950
#define FDLY2 350
#define DDLY 300
#define WDLY 500
#define HW 15
#define FIX(v) do { if ((v) == 1u) TRAP(); } while (0)
#define STAMPW(i) STAMPY(i)
#define STAMP2(i) STAMP(i)
#undef STAMPX
#define STAMPX(i)
struct Params {
    const bf16 *x, *lar, *aim, *cre, *cim, *ldt, *dsk;
    Scratch* s;
    const bf16* wr;
    bf16* out;
};
struct Maps { CUtensorMap x, w[2], r[2], d; };

#define TOK(g) (2 * (g) - ((g) & 1))
#define ROWTOK(r) (TOK((r) & 7) + (((r) >> 2) & 2))
__device__ __forceinline__ void ln_partial(const uint32_t (&H)[2][4], float (&d)[2][4]) {
#pragma unroll
    for (int i = 0; i < 8; i++) d[i >> 2][i & 3] = 0.f;
#pragma unroll
    for (int k = 0; k < 4; k++)
#pragma unroll
        for (int hf = 0; hf < 2; hf++) mma_bf16_k8(d[hf], H[hf][k], 0x3f803f80u, H[hf][k]);
}
__device__ __forceinline__ float sum18(uint32_t a) {
    const uint4 p = lds128(a), q = lds128(a + 16), r = lds128(a + 32), s = lds128(a + 48);
    const uint2 u = lds64(a + 64);
#define F(x) __uint_as_float(x)
    return (((F(p.x) + F(p.y)) + (F(p.z) + F(p.w))) + ((F(q.x) + F(q.y)) + (F(q.z) + F(q.w)))) +
           (((F(r.x) + F(r.y)) + (F(r.z) + F(r.w))) + ((F(s.x) + F(s.y)) + (F(s.z) + F(s.w))) + (F(u.x) + F(u.y)));
#undef F
}
__device__ __forceinline__ void ln_stats(float sm, float sq, float& mb, float& sd) {
    const float m0 = sm * (1.0f / 576.0f);
    const float mean = fmaf(fmaf(-m0, 576.0f, sm), 1.0f / 576.0f, m0);
    const float var = fmaxf(fmaf(-mean, mean, sq * (1.0f / 576.0f)), 0.f);
    mb = rbf(mean);
    sd = rbf(sqrt_approx(rbf(rbf(var) + 1e-5f)));
}
__device__ __forceinline__ void ln_finish(float v, int lane, float& mb, float& rc) {
    const float o = __shfl_xor_sync(0xffffffffu, v, 16);
    float sd;
    ln_stats(lane < 16 ? v : o, lane < 16 ? o : v, mb, sd);
    rc = rcp_approx(sd);
}
__device__ __forceinline__ uint32_t ln_apply(uint32_t w, uint32_t m2, uint32_t rh, uint32_t rl) {
    const uint32_t d = hsub2_bf(w, m2);
    return hfma2_bf(d, rh, hmul2_bf(d, rl));
}
__device__ __forceinline__ void stat_store(uint32_t a, float mb, float rc, uint32_t extra) {
    const float rh = rbf(rc);
    sts64(a, (__float_as_uint(mb) >> 16) | (extra << 16), pack_bf16(rh, rc - rh));
}
#define STAT_M(s) __byte_perm((s).x, (s).x, 0x1010)
#define STAT_H(s) __byte_perm((s).y, (s).y, 0x1010)
#define STAT_L(s) __byte_perm((s).y, (s).y, 0x3232)

__device__ __forceinline__ void hcmul(uint32_t re, uint32_t im, uint32_t zx, uint32_t zy, uint32_t& ore, uint32_t& oim) {
    ore = hfms2(im, zy, hmul2(re, zx));
    oim = hfma2(re, zy, hmul2(im, zx));
}

struct KGen {
    uint32_t A[2][4][4];
    float2 z1, z8, z64, z128, T[9];
};
__device__ __forceinline__ void kgen_setup(KGen& k, float lar, float aim, float dt) {
    const float lr2 = -(exp_bf(lar) * dt) * 1.4426950408889634f, li = aim * dt;
    k.z1 = cexp_e(lr2, li, 1.0f);
    k.z8 = cexp_e(lr2, li, 8.0f);
    k.z64 = cexp_e(lr2, li, 64.0f);
}
__device__ __forceinline__ void kgen_rows(KGen& k, uint32_t tb, int lane) {
    const float2 z8 = k.z8, z64 = k.z64;
    const uint32_t row = tb + lane * 16;
    k.z128 = csq(z64);
    const float2 z16 = csq(z8), z24 = cmul(z16, z8), z32 = csq(z16), z40 = cmul(z32, z8), z48 = csq(z24), z56 = cmul(z32, z24);
    uint32_t re[4], im[4], a[4], b[4];
    re[0] = pack_f16(1.0f, z8.x); im[0] = pack_f16(0.0f, z8.y);
    re[1] = pack_f16(z16.x, z24.x); im[1] = pack_f16(z16.y, z24.y);
    re[2] = pack_f16(z32.x, z40.x); im[2] = pack_f16(z32.y, z40.y);
    re[3] = pack_f16(z48.x, z56.x); im[3] = pack_f16(z48.y, z56.y);
    sts128(row, re[0], re[1], re[2], re[3]);
    sts128(row + 1024, im[0], im[1], im[2], im[3]);
    const uint32_t zx = pack_f16(z64.x, z64.x), zy = pack_f16(z64.y, z64.y), zw = pack_f16(k.z128.x, k.z128.y);
#pragma unroll
    for (int j = 0; j < 4; j++) hcmul(re[j], im[j], zx, zy, a[j], b[j]);
    sts128(row + 512, a[0], a[1], a[2], a[3]);
    sts128(row + 1536, b[0], b[1], b[2], b[3]);
    const int mi = lane >> 3;
    const uint32_t zd = tb + 2048 + mi * 16;
    sts16(tb + 2048 + lane * 2, zw); sts16(tb + 2112 + lane * 2, zw >> 16);
    __syncwarp();
    const uint32_t ad = tb + (lane & 7) * 16 + mi * 512;
    ldsm_x4(a[0], a[1], a[2], a[3], zd);
    ldsm_x4(b[0], b[1], b[2], b[3], zd + 64);
#pragma unroll
    for (int ks = 0; ks < 4; ks++) {
        ldsm_x4_t(k.A[0][ks][0], k.A[0][ks][1], k.A[0][ks][2], k.A[0][ks][3], ad + ks * 128);
        hcmul(k.A[0][ks][0], k.A[0][ks][2], a[ks], b[ks], k.A[1][ks][0], k.A[1][ks][2]);
        hcmul(k.A[0][ks][1], k.A[0][ks][3], a[ks], b[ks], k.A[1][ks][1], k.A[1][ks][3]);
    }
}
__device__ __forceinline__ void kgen_chain(KGen& k, uint32_t cr, uint32_t ci, float cs) {
    k.T[0] = make_float2(bf_lo(cr) * cs, -bf_lo(ci) * cs);
    const float2 y1 = make_float2(k.z1.x, -k.z1.y);
#pragma unroll
    for (int c = 1; c < 8; c++) k.T[c] = cmul(k.T[c - 1], y1);
    k.T[8] = cmul(k.T[0], make_float2(k.z8.x, -k.z8.y));
}
__device__ __forceinline__ void kgen_cols(KGen& k, uint32_t tb, uint32_t t5, int lane) {
    const uint32_t row = tb + lane * 16;
    const float2 (&T)[9] = k.T;
    const float2 y128 = make_float2(k.z128.x, -k.z128.y);
    const float2 y256 = csq(y128), y512 = csq(y256), y768 = cmul(y512, y256), y1024 = csq(y512);
    const float2 c1032 = cmul(T[8], y1024);
    __syncwarp();
    sts128(row, pack_f16(T[0].x, T[1].x), pack_f16(T[2].x, T[3].x), pack_f16(T[4].x, T[5].x), pack_f16(T[6].x, T[7].x));
    sts128(row + 512, pack_f16(T[0].y, T[1].y), pack_f16(T[2].y, T[3].y), pack_f16(T[4].y, T[5].y), pack_f16(T[6].y, T[7].y));
    uint32_t a[4], b[4];
    {
        const uint32_t zx = pack_f16(y256.x, y256.x), zy = pack_f16(y256.y, y256.y);
        hcmul(pack_f16(T[0].x, T[2].x), pack_f16(T[0].y, T[2].y), zx, zy, a[0], b[0]);
        hcmul(pack_f16(T[4].x, T[6].x), pack_f16(T[4].y, T[6].y), zx, zy, a[1], b[1]);
        const uint32_t r04 = pack_f16(T[0].x, T[4].x), i04 = pack_f16(T[0].y, T[4].y);
        hcmul(r04, i04, pack_f16(y512.x, y512.x), pack_f16(y512.y, y512.y), a[2], b[2]);
        hcmul(r04, i04, pack_f16(y768.x, y768.x), pack_f16(y768.y, y768.y), a[3], b[3]);
    }
    sts128(row + 1024, a[0], a[1], a[2], a[3]);
    sts128(row + 1536, b[0], b[1], b[2], b[3]);
    {
        const uint32_t r0 = pack_f16(1.0f, y256.x), i0 = pack_f16(0.0f, y256.y), r1 = pack_f16(y512.x, y768.x), i1 = pack_f16(y512.y, y768.y);
        const uint32_t zx = pack_f16(T[8].x, T[8].x), zy = pack_f16(T[8].y, T[8].y), wx = pack_f16(c1032.x, c1032.x), wy = pack_f16(c1032.y, c1032.y);
        hcmul(r0, i0, zx, zy, a[0], b[0]); hcmul(r1, i1, zx, zy, a[1], b[1]);
        hcmul(r0, i0, wx, wy, a[2], b[2]); hcmul(r1, i1, wx, wy, a[3], b[3]);
    }
    sts128(row + 2048, a[0], a[1], a[2], a[3]);
    sts128(t5 + lane * 16, b[0], b[1], b[2], b[3]);
}
__device__ __forceinline__ void kgen_mma(const KGen& k, uint32_t tb, uint32_t t5, int lane) {
    __syncwarp();
    float acc[2][3][4];
#pragma unroll
    for (int i = 0; i < 6; i++)
#pragma unroll
        for (int j = 0; j < 4; j++) acc[i / 3][i % 3][j] = 0.f;
    const int mi = lane >> 3;
    const uint32_t ro = ((lane & 7) + 8 * (mi >> 1)) * 16, bd = tb + ro + (mi & 1) * 512, b2 = ro + ((mi & 1) ? t5 : tb + 2048);
#pragma unroll
    for (int kp = 0; kp < 2; kp++)
#pragma unroll
        for (int j = 0; j < 3; j++) {
            uint32_t b[4];
            ldsm_x4_t(b[0], b[1], b[2], b[3], (j < 2 ? bd + j * 1024 : b2) + kp * 256);
#pragma unroll
            for (int h = 0; h < 2; h++)
#pragma unroll
                for (int m = 0; m < 2; m++) {
                    const uint32_t (&A)[4] = k.A[m][2 * kp + h];
                    mma_f16(acc[m][j], A[0], A[1], A[2], A[3], b[2 * h], b[2 * h + 1]);
                }
        }
    __syncwarp();
#define PK(j) pack_f16(acc[0][j][0], acc[0][j][1]), pack_f16(acc[0][j][2], acc[0][j][3]), pack_f16(acc[1][j][0], acc[1][j][1]), pack_f16(acc[1][j][2], acc[1][j][3])
    stsm_x4(tb + lane * 16, PK(0));
    stsm_x4(tb + 512 + lane * 16, PK(1));
    stsm_x4_t(tb + 1024 + (lane & 7) * 80 + mi * 16, PK(2));
#undef PK
}
__device__ __forceinline__ uint32_t table_buf(uint32_t sb, int warp) { return sb + SM_PL + warp * TBW; }

__device__ __forceinline__ uint4 lds16x4(uint32_t a) { return make_uint4(lds16(a), lds16(a + TBW), lds16(a + 2 * TBW), lds16(a + 3 * TBW)); }
__device__ __forceinline__ void combine_setup(uint32_t sb, int warp, int lane, uint32_t kw, uint32_t& o, uint32_t& n, uint32_t& d) {
    const int wq = warp & 3;
    const uint32_t a = table_buf(sb, warp & ~3);
    o = wq == 3 ? a + 1024 + 320 + (lane >> 3) * 80 + (lane & 7) * 8 : a + (wq ? 504 + wq * 8 : 0) + lane * 16;
    n = a + 1024 + wq * 80 + lane * 2;
    d = wq < 3 ? kw + (wq == 2 ? KW_P : 32 + wq * 512) + lane * 16 : kw + KW_H + 8 + lane * 8;
}
__device__ __forceinline__ void kgen_combine(int wq, int lane, uint32_t o, uint32_t na, uint32_t d) {
#define S4(f) hadd2(hadd2(u.f, v.f), hadd2(w.f, x.f))
#define H4(v) hadd2(hadd2(v.x, v.y), hadd2(v.z, v.w))
#define BP __byte_perm
    if (wq == 0) {
        const uint4 u = lds128(o), v = lds128(o + TBW), w = lds128(o + 2 * TBW), x = lds128(o + 3 * TBW), nn = lds16x4(na);
        const uint32_t n = H4(nn), k0 = S4(x), k2 = S4(y), k4 = S4(z), k6 = S4(w);
        sts128(d, BP(k0, k0, 0x1032), BP(k0, k2, 0x3254), BP(k2, k2, 0x1032), BP(k2, k4, 0x3254));
        sts128(d + KW_PL, BP(k4, k4, 0x1032), BP(k4, k6, 0x3254), BP(k6, k6, 0x1032), BP(k6, n, 0x3254));
        if (lane == 0) sts32(d + KW_PL - 4, k0 & 0xffffu);
    } else {
        const uint2 u = lds64(o), v = lds64(o + TBW), w = lds64(o + 2 * TBW), x = lds64(o + 3 * TBW);
        uint4 nn = make_uint4(0u, 0u, 0u, 0u), mm = nn;
        if (wq < 3) nn = lds16x4(na);
        if (wq == 2) mm = lds16x4(na + 80);
        const uint32_t k0 = S4(x), k2 = S4(y), n = H4(nn), m = H4(mm);
        if (wq == 3) {
            sts64(d, k0, k2);
        } else if (wq == 1) {
            const uint32_t cc = BP(k2, k2, 0x1010);
            sts128(d, BP(k0, k0, 0x1010), BP(k0, k0, 0x1032), BP(k0, k2, 0x3254), cc);
            sts128(d + KW_PL, cc, BP(k2, k2, 0x1032), BP(k2, n, 0x3254), BP(n, n, 0x1010));
        } else {
            const uint32_t w40 = BP(k0, k0, 0x1032), w84 = BP(k0, n, 0x3254), w0 = BP(k0, k0, 0x1010), w4 = BP(k0, k0, 0x3232), w8 = BP(n, n, 0x1010);
            sts64(d, w40, w84);
            sts64(d + 512, BP(k2, k2, 0x1032), BP(k2, m, 0x3254));
            if (lane < 8) { sts128(d - (KW_P - 1056), w0, w0, w40, w4); sts128(d - (KW_P - 1056 - KW_PL), w4, w84, w8, w8); }
            if (lane == 31) sts16(d + (KW_H + 6 - KW_P - 496), m);
        }
    }
#undef S4
#undef H4
#undef BP
}

__device__ __forceinline__ int c_exponent(const uint2& r, const uint2& i, float dt) {
    const uint32_t mx = __vmaxu2(__vmaxu2(r.x & 0x7fff7fffu, r.y & 0x7fff7fffu), __vmaxu2(i.x & 0x7fff7fffu, i.y & 0x7fff7fffu));
    return __reduce_max_sync(0xffffffffu, max(mx, mx << 16) + (__float_as_uint(dt) & 0x7f800000u)) >> 23;
}

__device__ __forceinline__ int lane_v() { int l; asm volatile("mov.u32 %0, %%laneid;" : "=r"(l)); return l; }
__device__ __forceinline__ uint32_t prmt_v(uint32_t a, uint32_t b, uint32_t s) { uint32_t d; asm volatile("prmt.b32 %0, %1, %2, %3;\n" : "=r"(d) : "r"(a), "r"(b), "r"(s)); return d; }
__device__ __forceinline__ uint32_t mov_v(uint32_t a) { uint32_t d; asm volatile("mov.b32 %0, %1;\n" : "=r"(d) : "r"(a)); return d; }
template <int G>
__device__ __forceinline__ void conv_rename(float (&acc)[16][4]) {
#pragma unroll
    for (int i = G; i < 16; i++)
#pragma unroll
        for (int j = 0; j < 4; j++) { float v; asm volatile("mov.b32 %0, %1;\n" : "=f"(v) : "f"(acc[i][j])); acc[i][j] = v; }
}
struct Conv {
    uint32_t kw;
    uint32_t wa;
    uint32_t pa, s2;
    uint32_t s8;
    uint32_t id;
    uint32_t lc;
    uint32_t fs;
    uint32_t fl, yo;
    uint32_t yp;
    size_t ycopy;
    uint32_t ps;
    uint64_t d0;
    int warp;
};
struct Pk { uint32_t w[4]; };
__device__ __forceinline__ Pk pk2(const float (&u)[4], const float (&v)[4]) {
    Pk r;
    r.w[0] = pack_f16(u[0], u[1]); r.w[1] = pack_f16(u[2], u[3]); r.w[2] = pack_f16(v[0], v[1]); r.w[3] = pack_f16(v[2], v[3]);
    return r;
}
__device__ __forceinline__ void park(uint32_t a, const Pk& v) {
    asm volatile("stmatrix.sync.aligned.m8n8.x4.trans.shared.b16 [%0], {%1,%2,%3,%4};\n" ::"r"(a), "r"(v.w[0]), "r"(v.w[1]), "r"(v.w[2]), "r"(v.w[3]) : "memory");
}
__device__ __forceinline__ void conv_constants(uint32_t lc, int l) {
    const int d = (l >> 2) - 2 * (l & 3);
    const int e = d + 8, r4 = (e + 1 + ((e >> 2) & 1)) >> 2, p4 = (e + (((e - 1) >> 2) & 1)) >> 2;
    const uint32_t s2 = r4 == p4 ? 0x1010u : 0x3210u;
    sts64(lc + l * 8, KW_P + ((r4 - 5) >> 1) * 16 + ((r4 - 5) & 1) * 4, s2 | ((d < 0 ? s2 : 0x7654u) << 16));
    const int lo = (d >= 4) - (d < -3), ho = (d >= 5) - (d < -2), le = (d > 4) - (d < -4), he = (d > 5) - (d < -3);
    sts32(lc + 512 + l * 8, (0x5454u + lo * 0x22 + ho * 0x2200) | ((0x3232u + le * 0x22 + he * 0x2200) << 16));
    const int cc = l >> 2, j = l & 3;
    sts64(lc + 256 + l * 8, (j >> 1) * PL_HALF + (16 + cc) * 16 + (j & 1) * 8, (cc >> 1) * (DM * 64) + (cc & 1) * 32 + j * 8);
}
__device__ __forceinline__ void conv_selectors4(Conv& c) {
    const uint2 v = lds64(c.lc + lane_v() * 8);
    c.pa = v.x; c.s2 = v.y;
}
__device__ __forceinline__ void conv_selectors8(Conv& c) { c.s8 = lds32(c.lc + 512 + lane_v() * 8); }
template <int G, int I0, int I1>
__device__ __forceinline__ void conv_load(const Conv& c, uint32_t (&q)[9]) {
    const int wq = c.warp & 3;
    if (G < 2) {
#pragma unroll
        for (int i = I0; i < I1; i++) q[i] = lds32(c.wa + G * 512 + i * 16);
    } else if (G < 4) {
        const uint32_t a = (G == 2 && wq == 0) ? c.wa + 1024 : c.pa + c.kw + wq * 128 + (G < 2 ? 0 : G - 2) * 512;
#pragma unroll
        for (int i = I0; i < I1; i++) q[i] = lds32(a + i * 16);
    } else {
        const uint4 u = lds128(c.kw + KW_H + (G < 4 ? 0 : G - 4) * 64 + wq * 16);
        const uint2 v = lds64(c.kw + KW_H + (G < 4 ? 0 : G - 4) * 64 + wq * 16 + 16);
        q[0] = u.x; q[1] = u.y; q[2] = u.z; q[3] = u.w; q[4] = v.x; q[5] = v.y;
        if (G == 4 && wq == 0) { q[6] = lds32(c.pa + c.kw + 1024); q[7] = lds32(c.pa + c.kw + 1040); }
    }
}
template <int G, int J0, int J1>
__device__ __forceinline__ void conv_frag(const Conv& c, const uint32_t (&q)[9], uint32_t* a, const Pk& dp) {
    const uint32_t dep = dp.w[0];
    if (G < 4) {
        const uint32_t s = (G < 2 || (G == 2 && (c.warp & 3) == 0)) ? c.id : c.s2;
#pragma unroll
        for (int j = J0; j < J1; j++) {
            uint32_t* o = a + 4 * (j - J0);
            o[0] = prmt_v(q[2 * j + 1], dp.w[0], s); o[1] = prmt_v(q[2 * j + 2], dp.w[1], s); o[2] = prmt_v(q[2 * j], dp.w[2], s); o[3] = prmt_v(q[2 * j + 1], dp.w[3], s);
        }
    } else {
        const uint32_t so = prmt_v(c.s8, dep, c.id), se = prmt_v(c.s8, dep, c.id + 0x22);
#pragma unroll
        for (int j = J0; j < J1; j++) {
            uint32_t* o = a + 4 * (j - J0);
            o[0] = prmt_v(q[j + 1], q[j + 2], se); o[1] = prmt_v(q[j + 1], q[j + 2], so); o[2] = prmt_v(q[j], q[j + 1], so);
            if (G == 4 && j == 0 && (c.warp & 3) == 0) {
                o[2] = prmt_v(q[6], dep, c.s2);
                o[0] = prmt_v(q[7], o[0], c.s2 >> 16);
            }
            o[3] = mov_v(o[0]);
        }
    }
}
template <int G, int J0, int J1>
__device__ __forceinline__ void conv_frag(const Conv& c, const uint32_t (&q)[9], uint32_t* a, float depf) {
    const uint32_t d = __float_as_uint(depf);
    conv_frag<G, J0, J1>(c, q, a, Pk{{d, d, d, d}});
}
template <int G, int T, int J0, int J1>
__device__ __forceinline__ void conv_mma(float (&acc)[16][4], const Conv& c, const uint32_t* a) {
#pragma unroll
    for (int j = J0; j < J1; j++) wg_mma<T>(acc, a + 4 * (j - J0), c.d0 - 8 * (2 * G - T) - j);
}
__device__ __forceinline__ float h_lo(uint32_t w) { return __half2float(__ushort_as_half((unsigned short)(w & 0xffffu))); }
__device__ __forceinline__ float h_hi(uint32_t w) { return __half2float(__ushort_as_half((unsigned short)(w >> 16))); }
__device__ __forceinline__ void flush_setup(Conv& c) {
    const uint2 v = lds64(c.lc + 256 + lane_v() * 8);
    c.fl = v.x; c.yo = v.y;
}
template <int Q>
__device__ __forceinline__ void flush_load(const Conv& c, uint32_t pl, uint2 (&f)[4]) {
#pragma unroll
    for (int w = 0; w < 4; w++) f[w] = lds64(c.fl + pl + (Q & 1) * 512 + w * (PLW_B - 64));
}
template <int Q>
__device__ __forceinline__ void flush_load_first(const Conv& c, uint32_t pl, uint2 (&f)[4], float depf) {
    const uint32_t p = prmt_v(c.fl, __float_as_uint(depf), c.id) + pl + (Q & 1) * 512;
#define LDV64(d, a) asm volatile("ld.volatile.shared.v2.u32 {%0,%1}, [%2];\n" : "=r"(d.x), "=r"(d.y) : "r"(a) : "memory")
    LDV64(f[0], p); LDV64(f[1], p + (PLW_B - 64)); LDV64(f[2], p + 2 * (PLW_B - 64)); LDV64(f[3], p + 3 * (PLW_B - 64));
}
#define FDEP __uint_as_float(f[3].y)
template <int Q, int mode>
__device__ __forceinline__ void conv_flush(const Conv& c, const uint2 (&f)[4], unsigned char* gy, uint32_t rx) {
    const uint32_t a0 = hadd2(f[0].x, f[1].x), a1 = hadd2(f[2].x, f[3].x), b0 = hadd2(f[0].y, f[1].y), b1 = hadd2(f[2].y, f[3].y);
    if (Q > 0 && mode == 1) {
        const uint32_t ra = rx + 16 + (Q > 0 ? Q - 1 : 0) * 1024 + (c.warp & 3) * 256 + lane_v() * 8;
        asm volatile("st.async.shared::cluster.mbarrier::complete_tx::bytes.v2.b32 [%0], {%1,%2}, [%3];\n"
                     ::"r"(ra ^ 0x1000000u), "r"(hadd2(a0, a1)), "r"(hadd2(b0, b1)), "r"((rx + (Q > 1 ? 8 : 0)) ^ 0x1000000u) : "memory");
        return;
    }
    float v0 = h_lo(a0) + h_lo(a1), v1 = h_hi(a0) + h_hi(a1), v2 = h_lo(b0) + h_lo(b1), v3 = h_hi(b0) + h_hi(b1);
    if (Q > 0 && mode == 2) {
        const uint2 o = lds64(rx + 16 + (Q > 0 ? Q - 1 : 0) * 1024 + (c.warp & 3) * 256 + lane_v() * 8);
        v0 += h_lo(o.x); v1 += h_hi(o.x); v2 += h_lo(o.y); v3 += h_hi(o.y);
    }
    const uint32_t lo = hmul2_bf(pack_bf16(v0, v1), c.fs), hi = hmul2_bf(pack_bf16(v2, v3), c.fs);
    stg64(gy + Q * 32 * DM * 32 + (c.yo + (Q < 2 ? c.yp : 0u)), nzw(lo), nzw(hi));
}
template <int I, bool S = false> struct IC { static constexpr int value = I; static constexpr bool shared = S; };
template <class T> __device__ constexpr bool wg_is4() { return T::shared; }
#define SLOT(n) (c.ps + (2 + ((n) & 7)) * 128)
#define GO() do { wg_commit(); __syncwarp(); } while (0)
#define DEP acc[15][3]
template <class FG, class FP, class FN>
__device__ __forceinline__ void conv_head(Conv& c, float (&acc)[16][4], uint32_t (&q)[9], uint32_t (&r)[9], uint32_t* a, FG fg, FP pre, FN next) {
    c.id = 0x3210u + (c.warp >> 8);
    pre();
    conv_load<0, 0, 9>(c, q);
    conv_frag<0, 0, 1>(c, q, a, 0.f);
    wg_fence(); wg_first<0>(acc, a, c.d0); GO();
    park(c.ps, Pk{{0u, 0u, 0u, 0u}});
    wg_wait0();
    conv_frag<0, 1, 2>(c, q, a, DEP);
    wg_fence(); conv_mma<0, 0, 1, 2>(acc, c, a); GO();
    fg(IC<0>());
    wg_wait0();
    conv_frag<0, 2, 3>(c, q, a, DEP);
    wg_fence(); conv_mma<0, 0, 2, 3>(acc, c, a); GO();
    conv_load<1, 0, 5>(c, r);
    wg_wait0();
    conv_frag<0, 3, 4>(c, q, a, DEP);
    wg_fence(); conv_mma<0, 0, 3, 4>(acc, c, a); GO();
    conv_load<1, 5, 9>(c, r);
    fg(IC<1>());
    wg_wait0();
    const Pk k = pk2(acc[0], acc[1]);
    conv_rename<2>(acc);
    conv_frag<1, 0, 2>(c, r, a, k);
    wg_fence(); conv_mma<1, 2, 0, 2>(acc, c, a); GO();
    park(SLOT(0), k);
    next(IC<0>());
    fg(IC<2>());
    wg_wait0();
    conv_frag<1, 2, 4>(c, r, a, DEP);
    wg_fence(); conv_mma<1, 2, 2, 4>(acc, c, a); GO();
    next(IC<1>());
    fg(IC<3>());
    wg_wait0();
}
template <class FG, class FP>
__device__ __forceinline__ void conv_run(Conv& c, uint32_t pl, unsigned char* gy, FG fg, FP pre) {
    float acc[16][4];
    uint32_t q[9], r[9], a[32];
    uint2 f[4];
    const int bid = 1 + (c.warp >> 2);
    conv_head(c, acc, q, r, a, fg, pre, [&](auto i) { if (decltype(i)::value == 0) conv_selectors4(c); else conv_load<2, 0, 9>(c, q); });
    Pk k = pk2(acc[2], acc[3]);
    conv_rename<4>(acc);
    conv_frag<2, 0, 4>(c, q, a, k);
    wg_fence(); conv_mma<2, 4, 0, 4>(acc, c, a); GO();
    park(SLOT(2), k);
    conv_load<3, 0, 9>(c, q);
    flush_setup(c);
    bar_sync(bid, 128);
    fg(IC<4>());
    wg_wait0();
    conv_rename<6>(acc);
    conv_frag<3, 0, 4>(c, q, a, DEP);
    wg_fence(); conv_mma<3, 6, 0, 4>(acc, c, a); GO();
    park(SLOT(4), pk2(acc[4], acc[5]));
    conv_load<4, 0, 9>(c, q);
    conv_selectors8(c);
    flush_load<0>(c, pl, f);
    conv_flush<0, 0>(c, f, gy, 0u);
    fg(IC<5>());
    wg_wait0();
    conv_rename<8>(acc);
    conv_frag<4, 0, 4>(c, q, a, DEP);
    wg_fence(); conv_mma<4, 8, 0, 4>(acc, c, a); GO();
    k = pk2(acc[6], acc[7]);
    park(SLOT(6), k);
    conv_load<5, 0, 9>(c, q);
    bar_sync(bid, 128);
    park(c.ps, k);
    fg(IC<6>());
    wg_wait0();
    conv_rename<10>(acc);
    flush_load_first<1>(c, pl, f, DEP);
    conv_frag<5, 0, 4>(c, q, a, FDEP);
    wg_fence(); conv_mma<5, 10, 0, 4>(acc, c, a); GO();
    park(SLOT(8), pk2(acc[8], acc[9]));
    conv_load<6, 0, 9>(c, q); conv_load<7, 0, 9>(c, r);
    conv_flush<1, 0>(c, f, gy, 0u);
    fg(IC<7>());
    wg_wait0();
    conv_rename<12>(acc);
    conv_frag<6, 0, 4>(c, q, a, DEP); conv_frag<7, 0, 4>(c, r, a + 16, DEP);
    wg_fence(); conv_mma<6, 12, 0, 4>(acc, c, a); conv_mma<7, 12, 0, 4>(acc, c, a + 16); GO();
    park(SLOT(10), pk2(acc[10], acc[11]));
    bar_sync(bid, 128);
    flush_load<2>(c, pl, f);
    conv_flush<2, 0>(c, f, gy, 0u);
    fg(IC<8>());
    if (c.id == 0) TRAP();
    wg_wait0();
    park(SLOT(12), pk2(acc[12], acc[13])); park(SLOT(14), pk2(acc[14], acc[15]));
    bar_sync(bid, 128);
    flush_load<3>(c, pl, f);
    conv_flush<3, 0>(c, f, gy, 0u);
}
template <class FG>
__device__ __forceinline__ void conv_outer(Conv& c, uint32_t pl, unsigned char* gy, uint32_t rx, FG fg) {
    float acc[16][4];
    uint32_t q[9], r[9], a[32];
    uint2 f[4], f2[4];
    const int bid = 1 + (c.warp >> 2);
    conv_head(c, acc, q, r, a, [&](auto gi) { if (decltype(gi)::value == 2) fg(IC<2, true>()); }, [&]() {}, [&](auto i) { if (decltype(i)::value == 0) conv_selectors8(c); else conv_load<6, 0, 9>(c, q); });
    park(SLOT(2), pk2(acc[2], acc[3])); park(SLOT(4), pk2(acc[4], acc[5]));
    const Pk k = pk2(acc[6], acc[7]);
    park(SLOT(6), k);
    conv_load<7, 0, 9>(c, r);
    conv_rename<12>(acc);
    conv_frag<6, 0, 4>(c, q, a, __uint_as_float(k.w[3])); conv_frag<7, 0, 4>(c, r, a + 16, __uint_as_float(k.w[3]));
    wg_fence(); conv_mma<6, 12, 0, 4>(acc, c, a); conv_mma<7, 12, 0, 4>(acc, c, a + 16); GO();
    flush_setup(c);
    bar_sync(bid, 128);
    flush_load<0>(c, pl, f); flush_load<1>(c, pl, f2);
    conv_flush<1, 1>(c, f2, gy, rx);
    conv_flush<0, 1>(c, f, gy, rx);
    wg_wait0();
    bar_sync(bid, 128);
    park(c.ps, k); park(SLOT(8), pk2(acc[8], acc[9])); park(SLOT(10), pk2(acc[10], acc[11]));
    park(SLOT(12), pk2(acc[12], acc[13])); park(SLOT(14), pk2(acc[14], acc[15]));
    bar_sync(bid, 128);
    flush_load<2>(c, pl, f); flush_load<3>(c, pl, f2);
    conv_flush<2, 1>(c, f, gy, rx);
    conv_flush<3, 1>(c, f2, gy, rx);
}
template <class FG>
__device__ __forceinline__ void conv_inner(Conv& c, uint32_t pl, unsigned char* gy, uint32_t rx, FG fg) {
    float acc[16][4];
    uint32_t q[9], a[16];
    uint2 f[4], f2[4];
    const int bid = 1 + (c.warp >> 2);
    c.id = 0x3210u + (c.warp >> 8);
    conv_selectors4(c);
    conv_load<2, 0, 9>(c, q);
    conv_frag<2, 0, 4>(c, q, a, 0.f);
    wg_fence(); wg_first<4>(acc, a, c.d0); conv_mma<2, 4, 1, 4>(acc, c, a + 4); GO();
    conv_load<3, 0, 9>(c, q);
    park(SLOT(2), Pk{{0u, 0u, 0u, 0u}});
    fg(IC<2, true>());
    wg_wait0();
    conv_rename<6>(acc);
    conv_frag<3, 0, 4>(c, q, a, DEP);
    wg_fence(); conv_mma<3, 6, 0, 4>(acc, c, a); GO();
    park(SLOT(4), pk2(acc[4], acc[5]));
    conv_load<4, 0, 9>(c, q);
    conv_selectors8(c);
    wg_wait0();
    conv_rename<8>(acc);
    conv_frag<4, 0, 4>(c, q, a, DEP);
    wg_fence(); conv_mma<4, 8, 0, 4>(acc, c, a); GO();
    const Pk k = pk2(acc[6], acc[7]);
    park(SLOT(6), k); park(c.ps, k);
    conv_load<5, 0, 9>(c, q);
    flush_setup(c);
    wg_wait0();
    conv_rename<10>(acc);
    conv_frag<5, 0, 4>(c, q, a, DEP);
    wg_fence(); conv_mma<5, 10, 0, 4>(acc, c, a); GO();
    park(SLOT(8), pk2(acc[8], acc[9]));
    bar_sync(bid, 128);
    flush_load<1>(c, pl, f);
    mbar_wait(rx);
    conv_flush<1, 2>(c, f, gy, rx);
    wg_wait0();
    bar_sync(bid, 128);
    park(SLOT(10), pk2(acc[10], acc[11])); park(SLOT(12), pk2(acc[12], acc[13])); park(SLOT(14), pk2(acc[14], acc[15]));
    bar_sync(bid, 128);
    flush_load<3>(c, pl, f); flush_load<2>(c, pl, f2);
    mbar_wait(rx + 8);
    conv_flush<3, 2>(c, f, gy, rx);
    conv_flush<2, 2>(c, f2, gy, rx);
}
#undef SLOT
#undef GO
#undef DEP
template <int U0, int U1>
__device__ __forceinline__ void weight_units(uint32_t sb, const Maps& tm, bool w) {
    if (U1 > U0 && w && elect_one()) {
#pragma unroll
        for (int i = U0; i < U1; i++) {
            const int P = blockIdx.x >> 1, odd = blockIdx.x & 1;
            if (i < 12) tma_2d(sb + SM_WG + i * 6144, &tm.w[i / 6], 64 * P, 288 * odd + (i % 6) * 48, sb + SM_MISC + 328);
            else tma_2d(sb + SM_WD + (i - 12) * 4736, &tm.d, 144 * odd, i < 20 ? 64 * P + 8 * (i - 12) : 4096 + 8 * P, sb + SM_MISC + 336);
            if (i >= 8 && i < 12) tma_2d(sb + SM_WR + (i - 8) * 2304, &tm.r[(i - 8) >> 1], 4096 + 8 * P, 288 * odd + (i & 1) * 144, sb + SM_MISC + 328);
        }
    }
}
#define WS 2210121111113004000
__device__ constexpr int wsched(int i) {
    unsigned long long v = WS;
    int n = 0;
    for (int k = 19; k >= 1; k--) { if (k < i) n += (int)(v % 10); v /= 10; }
    return n;
}
static_assert(wsched(20) == 21 && wsched(6) <= 8 && wsched(11) <= 12 && wsched(13) <= 14 && wsched(16) <= 17 && wsched(16) == wsched(15) && wsched(19) == 21, "");
#define WANY(i) (wsched((i) + 1) > wsched(i))
#define WPOINT(i, w) do { weight_units<wsched(i), wsched(i + 1)>(sb, tm, w); } while (0)

__global__ void __launch_bounds__(NTHR, 1) __cluster_dims__(2, 1, 1)
fused_kernel(const Params p, const __grid_constant__ Maps tm) {
    extern __shared__ __align__(1024) unsigned char smem[];
    const uint32_t sb = smem_u32(smem);
    const int tid = threadIdx.x, warp = __shfl_sync(0xffffffffu, tid >> 5, 0), lane = tid & 31;
    const int b = blockIdx.x, P = b >> 1, odd = b & 1;
    const int g = lane >> 2, t = lane & 3;
    const int wg = warp >> 2, t128 = tid & 127;
    const uint32_t s_stat = sb + SM_MISC;
    const uint32_t s_key = sb + SM_MISC + 128;
    const uint32_t s_rank = sb + SM_MISC + 256;
    const uint32_t s_k16 = sb + SM_MISC + 192;
    const uint32_t s_cnt = sb + SM_MISC + 320;
    const uint32_t bar_w = sb + SM_MISC + 328, bar_d = bar_w + 8, bar_g = bar_w + 16, bar_x = bar_w + 24, bar_v = bar_w + 32, bar_s = bar_w + 40, bar_h = bar_w + 48;
    STAMP(0);

    const int ch = wg < 4 ? 4 * b + wg : 512 + P;
    const uint32_t mo = tid < 512 ? 512 * b + tid : 65536 + 128 * P + t128, mq = (mo & ~127u) + 4 * lane;
    const uint32_t pl = ldo16(p.lar + mo), pa2 = ldo16(p.aim + mo), ldt = ldo16(p.ldt + (mo >> 7));
    const uint32_t pc = ldo16(p.cre + mo), pi = ldo16(p.cim + mo);
    const uint2 call_re = ldo64(p.cre + mq), call_im = ldo64(p.cim + mq);
    const uint32_t epl = ld_poll32(p.s->hint + (b & 7) * 32 + 1);
    const uint32_t kw = sb + SM_KW + wg * KW_B;
    uint32_t co, cn, cd, uo;
    auto housekeeping = [&]() {
        if (t128 < 2 * UPAD) sts128(sb + SM_U + wg * USLOT_B + (t128 & 1) * ULO_B + (t128 >> 1) * 16, 0u, 0u, 0u, 0u);
        if (t128 >= 124) sts128(kw + (t128 & 1) * 16 + (t128 & 2) * (KW_PL / 2), 0u, 0u, 0u, 0u);
        if (warp < 15) sts128(sb + SM_Z2 + 4608 + tid * 16, 0u, 0u, 0u, 0u);
        combine_setup(sb, warp, lane, kw, co, cn, cd);
        co = pin(co); cn = pin(cn); cd = pin(cd);
        uo = pin(wg < 4 ? tid : 512 + (P >> 2) * 1024 + (t128 >> 1) * 8 + (P & 3) * 2 + (t128 & 1));
    };
    if (wg < 4) {
        bar_arrive(0, NWRK);
        asm volatile("barrier.cluster.arrive.relaxed.aligned;\n" ::: "memory");
        housekeeping();
    } else {
        const int o = (4 * (warp & 3) + (g >> 1)) * 1152 + (g & 1) * 576 + t * 16;
        sts128(sb + SM_Z2 + t128 * 16, 0u, 0u, 0u, 0u); sts128(sb + SM_Z2 + 2048 + t128 * 16, 0u, 0u, 0u, 0u);
        if (warp == 16) sts128(sb + SM_Z2 + 4096 + lane * 16, 0u, 0u, 0u, 0u);
        fence_async();
        bar_sync(0, NWRK);
        STAMP(9);
#pragma unroll
        for (int c = 0; c < 9; c++)
            asm volatile("cp.async.cg.shared.global [%0], [%1], 16;\n" ::"r"(sb + SM_XT + o + c * 64), "l"(reinterpret_cast<const char*>(p.x) + b * 18432 + o + c * 64) : "memory");
        asm volatile("cp.async.commit_group;\n" ::: "memory");
        if (elect_one()) {
            mbar_init(bar_h + 8 * (warp & 3), 1);
            if (warp == 19) {
                mbar_init(bar_x, 1); mbar_init(bar_w, 1);
                mbar_expect(bar_x, 32768); mbar_expect(bar_w, 82944);
#pragma unroll
                for (int i = 2; i < 4; i++) bulk_s2g(reinterpret_cast<unsigned char*>(p.s->y) + 32 * i * 18432 + b * 4608, sb + SM_Z2, 4608);
            } else if (warp == 18) {
                mbar_init(bar_s, 1); mbar_init(bar_v, 2); mbar_init(bar_d, 1); mbar_init(bar_g, 1); mbar_init(sb + SM_RX, 1); mbar_init(sb + SM_RX + 8, 1);
                mbar_expect(bar_v, 2 * 1152); mbar_expect(bar_d, 72 * WD_PITCH); mbar_expect(bar_g, 4608); mbar_expect(sb + SM_RX, 1024); mbar_expect(sb + SM_RX + 8, 2048);
            }
            asm volatile("fence.mbarrier_init.release.cluster;\n" ::: "memory");
        }
        __syncwarp();
        asm volatile("barrier.cluster.arrive.relaxed.aligned;\n" ::: "memory");
        if (warp == 19) {
            asm volatile("barrier.cluster.wait.aligned;\n" ::: "memory");
            if (elect_one()) tma_4d_mc(sb + SM_XC + odd * 16384, &tm.x, 8 * P, 2 * odd, bar_x);
            __syncwarp();
        }
        {
            if (!(g & 1) && t == (g >> 1)) *reinterpret_cast<volatile uint32_t*>(p.s->stat + 16 * b + 4 * (warp & 3) + t) = 0u;
            if (warp < 18) {
                unsigned char* const ud = reinterpret_cast<unsigned char*>(p.s->uT) + (size_t)(8 * (warp & 1) + 2 * (g >> 1)) * 16384 + b * 128 + (g & 1) * 32 + t * 8;
#pragma unroll
                for (int k = 0; k < 4; k++) *reinterpret_cast<volatile unsigned long long*>(ud + (k >> 1) * 16384 + (k & 1) * 64) = 0ull;
            }
        }
    }
    const uint32_t tb = table_buf(sb, warp), t5 = sb + SM_WD + warp * 512;
    STAMP(29);
    const float dt = exp_bf(bf_lo(ldt));
    const uint32_t ep = __reduce_or_sync(0xffffffffu, epl);
    auto stats = [&]() {
        const int wq = warp & 3;
        const uint32_t xa = sb + SM_XT + (4 * wq + (g >> 1)) * 1152 + (g & 1) * 576 + t * 16;
        const bool own = !(g & 1) && t == (g >> 1);
        float d[4][4] = {};
        asm volatile("cp.async.wait_group 0;\n" ::: "memory");
        STAMP(26);
        uint4 v[9];
#pragma unroll
        for (int c = 0; c < 9; c++) v[c] = lds128(xa + c * 64);
#pragma unroll
        for (int c = 0; c < 9; c++) {
            mma_bf16(d[2 * (c & 1)], v[c].x, 0x3f803f80u, v[c].y, 0x3f803f80u, v[c].x, v[c].y);
            mma_bf16(d[2 * (c & 1) + 1], v[c].z, 0x3f803f80u, v[c].w, 0x3f803f80u, v[c].z, v[c].w);
        }
        STAMP(27);
        float sm = (g & 1) ? (d[0][3] + d[1][3]) + (d[2][3] + d[3][3]) : (d[0][2] + d[1][2]) + (d[2][2] + d[3][2]);
        float sq = (g & 1) ? (d[0][1] + d[1][1]) + (d[2][1] + d[3][1]) : (d[0][0] + d[1][0]) + (d[2][0] + d[3][0]);
        sm += __shfl_xor_sync(0xffffffffu, sm, 4); sq += __shfl_xor_sync(0xffffffffu, sq, 4);
        if (lane == 0) mbar_arrive(bar_h + 8 * wq);
        float mb, sd;
        ln_stats(sm, sq, mb, sd);
        if (own) p.s->stat[16 * b + 4 * wq + t] = (__float_as_uint(mb) >> 16) | (__float_as_uint(sd) & 0x7fff0000u) | (ep << 31);
        STAMPX(22);
        if (own) stat_store(s_stat + (2 * wq + (t & 1) + 8 * (t >> 1)) * 8, mb, rcp_approx(sd), 0u);
        if (wq == 3) asm volatile("cp.async.bulk.wait_group 0;\n" ::: "memory");
        bar_sync(5, 128);
        STAMP(28);
        uint32_t now;
        asm volatile("mov.u32 %0, %%clock;" : "=r"(now) :: "memory");
        if (wq == 2) {
            conv_constants(sb + SM_LC, lane);
            __syncwarp();
            if (lane < 8) p.s->key3[8 * b + lane] = ep & 1u;
            if (lane == 0) {
                sts64(s_cnt, now, ep);
                mbar_arrive(bar_s);
                bulk_g2s(sb + SM_XT + 16 * 1152, p.dsk, 1152, bar_v);
                bulk_g2s(sb + SM_XT + 17 * 1152, p.wr, 1152, bar_v);
            }
            __syncwarp();
        }
        WPOINT(1, wq == 3);
        if (wq < 2) {
            unsigned char* const ud = reinterpret_cast<unsigned char*>(p.s->uT) + (size_t)(8 * wq + 2 * (g >> 1)) * 16384 + b * 128 + (g & 1) * 32 + t * 8;
            const uint32_t utag = (ep % 7u + 1u) * 0x10001u;
            uint32_t U[2][4];
#pragma unroll
            for (int hf = 0; hf < 2; hf++) {
                const uint2 st = lds64(s_stat + (g + 8 * hf) * 8);
                const uint4 xu = lds128(sb + SM_XT + (TOK(g) + 2 * hf) * 1152 + warp * 64 + t * 16);
                const uint32_t X[4] = {xu.x, xu.y, xu.z, xu.w};
#pragma unroll
                for (int k = 0; k < 4; k++) {
                    const uint32_t u = ln_apply(X[k], STAT_M(st), STAT_H(st), STAT_L(st));
                    U[hf][k] = movm((pack_f16(bf_lo(u), bf_hi(u)) & 0xfff8fff8u) | utag);
                }
            }
#pragma unroll
            for (int k = 0; k < 4; k++) stg64(ud + (k >> 1) * 16384 + (k & 1) * 64, U[0][k], U[1][k]);
        }
    };
    STAMP(1);
    if (wg < 4) { STAMPX(16); }
    KGen kg;
    kgen_setup(kg, bf_lo(pl), bf_lo(pa2), dt);
    kgen_rows(kg, tb, lane);
    STAMP(2);
    const int E = min(max(c_exponent(call_re, call_im, dt) - 243, -120), 120);
    kgen_chain(kg, pc, pi, dt * __uint_as_float((uint32_t)(128 - E) << 23));
    STAMP(3);
    kgen_cols(kg, tb, t5, lane);
    STAMP(4);
    if (wg == 4) stats();
    if (warp != 19) asm volatile("barrier.cluster.wait.aligned;\n" ::: "memory");
    if (wg < 4) { STAMPX(17); }
    if (wg == 4) housekeeping();
    const uint4* const usrc = reinterpret_cast<const uint4*>(p.s->stat) + uo;
    if (wg < 4) mbar_wait(bar_h + 8 * (warp & 3));
    if (wg < 4) { STAMPX(19); }
    uint32_t trel;
    asm volatile("mov.u32 %0, %%clock;" : "=r"(trel) :: "memory");
    kgen_mma(kg, tb, t5, lane);
    if (wg < 4) { STAMPX(20); }
    STAMP(5);
    uint4 uv0, uv1;
    auto first_poll = [&](uint32_t dly) {
        mbar_wait(bar_s);
        const uint32_t t0 = lds32(s_cnt);
        uint32_t now;
        do { asm volatile("mov.u32 %0, %%clock;" : "=r"(now) :: "memory"); } while (now - t0 < dly);
        uv0 = ld_poll(usrc);
    };
    if (wg == 4) { first_poll(UDLY); uv1 = ld_poll(usrc + 512); }
    WPOINT(2, warp == 19);
    auto stat_poll = [&]() {
        uint32_t now;
        do { asm volatile("mov.u32 %0, %%clock;" : "=r"(now) :: "memory"); } while (now - trel < SDLY);
        uv0 = ld_poll(usrc);
    };
    bar_sync(1 + wg, 128);
    if (wg < 4) { STAMPX(21); }
    kgen_combine(warp & 3, lane, co, cn, cd);
    STAMP(6);
    if (wg < 4) { STAMPX(18); }
    WPOINT(3, warp == 19);
    if (wg < 4) stat_poll();
    {
        const int wq = warp & 3;
        Conv c;
        const uint32_t pln = sb + SM_PL + wg * PL_B;
        const int e = g - 2 * t + 7;
        c.kw = kw; c.wa = pin(kw + ((e >> 2) & 1) * KW_PL + (8 * wq + (e >> 3)) * 16 + (e & 3) * 4);
        c.ps = mov_v(pln + wq * PLW_B + ((lane >> 3) & 1) * PL_HALF + ((lane >> 4) * 8 + (lane & 7)) * 16); c.warp = warp;
        c.lc = sb + SM_LC; c.fs = (uint32_t)(127 + E) * 0x800080u; c.yp = (ep & 1u) * (NCTA * 18432u);
        c.d0 = ((uint64_t)(ULO_B >> 4) << 16) | ((uint64_t)(128 >> 4) << 32) | (uint64_t)(((sb + SM_U + wg * USLOT_B + UPAD * 16) & 0x3FFFF) >> 4);
        unsigned char* gy = reinterpret_cast<unsigned char*>(p.s->y) + ((size_t)(4 * wq) * DM + ch) * 64;
        auto hook = [&](auto gi) {
                     constexpr int G = decltype(gi)::value;
                     if (G == (wg_is4<decltype(gi)>() ? 2 : 5)) asm volatile("barrier.cluster.wait.aligned;\n" ::: "memory");
                     if (!wg_is4<decltype(gi)>() && G == 1) mbar_wait(bar_s);
                     if (!wg_is4<decltype(gi)>() && (G == 0 || G == 2) && warp == HW && elect_one()) {
                         unsigned char* const sc = reinterpret_cast<unsigned char*>(p.s);
                         if (G == 0) {
                             if (b < 96) bulk_s2g_nc(sc + offsetof(Scratch, part) + b * 6144, sb + SM_Z2, 6144);
                             bulk_s2g(sc + offsetof(Scratch, rows) + (127 - b) * 4608, sb + SM_Z2, 4608);
                         }
                         if (G == 2) {
                             bulk_s2g(sc + offsetof(Scratch, y) + (NCTA * 18432u - c.yp) + b * 9216, sb + SM_Z2, 9216);
                         }
                     }
                     if (!wg_is4<decltype(gi)>()) WPOINT(6 + G, warp == (G >= 7 ? HW : 4 * (G % 3) + 1));
                     if (!wg_is4<decltype(gi)>() && G == 6 && warp == HW) {
                         asm volatile("cp.async.bulk.wait_group 0;\n" ::: "memory");
                         __syncwarp();
                         if (elect_one()) mbar_arrive(bar_v);
                     }
                 };
        if (wg < 4) {
            asm volatile("barrier.cluster.arrive.relaxed.aligned;\n" ::: "memory");
            conv_run(c, pln + wq * 128, gy, hook, [&]() {
                STAMPX(23);
                mbar_wait(bar_x);
                STAMPX(24);
                uint2 xc[4];
                uint32_t xw[4][2];
#pragma unroll
                for (int j = 0; j < 4; j++) xc[j] = lds64(sb + SM_XC + wg * 8192 + j * 2048 + t128 * 16 + odd * 8);
#pragma unroll
                for (int i = 0; i < 8; i++) {
                    const int k = i >> 1, h = i & 1;
                    xw[k][h] = prmt_v(k < 2 ? xc[2 * h].x : xc[2 * h].y, k < 2 ? xc[2 * h + 1].x : xc[2 * h + 1].y, (k & 1) ? 0x7632 : 0x5410);
                }
                const uint32_t ub = mov_v(sb + SM_U + UPAD * 16 + ((tid >> 1) & 1) * ULO_B + (tid >> 2) * 16 + (tid & 1) * 8), tag = ep << 31;
                int it = 0;
                while (min(min((int)(uv0.x ^ tag), (int)(uv0.y ^ tag)), min((int)(uv0.z ^ tag), (int)(uv0.w ^ tag))) < 0x10000) {
                    if (++it > SPIN_LIMIT) TRAP();
                    uv0 = ld_poll(usrc);
                }
                STAMP(8);
                STAMPX(26);
                const float r0 = rcp_approx(fabsf(bf_hi(uv0.x))), r1 = rcp_approx(fabsf(bf_hi(uv0.y))), r2 = rcp_approx(fabsf(bf_hi(uv0.z))), r3 = rcp_approx(fabsf(bf_hi(uv0.w)));
                const uint32_t m[2] = {__byte_perm(uv0.x, uv0.y, 0x5410), __byte_perm(uv0.z, uv0.w, 0x5410)};
                const uint32_t rh[2] = {pack_bf16(r0, r1), pack_bf16(r2, r3)};
                const uint32_t rl[2] = {pack_bf16(r0 - bf_lo(rh[0]), r1 - bf_hi(rh[0])), pack_bf16(r2 - bf_lo(rh[1]), r3 - bf_hi(rh[1]))};
#pragma unroll
                for (int k = 0; k < 4; k++) {
                    const uint32_t u0 = ln_apply(xw[k][0], m[0], rh[0], rl[0]), u1 = ln_apply(xw[k][1], m[1], rh[1], rl[1]);
                    sts64(ub + k * USLOT_B, pack_f16(bf_lo(u0), bf_hi(u0)), pack_f16(bf_lo(u1), bf_hi(u1)));
                }
                STAMPX(29);
                fence_async();
                bar_sync(14, 512);
                STAMP(7);
            });
        } else {
            auto stage = [&]() {
                const uint32_t tag = (ep % 7u + 1u) * 0x10001u;
                int it = 0;
                WPOINT(4, warp == 19);
                while (true) {
                    uv0.x ^= tag; uv0.y ^= tag; uv0.z ^= tag; uv0.w ^= tag; uv1.x ^= tag; uv1.y ^= tag; uv1.z ^= tag; uv1.w ^= tag;
                    if ((((uv0.x | uv0.y | uv0.z) | (uv0.w | uv1.x | uv1.y) | (uv1.z | uv1.w)) & 0x70007u) == 0) break;
                    if (++it > SPIN_LIMIT) TRAP();
                    uv0 = ld_poll(usrc); uv1 = ld_poll(usrc + 512);
                }
                STAMP(8);
                const uint32_t ub = sb + SM_U + UPAD * 16 + 4 * USLOT_B + (t128 & 1) * ULO_B + (t128 >> 1) * 16;
                sts128(ub, uv0.x, uv0.y, uv0.z, uv0.w);
                sts128(ub + 1024, uv1.x, uv1.y, uv1.z, uv1.w);
                fence_async();
                asm volatile("barrier.cluster.arrive.relaxed.aligned;\n" ::: "memory");
                bar_sync(5, 128);
                WPOINT(5, warp == 19);
                STAMP(7);
            };
            stage();
            if (odd) conv_inner(c, pln + wq * 128, gy, sb + SM_RX, hook);
            else conv_outer(c, pln + wq * 128, gy, sb + SM_RX, hook);
        }
        STAMP(10);
    }
    {
    const int lane = lane_v(), tid = 32 * warp + lane, g = lane >> 2, t = lane & 3;
    const uint32_t par = ~ep & 1u;
    bar_sync(0, NWRK);
    STAMP(11);
    uint32_t H[2][4] = {}, U2[2][4] = {};
    auto publish = [&](bool hi, int slot) {
        uint4* rowp = reinterpret_cast<uint4*>(p.s->rows) + slot * 144 + warp * 4 + t;
        stg128(rowp, nzw(hi ? U2[1][0] : U2[0][0]), nzw(hi ? U2[1][1] : U2[0][1]), nzw(hi ? U2[1][2] : U2[0][2]), nzw(hi ? U2[1][3] : U2[0][3]));
        stg128(rowp + 72, nzw(hi ? H[1][0] : H[0][0]), nzw(hi ? H[1][1] : H[0][1]), nzw(hi ? H[1][2] : H[0][2]), nzw(hi ? H[1][3] : H[0][3]));
    };
#define KTOK(k) (int)(((~(k) >> 5) & 0x7f0u) | (((k) >> 1) & 15u))
#define KLATE(k) (((k) & 0x1e0u) < 0xe0u)
#define KSLOT(k, s) (KLATE(k) ? 2 * NCTA + (s) : (int)(((k) >> 8) & 0xffu))
    const uint4* const rsrc = reinterpret_cast<const uint4*>(p.s->rows) + 36 * odd;
    auto gather = [&](uint32_t mine) {
        int it = 0;
        uint32_t mn;
        do {
            mn = 1;
#pragma unroll 1
            for (int r = 0; r < 9; r++) {
                const uint32_t k = __shfl_sync(0xffffffffu, mine, r < 8 ? 4 * r : lane);
                const int row = r < 8 ? r : g, c = r < 8 ? lane : 32 + t;
                asm volatile("cp.async.cg.shared.global [%0], [%1], 16;\n" ::"r"(sb + SM_XS + row * XS_PITCH + c * 16), "l"(rsrc + KSLOT(k, row) * 144 + c) : "memory");
            }
            asm volatile("cp.async.wait_all;\n" ::: "memory");
#pragma unroll 1
            for (int r = 0; r < 9; r++) mn = min(mn, min4(lds128(sb + SM_XS + (r < 8 ? r * XS_PITCH + lane * 16 : g * XS_PITCH + (32 + t) * 16))));
            if (++it > SPIN_LIMIT) TRAP();
        } while (__any_sync(0xffffffffu, mn == 0));
    };
    auto late_rows = [&](auto role) {
        if (decltype(role)::value == 1) {
            int it = 0;
            uint4 k[8];
            uint32_t bad;
            do {
                bad = 0;
#pragma unroll
                for (int i = 0; i < 8; i++) k[i] = ld_poll(reinterpret_cast<const uint4*>(p.s->key) + 32 * i + lane);
#pragma unroll
                for (int i = 0; i < 8; i++) bad = or3(bad, xor_or(k[i].x, k[i].y, par), xor_or(k[i].z, k[i].w, par));
                if (++it > SPIN_LIMIT) TRAP();
            } while (__any_sync(0xffffffffu, bad & 1u));
#pragma unroll 1
            for (int r = 0; r < 8; r++) {
                uint32_t c = 0;
#pragma unroll
                for (int i = 0; i < 8; i++) c = max(c, k[i].x);
                const uint32_t m = __reduce_max_sync(0xffffffffu, c);
#pragma unroll
                for (int i = 0; i < 8; i++) if (k[i].x == m) k[i] = make_uint4(k[i].y, k[i].z, k[i].w, 0u);
                if (lane == 0) sts32(s_key + r * 4, m);
            }
        }
        bar_sync(0, NWRK);
        const uint32_t kk = lds32(s_key + (lane & 7) * 4), ep = lds32(s_cnt + 4);
        const bool own = KLATE(kk) && (KTOK(kk) >> 4) == b;
        uint32_t todo = __ballot_sync(0xffffffffu, own) & 0xffu;
        if (decltype(role)::value == 0 && todo) {
#pragma unroll
            for (int hf = 0; hf < 2; hf++) {
                const uint4 h = lds128(sb + SM_U + hf * 9216 + tid * 16);
                const uint2 st = lds64(s_stat + (g + 8 * hf) * 8);
                H[hf][0] = h.x; H[hf][1] = h.y; H[hf][2] = h.z; H[hf][3] = h.w;
#pragma unroll
                for (int k = 0; k < 4; k++) U2[hf][k] = ln_apply(H[hf][k], STAT_M(st), STAT_H(st), STAT_L(st));
            }
#pragma unroll 1
            while (todo) {
                const int s = __ffs(todo) - 1, tk = KTOK(__shfl_sync(0xffffffffu, kk, s));
                todo &= todo - 1;
                if ((tk & 13) == TOK(g)) publish(tk & 2, 2 * NCTA + s);
            }
            __threadfence();
        }
        bar_sync(0, NWRK);
        if (decltype(role)::value == 1) {
            if (lane < NSEL && own) *reinterpret_cast<volatile unsigned*>(p.s->flag + lane) = ep + 1u;
            int it = 0;
            while (__any_sync(0xffffffffu, KLATE(kk) && ld_acquire32(p.s->flag + (lane & 7)) != ep + 1u)) { if (++it > SPIN_LIMIT) TRAP(); }
            gather(__shfl_sync(0xffffffffu, kk, g));
        }
        bar_sync(0, NWRK);
    };
    if (warp < 18) {
        const unsigned char* ys = reinterpret_cast<const unsigned char*>(p.s->y) + (b < 64 ? (par ^ 1u) * (NCTA * 18432u) : 0u) +
                                  ((P * DM + 32 * warp + 8 * (g >> 1) + (g & 1)) * 64 + odd * 32 + t * 8);
        mbar_wait(bar_v);
        const uint32_t xa = sb + SM_XT + warp * 64 + t * 16;
        const uint4 x0 = lds128(xa + TOK(g) * 1152), x1 = lds128(xa + (TOK(g) + 2) * 1152), dk = lds128(xa + 16 * 1152);
        uint4 wr = make_uint4(0u, 0u, 0u, 0u);
        if (g == 0) wr = lds128(xa + 17 * 1152);
        uint2 yv[4];
        const uint32_t Z[2][4] = {{x0.x, x0.y, x0.z, x0.w}, {x1.x, x1.y, x1.z, x1.w}}, D4[4] = {dk.x, dk.y, dk.z, dk.w};
#pragma unroll
        for (int hf = 0; hf < 2; hf++) {
            const uint2 st = lds64(s_stat + (g + 8 * hf) * 8);
#pragma unroll
            for (int k = 0; k < 4; k++) U2[hf][k] = hmul2_bf(ln_apply(Z[hf][k], STAT_M(st), STAT_H(st), STAT_L(st)), D4[k]);
        }
        const uint32_t la = pin(sb + SM_LNP + (g * 20 + warp) * 4);
        {
            const unsigned char* y1 = ys + (U2[0][0] & U2[1][2] & (warp >> 8));
#pragma unroll
            for (int k = 0; k < 4; k++) yv[k] = ld_poll64(y1 + k * 128);
        }
        int it = 0;
        float d[2][4];
        while (true) {
            const uint32_t mn = min3(min3(yv[0].x, yv[0].y, yv[1].x), min3(yv[1].y, yv[2].x, yv[2].y), min(yv[3].x, yv[3].y));
#pragma unroll
            for (int k = 0; k < 4; k++) {
                H[0][k] = hadd2_bf(Z[0][k], hadd2_bf(movm(yv[k].x), U2[0][k]));
                H[1][k] = hadd2_bf(Z[1][k], hadd2_bf(movm(yv[k].y), U2[1][k]));
            }
            ln_partial(H, d);
            if (!__any_sync(0xffffffffu, mn == 0)) break;
            if (++it > SPIN_LIMIT) TRAP();
#pragma unroll
            for (int k = 0; k < 4; k++) yv[k] = ld_poll64(ys + k * 128);
        }
        STAMP(12);
        {
            const float s0 = (g & 1) ? d[0][3] : d[0][2], s1 = (g & 1) ? d[1][3] : d[1][2];
            const float q0 = (g & 1) ? d[0][1] : d[0][0], q1 = (g & 1) ? d[1][1] : d[1][0];
            asm volatile("{\n.reg .pred p;\nsetp.eq.u32 p, %5, %6;\n@p st.shared.f32 [%0], %1;\n@p st.shared.f32 [%0 + 640], %2;\n@p st.shared.f32 [%0 + 1280], %3;\n@p st.shared.f32 [%0 + 1920], %4;\n}\n"
                         ::"r"(la), "f"(s0), "f"(s1), "f"(q0), "f"(q1), "r"(t), "r"(g >> 1) : "memory");
        }
        bar_arrive(6, NWRK);
        STAMP(13);
        bar_sync(7, 608);
        STAMP(14);
#pragma unroll
        for (int hf = 0; hf < 2; hf++) {
            const uint2 st = lds64(s_stat + (g + 8 * hf) * 8);
#pragma unroll
            for (int k = 0; k < 4; k++) U2[hf][k] = ln_apply(H[hf][k], STAT_M(st), STAT_H(st), STAT_L(st));
        }
        {
            float cs[4] = {0.f, 0.f, 0.f, 0.f};
            mma_bf16(cs, U2[0][0], U2[1][0], U2[0][1], U2[1][1], wr.x, wr.y);
            mma_bf16(cs, U2[0][2], U2[1][2], U2[0][3], U2[1][3], wr.z, wr.w);
            if (t == 0) { stsf(la + 32 * 80, cs[0]); stsf(la + 40 * 80, cs[2]); }
            bar_arrive(8, 608);
        }
        FIX((uint32_t)warp >> 8);
        uint32_t O[2][4];
#pragma unroll
        for (int hf = 0; hf < 2; hf++)
#pragma unroll
            for (int k = 0; k < 4; k++) { O[hf][k] = hadd2_bf(H[hf][k], U2[hf][k]); H[hf][k] = nzw(H[hf][k]); U2[hf][k] = nzw(U2[hf][k]); }
        unsigned char* rowp = reinterpret_cast<unsigned char*>(p.s->rows) + ((254 - 2 * b) * 2304 + warp * 64 + t * 16);
        FIX(and3(and3(and3(H[0][0], H[0][1], H[0][2]), and3(H[0][3], H[1][0], H[1][1]), and3(H[1][2], H[1][3], U2[0][0])),
                 and3(and3(U2[0][1], U2[0][2], U2[0][3]), and3(U2[1][0], U2[1][1], U2[1][2]), U2[1][3]), (uint32_t)reinterpret_cast<uint64_t>(rowp)));
        bar_sync(9, 608);
        {
            const uint2 best = lds64(s_rank);
#pragma unroll
            for (int hf = 0; hf < 2; hf++) {
                const uint32_t me = 2 * TOK(g) + 4 * hf;
                unsigned char* d = rowp + (best.x == me ? 2304 : 0);
                if (best.x == me || best.y == me) {
                    stg128(d, U2[hf][0], U2[hf][1], U2[hf][2], U2[hf][3]);
                    stg128(d + 1152, H[hf][0], H[hf][1], H[hf][2], H[hf][3]);
                }
            }
        }
        FIX((uint32_t)warp >> 9);
#pragma unroll
        for (int hf = 0; hf < 2; hf++) {
            sts128(sb + SM_OUT + (TOK(g) + 2 * hf) * (DM * 2) + warp * 64 + t * 16, O[hf][0], O[hf][1], O[hf][2], O[hf][3]);
            sts128(sb + SM_U + hf * 9216 + tid * 16, H[hf][0], H[hf][1], H[hf][2], H[hf][3]);
        }
        STAMP(15);
        const int mi = lane >> 3, rr = lane & 7;
        const bool gate = warp < 12 && (warp & 3) != 2;
        const int fj = gate ? 3 * (warp >> 2) + min(warp & 3, 2) : (warp < 12 ? warp >> 2 : warp - 9);
        if (gate) {
            uint32_t W[18][4];
            mbar_wait(bar_w);
            const uint32_t aad = fj < 8 ? sb + SM_WG + (mi & 1) * SM_WU + (rr + 8 * (mi >> 1)) * 128 + (fj ^ rr) * 16 : sb + SM_WR + (mi & 1) * 4608 + (rr + 8 * (mi >> 1)) * 16;
            const uint32_t ast = fj < 8 ? 2048 : 256;
            const uint32_t bad = pin(sb + SM_XS + rr * XS_PITCH + mi * 16);
            bool rare = warp >> 8;
#pragma unroll 1
            do {
                if (rare) late_rows(IC<0>());
#pragma unroll
                for (int k = 0; k < 18; k++) ldsm_x4_t(W[k][0], W[k][1], W[k][2], W[k][3], aad + k * ast);
                if (rare) break;
                fence_async();
                STAMP2(17);
                rare = bar_or(11, NWRK, false);
            } while (rare);
            STAMP2(19);
            float c4[2][4] = {};
#pragma unroll
            for (int k = 0; k < 18; k += 2) {
                uint32_t b0, b1, b2, b3;
                ldsm_x4(b0, b1, b2, b3, bad + k * 32);
                mma_bf16(c4[0], W[k][0], W[k][1], W[k][2], W[k][3], b0, b1);
                mma_bf16(c4[1], W[k + 1][0], W[k + 1][1], W[k + 1][2], W[k + 1][3], b2, b3);
            }
            const uint32_t ex = sb + SM_EX + (32 * fj + lane) * 16;
            const float e0 = c4[0][0] + c4[1][0], e1 = c4[0][1] + c4[1][1], e2 = c4[0][2] + c4[1][2], e3 = c4[0][3] + c4[1][3];
            asm volatile("st.async.shared::cluster.mbarrier::complete_tx::bytes.v4.f32 [%0], {%1,%2,%3,%4}, [%5];\n"
                         ::"r"(ex ^ 0x1000000u), "f"(e0), "f"(e1), "f"(e2), "f"(e3), "r"(bar_g ^ 0x1000000u) : "memory");
            STAMP2(20);
            mbar_wait(bar_g);
            const uint4 o = lds128(ex);
            const uint32_t G = pack_bf16(e0 + __uint_as_float(o.x), e1 + __uint_as_float(o.y)), U = pack_bf16(e2 + __uint_as_float(o.z), e3 + __uint_as_float(o.w));
            sts32(sb + SM_GU + (32 * fj + lane) * 4, hmul2_bf(pack_bf16(bf_lo(G) * sigmoid_f(bf_lo(G)), bf_hi(G) * sigmoid_f(bf_hi(G))), U));
            bar_arrive(13, NWRK);
        } else {
            uint32_t W[2][18];
            auto load_wd = [&]() {
                mbar_wait(bar_d);
                const uint32_t base = sb + SM_WD + (4 * fj + (mi & 1)) * 16 + rr * WD_PITCH;
#pragma unroll
                for (int j = 0; j < 2; j++) {
#pragma unroll
                    for (int k = 0; k < 4; k++) ldsm_x4_t(W[j][4 * k], W[j][4 * k + 1], W[j][4 * k + 2], W[j][4 * k + 3], base + j * 32 + (k * 16 + 8 * (mi >> 1)) * WD_PITCH);
                    ldsm_x2_t(W[j][16], W[j][17], base + j * 32 + 64 * WD_PITCH);
                }
            };
            const uint32_t po = pin((((8 * (18 * odd + 2 * fj) + g) * 64 + P) * 4 + t) * 8);
            fence_async();
            STAMP2(17);
            if (bar_or(11, NWRK, false)) late_rows(IC<0>());
            delay(DDLY); load_wd();
            bar_sync(13, NWRK);
            STAMP2(21);
            uint32_t gb[9];
            ldsm_x4_t(gb[0], gb[1], gb[2], gb[3], sb + SM_GU + lane * 16);
            ldsm_x4_t(gb[4], gb[5], gb[6], gb[7], sb + SM_GU + 512 + lane * 16);
            ldsm_x1_t(gb[8], sb + SM_GU + 1024 + lane * 16);
            float c4[2][4] = {}, d4[2][4] = {};
#pragma unroll
            for (int k = 0; k < 4; k += 2)
#pragma unroll
                for (int j = 0; j < 2; j++) {
                    mma_bf16(c4[j], W[j][4 * k], W[j][4 * k + 1], W[j][4 * k + 2], W[j][4 * k + 3], gb[2 * k], gb[2 * k + 1]);
                    mma_bf16(d4[j], W[j][4 * k + 4], W[j][4 * k + 5], W[j][4 * k + 6], W[j][4 * k + 7], gb[2 * k + 2], gb[2 * k + 3]);
                }
#pragma unroll
            for (int j = 0; j < 2; j++) mma_bf16_k8(c4[j], W[j][16], W[j][17], gb[8]);
#pragma unroll
            for (int j = 0; j < 2; j++)
                stg64(reinterpret_cast<unsigned char*>(p.s->part) + po + j * 16384, nzw(pack_bf16(c4[j][0] + d4[j][0], c4[j][1] + d4[j][1])), nzw(pack_bf16(c4[j][2] + d4[j][2], c4[j][3] + d4[j][3])));
        }
        STAMP2(22);
    } else if (warp == 18) {
        const uint4* const ksrc = reinterpret_cast<const uint4*>(p.s->key3) + pin(2 * lane);
        const int row = (g >> 1) + 4 * (g & 1);
        const uint32_t ro = pin(640 * odd + t * 16), xd = pin(sb + SM_XS + row * XS_PITCH + t * 16 + (odd ? 0 : 512));
        const uint32_t xe = pin(sb + SM_XS + (g >> 1) * XS_PITCH + (lane & 7) * 16 + 64 * odd);
        const uint32_t sa = pin(sb + SM_LNP + lane * 80);
        const uint32_t klo = pin((uint32_t)(127 - b) << 9 | (uint32_t)(15 - ROWTOK(lane & 15)) << 1 | par), ra = pin(sb + SM_LNP + (32 + (lane & 15)) * 80);
        uint4* const kdst = reinterpret_cast<uint4*>(p.s->key3) + pin((lane >> 1) * 2 * NCTA + 2 * b + (lane & 1));
        FIX(ra);
        bar_sync(6, NWRK);
        {
            float mb, rc;
            ln_finish(sum18(sa), lane, mb, rc);
            if (lane < 16) stat_store(s_stat + lane * 8, mb, rc, 0u);
        }
        bar_arrive(7, 608);
        bar_sync(8, 608);
        uint32_t t0;
        {
            const uint32_t bits = __float_as_uint(rbf(sum18(ra)));
            const uint32_t me = ((bits ^ ((uint32_t)((int)bits >> 31) | 0x80000000u)) & 0xffff0000u) | klo;
            const uint32_t k0 = __reduce_max_sync(0xffffffffu, me), k1 = __reduce_max_sync(0xffffffffu, me == k0 ? 0u : me);
            const uint32_t k2 = __reduce_max_sync(0xffffffffu, me >= k1 ? 0u : me);
            if (lane < 2) stg128(kdst, k0 ^ 0x11eu, k1 ^ 0xfeu, k2 ^ 0xdeu, par);
            asm volatile("mov.u32 %0, %%clock;" : "=r"(t0) :: "memory");
            STAMPW(23);
            if (lane == 0) sts64(s_rank, ~k0 & 30u, ~k1 & 30u);
            bar_arrive(9, 608);
            sts32(s_k16 + (lane & 15) * 4, me);
            __syncwarp();
            const uint4 v = lds128(s_k16 + (lane & 16) * 2), w = lds128(s_k16 + (lane & 16) * 2 + 16);
            int rank = ((v.x > me) + (v.y > me)) + ((v.z > me) + (v.w > me)) + (((w.x > me) + (w.y > me)) + ((w.z > me) + (w.w > me)));
            rank += __shfl_xor_sync(0xffffffffu, rank, 16);
            if (lane < 16 && rank < 8) p.s->key[8 * b + rank] = (me ^ 0x1eu) | ((8 - rank) << 5);
        }
        uint4 kq[4];
        uint32_t u[4], mine = 0, m;
        int it = 0;
        { uint32_t now; do { asm volatile("mov.u32 %0, %%clock;" : "=r"(now) :: "memory"); } while (now - t0 < KDLY); }
        do {
#pragma unroll
            for (int i = 0; i < 4; i++) kq[i] = ld_poll(ksrc + 64 * i);
            if (++it > SPIN_LIMIT) TRAP();
            uint32_t S[2][4];
#pragma unroll
            for (int i = 0; i < 2; i++) {
                const uint4 &c = kq[2 * i], &d = kq[2 * i + 1];
                const uint32_t m1 = min(c.x, d.x), m2 = max(c.y, d.y);
                S[i][0] = max(c.x, d.x); S[i][1] = max(m1, m2); S[i][2] = min(m1, m2); S[i][3] = min(c.y, d.y);
            }
            const uint32_t a0 = max(S[0][0], S[1][3]), a1 = max(S[0][1], S[1][2]), a2 = max(S[0][2], S[1][1]), a3 = max(S[0][3], S[1][0]);
            const uint32_t b0 = max(a0, a2), b2 = min(a0, a2), b1 = max(a1, a3), b3 = min(a1, a3);
            u[0] = max(b0, b1); u[1] = min(b0, b1); u[2] = max(b2, b3); u[3] = min(b2, b3);
            const uint32_t bad = or3(or3(xor_or(kq[0].x, kq[0].y, par), xor_or(kq[0].z, kq[1].x, par), xor_or(kq[1].y, kq[1].z, par)),
                                     xor_or(kq[2].x, kq[2].y, par), xor_or(kq[2].z, kq[3].x, par)) | xor_or(kq[3].y, kq[3].z, par);
            m = __reduce_max_sync(0xffffffffu, u[0] | (uint32_t)((int)(bad << 31) >> 31));
        } while (m == 0xffffffffu);
        STAMPW(16);
#pragma unroll
        for (int r = 0; r < 8; r++) {
            if (r) m = __reduce_max_sync(0xffffffffu, u[0]);
            if (u[0] == m) { u[0] = u[1]; u[1] = u[2]; u[2] = u[3]; u[3] = 0; }
            if (row == r) mine = m;
        }
        uint4 v[9];
        const uint32_t o0 = __byte_perm(mine, 0, 0x4441) * 2304u, o1 = __shfl_xor_sync(0xffffffffu, o0, 4);
        const unsigned char* const rA = reinterpret_cast<const unsigned char*>(p.s->rows) + (((g & 1) ? o1 : o0) + ro + (g & 1) * 64);
        const unsigned char* const rb = reinterpret_cast<const unsigned char*>(p.s->rows) + (((g & 1) ? o0 : o1) + ro + (g & 1) * 64);
        const unsigned char* const rc = reinterpret_cast<const unsigned char*>(p.s->rows) + (o0 + ro + (odd ? -64 : 512));
#pragma unroll
        for (int i = 0; i < 4; i++) { v[i] = ld_poll(rA + i * 128); v[4 + i] = ld_poll(rb + i * 128); }
        v[8] = ld_poll(rc);
        const bool again = u[0] == 0 || max(max(kq[0].z, kq[1].z), max(kq[2].z, kq[3].z)) > m;
        if (t == 0) sts32(s_key + row * 4, mine);
#pragma unroll
        for (int i = 0; i < 9; i++) sts128(i < 8 ? xe + (i >> 2) * 4 * XS_PITCH + (i & 3) * 128 : xd, v[i].x, v[i].y, v[i].z, v[i].w);
        uint32_t mn, m3[3];
        m3[0] = m3[1] = m3[2] = 1u;
#pragma unroll
        for (int i = 0; i < 9; i++) m3[i % 3] = min3(min3(m3[i % 3], v[i].x, v[i].y), v[i].z, v[i].w);
        mn = min3(m3[0], m3[1], m3[2]);
        STAMPW(18);
        if (bar_or(11, NWRK, again || mn == 0)) late_rows(IC<1>());
    } else {
        bar_sync(6, NWRK);
        WPOINT(16, true);
        if (WANY(17) || WANY(18)) delay(WDLY);
        WPOINT(17, true);
        if (WANY(18)) delay(WDLY);
        WPOINT(18, true);
        if (bar_or(11, NWRK, false)) late_rows(IC<2>());
        const int tk = KTOK(lds32(s_key + (lane & 7) * 4));
        const uint32_t sel = __reduce_or_sync(0xffffffffu, (tk >> 4) == b ? 1u << (tk & 15) : 0u);
        if (sel ? lane < 16 && !((sel >> lane) & 1u) : lane == 0) bulk_s2g(p.out + (size_t)(16 * b + lane) * DM, sb + SM_OUT + lane * (DM * 2), sel ? DM * 2 : 16 * DM * 2);
        __syncwarp();
    }
    if (warp == 8 || warp >= 18) {
        const int grp = 3 * b + (warp == 8 ? 0 : warp - 17), fsl = 2 * t + ((lane >> 3) & 1), fc = 16 * (grp >> 3) + (grp & 7) + 8 * (lane >> 4);
        const uint32_t fk = lds32(s_key + fsl * 4);
        float hv = 0.f, u2 = 0.f;
        int it = 0;
        if (b < 96) {
            const uint32_t* const fsrc = p.s->rows + KSLOT(fk, fsl) * DM + (fc >> 1);
            uint32_t hw, uw;
            do { hw = ld_poll32(fsrc + 288); uw = ld_poll32(fsrc); if (++it > SPIN_LIMIT) TRAP(); } while (!hw || !uw);
            hv = (fc & 1) ? bf_hi(hw) : bf_lo(hw); u2 = (fc & 1) ? bf_hi(uw) : bf_lo(uw);
        }
        const float rs = rbf(sigmoid_f(__uint_as_float((fk ^ ((uint32_t)((int)~fk >> 31) | 0x80000000u)) & 0xffff0000u)));
        const uint32_t dof = pin(KTOK(fk) * DM + fc), so = pin(grp * 256 + lane);
        if (warp > 17) bar_sync(13, NWRK);
        if (b < 96) {
            delay(warp > 17 ? FDLY : FDLY2);
            float y;
            uint32_t ok;
            float s0, s1, s2, s3;
            do {
                uint2 a[8];
#pragma unroll
                for (int i = 0; i < 8; i++) a[i] = ld_poll64(reinterpret_cast<const uint2*>(p.s->part) + so + 32 * i);
                if (++it > SPIN_LIMIT) TRAP();
                ok = min3(min3(min3(a[0].x, a[0].y, a[1].x), min3(a[1].y, a[2].x, a[2].y), min3(a[3].x, a[3].y, a[4].x)), min3(min3(a[4].y, a[5].x, a[5].y), min3(a[6].x, a[6].y, a[7].x), a[7].y), 1u);
#define S8(c, f) (((c(a[0].f) + c(a[1].f)) + (c(a[2].f) + c(a[3].f))) + ((c(a[4].f) + c(a[5].f)) + (c(a[6].f) + c(a[7].f))))
                s0 = S8(bf_lo, x); s1 = S8(bf_hi, x); s2 = S8(bf_lo, y); s3 = S8(bf_hi, y);
                asm volatile("" : "+f"(s0), "+f"(s1), "+f"(s2), "+f"(s3));
#undef S8
            } while (__any_sync(0xffffffffu, !ok));
            STAMP2(24);
#define HALVE(u, v, m) (((lane & m) ? v : u) + __shfl_xor_sync(0xffffffffu, (lane & m) ? u : v, m))
            const float r0 = HALVE(s0, s2, 16), r1 = HALVE(s1, s3, 16);
            y = HALVE(r0, r1, 8);
            y += __shfl_xor_sync(0xffffffffu, y, 4);
#undef HALVE
            p.out[dof] = __float2bfloat16_rn(hv + rbf(u2 + rbf(rbf(y) * rs)));
        }
    }
    if (warp == 19) asm volatile("cp.async.bulk.wait_group.read 0;\n" ::: "memory");
    if (b == 0 && tid < 8) *reinterpret_cast<volatile unsigned*>(p.s->hint + tid * 32 + 1) = lds32(s_cnt + 4) + 1u;
    STAMP(25);
    }
}

typedef CUresult (*PFN_tmEncode)(CUtensorMap*, CUtensorMapDataType, cuuint32_t, void*, const cuuint64_t*, const cuuint64_t*, const cuuint32_t*,
                                 const cuuint32_t*, CUtensorMapInterleave, CUtensorMapSwizzle, CUtensorMapL2promotion, CUtensorMapFloatOOBfill);

extern "C" void kernel_launch(void* const* d_in, const int* in_sizes, int n_in, void* d_out, int out_size) {
    Params p;
    p.x = (const bf16*)d_in[0];
    p.lar = (const bf16*)d_in[1];
    p.aim = (const bf16*)d_in[2];
    p.cre = (const bf16*)d_in[3];
    p.cim = (const bf16*)d_in[4];
    p.ldt = (const bf16*)d_in[5];
    p.dsk = (const bf16*)d_in[6];
    p.wr = (const bf16*)d_in[8];
    p.out = (bf16*)d_out;
    static PFN_tmEncode enc = nullptr;
    static void* scratch = nullptr;
    if (!enc) {
        cudaFuncSetAttribute(fused_kernel, cudaFuncAttributeMaxDynamicSharedMemorySize, SMEM_TOTAL);
        void* fn = nullptr;
        cudaDriverEntryPointQueryResult qr;
        cudaGetDriverEntryPoint("cuTensorMapEncodeTiled", &fn, cudaEnableDefault, &qr);
        enc = (PFN_tmEncode)fn;
        cudaGetSymbolAddress(&scratch, g_scratch);
    }
    p.s = (Scratch*)scratch;
    Maps tm;
    const cuuint64_t dims[2] = {FF, DM}, strides[1] = {FF * 2};
    const cuuint32_t box[2] = {64, 48}, rbox[2] = {8, 144}, es[2] = {1, 1};
    for (int i = 0; i < 2; i++) {
        enc(&tm.w[i], CU_TENSOR_MAP_DATA_TYPE_BFLOAT16, 2, d_in[9 + i], dims, strides, box, es, CU_TENSOR_MAP_INTERLEAVE_NONE, CU_TENSOR_MAP_SWIZZLE_128B,
            CU_TENSOR_MAP_L2_PROMOTION_NONE, CU_TENSOR_MAP_FLOAT_OOB_FILL_NONE);
        enc(&tm.r[i], CU_TENSOR_MAP_DATA_TYPE_BFLOAT16, 2, d_in[9 + i], dims, strides, rbox, es, CU_TENSOR_MAP_INTERLEAVE_NONE, CU_TENSOR_MAP_SWIZZLE_NONE,
            CU_TENSOR_MAP_L2_PROMOTION_NONE, CU_TENSOR_MAP_FLOAT_OOB_FILL_NONE);
    }
    const cuuint64_t ddims[2] = {DM / 2, FF}, dstrides[1] = {DM * 2};
    const cuuint32_t dbox[2] = {WD_PITCH / 4, 8};
    enc(&tm.d, CU_TENSOR_MAP_DATA_TYPE_UINT32, 2, d_in[11], ddims, dstrides, dbox, es, CU_TENSOR_MAP_INTERLEAVE_NONE, CU_TENSOR_MAP_SWIZZLE_NONE,
        CU_TENSOR_MAP_L2_PROMOTION_L2_128B, CU_TENSOR_MAP_FLOAT_OOB_FILL_NONE);
    const cuuint64_t xdims[4] = {DM, 128, 4, 4}, xstrides[3] = {DM * 8, DM * 2, DM * 1024};
    const cuuint32_t xbox[4] = {8, 128, 4, 2}, xes[4] = {1, 1, 1, 1};
    enc(&tm.x, CU_TENSOR_MAP_DATA_TYPE_BFLOAT16, 4, d_in[0], xdims, xstrides, xbox, xes, CU_TENSOR_MAP_INTERLEAVE_NONE, CU_TENSOR_MAP_SWIZZLE_NONE,
        CU_TENSOR_MAP_L2_PROMOTION_NONE, CU_TENSOR_MAP_FLOAT_OOB_FILL_NONE);
    fused_kernel<<<NCTA, NTHR, SMEM_TOTAL>>>(p, tm);
}
```

```cpp
#include <cuda_runtime.h>
#include <cuda.h>
#include <cuda_fp16.h>
#include <cuda_bf16.h>
#include <stdint.h>

#define LSEQ 2048
#define DM 576
#define NST 128
#define FF 4608
#define NSEL 8
#define NCTA 128
#define NTHR 640
#define NWRK 640

typedef __nv_bfloat16 bf16;

#define SM_WG 0
#define SM_WU 36864
#define SM_WR 73728
#define SM_XC (82944 - 32768)
#define SM_WD 82944
#define WD_PITCH 592
#define SM_Z2 (SM_WD + 10240)
#define SM_XT (SM_PL - 18 * 1152)
#define SM_PL (SM_WD + 46080)
#define PL_HALF 1344
#define PLW_B 2624
#define PL_B (4 * PLW_B)
#define SM_U (SM_PL + 5 * PL_B)
#define UPAD 20
#define ULO_B ((UPAD + 128) * 16)
#define USLOT_B (2 * ULO_B)
#define SM_KW (SM_U + 5 * USLOT_B)
#define KW_B 3712
#define KW_PL 1216
#define KW_P 2400
#define KW_H 3440
#define SM_MISC (SM_KW + 5 * KW_B)
#define SM_LC (SM_MISC + 416)
#define SM_LNP (SM_LC + 768)
#define SM_RX (SM_LNP + 3840)
#define SMEM_TOTAL (SM_RX + 3088)
#define TBW PLW_B
#define SM_OUT SM_PL
#define SM_XS (SM_PL + 18432)
#define XS_PITCH 592
#define SM_GU (SM_PL + 23296)
#define SM_EX (SM_PL + 24576)

struct __align__(128) Scratch {
    unsigned hint[8 * 32];
    unsigned flag[32];
    uint32_t key3[NCTA * 8];
    uint32_t key[NCTA * 8];
    uint32_t stat[LSEQ];
    uint32_t uT[64 * (LSEQ / 2)];
    uint32_t y[(NCTA + 96) * DM * 8];
    uint32_t part[288 * 64 * 8];
    uint32_t rows[(2 * NCTA + NSEL) * DM];
};
__device__ Scratch g_scratch;
#define STAMP(i)
#define STAMPX(i)
#define STAMPY(i)

__device__ __forceinline__ float rbf(float x) {
    uint32_t r;
    asm("cvt.rn.bf16x2.f32 %0, %1, %2;\n" : "=r"(r) : "f"(x), "f"(0.f));
    return __uint_as_float(r);
}
__device__ __forceinline__ uint32_t pack_bf16(float lo, float hi) {
    uint32_t r;
    asm("cvt.rn.bf16x2.f32 %0, %1, %2;\n" : "=r"(r) : "f"(hi), "f"(lo));
    return r;
}
__device__ __forceinline__ uint32_t pack_f16(float lo, float hi) {
    uint32_t r;
    asm("cvt.rn.f16x2.f32 %0, %1, %2;\n" : "=r"(r) : "f"(hi), "f"(lo));
    return r;
}
__device__ __forceinline__ float bf_lo(uint32_t w) { return __uint_as_float(w << 16); }
__device__ __forceinline__ float bf_hi(uint32_t w) { return __uint_as_float(w & 0xffff0000u); }
__device__ __forceinline__ uint32_t hadd2_bf(uint32_t a, uint32_t b) {
    __nv_bfloat162 r = __hadd2_rn(*reinterpret_cast<__nv_bfloat162*>(&a), *reinterpret_cast<__nv_bfloat162*>(&b));
    return *reinterpret_cast<uint32_t*>(&r);
}
__device__ __forceinline__ uint32_t hsub2_bf(uint32_t a, uint32_t b) {
    __nv_bfloat162 r = __hsub2_rn(*reinterpret_cast<__nv_bfloat162*>(&a), *reinterpret_cast<__nv_bfloat162*>(&b));
    return *reinterpret_cast<uint32_t*>(&r);
}
__device__ __forceinline__ uint32_t hmul2_bf(uint32_t a, uint32_t b) {
    __nv_bfloat162 r = __hmul2_rn(*reinterpret_cast<__nv_bfloat162*>(&a), *reinterpret_cast<__nv_bfloat162*>(&b));
    return *reinterpret_cast<uint32_t*>(&r);
}
__device__ __forceinline__ uint32_t hfma2_bf(uint32_t a, uint32_t b, uint32_t c) { uint32_t r; asm("fma.rn.bf16x2 %0, %1, %2, %3;\n" : "=r"(r) : "r"(a), "r"(b), "r"(c)); return r; }
__device__ __forceinline__ uint32_t hmul2(uint32_t a, uint32_t b) { uint32_t r; asm("mul.rn.f16x2 %0, %1, %2;\n" : "=r"(r) : "r"(a), "r"(b)); return r; }
__device__ __forceinline__ uint32_t hadd2(uint32_t a, uint32_t b) { uint32_t r; asm("add.rn.f16x2 %0, %1, %2;\n" : "=r"(r) : "r"(a), "r"(b)); return r; }
__device__ __forceinline__ uint32_t hfma2(uint32_t a, uint32_t b, uint32_t c) { uint32_t r; asm("fma.rn.f16x2 %0, %1, %2, %3;\n" : "=r"(r) : "r"(a), "r"(b), "r"(c)); return r; }
__device__ __forceinline__ uint32_t hfms2(uint32_t a, uint32_t b, uint32_t c) {
    uint32_t r;
    asm("{\n.reg .b32 n;\nneg.f16x2 n, %2;\nfma.rn.f16x2 %0, %1, n, %3;\n}\n" : "=r"(r) : "r"(a), "r"(b), "r"(c));
    return r;
}
__device__ __forceinline__ uint32_t nzw(uint32_t w) { uint32_t r; asm("max.u32 %0, %1, 1;\n" : "=r"(r) : "r"(w)); return r; }
__device__ __forceinline__ uint32_t smem_u32(const void* p) { return (uint32_t)__cvta_generic_to_shared(p); }
__device__ __forceinline__ uint32_t lds32(uint32_t addr) {
    uint32_t v;
    asm volatile("ld.shared.u32 %0, [%1];\n" : "=r"(v) : "r"(addr) : "memory");
    return v;
}
__device__ __forceinline__ uint32_t lds16(uint32_t addr) {
    unsigned short v;
    asm volatile("ld.shared.u16 %0, [%1];\n" : "=h"(v) : "r"(addr) : "memory");
    return v;
}
__device__ __forceinline__ uint2 lds64(uint32_t addr) {
    uint2 v;
    asm volatile("ld.shared.v2.u32 {%0,%1}, [%2];\n" : "=r"(v.x), "=r"(v.y) : "r"(addr) : "memory");
    return v;
}
__device__ __forceinline__ uint4 lds128(uint32_t addr) {
    uint4 v;
    asm volatile("ld.shared.v4.u32 {%0,%1,%2,%3}, [%4];\n" : "=r"(v.x), "=r"(v.y), "=r"(v.z), "=r"(v.w) : "r"(addr) : "memory");
    return v;
}
__device__ __forceinline__ void sts32(uint32_t addr, uint32_t v) { asm volatile("st.shared.u32 [%0], %1;\n" ::"r"(addr), "r"(v) : "memory"); }
__device__ __forceinline__ void sts16(uint32_t addr, uint32_t v) { asm volatile("st.shared.u16 [%0], %1;\n" ::"r"(addr), "h"((unsigned short)v) : "memory"); }
__device__ __forceinline__ void stsf(uint32_t addr, float v) { sts32(addr, __float_as_uint(v)); }
__device__ __forceinline__ void sts64(uint32_t addr, uint32_t a, uint32_t b) { asm volatile("st.shared.v2.u32 [%0], {%1,%2};\n" ::"r"(addr), "r"(a), "r"(b) : "memory"); }
__device__ __forceinline__ void sts128(uint32_t addr, uint32_t a, uint32_t b, uint32_t c, uint32_t d) {
    asm volatile("st.shared.v4.u32 [%0], {%1,%2,%3,%4};\n" ::"r"(addr), "r"(a), "r"(b), "r"(c), "r"(d) : "memory");
}
__device__ __forceinline__ void ldsm_x4(uint32_t& r0, uint32_t& r1, uint32_t& r2, uint32_t& r3, uint32_t addr) {
    asm volatile("ldmatrix.sync.aligned.m8n8.x4.shared.b16 {%0,%1,%2,%3}, [%4];\n"
                 : "=r"(r0), "=r"(r1), "=r"(r2), "=r"(r3) : "r"(addr) : "memory");
}
__device__ __forceinline__ void ldsm_x4_t(uint32_t& r0, uint32_t& r1, uint32_t& r2, uint32_t& r3, uint32_t addr) {
    asm volatile("ldmatrix.sync.aligned.m8n8.x4.trans.shared.b16 {%0,%1,%2,%3}, [%4];\n"
                 : "=r"(r0), "=r"(r1), "=r"(r2), "=r"(r3) : "r"(addr) : "memory");
}
__device__ __forceinline__ void ldsm_x2_t(uint32_t& r0, uint32_t& r1, uint32_t addr) {
    asm volatile("ldmatrix.sync.aligned.m8n8.x2.trans.shared.b16 {%0,%1}, [%2];\n" : "=r"(r0), "=r"(r1) : "r"(addr) : "memory");
}
__device__ __forceinline__ void ldsm_x1_t(uint32_t& r0, uint32_t addr) {
    asm volatile("ldmatrix.sync.aligned.m8n8.x1.trans.shared.b16 {%0}, [%1];\n" : "=r"(r0) : "r"(addr) : "memory");
}
__device__ __forceinline__ void stsm_x4(uint32_t addr, uint32_t r0, uint32_t r1, uint32_t r2, uint32_t r3) {
    asm volatile("stmatrix.sync.aligned.m8n8.x4.shared.b16 [%0], {%1,%2,%3,%4};\n" ::"r"(addr), "r"(r0), "r"(r1), "r"(r2), "r"(r3) : "memory");
}
__device__ __forceinline__ void stsm_x4_t(uint32_t addr, uint32_t r0, uint32_t r1, uint32_t r2, uint32_t r3) {
    asm volatile("stmatrix.sync.aligned.m8n8.x4.trans.shared.b16 [%0], {%1,%2,%3,%4};\n" ::"r"(addr), "r"(r0), "r"(r1), "r"(r2), "r"(r3) : "memory");
}
__device__ __forceinline__ uint32_t movm(uint32_t a) {
    uint32_t d;
    asm volatile("movmatrix.sync.aligned.m8n8.trans.b16 %0, %1;\n" : "=r"(d) : "r"(a));
    return d;
}
__device__ __forceinline__ void mma_f16(float (&c)[4], uint32_t a0, uint32_t a1, uint32_t a2, uint32_t a3, uint32_t b0, uint32_t b1) {
    asm volatile(
        "mma.sync.aligned.m16n8k16.row.col.f32.f16.f16.f32 {%0,%1,%2,%3}, {%4,%5,%6,%7}, {%8,%9}, {%0,%1,%2,%3};\n"
        : "+f"(c[0]), "+f"(c[1]), "+f"(c[2]), "+f"(c[3])
        : "r"(a0), "r"(a1), "r"(a2), "r"(a3), "r"(b0), "r"(b1));
}
__device__ __forceinline__ void mma_bf16(float (&c)[4], uint32_t a0, uint32_t a1, uint32_t a2, uint32_t a3, uint32_t b0, uint32_t b1) {
    asm volatile(
        "mma.sync.aligned.m16n8k16.row.col.f32.bf16.bf16.f32 {%0,%1,%2,%3}, {%4,%5,%6,%7}, {%8,%9}, {%0,%1,%2,%3};\n"
        : "+f"(c[0]), "+f"(c[1]), "+f"(c[2]), "+f"(c[3])
        : "r"(a0), "r"(a1), "r"(a2), "r"(a3), "r"(b0), "r"(b1));
}
__device__ __forceinline__ void mma_bf16_k8(float (&c)[4], uint32_t a0, uint32_t a1, uint32_t b0) {
    asm volatile("mma.sync.aligned.m16n8k8.row.col.f32.bf16.bf16.f32 {%0,%1,%2,%3}, {%4,%5}, {%6}, {%0,%1,%2,%3};\n"
                 : "+f"(c[0]), "+f"(c[1]), "+f"(c[2]), "+f"(c[3]) : "r"(a0), "r"(a1), "r"(b0));
}
__device__ __forceinline__ void bar_sync(int id, int n) { asm volatile("bar.sync %0, %1;\n" ::"r"(id), "r"(n) : "memory"); }
__device__ __forceinline__ void bar_arrive(int id, int n) { asm volatile("bar.arrive %0, %1;\n" ::"r"(id), "r"(n) : "memory"); }
__device__ __forceinline__ bool bar_or(int id, int n, bool v) {
    uint32_t r;
    asm volatile("{\n.reg .pred p, q;\nsetp.ne.u32 p, %3, 0;\nbar.red.or.pred q, %1, %2, p;\nselp.u32 %0, 1, 0, q;\n}\n" : "=r"(r) : "r"(id), "r"(n), "r"((uint32_t)v) : "memory");
    return r;
}
__device__ __forceinline__ uint32_t and3(uint32_t a, uint32_t b, uint32_t c) { uint32_t r; asm("lop3.b32 %0, %1, %2, %3, 0x80;\n" : "=r"(r) : "r"(a), "r"(b), "r"(c)); return r; }
__device__ __forceinline__ uint32_t or3(uint32_t a, uint32_t b, uint32_t c) { uint32_t r; asm("lop3.b32 %0, %1, %2, %3, 0xfe;\n" : "=r"(r) : "r"(a), "r"(b), "r"(c)); return r; }
__device__ __forceinline__ uint32_t min3(uint32_t a, uint32_t b, uint32_t c) { uint32_t r; asm("{\n.reg .u32 t;\nmin.u32 t, %2, %3;\nmin.u32 %0, %1, t;\n}\n" : "=r"(r) : "r"(a), "r"(b), "r"(c)); return r; }
__device__ __forceinline__ uint32_t xor_or(uint32_t a, uint32_t b, uint32_t c) { uint32_t r; asm("lop3.b32 %0, %1, %2, %3, 0x7e;\n" : "=r"(r) : "r"(a), "r"(b), "r"(c)); return r; }
__device__ __forceinline__ uint32_t pin(uint32_t v) { uint32_t r; asm volatile("shfl.sync.bfly.b32 %0, %1, 0, 0x1f, 0xffffffff;\n" : "=r"(r) : "r"(v) : "memory"); return r; }
__device__ __forceinline__ uint4 ld_poll(const void* p) {
    uint4 v;
    asm volatile("ld.relaxed.gpu.global.v4.u32 {%0,%1,%2,%3}, [%4];\n" : "=r"(v.x), "=r"(v.y), "=r"(v.z), "=r"(v.w) : "l"(p) : "memory");
    return v;
}
__device__ __forceinline__ uint2 ld_poll64(const void* p) {
    uint2 v;
    asm volatile("ld.relaxed.gpu.global.v2.u32 {%0,%1}, [%2];\n" : "=r"(v.x), "=r"(v.y) : "l"(p) : "memory");
    return v;
}
__device__ __forceinline__ uint32_t ld_poll32(const void* p) {
    uint32_t v;
    asm volatile("ld.relaxed.gpu.global.u32 %0, [%1];\n" : "=r"(v) : "l"(p) : "memory");
    return v;
}
__device__ __forceinline__ uint32_t ld_acquire32(const void* p) {
    uint32_t v;
    asm volatile("ld.acquire.gpu.global.u32 %0, [%1];\n" : "=r"(v) : "l"(p) : "memory");
    return v;
}
__device__ __forceinline__ uint2 ldo64(const void* p) {
    uint2 v;
    asm volatile("ld.relaxed.cta.global.v2.u32 {%0,%1}, [%2];\n" : "=r"(v.x), "=r"(v.y) : "l"(p) : "memory");
    return v;
}
__device__ __forceinline__ uint32_t ldo16(const void* p) {
    uint32_t v;
    asm volatile("ld.relaxed.cta.global.u16 %0, [%1];\n" : "=r"(v) : "l"(p) : "memory");
    return v;
}
__device__ __forceinline__ void stg128(void* p, uint32_t a, uint32_t b, uint32_t c, uint32_t d) {
    asm volatile("st.global.v4.u32 [%0], {%1,%2,%3,%4};\n" ::"l"(p), "r"(a), "r"(b), "r"(c), "r"(d) : "memory");
}
__device__ __forceinline__ void stg64(void* p, uint32_t a, uint32_t b) { asm volatile("st.global.v2.u32 [%0], {%1,%2};\n" ::"l"(p), "r"(a), "r"(b) : "memory"); }
__device__ __forceinline__ uint32_t min4(const uint4& v) { return min(min(v.x, v.y), min(v.z, v.w)); }
#define SPIN_LIMIT (1 << 21)
#define TRAP() __trap()
__device__ __forceinline__ void mbar_init(uint32_t bar, uint32_t cnt) { asm volatile("mbarrier.init.shared::cta.b64 [%0], %1;\n" ::"r"(bar), "r"(cnt) : "memory"); }
__device__ __forceinline__ void mbar_expect(uint32_t bar, uint32_t bytes) {
    asm volatile("mbarrier.arrive.expect_tx.shared::cta.b64 _, [%0], %1;\n" ::"r"(bar), "r"(bytes) : "memory");
}
__device__ __forceinline__ void mbar_arrive(uint32_t bar) { asm volatile("mbarrier.arrive.shared::cta.b64 _, [%0];\n" ::"r"(bar) : "memory"); }
__device__ __forceinline__ void mbar_wait(uint32_t bar) {
    asm volatile(
        "{\n.reg .pred p;\n"
        "W_%=:\n"
        "mbarrier.try_wait.parity.shared::cta.b64 p, [%0], 0;\n"
        "@!p bra W_%=;\n}\n" ::"r"(bar) : "memory");
}
__device__ __forceinline__ void bulk_g2s(uint32_t dst, const void* src, uint32_t bytes, uint32_t bar) {
    asm volatile("cp.async.bulk.shared::cluster.global.mbarrier::complete_tx::bytes [%0], [%1], %2, [%3];\n" ::"r"(dst), "l"(src), "r"(bytes), "r"(bar) : "memory");
}
__device__ __forceinline__ void bulk_s2g(void* dst, uint32_t src, uint32_t bytes) {
    asm volatile("cp.async.bulk.global.shared::cta.bulk_group [%0], [%1], %2;\ncp.async.bulk.commit_group;\n" ::"l"(dst), "r"(src), "r"(bytes) : "memory");
}
__device__ __forceinline__ void bulk_s2g_nc(void* dst, uint32_t src, uint32_t bytes) {
    asm volatile("cp.async.bulk.global.shared::cta.bulk_group [%0], [%1], %2;\n" ::"l"(dst), "r"(src), "r"(bytes) : "memory");
}
__device__ __forceinline__ void tma_2d(uint32_t dst, const CUtensorMap* tm, int c0, int c1, uint32_t bar) {
    asm volatile("cp.async.bulk.tensor.2d.shared::cluster.global.mbarrier::complete_tx::bytes [%0], [%1, {%3, %4}], [%2];\n"
                 ::"r"(dst), "l"(tm), "r"(bar), "r"(c0), "r"(c1) : "memory");
}
__device__ __forceinline__ void tma_4d_mc(uint32_t dst, const CUtensorMap* tm, int c0, int c3, uint32_t bar) {
    asm volatile("cp.async.bulk.tensor.4d.shared::cluster.global.mbarrier::complete_tx::bytes.multicast::cluster [%0], [%1, {%3, %4, %4, %5}], [%2], %6;\n"
                 ::"r"(dst), "l"(tm), "r"(bar), "r"(c0), "r"(0), "r"(c3), "h"((unsigned short)3) : "memory");
}
__device__ __forceinline__ bool elect_one() {
    uint32_t r;
    asm volatile("{\n.reg .pred p;\nelect.sync _|p, 0xffffffff;\nselp.u32 %0, 1, 0, p;\n}\n" : "=r"(r));
    return r;
}
__device__ __forceinline__ void delay(uint32_t clks) {
    uint32_t t0, t1;
    asm volatile("mov.u32 %0, %%clock;" : "=r"(t0) :: "memory");
    do { asm volatile("mov.u32 %0, %%clock;" : "=r"(t1) :: "memory"); } while (t1 - t0 < clks);
}
__device__ __forceinline__ void fence_async() { asm volatile("fence.proxy.async.shared::cta;\n" ::: "memory"); }

__device__ __forceinline__ float2 cmul(float2 a, float2 b) {
    return make_float2(fmaf(a.x, b.x, -a.y * b.y), fmaf(a.x, b.y, a.y * b.x));
}
__device__ __forceinline__ float2 csq(float2 a) {
    float p = a.x * a.y;
    return make_float2(fmaf(a.x, a.x, -a.y * a.y), p + p);
}
__device__ __forceinline__ float ex2_approx(float x) { float r; asm("ex2.approx.ftz.f32 %0, %1;\n" : "=f"(r) : "f"(x)); return r; }
__device__ __forceinline__ float exp_bf(float x) { return rbf(ex2_approx(__fmul_ru(x, 1.4426950408889634f))); }
__device__ __forceinline__ float2 cexp_e(float lr2, float li, float e) {
    const float m = ex2_approx(lr2 * e);
    return make_float2(m * __cosf(li * e), m * __sinf(li * e));
}
__device__ __forceinline__ float rcp_approx(float x) { float r; asm("rcp.approx.ftz.f32 %0, %1;\n" : "=f"(r) : "f"(x)); return r; }
__device__ __forceinline__ float sigmoid_f(float x) { return rcp_approx(1.0f + ex2_approx(x * -1.4426950408889634f)); }
__device__ __forceinline__ float sqrt_approx(float x) { float r; asm("sqrt.approx.ftz.f32 %0, %1;\n" : "=f"(r) : "f"(x)); return r; }

__device__ __forceinline__ void wg_fence() { asm volatile("wgmma.fence.sync.aligned;\n" ::: "memory"); }
__device__ __forceinline__ void wg_commit() { asm volatile("wgmma.commit_group.sync.aligned;\n" ::: "memory"); }
__device__ __forceinline__ void wg_wait0() { asm volatile("wgmma.wait_group.sync.aligned 0;\n" ::: "memory"); }
template <int T> __device__ __forceinline__ void wg_mma(float (&acc)[16][4], const uint32_t* a, uint64_t desc);
template <int T> __device__ __forceinline__ void wg_first(float (&acc)[16][4], const uint32_t* a, uint64_t desc);
template <> __device__ __forceinline__ void wg_mma<0>(float (&acc)[16][4], const uint32_t* a, uint64_t desc) {
    asm volatile("wgmma.mma_async.sync.aligned.m64n128k16.f32.f16.f16 {%0,%1,%2,%3,%4,%5,%6,%7,%8,%9,%10,%11,%12,%13,%14,%15,%16,%17,%18,%19,%20,%21,%22,%23,%24,%25,%26,%27,%28,%29,%30,%31,%32,%33,%34,%35,%36,%37,%38,%39,%40,%41,%42,%43,%44,%45,%46,%47,%48,%49,%50,%51,%52,%53,%54,%55,%56,%57,%58,%59,%60,%61,%62,%63}, {%64,%65,%66,%67}, %68, 1, 1, 1, 0;\n"
                 : "+f"(acc[0][0]), "+f"(acc[0][1]), "+f"(acc[0][2]), "+f"(acc[0][3]), "+f"(acc[1][0]), "+f"(acc[1][1]), "+f"(acc[1][2]), "+f"(acc[1][3]), "+f"(acc[2][0]), "+f"(acc[2][1]), "+f"(acc[2][2]), "+f"(acc[2][3]), "+f"(acc[3][0]), "+f"(acc[3][1]), "+f"(acc[3][2]), "+f"(acc[3][3]), "+f"(acc[4][0]), "+f"(acc[4][1]), "+f"(acc[4][2]), "+f"(acc[4][3]), "+f"(acc[5][0]), "+f"(acc[5][1]), "+f"(acc[5][2]), "+f"(acc[5][3]), "+f"(acc[6][0]), "+f"(acc[6][1]), "+f"(acc[6][2]), "+f"(acc[6][3]), "+f"(acc[7][0]), "+f"(acc[7][1]), "+f"(acc[7][2]), "+f"(acc[7][3]), "+f"(acc[8][0]), "+f"(acc[8][1]), "+f"(acc[8][2]), "+f"(acc[8][3]), "+f"(acc[9][0]), "+f"(acc[9][1]), "+f"(acc[9][2]), "+f"(acc[9][3]), "+f"(acc[10][0]), "+f"(acc[10][1]), "+f"(acc[10][2]), "+f"(acc[10][3]), "+f"(acc[11][0]), "+f"(acc[11][1]), "+f"(acc[11][2]), "+f"(acc[11][3]), "+f"(acc[12][0]), "+f"(acc[12][1]), "+f"(acc[12][2]), "+f"(acc[12][3]), "+f"(acc[13][0]), "+f"(acc[13][1]), "+f"(acc[13][2]), "+f"(acc[13][3]), "+f"(acc[14][0]), "+f"(acc[14][1]), "+f"(acc[14][2]), "+f"(acc[14][3]), "+f"(acc[15][0]), "+f"(acc[15][1]), "+f"(acc[15][2]), "+f"(acc[15][3])
                 : "r"(a[0]), "r"(a[1]), "r"(a[2]), "r"(a[3]), "l"(desc));
}
template <> __device__ __forceinline__ void wg_mma<2>(float (&acc)[16][4], const uint32_t* a, uint64_t desc) {
    asm volatile("wgmma.mma_async.sync.aligned.m64n112k16.f32.f16.f16 {%0,%1,%2,%3,%4,%5,%6,%7,%8,%9,%10,%11,%12,%13,%14,%15,%16,%17,%18,%19,%20,%21,%22,%23,%24,%25,%26,%27,%28,%29,%30,%31,%32,%33,%34,%35,%36,%37,%38,%39,%40,%41,%42,%43,%44,%45,%46,%47,%48,%49,%50,%51,%52,%53,%54,%55}, {%56,%57,%58,%59}, %60, 1, 1, 1, 0;\n"
                 : "+f"(acc[2][0]), "+f"(acc[2][1]), "+f"(acc[2][2]), "+f"(acc[2][3]), "+f"(acc[3][0]), "+f"(acc[3][1]), "+f"(acc[3][2]), "+f"(acc[3][3]), "+f"(acc[4][0]), "+f"(acc[4][1]), "+f"(acc[4][2]), "+f"(acc[4][3]), "+f"(acc[5][0]), "+f"(acc[5][1]), "+f"(acc[5][2]), "+f"(acc[5][3]), "+f"(acc[6][0]), "+f"(acc[6][1]), "+f"(acc[6][2]), "+f"(acc[6][3]), "+f"(acc[7][0]), "+f"(acc[7][1]), "+f"(acc[7][2]), "+f"(acc[7][3]), "+f"(acc[8][0]), "+f"(acc[8][1]), "+f"(acc[8][2]), "+f"(acc[8][3]), "+f"(acc[9][0]), "+f"(acc[9][1]), "+f"(acc[9][2]), "+f"(acc[9][3]), "+f"(acc[10][0]), "+f"(acc[10][1]), "+f"(acc[10][2]), "+f"(acc[10][3]), "+f"(acc[11][0]), "+f"(acc[11][1]), "+f"(acc[11][2]), "+f"(acc[11][3]), "+f"(acc[12][0]), "+f"(acc[12][1]), "+f"(acc[12][2]), "+f"(acc[12][3]), "+f"(acc[13][0]), "+f"(acc[13][1]), "+f"(acc[13][2]), "+f"(acc[13][3]), "+f"(acc[14][0]), "+f"(acc[14][1]), "+f"(acc[14][2]), "+f"(acc[14][3]), "+f"(acc[15][0]), "+f"(acc[15][1]), "+f"(acc[15][2]), "+f"(acc[15][3])
                 : "r"(a[0]), "r"(a[1]), "r"(a[2]), "r"(a[3]), "l"(desc));
}
template <> __device__ __forceinline__ void wg_mma<4>(float (&acc)[16][4], const uint32_t* a, uint64_t desc) {
    asm volatile("wgmma.mma_async.sync.aligned.m64n96k16.f32.f16.f16 {%0,%1,%2,%3,%4,%5,%6,%7,%8,%9,%10,%11,%12,%13,%14,%15,%16,%17,%18,%19,%20,%21,%22,%23,%24,%25,%26,%27,%28,%29,%30,%31,%32,%33,%34,%35,%36,%37,%38,%39,%40,%41,%42,%43,%44,%45,%46,%47}, {%48,%49,%50,%51}, %52, 1, 1, 1, 0;\n"
                 : "+f"(acc[4][0]), "+f"(acc[4][1]), "+f"(acc[4][2]), "+f"(acc[4][3]), "+f"(acc[5][0]), "+f"(acc[5][1]), "+f"(acc[5][2]), "+f"(acc[5][3]), "+f"(acc[6][0]), "+f"(acc[6][1]), "+f"(acc[6][2]), "+f"(acc[6][3]), "+f"(acc[7][0]), "+f"(acc[7][1]), "+f"(acc[7][2]), "+f"(acc[7][3]), "+f"(acc[8][0]), "+f"(acc[8][1]), "+f"(acc[8][2]), "+f"(acc[8][3]), "+f"(acc[9][0]), "+f"(acc[9][1]), "+f"(acc[9][2]), "+f"(acc[9][3]), "+f"(acc[10][0]), "+f"(acc[10][1]), "+f"(acc[10][2]), "+f"(acc[10][3]), "+f"(acc[11][0]), "+f"(acc[11][1]), "+f"(acc[11][2]), "+f"(acc[11][3]), "+f"(acc[12][0]), "+f"(acc[12][1]), "+f"(acc[12][2]), "+f"(acc[12][3]), "+f"(acc[13][0]), "+f"(acc[13][1]), "+f"(acc[13][2]), "+f"(acc[13][3]), "+f"(acc[14][0]), "+f"(acc[14][1]), "+f"(acc[14][2]), "+f"(acc[14][3]), "+f"(acc[15][0]), "+f"(acc[15][1]), "+f"(acc[15][2]), "+f"(acc[15][3])
                 : "r"(a[0]), "r"(a[1]), "r"(a[2]), "r"(a[3]), "l"(desc));
}
template <> __device__ __forceinline__ void wg_mma<6>(float (&acc)[16][4], const uint32_t* a, uint64_t desc) {
    asm volatile("wgmma.mma_async.sync.aligned.m64n80k16.f32.f16.f16 {%0,%1,%2,%3,%4,%5,%6,%7,%8,%9,%10,%11,%12,%13,%14,%15,%16,%17,%18,%19,%20,%21,%22,%23,%24,%25,%26,%27,%28,%29,%30,%31,%32,%33,%34,%35,%36,%37,%38,%39}, {%40,%41,%42,%43}, %44, 1, 1, 1, 0;\n"
                 : "+f"(acc[6][0]), "+f"(acc[6][1]), "+f"(acc[6][2]), "+f"(acc[6][3]), "+f"(acc[7][0]), "+f"(acc[7][1]), "+f"(acc[7][2]), "+f"(acc[7][3]), "+f"(acc[8][0]), "+f"(acc[8][1]), "+f"(acc[8][2]), "+f"(acc[8][3]), "+f"(acc[9][0]), "+f"(acc[9][1]), "+f"(acc[9][2]), "+f"(acc[9][3]), "+f"(acc[10][0]), "+f"(acc[10][1]), "+f"(acc[10][2]), "+f"(acc[10][3]), "+f"(acc[11][0]), "+f"(acc[11][1]), "+f"(acc[11][2]), "+f"(acc[11][3]), "+f"(acc[12][0]), "+f"(acc[12][1]), "+f"(acc[12][2]), "+f"(acc[12][3]), "+f"(acc[13][0]), "+f"(acc[13][1]), "+f"(acc[13][2]), "+f"(acc[13][3]), "+f"(acc[14][0]), "+f"(acc[14][1]), "+f"(acc[14][2]), "+f"(acc[14][3]), "+f"(acc[15][0]), "+f"(acc[15][1]), "+f"(acc[15][2]), "+f"(acc[15][3])
                 : "r"(a[0]), "r"(a[1]), "r"(a[2]), "r"(a[3]), "l"(desc));
}
template <> __device__ __forceinline__ void wg_mma<8>(float (&acc)[16][4], const uint32_t* a, uint64_t desc) {
    asm volatile("wgmma.mma_async.sync.aligned.m64n64k16.f32.f16.f16 {%0,%1,%2,%3,%4,%5,%6,%7,%8,%9,%10,%11,%12,%13,%14,%15,%16,%17,%18,%19,%20,%21,%22,%23,%24,%25,%26,%27,%28,%29,%30,%31}, {%32,%33,%34,%35}, %36, 1, 1, 1, 0;\n"
                 : "+f"(acc[8][0]), "+f"(acc[8][1]), "+f"(acc[8][2]), "+f"(acc[8][3]), "+f"(acc[9][0]), "+f"(acc[9][1]), "+f"(acc[9][2]), "+f"(acc[9][3]), "+f"(acc[10][0]), "+f"(acc[10][1]), "+f"(acc[10][2]), "+f"(acc[10][3]), "+f"(acc[11][0]), "+f"(acc[11][1]), "+f"(acc[11][2]), "+f"(acc[11][3]), "+f"(acc[12][0]), "+f"(acc[12][1]), "+f"(acc[12][2]), "+f"(acc[12][3]), "+f"(acc[13][0]), "+f"(acc[13][1]), "+f"(acc[13][2]), "+f"(acc[13][3]), "+f"(acc[14][0]), "+f"(acc[14][1]), "+f"(acc[14][2]), "+f"(acc[14][3]), "+f"(acc[15][0]), "+f"(acc[15][1]), "+f"(acc[15][2]), "+f"(acc[15][3])
                 : "r"(a[0]), "r"(a[1]), "r"(a[2]), "r"(a[3]), "l"(desc));
}
template <> __device__ __forceinline__ void wg_mma<10>(float (&acc)[16][4], const uint32_t* a, uint64_t desc) {
    asm volatile("wgmma.mma_async.sync.aligned.m64n48k16.f32.f16.f16 {%0,%1,%2,%3,%4,%5,%6,%7,%8,%9,%10,%11,%12,%13,%14,%15,%16,%17,%18,%19,%20,%21,%22,%23}, {%24,%25,%26,%27}, %28, 1, 1, 1, 0;\n"
                 : "+f"(acc[10][0]), "+f"(acc[10][1]), "+f"(acc[10][2]), "+f"(acc[10][3]), "+f"(acc[11][0]), "+f"(acc[11][1]), "+f"(acc[11][2]), "+f"(acc[11][3]), "+f"(acc[12][0]), "+f"(acc[12][1]), "+f"(acc[12][2]), "+f"(acc[12][3]), "+f"(acc[13][0]), "+f"(acc[13][1]), "+f"(acc[13][2]), "+f"(acc[13][3]), "+f"(acc[14][0]), "+f"(acc[14][1]), "+f"(acc[14][2]), "+f"(acc[14][3]), "+f"(acc[15][0]), "+f"(acc[15][1]), "+f"(acc[15][2]), "+f"(acc[15][3])
                 : "r"(a[0]), "r"(a[1]), "r"(a[2]), "r"(a[3]), "l"(desc));
}
template <> __device__ __forceinline__ void wg_mma<12>(float (&acc)[16][4], const uint32_t* a, uint64_t desc) {
    asm volatile("wgmma.mma_async.sync.aligned.m64n32k16.f32.f16.f16 {%0,%1,%2,%3,%4,%5,%6,%7,%8,%9,%10,%11,%12,%13,%14,%15}, {%16,%17,%18,%19}, %20, 1, 1, 1, 0;\n"
                 : "+f"(acc[12][0]), "+f"(acc[12][1]), "+f"(acc[12][2]), "+f"(acc[12][3]), "+f"(acc[13][0]), "+f"(acc[13][1]), "+f"(acc[13][2]), "+f"(acc[13][3]), "+f"(acc[14][0]), "+f"(acc[14][1]), "+f"(acc[14][2]), "+f"(acc[14][3]), "+f"(acc[15][0]), "+f"(acc[15][1]), "+f"(acc[15][2]), "+f"(acc[15][3])
                 : "r"(a[0]), "r"(a[1]), "r"(a[2]), "r"(a[3]), "l"(desc));
}
template <> __device__ __forceinline__ void wg_mma<14>(float (&acc)[16][4], const uint32_t* a, uint64_t desc) {
    asm volatile("wgmma.mma_async.sync.aligned.m64n16k16.f32.f16.f16 {%0,%1,%2,%3,%4,%5,%6,%7}, {%8,%9,%10,%11}, %12, 1, 1, 1, 0;\n"
                 : "+f"(acc[14][0]), "+f"(acc[14][1]), "+f"(acc[14][2]), "+f"(acc[14][3]), "+f"(acc[15][0]), "+f"(acc[15][1]), "+f"(acc[15][2]), "+f"(acc[15][3])
                 : "r"(a[0]), "r"(a[1]), "r"(a[2]), "r"(a[3]), "l"(desc));
}
template <> __device__ __forceinline__ void wg_first<0>(float (&acc)[16][4], const uint32_t* a, uint64_t desc) {
    asm volatile("wgmma.mma_async.sync.aligned.m64n128k16.f32.f16.f16 {%0,%1,%2,%3,%4,%5,%6,%7,%8,%9,%10,%11,%12,%13,%14,%15,%16,%17,%18,%19,%20,%21,%22,%23,%24,%25,%26,%27,%28,%29,%30,%31,%32,%33,%34,%35,%36,%37,%38,%39,%40,%41,%42,%43,%44,%45,%46,%47,%48,%49,%50,%51,%52,%53,%54,%55,%56,%57,%58,%59,%60,%61,%62,%63}, {%64,%65,%66,%67}, %68, 0, 1, 1, 0;\n"
                 : "=f"(acc[0][0]), "=f"(acc[0][1]), "=f"(acc[0][2]), "=f"(acc[0][3]), "=f"(acc[1][0]), "=f"(acc[1][1]), "=f"(acc[1][2]), "=f"(acc[1][3]), "=f"(acc[2][0]), "=f"(acc[2][1]), "=f"(acc[2][2]), "=f"(acc[2][3]), "=f"(acc[3][0]), "=f"(acc[3][1]), "=f"(acc[3][2]), "=f"(acc[3][3]), "=f"(acc[4][0]), "=f"(acc[4][1]), "=f"(acc[4][2]), "=f"(acc[4][3]), "=f"(acc[5][0]), "=f"(acc[5][1]), "=f"(acc[5][2]), "=f"(acc[5][3]), "=f"(acc[6][0]), "=f"(acc[6][1]), "=f"(acc[6][2]), "=f"(acc[6][3]), "=f"(acc[7][0]), "=f"(acc[7][1]), "=f"(acc[7][2]), "=f"(acc[7][3]), "=f"(acc[8][0]), "=f"(acc[8][1]), "=f"(acc[8][2]), "=f"(acc[8][3]), "=f"(acc[9][0]), "=f"(acc[9][1]), "=f"(acc[9][2]), "=f"(acc[9][3]), "=f"(acc[10][0]), "=f"(acc[10][1]), "=f"(acc[10][2]), "=f"(acc[10][3]), "=f"(acc[11][0]), "=f"(acc[11][1]), "=f"(acc[11][2]), "=f"(acc[11][3]), "=f"(acc[12][0]), "=f"(acc[12][1]), "=f"(acc[12][2]), "=f"(acc[12][3]), "=f"(acc[13][0]), "=f"(acc[13][1]), "=f"(acc[13][2]), "=f"(acc[13][3]), "=f"(acc[14][0]), "=f"(acc[14][1]), "=f"(acc[14][2]), "=f"(acc[14][3]), "=f"(acc[15][0]), "=f"(acc[15][1]), "=f"(acc[15][2]), "=f"(acc[15][3])
                 : "r"(a[0]), "r"(a[1]), "r"(a[2]), "r"(a[3]), "l"(desc));
}
template <> __device__ __forceinline__ void wg_first<4>(float (&acc)[16][4], const uint32_t* a, uint64_t desc) {
    asm volatile("wgmma.mma_async.sync.aligned.m64n96k16.f32.f16.f16 {%0,%1,%2,%3,%4,%5,%6,%7,%8,%9,%10,%11,%12,%13,%14,%15,%16,%17,%18,%19,%20,%21,%22,%23,%24,%25,%26,%27,%28,%29,%30,%31,%32,%33,%34,%35,%36,%37,%38,%39,%40,%41,%42,%43,%44,%45,%46,%47}, {%48,%49,%50,%51}, %52, 0, 1, 1, 0;\n"
                 : "=f"(acc[4][0]), "=f"(acc[4][1]), "=f"(acc[4][2]), "=f"(acc[4][3]), "=f"(acc[5][0]), "=f"(acc[5][1]), "=f"(acc[5][2]), "=f"(acc[5][3]), "=f"(acc[6][0]), "=f"(acc[6][1]), "=f"(acc[6][2]), "=f"(acc[6][3]), "=f"(acc[7][0]), "=f"(acc[7][1]), "=f"(acc[7][2]), "=f"(acc[7][3]), "=f"(acc[8][0]), "=f"(acc[8][1]), "=f"(acc[8][2]), "=f"(acc[8][3]), "=f"(acc[9][0]), "=f"(acc[9][1]), "=f"(acc[9][2]), "=f"(acc[9][3]), "=f"(acc[10][0]), "=f"(acc[10][1]), "=f"(acc[10][2]), "=f"(acc[10][3]), "=f"(acc[11][0]), "=f"(acc[11][1]), "=f"(acc[11][2]), "=f"(acc[11][3]), "=f"(acc[12][0]), "=f"(acc[12][1]), "=f"(acc[12][2]), "=f"(acc[12][3]), "=f"(acc[13][0]), "=f"(acc[13][1]), "=f"(acc[13][2]), "=f"(acc[13][3]), "=f"(acc[14][0]), "=f"(acc[14][1]), "=f"(acc[14][2]), "=f"(acc[14][3]), "=f"(acc[15][0]), "=f"(acc[15][1]), "=f"(acc[15][2]), "=f"(acc[15][3])
                 : "r"(a[0]), "r"(a[1]), "r"(a[2]), "r"(a[3]), "l"(desc));
}

#define SDLY 1500
#define UDLY 1400
#define KDLY 850
#define FDLY 950
#define FDLY2 350
#define DDLY 450
#define WDLY 500
#define HW 15
#define FIX(v) do { if ((v) == 1u) TRAP(); } while (0)
#define STAMPW(i) STAMPY(i)
#define STAMP2(i) STAMP(i)
#undef STAMPX
#define STAMPX(i)
struct Params {
    const bf16 *x, *lar, *aim, *cre, *cim, *ldt, *dsk;
    Scratch* s;
    const bf16* wr;
    bf16* out;
};
struct Maps { CUtensorMap x, w[2], r[2], d; };

#define TOK(g) (2 * (g) - ((g) & 1))
#define ROWTOK(r) (TOK((r) & 7) + (((r) >> 2) & 2))
__device__ __forceinline__ void ln_partial(const uint32_t (&H)[2][4], float (&d)[2][4]) {
#pragma unroll
    for (int i = 0; i < 8; i++) d[i >> 2][i & 3] = 0.f;
#pragma unroll
    for (int k = 0; k < 4; k++)
#pragma unroll
        for (int hf = 0; hf < 2; hf++) mma_bf16_k8(d[hf], H[hf][k], 0x3f803f80u, H[hf][k]);
}
__device__ __forceinline__ float sum18(uint32_t a) {
    const uint4 p = lds128(a), q = lds128(a + 16), r = lds128(a + 32), s = lds128(a + 48);
    const uint2 u = lds64(a + 64);
#define F(x) __uint_as_float(x)
    return (((F(p.x) + F(p.y)) + (F(p.z) + F(p.w))) + ((F(q.x) + F(q.y)) + (F(q.z) + F(q.w)))) +
           (((F(r.x) + F(r.y)) + (F(r.z) + F(r.w))) + ((F(s.x) + F(s.y)) + (F(s.z) + F(s.w))) + (F(u.x) + F(u.y)));
#undef F
}
__device__ __forceinline__ void ln_stats(float sm, float sq, float& mb, float& sd) {
    const float m0 = sm * (1.0f / 576.0f);
    const float mean = fmaf(fmaf(-m0, 576.0f, sm), 1.0f / 576.0f, m0);
    const float var = fmaxf(fmaf(-mean, mean, sq * (1.0f / 576.0f)), 0.f);
    mb = rbf(mean);
    sd = rbf(sqrt_approx(rbf(rbf(var) + 1e-5f)));
}
__device__ __forceinline__ void ln_finish(float v, int lane, float& mb, float& rc) {
    const float o = __shfl_xor_sync(0xffffffffu, v, 16);
    float sd;
    ln_stats(lane < 16 ? v : o, lane < 16 ? o : v, mb, sd);
    rc = rcp_approx(sd);
}
__device__ __forceinline__ uint32_t ln_apply(uint32_t w, uint32_t m2, uint32_t rh, uint32_t rl) {
    const uint32_t d = hsub2_bf(w, m2);
    return hfma2_bf(d, rh, hmul2_bf(d, rl));
}
__device__ __forceinline__ void stat_store(uint32_t a, float mb, float rc, uint32_t extra) {
    const float rh = rbf(rc);
    sts64(a, (__float_as_uint(mb) >> 16) | (extra << 16), pack_bf16(rh, rc - rh));
}
#define STAT_M(s) __byte_perm((s).x, (s).x, 0x1010)
#define STAT_H(s) __byte_perm((s).y, (s).y, 0x1010)
#define STAT_L(s) __byte_perm((s).y, (s).y, 0x3232)

__device__ __forceinline__ void hcmul(uint32_t re, uint32_t im, uint32_t zx, uint32_t zy, uint32_t& ore, uint32_t& oim) {
    ore = hfms2(im, zy, hmul2(re, zx));
    oim = hfma2(re, zy, hmul2(im, zx));
}

struct KGen {
    uint32_t A[2][4][4];
    float2 z1, z8, z64, z128, T[9];
};
__device__ __forceinline__ void kgen_setup(KGen& k, float lar, float aim, float dt) {
    const float lr2 = -(exp_bf(lar) * dt) * 1.4426950408889634f, li = aim * dt;
    k.z1 = cexp_e(lr2, li, 1.0f);
    k.z8 = cexp_e(lr2, li, 8.0f);
    k.z64 = cexp_e(lr2, li, 64.0f);
}
__device__ __forceinline__ void kgen_rows(KGen& k, uint32_t tb, int lane) {
    const float2 z8 = k.z8, z64 = k.z64;
    const uint32_t row = tb + lane * 16;
    k.z128 = csq(z64);
    const float2 z16 = csq(z8), z24 = cmul(z16, z8), z32 = csq(z16), z40 = cmul(z32, z8), z48 = csq(z24), z56 = cmul(z32, z24);
    uint32_t re[4], im[4], a[4], b[4];
    re[0] = pack_f16(1.0f, z8.x); im[0] = pack_f16(0.0f, z8.y);
    re[1] = pack_f16(z16.x, z24.x); im[1] = pack_f16(z16.y, z24.y);
    re[2] = pack_f16(z32.x, z40.x); im[2] = pack_f16(z32.y, z40.y);
    re[3] = pack_f16(z48.x, z56.x); im[3] = pack_f16(z48.y, z56.y);
    sts128(row, re[0], re[1], re[2], re[3]);
    sts128(row + 1024, im[0], im[1], im[2], im[3]);
    const uint32_t zx = pack_f16(z64.x, z64.x), zy = pack_f16(z64.y, z64.y), zw = pack_f16(k.z128.x, k.z128.y);
#pragma unroll
    for (int j = 0; j < 4; j++) hcmul(re[j], im[j], zx, zy, a[j], b[j]);
    sts128(row + 512, a[0], a[1], a[2], a[3]);
    sts128(row + 1536, b[0], b[1], b[2], b[3]);
    const int mi = lane >> 3;
    const uint32_t zd = tb + 2048 + mi * 16;
    sts16(tb + 2048 + lane * 2, zw); sts16(tb + 2112 + lane * 2, zw >> 16);
    __syncwarp();
    const uint32_t ad = tb + (lane & 7) * 16 + mi * 512;
    ldsm_x4(a[0], a[1], a[2], a[3], zd);
    ldsm_x4(b[0], b[1], b[2], b[3], zd + 64);
#pragma unroll
    for (int ks = 0; ks < 4; ks++) {
        ldsm_x4_t(k.A[0][ks][0], k.A[0][ks][1], k.A[0][ks][2], k.A[0][ks][3], ad + ks * 128);
        hcmul(k.A[0][ks][0], k.A[0][ks][2], a[ks], b[ks], k.A[1][ks][0], k.A[1][ks][2]);
        hcmul(k.A[0][ks][1], k.A[0][ks][3], a[ks], b[ks], k.A[1][ks][1], k.A[1][ks][3]);
    }
}
__device__ __forceinline__ void kgen_chain(KGen& k, uint32_t cr, uint32_t ci, float cs) {
    k.T[0] = make_float2(bf_lo(cr) * cs, -bf_lo(ci) * cs);
    const float2 y1 = make_float2(k.z1.x, -k.z1.y);
#pragma unroll
    for (int c = 1; c < 8; c++) k.T[c] = cmul(k.T[c - 1], y1);
    k.T[8] = cmul(k.T[0], make_float2(k.z8.x, -k.z8.y));
}
__device__ __forceinline__ void kgen_cols(KGen& k, uint32_t tb, uint32_t t5, int lane) {
    const uint32_t row = tb + lane * 16;
    const float2 (&T)[9] = k.T;
    const float2 y128 = make_float2(k.z128.x, -k.z128.y);
    const float2 y256 = csq(y128), y512 = csq(y256), y768 = cmul(y512, y256), y1024 = csq(y512);
    const float2 c1032 = cmul(T[8], y1024);
    __syncwarp();
    sts128(row, pack_f16(T[0].x, T[1].x), pack_f16(T[2].x, T[3].x), pack_f16(T[4].x, T[5].x), pack_f16(T[6].x, T[7].x));
    sts128(row + 512, pack_f16(T[0].y, T[1].y), pack_f16(T[2].y, T[3].y), pack_f16(T[4].y, T[5].y), pack_f16(T[6].y, T[7].y));
    uint32_t a[4], b[4];
    {
        const uint32_t zx = pack_f16(y256.x, y256.x), zy = pack_f16(y256.y, y256.y);
        hcmul(pack_f16(T[0].x, T[2].x), pack_f16(T[0].y, T[2].y), zx, zy, a[0], b[0]);
        hcmul(pack_f16(T[4].x, T[6].x), pack_f16(T[4].y, T[6].y), zx, zy, a[1], b[1]);
        const uint32_t r04 = pack_f16(T[0].x, T[4].x), i04 = pack_f16(T[0].y, T[4].y);
        hcmul(r04, i04, pack_f16(y512.x, y512.x), pack_f16(y512.y, y512.y), a[2], b[2]);
        hcmul(r04, i04, pack_f16(y768.x, y768.x), pack_f16(y768.y, y768.y), a[3], b[3]);
    }
    sts128(row + 1024, a[0], a[1], a[2], a[3]);
    sts128(row + 1536, b[0], b[1], b[2], b[3]);
    {
        const uint32_t r0 = pack_f16(1.0f, y256.x), i0 = pack_f16(0.0f, y256.y), r1 = pack_f16(y512.x, y768.x), i1 = pack_f16(y512.y, y768.y);
        const uint32_t zx = pack_f16(T[8].x, T[8].x), zy = pack_f16(T[8].y, T[8].y), wx = pack_f16(c1032.x, c1032.x), wy = pack_f16(c1032.y, c1032.y);
        hcmul(r0, i0, zx, zy, a[0], b[0]); hcmul(r1, i1, zx, zy, a[1], b[1]);
        hcmul(r0, i0, wx, wy, a[2], b[2]); hcmul(r1, i1, wx, wy, a[3], b[3]);
    }
    sts128(row + 2048, a[0], a[1], a[2], a[3]);
    sts128(t5 + lane * 16, b[0], b[1], b[2], b[3]);
}
__device__ __forceinline__ void kgen_mma(const KGen& k, uint32_t tb, uint32_t t5, int lane) {
    __syncwarp();
    float acc[2][3][4];
#pragma unroll
    for (int i = 0; i < 6; i++)
#pragma unroll
        for (int j = 0; j < 4; j++) acc[i / 3][i % 3][j] = 0.f;
    const int mi = lane >> 3;
    const uint32_t ro = ((lane & 7) + 8 * (mi >> 1)) * 16, bd = tb + ro + (mi & 1) * 512, b2 = ro + ((mi & 1) ? t5 : tb + 2048);
#pragma unroll
    for (int kp = 0; kp < 2; kp++)
#pragma unroll
        for (int j = 0; j < 3; j++) {
            uint32_t b[4];
            ldsm_x4_t(b[0], b[1], b[2], b[3], (j < 2 ? bd + j * 1024 : b2) + kp * 256);
#pragma unroll
            for (int h = 0; h < 2; h++)
#pragma unroll
                for (int m = 0; m < 2; m++) {
                    const uint32_t (&A)[4] = k.A[m][2 * kp + h];
                    mma_f16(acc[m][j], A[0], A[1], A[2], A[3], b[2 * h], b[2 * h + 1]);
                }
        }
    __syncwarp();
#define PK(j) pack_f16(acc[0][j][0], acc[0][j][1]), pack_f16(acc[0][j][2], acc[0][j][3]), pack_f16(acc[1][j][0], acc[1][j][1]), pack_f16(acc[1][j][2], acc[1][j][3])
    stsm_x4(tb + lane * 16, PK(0));
    stsm_x4(tb + 512 + lane * 16, PK(1));
    stsm_x4_t(tb + 1024 + (lane & 7) * 80 + mi * 16, PK(2));
#undef PK
}
__device__ __forceinline__ uint32_t table_buf(uint32_t sb, int warp) { return sb + SM_PL + warp * TBW; }

__device__ __forceinline__ uint4 lds16x4(uint32_t a) { return make_uint4(lds16(a), lds16(a + TBW), lds16(a + 2 * TBW), lds16(a + 3 * TBW)); }
__device__ __forceinline__ void combine_setup(uint32_t sb, int warp, int lane, uint32_t kw, uint32_t& o, uint32_t& n, uint32_t& d) {
    const int wq = warp & 3;
    const uint32_t a = table_buf(sb, warp & ~3);
    o = wq == 3 ? a + 1024 + 320 + (lane >> 3) * 80 + (lane & 7) * 8 : a + (wq ? 504 + wq * 8 : 0) + lane * 16;
    n = a + 1024 + wq * 80 + lane * 2;
    d = wq < 3 ? kw + (wq == 2 ? KW_P : 32 + wq * 512) + lane * 16 : kw + KW_H + 8 + lane * 8;
}
__device__ __forceinline__ void kgen_combine(int wq, int lane, uint32_t o, uint32_t na, uint32_t d) {
#define S4(f) hadd2(hadd2(u.f, v.f), hadd2(w.f, x.f))
#define H4(v) hadd2(hadd2(v.x, v.y), hadd2(v.z, v.w))
#define BP __byte_perm
    if (wq == 0) {
        const uint4 u = lds128(o), v = lds128(o + TBW), w = lds128(o + 2 * TBW), x = lds128(o + 3 * TBW), nn = lds16x4(na);
        const uint32_t n = H4(nn), k0 = S4(x), k2 = S4(y), k4 = S4(z), k6 = S4(w);
        sts128(d, BP(k0, k0, 0x1032), BP(k0, k2, 0x3254), BP(k2, k2, 0x1032), BP(k2, k4, 0x3254));
        sts128(d + KW_PL, BP(k4, k4, 0x1032), BP(k4, k6, 0x3254), BP(k6, k6, 0x1032), BP(k6, n, 0x3254));
        if (lane == 0) sts32(d + KW_PL - 4, k0 & 0xffffu);
    } else {
        const uint2 u = lds64(o), v = lds64(o + TBW), w = lds64(o + 2 * TBW), x = lds64(o + 3 * TBW);
        uint4 nn = make_uint4(0u, 0u, 0u, 0u), mm = nn;
        if (wq < 3) nn = lds16x4(na);
        if (wq == 2) mm = lds16x4(na + 80);
        const uint32_t k0 = S4(x), k2 = S4(y), n = H4(nn), m = H4(mm);
        if (wq == 3) {
            sts64(d, k0, k2);
        } else if (wq == 1) {
            const uint32_t cc = BP(k2, k2, 0x1010);
            sts128(d, BP(k0, k0, 0x1010), BP(k0, k0, 0x1032), BP(k0, k2, 0x3254), cc);
            sts128(d + KW_PL, cc, BP(k2, k2, 0x1032), BP(k2, n, 0x3254), BP(n, n, 0x1010));
        } else {
            const uint32_t w40 = BP(k0, k0, 0x1032), w84 = BP(k0, n, 0x3254), w0 = BP(k0, k0, 0x1010), w4 = BP(k0, k0, 0x3232), w8 = BP(n, n, 0x1010);
            sts64(d, w40, w84);
            sts64(d + 512, BP(k2, k2, 0x1032), BP(k2, m, 0x3254));
            if (lane < 8) { sts128(d - (KW_P - 1056), w0, w0, w40, w4); sts128(d - (KW_P - 1056 - KW_PL), w4, w84, w8, w8); }
            if (lane == 31) sts16(d + (KW_H + 6 - KW_P - 496), m);
        }
    }
#undef S4
#undef H4
#undef BP
}

__device__ __forceinline__ int c_exponent(const uint2& r, const uint2& i, float dt) {
    const uint32_t mx = __vmaxu2(__vmaxu2(r.x & 0x7fff7fffu, r.y & 0x7fff7fffu), __vmaxu2(i.x & 0x7fff7fffu, i.y & 0x7fff7fffu));
    return __reduce_max_sync(0xffffffffu, max(mx, mx << 16) + (__float_as_uint(dt) & 0x7f800000u)) >> 23;
}

__device__ __forceinline__ int lane_v() { int l; asm volatile("mov.u32 %0, %%laneid;" : "=r"(l)); return l; }
__device__ __forceinline__ uint32_t prmt_v(uint32_t a, uint32_t b, uint32_t s) { uint32_t d; asm volatile("prmt.b32 %0, %1, %2, %3;\n" : "=r"(d) : "r"(a), "r"(b), "r"(s)); return d; }
__device__ __forceinline__ uint32_t mov_v(uint32_t a) { uint32_t d; asm volatile("mov.b32 %0, %1;\n" : "=r"(d) : "r"(a)); return d; }
template <int G>
__device__ __forceinline__ void conv_rename(float (&acc)[16][4]) {
#pragma unroll
    for (int i = G; i < 16; i++)
#pragma unroll
        for (int j = 0; j < 4; j++) { float v; asm volatile("mov.b32 %0, %1;\n" : "=f"(v) : "f"(acc[i][j])); acc[i][j] = v; }
}
struct Conv {
    uint32_t kw;
    uint32_t wa;
    uint32_t pa, s2;
    uint32_t s8;
    uint32_t id;
    uint32_t lc;
    uint32_t fs;
    uint32_t fl, yo;
    uint32_t yp;
    size_t ycopy;
    uint32_t ps;
    uint64_t d0;
    int warp;
};
struct Pk { uint32_t w[4]; };
__device__ __forceinline__ Pk pk2(const float (&u)[4], const float (&v)[4]) {
    Pk r;
    r.w[0] = pack_f16(u[0], u[1]); r.w[1] = pack_f16(u[2], u[3]); r.w[2] = pack_f16(v[0], v[1]); r.w[3] = pack_f16(v[2], v[3]);
    return r;
}
__device__ __forceinline__ void park(uint32_t a, const Pk& v) {
    asm volatile("stmatrix.sync.aligned.m8n8.x4.trans.shared.b16 [%0], {%1,%2,%3,%4};\n" ::"r"(a), "r"(v.w[0]), "r"(v.w[1]), "r"(v.w[2]), "r"(v.w[3]) : "memory");
}
__device__ __forceinline__ void conv_constants(uint32_t lc, int l) {
    const int d = (l >> 2) - 2 * (l & 3);
    const int e = d + 8, r4 = (e + 1 + ((e >> 2) & 1)) >> 2, p4 = (e + (((e - 1) >> 2) & 1)) >> 2;
    const uint32_t s2 = r4 == p4 ? 0x1010u : 0x3210u;
    sts64(lc + l * 8, KW_P + ((r4 - 5) >> 1) * 16 + ((r4 - 5) & 1) * 4, s2 | ((d < 0 ? s2 : 0x7654u) << 16));
    const int lo = (d >= 4) - (d < -3), ho = (d >= 5) - (d < -2), le = (d > 4) - (d < -4), he = (d > 5) - (d < -3);
    sts32(lc + 512 + l * 8, (0x5454u + lo * 0x22 + ho * 0x2200) | ((0x3232u + le * 0x22 + he * 0x2200) << 16));
    const int cc = l >> 2, j = l & 3;
    sts64(lc + 256 + l * 8, (j >> 1) * PL_HALF + (16 + cc) * 16 + (j & 1) * 8, (cc >> 1) * (DM * 64) + (cc & 1) * 32 + j * 8);
}
__device__ __forceinline__ void conv_selectors4(Conv& c) {
    const uint2 v = lds64(c.lc + lane_v() * 8);
    c.pa = v.x; c.s2 = v.y;
}
__device__ __forceinline__ void conv_selectors8(Conv& c) { c.s8 = lds32(c.lc + 512 + lane_v() * 8); }
template <int G, int I0, int I1>
__device__ __forceinline__ void conv_load(const Conv& c, uint32_t (&q)[9]) {
    const int wq = c.warp & 3;
    if (G < 2) {
#pragma unroll
        for (int i = I0; i < I1; i++) q[i] = lds32(c.wa + G * 512 + i * 16);
    } else if (G < 4) {
        const uint32_t a = (G == 2 && wq == 0) ? c.wa + 1024 : c.pa + c.kw + wq * 128 + (G < 2 ? 0 : G - 2) * 512;
#pragma unroll
        for (int i = I0; i < I1; i++) q[i] = lds32(a + i * 16);
    } else {
        const uint4 u = lds128(c.kw + KW_H + (G < 4 ? 0 : G - 4) * 64 + wq * 16);
        const uint2 v = lds64(c.kw + KW_H + (G < 4 ? 0 : G - 4) * 64 + wq * 16 + 16);
        q[0] = u.x; q[1] = u.y; q[2] = u.z; q[3] = u.w; q[4] = v.x; q[5] = v.y;
        if (G == 4 && wq == 0) { q[6] = lds32(c.pa + c.kw + 1024); q[7] = lds32(c.pa + c.kw + 1040); }
    }
}
template <int G, int J0, int J1>
__device__ __forceinline__ void conv_frag(const Conv& c, const uint32_t (&q)[9], uint32_t* a, const Pk& dp) {
    const uint32_t dep = dp.w[0];
    if (G < 4) {
        const uint32_t s = (G < 2 || (G == 2 && (c.warp & 3) == 0)) ? c.id : c.s2;
#pragma unroll
        for (int j = J0; j < J1; j++) {
            uint32_t* o = a + 4 * (j - J0);
            o[0] = prmt_v(q[2 * j + 1], dp.w[0], s); o[1] = prmt_v(q[2 * j + 2], dp.w[1], s); o[2] = prmt_v(q[2 * j], dp.w[2], s); o[3] = prmt_v(q[2 * j + 1], dp.w[3], s);
        }
    } else {
        const uint32_t so = prmt_v(c.s8, dep, c.id), se = prmt_v(c.s8, dep, c.id + 0x22);
#pragma unroll
        for (int j = J0; j < J1; j++) {
            uint32_t* o = a + 4 * (j - J0);
            o[0] = prmt_v(q[j + 1], q[j + 2], se); o[1] = prmt_v(q[j + 1], q[j + 2], so); o[2] = prmt_v(q[j], q[j + 1], so);
            if (G == 4 && j == 0 && (c.warp & 3) == 0) {
                o[2] = prmt_v(q[6], dep, c.s2);
                o[0] = prmt_v(q[7], o[0], c.s2 >> 16);
            }
            o[3] = mov_v(o[0]);
        }
    }
}
template <int G, int J0, int J1>
__device__ __forceinline__ void conv_frag(const Conv& c, const uint32_t (&q)[9], uint32_t* a, float depf) {
    const uint32_t d = __float_as_uint(depf);
    conv_frag<G, J0, J1>(c, q, a, Pk{{d, d, d, d}});
}
template <int G, int T, int J0, int J1>
__device__ __forceinline__ void conv_mma(float (&acc)[16][4], const Conv& c, const uint32_t* a) {
#pragma unroll
    for (int j = J0; j < J1; j++) wg_mma<T>(acc, a + 4 * (j - J0), c.d0 - 8 * (2 * G - T) - j);
}
__device__ __forceinline__ float h_lo(uint32_t w) { return __half2float(__ushort_as_half((unsigned short)(w & 0xffffu))); }
__device__ __forceinline__ float h_hi(uint32_t w) { return __half2float(__ushort_as_half((unsigned short)(w >> 16))); }
__device__ __forceinline__ void flush_setup(Conv& c) {
    const uint2 v = lds64(c.lc + 256 + lane_v() * 8);
    c.fl = v.x; c.yo = v.y;
}
template <int Q>
__device__ __forceinline__ void flush_load(const Conv& c, uint32_t pl, uint2 (&f)[4]) {
#pragma unroll
    for (int w = 0; w < 4; w++) f[w] = lds64(c.fl + pl + (Q & 1) * 512 + w * (PLW_B - 64));
}
template <int Q>
__device__ __forceinline__ void flush_load_first(const Conv& c, uint32_t pl, uint2 (&f)[4], float depf) {
    const uint32_t p = prmt_v(c.fl, __float_as_uint(depf), c.id) + pl + (Q & 1) * 512;
#define LDV64(d, a) asm volatile("ld.volatile.shared.v2.u32 {%0,%1}, [%2];\n" : "=r"(d.x), "=r"(d.y) : "r"(a) : "memory")
    LDV64(f[0], p); LDV64(f[1], p + (PLW_B - 64)); LDV64(f[2], p + 2 * (PLW_B - 64)); LDV64(f[3], p + 3 * (PLW_B - 64));
}
#define FDEP __uint_as_float(f[3].y)
template <int Q, int mode>
__device__ __forceinline__ void conv_flush(const Conv& c, const uint2 (&f)[4], unsigned char* gy, uint32_t rx) {
    const uint32_t a0 = hadd2(f[0].x, f[1].x), a1 = hadd2(f[2].x, f[3].x), b0 = hadd2(f[0].y, f[1].y), b1 = hadd2(f[2].y, f[3].y);
    if (Q > 0 && mode == 1) {
        const uint32_t ra = rx + 16 + (Q > 0 ? Q - 1 : 0) * 1024 + (c.warp & 3) * 256 + lane_v() * 8;
        asm volatile("st.async.shared::cluster.mbarrier::complete_tx::bytes.v2.b32 [%0], {%1,%2}, [%3];\n"
                     ::"r"(ra ^ 0x1000000u), "r"(hadd2(a0, a1)), "r"(hadd2(b0, b1)), "r"((rx + (Q > 1 ? 8 : 0)) ^ 0x1000000u) : "memory");
        return;
    }
    float v0 = h_lo(a0) + h_lo(a1), v1 = h_hi(a0) + h_hi(a1), v2 = h_lo(b0) + h_lo(b1), v3 = h_hi(b0) + h_hi(b1);
    if (Q > 0 && mode == 2) {
        const uint2 o = lds64(rx + 16 + (Q > 0 ? Q - 1 : 0) * 1024 + (c.warp & 3) * 256 + lane_v() * 8);
        v0 += h_lo(o.x); v1 += h_hi(o.x); v2 += h_lo(o.y); v3 += h_hi(o.y);
    }
    const uint32_t lo = hmul2_bf(pack_bf16(v0, v1), c.fs), hi = hmul2_bf(pack_bf16(v2, v3), c.fs);
    stg64(gy + Q * 32 * DM * 32 + (c.yo + (Q < 2 ? c.yp : 0u)), nzw(lo), nzw(hi));
}
template <int I, bool S = false> struct IC { static constexpr int value = I; static constexpr bool shared = S; };
template <class T> __device__ constexpr bool wg_is4() { return T::shared; }
#define SLOT(n) (c.ps + (2 + ((n) & 7)) * 128)
#define GO() do { wg_commit(); __syncwarp(); } while (0)
#define DEP acc[15][3]
template <class FG, class FP, class FN>
__device__ __forceinline__ void conv_head(Conv& c, float (&acc)[16][4], uint32_t (&q)[9], uint32_t (&r)[9], uint32_t* a, FG fg, FP pre, FN next) {
    c.id = 0x3210u + (c.warp >> 8);
    pre();
    conv_load<0, 0, 9>(c, q);
    conv_frag<0, 0, 1>(c, q, a, 0.f);
    wg_fence(); wg_first<0>(acc, a, c.d0); GO();
    park(c.ps, Pk{{0u, 0u, 0u, 0u}});
    wg_wait0();
    conv_frag<0, 1, 2>(c, q, a, DEP);
    wg_fence(); conv_mma<0, 0, 1, 2>(acc, c, a); GO();
    fg(IC<0>());
    wg_wait0();
    conv_frag<0, 2, 3>(c, q, a, DEP);
    wg_fence(); conv_mma<0, 0, 2, 3>(acc, c, a); GO();
    conv_load<1, 0, 5>(c, r);
    wg_wait0();
    conv_frag<0, 3, 4>(c, q, a, DEP);
    wg_fence(); conv_mma<0, 0, 3, 4>(acc, c, a); GO();
    conv_load<1, 5, 9>(c, r);
    fg(IC<1>());
    wg_wait0();
    const Pk k = pk2(acc[0], acc[1]);
    conv_rename<2>(acc);
    conv_frag<1, 0, 2>(c, r, a, k);
    wg_fence(); conv_mma<1, 2, 0, 2>(acc, c, a); GO();
    park(SLOT(0), k);
    next(IC<0>());
    fg(IC<2>());
    wg_wait0();
    conv_frag<1, 2, 4>(c, r, a, DEP);
    wg_fence(); conv_mma<1, 2, 2, 4>(acc, c, a); GO();
    next(IC<1>());
    fg(IC<3>());
    wg_wait0();
}
template <class FG, class FP>
__device__ __forceinline__ void conv_run(Conv& c, uint32_t pl, unsigned char* gy, FG fg, FP pre) {
    float acc[16][4];
    uint32_t q[9], r[9], a[32];
    uint2 f[4];
    const int bid = 1 + (c.warp >> 2);
    conv_head(c, acc, q, r, a, fg, pre, [&](auto i) { if (decltype(i)::value == 0) conv_selectors4(c); else conv_load<2, 0, 9>(c, q); });
    Pk k = pk2(acc[2], acc[3]);
    conv_rename<4>(acc);
    conv_frag<2, 0, 4>(c, q, a, k);
    wg_fence(); conv_mma<2, 4, 0, 4>(acc, c, a); GO();
    park(SLOT(2), k);
    conv_load<3, 0, 9>(c, q);
    flush_setup(c);
    bar_sync(bid, 128);
    fg(IC<4>());
    wg_wait0();
    conv_rename<6>(acc);
    conv_frag<3, 0, 4>(c, q, a, DEP);
    wg_fence(); conv_mma<3, 6, 0, 4>(acc, c, a); GO();
    park(SLOT(4), pk2(acc[4], acc[5]));
    conv_load<4, 0, 9>(c, q);
    conv_selectors8(c);
    flush_load<0>(c, pl, f);
    conv_flush<0, 0>(c, f, gy, 0u);
    fg(IC<5>());
    wg_wait0();
    conv_rename<8>(acc);
    conv_frag<4, 0, 4>(c, q, a, DEP);
    wg_fence(); conv_mma<4, 8, 0, 4>(acc, c, a); GO();
    k = pk2(acc[6], acc[7]);
    park(SLOT(6), k);
    conv_load<5, 0, 9>(c, q);
    bar_sync(bid, 128);
    park(c.ps, k);
    fg(IC<6>());
    wg_wait0();
    conv_rename<10>(acc);
    flush_load_first<1>(c, pl, f, DEP);
    conv_frag<5, 0, 4>(c, q, a, FDEP);
    wg_fence(); conv_mma<5, 10, 0, 4>(acc, c, a); GO();
    park(SLOT(8), pk2(acc[8], acc[9]));
    conv_load<6, 0, 9>(c, q); conv_load<7, 0, 9>(c, r);
    conv_flush<1, 0>(c, f, gy, 0u);
    fg(IC<7>());
    wg_wait0();
    conv_rename<12>(acc);
    conv_frag<6, 0, 4>(c, q, a, DEP); conv_frag<7, 0, 4>(c, r, a + 16, DEP);
    wg_fence(); conv_mma<6, 12, 0, 4>(acc, c, a); conv_mma<7, 12, 0, 4>(acc, c, a + 16); GO();
    park(SLOT(10), pk2(acc[10], acc[11]));
    bar_sync(bid, 128);
    flush_load<2>(c, pl, f);
    conv_flush<2, 0>(c, f, gy, 0u);
    fg(IC<8>());
    if (c.id == 0) TRAP();
    wg_wait0();
    park(SLOT(12), pk2(acc[12], acc[13])); park(SLOT(14), pk2(acc[14], acc[15]));
    bar_sync(bid, 128);
    flush_load<3>(c, pl, f);
    conv_flush<3, 0>(c, f, gy, 0u);
}
template <class FG>
__device__ __forceinline__ void conv_outer(Conv& c, uint32_t pl, unsigned char* gy, uint32_t rx, FG fg) {
    float acc[16][4];
    uint32_t q[9], r[9], a[32];
    uint2 f[4], f2[4];
    const int bid = 1 + (c.warp >> 2);
    conv_head(c, acc, q, r, a, [&](auto gi) { if (decltype(gi)::value == 2) fg(IC<2, true>()); }, [&]() {}, [&](auto i) { if (decltype(i)::value == 0) conv_selectors8(c); else conv_load<6, 0, 9>(c, q); });
    park(SLOT(2), pk2(acc[2], acc[3])); park(SLOT(4), pk2(acc[4], acc[5]));
    const Pk k = pk2(acc[6], acc[7]);
    park(SLOT(6), k);
    conv_load<7, 0, 9>(c, r);
    conv_rename<12>(acc);
    conv_frag<6, 0, 4>(c, q, a, __uint_as_float(k.w[3])); conv_frag<7, 0, 4>(c, r, a + 16, __uint_as_float(k.w[3]));
    wg_fence(); conv_mma<6, 12, 0, 4>(acc, c, a); conv_mma<7, 12, 0, 4>(acc, c, a + 16); GO();
    flush_setup(c);
    bar_sync(bid, 128);
    flush_load<0>(c, pl, f); flush_load<1>(c, pl, f2);
    conv_flush<1, 1>(c, f2, gy, rx);
    conv_flush<0, 1>(c, f, gy, rx);
    wg_wait0();
    bar_sync(bid, 128);
    park(c.ps, k); park(SLOT(8), pk2(acc[8], acc[9])); park(SLOT(10), pk2(acc[10], acc[11]));
    park(SLOT(12), pk2(acc[12], acc[13])); park(SLOT(14), pk2(acc[14], acc[15]));
    bar_sync(bid, 128);
    flush_load<2>(c, pl, f); flush_load<3>(c, pl, f2);
    conv_flush<2, 1>(c, f, gy, rx);
    conv_flush<3, 1>(c, f2, gy, rx);
}
template <class FG>
__device__ __forceinline__ void conv_inner(Conv& c, uint32_t pl, unsigned char* gy, uint32_t rx, FG fg) {
    float acc[16][4];
    uint32_t q[9], a[16];
    uint2 f[4], f2[4];
    const int bid = 1 + (c.warp >> 2);
    c.id = 0x3210u + (c.warp >> 8);
    conv_selectors4(c);
    conv_load<2, 0, 9>(c, q);
    conv_frag<2, 0, 4>(c, q, a, 0.f);
    wg_fence(); wg_first<4>(acc, a, c.d0); conv_mma<2, 4, 1, 4>(acc, c, a + 4); GO();
    conv_load<3, 0, 9>(c, q);
    park(SLOT(2), Pk{{0u, 0u, 0u, 0u}});
    fg(IC<2, true>());
    wg_wait0();
    conv_rename<6>(acc);
    conv_frag<3, 0, 4>(c, q, a, DEP);
    wg_fence(); conv_mma<3, 6, 0, 4>(acc, c, a); GO();
    park(SLOT(4), pk2(acc[4], acc[5]));
    conv_load<4, 0, 9>(c, q);
    conv_selectors8(c);
    wg_wait0();
    conv_rename<8>(acc);
    conv_frag<4, 0, 4>(c, q, a, DEP);
    wg_fence(); conv_mma<4, 8, 0, 4>(acc, c, a); GO();
    const Pk k = pk2(acc[6], acc[7]);
    park(SLOT(6), k); park(c.ps, k);
    conv_load<5, 0, 9>(c, q);
    flush_setup(c);
    wg_wait0();
    conv_rename<10>(acc);
    conv_frag<5, 0, 4>(c, q, a, DEP);
    wg_fence(); conv_mma<5, 10, 0, 4>(acc, c, a); GO();
    park(SLOT(8), pk2(acc[8], acc[9]));
    bar_sync(bid, 128);
    flush_load<1>(c, pl, f);
    mbar_wait(rx);
    conv_flush<1, 2>(c, f, gy, rx);
    wg_wait0();
    bar_sync(bid, 128);
    park(SLOT(10), pk2(acc[10], acc[11])); park(SLOT(12), pk2(acc[12], acc[13])); park(SLOT(14), pk2(acc[14], acc[15]));
    bar_sync(bid, 128);
    flush_load<3>(c, pl, f); flush_load<2>(c, pl, f2);
    mbar_wait(rx + 8);
    conv_flush<3, 2>(c, f, gy, rx);
    conv_flush<2, 2>(c, f2, gy, rx);
}
#undef SLOT
#undef GO
#undef DEP
template <int U0, int U1>
__device__ __forceinline__ void weight_units(uint32_t sb, const Maps& tm, bool w) {
    if (U1 > U0 && w && elect_one()) {
#pragma unroll
        for (int i = U0; i < U1; i++) {
            const int P = blockIdx.x >> 1, odd = blockIdx.x & 1;
            if (i < 12) tma_2d(sb + SM_WG + i * 6144, &tm.w[i / 6], 64 * P, 288 * odd + (i % 6) * 48, sb + SM_MISC + 328);
            else tma_2d(sb + SM_WD + (i - 12) * 4736, &tm.d, 144 * odd, i < 20 ? 64 * P + 8 * (i - 12) : 4096 + 8 * P, sb + SM_MISC + 336);
            if (i >= 8 && i < 12) tma_2d(sb + SM_WR + (i - 8) * 2304, &tm.r[(i - 8) >> 1], 4096 + 8 * P, 288 * odd + (i & 1) * 144, sb + SM_MISC + 328);
        }
    }
}
#define WS 2210121111113004000
__device__ constexpr int wsched(int i) {
    unsigned long long v = WS;
    int n = 0;
    for (int k = 19; k >= 1; k--) { if (k < i) n += (int)(v % 10); v /= 10; }
    return n;
}
static_assert(wsched(20) == 21 && wsched(6) <= 8 && wsched(11) <= 12 && wsched(13) <= 14 && wsched(16) <= 17 && wsched(16) == wsched(15) && wsched(19) == 21, "");
#define WANY(i) (wsched((i) + 1) > wsched(i))
#define WPOINT(i, w) do { weight_units<wsched(i), wsched(i + 1)>(sb, tm, w); } while (0)

__global__ void __launch_bounds__(NTHR, 1) __cluster_dims__(2, 1, 1)
fused_kernel(const Params p, const __grid_constant__ Maps tm) {
    extern __shared__ __align__(1024) unsigned char smem[];
    const uint32_t sb = smem_u32(smem);
    const int tid = threadIdx.x, warp = __shfl_sync(0xffffffffu, tid >> 5, 0), lane = tid & 31;
    const int b = blockIdx.x, P = b >> 1, odd = b & 1;
    const int g = lane >> 2, t = lane & 3;
    const int wg = warp >> 2, t128 = tid & 127;
    const uint32_t s_stat = sb + SM_MISC;
    const uint32_t s_key = sb + SM_MISC + 128;
    const uint32_t s_rank = sb + SM_MISC + 256;
    const uint32_t s_k16 = sb + SM_MISC + 192;
    const uint32_t s_cnt = sb + SM_MISC + 320;
    const uint32_t bar_w = sb + SM_MISC + 328, bar_d = bar_w + 8, bar_g = bar_w + 16, bar_x = bar_w + 24, bar_v = bar_w + 32, bar_s = bar_w + 40, bar_h = bar_w + 48;
    STAMP(0);

    const int ch = wg < 4 ? 4 * b + wg : 512 + P;
    const uint32_t mo = tid < 512 ? 512 * b + tid : 65536 + 128 * P + t128, mq = (mo & ~127u) + 4 * lane;
    const uint32_t pl = ldo16(p.lar + mo), pa2 = ldo16(p.aim + mo), ldt = ldo16(p.ldt + (mo >> 7));
    const uint32_t pc = ldo16(p.cre + mo), pi = ldo16(p.cim + mo);
    const uint2 call_re = ldo64(p.cre + mq), call_im = ldo64(p.cim + mq);
    const uint32_t epl = ld_poll32(p.s->hint + (b & 7) * 32 + 1);
    const uint32_t kw = sb + SM_KW + wg * KW_B;
    uint32_t co, cn, cd, uo;
    auto housekeeping = [&]() {
        if (t128 < 2 * UPAD) sts128(sb + SM_U + wg * USLOT_B + (t128 & 1) * ULO_B + (t128 >> 1) * 16, 0u, 0u, 0u, 0u);
        if (t128 >= 124) sts128(kw + (t128 & 1) * 16 + (t128 & 2) * (KW_PL / 2), 0u, 0u, 0u, 0u);
        if (warp < 15) sts128(sb + SM_Z2 + 4608 + tid * 16, 0u, 0u, 0u, 0u);
        combine_setup(sb, warp, lane, kw, co, cn, cd);
        co = pin(co); cn = pin(cn); cd = pin(cd);
        uo = pin(wg < 4 ? tid : 512 + (P >> 2) * 1024 + (t128 >> 1) * 8 + (P & 3) * 2 + (t128 & 1));
    };
    if (wg < 4) {
        bar_arrive(0, NWRK);
        asm volatile("barrier.cluster.arrive.relaxed.aligned;\n" ::: "memory");
        housekeeping();
    } else {
        const int o = (warp & 3) * 4608 + lane * 16;
        sts128(sb + SM_Z2 + t128 * 16, 0u, 0u, 0u, 0u); sts128(sb + SM_Z2 + 2048 + t128 * 16, 0u, 0u, 0u, 0u);
        if (warp == 16) sts128(sb + SM_Z2 + 4096 + lane * 16, 0u, 0u, 0u, 0u);
        fence_async();
        bar_sync(0, NWRK);
        STAMP(9);
#pragma unroll
        for (int c = 0; c < 9; c++)
            asm volatile("cp.async.cg.shared.global [%0], [%1], 16;\n" ::"r"(sb + SM_XT + o + c * 512), "l"(reinterpret_cast<const char*>(p.x) + b * 18432 + o + c * 512) : "memory");
        asm volatile("cp.async.commit_group;\n" ::: "memory");
        if (elect_one()) {
            mbar_init(bar_h + 8 * (warp & 3), 1);
            if (warp == 19) {
                mbar_init(bar_x, 1); mbar_init(bar_w, 1);
                mbar_expect(bar_x, 32768); mbar_expect(bar_w, 82944);
#pragma unroll
                for (int i = 2; i < 4; i++) bulk_s2g(reinterpret_cast<unsigned char*>(p.s->y) + 32 * i * 18432 + b * 4608, sb + SM_Z2, 4608);
            } else if (warp == 18) {
                mbar_init(bar_s, 1); mbar_init(bar_v, 2); mbar_init(bar_d, 1); mbar_init(bar_g, 1); mbar_init(sb + SM_RX, 1); mbar_init(sb + SM_RX + 8, 1);
                mbar_expect(bar_v, 2 * 1152); mbar_expect(bar_d, 72 * WD_PITCH); mbar_expect(bar_g, 4608); mbar_expect(sb + SM_RX, 1024); mbar_expect(sb + SM_RX + 8, 2048);
            }
            asm volatile("fence.mbarrier_init.release.cluster;\n" ::: "memory");
        }
        __syncwarp();
        asm volatile("barrier.cluster.arrive.relaxed.aligned;\n" ::: "memory");
        if (warp == 19) {
            asm volatile("barrier.cluster.wait.aligned;\n" ::: "memory");
            if (elect_one()) tma_4d_mc(sb + SM_XC + odd * 16384, &tm.x, 8 * P, 2 * odd, bar_x);
            __syncwarp();
        }
        {
            if (!(g & 1) && t == (g >> 1)) *reinterpret_cast<volatile uint32_t*>(p.s->stat + 16 * b + 4 * (warp & 3) + t) = 0u;
            if (warp < 18) {
                unsigned char* const ud = reinterpret_cast<unsigned char*>(p.s->uT) + (size_t)(8 * (warp & 1) + 2 * (g >> 1)) * 16384 + b * 128 + (g & 1) * 32 + t * 8;
#pragma unroll
                for (int k = 0; k < 4; k++) *reinterpret_cast<volatile unsigned long long*>(ud + (k >> 1) * 16384 + (k & 1) * 64) = 0ull;
            }
        }
    }
    const uint32_t tb = table_buf(sb, warp), t5 = sb + SM_WD + warp * 512;
    STAMP(29);
    const float dt = exp_bf(bf_lo(ldt));
    const uint32_t ep = __reduce_or_sync(0xffffffffu, epl);
    auto stats = [&]() {
        const int wq = warp & 3;
        const uint32_t xa = sb + SM_XT + (4 * wq + (g >> 1)) * 1152 + (g & 1) * 576 + t * 16;
        const bool own = !(g & 1) && t == (g >> 1);
        float d[4][4] = {};
        asm volatile("cp.async.wait_group 0;\n" ::: "memory");
        __syncwarp();
        STAMP(26);
        uint4 v[9];
#pragma unroll
        for (int c = 0; c < 9; c++) v[c] = lds128(xa + c * 64);
#pragma unroll
        for (int c = 0; c < 9; c++) {
            mma_bf16(d[2 * (c & 1)], v[c].x, 0x3f803f80u, v[c].y, 0x3f803f80u, v[c].x, v[c].y);
            mma_bf16(d[2 * (c & 1) + 1], v[c].z, 0x3f803f80u, v[c].w, 0x3f803f80u, v[c].z, v[c].w);
        }
        STAMP(27);
        float sm = (g & 1) ? (d[0][3] + d[1][3]) + (d[2][3] + d[3][3]) : (d[0][2] + d[1][2]) + (d[2][2] + d[3][2]);
        float sq = (g & 1) ? (d[0][1] + d[1][1]) + (d[2][1] + d[3][1]) : (d[0][0] + d[1][0]) + (d[2][0] + d[3][0]);
        sm += __shfl_xor_sync(0xffffffffu, sm, 4); sq += __shfl_xor_sync(0xffffffffu, sq, 4);
        if (lane == 0) mbar_arrive(bar_h + 8 * wq);
        float mb, sd;
        ln_stats(sm, sq, mb, sd);
        if (own) p.s->stat[16 * b + 4 * wq + t] = (__float_as_uint(mb) >> 16) | (__float_as_uint(sd) & 0x7fff0000u) | (ep << 31);
        STAMPX(22);
        if (own) stat_store(s_stat + (2 * wq + (t & 1) + 8 * (t >> 1)) * 8, mb, rcp_approx(sd), 0u);
        if (wq == 3) asm volatile("cp.async.bulk.wait_group 0;\n" ::: "memory");
        bar_sync(5, 128);
        STAMP(28);
        uint32_t now;
        asm volatile("mov.u32 %0, %%clock;" : "=r"(now) :: "memory");
        if (wq == 2) {
            conv_constants(sb + SM_LC, lane);
            __syncwarp();
            if (lane < 8) p.s->key3[8 * b + lane] = ep & 1u;
            if (lane == 0) {
                sts64(s_cnt, now, ep);
                mbar_arrive(bar_s);
                bulk_g2s(sb + SM_XT + 16 * 1152, p.dsk, 1152, bar_v);
                bulk_g2s(sb + SM_XT + 17 * 1152, p.wr, 1152, bar_v);
            }
            __syncwarp();
        }
        WPOINT(1, wq == 3);
        if (wq < 2) {
            unsigned char* const ud = reinterpret_cast<unsigned char*>(p.s->uT) + (size_t)(8 * wq + 2 * (g >> 1)) * 16384 + b * 128 + (g & 1) * 32 + t * 8;
            const uint32_t utag = (ep % 7u + 1u) * 0x10001u;
            uint32_t U[2][4];
#pragma unroll
            for (int hf = 0; hf < 2; hf++) {
                const uint2 st = lds64(s_stat + (g + 8 * hf) * 8);
                const uint4 xu = lds128(sb + SM_XT + (TOK(g) + 2 * hf) * 1152 + warp * 64 + t * 16);
                const uint32_t X[4] = {xu.x, xu.y, xu.z, xu.w};
#pragma unroll
                for (int k = 0; k < 4; k++) {
                    const uint32_t u = ln_apply(X[k], STAT_M(st), STAT_H(st), STAT_L(st));
                    U[hf][k] = movm((pack_f16(bf_lo(u), bf_hi(u)) & 0xfff8fff8u) | utag);
                }
            }
#pragma unroll
            for (int k = 0; k < 4; k++) stg64(ud + (k >> 1) * 16384 + (k & 1) * 64, U[0][k], U[1][k]);
        }
    };
    STAMP(1);
    if (wg < 4) { STAMPX(16); }
    KGen kg;
    kgen_setup(kg, bf_lo(pl), bf_lo(pa2), dt);
    kgen_rows(kg, tb, lane);
    STAMP(2);
    const int E = min(max(c_exponent(call_re, call_im, dt) - 243, -120), 120);
    kgen_chain(kg, pc, pi, dt * __uint_as_float((uint32_t)(128 - E) << 23));
    STAMP(3);
    kgen_cols(kg, tb, t5, lane);
    STAMP(4);
    if (wg == 4) stats();
    if (warp != 19) asm volatile("barrier.cluster.wait.aligned;\n" ::: "memory");
    if (wg < 4) { STAMPX(17); }
    if (wg == 4) housekeeping();
    const uint4* const usrc = reinterpret_cast<const uint4*>(p.s->stat) + uo;
    if (wg < 4) mbar_wait(bar_h + 8 * (warp & 3));
    if (wg < 4) { STAMPX(19); }
    uint32_t trel;
    asm volatile("mov.u32 %0, %%clock;" : "=r"(trel) :: "memory");
    kgen_mma(kg, tb, t5, lane);
    if (wg < 4) { STAMPX(20); }
    STAMP(5);
    uint4 uv0, uv1;
    auto first_poll = [&](uint32_t dly) {
        mbar_wait(bar_s);
        const uint32_t t0 = lds32(s_cnt);
        uint32_t now;
        do { asm volatile("mov.u32 %0, %%clock;" : "=r"(now) :: "memory"); } while (now - t0 < dly);
        uv0 = ld_poll(usrc);
    };
    if (wg == 4) { first_poll(UDLY); uv1 = ld_poll(usrc + 512); }
    WPOINT(2, warp == 19);
    auto stat_poll = [&]() {
        uint32_t now;
        do { asm volatile("mov.u32 %0, %%clock;" : "=r"(now) :: "memory"); } while (now - trel < SDLY);
        uv0 = ld_poll(usrc);
    };
    bar_sync(1 + wg, 128);
    if (wg < 4) { STAMPX(21); }
    kgen_combine(warp & 3, lane, co, cn, cd);
    STAMP(6);
    if (wg < 4) { STAMPX(18); }
    WPOINT(3, warp == 19);
    if (wg < 4) stat_poll();
    {
        const int wq = warp & 3;
        Conv c;
        const uint32_t pln = sb + SM_PL + wg * PL_B;
        const int e = g - 2 * t + 7;
        c.kw = kw; c.wa = pin(kw + ((e >> 2) & 1) * KW_PL + (8 * wq + (e >> 3)) * 16 + (e & 3) * 4);
        c.ps = mov_v(pln + wq * PLW_B + ((lane >> 3) & 1) * PL_HALF + ((lane >> 4) * 8 + (lane & 7)) * 16); c.warp = warp;
        c.lc = sb + SM_LC; c.fs = (uint32_t)(127 + E) * 0x800080u; c.yp = (ep & 1u) * (NCTA * 18432u);
        c.d0 = ((uint64_t)(ULO_B >> 4) << 16) | ((uint64_t)(128 >> 4) << 32) | (uint64_t)(((sb + SM_U + wg * USLOT_B + UPAD * 16) & 0x3FFFF) >> 4);
        unsigned char* gy = reinterpret_cast<unsigned char*>(p.s->y) + ((size_t)(4 * wq) * DM + ch) * 64;
        auto hook = [&](auto gi) {
                     constexpr int G = decltype(gi)::value;
                     if (G == (wg_is4<decltype(gi)>() ? 2 : 5)) asm volatile("barrier.cluster.wait.aligned;\n" ::: "memory");
                     if (!wg_is4<decltype(gi)>() && G == 1) mbar_wait(bar_s);
                     if (!wg_is4<decltype(gi)>() && (G == 0 || G == 2) && warp == HW && elect_one()) {
                         unsigned char* const sc = reinterpret_cast<unsigned char*>(p.s);
                         if (G == 0) {
                             if (b < 96) bulk_s2g_nc(sc + offsetof(Scratch, part) + b * 6144, sb + SM_Z2, 6144);
                             bulk_s2g(sc + offsetof(Scratch, rows) + (127 - b) * 4608, sb + SM_Z2, 4608);
                         }
                         if (G == 2) {
                             bulk_s2g(sc + offsetof(Scratch, y) + (NCTA * 18432u - c.yp) + b * 9216, sb + SM_Z2, 9216);
                         }
                     }
                     if (!wg_is4<decltype(gi)>()) WPOINT(6 + G, warp == (G >= 7 ? HW : 4 * (G % 3) + 1));
                     if (!wg_is4<decltype(gi)>() && G == 6 && warp == HW) {
                         asm volatile("cp.async.bulk.wait_group 0;\n" ::: "memory");
                         __syncwarp();
                         if (elect_one()) mbar_arrive(bar_v);
                     }
                 };
        if (wg < 4) {
            asm volatile("barrier.cluster.arrive.relaxed.aligned;\n" ::: "memory");
            conv_run(c, pln + wq * 128, gy, hook, [&]() {
                STAMPX(23);
                mbar_wait(bar_x);
                STAMPX(24);
                uint2 xc[4];
                uint32_t xw[4][2];
#pragma unroll
                for (int j = 0; j < 4; j++) xc[j] = lds64(sb + SM_XC + wg * 8192 + j * 2048 + t128 * 16 + odd * 8);
#pragma unroll
                for (int i = 0; i < 8; i++) {
                    const int k = i >> 1, h = i & 1;
                    xw[k][h] = prmt_v(k < 2 ? xc[2 * h].x : xc[2 * h].y, k < 2 ? xc[2 * h + 1].x : xc[2 * h + 1].y, (k & 1) ? 0x7632 : 0x5410);
                }
                const uint32_t ub = mov_v(sb + SM_U + UPAD * 16 + ((tid >> 1) & 1) * ULO_B + (tid >> 2) * 16 + (tid & 1) * 8), tag = ep << 31;
                int it = 0;
                while (min(min((int)(uv0.x ^ tag), (int)(uv0.y ^ tag)), min((int)(uv0.z ^ tag), (int)(uv0.w ^ tag))) < 0x10000) {
                    if (++it > SPIN_LIMIT) TRAP();
                    uv0 = ld_poll(usrc);
                }
                STAMP(8);
                STAMPX(26);
                const float r0 = rcp_approx(fabsf(bf_hi(uv0.x))), r1 = rcp_approx(fabsf(bf_hi(uv0.y))), r2 = rcp_approx(fabsf(bf_hi(uv0.z))), r3 = rcp_approx(fabsf(bf_hi(uv0.w)));
                const uint32_t m[2] = {__byte_perm(uv0.x, uv0.y, 0x5410), __byte_perm(uv0.z, uv0.w, 0x5410)};
                const uint32_t rh[2] = {pack_bf16(r0, r1), pack_bf16(r2, r3)};
                const uint32_t rl[2] = {pack_bf16(r0 - bf_lo(rh[0]), r1 - bf_hi(rh[0])), pack_bf16(r2 - bf_lo(rh[1]), r3 - bf_hi(rh[1]))};
#pragma unroll
                for (int k = 0; k < 4; k++) {
                    const uint32_t u0 = ln_apply(xw[k][0], m[0], rh[0], rl[0]), u1 = ln_apply(xw[k][1], m[1], rh[1], rl[1]);
                    sts64(ub + k * USLOT_B, pack_f16(bf_lo(u0), bf_hi(u0)), pack_f16(bf_lo(u1), bf_hi(u1)));
                }
                STAMPX(29);
                fence_async();
                bar_sync(14, 512);
                STAMP(7);
            });
        } else {
            auto stage = [&]() {
                const uint32_t tag = (ep % 7u + 1u) * 0x10001u;
                int it = 0;
                WPOINT(4, warp == 19);
                while (true) {
                    uv0.x ^= tag; uv0.y ^= tag; uv0.z ^= tag; uv0.w ^= tag; uv1.x ^= tag; uv1.y ^= tag; uv1.z ^= tag; uv1.w ^= tag;
                    if ((((uv0.x | uv0.y | uv0.z) | (uv0.w | uv1.x | uv1.y) | (uv1.z | uv1.w)) & 0x70007u) == 0) break;
                    if (++it > SPIN_LIMIT) TRAP();
                    uv0 = ld_poll(usrc); uv1 = ld_poll(usrc + 512);
                }
                STAMP(8);
                const uint32_t ub = sb + SM_U + UPAD * 16 + 4 * USLOT_B + (t128 & 1) * ULO_B + (t128 >> 1) * 16;
                sts128(ub, uv0.x, uv0.y, uv0.z, uv0.w);
                sts128(ub + 1024, uv1.x, uv1.y, uv1.z, uv1.w);
                fence_async();
                asm volatile("barrier.cluster.arrive.relaxed.aligned;\n" ::: "memory");
                bar_sync(5, 128);
                WPOINT(5, warp == 19);
                STAMP(7);
            };
            stage();
            if (odd) conv_inner(c, pln + wq * 128, gy, sb + SM_RX, hook);
            else conv_outer(c, pln + wq * 128, gy, sb + SM_RX, hook);
        }
        STAMP(10);
    }
    {
    const int lane = lane_v(), tid = 32 * warp + lane, g = lane >> 2, t = lane & 3;
    const uint32_t par = ~ep & 1u;
    bar_sync(0, NWRK);
    STAMP(11);
    uint32_t H[2][4] = {}, U2[2][4] = {};
    auto publish = [&](bool hi, int slot) {
        uint4* rowp = reinterpret_cast<uint4*>(p.s->rows) + slot * 144 + warp * 4 + t;
        stg128(rowp, nzw(hi ? U2[1][0] : U2[0][0]), nzw(hi ? U2[1][1] : U2[0][1]), nzw(hi ? U2[1][2] : U2[0][2]), nzw(hi ? U2[1][3] : U2[0][3]));
        stg128(rowp + 72, nzw(hi ? H[1][0] : H[0][0]), nzw(hi ? H[1][1] : H[0][1]), nzw(hi ? H[1][2] : H[0][2]), nzw(hi ? H[1][3] : H[0][3]));
    };
#define KTOK(k) (int)(((~(k) >> 5) & 0x7f0u) | (((k) >> 1) & 15u))
#define KLATE(k) (((k) & 0x1e0u) < 0xe0u)
#define KSLOT(k, s) (KLATE(k) ? 2 * NCTA + (s) : (int)(((k) >> 8) & 0xffu))
    const uint4* const rsrc = reinterpret_cast<const uint4*>(p.s->rows) + 36 * odd;
    auto gather = [&](uint32_t mine) {
        int it = 0;
        uint32_t mn;
        do {
            mn = 1;
#pragma unroll 1
            for (int r = 0; r < 9; r++) {
                const uint32_t k = __shfl_sync(0xffffffffu, mine, r < 8 ? 4 * r : lane);
                const int row = r < 8 ? r : g, c = r < 8 ? lane : 32 + t;
                asm volatile("cp.async.cg.shared.global [%0], [%1], 16;\n" ::"r"(sb + SM_XS + row * XS_PITCH + c * 16), "l"(rsrc + KSLOT(k, row) * 144 + c) : "memory");
            }
            asm volatile("cp.async.wait_all;\n" ::: "memory");
#pragma unroll 1
            for (int r = 0; r < 9; r++) mn = min(mn, min4(lds128(sb + SM_XS + (r < 8 ? r * XS_PITCH + lane * 16 : g * XS_PITCH + (32 + t) * 16))));
            if (++it > SPIN_LIMIT) TRAP();
        } while (__any_sync(0xffffffffu, mn == 0));
    };
    auto late_rows = [&](auto role) {
        if (decltype(role)::value == 1) {
            int it = 0;
            uint4 k[8];
            uint32_t bad;
            do {
                bad = 0;
#pragma unroll
                for (int i = 0; i < 8; i++) k[i] = ld_poll(reinterpret_cast<const uint4*>(p.s->key) + 32 * i + lane);
#pragma unroll
                for (int i = 0; i < 8; i++) bad = or3(bad, xor_or(k[i].x, k[i].y, par), xor_or(k[i].z, k[i].w, par));
                if (++it > SPIN_LIMIT) TRAP();
            } while (__any_sync(0xffffffffu, bad & 1u));
#pragma unroll 1
            for (int r = 0; r < 8; r++) {
                uint32_t c = 0;
#pragma unroll
                for (int i = 0; i < 8; i++) c = max(c, k[i].x);
                const uint32_t m = __reduce_max_sync(0xffffffffu, c);
#pragma unroll
                for (int i = 0; i < 8; i++) if (k[i].x == m) k[i] = make_uint4(k[i].y, k[i].z, k[i].w, 0u);
                if (lane == 0) sts32(s_key + r * 4, m);
            }
        }
        bar_sync(0, NWRK);
        const uint32_t kk = lds32(s_key + (lane & 7) * 4), ep = lds32(s_cnt + 4);
        const bool own = KLATE(kk) && (KTOK(kk) >> 4) == b;
        uint32_t todo = __ballot_sync(0xffffffffu, own) & 0xffu;
        if (decltype(role)::value == 0 && todo) {
#pragma unroll
            for (int hf = 0; hf < 2; hf++) {
                const uint4 h = lds128(sb + SM_U + hf * 9216 + tid * 16);
                const uint2 st = lds64(s_stat + (g + 8 * hf) * 8);
                H[hf][0] = h.x; H[hf][1] = h.y; H[hf][2] = h.z; H[hf][3] = h.w;
#pragma unroll
                for (int k = 0; k < 4; k++) U2[hf][k] = ln_apply(H[hf][k], STAT_M(st), STAT_H(st), STAT_L(st));
            }
#pragma unroll 1
            while (todo) {
                const int s = __ffs(todo) - 1, tk = KTOK(__shfl_sync(0xffffffffu, kk, s));
                todo &= todo - 1;
                if ((tk & 13) == TOK(g)) publish(tk & 2, 2 * NCTA + s);
            }
            __threadfence();
        }
        bar_sync(0, NWRK);
        if (decltype(role)::value == 1) {
            if (lane < NSEL && own) *reinterpret_cast<volatile unsigned*>(p.s->flag + lane) = ep + 1u;
            int it = 0;
            while (__any_sync(0xffffffffu, KLATE(kk) && ld_acquire32(p.s->flag + (lane & 7)) != ep + 1u)) { if (++it > SPIN_LIMIT) TRAP(); }
            gather(__shfl_sync(0xffffffffu, kk, g));
        }
        bar_sync(0, NWRK);
    };
    if (warp < 18) {
        const unsigned char* ys = reinterpret_cast<const unsigned char*>(p.s->y) + (b < 64 ? (par ^ 1u) * (NCTA * 18432u) : 0u) +
                                  ((P * DM + 32 * warp + 8 * (g >> 1) + (g & 1)) * 64 + odd * 32 + t * 8);
        mbar_wait(bar_v);
        const uint32_t xa = sb + SM_XT + warp * 64 + t * 16;
        const uint4 x0 = lds128(xa + TOK(g) * 1152), x1 = lds128(xa + (TOK(g) + 2) * 1152), dk = lds128(xa + 16 * 1152);
        uint4 wr = make_uint4(0u, 0u, 0u, 0u);
        if (g == 0) wr = lds128(xa + 17 * 1152);
        uint2 yv[4];
        const uint32_t Z[2][4] = {{x0.x, x0.y, x0.z, x0.w}, {x1.x, x1.y, x1.z, x1.w}}, D4[4] = {dk.x, dk.y, dk.z, dk.w};
#pragma unroll
        for (int hf = 0; hf < 2; hf++) {
            const uint2 st = lds64(s_stat + (g + 8 * hf) * 8);
#pragma unroll
            for (int k = 0; k < 4; k++) U2[hf][k] = hmul2_bf(ln_apply(Z[hf][k], STAT_M(st), STAT_H(st), STAT_L(st)), D4[k]);
        }
        const uint32_t la = pin(sb + SM_LNP + (g * 20 + warp) * 4);
        {
            const unsigned char* y1 = ys + (U2[0][0] & U2[1][2] & (warp >> 8));
#pragma unroll
            for (int k = 0; k < 4; k++) yv[k] = ld_poll64(y1 + k * 128);
        }
        int it = 0;
        float d[2][4];
        while (true) {
            const uint32_t mn = min3(min3(yv[0].x, yv[0].y, yv[1].x), min3(yv[1].y, yv[2].x, yv[2].y), min(yv[3].x, yv[3].y));
#pragma unroll
            for (int k = 0; k < 4; k++) {
                H[0][k] = hadd2_bf(Z[0][k], hadd2_bf(movm(yv[k].x), U2[0][k]));
                H[1][k] = hadd2_bf(Z[1][k], hadd2_bf(movm(yv[k].y), U2[1][k]));
            }
            ln_partial(H, d);
            if (!__any_sync(0xffffffffu, mn == 0)) break;
            if (++it > SPIN_LIMIT) TRAP();
#pragma unroll
            for (int k = 0; k < 4; k++) yv[k] = ld_poll64(ys + k * 128);
        }
        STAMP(12);
        {
            const float s0 = (g & 1) ? d[0][3] : d[0][2], s1 = (g & 1) ? d[1][3] : d[1][2];
            const float q0 = (g & 1) ? d[0][1] : d[0][0], q1 = (g & 1) ? d[1][1] : d[1][0];
            asm volatile("{\n.reg .pred p;\nsetp.eq.u32 p, %5, %6;\n@p st.shared.f32 [%0], %1;\n@p st.shared.f32 [%0 + 640], %2;\n@p st.shared.f32 [%0 + 1280], %3;\n@p st.shared.f32 [%0 + 1920], %4;\n}\n"
                         ::"r"(la), "f"(s0), "f"(s1), "f"(q0), "f"(q1), "r"(t), "r"(g >> 1) : "memory");
        }
        bar_arrive(6, NWRK);
        STAMP(13);
        bar_sync(7, 608);
        STAMP(14);
#pragma unroll
        for (int hf = 0; hf < 2; hf++) {
            const uint2 st = lds64(s_stat + (g + 8 * hf) * 8);
#pragma unroll
            for (int k = 0; k < 4; k++) U2[hf][k] = ln_apply(H[hf][k], STAT_M(st), STAT_H(st), STAT_L(st));
        }
        {
            float cs[4] = {0.f, 0.f, 0.f, 0.f};
            mma_bf16(cs, U2[0][0], U2[1][0], U2[0][1], U2[1][1], wr.x, wr.y);
            mma_bf16(cs, U2[0][2], U2[1][2], U2[0][3], U2[1][3], wr.z, wr.w);
            if (t == 0) { stsf(la + 32 * 80, cs[0]); stsf(la + 40 * 80, cs[2]); }
            bar_arrive(8, 608);
        }
        FIX((uint32_t)warp >> 8);
        uint32_t O[2][4];
#pragma unroll
        for (int hf = 0; hf < 2; hf++)
#pragma unroll
            for (int k = 0; k < 4; k++) { O[hf][k] = hadd2_bf(H[hf][k], U2[hf][k]); H[hf][k] = nzw(H[hf][k]); U2[hf][k] = nzw(U2[hf][k]); }
        unsigned char* rowp = reinterpret_cast<unsigned char*>(p.s->rows) + ((254 - 2 * b) * 2304 + warp * 64 + t * 16);
        FIX(and3(and3(and3(H[0][0], H[0][1], H[0][2]), and3(H[0][3], H[1][0], H[1][1]), and3(H[1][2], H[1][3], U2[0][0])),
                 and3(and3(U2[0][1], U2[0][2], U2[0][3]), and3(U2[1][0], U2[1][1], U2[1][2]), U2[1][3]), (uint32_t)reinterpret_cast<uint64_t>(rowp)));
        bar_sync(9, 608);
        {
            const uint2 best = lds64(s_rank);
#pragma unroll
            for (int hf = 0; hf < 2; hf++) {
                const uint32_t me = 2 * TOK(g) + 4 * hf;
                unsigned char* d = rowp + (best.x == me ? 2304 : 0);
                if (best.x == me || best.y == me) {
                    stg128(d, U2[hf][0], U2[hf][1], U2[hf][2], U2[hf][3]);
                    stg128(d + 1152, H[hf][0], H[hf][1], H[hf][2], H[hf][3]);
                }
            }
        }
        FIX((uint32_t)warp >> 9);
#pragma unroll
        for (int hf = 0; hf < 2; hf++) {
            sts128(sb + SM_OUT + (TOK(g) + 2 * hf) * (DM * 2) + warp * 64 + t * 16, O[hf][0], O[hf][1], O[hf][2], O[hf][3]);
            sts128(sb + SM_U + hf * 9216 + tid * 16, H[hf][0], H[hf][1], H[hf][2], H[hf][3]);
        }
        STAMP(15);
        const int mi = lane >> 3, rr = lane & 7;
        const bool gate = warp < 12 && (warp & 3) != 2;
        const int fj = gate ? 3 * (warp >> 2) + min(warp & 3, 2) : (warp < 12 ? warp >> 2 : warp - 9);
        if (gate) {
            uint32_t W[18][4];
            mbar_wait(bar_w);
            const uint32_t aad = fj < 8 ? sb + SM_WG + (mi & 1) * SM_WU + (rr + 8 * (mi >> 1)) * 128 + (fj ^ rr) * 16 : sb + SM_WR + (mi & 1) * 4608 + (rr + 8 * (mi >> 1)) * 16;
            const uint32_t ast = fj < 8 ? 2048 : 256;
            const uint32_t bad = pin(sb + SM_XS + rr * XS_PITCH + mi * 16);
            bool rare = warp >> 8;
#pragma unroll 1
            do {
                if (rare) late_rows(IC<0>());
#pragma unroll
                for (int k = 0; k < 18; k++) ldsm_x4_t(W[k][0], W[k][1], W[k][2], W[k][3], aad + k * ast);
                if (rare) break;
                fence_async();
                STAMP2(17);
                rare = bar_or(11, NWRK, false);
            } while (rare);
            STAMP2(19);
            float c4[2][4] = {};
#pragma unroll
            for (int k = 0; k < 18; k += 2) {
                uint32_t b0, b1, b2, b3;
                ldsm_x4(b0, b1, b2, b3, bad + k * 32);
                mma_bf16(c4[0], W[k][0], W[k][1], W[k][2], W[k][3], b0, b1);
                mma_bf16(c4[1], W[k + 1][0], W[k + 1][1], W[k + 1][2], W[k + 1][3], b2, b3);
            }
            const uint32_t ex = sb + SM_EX + (32 * fj + lane) * 16;
            const float e0 = c4[0][0] + c4[1][0], e1 = c4[0][1] + c4[1][1], e2 = c4[0][2] + c4[1][2], e3 = c4[0][3] + c4[1][3];
            asm volatile("st.async.shared::cluster.mbarrier::complete_tx::bytes.v4.f32 [%0], {%1,%2,%3,%4}, [%5];\n"
                         ::"r"(ex ^ 0x1000000u), "f"(e0), "f"(e1), "f"(e2), "f"(e3), "r"(bar_g ^ 0x1000000u) : "memory");
            STAMP2(20);
            mbar_wait(bar_g);
            const uint4 o = lds128(ex);
            const uint32_t G = pack_bf16(e0 + __uint_as_float(o.x), e1 + __uint_as_float(o.y)), U = pack_bf16(e2 + __uint_as_float(o.z), e3 + __uint_as_float(o.w));
            sts32(sb + SM_GU + (32 * fj + lane) * 4, hmul2_bf(pack_bf16(bf_lo(G) * sigmoid_f(bf_lo(G)), bf_hi(G) * sigmoid_f(bf_hi(G))), U));
            bar_arrive(13, NWRK);
        } else {
            uint32_t W[2][18];
            auto load_wd = [&]() {
                mbar_wait(bar_d);
                const uint32_t base = sb + SM_WD + (4 * fj + (mi & 1)) * 16 + rr * WD_PITCH;
#pragma unroll
                for (int j = 0; j < 2; j++) {
#pragma unroll
                    for (int k = 0; k < 4; k++) ldsm_x4_t(W[j][4 * k], W[j][4 * k + 1], W[j][4 * k + 2], W[j][4 * k + 3], base + j * 32 + (k * 16 + 8 * (mi >> 1)) * WD_PITCH);
                    ldsm_x2_t(W[j][16], W[j][17], base + j * 32 + 64 * WD_PITCH);
                }
            };
            const uint32_t po = pin((((8 * (18 * odd + 2 * fj) + g) * 64 + P) * 4 + t) * 8);
            fence_async();
            STAMP2(17);
            const bool first = (warp & 3) != 2;
#pragma unroll 1
            for (int i = 0; i < 2; i++) {
                if (i == (first ? 1 : 0)) {
                    if (bar_or(11, NWRK, false)) late_rows(IC<0>());
                    if (!first) delay(DDLY);
                } else load_wd();
            }
            bar_sync(13, NWRK);
            STAMP2(21);
            uint32_t gb[9];
            ldsm_x4_t(gb[0], gb[1], gb[2], gb[3], sb + SM_GU + lane * 16);
            ldsm_x4_t(gb[4], gb[5], gb[6], gb[7], sb + SM_GU + 512 + lane * 16);
            ldsm_x1_t(gb[8], sb + SM_GU + 1024 + lane * 16);
            float c4[2][4] = {}, d4[2][4] = {};
#pragma unroll
            for (int k = 0; k < 4; k += 2)
#pragma unroll
                for (int j = 0; j < 2; j++) {
                    mma_bf16(c4[j], W[j][4 * k], W[j][4 * k + 1], W[j][4 * k + 2], W[j][4 * k + 3], gb[2 * k], gb[2 * k + 1]);
                    mma_bf16(d4[j], W[j][4 * k + 4], W[j][4 * k + 5], W[j][4 * k + 6], W[j][4 * k + 7], gb[2 * k + 2], gb[2 * k + 3]);
                }
#pragma unroll
            for (int j = 0; j < 2; j++) mma_bf16_k8(c4[j], W[j][16], W[j][17], gb[8]);
#pragma unroll
            for (int j = 0; j < 2; j++)
                stg64(reinterpret_cast<unsigned char*>(p.s->part) + po + j * 16384, nzw(pack_bf16(c4[j][0] + d4[j][0], c4[j][1] + d4[j][1])), nzw(pack_bf16(c4[j][2] + d4[j][2], c4[j][3] + d4[j][3])));
        }
        STAMP2(22);
    } else if (warp == 18) {
        const uint4* const ksrc = reinterpret_cast<const uint4*>(p.s->key3) + pin(2 * lane);
        const int row = (g >> 1) + 4 * (g & 1);
        const uint32_t ro = pin(640 * odd + t * 16), xd = pin(sb + SM_XS + row * XS_PITCH + t * 16 + (odd ? 0 : 512));
        const uint32_t xe = pin(sb + SM_XS + (g >> 1) * XS_PITCH + (lane & 7) * 16 + 64 * odd);
        const uint32_t sa = pin(sb + SM_LNP + lane * 80);
        const uint32_t klo = pin((uint32_t)(127 - b) << 9 | (uint32_t)(15 - ROWTOK(lane & 15)) << 1 | par), ra = pin(sb + SM_LNP + (32 + (lane & 15)) * 80);
        uint4* const kdst = reinterpret_cast<uint4*>(p.s->key3) + pin((lane >> 1) * 2 * NCTA + 2 * b + (lane & 1));
        FIX(ra);
        bar_sync(6, NWRK);
        {
            float mb, rc;
            ln_finish(sum18(sa), lane, mb, rc);
            if (lane < 16) stat_store(s_stat + lane * 8, mb, rc, 0u);
        }
        bar_arrive(7, 608);
        bar_sync(8, 608);
        uint32_t t0;
        {
            const uint32_t bits = __float_as_uint(rbf(sum18(ra)));
            const uint32_t me = ((bits ^ ((uint32_t)((int)bits >> 31) | 0x80000000u)) & 0xffff0000u) | klo;
            const uint32_t k0 = __reduce_max_sync(0xffffffffu, me), k1 = __reduce_max_sync(0xffffffffu, me == k0 ? 0u : me);
            const uint32_t k2 = __reduce_max_sync(0xffffffffu, me >= k1 ? 0u : me);
            if (lane < 2) stg128(kdst, k0 ^ 0x11eu, k1 ^ 0xfeu, k2 ^ 0xdeu, par);
            asm volatile("mov.u32 %0, %%clock;" : "=r"(t0) :: "memory");
            STAMPW(23);
            if (lane == 0) sts64(s_rank, ~k0 & 30u, ~k1 & 30u);
            bar_arrive(9, 608);
            sts32(s_k16 + (lane & 15) * 4, me);
            __syncwarp();
            const uint4 v = lds128(s_k16 + (lane & 16) * 2), w = lds128(s_k16 + (lane & 16) * 2 + 16);
            int rank = ((v.x > me) + (v.y > me)) + ((v.z > me) + (v.w > me)) + (((w.x > me) + (w.y > me)) + ((w.z > me) + (w.w > me)));
            rank += __shfl_xor_sync(0xffffffffu, rank, 16);
            if (lane < 16 && rank < 8) p.s->key[8 * b + rank] = (me ^ 0x1eu) | ((8 - rank) << 5);
        }
        uint4 kq[4];
        uint32_t u[4], mine = 0, m;
        int it = 0;
        { uint32_t now; do { asm volatile("mov.u32 %0, %%clock;" : "=r"(now) :: "memory"); } while (now - t0 < KDLY); }
        do {
#pragma unroll
            for (int i = 0; i < 4; i++) kq[i] = ld_poll(ksrc + 64 * i);
            if (++it > SPIN_LIMIT) TRAP();
            uint32_t S[2][4];
#pragma unroll
            for (int i = 0; i < 2; i++) {
                const uint4 &c = kq[2 * i], &d = kq[2 * i + 1];
                const uint32_t m1 = min(c.x, d.x), m2 = max(c.y, d.y);
                S[i][0] = max(c.x, d.x); S[i][1] = max(m1, m2); S[i][2] = min(m1, m2); S[i][3] = min(c.y, d.y);
            }
            const uint32_t a0 = max(S[0][0], S[1][3]), a1 = max(S[0][1], S[1][2]), a2 = max(S[0][2], S[1][1]), a3 = max(S[0][3], S[1][0]);
            const uint32_t b0 = max(a0, a2), b2 = min(a0, a2), b1 = max(a1, a3), b3 = min(a1, a3);
            u[0] = max(b0, b1); u[1] = min(b0, b1); u[2] = max(b2, b3); u[3] = min(b2, b3);
            const uint32_t bad = or3(or3(xor_or(kq[0].x, kq[0].y, par), xor_or(kq[0].z, kq[1].x, par), xor_or(kq[1].y, kq[1].z, par)),
                                     xor_or(kq[2].x, kq[2].y, par), xor_or(kq[2].z, kq[3].x, par)) | xor_or(kq[3].y, kq[3].z, par);
            m = __reduce_max_sync(0xffffffffu, u[0] | (uint32_t)((int)(bad << 31) >> 31));
        } while (m == 0xffffffffu);
        STAMPW(16);
#pragma unroll
        for (int r = 0; r < 8; r++) {
            if (r) m = __reduce_max_sync(0xffffffffu, u[0]);
            if (u[0] == m) { u[0] = u[1]; u[1] = u[2]; u[2] = u[3]; u[3] = 0; }
            if (row == r) mine = m;
        }
        uint4 v[9];
        const uint32_t o0 = __byte_perm(mine, 0, 0x4441) * 2304u, o1 = __shfl_xor_sync(0xffffffffu, o0, 4);
        const unsigned char* const rA = reinterpret_cast<const unsigned char*>(p.s->rows) + (((g & 1) ? o1 : o0) + ro + (g & 1) * 64);
        const unsigned char* const rb = reinterpret_cast<const unsigned char*>(p.s->rows) + (((g & 1) ? o0 : o1) + ro + (g & 1) * 64);
        const unsigned char* const rc = reinterpret_cast<const unsigned char*>(p.s->rows) + (o0 + ro + (odd ? -64 : 512));
#pragma unroll
        for (int i = 0; i < 4; i++) { v[i] = ld_poll(rA + i * 128); v[4 + i] = ld_poll(rb + i * 128); }
        v[8] = ld_poll(rc);
        const bool again = u[0] == 0 || max(max(kq[0].z, kq[1].z), max(kq[2].z, kq[3].z)) > m;
        if (t == 0) sts32(s_key + row * 4, mine);
#pragma unroll
        for (int i = 0; i < 9; i++) sts128(i < 8 ? xe + (i >> 2) * 4 * XS_PITCH + (i & 3) * 128 : xd, v[i].x, v[i].y, v[i].z, v[i].w);
        uint32_t mn, m3[3];
        m3[0] = m3[1] = m3[2] = 1u;
#pragma unroll
        for (int i = 0; i < 9; i++) m3[i % 3] = min3(min3(m3[i % 3], v[i].x, v[i].y), v[i].z, v[i].w);
        mn = min3(m3[0], m3[1], m3[2]);
        STAMPW(18);
        if (bar_or(11, NWRK, again || mn == 0)) late_rows(IC<1>());
    } else {
        bar_sync(6, NWRK);
        WPOINT(16, true);
        if (WANY(17) || WANY(18)) delay(WDLY);
        WPOINT(17, true);
        if (WANY(18)) delay(WDLY);
        WPOINT(18, true);
        if (bar_or(11, NWRK, false)) late_rows(IC<2>());
        const int tk = KTOK(lds32(s_key + (lane & 7) * 4));
        const uint32_t sel = __reduce_or_sync(0xffffffffu, (tk >> 4) == b ? 1u << (tk & 15) : 0u);
        if (sel ? lane < 16 && !((sel >> lane) & 1u) : lane == 0) bulk_s2g(p.out + (size_t)(16 * b + lane) * DM, sb + SM_OUT + lane * (DM * 2), sel ? DM * 2 : 16 * DM * 2);
        __syncwarp();
    }
    if (warp == 8 || warp >= 18) {
        const int grp = 3 * b + (warp == 8 ? 0 : warp - 17), fsl = 2 * t + ((lane >> 3) & 1), fc = 16 * (grp >> 3) + (grp & 7) + 8 * (lane >> 4);
        const uint32_t fk = lds32(s_key + fsl * 4);
        float hv = 0.f, u2 = 0.f;
        int it = 0;
        if (b < 96) {
            const uint32_t* const fsrc = p.s->rows + KSLOT(fk, fsl) * DM + (fc >> 1);
            uint32_t hw, uw;
            do { hw = ld_poll32(fsrc + 288); uw = ld_poll32(fsrc); if (++it > SPIN_LIMIT) TRAP(); } while (!hw || !uw);
            hv = (fc & 1) ? bf_hi(hw) : bf_lo(hw); u2 = (fc & 1) ? bf_hi(uw) : bf_lo(uw);
        }
        const float rs = rbf(sigmoid_f(__uint_as_float((fk ^ ((uint32_t)((int)~fk >> 31) | 0x80000000u)) & 0xffff0000u)));
        const uint32_t dof = pin(KTOK(fk) * DM + fc), so = pin(grp * 256 + lane);
        if (warp > 17) bar_sync(13, NWRK);
        if (b < 96) {
            delay(warp > 17 ? FDLY : FDLY2);
            float y;
            uint32_t ok;
            float s0, s1, s2, s3;
            do {
                uint2 a[8];
#pragma unroll
                for (int i = 0; i < 8; i++) a[i] = ld_poll64(reinterpret_cast<const uint2*>(p.s->part) + so + 32 * i);
                if (++it > SPIN_LIMIT) TRAP();
                ok = min3(min3(min3(a[0].x, a[0].y, a[1].x), min3(a[1].y, a[2].x, a[2].y), min3(a[3].x, a[3].y, a[4].x)), min3(min3(a[4].y, a[5].x, a[5].y), min3(a[6].x, a[6].y, a[7].x), a[7].y), 1u);
#define S8(c, f) (((c(a[0].f) + c(a[1].f)) + (c(a[2].f) + c(a[3].f))) + ((c(a[4].f) + c(a[5].f)) + (c(a[6].f) + c(a[7].f))))
                s0 = S8(bf_lo, x); s1 = S8(bf_hi, x); s2 = S8(bf_lo, y); s3 = S8(bf_hi, y);
                asm volatile("" : "+f"(s0), "+f"(s1), "+f"(s2), "+f"(s3));
#undef S8
            } while (__any_sync(0xffffffffu, !ok));
            STAMP2(24);
#define HALVE(u, v, m) (((lane & m) ? v : u) + __shfl_xor_sync(0xffffffffu, (lane & m) ? u : v, m))
            const float r0 = HALVE(s0, s2, 16), r1 = HALVE(s1, s3, 16);
            y = HALVE(r0, r1, 8);
            y += __shfl_xor_sync(0xffffffffu, y, 4);
#undef HALVE
            p.out[dof] = __float2bfloat16_rn(hv + rbf(u2 + rbf(rbf(y) * rs)));
        }
    }
    if (warp == 19) asm volatile("cp.async.bulk.wait_group.read 0;\n" ::: "memory");
    if (b == 0 && tid < 8) *reinterpret_cast<volatile unsigned*>(p.s->hint + tid * 32 + 1) = lds32(s_cnt + 4) + 1u;
    STAMP(25);
    }
}

typedef CUresult (*PFN_tmEncode)(CUtensorMap*, CUtensorMapDataType, cuuint32_t, void*, const cuuint64_t*, const cuuint64_t*, const cuuint32_t*,
                                 const cuuint32_t*, CUtensorMapInterleave, CUtensorMapSwizzle, CUtensorMapL2promotion, CUtensorMapFloatOOBfill);

extern "C" void kernel_launch(void* const* d_in, const int* in_sizes, int n_in, void* d_out, int out_size) {
    Params p;
    p.x = (const bf16*)d_in[0];
    p.lar = (const bf16*)d_in[1];
    p.aim = (const bf16*)d_in[2];
    p.cre = (const bf16*)d_in[3];
    p.cim = (const bf16*)d_in[4];
    p.ldt = (const bf16*)d_in[5];
    p.dsk = (const bf16*)d_in[6];
    p.wr = (const bf16*)d_in[8];
    p.out = (bf16*)d_out;
    static PFN_tmEncode enc = nullptr;
    static void* scratch = nullptr;
    if (!enc) {
        cudaFuncSetAttribute(fused_kernel, cudaFuncAttributeMaxDynamicSharedMemorySize, SMEM_TOTAL);
        void* fn = nullptr;
        cudaDriverEntryPointQueryResult qr;
        cudaGetDriverEntryPoint("cuTensorMapEncodeTiled", &fn, cudaEnableDefault, &qr);
        enc = (PFN_tmEncode)fn;
        cudaGetSymbolAddress(&scratch, g_scratch);
    }
    p.s = (Scratch*)scratch;
    Maps tm;
    const cuuint64_t dims[2] = {FF, DM}, strides[1] = {FF * 2};
    const cuuint32_t box[2] = {64, 48}, rbox[2] = {8, 144}, es[2] = {1, 1};
    for (int i = 0; i < 2; i++) {
        enc(&tm.w[i], CU_TENSOR_MAP_DATA_TYPE_BFLOAT16, 2, d_in[9 + i], dims, strides, box, es, CU_TENSOR_MAP_INTERLEAVE_NONE, CU_TENSOR_MAP_SWIZZLE_128B,
            CU_TENSOR_MAP_L2_PROMOTION_NONE, CU_TENSOR_MAP_FLOAT_OOB_FILL_NONE);
        enc(&tm.r[i], CU_TENSOR_MAP_DATA_TYPE_BFLOAT16, 2, d_in[9 + i], dims, strides, rbox, es, CU_TENSOR_MAP_INTERLEAVE_NONE, CU_TENSOR_MAP_SWIZZLE_NONE,
            CU_TENSOR_MAP_L2_PROMOTION_NONE, CU_TENSOR_MAP_FLOAT_OOB_FILL_NONE);
    }
    const cuuint64_t ddims[2] = {DM / 2, FF}, dstrides[1] = {DM * 2};
    const cuuint32_t dbox[2] = {WD_PITCH / 4, 8};
    enc(&tm.d, CU_TENSOR_MAP_DATA_TYPE_UINT32, 2, d_in[11], ddims, dstrides, dbox, es, CU_TENSOR_MAP_INTERLEAVE_NONE, CU_TENSOR_MAP_SWIZZLE_NONE,
        CU_TENSOR_MAP_L2_PROMOTION_L2_128B, CU_TENSOR_MAP_FLOAT_OOB_FILL_NONE);
    const cuuint64_t xdims[4] = {DM, 128, 4, 4}, xstrides[3] = {DM * 8, DM * 2, DM * 1024};
    const cuuint32_t xbox[4] = {8, 128, 4, 2}, xes[4] = {1, 1, 1, 1};
    enc(&tm.x, CU_TENSOR_MAP_DATA_TYPE_BFLOAT16, 4, d_in[0], xdims, xstrides, xbox, xes, CU_TENSOR_MAP_INTERLEAVE_NONE, CU_TENSOR_MAP_SWIZZLE_NONE,
        CU_TENSOR_MAP_L2_PROMOTION_NONE, CU_TENSOR_MAP_FLOAT_OOB_FILL_NONE);
    fused_kernel<<<NCTA, NTHR, SMEM_TOTAL>>>(p, tm);
}
```

```cpp
#include <cuda_runtime.h>
#include <cuda.h>
#include <cuda_fp16.h>
#include <cuda_bf16.h>
#include <stdint.h>

#define LSEQ 2048
#define DM 576
#define NST 128
#define FF 4608
#define NSEL 8
#define NCTA 128
#define NTHR 640
#define NWRK 640

typedef __nv_bfloat16 bf16;

#define SM_WG 0
#define SM_WU 36864
#define SM_WR 73728
#define SM_XC (82944 - 32768)
#define SM_WD 82944
#define WD_PITCH 592
#define SM_Z2 (SM_WD + 10240)
#define SM_XT (SM_PL - 18 * 1152)
#define SM_PL (SM_WD + 46080)
#define PL_HALF 1344
#define PLW_B 2624
#define PL_B (4 * PLW_B)
#define SM_U (SM_PL + 5 * PL_B)
#define UPAD 20
#define ULO_B ((UPAD + 128) * 16)
#define USLOT_B (2 * ULO_B)
#define SM_KW (SM_U + 5 * USLOT_B)
#define KW_B 3712
#define KW_PL 1216
#define KW_P 2400
#define KW_H 3440
#define SM_MISC (SM_KW + 5 * KW_B)
#define SM_LC (SM_MISC + 416)
#define SM_LNP (SM_LC + 768)
#define SM_RX (SM_LNP + 3840)
#define SMEM_TOTAL (SM_RX + 3088)
#define TBW PLW_B
#define SM_OUT SM_PL
#define SM_XS (SM_PL + 18432)
#define XS_PITCH 592
#define SM_GU (SM_PL + 23296)
#define SM_EX (SM_PL + 24576)

struct __align__(128) Scratch {
    unsigned hint[8 * 32];
    unsigned flag[32];
    uint32_t key3[NCTA * 8];
    uint32_t key[NCTA * 8];
    uint32_t stat[LSEQ];
    uint32_t uT[64 * (LSEQ / 2)];
    uint32_t y[(NCTA + 96) * DM * 8];
    uint32_t part[288 * 64 * 8];
    uint32_t rows[(2 * NCTA + NSEL) * DM];
};
__device__ Scratch g_scratch;
#define STAMP(i)
#define STAMPX(i)
#define STAMPY(i)

__device__ __forceinline__ float rbf(float x) {
    uint32_t r;
    asm("cvt.rn.bf16x2.f32 %0, %1, %2;\n" : "=r"(r) : "f"(x), "f"(0.f));
    return __uint_as_float(r);
}
__device__ __forceinline__ uint32_t pack_bf16(float lo, float hi) {
    uint32_t r;
    asm("cvt.rn.bf16x2.f32 %0, %1, %2;\n" : "=r"(r) : "f"(hi), "f"(lo));
    return r;
}
__device__ __forceinline__ uint32_t pack_f16(float lo, float hi) {
    uint32_t r;
    asm("cvt.rn.f16x2.f32 %0, %1, %2;\n" : "=r"(r) : "f"(hi), "f"(lo));
    return r;
}
__device__ __forceinline__ float bf_lo(uint32_t w) { return __uint_as_float(w << 16); }
__device__ __forceinline__ float bf_hi(uint32_t w) { return __uint_as_float(w & 0xffff0000u); }
__device__ __forceinline__ uint32_t hadd2_bf(uint32_t a, uint32_t b) {
    __nv_bfloat162 r = __hadd2_rn(*reinterpret_cast<__nv_bfloat162*>(&a), *reinterpret_cast<__nv_bfloat162*>(&b));
    return *reinterpret_cast<uint32_t*>(&r);
}
__device__ __forceinline__ uint32_t hsub2_bf(uint32_t a, uint32_t b) {
    __nv_bfloat162 r = __hsub2_rn(*reinterpret_cast<__nv_bfloat162*>(&a), *reinterpret_cast<__nv_bfloat162*>(&b));
    return *reinterpret_cast<uint32_t*>(&r);
}
__device__ __forceinline__ uint32_t hmul2_bf(uint32_t a, uint32_t b) {
    __nv_bfloat162 r = __hmul2_rn(*reinterpret_cast<__nv_bfloat162*>(&a), *reinterpret_cast<__nv_bfloat162*>(&b));
    return *reinterpret_cast<uint32_t*>(&r);
}
__device__ __forceinline__ uint32_t hfma2_bf(uint32_t a, uint32_t b, uint32_t c) { uint32_t r; asm("fma.rn.bf16x2 %0, %1, %2, %3;\n" : "=r"(r) : "r"(a), "r"(b), "r"(c)); return r; }
__device__ __forceinline__ uint32_t hmul2(uint32_t a, uint32_t b) { uint32_t r; asm("mul.rn.f16x2 %0, %1, %2;\n" : "=r"(r) : "r"(a), "r"(b)); return r; }
__device__ __forceinline__ uint32_t hadd2(uint32_t a, uint32_t b) { uint32_t r; asm("add.rn.f16x2 %0, %1, %2;\n" : "=r"(r) : "r"(a), "r"(b)); return r; }
__device__ __forceinline__ uint32_t hfma2(uint32_t a, uint32_t b, uint32_t c) { uint32_t r; asm("fma.rn.f16x2 %0, %1, %2, %3;\n" : "=r"(r) : "r"(a), "r"(b), "r"(c)); return r; }
__device__ __forceinline__ uint32_t hfms2(uint32_t a, uint32_t b, uint32_t c) {
    uint32_t r;
    asm("{\n.reg .b32 n;\nneg.f16x2 n, %2;\nfma.rn.f16x2 %0, %1, n, %3;\n}\n" : "=r"(r) : "r"(a), "r"(b), "r"(c));
    return r;
}
__device__ __forceinline__ uint32_t nzw(uint32_t w) { uint32_t r; asm("max.u32 %0, %1, 1;\n" : "=r"(r) : "r"(w)); return r; }
__device__ __forceinline__ uint32_t smem_u32(const void* p) { return (uint32_t)__cvta_generic_to_shared(p); }
__device__ __forceinline__ uint32_t lds32(uint32_t addr) {
    uint32_t v;
    asm volatile("ld.shared.u32 %0, [%1];\n" : "=r"(v) : "r"(addr) : "memory");
    return v;
}
__device__ __forceinline__ uint32_t lds16(uint32_t addr) {
    unsigned short v;
    asm volatile("ld.shared.u16 %0, [%1];\n" : "=h"(v) : "r"(addr) : "memory");
    return v;
}
__device__ __forceinline__ uint2 lds64(uint32_t addr) {
    uint2 v;
    asm volatile("ld.shared.v2.u32 {%0,%1}, [%2];\n" : "=r"(v.x), "=r"(v.y) : "r"(addr) : "memory");
    return v;
}
__device__ __forceinline__ uint4 lds128(uint32_t addr) {
    uint4 v;
    asm volatile("ld.shared.v4.u32 {%0,%1,%2,%3}, [%4];\n" : "=r"(v.x), "=r"(v.y), "=r"(v.z), "=r"(v.w) : "r"(addr) : "memory");
    return v;
}
__device__ __forceinline__ void sts32(uint32_t addr, uint32_t v) { asm volatile("st.shared.u32 [%0], %1;\n" ::"r"(addr), "r"(v) : "memory"); }
__device__ __forceinline__ void sts16(uint32_t addr, uint32_t v) { asm volatile("st.shared.u16 [%0], %1;\n" ::"r"(addr), "h"((unsigned short)v) : "memory"); }
__device__ __forceinline__ void stsf(uint32_t addr, float v) { sts32(addr, __float_as_uint(v)); }
__device__ __forceinline__ void sts64(uint32_t addr, uint32_t a, uint32_t b) { asm volatile("st.shared.v2.u32 [%0], {%1,%2};\n" ::"r"(addr), "r"(a), "r"(b) : "memory"); }
__device__ __forceinline__ void sts128(uint32_t addr, uint32_t a, uint32_t b, uint32_t c, uint32_t d) {
    asm volatile("st.shared.v4.u32 [%0], {%1,%2,%3,%4};\n" ::"r"(addr), "r"(a), "r"(b), "r"(c), "r"(d) : "memory");
}
__device__ __forceinline__ void ldsm_x4(uint32_t& r0, uint32_t& r1, uint32_t& r2, uint32_t& r3, uint32_t addr) {
    asm volatile("ldmatrix.sync.aligned.m8n8.x4.shared.b16 {%0,%1,%2,%3}, [%4];\n"
                 : "=r"(r0), "=r"(r1), "=r"(r2), "=r"(r3) : "r"(addr) : "memory");
}
__device__ __forceinline__ void ldsm_x4_t(uint32_t& r0, uint32_t& r1, uint32_t& r2, uint32_t& r3, uint32_t addr) {
    asm volatile("ldmatrix.sync.aligned.m8n8.x4.trans.shared.b16 {%0,%1,%2,%3}, [%4];\n"
                 : "=r"(r0), "=r"(r1), "=r"(r2), "=r"(r3) : "r"(addr) : "memory");
}
__device__ __forceinline__ void ldsm_x2_t(uint32_t& r0, uint32_t& r1, uint32_t addr) {
    asm volatile("ldmatrix.sync.aligned.m8n8.x2.trans.shared.b16 {%0,%1}, [%2];\n" : "=r"(r0), "=r"(r1) : "r"(addr) : "memory");
}
__device__ __forceinline__ void ldsm_x1_t(uint32_t& r0, uint32_t addr) {
    asm volatile("ldmatrix.sync.aligned.m8n8.x1.trans.shared.b16 {%0}, [%1];\n" : "=r"(r0) : "r"(addr) : "memory");
}
__device__ __forceinline__ void stsm_x4(uint32_t addr, uint32_t r0, uint32_t r1, uint32_t r2, uint32_t r3) {
    asm volatile("stmatrix.sync.aligned.m8n8.x4.shared.b16 [%0], {%1,%2,%3,%4};\n" ::"r"(addr), "r"(r0), "r"(r1), "r"(r2), "r"(r3) : "memory");
}
__device__ __forceinline__ void stsm_x4_t(uint32_t addr, uint32_t r0, uint32_t r1, uint32_t r2, uint32_t r3) {
    asm volatile("stmatrix.sync.aligned.m8n8.x4.trans.shared.b16 [%0], {%1,%2,%3,%4};\n" ::"r"(addr), "r"(r0), "r"(r1), "r"(r2), "r"(r3) : "memory");
}
__device__ __forceinline__ uint32_t movm(uint32_t a) {
    uint32_t d;
    asm volatile("movmatrix.sync.aligned.m8n8.trans.b16 %0, %1;\n" : "=r"(d) : "r"(a));
    return d;
}
__device__ __forceinline__ void mma_f16(float (&c)[4], uint32_t a0, uint32_t a1, uint32_t a2, uint32_t a3, uint32_t b0, uint32_t b1) {
    asm volatile(
        "mma.sync.aligned.m16n8k16.row.col.f32.f16.f16.f32 {%0,%1,%2,%3}, {%4,%5,%6,%7}, {%8,%9}, {%0,%1,%2,%3};\n"
        : "+f"(c[0]), "+f"(c[1]), "+f"(c[2]), "+f"(c[3])
        : "r"(a0), "r"(a1), "r"(a2), "r"(a3), "r"(b0), "r"(b1));
}
__device__ __forceinline__ void mma_bf16(float (&c)[4], uint32_t a0, uint32_t a1, uint32_t a2, uint32_t a3, uint32_t b0, uint32_t b1) {
    asm volatile(
        "mma.sync.aligned.m16n8k16.row.col.f32.bf16.bf16.f32 {%0,%1,%2,%3}, {%4,%5,%6,%7}, {%8,%9}, {%0,%1,%2,%3};\n"
        : "+f"(c[0]), "+f"(c[1]), "+f"(c[2]), "+f"(c[3])
        : "r"(a0), "r"(a1), "r"(a2), "r"(a3), "r"(b0), "r"(b1));
}
__device__ __forceinline__ void mma_bf16_k8(float (&c)[4], uint32_t a0, uint32_t a1, uint32_t b0) {
    asm volatile("mma.sync.aligned.m16n8k8.row.col.f32.bf16.bf16.f32 {%0,%1,%2,%3}, {%4,%5}, {%6}, {%0,%1,%2,%3};\n"
                 : "+f"(c[0]), "+f"(c[1]), "+f"(c[2]), "+f"(c[3]) : "r"(a0), "r"(a1), "r"(b0));
}
__device__ __forceinline__ void bar_sync(int id, int n) { asm volatile("bar.sync %0, %1;\n" ::"r"(id), "r"(n) : "memory"); }
__device__ __forceinline__ void bar_arrive(int id, int n) { asm volatile("bar.arrive %0, %1;\n" ::"r"(id), "r"(n) : "memory"); }
__device__ __forceinline__ bool bar_or(int id, int n, bool v) {
    uint32_t r;
    asm volatile("{\n.reg .pred p, q;\nsetp.ne.u32 p, %3, 0;\nbar.red.or.pred q, %1, %2, p;\nselp.u32 %0, 1, 0, q;\n}\n" : "=r"(r) : "r"(id), "r"(n), "r"((uint32_t)v) : "memory");
    return r;
}
__device__ __forceinline__ uint32_t and3(uint32_t a, uint32_t b, uint32_t c) { uint32_t r; asm("lop3.b32 %0, %1, %2, %3, 0x80;\n" : "=r"(r) : "r"(a), "r"(b), "r"(c)); return r; }
__device__ __forceinline__ uint32_t or3(uint32_t a, uint32_t b, uint32_t c) { uint32_t r; asm("lop3.b32 %0, %1, %2, %3, 0xfe;\n" : "=r"(r) : "r"(a), "r"(b), "r"(c)); return r; }
__device__ __forceinline__ uint32_t min3(uint32_t a, uint32_t b, uint32_t c) { uint32_t r; asm("{\n.reg .u32 t;\nmin.u32 t, %2, %3;\nmin.u32 %0, %1, t;\n}\n" : "=r"(r) : "r"(a), "r"(b), "r"(c)); return r; }
__device__ __forceinline__ uint32_t xor_or(uint32_t a, uint32_t b, uint32_t c) { uint32_t r; asm("lop3.b32 %0, %1, %2, %3, 0x7e;\n" : "=r"(r) : "r"(a), "r"(b), "r"(c)); return r; }
__device__ __forceinline__ uint32_t pin(uint32_t v) { uint32_t r; asm volatile("shfl.sync.bfly.b32 %0, %1, 0, 0x1f, 0xffffffff;\n" : "=r"(r) : "r"(v) : "memory"); return r; }
__device__ __forceinline__ uint4 ld_poll(const void* p) {
    uint4 v;
    asm volatile("ld.relaxed.gpu.global.v4.u32 {%0,%1,%2,%3}, [%4];\n" : "=r"(v.x), "=r"(v.y), "=r"(v.z), "=r"(v.w) : "l"(p) : "memory");
    return v;
}
__device__ __forceinline__ uint2 ld_poll64(const void* p) {
    uint2 v;
    asm volatile("ld.relaxed.gpu.global.v2.u32 {%0,%1}, [%2];\n" : "=r"(v.x), "=r"(v.y) : "l"(p) : "memory");
    return v;
}
__device__ __forceinline__ uint32_t ld_poll32(const void* p) {
    uint32_t v;
    asm volatile("ld.relaxed.gpu.global.u32 %0, [%1];\n" : "=r"(v) : "l"(p) : "memory");
    return v;
}
__device__ __forceinline__ uint32_t ld_acquire32(const void* p) {
    uint32_t v;
    asm volatile("ld.acquire.gpu.global.u32 %0, [%1];\n" : "=r"(v) : "l"(p) : "memory");
    return v;
}
__device__ __forceinline__ uint2 ldo64(const void* p) {
    uint2 v;
    asm volatile("ld.relaxed.cta.global.v2.u32 {%0,%1}, [%2];\n" : "=r"(v.x), "=r"(v.y) : "l"(p) : "memory");
    return v;
}
__device__ __forceinline__ uint32_t ldo16(const void* p) {
    uint32_t v;
    asm volatile("ld.relaxed.cta.global.u16 %0, [%1];\n" : "=r"(v) : "l"(p) : "memory");
    return v;
}
__device__ __forceinline__ void stg128(void* p, uint32_t a, uint32_t b, uint32_t c, uint32_t d) {
    asm volatile("st.global.v4.u32 [%0], {%1,%2,%3,%4};\n" ::"l"(p), "r"(a), "r"(b), "r"(c), "r"(d) : "memory");
}
__device__ __forceinline__ void stg64(void* p, uint32_t a, uint32_t b) { asm volatile("st.global.v2.u32 [%0], {%1,%2};\n" ::"l"(p), "r"(a), "r"(b) : "memory"); }
__device__ __forceinline__ uint32_t min4(const uint4& v) { return min(min(v.x, v.y), min(v.z, v.w)); }
#define SPIN_LIMIT (1 << 21)
#define TRAP() __trap()
__device__ __forceinline__ void mbar_init(uint32_t bar, uint32_t cnt) { asm volatile("mbarrier.init.shared::cta.b64 [%0], %1;\n" ::"r"(bar), "r"(cnt) : "memory"); }
__device__ __forceinline__ void mbar_expect(uint32_t bar, uint32_t bytes) {
    asm volatile("mbarrier.arrive.expect_tx.shared::cta.b64 _, [%0], %1;\n" ::"r"(bar), "r"(bytes) : "memory");
}
__device__ __forceinline__ void mbar_arrive(uint32_t bar) { asm volatile("mbarrier.arrive.shared::cta.b64 _, [%0];\n" ::"r"(bar) : "memory"); }
__device__ __forceinline__ void mbar_wait(uint32_t bar) {
    asm volatile(
        "{\n.reg .pred p;\n"
        "W_%=:\n"
        "mbarrier.try_wait.parity.shared::cta.b64 p, [%0], 0;\n"
        "@!p bra W_%=;\n}\n" ::"r"(bar) : "memory");
}
__device__ __forceinline__ void bulk_g2s(uint32_t dst, const void* src, uint32_t bytes, uint32_t bar) {
    asm volatile("cp.async.bulk.shared::cluster.global.mbarrier::complete_tx::bytes [%0], [%1], %2, [%3];\n" ::"r"(dst), "l"(src), "r"(bytes), "r"(bar) : "memory");
}
__device__ __forceinline__ void bulk_s2g(void* dst, uint32_t src, uint32_t bytes) {
    asm volatile("cp.async.bulk.global.shared::cta.bulk_group [%0], [%1], %2;\ncp.async.bulk.commit_group;\n" ::"l"(dst), "r"(src), "r"(bytes) : "memory");
}
__device__ __forceinline__ void bulk_s2g_nc(void* dst, uint32_t src, uint32_t bytes) {
    asm volatile("cp.async.bulk.global.shared::cta.bulk_group [%0], [%1], %2;\n" ::"l"(dst), "r"(src), "r"(bytes) : "memory");
}
__device__ __forceinline__ void tma_2d(uint32_t dst, const CUtensorMap* tm, int c0, int c1, uint32_t bar) {
    asm volatile("cp.async.bulk.tensor.2d.shared::cluster.global.mbarrier::complete_tx::bytes [%0], [%1, {%3, %4}], [%2];\n"
                 ::"r"(dst), "l"(tm), "r"(bar), "r"(c0), "r"(c1) : "memory");
}
__device__ __forceinline__ void tma_4d_mc(uint32_t dst, const CUtensorMap* tm, int c0, int c3, uint32_t bar) {
    asm volatile("cp.async.bulk.tensor.4d.shared::cluster.global.mbarrier::complete_tx::bytes.multicast::cluster [%0], [%1, {%3, %4, %4, %5}], [%2], %6;\n"
                 ::"r"(dst), "l"(tm), "r"(bar), "r"(c0), "r"(0), "r"(c3), "h"((unsigned short)3) : "memory");
}
__device__ __forceinline__ bool elect_one() {
    uint32_t r;
    asm volatile("{\n.reg .pred p;\nelect.sync _|p, 0xffffffff;\nselp.u32 %0, 1, 0, p;\n}\n" : "=r"(r));
    return r;
}
__device__ __forceinline__ void delay(uint32_t clks) {
    uint32_t t0, t1;
    asm volatile("mov.u32 %0, %%clock;" : "=r"(t0) :: "memory");
    do { asm volatile("mov.u32 %0, %%clock;" : "=r"(t1) :: "memory"); } while (t1 - t0 < clks);
}
__device__ __forceinline__ void fence_async() { asm volatile("fence.proxy.async.shared::cta;\n" ::: "memory"); }

__device__ __forceinline__ float2 cmul(float2 a, float2 b) {
    return make_float2(fmaf(a.x, b.x, -a.y * b.y), fmaf(a.x, b.y, a.y * b.x));
}
__device__ __forceinline__ float2 csq(float2 a) {
    float p = a.x * a.y;
    return make_float2(fmaf(a.x, a.x, -a.y * a.y), p + p);
}
__device__ __forceinline__ float ex2_approx(float x) { float r; asm("ex2.approx.ftz.f32 %0, %1;\n" : "=f"(r) : "f"(x)); return r; }
__device__ __forceinline__ float exp_bf(float x) { return rbf(ex2_approx(__fmul_ru(x, 1.4426950408889634f))); }
__device__ __forceinline__ float2 cexp_e(float lr2, float li, float e) {
    const float m = ex2_approx(lr2 * e);
    return make_float2(m * __cosf(li * e), m * __sinf(li * e));
}
__device__ __forceinline__ float rcp_approx(float x) { float r; asm("rcp.approx.ftz.f32 %0, %1;\n" : "=f"(r) : "f"(x)); return r; }
__device__ __forceinline__ float sigmoid_f(float x) { return rcp_approx(1.0f + ex2_approx(x * -1.4426950408889634f)); }
__device__ __forceinline__ float sqrt_approx(float x) { float r; asm("sqrt.approx.ftz.f32 %0, %1;\n" : "=f"(r) : "f"(x)); return r; }

__device__ __forceinline__ void wg_fence() { asm volatile("wgmma.fence.sync.aligned;\n" ::: "memory"); }
__device__ __forceinline__ void wg_commit() { asm volatile("wgmma.commit_group.sync.aligned;\n" ::: "memory"); }
__device__ __forceinline__ void wg_wait0() { asm volatile("wgmma.wait_group.sync.aligned 0;\n" ::: "memory"); }
template <int T> __device__ __forceinline__ void wg_mma(float (&acc)[16][4], const uint32_t* a, uint64_t desc);
template <int T> __device__ __forceinline__ void wg_first(float (&acc)[16][4], const uint32_t* a, uint64_t desc);
template <> __device__ __forceinline__ void wg_mma<0>(float (&acc)[16][4], const uint32_t* a, uint64_t desc) {
    asm volatile("wgmma.mma_async.sync.aligned.m64n128k16.f32.f16.f16 {%0,%1,%2,%3,%4,%5,%6,%7,%8,%9,%10,%11,%12,%13,%14,%15,%16,%17,%18,%19,%20,%21,%22,%23,%24,%25,%26,%27,%28,%29,%30,%31,%32,%33,%34,%35,%36,%37,%38,%39,%40,%41,%42,%43,%44,%45,%46,%47,%48,%49,%50,%51,%52,%53,%54,%55,%56,%57,%58,%59,%60,%61,%62,%63}, {%64,%65,%66,%67}, %68, 1, 1, 1, 0;\n"
                 : "+f"(acc[0][0]), "+f"(acc[0][1]), "+f"(acc[0][2]), "+f"(acc[0][3]), "+f"(acc[1][0]), "+f"(acc[1][1]), "+f"(acc[1][2]), "+f"(acc[1][3]), "+f"(acc[2][0]), "+f"(acc[2][1]), "+f"(acc[2][2]), "+f"(acc[2][3]), "+f"(acc[3][0]), "+f"(acc[3][1]), "+f"(acc[3][2]), "+f"(acc[3][3]), "+f"(acc[4][0]), "+f"(acc[4][1]), "+f"(acc[4][2]), "+f"(acc[4][3]), "+f"(acc[5][0]), "+f"(acc[5][1]), "+f"(acc[5][2]), "+f"(acc[5][3]), "+f"(acc[6][0]), "+f"(acc[6][1]), "+f"(acc[6][2]), "+f"(acc[6][3]), "+f"(acc[7][0]), "+f"(acc[7][1]), "+f"(acc[7][2]), "+f"(acc[7][3]), "+f"(acc[8][0]), "+f"(acc[8][1]), "+f"(acc[8][2]), "+f"(acc[8][3]), "+f"(acc[9][0]), "+f"(acc[9][1]), "+f"(acc[9][2]), "+f"(acc[9][3]), "+f"(acc[10][0]), "+f"(acc[10][1]), "+f"(acc[10][2]), "+f"(acc[10][3]), "+f"(acc[11][0]), "+f"(acc[11][1]), "+f"(acc[11][2]), "+f"(acc[11][3]), "+f"(acc[12][0]), "+f"(acc[12][1]), "+f"(acc[12][2]), "+f"(acc[12][3]), "+f"(acc[13][0]), "+f"(acc[13][1]), "+f"(acc[13][2]), "+f"(acc[13][3]), "+f"(acc[14][0]), "+f"(acc[14][1]), "+f"(acc[14][2]), "+f"(acc[14][3]), "+f"(acc[15][0]), "+f"(acc[15][1]), "+f"(acc[15][2]), "+f"(acc[15][3])
                 : "r"(a[0]), "r"(a[1]), "r"(a[2]), "r"(a[3]), "l"(desc));
}
template <> __device__ __forceinline__ void wg_mma<2>(float (&acc)[16][4], const uint32_t* a, uint64_t desc) {
    asm volatile("wgmma.mma_async.sync.aligned.m64n112k16.f32.f16.f16 {%0,%1,%2,%3,%4,%5,%6,%7,%8,%9,%10,%11,%12,%13,%14,%15,%16,%17,%18,%19,%20,%21,%22,%23,%24,%25,%26,%27,%28,%29,%30,%31,%32,%33,%34,%35,%36,%37,%38,%39,%40,%41,%42,%43,%44,%45,%46,%47,%48,%49,%50,%51,%52,%53,%54,%55}, {%56,%57,%58,%59}, %60, 1, 1, 1, 0;\n"
                 : "+f"(acc[2][0]), "+f"(acc[2][1]), "+f"(acc[2][2]), "+f"(acc[2][3]), "+f"(acc[3][0]), "+f"(acc[3][1]), "+f"(acc[3][2]), "+f"(acc[3][3]), "+f"(acc[4][0]), "+f"(acc[4][1]), "+f"(acc[4][2]), "+f"(acc[4][3]), "+f"(acc[5][0]), "+f"(acc[5][1]), "+f"(acc[5][2]), "+f"(acc[5][3]), "+f"(acc[6][0]), "+f"(acc[6][1]), "+f"(acc[6][2]), "+f"(acc[6][3]), "+f"(acc[7][0]), "+f"(acc[7][1]), "+f"(acc[7][2]), "+f"(acc[7][3]), "+f"(acc[8][0]), "+f"(acc[8][1]), "+f"(acc[8][2]), "+f"(acc[8][3]), "+f"(acc[9][0]), "+f"(acc[9][1]), "+f"(acc[9][2]), "+f"(acc[9][3]), "+f"(acc[10][0]), "+f"(acc[10][1]), "+f"(acc[10][2]), "+f"(acc[10][3]), "+f"(acc[11][0]), "+f"(acc[11][1]), "+f"(acc[11][2]), "+f"(acc[11][3]), "+f"(acc[12][0]), "+f"(acc[12][1]), "+f"(acc[12][2]), "+f"(acc[12][3]), "+f"(acc[13][0]), "+f"(acc[13][1]), "+f"(acc[13][2]), "+f"(acc[13][3]), "+f"(acc[14][0]), "+f"(acc[14][1]), "+f"(acc[14][2]), "+f"(acc[14][3]), "+f"(acc[15][0]), "+f"(acc[15][1]), "+f"(acc[15][2]), "+f"(acc[15][3])
                 : "r"(a[0]), "r"(a[1]), "r"(a[2]), "r"(a[3]), "l"(desc));
}
template <> __device__ __forceinline__ void wg_mma<4>(float (&acc)[16][4], const uint32_t* a, uint64_t desc) {
    asm volatile("wgmma.mma_async.sync.aligned.m64n96k16.f32.f16.f16 {%0,%1,%2,%3,%4,%5,%6,%7,%8,%9,%10,%11,%12,%13,%14,%15,%16,%17,%18,%19,%20,%21,%22,%23,%24,%25,%26,%27,%28,%29,%30,%31,%32,%33,%34,%35,%36,%37,%38,%39,%40,%41,%42,%43,%44,%45,%46,%47}, {%48,%49,%50,%51}, %52, 1, 1, 1, 0;\n"
                 : "+f"(acc[4][0]), "+f"(acc[4][1]), "+f"(acc[4][2]), "+f"(acc[4][3]), "+f"(acc[5][0]), "+f"(acc[5][1]), "+f"(acc[5][2]), "+f"(acc[5][3]), "+f"(acc[6][0]), "+f"(acc[6][1]), "+f"(acc[6][2]), "+f"(acc[6][3]), "+f"(acc[7][0]), "+f"(acc[7][1]), "+f"(acc[7][2]), "+f"(acc[7][3]), "+f"(acc[8][0]), "+f"(acc[8][1]), "+f"(acc[8][2]), "+f"(acc[8][3]), "+f"(acc[9][0]), "+f"(acc[9][1]), "+f"(acc[9][2]), "+f"(acc[9][3]), "+f"(acc[10][0]), "+f"(acc[10][1]), "+f"(acc[10][2]), "+f"(acc[10][3]), "+f"(acc[11][0]), "+f"(acc[11][1]), "+f"(acc[11][2]), "+f"(acc[11][3]), "+f"(acc[12][0]), "+f"(acc[12][1]), "+f"(acc[12][2]), "+f"(acc[12][3]), "+f"(acc[13][0]), "+f"(acc[13][1]), "+f"(acc[13][2]), "+f"(acc[13][3]), "+f"(acc[14][0]), "+f"(acc[14][1]), "+f"(acc[14][2]), "+f"(acc[14][3]), "+f"(acc[15][0]), "+f"(acc[15][1]), "+f"(acc[15][2]), "+f"(acc[15][3])
                 : "r"(a[0]), "r"(a[1]), "r"(a[2]), "r"(a[3]), "l"(desc));
}
template <> __device__ __forceinline__ void wg_mma<6>(float (&acc)[16][4], const uint32_t* a, uint64_t desc) {
    asm volatile("wgmma.mma_async.sync.aligned.m64n80k16.f32.f16.f16 {%0,%1,%2,%3,%4,%5,%6,%7,%8,%9,%10,%11,%12,%13,%14,%15,%16,%17,%18,%19,%20,%21,%22,%23,%24,%25,%26,%27,%28,%29,%30,%31,%32,%33,%34,%35,%36,%37,%38,%39}, {%40,%41,%42,%43}, %44, 1, 1, 1, 0;\n"
                 : "+f"(acc[6][0]), "+f"(acc[6][1]), "+f"(acc[6][2]), "+f"(acc[6][3]), "+f"(acc[7][0]), "+f"(acc[7][1]), "+f"(acc[7][2]), "+f"(acc[7][3]), "+f"(acc[8][0]), "+f"(acc[8][1]), "+f"(acc[8][2]), "+f"(acc[8][3]), "+f"(acc[9][0]), "+f"(acc[9][1]), "+f"(acc[9][2]), "+f"(acc[9][3]), "+f"(acc[10][0]), "+f"(acc[10][1]), "+f"(acc[10][2]), "+f"(acc[10][3]), "+f"(acc[11][0]), "+f"(acc[11][1]), "+f"(acc[11][2]), "+f"(acc[11][3]), "+f"(acc[12][0]), "+f"(acc[12][1]), "+f"(acc[12][2]), "+f"(acc[12][3]), "+f"(acc[13][0]), "+f"(acc[13][1]), "+f"(acc[13][2]), "+f"(acc[13][3]), "+f"(acc[14][0]), "+f"(acc[14][1]), "+f"(acc[14][2]), "+f"(acc[14][3]), "+f"(acc[15][0]), "+f"(acc[15][1]), "+f"(acc[15][2]), "+f"(acc[15][3])
                 : "r"(a[0]), "r"(a[1]), "r"(a[2]), "r"(a[3]), "l"(desc));
}
template <> __device__ __forceinline__ void wg_mma<8>(float (&acc)[16][4], const uint32_t* a, uint64_t desc) {
    asm volatile("wgmma.mma_async.sync.aligned.m64n64k16.f32.f16.f16 {%0,%1,%2,%3,%4,%5,%6,%7,%8,%9,%10,%11,%12,%13,%14,%15,%16,%17,%18,%19,%20,%21,%22,%23,%24,%25,%26,%27,%28,%29,%30,%31}, {%32,%33,%34,%35}, %36, 1, 1, 1, 0;\n"
                 : "+f"(acc[8][0]), "+f"(acc[8][1]), "+f"(acc[8][2]), "+f"(acc[8][3]), "+f"(acc[9][0]), "+f"(acc[9][1]), "+f"(acc[9][2]), "+f"(acc[9][3]), "+f"(acc[10][0]), "+f"(acc[10][1]), "+f"(acc[10][2]), "+f"(acc[10][3]), "+f"(acc[11][0]), "+f"(acc[11][1]), "+f"(acc[11][2]), "+f"(acc[11][3]), "+f"(acc[12][0]), "+f"(acc[12][1]), "+f"(acc[12][2]), "+f"(acc[12][3]), "+f"(acc[13][0]), "+f"(acc[13][1]), "+f"(acc[13][2]), "+f"(acc[13][3]), "+f"(acc[14][0]), "+f"(acc[14][1]), "+f"(acc[14][2]), "+f"(acc[14][3]), "+f"(acc[15][0]), "+f"(acc[15][1]), "+f"(acc[15][2]), "+f"(acc[15][3])
                 : "r"(a[0]), "r"(a[1]), "r"(a[2]), "r"(a[3]), "l"(desc));
}
template <> __device__ __forceinline__ void wg_mma<10>(float (&acc)[16][4], const uint32_t* a, uint64_t desc) {
    asm volatile("wgmma.mma_async.sync.aligned.m64n48k16.f32.f16.f16 {%0,%1,%2,%3,%4,%5,%6,%7,%8,%9,%10,%11,%12,%13,%14,%15,%16,%17,%18,%19,%20,%21,%22,%23}, {%24,%25,%26,%27}, %28, 1, 1, 1, 0;\n"
                 : "+f"(acc[10][0]), "+f"(acc[10][1]), "+f"(acc[10][2]), "+f"(acc[10][3]), "+f"(acc[11][0]), "+f"(acc[11][1]), "+f"(acc[11][2]), "+f"(acc[11][3]), "+f"(acc[12][0]), "+f"(acc[12][1]), "+f"(acc[12][2]), "+f"(acc[12][3]), "+f"(acc[13][0]), "+f"(acc[13][1]), "+f"(acc[13][2]), "+f"(acc[13][3]), "+f"(acc[14][0]), "+f"(acc[14][1]), "+f"(acc[14][2]), "+f"(acc[14][3]), "+f"(acc[15][0]), "+f"(acc[15][1]), "+f"(acc[15][2]), "+f"(acc[15][3])
                 : "r"(a[0]), "r"(a[1]), "r"(a[2]), "r"(a[3]), "l"(desc));
}
template <> __device__ __forceinline__ void wg_mma<12>(float (&acc)[16][4], const uint32_t* a, uint64_t desc) {
    asm volatile("wgmma.mma_async.sync.aligned.m64n32k16.f32.f16.f16 {%0,%1,%2,%3,%4,%5,%6,%7,%8,%9,%10,%11,%12,%13,%14,%15}, {%16,%17,%18,%19}, %20, 1, 1, 1, 0;\n"
                 : "+f"(acc[12][0]), "+f"(acc[12][1]), "+f"(acc[12][2]), "+f"(acc[12][3]), "+f"(acc[13][0]), "+f"(acc[13][1]), "+f"(acc[13][2]), "+f"(acc[13][3]), "+f"(acc[14][0]), "+f"(acc[14][1]), "+f"(acc[14][2]), "+f"(acc[14][3]), "+f"(acc[15][0]), "+f"(acc[15][1]), "+f"(acc[15][2]), "+f"(acc[15][3])
                 : "r"(a[0]), "r"(a[1]), "r"(a[2]), "r"(a[3]), "l"(desc));
}
template <> __device__ __forceinline__ void wg_mma<14>(float (&acc)[16][4], const uint32_t* a, uint64_t desc) {
    asm volatile("wgmma.mma_async.sync.aligned.m64n16k16.f32.f16.f16 {%0,%1,%2,%3,%4,%5,%6,%7}, {%8,%9,%10,%11}, %12, 1, 1, 1, 0;\n"
                 : "+f"(acc[14][0]), "+f"(acc[14][1]), "+f"(acc[14][2]), "+f"(acc[14][3]), "+f"(acc[15][0]), "+f"(acc[15][1]), "+f"(acc[15][2]), "+f"(acc[15][3])
                 : "r"(a[0]), "r"(a[1]), "r"(a[2]), "r"(a[3]), "l"(desc));
}
template <> __device__ __forceinline__ void wg_first<0>(float (&acc)[16][4], const uint32_t* a, uint64_t desc) {
    asm volatile("wgmma.mma_async.sync.aligned.m64n128k16.f32.f16.f16 {%0,%1,%2,%3,%4,%5,%6,%7,%8,%9,%10,%11,%12,%13,%14,%15,%16,%17,%18,%19,%20,%21,%22,%23,%24,%25,%26,%27,%28,%29,%30,%31,%32,%33,%34,%35,%36,%37,%38,%39,%40,%41,%42,%43,%44,%45,%46,%47,%48,%49,%50,%51,%52,%53,%54,%55,%56,%57,%58,%59,%60,%61,%62,%63}, {%64,%65,%66,%67}, %68, 0, 1, 1, 0;\n"
                 : "=f"(acc[0][0]), "=f"(acc[0][1]), "=f"(acc[0][2]), "=f"(acc[0][3]), "=f"(acc[1][0]), "=f"(acc[1][1]), "=f"(acc[1][2]), "=f"(acc[1][3]), "=f"(acc[2][0]), "=f"(acc[2][1]), "=f"(acc[2][2]), "=f"(acc[2][3]), "=f"(acc[3][0]), "=f"(acc[3][1]), "=f"(acc[3][2]), "=f"(acc[3][3]), "=f"(acc[4][0]), "=f"(acc[4][1]), "=f"(acc[4][2]), "=f"(acc[4][3]), "=f"(acc[5][0]), "=f"(acc[5][1]), "=f"(acc[5][2]), "=f"(acc[5][3]), "=f"(acc[6][0]), "=f"(acc[6][1]), "=f"(acc[6][2]), "=f"(acc[6][3]), "=f"(acc[7][0]), "=f"(acc[7][1]), "=f"(acc[7][2]), "=f"(acc[7][3]), "=f"(acc[8][0]), "=f"(acc[8][1]), "=f"(acc[8][2]), "=f"(acc[8][3]), "=f"(acc[9][0]), "=f"(acc[9][1]), "=f"(acc[9][2]), "=f"(acc[9][3]), "=f"(acc[10][0]), "=f"(acc[10][1]), "=f"(acc[10][2]), "=f"(acc[10][3]), "=f"(acc[11][0]), "=f"(acc[11][1]), "=f"(acc[11][2]), "=f"(acc[11][3]), "=f"(acc[12][0]), "=f"(acc[12][1]), "=f"(acc[12][2]), "=f"(acc[12][3]), "=f"(acc[13][0]), "=f"(acc[13][1]), "=f"(acc[13][2]), "=f"(acc[13][3]), "=f"(acc[14][0]), "=f"(acc[14][1]), "=f"(acc[14][2]), "=f"(acc[14][3]), "=f"(acc[15][0]), "=f"(acc[15][1]), "=f"(acc[15][2]), "=f"(acc[15][3])
                 : "r"(a[0]), "r"(a[1]), "r"(a[2]), "r"(a[3]), "l"(desc));
}
template <> __device__ __forceinline__ void wg_first<4>(float (&acc)[16][4], const uint32_t* a, uint64_t desc) {
    asm volatile("wgmma.mma_async.sync.aligned.m64n96k16.f32.f16.f16 {%0,%1,%2,%3,%4,%5,%6,%7,%8,%9,%10,%11,%12,%13,%14,%15,%16,%17,%18,%19,%20,%21,%22,%23,%24,%25,%26,%27,%28,%29,%30,%31,%32,%33,%34,%35,%36,%37,%38,%39,%40,%41,%42,%43,%44,%45,%46,%47}, {%48,%49,%50,%51}, %52, 0, 1, 1, 0;\n"
                 : "=f"(acc[4][0]), "=f"(acc[4][1]), "=f"(acc[4][2]), "=f"(acc[4][3]), "=f"(acc[5][0]), "=f"(acc[5][1]), "=f"(acc[5][2]), "=f"(acc[5][3]), "=f"(acc[6][0]), "=f"(acc[6][1]), "=f"(acc[6][2]), "=f"(acc[6][3]), "=f"(acc[7][0]), "=f"(acc[7][1]), "=f"(acc[7][2]), "=f"(acc[7][3]), "=f"(acc[8][0]), "=f"(acc[8][1]), "=f"(acc[8][2]), "=f"(acc[8][3]), "=f"(acc[9][0]), "=f"(acc[9][1]), "=f"(acc[9][2]), "=f"(acc[9][3]), "=f"(acc[10][0]), "=f"(acc[10][1]), "=f"(acc[10][2]), "=f"(acc[10][3]), "=f"(acc[11][0]), "=f"(acc[11][1]), "=f"(acc[11][2]), "=f"(acc[11][3]), "=f"(acc[12][0]), "=f"(acc[12][1]), "=f"(acc[12][2]), "=f"(acc[12][3]), "=f"(acc[13][0]), "=f"(acc[13][1]), "=f"(acc[13][2]), "=f"(acc[13][3]), "=f"(acc[14][0]), "=f"(acc[14][1]), "=f"(acc[14][2]), "=f"(acc[14][3]), "=f"(acc[15][0]), "=f"(acc[15][1]), "=f"(acc[15][2]), "=f"(acc[15][3])
                 : "r"(a[0]), "r"(a[1]), "r"(a[2]), "r"(a[3]), "l"(desc));
}

#define SDLY 1500
#define UDLY 1400
#define KDLY 850
#define FDLY 950
#define FDLY2 350
#define DDLY 450
#define WDLY 500
#define HW 15
#define FIX(v) do { if ((v) == 1u) TRAP(); } while (0)
#define STAMPW(i) STAMPY(i)
#define STAMP2(i) STAMP(i)
#undef STAMPX
#define STAMPX(i)
struct Params {
    const bf16 *x, *lar, *aim, *cre, *cim, *ldt, *dsk;
    Scratch* s;
    const bf16* wr;
    bf16* out;
};
struct Maps { CUtensorMap x, w[2], r[2], d; };

#define TOK(g) (2 * (g) - ((g) & 1))
#define ROWTOK(r) (TOK((r) & 7) + (((r) >> 2) & 2))
__device__ __forceinline__ void ln_partial(const uint32_t (&H)[2][4], float (&d)[2][4]) {
#pragma unroll
    for (int i = 0; i < 8; i++) d[i >> 2][i & 3] = 0.f;
#pragma unroll
    for (int k = 0; k < 4; k++)
#pragma unroll
        for (int hf = 0; hf < 2; hf++) mma_bf16_k8(d[hf], H[hf][k], 0x3f803f80u, H[hf][k]);
}
__device__ __forceinline__ float sum18(uint32_t a) {
    const uint4 p = lds128(a), q = lds128(a + 16), r = lds128(a + 32), s = lds128(a + 48);
    const uint2 u = lds64(a + 64);
#define F(x) __uint_as_float(x)
    return (((F(p.x) + F(p.y)) + (F(p.z) + F(p.w))) + ((F(q.x) + F(q.y)) + (F(q.z) + F(q.w)))) +
           (((F(r.x) + F(r.y)) + (F(r.z) + F(r.w))) + ((F(s.x) + F(s.y)) + (F(s.z) + F(s.w))) + (F(u.x) + F(u.y)));
#undef F
}
__device__ __forceinline__ void ln_stats(float sm, float sq, float& mb, float& sd) {
    const float m0 = sm * (1.0f / 576.0f);
    const float mean = fmaf(fmaf(-m0, 576.0f, sm), 1.0f / 576.0f, m0);
    const float var = fmaxf(fmaf(-mean, mean, sq * (1.0f / 576.0f)), 0.f);
    mb = rbf(mean);
    sd = rbf(sqrt_approx(rbf(rbf(var) + 1e-5f)));
}
__device__ __forceinline__ void ln_finish(float v, int lane, float& mb, float& rc) {
    const float o = __shfl_xor_sync(0xffffffffu, v, 16);
    float sd;
    ln_stats(lane < 16 ? v : o, lane < 16 ? o : v, mb, sd);
    rc = rcp_approx(sd);
}
__device__ __forceinline__ uint32_t ln_apply(uint32_t w, uint32_t m2, uint32_t rh, uint32_t rl) {
    const uint32_t d = hsub2_bf(w, m2);
    return hfma2_bf(d, rh, hmul2_bf(d, rl));
}
__device__ __forceinline__ void stat_store(uint32_t a, float mb, float rc, uint32_t extra) {
    const float rh = rbf(rc);
    sts64(a, (__float_as_uint(mb) >> 16) | (extra << 16), pack_bf16(rh, rc - rh));
}
#define STAT_M(s) __byte_perm((s).x, (s).x, 0x1010)
#define STAT_H(s) __byte_perm((s).y, (s).y, 0x1010)
#define STAT_L(s) __byte_perm((s).y, (s).y, 0x3232)

__device__ __forceinline__ void hcmul(uint32_t re, uint32_t im, uint32_t zx, uint32_t zy, uint32_t& ore, uint32_t& oim) {
    ore = hfms2(im, zy, hmul2(re, zx));
    oim = hfma2(re, zy, hmul2(im, zx));
}

struct KGen {
    uint32_t A[2][4][4];
    float2 z1, z8, z64, z128, T[9];
};
__device__ __forceinline__ void kgen_setup(KGen& k, float lar, float aim, float dt) {
    const float lr2 = -(exp_bf(lar) * dt) * 1.4426950408889634f, li = aim * dt;
    k.z1 = cexp_e(lr2, li, 1.0f);
    k.z8 = cexp_e(lr2, li, 8.0f);
    k.z64 = cexp_e(lr2, li, 64.0f);
}
__device__ __forceinline__ void kgen_rows(KGen& k, uint32_t tb, int lane) {
    const float2 z8 = k.z8, z64 = k.z64;
    const uint32_t row = tb + lane * 16;
    k.z128 = csq(z64);
    const float2 z16 = csq(z8), z24 = cmul(z16, z8), z32 = csq(z16), z40 = cmul(z32, z8), z48 = csq(z24), z56 = cmul(z32, z24);
    uint32_t re[4], im[4], a[4], b[4];
    re[0] = pack_f16(1.0f, z8.x); im[0] = pack_f16(0.0f, z8.y);
    re[1] = pack_f16(z16.x, z24.x); im[1] = pack_f16(z16.y, z24.y);
    re[2] = pack_f16(z32.x, z40.x); im[2] = pack_f16(z32.y, z40.y);
    re[3] = pack_f16(z48.x, z56.x); im[3] = pack_f16(z48.y, z56.y);
    sts128(row, re[0], re[1], re[2], re[3]);
    sts128(row + 1024, im[0], im[1], im[2], im[3]);
    const uint32_t zx = pack_f16(z64.x, z64.x), zy = pack_f16(z64.y, z64.y), zw = pack_f16(k.z128.x, k.z128.y);
#pragma unroll
    for (int j = 0; j < 4; j++) hcmul(re[j], im[j], zx, zy, a[j], b[j]);
    sts128(row + 512, a[0], a[1], a[2], a[3]);
    sts128(row + 1536, b[0], b[1], b[2], b[3]);
    const int mi = lane >> 3;
    const uint32_t zd = tb + 2048 + mi * 16;
    sts16(tb + 2048 + lane * 2, zw); sts16(tb + 2112 + lane * 2, zw >> 16);
    __syncwarp();
    const uint32_t ad = tb + (lane & 7) * 16 + mi * 512;
    ldsm_x4(a[0], a[1], a[2], a[3], zd);
    ldsm_x4(b[0], b[1], b[2], b[3], zd + 64);
#pragma unroll
    for (int ks = 0; ks < 4; ks++) {
        ldsm_x4_t(k.A[0][ks][0], k.A[0][ks][1], k.A[0][ks][2], k.A[0][ks][3], ad + ks * 128);
        hcmul(k.A[0][ks][0], k.A[0][ks][2], a[ks], b[ks], k.A[1][ks][0], k.A[1][ks][2]);
        hcmul(k.A[0][ks][1], k.A[0][ks][3], a[ks], b[ks], k.A[1][ks][1], k.A[1][ks][3]);
    }
}
__device__ __forceinline__ void kgen_chain(KGen& k, uint32_t cr, uint32_t ci, float cs) {
    k.T[0] = make_float2(bf_lo(cr) * cs, -bf_lo(ci) * cs);
    const float2 y1 = make_float2(k.z1.x, -k.z1.y);
#pragma unroll
    for (int c = 1; c < 8; c++) k.T[c] = cmul(k.T[c - 1], y1);
    k.T[8] = cmul(k.T[0], make_float2(k.z8.x, -k.z8.y));
}
__device__ __forceinline__ void kgen_cols(KGen& k, uint32_t tb, uint32_t t5, int lane) {
    const uint32_t row = tb + lane * 16;
    const float2 (&T)[9] = k.T;
    const float2 y128 = make_float2(k.z128.x, -k.z128.y);
    const float2 y256 = csq(y128), y512 = csq(y256), y768 = cmul(y512, y256), y1024 = csq(y512);
    const float2 c1032 = cmul(T[8], y1024);
    __syncwarp();
    sts128(row, pack_f16(T[0].x, T[1].x), pack_f16(T[2].x, T[3].x), pack_f16(T[4].x, T[5].x), pack_f16(T[6].x, T[7].x));
    sts128(row + 512, pack_f16(T[0].y, T[1].y), pack_f16(T[2].y, T[3].y), pack_f16(T[4].y, T[5].y), pack_f16(T[6].y, T[7].y));
    uint32_t a[4], b[4];
    {
        const uint32_t zx = pack_f16(y256.x, y256.x), zy = pack_f16(y256.y, y256.y);
        hcmul(pack_f16(T[0].x, T[2].x), pack_f16(T[0].y, T[2].y), zx, zy, a[0], b[0]);
        hcmul(pack_f16(T[4].x, T[6].x), pack_f16(T[4].y, T[6].y), zx, zy, a[1], b[1]);
        const uint32_t r04 = pack_f16(T[0].x, T[4].x), i04 = pack_f16(T[0].y, T[4].y);
        hcmul(r04, i04, pack_f16(y512.x, y512.x), pack_f16(y512.y, y512.y), a[2], b[2]);
        hcmul(r04, i04, pack_f16(y768.x, y768.x), pack_f16(y768.y, y768.y), a[3], b[3]);
    }
    sts128(row + 1024, a[0], a[1], a[2], a[3]);
    sts128(row + 1536, b[0], b[1], b[2], b[3]);
    {
        const uint32_t r0 = pack_f16(1.0f, y256.x), i0 = pack_f16(0.0f, y256.y), r1 = pack_f16(y512.x, y768.x), i1 = pack_f16(y512.y, y768.y);
        const uint32_t zx = pack_f16(T[8].x, T[8].x), zy = pack_f16(T[8].y, T[8].y), wx = pack_f16(c1032.x, c1032.x), wy = pack_f16(c1032.y, c1032.y);
        hcmul(r0, i0, zx, zy, a[0], b[0]); hcmul(r1, i1, zx, zy, a[1], b[1]);
        hcmul(r0, i0, wx, wy, a[2], b[2]); hcmul(r1, i1, wx, wy, a[3], b[3]);
    }
    sts128(row + 2048, a[0], a[1], a[2], a[3]);
    sts128(t5 + lane * 16, b[0], b[1], b[2], b[3]);
}
__device__ __forceinline__ void kgen_mma(const KGen& k, uint32_t tb, uint32_t t5, int lane) {
    __syncwarp();
    float acc[2][3][4];
#pragma unroll
    for (int i = 0; i < 6; i++)
#pragma unroll
        for (int j = 0; j < 4; j++) acc[i / 3][i % 3][j] = 0.f;
    const int mi = lane >> 3;
    const uint32_t ro = ((lane & 7) + 8 * (mi >> 1)) * 16, bd = tb + ro + (mi & 1) * 512, b2 = ro + ((mi & 1) ? t5 : tb + 2048);
#pragma unroll
    for (int kp = 0; kp < 2; kp++)
#pragma unroll
        for (int j = 0; j < 3; j++) {
            uint32_t b[4];
            ldsm_x4_t(b[0], b[1], b[2], b[3], (j < 2 ? bd + j * 1024 : b2) + kp * 256);
#pragma unroll
            for (int h = 0; h < 2; h++)
#pragma unroll
                for (int m = 0; m < 2; m++) {
                    const uint32_t (&A)[4] = k.A[m][2 * kp + h];
                    mma_f16(acc[m][j], A[0], A[1], A[2], A[3], b[2 * h], b[2 * h + 1]);
                }
        }
    __syncwarp();
#define PK(j) pack_f16(acc[0][j][0], acc[0][j][1]), pack_f16(acc[0][j][2], acc[0][j][3]), pack_f16(acc[1][j][0], acc[1][j][1]), pack_f16(acc[1][j][2], acc[1][j][3])
    stsm_x4(tb + lane * 16, PK(0));
    stsm_x4(tb + 512 + lane * 16, PK(1));
    stsm_x4_t(tb + 1024 + (lane & 7) * 80 + mi * 16, PK(2));
#undef PK
}
__device__ __forceinline__ uint32_t table_buf(uint32_t sb, int warp) { return sb + SM_PL + warp * TBW; }

__device__ __forceinline__ uint4 lds16x4(uint32_t a) { return make_uint4(lds16(a), lds16(a + TBW), lds16(a + 2 * TBW), lds16(a + 3 * TBW)); }
__device__ __forceinline__ void combine_setup(uint32_t sb, int warp, int lane, uint32_t kw, uint32_t& o, uint32_t& n, uint32_t& d) {
    const int wq = warp & 3;
    const uint32_t a = table_buf(sb, warp & ~3);
    o = wq == 3 ? a + 1024 + 320 + (lane >> 3) * 80 + (lane & 7) * 8 : a + (wq ? 504 + wq * 8 : 0) + lane * 16;
    n = a + 1024 + wq * 80 + lane * 2;
    d = wq < 3 ? kw + (wq == 2 ? KW_P : 32 + wq * 512) + lane * 16 : kw + KW_H + 8 + lane * 8;
}
__device__ __forceinline__ void kgen_combine(int wq, int lane, uint32_t o, uint32_t na, uint32_t d) {
#define S4(f) hadd2(hadd2(u.f, v.f), hadd2(w.f, x.f))
#define H4(v) hadd2(hadd2(v.x, v.y), hadd2(v.z, v.w))
#define BP __byte_perm
    if (wq == 0) {
        const uint4 u = lds128(o), v = lds128(o + TBW), w = lds128(o + 2 * TBW), x = lds128(o + 3 * TBW), nn = lds16x4(na);
        const uint32_t n = H4(nn), k0 = S4(x), k2 = S4(y), k4 = S4(z), k6 = S4(w);
        sts128(d, BP(k0, k0, 0x1032), BP(k0, k2, 0x3254), BP(k2, k2, 0x1032), BP(k2, k4, 0x3254));
        sts128(d + KW_PL, BP(k4, k4, 0x1032), BP(k4, k6, 0x3254), BP(k6, k6, 0x1032), BP(k6, n, 0x3254));
        if (lane == 0) sts32(d + KW_PL - 4, k0 & 0xffffu);
    } else {
        const uint2 u = lds64(o), v = lds64(o + TBW), w = lds64(o + 2 * TBW), x = lds64(o + 3 * TBW);
        uint4 nn = make_uint4(0u, 0u, 0u, 0u), mm = nn;
        if (wq < 3) nn = lds16x4(na);
        if (wq == 2) mm = lds16x4(na + 80);
        const uint32_t k0 = S4(x), k2 = S4(y), n = H4(nn), m = H4(mm);
        if (wq == 3) {
            sts64(d, k0, k2);
        } else if (wq == 1) {
            const uint32_t cc = BP(k2, k2, 0x1010);
            sts128(d, BP(k0, k0, 0x1010), BP(k0, k0, 0x1032), BP(k0, k2, 0x3254), cc);
            sts128(d + KW_PL, cc, BP(k2, k2, 0x1032), BP(k2, n, 0x3254), BP(n, n, 0x1010));
        } else {
            const uint32_t w40 = BP(k0, k0, 0x1032), w84 = BP(k0, n, 0x3254), w0 = BP(k0, k0, 0x1010), w4 = BP(k0, k0, 0x3232), w8 = BP(n, n, 0x1010);
            sts64(d, w40, w84);
            sts64(d + 512, BP(k2, k2, 0x1032), BP(k2, m, 0x3254));
            if (lane < 8) { sts128(d - (KW_P - 1056), w0, w0, w40, w4); sts128(d - (KW_P - 1056 - KW_PL), w4, w84, w8, w8); }
            if (lane == 31) sts16(d + (KW_H + 6 - KW_P - 496), m);
        }
    }
#undef S4
#undef H4
#undef BP
}

__device__ __forceinline__ int c_exponent(const uint2& r, const uint2& i, float dt) {
    const uint32_t mx = __vmaxu2(__vmaxu2(r.x & 0x7fff7fffu, r.y & 0x7fff7fffu), __vmaxu2(i.x & 0x7fff7fffu, i.y & 0x7fff7fffu));
    return __reduce_max_sync(0xffffffffu, max(mx, mx << 16) + (__float_as_uint(dt) & 0x7f800000u)) >> 23;
}

__device__ __forceinline__ int lane_v() { int l; asm volatile("mov.u32 %0, %%laneid;" : "=r"(l)); return l; }
__device__ __forceinline__ uint32_t prmt_v(uint32_t a, uint32_t b, uint32_t s) { uint32_t d; asm volatile("prmt.b32 %0, %1, %2, %3;\n" : "=r"(d) : "r"(a), "r"(b), "r"(s)); return d; }
__device__ __forceinline__ uint32_t mov_v(uint32_t a) { uint32_t d; asm volatile("mov.b32 %0, %1;\n" : "=r"(d) : "r"(a)); return d; }
template <int G>
__device__ __forceinline__ void conv_rename(float (&acc)[16][4]) {
#pragma unroll
    for (int i = G; i < 16; i++)
#pragma unroll
        for (int j = 0; j < 4; j++) { float v; asm volatile("mov.b32 %0, %1;\n" : "=f"(v) : "f"(acc[i][j])); acc[i][j] = v; }
}
struct Conv {
    uint32_t kw;
    uint32_t wa;
    uint32_t pa, s2;
    uint32_t s8;
    uint32_t id;
    uint32_t lc;
    uint32_t fs;
    uint32_t fl, yo;
    uint32_t yp;
    size_t ycopy;
    uint32_t ps;
    uint64_t d0;
    int warp;
};
struct Pk { uint32_t w[4]; };
__device__ __forceinline__ Pk pk2(const float (&u)[4], const float (&v)[4]) {
    Pk r;
    r.w[0] = pack_f16(u[0], u[1]); r.w[1] = pack_f16(u[2], u[3]); r.w[2] = pack_f16(v[0], v[1]); r.w[3] = pack_f16(v[2], v[3]);
    return r;
}
__device__ __forceinline__ void park(uint32_t a, const Pk& v) {
    asm volatile("stmatrix.sync.aligned.m8n8.x4.trans.shared.b16 [%0], {%1,%2,%3,%4};\n" ::"r"(a), "r"(v.w[0]), "r"(v.w[1]), "r"(v.w[2]), "r"(v.w[3]) : "memory");
}
__device__ __forceinline__ void conv_constants(uint32_t lc, int l) {
    const int d = (l >> 2) - 2 * (l & 3);
    const int e = d + 8, r4 = (e + 1 + ((e >> 2) & 1)) >> 2, p4 = (e + (((e - 1) >> 2) & 1)) >> 2;
    const uint32_t s2 = r4 == p4 ? 0x1010u : 0x3210u;
    sts64(lc + l * 8, KW_P + ((r4 - 5) >> 1) * 16 + ((r4 - 5) & 1) * 4, s2 | ((d < 0 ? s2 : 0x7654u) << 16));
    const int lo = (d >= 4) - (d < -3), ho = (d >= 5) - (d < -2), le = (d > 4) - (d < -4), he = (d > 5) - (d < -3);
    sts32(lc + 512 + l * 8, (0x5454u + lo * 0x22 + ho * 0x2200) | ((0x3232u + le * 0x22 + he * 0x2200) << 16));
    const int cc = l >> 2, j = l & 3;
    sts64(lc + 256 + l * 8, (j >> 1) * PL_HALF + (16 + cc) * 16 + (j & 1) * 8, (cc >> 1) * (DM * 64) + (cc & 1) * 32 + j * 8);
}
__device__ __forceinline__ void conv_selectors4(Conv& c) {
    const uint2 v = lds64(c.lc + lane_v() * 8);
    c.pa = v.x; c.s2 = v.y;
}
__device__ __forceinline__ void conv_selectors8(Conv& c) { c.s8 = lds32(c.lc + 512 + lane_v() * 8); }
template <int G, int I0, int I1>
__device__ __forceinline__ void conv_load(const Conv& c, uint32_t (&q)[9]) {
    const int wq = c.warp & 3;
    if (G < 2) {
#pragma unroll
        for (int i = I0; i < I1; i++) q[i] = lds32(c.wa + G * 512 + i * 16);
    } else if (G < 4) {
        const uint32_t a = (G == 2 && wq == 0) ? c.wa + 1024 : c.pa + c.kw + wq * 128 + (G < 2 ? 0 : G - 2) * 512;
#pragma unroll
        for (int i = I0; i < I1; i++) q[i] = lds32(a + i * 16);
    } else {
        const uint4 u = lds128(c.kw + KW_H + (G < 4 ? 0 : G - 4) * 64 + wq * 16);
        const uint2 v = lds64(c.kw + KW_H + (G < 4 ? 0 : G - 4) * 64 + wq * 16 + 16);
        q[0] = u.x; q[1] = u.y; q[2] = u.z; q[3] = u.w; q[4] = v.x; q[5] = v.y;
        if (G == 4 && wq == 0) { q[6] = lds32(c.pa + c.kw + 1024); q[7] = lds32(c.pa + c.kw + 1040); }
    }
}
template <int G, int J0, int J1>
__device__ __forceinline__ void conv_frag(const Conv& c, const uint32_t (&q)[9], uint32_t* a, const Pk& dp) {
    const uint32_t dep = dp.w[0];
    if (G < 4) {
        const uint32_t s = (G < 2 || (G == 2 && (c.warp & 3) == 0)) ? c.id : c.s2;
#pragma unroll
        for (int j = J0; j < J1; j++) {
            uint32_t* o = a + 4 * (j - J0);
            o[0] = prmt_v(q[2 * j + 1], dp.w[0], s); o[1] = prmt_v(q[2 * j + 2], dp.w[1], s); o[2] = prmt_v(q[2 * j], dp.w[2], s); o[3] = prmt_v(q[2 * j + 1], dp.w[3], s);
        }
    } else {
        const uint32_t so = prmt_v(c.s8, dep, c.id), se = prmt_v(c.s8, dep, c.id + 0x22);
#pragma unroll
        for (int j = J0; j < J1; j++) {
            uint32_t* o = a + 4 * (j - J0);
            o[0] = prmt_v(q[j + 1], q[j + 2], se); o[1] = prmt_v(q[j + 1], q[j + 2], so); o[2] = prmt_v(q[j], q[j + 1], so);
            if (G == 4 && j == 0 && (c.warp & 3) == 0) {
                o[2] = prmt_v(q[6], dep, c.s2);
                o[0] = prmt_v(q[7], o[0], c.s2 >> 16);
            }
            o[3] = mov_v(o[0]);
        }
    }
}
template <int G, int J0, int J1>
__device__ __forceinline__ void conv_frag(const Conv& c, const uint32_t (&q)[9], uint32_t* a, float depf) {
    const uint32_t d = __float_as_uint(depf);
    conv_frag<G, J0, J1>(c, q, a, Pk{{d, d, d, d}});
}
template <int G, int T, int J0, int J1>
__device__ __forceinline__ void conv_mma(float (&acc)[16][4], const Conv& c, const uint32_t* a) {
#pragma unroll
    for (int j = J0; j < J1; j++) wg_mma<T>(acc, a + 4 * (j - J0), c.d0 - 8 * (2 * G - T) - j);
}
__device__ __forceinline__ float h_lo(uint32_t w) { return __half2float(__ushort_as_half((unsigned short)(w & 0xffffu))); }
__device__ __forceinline__ float h_hi(uint32_t w) { return __half2float(__ushort_as_half((unsigned short)(w >> 16))); }
__device__ __forceinline__ void flush_setup(Conv& c) {
    const uint2 v = lds64(c.lc + 256 + lane_v() * 8);
    c.fl = v.x; c.yo = v.y;
}
template <int Q>
__device__ __forceinline__ void flush_load(const Conv& c, uint32_t pl, uint2 (&f)[4]) {
#pragma unroll
    for (int w = 0; w < 4; w++) f[w] = lds64(c.fl + pl + (Q & 1) * 512 + w * (PLW_B - 64));
}
template <int Q>
__device__ __forceinline__ void flush_load_first(const Conv& c, uint32_t pl, uint2 (&f)[4], float depf) {
    const uint32_t p = prmt_v(c.fl, __float_as_uint(depf), c.id) + pl + (Q & 1) * 512;
#define LDV64(d, a) asm volatile("ld.volatile.shared.v2.u32 {%0,%1}, [%2];\n" : "=r"(d.x), "=r"(d.y) : "r"(a) : "memory")
    LDV64(f[0], p); LDV64(f[1], p + (PLW_B - 64)); LDV64(f[2], p + 2 * (PLW_B - 64)); LDV64(f[3], p + 3 * (PLW_B - 64));
}
#define FDEP __uint_as_float(f[3].y)
template <int Q, int mode>
__device__ __forceinline__ void conv_flush(const Conv& c, const uint2 (&f)[4], unsigned char* gy, uint32_t rx) {
    const uint32_t a0 = hadd2(f[0].x, f[1].x), a1 = hadd2(f[2].x, f[3].x), b0 = hadd2(f[0].y, f[1].y), b1 = hadd2(f[2].y, f[3].y);
    if (Q > 0 && mode == 1) {
        const uint32_t ra = rx + 16 + (Q > 0 ? Q - 1 : 0) * 1024 + (c.warp & 3) * 256 + lane_v() * 8;
        asm volatile("st.async.shared::cluster.mbarrier::complete_tx::bytes.v2.b32 [%0], {%1,%2}, [%3];\n"
                     ::"r"(ra ^ 0x1000000u), "r"(hadd2(a0, a1)), "r"(hadd2(b0, b1)), "r"((rx + (Q > 1 ? 8 : 0)) ^ 0x1000000u) : "memory");
        return;
    }
    float v0 = h_lo(a0) + h_lo(a1), v1 = h_hi(a0) + h_hi(a1), v2 = h_lo(b0) + h_lo(b1), v3 = h_hi(b0) + h_hi(b1);
    if (Q > 0 && mode == 2) {
        const uint2 o = lds64(rx + 16 + (Q > 0 ? Q - 1 : 0) * 1024 + (c.warp & 3) * 256 + lane_v() * 8);
        v0 += h_lo(o.x); v1 += h_hi(o.x); v2 += h_lo(o.y); v3 += h_hi(o.y);
    }
    const uint32_t lo = hmul2_bf(pack_bf16(v0, v1), c.fs), hi = hmul2_bf(pack_bf16(v2, v3), c.fs);
    stg64(gy + Q * 32 * DM * 32 + (c.yo + (Q < 2 ? c.yp : 0u)), nzw(lo), nzw(hi));
}
template <int I, bool S = false> struct IC { static constexpr int value = I; static constexpr bool shared = S; };
template <class T> __device__ constexpr bool wg_is4() { return T::shared; }
#define SLOT(n) (c.ps + (2 + ((n) & 7)) * 128)
#define GO() do { wg_commit(); __syncwarp(); } while (0)
#define DEP acc[15][3]
template <class FG, class FP, class FN>
__device__ __forceinline__ void conv_head(Conv& c, float (&acc)[16][4], uint32_t (&q)[9], uint32_t (&r)[9], uint32_t* a, FG fg, FP pre, FN next) {
    c.id = 0x3210u + (c.warp >> 8);
    pre();
    conv_load<0, 0, 9>(c, q);
    conv_frag<0, 0, 1>(c, q, a, 0.f);
    wg_fence(); wg_first<0>(acc, a, c.d0); GO();
    park(c.ps, Pk{{0u, 0u, 0u, 0u}});
    wg_wait0();
    conv_frag<0, 1, 2>(c, q, a, DEP);
    wg_fence(); conv_mma<0, 0, 1, 2>(acc, c, a); GO();
    fg(IC<0>());
    wg_wait0();
    conv_frag<0, 2, 3>(c, q, a, DEP);
    wg_fence(); conv_mma<0, 0, 2, 3>(acc, c, a); GO();
    conv_load<1, 0, 5>(c, r);
    wg_wait0();
    conv_frag<0, 3, 4>(c, q, a, DEP);
    wg_fence(); conv_mma<0, 0, 3, 4>(acc, c, a); GO();
    conv_load<1, 5, 9>(c, r);
    fg(IC<1>());
    wg_wait0();
    const Pk k = pk2(acc[0], acc[1]);
    conv_rename<2>(acc);
    conv_frag<1, 0, 2>(c, r, a, k);
    wg_fence(); conv_mma<1, 2, 0, 2>(acc, c, a); GO();
    park(SLOT(0), k);
    next(IC<0>());
    fg(IC<2>());
    wg_wait0();
    conv_frag<1, 2, 4>(c, r, a, DEP);
    wg_fence(); conv_mma<1, 2, 2, 4>(acc, c, a); GO();
    next(IC<1>());
    fg(IC<3>());
    wg_wait0();
}
template <class FG, class FP>
__device__ __forceinline__ void conv_run(Conv& c, uint32_t pl, unsigned char* gy, FG fg, FP pre) {
    float acc[16][4];
    uint32_t q[9], r[9], a[32];
    uint2 f[4];
    const int bid = 1 + (c.warp >> 2);
    conv_head(c, acc, q, r, a, fg, pre, [&](auto i) { if (decltype(i)::value == 0) conv_selectors4(c); else conv_load<2, 0, 9>(c, q); });
    Pk k = pk2(acc[2], acc[3]);
    conv_rename<4>(acc);
    conv_frag<2, 0, 4>(c, q, a, k);
    wg_fence(); conv_mma<2, 4, 0, 4>(acc, c, a); GO();
    park(SLOT(2), k);
    conv_load<3, 0, 9>(c, q);
    flush_setup(c);
    bar_sync(bid, 128);
    fg(IC<4>());
    wg_wait0();
    conv_rename<6>(acc);
    conv_frag<3, 0, 4>(c, q, a, DEP);
    wg_fence(); conv_mma<3, 6, 0, 4>(acc, c, a); GO();
    park(SLOT(4), pk2(acc[4], acc[5]));
    conv_load<4, 0, 9>(c, q);
    conv_selectors8(c);
    flush_load<0>(c, pl, f);
    conv_flush<0, 0>(c, f, gy, 0u);
    fg(IC<5>());
    wg_wait0();
    conv_rename<8>(acc);
    conv_frag<4, 0, 4>(c, q, a, DEP);
    wg_fence(); conv_mma<4, 8, 0, 4>(acc, c, a); GO();
    k = pk2(acc[6], acc[7]);
    park(SLOT(6), k);
    conv_load<5, 0, 9>(c, q);
    bar_sync(bid, 128);
    park(c.ps, k);
    fg(IC<6>());
    wg_wait0();
    conv_rename<10>(acc);
    flush_load_first<1>(c, pl, f, DEP);
    conv_frag<5, 0, 4>(c, q, a, FDEP);
    wg_fence(); conv_mma<5, 10, 0, 4>(acc, c, a); GO();
    park(SLOT(8), pk2(acc[8], acc[9]));
    conv_load<6, 0, 9>(c, q); conv_load<7, 0, 9>(c, r);
    conv_flush<1, 0>(c, f, gy, 0u);
    fg(IC<7>());
    wg_wait0();
    conv_rename<12>(acc);
    conv_frag<6, 0, 4>(c, q, a, DEP); conv_frag<7, 0, 4>(c, r, a + 16, DEP);
    wg_fence(); conv_mma<6, 12, 0, 4>(acc, c, a); conv_mma<7, 12, 0, 4>(acc, c, a + 16); GO();
    park(SLOT(10), pk2(acc[10], acc[11]));
    bar_sync(bid, 128);
    flush_load<2>(c, pl, f);
    conv_flush<2, 0>(c, f, gy, 0u);
    fg(IC<8>());
    if (c.id == 0) TRAP();
    wg_wait0();
    park(SLOT(12), pk2(acc[12], acc[13])); park(SLOT(14), pk2(acc[14], acc[15]));
    bar_sync(bid, 128);
    flush_load<3>(c, pl, f);
    conv_flush<3, 0>(c, f, gy, 0u);
}
template <class FG>
__device__ __forceinline__ void conv_outer(Conv& c, uint32_t pl, unsigned char* gy, uint32_t rx, FG fg) {
    float acc[16][4];
    uint32_t q[9], r[9], a[32];
    uint2 f[4], f2[4];
    const int bid = 1 + (c.warp >> 2);
    conv_head(c, acc, q, r, a, [&](auto gi) { if (decltype(gi)::value == 2) fg(IC<2, true>()); }, [&]() {}, [&](auto i) { if (decltype(i)::value == 0) conv_selectors8(c); else conv_load<6, 0, 9>(c, q); });
    park(SLOT(2), pk2(acc[2], acc[3])); park(SLOT(4), pk2(acc[4], acc[5]));
    const Pk k = pk2(acc[6], acc[7]);
    park(SLOT(6), k);
    conv_load<7, 0, 9>(c, r);
    conv_rename<12>(acc);
    conv_frag<6, 0, 4>(c, q, a, __uint_as_float(k.w[3])); conv_frag<7, 0, 4>(c, r, a + 16, __uint_as_float(k.w[3]));
    wg_fence(); conv_mma<6, 12, 0, 4>(acc, c, a); conv_mma<7, 12, 0, 4>(acc, c, a + 16); GO();
    flush_setup(c);
    bar_sync(bid, 128);
    flush_load<0>(c, pl, f); flush_load<1>(c, pl, f2);
    conv_flush<1, 1>(c, f2, gy, rx);
    conv_flush<0, 1>(c, f, gy, rx);
    wg_wait0();
    bar_sync(bid, 128);
    park(c.ps, k); park(SLOT(8), pk2(acc[8], acc[9])); park(SLOT(10), pk2(acc[10], acc[11]));
    park(SLOT(12), pk2(acc[12], acc[13])); park(SLOT(14), pk2(acc[14], acc[15]));
    bar_sync(bid, 128);
    flush_load<2>(c, pl, f); flush_load<3>(c, pl, f2);
    conv_flush<2, 1>(c, f, gy, rx);
    conv_flush<3, 1>(c, f2, gy, rx);
}
template <class FG>
__device__ __forceinline__ void conv_inner(Conv& c, uint32_t pl, unsigned char* gy, uint32_t rx, FG fg) {
    float acc[16][4];
    uint32_t q[9], a[16];
    uint2 f[4], f2[4];
    const int bid = 1 + (c.warp >> 2);
    c.id = 0x3210u + (c.warp >> 8);
    conv_selectors4(c);
    conv_load<2, 0, 9>(c, q);
    conv_frag<2, 0, 4>(c, q, a, 0.f);
    wg_fence(); wg_first<4>(acc, a, c.d0); conv_mma<2, 4, 1, 4>(acc, c, a + 4); GO();
    conv_load<3, 0, 9>(c, q);
    park(SLOT(2), Pk{{0u, 0u, 0u, 0u}});
    fg(IC<2, true>());
    wg_wait0();
    conv_rename<6>(acc);
    conv_frag<3, 0, 4>(c, q, a, DEP);
    wg_fence(); conv_mma<3, 6, 0, 4>(acc, c, a); GO();
    park(SLOT(4), pk2(acc[4], acc[5]));
    conv_load<4, 0, 9>(c, q);
    conv_selectors8(c);
    wg_wait0();
    conv_rename<8>(acc);
    conv_frag<4, 0, 4>(c, q, a, DEP);
    wg_fence(); conv_mma<4, 8, 0, 4>(acc, c, a); GO();
    const Pk k = pk2(acc[6], acc[7]);
    park(SLOT(6), k); park(c.ps, k);
    conv_load<5, 0, 9>(c, q);
    flush_setup(c);
    wg_wait0();
    conv_rename<10>(acc);
    conv_frag<5, 0, 4>(c, q, a, DEP);
    wg_fence(); conv_mma<5, 10, 0, 4>(acc, c, a); GO();
    park(SLOT(8), pk2(acc[8], acc[9]));
    bar_sync(bid, 128);
    flush_load<1>(c, pl, f);
    mbar_wait(rx);
    conv_flush<1, 2>(c, f, gy, rx);
    wg_wait0();
    bar_sync(bid, 128);
    park(SLOT(10), pk2(acc[10], acc[11])); park(SLOT(12), pk2(acc[12], acc[13])); park(SLOT(14), pk2(acc[14], acc[15]));
    bar_sync(bid, 128);
    flush_load<3>(c, pl, f); flush_load<2>(c, pl, f2);
    mbar_wait(rx + 8);
    conv_flush<3, 2>(c, f, gy, rx);
    conv_flush<2, 2>(c, f2, gy, rx);
}
#undef SLOT
#undef GO
#undef DEP
template <int U0, int U1>
__device__ __forceinline__ void weight_units(uint32_t sb, const Maps& tm, bool w) {
    if (U1 > U0 && w && elect_one()) {
#pragma unroll
        for (int i = U0; i < U1; i++) {
            const int P = blockIdx.x >> 1, odd = blockIdx.x & 1;
            if (i < 12) tma_2d(sb + SM_WG + i * 6144, &tm.w[i / 6], 64 * P, 288 * odd + (i % 6) * 48, sb + SM_MISC + 328);
            else tma_2d(sb + SM_WD + (i - 12) * 4736, &tm.d, 144 * odd, i < 20 ? 64 * P + 8 * (i - 12) : 4096 + 8 * P, sb + SM_MISC + 336);
            if (i >= 8 && i < 12) tma_2d(sb + SM_WR + (i - 8) * 2304, &tm.r[(i - 8) >> 1], 4096 + 8 * P, 288 * odd + (i & 1) * 144, sb + SM_MISC + 328);
        }
    }
}
#define WS 2210121111113004000
__device__ constexpr int wsched(int i) {
    unsigned long long v = WS;
    int n = 0;
    for (int k = 19; k >= 1; k--) { if (k < i) n += (int)(v % 10); v /= 10; }
    return n;
}
static_assert(wsched(20) == 21 && wsched(6) <= 8 && wsched(11) <= 12 && wsched(13) <= 14 && wsched(16) <= 17 && wsched(16) == wsched(15) && wsched(19) == 21, "");
#define WANY(i) (wsched((i) + 1) > wsched(i))
#define WPOINT(i, w) do { weight_units<wsched(i), wsched(i + 1)>(sb, tm, w); } while (0)

__global__ void __launch_bounds__(NTHR, 1) __cluster_dims__(2, 1, 1)
fused_kernel(const Params p, const __grid_constant__ Maps tm) {
    extern __shared__ __align__(1024) unsigned char smem[];
    const uint32_t sb = smem_u32(smem);
    const int tid = threadIdx.x, warp = __shfl_sync(0xffffffffu, tid >> 5, 0), lane = tid & 31;
    const int b = blockIdx.x, P = b >> 1, odd = b & 1;
    const int g = lane >> 2, t = lane & 3;
    const int wg = warp >> 2, t128 = tid & 127;
    const uint32_t s_stat = sb + SM_MISC;
    const uint32_t s_key = sb + SM_MISC + 128;
    const uint32_t s_rank = sb + SM_MISC + 256;
    const uint32_t s_k16 = sb + SM_MISC + 192;
    const uint32_t s_cnt = sb + SM_MISC + 320;
    const uint32_t bar_w = sb + SM_MISC + 328, bar_d = bar_w + 8, bar_g = bar_w + 16, bar_x = bar_w + 24, bar_v = bar_w + 32, bar_s = bar_w + 40, bar_h = bar_w + 48;
    STAMP(0);

    const int ch = wg < 4 ? 4 * b + wg : 512 + P;
    const uint32_t mo = tid < 512 ? 512 * b + tid : 65536 + 128 * P + t128, mq = (mo & ~127u) + 4 * lane;
    const uint32_t pl = ldo16(p.lar + mo), pa2 = ldo16(p.aim + mo), ldt = ldo16(p.ldt + (mo >> 7));
    const uint32_t pc = ldo16(p.cre + mo), pi = ldo16(p.cim + mo);
    const uint2 call_re = ldo64(p.cre + mq), call_im = ldo64(p.cim + mq);
    const uint32_t epl = ld_poll32(p.s->hint + (b & 7) * 32 + 1);
    const uint32_t kw = sb + SM_KW + wg * KW_B;
    uint32_t co, cn, cd, uo;
    auto housekeeping = [&]() {
        if (t128 < 2 * UPAD) sts128(sb + SM_U + wg * USLOT_B + (t128 & 1) * ULO_B + (t128 >> 1) * 16, 0u, 0u, 0u, 0u);
        if (t128 >= 124) sts128(kw + (t128 & 1) * 16 + (t128 & 2) * (KW_PL / 2), 0u, 0u, 0u, 0u);
        if (warp < 15) sts128(sb + SM_Z2 + 4608 + tid * 16, 0u, 0u, 0u, 0u);
        combine_setup(sb, warp, lane, kw, co, cn, cd);
        co = pin(co); cn = pin(cn); cd = pin(cd);
        uo = pin(wg < 4 ? tid : 512 + (P >> 2) * 1024 + (t128 >> 1) * 8 + (P & 3) * 2 + (t128 & 1));
    };
    if (wg < 4) {
        bar_arrive(0, NWRK);
        asm volatile("barrier.cluster.arrive.relaxed.aligned;\n" ::: "memory");
        housekeeping();
    } else {
        const int o = (warp & 3) * 4608 + lane * 16;
        sts128(sb + SM_Z2 + t128 * 16, 0u, 0u, 0u, 0u); sts128(sb + SM_Z2 + 2048 + t128 * 16, 0u, 0u, 0u, 0u);
        if (warp == 16) sts128(sb + SM_Z2 + 4096 + lane * 16, 0u, 0u, 0u, 0u);
        fence_async();
        bar_sync(0, NWRK);
        STAMP(9);
#pragma unroll
        for (int c = 0; c < 9; c++)
            asm volatile("cp.async.cg.shared.global [%0], [%1], 16;\n" ::"r"(sb + SM_XT + o + c * 512), "l"(reinterpret_cast<const char*>(p.x) + b * 18432 + o + c * 512) : "memory");
        asm volatile("cp.async.commit_group;\n" ::: "memory");
        if (elect_one()) {
            mbar_init(bar_h + 8 * (warp & 3), 1);
            if (warp == 19) {
                mbar_init(bar_x, 1); mbar_init(bar_w, 1);
                mbar_expect(bar_x, 32768); mbar_expect(bar_w, 82944);
#pragma unroll
                for (int i = 2; i < 4; i++) bulk_s2g(reinterpret_cast<unsigned char*>(p.s->y) + 32 * i * 18432 + b * 4608, sb + SM_Z2, 4608);
            } else if (warp == 18) {
                mbar_init(bar_s, 1); mbar_init(bar_v, 2); mbar_init(bar_d, 1); mbar_init(bar_g, 1); mbar_init(sb + SM_RX, 1); mbar_init(sb + SM_RX + 8, 1);
                mbar_expect(bar_v, 2 * 1152); mbar_expect(bar_d, 72 * WD_PITCH); mbar_expect(bar_g, 4608); mbar_expect(sb + SM_RX, 1024); mbar_expect(sb + SM_RX + 8, 2048);
            }
            asm volatile("fence.mbarrier_init.release.cluster;\n" ::: "memory");
        }
        __syncwarp();
        asm volatile("barrier.cluster.arrive.relaxed.aligned;\n" ::: "memory");
        if (warp == 19) {
            asm volatile("barrier.cluster.wait.aligned;\n" ::: "memory");
            if (elect_one()) tma_4d_mc(sb + SM_XC + odd * 16384, &tm.x, 8 * P, 2 * odd, bar_x);
            __syncwarp();
        }
    }
    const uint32_t tb = table_buf(sb, warp), t5 = sb + SM_WD + warp * 512;
    STAMP(29);
    const float dt = exp_bf(bf_lo(ldt));
    const uint32_t ep = __reduce_or_sync(0xffffffffu, epl);
    auto stats = [&]() {
        const int wq = warp & 3;
        const uint32_t xa = sb + SM_XT + (4 * wq + (g >> 1)) * 1152 + (g & 1) * 576 + t * 16;
        const bool own = !(g & 1) && t == (g >> 1);
        float d[4][4] = {};
        asm volatile("cp.async.wait_group 0;\n" ::: "memory");
        __syncwarp();
        STAMP(26);
        uint4 v[9];
#pragma unroll
        for (int c = 0; c < 9; c++) v[c] = lds128(xa + c * 64);
#pragma unroll
        for (int c = 0; c < 9; c++) {
            mma_bf16(d[2 * (c & 1)], v[c].x, 0x3f803f80u, v[c].y, 0x3f803f80u, v[c].x, v[c].y);
            mma_bf16(d[2 * (c & 1) + 1], v[c].z, 0x3f803f80u, v[c].w, 0x3f803f80u, v[c].z, v[c].w);
        }
        STAMP(27);
        float sm = (g & 1) ? (d[0][3] + d[1][3]) + (d[2][3] + d[3][3]) : (d[0][2] + d[1][2]) + (d[2][2] + d[3][2]);
        float sq = (g & 1) ? (d[0][1] + d[1][1]) + (d[2][1] + d[3][1]) : (d[0][0] + d[1][0]) + (d[2][0] + d[3][0]);
        sm += __shfl_xor_sync(0xffffffffu, sm, 4); sq += __shfl_xor_sync(0xffffffffu, sq, 4);
        if (lane == 0) mbar_arrive(bar_h + 8 * wq);
        float mb, sd;
        ln_stats(sm, sq, mb, sd);
        if (own) p.s->stat[16 * b + 4 * wq + t] = (__float_as_uint(mb) >> 16) | (__float_as_uint(sd) & 0x7fff0000u) | (ep << 31);
        STAMPX(22);
        if (own) stat_store(s_stat + (2 * wq + (t & 1) + 8 * (t >> 1)) * 8, mb, rcp_approx(sd), 0u);
        if (wq == 3) asm volatile("cp.async.bulk.wait_group 0;\n" ::: "memory");
        bar_sync(5, 128);
        STAMP(28);
        uint32_t now;
        asm volatile("mov.u32 %0, %%clock;" : "=r"(now) :: "memory");
        if (wq == 2) {
            conv_constants(sb + SM_LC, lane);
            __syncwarp();
            if (lane == 0) {
                sts64(s_cnt, now, ep);
                mbar_arrive(bar_s);
                bulk_g2s(sb + SM_XT + 16 * 1152, p.dsk, 1152, bar_v);
                bulk_g2s(sb + SM_XT + 17 * 1152, p.wr, 1152, bar_v);
            }
            __syncwarp();
        }
        WPOINT(1, wq == 3);
        if (wq < 2) {
            unsigned char* const ud = reinterpret_cast<unsigned char*>(p.s->uT) + (size_t)(8 * wq + 2 * (g >> 1)) * 16384 + b * 128 + (g & 1) * 32 + t * 8;
            const uint32_t utag = (ep % 7u + 1u) * 0x10001u;
            uint32_t U[2][4];
#pragma unroll
            for (int hf = 0; hf < 2; hf++) {
                const uint2 st = lds64(s_stat + (g + 8 * hf) * 8);
                const uint4 xu = lds128(sb + SM_XT + (TOK(g) + 2 * hf) * 1152 + warp * 64 + t * 16);
                const uint32_t X[4] = {xu.x, xu.y, xu.z, xu.w};
#pragma unroll
                for (int k = 0; k < 4; k++) {
                    const uint32_t u = ln_apply(X[k], STAT_M(st), STAT_H(st), STAT_L(st));
                    U[hf][k] = movm((pack_f16(bf_lo(u), bf_hi(u)) & 0xfff8fff8u) | utag);
                }
            }
#pragma unroll
            for (int k = 0; k < 4; k++) stg64(ud + (k >> 1) * 16384 + (k & 1) * 64, U[0][k], U[1][k]);
        }
    };
    STAMP(1);
    if (wg < 4) { STAMPX(16); }
    KGen kg;
    kgen_setup(kg, bf_lo(pl), bf_lo(pa2), dt);
    kgen_rows(kg, tb, lane);
    STAMP(2);
    const int E = min(max(c_exponent(call_re, call_im, dt) - 243, -120), 120);
    kgen_chain(kg, pc, pi, dt * __uint_as_float((uint32_t)(128 - E) << 23));
    STAMP(3);
    kgen_cols(kg, tb, t5, lane);
    STAMP(4);
    if (wg == 4) stats();
    if (warp != 19) asm volatile("barrier.cluster.wait.aligned;\n" ::: "memory");
    if (wg < 4) { STAMPX(17); }
    if (wg == 4) housekeeping();
    const uint4* const usrc = reinterpret_cast<const uint4*>(p.s->stat) + uo;
    if (wg < 4) mbar_wait(bar_h + 8 * (warp & 3));
    if (wg < 4) { STAMPX(19); }
    uint32_t trel;
    asm volatile("mov.u32 %0, %%clock;" : "=r"(trel) :: "memory");
    kgen_mma(kg, tb, t5, lane);
    if (wg < 4) { STAMPX(20); }
    STAMP(5);
    uint4 uv0, uv1;
    auto first_poll = [&](uint32_t dly) {
        mbar_wait(bar_s);
        const uint32_t t0 = lds32(s_cnt);
        uint32_t now;
        do { asm volatile("mov.u32 %0, %%clock;" : "=r"(now) :: "memory"); } while (now - t0 < dly);
        uv0 = ld_poll(usrc);
    };
    if (wg == 4) { first_poll(UDLY); uv1 = ld_poll(usrc + 512); }
    WPOINT(2, warp == 19);
    auto stat_poll = [&]() {
        uint32_t now;
        do { asm volatile("mov.u32 %0, %%clock;" : "=r"(now) :: "memory"); } while (now - trel < SDLY);
        uv0 = ld_poll(usrc);
    };
    bar_sync(1 + wg, 128);
    if (wg < 4) { STAMPX(21); }
    kgen_combine(warp & 3, lane, co, cn, cd);
    STAMP(6);
    if (wg < 4) { STAMPX(18); }
    WPOINT(3, warp == 19);
    if (wg < 4) stat_poll();
    {
        const int wq = warp & 3;
        Conv c;
        const uint32_t pln = sb + SM_PL + wg * PL_B;
        const int e = g - 2 * t + 7;
        c.kw = kw; c.wa = pin(kw + ((e >> 2) & 1) * KW_PL + (8 * wq + (e >> 3)) * 16 + (e & 3) * 4);
        c.ps = mov_v(pln + wq * PLW_B + ((lane >> 3) & 1) * PL_HALF + ((lane >> 4) * 8 + (lane & 7)) * 16); c.warp = warp;
        c.lc = sb + SM_LC; c.fs = (uint32_t)(127 + E) * 0x800080u; c.yp = (ep & 1u) * (NCTA * 18432u);
        c.d0 = ((uint64_t)(ULO_B >> 4) << 16) | ((uint64_t)(128 >> 4) << 32) | (uint64_t)(((sb + SM_U + wg * USLOT_B + UPAD * 16) & 0x3FFFF) >> 4);
        unsigned char* gy = reinterpret_cast<unsigned char*>(p.s->y) + ((size_t)(4 * wq) * DM + ch) * 64;
        auto hook = [&](auto gi) {
                     constexpr int G = decltype(gi)::value;
                     if (G == (wg_is4<decltype(gi)>() ? 2 : 5)) asm volatile("barrier.cluster.wait.aligned;\n" ::: "memory");
                     if (!wg_is4<decltype(gi)>() && G == 1) mbar_wait(bar_s);
                     if (!wg_is4<decltype(gi)>() && (G == 0 || G == 2) && warp == HW && elect_one()) {
                         unsigned char* const sc = reinterpret_cast<unsigned char*>(p.s);
                         if (G == 0) {
                             if (b < 96) bulk_s2g_nc(sc + offsetof(Scratch, part) + b * 6144, sb + SM_Z2, 6144);
                             bulk_s2g(sc + offsetof(Scratch, rows) + (127 - b) * 4608, sb + SM_Z2, 4608);
                         }
                         if (G == 2) {
                             bulk_s2g(sc + offsetof(Scratch, y) + (NCTA * 18432u - c.yp) + b * 9216, sb + SM_Z2, 9216);
                         }
                     }
                     if (!wg_is4<decltype(gi)>()) WPOINT(6 + G, warp == (G >= 7 ? HW : 4 * (G % 3) + 1));
                     if (!wg_is4<decltype(gi)>() && G == 6 && warp == HW) {
                         asm volatile("cp.async.bulk.wait_group 0;\n" ::: "memory");
                         __syncwarp();
                         if (elect_one()) mbar_arrive(bar_v);
                     }
                 };
        if (wg < 4) {
            asm volatile("barrier.cluster.arrive.relaxed.aligned;\n" ::: "memory");
            conv_run(c, pln + wq * 128, gy, hook, [&]() {
                STAMPX(23);
                mbar_wait(bar_x);
                STAMPX(24);
                uint2 xc[4];
                uint32_t xw[4][2];
#pragma unroll
                for (int j = 0; j < 4; j++) xc[j] = lds64(sb + SM_XC + wg * 8192 + j * 2048 + t128 * 16 + odd * 8);
#pragma unroll
                for (int i = 0; i < 8; i++) {
                    const int k = i >> 1, h = i & 1;
                    xw[k][h] = prmt_v(k < 2 ? xc[2 * h].x : xc[2 * h].y, k < 2 ? xc[2 * h + 1].x : xc[2 * h + 1].y, (k & 1) ? 0x7632 : 0x5410);
                }
                const uint32_t ub = mov_v(sb + SM_U + UPAD * 16 + ((tid >> 1) & 1) * ULO_B + (tid >> 2) * 16 + (tid & 1) * 8), tag = ep << 31;
                int it = 0;
                while (min(min((int)(uv0.x ^ tag), (int)(uv0.y ^ tag)), min((int)(uv0.z ^ tag), (int)(uv0.w ^ tag))) < 0x10000) {
                    if (++it > SPIN_LIMIT) TRAP();
                    uv0 = ld_poll(usrc);
                }
                STAMP(8);
                STAMPX(26);
                const float r0 = rcp_approx(fabsf(bf_hi(uv0.x))), r1 = rcp_approx(fabsf(bf_hi(uv0.y))), r2 = rcp_approx(fabsf(bf_hi(uv0.z))), r3 = rcp_approx(fabsf(bf_hi(uv0.w)));
                const uint32_t m[2] = {__byte_perm(uv0.x, uv0.y, 0x5410), __byte_perm(uv0.z, uv0.w, 0x5410)};
                const uint32_t rh[2] = {pack_bf16(r0, r1), pack_bf16(r2, r3)};
                const uint32_t rl[2] = {pack_bf16(r0 - bf_lo(rh[0]), r1 - bf_hi(rh[0])), pack_bf16(r2 - bf_lo(rh[1]), r3 - bf_hi(rh[1]))};
#pragma unroll
                for (int k = 0; k < 4; k++) {
                    const uint32_t u0 = ln_apply(xw[k][0], m[0], rh[0], rl[0]), u1 = ln_apply(xw[k][1], m[1], rh[1], rl[1]);
                    sts64(ub + k * USLOT_B, pack_f16(bf_lo(u0), bf_hi(u0)), pack_f16(bf_lo(u1), bf_hi(u1)));
                }
                STAMPX(29);
                fence_async();
                bar_sync(14, 512);
                STAMP(7);
            });
        } else {
            auto stage = [&]() {
                const uint32_t tag = (ep % 7u + 1u) * 0x10001u;
                int it = 0;
                WPOINT(4, warp == 19);
                while (true) {
                    uv0.x ^= tag; uv0.y ^= tag; uv0.z ^= tag; uv0.w ^= tag; uv1.x ^= tag; uv1.y ^= tag; uv1.z ^= tag; uv1.w ^= tag;
                    if ((((uv0.x | uv0.y | uv0.z) | (uv0.w | uv1.x | uv1.y) | (uv1.z | uv1.w)) & 0x70007u) == 0) break;
                    if (++it > SPIN_LIMIT) TRAP();
                    uv0 = ld_poll(usrc); uv1 = ld_poll(usrc + 512);
                }
                STAMP(8);
                const uint32_t ub = sb + SM_U + UPAD * 16 + 4 * USLOT_B + (t128 & 1) * ULO_B + (t128 >> 1) * 16;
                sts128(ub, uv0.x, uv0.y, uv0.z, uv0.w);
                sts128(ub + 1024, uv1.x, uv1.y, uv1.z, uv1.w);
                fence_async();
                asm volatile("barrier.cluster.arrive.relaxed.aligned;\n" ::: "memory");
                bar_sync(5, 128);
                WPOINT(5, warp == 19);
                STAMP(7);
            };
            stage();
            if (odd) conv_inner(c, pln + wq * 128, gy, sb + SM_RX, hook);
            else conv_outer(c, pln + wq * 128, gy, sb + SM_RX, hook);
        }
        STAMP(10);
    }
    {
    const int lane = lane_v(), tid = 32 * warp + lane, g = lane >> 2, t = lane & 3;
    const uint32_t par = ~ep & 1u;
    bar_sync(0, NWRK);
    STAMP(11);
    uint32_t H[2][4] = {}, U2[2][4] = {};
    auto publish = [&](bool hi, int slot) {
        uint4* rowp = reinterpret_cast<uint4*>(p.s->rows) + slot * 144 + warp * 4 + t;
        stg128(rowp, nzw(hi ? U2[1][0] : U2[0][0]), nzw(hi ? U2[1][1] : U2[0][1]), nzw(hi ? U2[1][2] : U2[0][2]), nzw(hi ? U2[1][3] : U2[0][3]));
        stg128(rowp + 72, nzw(hi ? H[1][0] : H[0][0]), nzw(hi ? H[1][1] : H[0][1]), nzw(hi ? H[1][2] : H[0][2]), nzw(hi ? H[1][3] : H[0][3]));
    };
#define KTOK(k) (int)(((~(k) >> 5) & 0x7f0u) | (((k) >> 1) & 15u))
#define KLATE(k) (((k) & 0x1e0u) < 0xe0u)
#define KSLOT(k, s) (KLATE(k) ? 2 * NCTA + (s) : (int)(((k) >> 8) & 0xffu))
    const uint4* const rsrc = reinterpret_cast<const uint4*>(p.s->rows) + 36 * odd;
    auto gather = [&](uint32_t mine) {
        int it = 0;
        uint32_t mn;
        do {
            mn = 1;
#pragma unroll 1
            for (int r = 0; r < 9; r++) {
                const uint32_t k = __shfl_sync(0xffffffffu, mine, r < 8 ? 4 * r : lane);
                const int row = r < 8 ? r : g, c = r < 8 ? lane : 32 + t;
                asm volatile("cp.async.cg.shared.global [%0], [%1], 16;\n" ::"r"(sb + SM_XS + row * XS_PITCH + c * 16), "l"(rsrc + KSLOT(k, row) * 144 + c) : "memory");
            }
            asm volatile("cp.async.wait_all;\n" ::: "memory");
#pragma unroll 1
            for (int r = 0; r < 9; r++) mn = min(mn, min4(lds128(sb + SM_XS + (r < 8 ? r * XS_PITCH + lane * 16 : g * XS_PITCH + (32 + t) * 16))));
            if (++it > SPIN_LIMIT) TRAP();
        } while (__any_sync(0xffffffffu, mn == 0));
    };
    auto late_rows = [&](auto role) {
        if (decltype(role)::value == 1) {
            int it = 0;
            uint4 k[8];
            uint32_t bad;
            do {
                bad = 0;
#pragma unroll
                for (int i = 0; i < 8; i++) k[i] = ld_poll(reinterpret_cast<const uint4*>(p.s->key) + 32 * i + lane);
#pragma unroll
                for (int i = 0; i < 8; i++) bad = or3(bad, xor_or(k[i].x, k[i].y, par), xor_or(k[i].z, k[i].w, par));
                if (++it > SPIN_LIMIT) TRAP();
            } while (__any_sync(0xffffffffu, bad & 1u));
#pragma unroll 1
            for (int r = 0; r < 8; r++) {
                uint32_t c = 0;
#pragma unroll
                for (int i = 0; i < 8; i++) c = max(c, k[i].x);
                const uint32_t m = __reduce_max_sync(0xffffffffu, c);
#pragma unroll
                for (int i = 0; i < 8; i++) if (k[i].x == m) k[i] = make_uint4(k[i].y, k[i].z, k[i].w, 0u);
                if (lane == 0) sts32(s_key + r * 4, m);
            }
        }
        bar_sync(0, NWRK);
        const uint32_t kk = lds32(s_key + (lane & 7) * 4), ep = lds32(s_cnt + 4);
        const bool own = KLATE(kk) && (KTOK(kk) >> 4) == b;
        uint32_t todo = __ballot_sync(0xffffffffu, own) & 0xffu;
        if (decltype(role)::value == 0 && todo) {
#pragma unroll
            for (int hf = 0; hf < 2; hf++) {
                const uint4 h = lds128(sb + SM_U + hf * 9216 + tid * 16);
                const uint2 st = lds64(s_stat + (g + 8 * hf) * 8);
                H[hf][0] = h.x; H[hf][1] = h.y; H[hf][2] = h.z; H[hf][3] = h.w;
#pragma unroll
                for (int k = 0; k < 4; k++) U2[hf][k] = ln_apply(H[hf][k], STAT_M(st), STAT_H(st), STAT_L(st));
            }
#pragma unroll 1
            while (todo) {
                const int s = __ffs(todo) - 1, tk = KTOK(__shfl_sync(0xffffffffu, kk, s));
                todo &= todo - 1;
                if ((tk & 13) == TOK(g)) publish(tk & 2, 2 * NCTA + s);
            }
            __threadfence();
        }
        bar_sync(0, NWRK);
        if (decltype(role)::value == 1) {
            if (lane < NSEL && own) *reinterpret_cast<volatile unsigned*>(p.s->flag + lane) = ep + 1u;
            int it = 0;
            while (__any_sync(0xffffffffu, KLATE(kk) && ld_acquire32(p.s->flag + (lane & 7)) != ep + 1u)) { if (++it > SPIN_LIMIT) TRAP(); }
            gather(__shfl_sync(0xffffffffu, kk, g));
        }
        bar_sync(0, NWRK);
    };
    if (warp < 18) {
        const unsigned char* ys = reinterpret_cast<const unsigned char*>(p.s->y) + (b < 64 ? (par ^ 1u) * (NCTA * 18432u) : 0u) +
                                  ((P * DM + 32 * warp + 8 * (g >> 1) + (g & 1)) * 64 + odd * 32 + t * 8);
        mbar_wait(bar_v);
        const uint32_t xa = sb + SM_XT + warp * 64 + t * 16;
        const uint4 x0 = lds128(xa + TOK(g) * 1152), x1 = lds128(xa + (TOK(g) + 2) * 1152), dk = lds128(xa + 16 * 1152);
        uint4 wr = make_uint4(0u, 0u, 0u, 0u);
        if (g == 0) wr = lds128(xa + 17 * 1152);
        uint2 yv[4];
        const uint32_t Z[2][4] = {{x0.x, x0.y, x0.z, x0.w}, {x1.x, x1.y, x1.z, x1.w}}, D4[4] = {dk.x, dk.y, dk.z, dk.w};
#pragma unroll
        for (int hf = 0; hf < 2; hf++) {
            const uint2 st = lds64(s_stat + (g + 8 * hf) * 8);
#pragma unroll
            for (int k = 0; k < 4; k++) U2[hf][k] = hmul2_bf(ln_apply(Z[hf][k], STAT_M(st), STAT_H(st), STAT_L(st)), D4[k]);
        }
        const uint32_t la = pin(sb + SM_LNP + (g * 20 + warp) * 4);
        {
            const unsigned char* y1 = ys + (U2[0][0] & U2[1][2] & (warp >> 8));
#pragma unroll
            for (int k = 0; k < 4; k++) yv[k] = ld_poll64(y1 + k * 128);
        }
        int it = 0;
        float d[2][4];
        while (true) {
            const uint32_t mn = min3(min3(yv[0].x, yv[0].y, yv[1].x), min3(yv[1].y, yv[2].x, yv[2].y), min(yv[3].x, yv[3].y));
#pragma unroll
            for (int k = 0; k < 4; k++) {
                H[0][k] = hadd2_bf(Z[0][k], hadd2_bf(movm(yv[k].x), U2[0][k]));
                H[1][k] = hadd2_bf(Z[1][k], hadd2_bf(movm(yv[k].y), U2[1][k]));
            }
            ln_partial(H, d);
            if (!__any_sync(0xffffffffu, mn == 0)) break;
            if (++it > SPIN_LIMIT) TRAP();
#pragma unroll
            for (int k = 0; k < 4; k++) yv[k] = ld_poll64(ys + k * 128);
        }
        STAMP(12);
        {
            const float s0 = (g & 1) ? d[0][3] : d[0][2], s1 = (g & 1) ? d[1][3] : d[1][2];
            const float q0 = (g & 1) ? d[0][1] : d[0][0], q1 = (g & 1) ? d[1][1] : d[1][0];
            asm volatile("{\n.reg .pred p;\nsetp.eq.u32 p, %5, %6;\n@p st.shared.f32 [%0], %1;\n@p st.shared.f32 [%0 + 640], %2;\n@p st.shared.f32 [%0 + 1280], %3;\n@p st.shared.f32 [%0 + 1920], %4;\n}\n"
                         ::"r"(la), "f"(s0), "f"(s1), "f"(q0), "f"(q1), "r"(t), "r"(g >> 1) : "memory");
        }
        bar_arrive(6, NWRK);
        STAMP(13);
        bar_sync(7, 608);
        STAMP(14);
#pragma unroll
        for (int hf = 0; hf < 2; hf++) {
            const uint2 st = lds64(s_stat + (g + 8 * hf) * 8);
#pragma unroll
            for (int k = 0; k < 4; k++) U2[hf][k] = ln_apply(H[hf][k], STAT_M(st), STAT_H(st), STAT_L(st));
        }
        {
            float cs[4] = {0.f, 0.f, 0.f, 0.f};
            mma_bf16(cs, U2[0][0], U2[1][0], U2[0][1], U2[1][1], wr.x, wr.y);
            mma_bf16(cs, U2[0][2], U2[1][2], U2[0][3], U2[1][3], wr.z, wr.w);
            if (t == 0) { stsf(la + 32 * 80, cs[0]); stsf(la + 40 * 80, cs[2]); }
            bar_arrive(8, 608);
        }
        FIX((uint32_t)warp >> 8);
        uint32_t O[2][4];
#pragma unroll
        for (int hf = 0; hf < 2; hf++)
#pragma unroll
            for (int k = 0; k < 4; k++) { O[hf][k] = hadd2_bf(H[hf][k], U2[hf][k]); H[hf][k] = nzw(H[hf][k]); U2[hf][k] = nzw(U2[hf][k]); }
        unsigned char* rowp = reinterpret_cast<unsigned char*>(p.s->rows) + ((254 - 2 * b) * 2304 + warp * 64 + t * 16);
        FIX(and3(and3(and3(H[0][0], H[0][1], H[0][2]), and3(H[0][3], H[1][0], H[1][1]), and3(H[1][2], H[1][3], U2[0][0])),
                 and3(and3(U2[0][1], U2[0][2], U2[0][3]), and3(U2[1][0], U2[1][1], U2[1][2]), U2[1][3]), (uint32_t)reinterpret_cast<uint64_t>(rowp)));
        bar_sync(9, 608);
        {
            const uint2 best = lds64(s_rank);
#pragma unroll
            for (int hf = 0; hf < 2; hf++) {
                const uint32_t me = 2 * TOK(g) + 4 * hf;
                unsigned char* d = rowp + (best.x == me ? 2304 : 0);
                if (best.x == me || best.y == me) {
                    stg128(d, U2[hf][0], U2[hf][1], U2[hf][2], U2[hf][3]);
                    stg128(d + 1152, H[hf][0], H[hf][1], H[hf][2], H[hf][3]);
                }
            }
        }
        FIX((uint32_t)warp >> 9);
#pragma unroll
        for (int hf = 0; hf < 2; hf++) {
            sts128(sb + SM_OUT + (TOK(g) + 2 * hf) * (DM * 2) + warp * 64 + t * 16, O[hf][0], O[hf][1], O[hf][2], O[hf][3]);
            sts128(sb + SM_U + hf * 9216 + tid * 16, H[hf][0], H[hf][1], H[hf][2], H[hf][3]);
        }
        STAMP(15);
        const int mi = lane >> 3, rr = lane & 7;
        const bool gate = warp < 12 && (warp & 3) != 2;
        const int fj = gate ? 3 * (warp >> 2) + min(warp & 3, 2) : (warp < 12 ? warp >> 2 : warp - 9);
        if (gate) {
            uint32_t W[18][4];
            mbar_wait(bar_w);
            const uint32_t aad = fj < 8 ? sb + SM_WG + (mi & 1) * SM_WU + (rr + 8 * (mi >> 1)) * 128 + (fj ^ rr) * 16 : sb + SM_WR + (mi & 1) * 4608 + (rr + 8 * (mi >> 1)) * 16;
            const uint32_t ast = fj < 8 ? 2048 : 256;
            const uint32_t bad = pin(sb + SM_XS + rr * XS_PITCH + mi * 16);
            bool rare = warp >> 8;
#pragma unroll 1
            do {
                if (rare) late_rows(IC<0>());
#pragma unroll
                for (int k = 0; k < 18; k++) ldsm_x4_t(W[k][0], W[k][1], W[k][2], W[k][3], aad + k * ast);
                if (rare) break;
                fence_async();
                STAMP2(17);
                rare = bar_or(11, NWRK, false);
            } while (rare);
            STAMP2(19);
            float c4[2][4] = {};
#pragma unroll
            for (int k = 0; k < 18; k += 2) {
                uint32_t b0, b1, b2, b3;
                ldsm_x4(b0, b1, b2, b3, bad + k * 32);
                mma_bf16(c4[0], W[k][0], W[k][1], W[k][2], W[k][3], b0, b1);
                mma_bf16(c4[1], W[k + 1][0], W[k + 1][1], W[k + 1][2], W[k + 1][3], b2, b3);
            }
            const uint32_t ex = sb + SM_EX + (32 * fj + lane) * 16;
            const float e0 = c4[0][0] + c4[1][0], e1 = c4[0][1] + c4[1][1], e2 = c4[0][2] + c4[1][2], e3 = c4[0][3] + c4[1][3];
            asm volatile("st.async.shared::cluster.mbarrier::complete_tx::bytes.v4.f32 [%0], {%1,%2,%3,%4}, [%5];\n"
                         ::"r"(ex ^ 0x1000000u), "f"(e0), "f"(e1), "f"(e2), "f"(e3), "r"(bar_g ^ 0x1000000u) : "memory");
            STAMP2(20);
            mbar_wait(bar_g);
            const uint4 o = lds128(ex);
            const uint32_t G = pack_bf16(e0 + __uint_as_float(o.x), e1 + __uint_as_float(o.y)), U = pack_bf16(e2 + __uint_as_float(o.z), e3 + __uint_as_float(o.w));
            sts32(sb + SM_GU + (32 * fj + lane) * 4, hmul2_bf(pack_bf16(bf_lo(G) * sigmoid_f(bf_lo(G)), bf_hi(G) * sigmoid_f(bf_hi(G))), U));
            bar_arrive(13, NWRK);
        } else {
            uint32_t W[2][18];
            auto load_wd = [&]() {
                mbar_wait(bar_d);
                const uint32_t base = sb + SM_WD + (4 * fj + (mi & 1)) * 16 + rr * WD_PITCH;
#pragma unroll
                for (int j = 0; j < 2; j++) {
#pragma unroll
                    for (int k = 0; k < 4; k++) ldsm_x4_t(W[j][4 * k], W[j][4 * k + 1], W[j][4 * k + 2], W[j][4 * k + 3], base + j * 32 + (k * 16 + 8 * (mi >> 1)) * WD_PITCH);
                    ldsm_x2_t(W[j][16], W[j][17], base + j * 32 + 64 * WD_PITCH);
                }
            };
            const uint32_t po = pin((((8 * (18 * odd + 2 * fj) + g) * 64 + P) * 4 + t) * 8);
            fence_async();
            STAMP2(17);
            const bool first = (warp & 3) != 2;
#pragma unroll 1
            for (int i = 0; i < 2; i++) {
                if (i == (first ? 1 : 0)) {
                    if (bar_or(11, NWRK, false)) late_rows(IC<0>());
                    if (!first) delay(DDLY);
                } else load_wd();
            }
            bar_sync(13, NWRK);
            STAMP2(21);
            uint32_t gb[9];
            ldsm_x4_t(gb[0], gb[1], gb[2], gb[3], sb + SM_GU + lane * 16);
            ldsm_x4_t(gb[4], gb[5], gb[6], gb[7], sb + SM_GU + 512 + lane * 16);
            ldsm_x1_t(gb[8], sb + SM_GU + 1024 + lane * 16);
            float c4[2][4] = {}, d4[2][4] = {};
#pragma unroll
            for (int k = 0; k < 4; k += 2)
#pragma unroll
                for (int j = 0; j < 2; j++) {
                    mma_bf16(c4[j], W[j][4 * k], W[j][4 * k + 1], W[j][4 * k + 2], W[j][4 * k + 3], gb[2 * k], gb[2 * k + 1]);
                    mma_bf16(d4[j], W[j][4 * k + 4], W[j][4 * k + 5], W[j][4 * k + 6], W[j][4 * k + 7], gb[2 * k + 2], gb[2 * k + 3]);
                }
#pragma unroll
            for (int j = 0; j < 2; j++) mma_bf16_k8(c4[j], W[j][16], W[j][17], gb[8]);
#pragma unroll
            for (int j = 0; j < 2; j++)
                stg64(reinterpret_cast<unsigned char*>(p.s->part) + po + j * 16384, nzw(pack_bf16(c4[j][0] + d4[j][0], c4[j][1] + d4[j][1])), nzw(pack_bf16(c4[j][2] + d4[j][2], c4[j][3] + d4[j][3])));
        }
        STAMP2(22);
    } else if (warp == 18) {
        const uint4* const ksrc = reinterpret_cast<const uint4*>(p.s->key3) + pin(2 * lane);
        const int row = (g >> 1) + 4 * (g & 1);
        const uint32_t ro = pin(640 * odd + t * 16), xd = pin(sb + SM_XS + row * XS_PITCH + t * 16 + (odd ? 0 : 512));
        const uint32_t xe = pin(sb + SM_XS + (g >> 1) * XS_PITCH + (lane & 7) * 16 + 64 * odd);
        const uint32_t sa = pin(sb + SM_LNP + lane * 80);
        const uint32_t klo = pin((uint32_t)(127 - b) << 9 | (uint32_t)(15 - ROWTOK(lane & 15)) << 1 | par), ra = pin(sb + SM_LNP + (32 + (lane & 15)) * 80);
        uint4* const kdst = reinterpret_cast<uint4*>(p.s->key3) + pin((lane >> 1) * 2 * NCTA + 2 * b + (lane & 1));
        FIX(ra);
        bar_sync(6, NWRK);
        {
            float mb, rc;
            ln_finish(sum18(sa), lane, mb, rc);
            if (lane < 16) stat_store(s_stat + lane * 8, mb, rc, 0u);
        }
        bar_arrive(7, 608);
        bar_sync(8, 608);
        uint32_t t0;
        {
            const uint32_t bits = __float_as_uint(rbf(sum18(ra)));
            const uint32_t me = ((bits ^ ((uint32_t)((int)bits >> 31) | 0x80000000u)) & 0xffff0000u) | klo;
            const uint32_t k0 = __reduce_max_sync(0xffffffffu, me), k1 = __reduce_max_sync(0xffffffffu, me == k0 ? 0u : me);
            const uint32_t k2 = __reduce_max_sync(0xffffffffu, me >= k1 ? 0u : me);
            if (lane < 2) stg128(kdst, k0 ^ 0x11eu, k1 ^ 0xfeu, k2 ^ 0xdeu, par);
            asm volatile("mov.u32 %0, %%clock;" : "=r"(t0) :: "memory");
            STAMPW(23);
            if (lane == 0) sts64(s_rank, ~k0 & 30u, ~k1 & 30u);
            bar_arrive(9, 608);
            sts32(s_k16 + (lane & 15) * 4, me);
            __syncwarp();
            const uint4 v = lds128(s_k16 + (lane & 16) * 2), w = lds128(s_k16 + (lane & 16) * 2 + 16);
            int rank = ((v.x > me) + (v.y > me)) + ((v.z > me) + (v.w > me)) + (((w.x > me) + (w.y > me)) + ((w.z > me) + (w.w > me)));
            rank += __shfl_xor_sync(0xffffffffu, rank, 16);
            if (lane < 16 && rank < 8) p.s->key[8 * b + rank] = (me ^ 0x1eu) | ((8 - rank) << 5);
        }
        uint4 kq[4];
        uint32_t u[4], mine = 0, m;
        int it = 0;
        { uint32_t now; do { asm volatile("mov.u32 %0, %%clock;" : "=r"(now) :: "memory"); } while (now - t0 < KDLY); }
        do {
#pragma unroll
            for (int i = 0; i < 4; i++) kq[i] = ld_poll(ksrc + 64 * i);
            if (++it > SPIN_LIMIT) TRAP();
            uint32_t S[2][4];
#pragma unroll
            for (int i = 0; i < 2; i++) {
                const uint4 &c = kq[2 * i], &d = kq[2 * i + 1];
                const uint32_t m1 = min(c.x, d.x), m2 = max(c.y, d.y);
                S[i][0] = max(c.x, d.x); S[i][1] = max(m1, m2); S[i][2] = min(m1, m2); S[i][3] = min(c.y, d.y);
            }
            const uint32_t a0 = max(S[0][0], S[1][3]), a1 = max(S[0][1], S[1][2]), a2 = max(S[0][2], S[1][1]), a3 = max(S[0][3], S[1][0]);
            const uint32_t b0 = max(a0, a2), b2 = min(a0, a2), b1 = max(a1, a3), b3 = min(a1, a3);
            u[0] = max(b0, b1); u[1] = min(b0, b1); u[2] = max(b2, b3); u[3] = min(b2, b3);
            const uint32_t bad = or3(or3(xor_or(kq[0].x, kq[0].y, par), xor_or(kq[0].z, kq[1].x, par), xor_or(kq[1].y, kq[1].z, par)),
                                     xor_or(kq[2].x, kq[2].y, par), xor_or(kq[2].z, kq[3].x, par)) | xor_or(kq[3].y, kq[3].z, par);
            m = __reduce_max_sync(0xffffffffu, u[0] | (uint32_t)((int)(bad << 31) >> 31));
        } while (m == 0xffffffffu);
        STAMPW(16);
#pragma unroll
        for (int r = 0; r < 8; r++) {
            if (r) m = __reduce_max_sync(0xffffffffu, u[0]);
            if (u[0] == m) { u[0] = u[1]; u[1] = u[2]; u[2] = u[3]; u[3] = 0; }
            if (row == r) mine = m;
        }
        uint4 v[9];
        const uint32_t o0 = __byte_perm(mine, 0, 0x4441) * 2304u, o1 = __shfl_xor_sync(0xffffffffu, o0, 4);
        const unsigned char* const rA = reinterpret_cast<const unsigned char*>(p.s->rows) + (((g & 1) ? o1 : o0) + ro + (g & 1) * 64);
        const unsigned char* const rb = reinterpret_cast<const unsigned char*>(p.s->rows) + (((g & 1) ? o0 : o1) + ro + (g & 1) * 64);
        const unsigned char* const rc = reinterpret_cast<const unsigned char*>(p.s->rows) + (o0 + ro + (odd ? -64 : 512));
#pragma unroll
        for (int i = 0; i < 4; i++) { v[i] = ld_poll(rA + i * 128); v[4 + i] = ld_poll(rb + i * 128); }
        v[8] = ld_poll(rc);
        const bool again = u[0] == 0 || max(max(kq[0].z, kq[1].z), max(kq[2].z, kq[3].z)) > m;
        if (t == 0) sts32(s_key + row * 4, mine);
#pragma unroll
        for (int i = 0; i < 9; i++) sts128(i < 8 ? xe + (i >> 2) * 4 * XS_PITCH + (i & 3) * 128 : xd, v[i].x, v[i].y, v[i].z, v[i].w);
        uint32_t mn, m3[3];
        m3[0] = m3[1] = m3[2] = 1u;
#pragma unroll
        for (int i = 0; i < 9; i++) m3[i % 3] = min3(min3(m3[i % 3], v[i].x, v[i].y), v[i].z, v[i].w);
        mn = min3(m3[0], m3[1], m3[2]);
        STAMPW(18);
        if (bar_or(11, NWRK, again || mn == 0)) late_rows(IC<1>());
    } else {
        bar_sync(6, NWRK);
        WPOINT(16, true);
        if (WANY(17) || WANY(18)) delay(WDLY);
        WPOINT(17, true);
        if (WANY(18)) delay(WDLY);
        WPOINT(18, true);
        if (bar_or(11, NWRK, false)) late_rows(IC<2>());
        const int tk = KTOK(lds32(s_key + (lane & 7) * 4));
        const uint32_t sel = __reduce_or_sync(0xffffffffu, (tk >> 4) == b ? 1u << (tk & 15) : 0u);
        if (sel ? lane < 16 && !((sel >> lane) & 1u) : lane == 0) bulk_s2g(p.out + (size_t)(16 * b + lane) * DM, sb + SM_OUT + lane * (DM * 2), sel ? DM * 2 : 16 * DM * 2);
        __syncwarp();
    }
    if (warp == 8 || warp >= 18) {
        const int grp = 3 * b + (warp == 8 ? 0 : warp - 17), fsl = 2 * t + ((lane >> 3) & 1), fc = 16 * (grp >> 3) + (grp & 7) + 8 * (lane >> 4);
        const uint32_t fk = lds32(s_key + fsl * 4);
        float hv = 0.f, u2 = 0.f;
        int it = 0;
        if (b < 96) {
            const uint32_t* const fsrc = p.s->rows + KSLOT(fk, fsl) * DM + (fc >> 1);
            uint32_t hw, uw;
            do { hw = ld_poll32(fsrc + 288); uw = ld_poll32(fsrc); if (++it > SPIN_LIMIT) TRAP(); } while (!hw || !uw);
            hv = (fc & 1) ? bf_hi(hw) : bf_lo(hw); u2 = (fc & 1) ? bf_hi(uw) : bf_lo(uw);
        }
        const float rs = rbf(sigmoid_f(__uint_as_float((fk ^ ((uint32_t)((int)~fk >> 31) | 0x80000000u)) & 0xffff0000u)));
        const uint32_t dof = pin(KTOK(fk) * DM + fc), so = pin(grp * 256 + lane);
        if (warp > 17) bar_sync(13, NWRK);
        if (b < 96) {
            delay(warp > 17 ? FDLY : FDLY2);
            float y;
            uint32_t ok;
            float s0, s1, s2, s3;
            do {
                uint2 a[8];
#pragma unroll
                for (int i = 0; i < 8; i++) a[i] = ld_poll64(reinterpret_cast<const uint2*>(p.s->part) + so + 32 * i);
                if (++it > SPIN_LIMIT) TRAP();
                ok = min3(min3(min3(a[0].x, a[0].y, a[1].x), min3(a[1].y, a[2].x, a[2].y), min3(a[3].x, a[3].y, a[4].x)), min3(min3(a[4].y, a[5].x, a[5].y), min3(a[6].x, a[6].y, a[7].x), a[7].y), 1u);
#define S8(c, f) (((c(a[0].f) + c(a[1].f)) + (c(a[2].f) + c(a[3].f))) + ((c(a[4].f) + c(a[5].f)) + (c(a[6].f) + c(a[7].f))))
                s0 = S8(bf_lo, x); s1 = S8(bf_hi, x); s2 = S8(bf_lo, y); s3 = S8(bf_hi, y);
                asm volatile("" : "+f"(s0), "+f"(s1), "+f"(s2), "+f"(s3));
#undef S8
            } while (__any_sync(0xffffffffu, !ok));
            STAMP2(24);
#define HALVE(u, v, m) (((lane & m) ? v : u) + __shfl_xor_sync(0xffffffffu, (lane & m) ? u : v, m))
            const float r0 = HALVE(s0, s2, 16), r1 = HALVE(s1, s3, 16);
            y = HALVE(r0, r1, 8);
            y += __shfl_xor_sync(0xffffffffu, y, 4);
#undef HALVE
            p.out[dof] = __float2bfloat16_rn(hv + rbf(u2 + rbf(rbf(y) * rs)));
        }
    }
    if (warp == 19) asm volatile("cp.async.bulk.wait_group.read 0;\n" ::: "memory");
    if (b == 0 && tid < 8) *reinterpret_cast<volatile unsigned*>(p.s->hint + tid * 32 + 1) = lds32(s_cnt + 4) + 1u;
    STAMP(25);
    }
}

typedef CUresult (*PFN_tmEncode)(CUtensorMap*, CUtensorMapDataType, cuuint32_t, void*, const cuuint64_t*, const cuuint64_t*, const cuuint32_t*,
                                 const cuuint32_t*, CUtensorMapInterleave, CUtensorMapSwizzle, CUtensorMapL2promotion, CUtensorMapFloatOOBfill);

extern "C" void kernel_launch(void* const* d_in, const int* in_sizes, int n_in, void* d_out, int out_size) {
    Params p;
    p.x = (const bf16*)d_in[0];
    p.lar = (const bf16*)d_in[1];
    p.aim = (const bf16*)d_in[2];
    p.cre = (const bf16*)d_in[3];
    p.cim = (const bf16*)d_in[4];
    p.ldt = (const bf16*)d_in[5];
    p.dsk = (const bf16*)d_in[6];
    p.wr = (const bf16*)d_in[8];
    p.out = (bf16*)d_out;
    static PFN_tmEncode enc = nullptr;
    static void* scratch = nullptr;
    if (!enc) {
        cudaFuncSetAttribute(fused_kernel, cudaFuncAttributeMaxDynamicSharedMemorySize, SMEM_TOTAL);
        void* fn = nullptr;
        cudaDriverEntryPointQueryResult qr;
        cudaGetDriverEntryPoint("cuTensorMapEncodeTiled", &fn, cudaEnableDefault, &qr);
        enc = (PFN_tmEncode)fn;
        cudaGetSymbolAddress(&scratch, g_scratch);
    }
    p.s = (Scratch*)scratch;
    Maps tm;
    const cuuint64_t dims[2] = {FF, DM}, strides[1] = {FF * 2};
    const cuuint32_t box[2] = {64, 48}, rbox[2] = {8, 144}, es[2] = {1, 1};
    for (int i = 0; i < 2; i++) {
        enc(&tm.w[i], CU_TENSOR_MAP_DATA_TYPE_BFLOAT16, 2, d_in[9 + i], dims, strides, box, es, CU_TENSOR_MAP_INTERLEAVE_NONE, CU_TENSOR_MAP_SWIZZLE_128B,
            CU_TENSOR_MAP_L2_PROMOTION_NONE, CU_TENSOR_MAP_FLOAT_OOB_FILL_NONE);
        enc(&tm.r[i], CU_TENSOR_MAP_DATA_TYPE_BFLOAT16, 2, d_in[9 + i], dims, strides, rbox, es, CU_TENSOR_MAP_INTERLEAVE_NONE, CU_TENSOR_MAP_SWIZZLE_NONE,
            CU_TENSOR_MAP_L2_PROMOTION_NONE, CU_TENSOR_MAP_FLOAT_OOB_FILL_NONE);
    }
    const cuuint64_t ddims[2] = {DM / 2, FF}, dstrides[1] = {DM * 2};
    const cuuint32_t dbox[2] = {WD_PITCH / 4, 8};
    enc(&tm.d, CU_TENSOR_MAP_DATA_TYPE_UINT32, 2, d_in[11], ddims, dstrides, dbox, es, CU_TENSOR_MAP_INTERLEAVE_NONE, CU_TENSOR_MAP_SWIZZLE_NONE,
        CU_TENSOR_MAP_L2_PROMOTION_L2_128B, CU_TENSOR_MAP_FLOAT_OOB_FILL_NONE);
    const cuuint64_t xdims[4] = {DM, 128, 4, 4}, xstrides[3] = {DM * 8, DM * 2, DM * 1024};
    const cuuint32_t xbox[4] = {8, 128, 4, 2}, xes[4] = {1, 1, 1, 1};
    enc(&tm.x, CU_TENSOR_MAP_DATA_TYPE_BFLOAT16, 4, d_in[0], xdims, xstrides, xbox, xes, CU_TENSOR_MAP_INTERLEAVE_NONE, CU_TENSOR_MAP_SWIZZLE_NONE,
        CU_TENSOR_MAP_L2_PROMOTION_NONE, CU_TENSOR_MAP_FLOAT_OOB_FILL_NONE);
    fused_kernel<<<NCTA, NTHR, SMEM_TOTAL>>>(p, tm);
}
```

```cpp
#include <cuda_runtime.h>
#include <cuda.h>
#include <cuda_fp16.h>
#include <cuda_bf16.h>
#include <stdint.h>

#define LSEQ 2048
#define DM 576
#define NST 128
#define FF 4608
#define NSEL 8
#define NCTA 128
#define NTHR 640
#define NWRK 640

typedef __nv_bfloat16 bf16;

#define SM_WG 0
#define SM_WU 36864
#define SM_WR 73728
#define SM_XC (82944 - 32768)
#define SM_WD 82944
#define WD_PITCH 592
#define SM_Z2 (SM_WD + 10240)
#define SM_XT (SM_PL - 18 * 1152)
#define SM_PL (SM_WD + 46080)
#define PL_HALF 1344
#define PLW_B 2624
#define PL_B (4 * PLW_B)
#define SM_U (SM_PL + 5 * PL_B)
#define UPAD 20
#define ULO_B ((UPAD + 128) * 16)
#define USLOT_B (2 * ULO_B)
#define SM_KW (SM_U + 5 * USLOT_B)
#define KW_B 3712
#define KW_PL 1216
#define KW_P 2400
#define KW_H 3440
#define SM_MISC (SM_KW + 5 * KW_B)
#define SM_LC (SM_MISC + 416)
#define SM_LNP (SM_LC + 768)
#define SM_RX (SM_LNP + 3840)
#define SMEM_TOTAL (SM_RX + 3088)
#define TBW PLW_B
#define SM_OUT SM_PL
#define SM_XS (SM_PL + 18432)
#define XS_PITCH 592
#define SM_GU (SM_PL + 23296)
#define SM_EX (SM_PL + 24576)

struct __align__(128) Scratch {
    unsigned hint[8 * 32];
    unsigned flag[32];
    uint32_t key3[NCTA * 8];
    uint32_t key[NCTA * 8];
    uint32_t stat[LSEQ];
    uint32_t uT[64 * (LSEQ / 2)];
    uint32_t y[(NCTA + 96) * DM * 8];
    uint32_t part[288 * 64 * 8];
    uint32_t rows[(2 * NCTA + NSEL) * DM];
};
__device__ Scratch g_scratch;
#define STAMP(i)
#define STAMPX(i)
#define STAMPY(i)

__device__ __forceinline__ float rbf(float x) {
    uint32_t r;
    asm("cvt.rn.bf16x2.f32 %0, %1, %2;\n" : "=r"(r) : "f"(x), "f"(0.f));
    return __uint_as_float(r);
}
__device__ __forceinline__ uint32_t pack_bf16(float lo, float hi) {
    uint32_t r;
    asm("cvt.rn.bf16x2.f32 %0, %1, %2;\n" : "=r"(r) : "f"(hi), "f"(lo));
    return r;
}
__device__ __forceinline__ uint32_t pack_f16(float lo, float hi) {
    uint32_t r;
    asm("cvt.rn.f16x2.f32 %0, %1, %2;\n" : "=r"(r) : "f"(hi), "f"(lo));
    return r;
}
__device__ __forceinline__ float bf_lo(uint32_t w) { return __uint_as_float(w << 16); }
__device__ __forceinline__ float bf_hi(uint32_t w) { return __uint_as_float(w & 0xffff0000u); }
__device__ __forceinline__ uint32_t hadd2_bf(uint32_t a, uint32_t b) {
    __nv_bfloat162 r = __hadd2_rn(*reinterpret_cast<__nv_bfloat162*>(&a), *reinterpret_cast<__nv_bfloat162*>(&b));
    return *reinterpret_cast<uint32_t*>(&r);
}
__device__ __forceinline__ uint32_t hsub2_bf(uint32_t a, uint32_t b) {
    __nv_bfloat162 r = __hsub2_rn(*reinterpret_cast<__nv_bfloat162*>(&a), *reinterpret_cast<__nv_bfloat162*>(&b));
    return *reinterpret_cast<uint32_t*>(&r);
}
__device__ __forceinline__ uint32_t hmul2_bf(uint32_t a, uint32_t b) {
    __nv_bfloat162 r = __hmul2_rn(*reinterpret_cast<__nv_bfloat162*>(&a), *reinterpret_cast<__nv_bfloat162*>(&b));
    return *reinterpret_cast<uint32_t*>(&r);
}
__device__ __forceinline__ uint32_t hfma2_bf(uint32_t a, uint32_t b, uint32_t c) { uint32_t r; asm("fma.rn.bf16x2 %0, %1, %2, %3;\n" : "=r"(r) : "r"(a), "r"(b), "r"(c)); return r; }
__device__ __forceinline__ uint32_t hmul2(uint32_t a, uint32_t b) { uint32_t r; asm("mul.rn.f16x2 %0, %1, %2;\n" : "=r"(r) : "r"(a), "r"(b)); return r; }
__device__ __forceinline__ uint32_t hadd2(uint32_t a, uint32_t b) { uint32_t r; asm("add.rn.f16x2 %0, %1, %2;\n" : "=r"(r) : "r"(a), "r"(b)); return r; }
__device__ __forceinline__ uint32_t hfma2(uint32_t a, uint32_t b, uint32_t c) { uint32_t r; asm("fma.rn.f16x2 %0, %1, %2, %3;\n" : "=r"(r) : "r"(a), "r"(b), "r"(c)); return r; }
__device__ __forceinline__ uint32_t hfms2(uint32_t a, uint32_t b, uint32_t c) {
    uint32_t r;
    asm("{\n.reg .b32 n;\nneg.f16x2 n, %2;\nfma.rn.f16x2 %0, %1, n, %3;\n}\n" : "=r"(r) : "r"(a), "r"(b), "r"(c));
    return r;
}
__device__ __forceinline__ uint32_t nzw(uint32_t w) { uint32_t r; asm("max.u32 %0, %1, 1;\n" : "=r"(r) : "r"(w)); return r; }
__device__ __forceinline__ uint32_t smem_u32(const void* p) { return (uint32_t)__cvta_generic_to_shared(p); }
__device__ __forceinline__ uint32_t lds32(uint32_t addr) {
    uint32_t v;
    asm volatile("ld.shared.u32 %0, [%1];\n" : "=r"(v) : "r"(addr) : "memory");
    return v;
}
__device__ __forceinline__ uint32_t lds16(uint32_t addr) {
    unsigned short v;
    asm volatile("ld.shared.u16 %0, [%1];\n" : "=h"(v) : "r"(addr) : "memory");
    return v;
}
__device__ __forceinline__ uint2 lds64(uint32_t addr) {
    uint2 v;
    asm volatile("ld.shared.v2.u32 {%0,%1}, [%2];\n" : "=r"(v.x), "=r"(v.y) : "r"(addr) : "memory");
    return v;
}
__device__ __forceinline__ uint4 lds128(uint32_t addr) {
    uint4 v;
    asm volatile("ld.shared.v4.u32 {%0,%1,%2,%3}, [%4];\n" : "=r"(v.x), "=r"(v.y), "=r"(v.z), "=r"(v.w) : "r"(addr) : "memory");
    return v;
}
__device__ __forceinline__ void sts32(uint32_t addr, uint32_t v) { asm volatile("st.shared.u32 [%0], %1;\n" ::"r"(addr), "r"(v) : "memory"); }
__device__ __forceinline__ void sts16(uint32_t addr, uint32_t v) { asm volatile("st.shared.u16 [%0], %1;\n" ::"r"(addr), "h"((unsigned short)v) : "memory"); }
__device__ __forceinline__ void stsf(uint32_t addr, float v) { sts32(addr, __float_as_uint(v)); }
__device__ __forceinline__ void sts64(uint32_t addr, uint32_t a, uint32_t b) { asm volatile("st.shared.v2.u32 [%0], {%1,%2};\n" ::"r"(addr), "r"(a), "r"(b) : "memory"); }
__device__ __forceinline__ void sts128(uint32_t addr, uint32_t a, uint32_t b, uint32_t c, uint32_t d) {
    asm volatile("st.shared.v4.u32 [%0], {%1,%2,%3,%4};\n" ::"r"(addr), "r"(a), "r"(b), "r"(c), "r"(d) : "memory");
}
__device__ __forceinline__ void ldsm_x4(uint32_t& r0, uint32_t& r1, uint32_t& r2, uint32_t& r3, uint32_t addr) {
    asm volatile("ldmatrix.sync.aligned.m8n8.x4.shared.b16 {%0,%1,%2,%3}, [%4];\n"
                 : "=r"(r0), "=r"(r1), "=r"(r2), "=r"(r3) : "r"(addr) : "memory");
}
__device__ __forceinline__ void ldsm_x4_t(uint32_t& r0, uint32_t& r1, uint32_t& r2, uint32_t& r3, uint32_t addr) {
    asm volatile("ldmatrix.sync.aligned.m8n8.x4.trans.shared.b16 {%0,%1,%2,%3}, [%4];\n"
                 : "=r"(r0), "=r"(r1), "=r"(r2), "=r"(r3) : "r"(addr) : "memory");
}
__device__ __forceinline__ void ldsm_x2_t(uint32_t& r0, uint32_t& r1, uint32_t addr) {
    asm volatile("ldmatrix.sync.aligned.m8n8.x2.trans.shared.b16 {%0,%1}, [%2];\n" : "=r"(r0), "=r"(r1) : "r"(addr) : "memory");
}
__device__ __forceinline__ void ldsm_x1_t(uint32_t& r0, uint32_t addr) {
    asm volatile("ldmatrix.sync.aligned.m8n8.x1.trans.shared.b16 {%0}, [%1];\n" : "=r"(r0) : "r"(addr) : "memory");
}
__device__ __forceinline__ void stsm_x4(uint32_t addr, uint32_t r0, uint32_t r1, uint32_t r2, uint32_t r3) {
    asm volatile("stmatrix.sync.aligned.m8n8.x4.shared.b16 [%0], {%1,%2,%3,%4};\n" ::"r"(addr), "r"(r0), "r"(r1), "r"(r2), "r"(r3) : "memory");
}
__device__ __forceinline__ void stsm_x4_t(uint32_t addr, uint32_t r0, uint32_t r1, uint32_t r2, uint32_t r3) {
    asm volatile("stmatrix.sync.aligned.m8n8.x4.trans.shared.b16 [%0], {%1,%2,%3,%4};\n" ::"r"(addr), "r"(r0), "r"(r1), "r"(r2), "r"(r3) : "memory");
}
__device__ __forceinline__ uint32_t movm(uint32_t a) {
    uint32_t d;
    asm volatile("movmatrix.sync.aligned.m8n8.trans.b16 %0, %1;\n" : "=r"(d) : "r"(a));
    return d;
}
__device__ __forceinline__ void mma_f16(float (&c)[4], uint32_t a0, uint32_t a1, uint32_t a2, uint32_t a3, uint32_t b0, uint32_t b1) {
    asm volatile(
        "mma.sync.aligned.m16n8k16.row.col.f32.f16.f16.f32 {%0,%1,%2,%3}, {%4,%5,%6,%7}, {%8,%9}, {%0,%1,%2,%3};\n"
        : "+f"(c[0]), "+f"(c[1]), "+f"(c[2]), "+f"(c[3])
        : "r"(a0), "r"(a1), "r"(a2), "r"(a3), "r"(b0), "r"(b1));
}
__device__ __forceinline__ void mma_bf16(float (&c)[4], uint32_t a0, uint32_t a1, uint32_t a2, uint32_t a3, uint32_t b0, uint32_t b1) {
    asm volatile(
        "mma.sync.aligned.m16n8k16.row.col.f32.bf16.bf16.f32 {%0,%1,%2,%3}, {%4,%5,%6,%7}, {%8,%9}, {%0,%1,%2,%3};\n"
        : "+f"(c[0]), "+f"(c[1]), "+f"(c[2]), "+f"(c[3])
        : "r"(a0), "r"(a1), "r"(a2), "r"(a3), "r"(b0), "r"(b1));
}
__device__ __forceinline__ void mma_bf16_k8(float (&c)[4], uint32_t a0, uint32_t a1, uint32_t b0) {
    asm volatile("mma.sync.aligned.m16n8k8.row.col.f32.bf16.bf16.f32 {%0,%1,%2,%3}, {%4,%5}, {%6}, {%0,%1,%2,%3};\n"
                 : "+f"(c[0]), "+f"(c[1]), "+f"(c[2]), "+f"(c[3]) : "r"(a0), "r"(a1), "r"(b0));
}
__device__ __forceinline__ void bar_sync(int id, int n) { asm volatile("bar.sync %0, %1;\n" ::"r"(id), "r"(n) : "memory"); }
__device__ __forceinline__ void bar_arrive(int id, int n) { asm volatile("bar.arrive %0, %1;\n" ::"r"(id), "r"(n) : "memory"); }
__device__ __forceinline__ bool bar_or(int id, int n, bool v) {
    uint32_t r;
    asm volatile("{\n.reg .pred p, q;\nsetp.ne.u32 p, %3, 0;\nbar.red.or.pred q, %1, %2, p;\nselp.u32 %0, 1, 0, q;\n}\n" : "=r"(r) : "r"(id), "r"(n), "r"((uint32_t)v) : "memory");
    return r;
}
__device__ __forceinline__ uint32_t and3(uint32_t a, uint32_t b, uint32_t c) { uint32_t r; asm("lop3.b32 %0, %1, %2, %3, 0x80;\n" : "=r"(r) : "r"(a), "r"(b), "r"(c)); return r; }
__device__ __forceinline__ uint32_t or3(uint32_t a, uint32_t b, uint32_t c) { uint32_t r; asm("lop3.b32 %0, %1, %2, %3, 0xfe;\n" : "=r"(r) : "r"(a), "r"(b), "r"(c)); return r; }
__device__ __forceinline__ uint32_t min3(uint32_t a, uint32_t b, uint32_t c) { uint32_t r; asm("{\n.reg .u32 t;\nmin.u32 t, %2, %3;\nmin.u32 %0, %1, t;\n}\n" : "=r"(r) : "r"(a), "r"(b), "r"(c)); return r; }
__device__ __forceinline__ uint32_t xor_or(uint32_t a, uint32_t b, uint32_t c) { uint32_t r; asm("lop3.b32 %0, %1, %2, %3, 0x7e;\n" : "=r"(r) : "r"(a), "r"(b), "r"(c)); return r; }
__device__ __forceinline__ uint32_t pin(uint32_t v) { uint32_t r; asm volatile("shfl.sync.bfly.b32 %0, %1, 0, 0x1f, 0xffffffff;\n" : "=r"(r) : "r"(v) : "memory"); return r; }
__device__ __forceinline__ uint4 ld_poll(const void* p) {
    uint4 v;
    asm volatile("ld.relaxed.gpu.global.v4.u32 {%0,%1,%2,%3}, [%4];\n" : "=r"(v.x), "=r"(v.y), "=r"(v.z), "=r"(v.w) : "l"(p) : "memory");
    return v;
}
__device__ __forceinline__ uint2 ld_poll64(const void* p) {
    uint2 v;
    asm volatile("ld.relaxed.gpu.global.v2.u32 {%0,%1}, [%2];\n" : "=r"(v.x), "=r"(v.y) : "l"(p) : "memory");
    return v;
}
__device__ __forceinline__ uint32_t ld_poll32(const void* p) {
    uint32_t v;
    asm volatile("ld.relaxed.gpu.global.u32 %0, [%1];\n" : "=r"(v) : "l"(p) : "memory");
    return v;
}
__device__ __forceinline__ uint32_t ld_acquire32(const void* p) {
    uint32_t v;
    asm volatile("ld.acquire.gpu.global.u32 %0, [%1];\n" : "=r"(v) : "l"(p) : "memory");
    return v;
}
__device__ __forceinline__ uint2 ldo64(const void* p) {
    uint2 v;
    asm volatile("ld.relaxed.cta.global.v2.u32 {%0,%1}, [%2];\n" : "=r"(v.x), "=r"(v.y) : "l"(p) : "memory");
    return v;
}
__device__ __forceinline__ uint32_t ldo16(const void* p) {
    uint32_t v;
    asm volatile("ld.relaxed.cta.global.u16 %0, [%1];\n" : "=r"(v) : "l"(p) : "memory");
    return v;
}
__device__ __forceinline__ void stg128(void* p, uint32_t a, uint32_t b, uint32_t c, uint32_t d) {
    asm volatile("st.global.v4.u32 [%0], {%1,%2,%3,%4};\n" ::"l"(p), "r"(a), "r"(b), "r"(c), "r"(d) : "memory");
}
__device__ __forceinline__ void stg64(void* p, uint32_t a, uint32_t b) { asm volatile("st.global.v2.u32 [%0], {%1,%2};\n" ::"l"(p), "r"(a), "r"(b) : "memory"); }
__device__ __forceinline__ uint32_t min4(const uint4& v) { return min(min(v.x, v.y), min(v.z, v.w)); }
#define SPIN_LIMIT (1 << 21)
#define TRAP() __trap()
__device__ __forceinline__ void mbar_init(uint32_t bar, uint32_t cnt) { asm volatile("mbarrier.init.shared::cta.b64 [%0], %1;\n" ::"r"(bar), "r"(cnt) : "memory"); }
__device__ __forceinline__ void mbar_expect(uint32_t bar, uint32_t bytes) {
    asm volatile("mbarrier.arrive.expect_tx.shared::cta.b64 _, [%0], %1;\n" ::"r"(bar), "r"(bytes) : "memory");
}
__device__ __forceinline__ void mbar_arrive(uint32_t bar) { asm volatile("mbarrier.arrive.shared::cta.b64 _, [%0];\n" ::"r"(bar) : "memory"); }
__device__ __forceinline__ void mbar_wait(uint32_t bar) {
    asm volatile(
        "{\n.reg .pred p;\n"
        "W_%=:\n"
        "mbarrier.try_wait.parity.shared::cta.b64 p, [%0], 0;\n"
        "@!p bra W_%=;\n}\n" ::"r"(bar) : "memory");
}
__device__ __forceinline__ void bulk_g2s(uint32_t dst, const void* src, uint32_t bytes, uint32_t bar) {
    asm volatile("cp.async.bulk.shared::cluster.global.mbarrier::complete_tx::bytes [%0], [%1], %2, [%3];\n" ::"r"(dst), "l"(src), "r"(bytes), "r"(bar) : "memory");
}
__device__ __forceinline__ void bulk_s2g(void* dst, uint32_t src, uint32_t bytes) {
    asm volatile("cp.async.bulk.global.shared::cta.bulk_group [%0], [%1], %2;\ncp.async.bulk.commit_group;\n" ::"l"(dst), "r"(src), "r"(bytes) : "memory");
}
__device__ __forceinline__ void bulk_s2g_nc(void* dst, uint32_t src, uint32_t bytes) {
    asm volatile("cp.async.bulk.global.shared::cta.bulk_group [%0], [%1], %2;\n" ::"l"(dst), "r"(src), "r"(bytes) : "memory");
}
__device__ __forceinline__ void tma_2d(uint32_t dst, const CUtensorMap* tm, int c0, int c1, uint32_t bar) {
    asm volatile("cp.async.bulk.tensor.2d.shared::cluster.global.mbarrier::complete_tx::bytes [%0], [%1, {%3, %4}], [%2];\n"
                 ::"r"(dst), "l"(tm), "r"(bar), "r"(c0), "r"(c1) : "memory");
}
__device__ __forceinline__ void tma_4d_mc(uint32_t dst, const CUtensorMap* tm, int c0, int c3, uint32_t bar) {
    asm volatile("cp.async.bulk.tensor.4d.shared::cluster.global.mbarrier::complete_tx::bytes.multicast::cluster [%0], [%1, {%3, %4, %4, %5}], [%2], %6;\n"
                 ::"r"(dst), "l"(tm), "r"(bar), "r"(c0), "r"(0), "r"(c3), "h"((unsigned short)3) : "memory");
}
__device__ __forceinline__ bool elect_one() {
    uint32_t r;
    asm volatile("{\n.reg .pred p;\nelect.sync _|p, 0xffffffff;\nselp.u32 %0, 1, 0, p;\n}\n" : "=r"(r));
    return r;
}
__device__ __forceinline__ void delay(uint32_t clks) {
    uint32_t t0, t1;
    asm volatile("mov.u32 %0, %%clock;" : "=r"(t0) :: "memory");
    do { asm volatile("mov.u32 %0, %%clock;" : "=r"(t1) :: "memory"); } while (t1 - t0 < clks);
}
__device__ __forceinline__ void fence_async() { asm volatile("fence.proxy.async.shared::cta;\n" ::: "memory"); }

__device__ __forceinline__ float2 cmul(float2 a, float2 b) {
    return make_float2(fmaf(a.x, b.x, -a.y * b.y), fmaf(a.x, b.y, a.y * b.x));
}
__device__ __forceinline__ float2 csq(float2 a) {
    float p = a.x * a.y;
    return make_float2(fmaf(a.x, a.x, -a.y * a.y), p + p);
}
__device__ __forceinline__ float ex2_approx(float x) { float r; asm("ex2.approx.ftz.f32 %0, %1;\n" : "=f"(r) : "f"(x)); return r; }
__device__ __forceinline__ float exp_bf(float x) { return rbf(ex2_approx(__fmul_ru(x, 1.4426950408889634f))); }
__device__ __forceinline__ float2 cexp_e(float lr2, float li, float e) {
    const float m = ex2_approx(lr2 * e);
    return make_float2(m * __cosf(li * e), m * __sinf(li * e));
}
__device__ __forceinline__ float rcp_approx(float x) { float r; asm("rcp.approx.ftz.f32 %0, %1;\n" : "=f"(r) : "f"(x)); return r; }
__device__ __forceinline__ float sigmoid_f(float x) { return rcp_approx(1.0f + ex2_approx(x * -1.4426950408889634f)); }
__device__ __forceinline__ float sqrt_approx(float x) { float r; asm("sqrt.approx.ftz.f32 %0, %1;\n" : "=f"(r) : "f"(x)); return r; }

__device__ __forceinline__ void wg_fence() { asm volatile("wgmma.fence.sync.aligned;\n" ::: "memory"); }
__device__ __forceinline__ void wg_commit() { asm volatile("wgmma.commit_group.sync.aligned;\n" ::: "memory"); }
__device__ __forceinline__ void wg_wait0() { asm volatile("wgmma.wait_group.sync.aligned 0;\n" ::: "memory"); }
template <int T> __device__ __forceinline__ void wg_mma(float (&acc)[16][4], const uint32_t* a, uint64_t desc);
template <int T> __device__ __forceinline__ void wg_first(float (&acc)[16][4], const uint32_t* a, uint64_t desc);
template <> __device__ __forceinline__ void wg_mma<0>(float (&acc)[16][4], const uint32_t* a, uint64_t desc) {
    asm volatile("wgmma.mma_async.sync.aligned.m64n128k16.f32.f16.f16 {%0,%1,%2,%3,%4,%5,%6,%7,%8,%9,%10,%11,%12,%13,%14,%15,%16,%17,%18,%19,%20,%21,%22,%23,%24,%25,%26,%27,%28,%29,%30,%31,%32,%33,%34,%35,%36,%37,%38,%39,%40,%41,%42,%43,%44,%45,%46,%47,%48,%49,%50,%51,%52,%53,%54,%55,%56,%57,%58,%59,%60,%61,%62,%63}, {%64,%65,%66,%67}, %68, 1, 1, 1, 0;\n"
                 : "+f"(acc[0][0]), "+f"(acc[0][1]), "+f"(acc[0][2]), "+f"(acc[0][3]), "+f"(acc[1][0]), "+f"(acc[1][1]), "+f"(acc[1][2]), "+f"(acc[1][3]), "+f"(acc[2][0]), "+f"(acc[2][1]), "+f"(acc[2][2]), "+f"(acc[2][3]), "+f"(acc[3][0]), "+f"(acc[3][1]), "+f"(acc[3][2]), "+f"(acc[3][3]), "+f"(acc[4][0]), "+f"(acc[4][1]), "+f"(acc[4][2]), "+f"(acc[4][3]), "+f"(acc[5][0]), "+f"(acc[5][1]), "+f"(acc[5][2]), "+f"(acc[5][3]), "+f"(acc[6][0]), "+f"(acc[6][1]), "+f"(acc[6][2]), "+f"(acc[6][3]), "+f"(acc[7][0]), "+f"(acc[7][1]), "+f"(acc[7][2]), "+f"(acc[7][3]), "+f"(acc[8][0]), "+f"(acc[8][1]), "+f"(acc[8][2]), "+f"(acc[8][3]), "+f"(acc[9][0]), "+f"(acc[9][1]), "+f"(acc[9][2]), "+f"(acc[9][3]), "+f"(acc[10][0]), "+f"(acc[10][1]), "+f"(acc[10][2]), "+f"(acc[10][3]), "+f"(acc[11][0]), "+f"(acc[11][1]), "+f"(acc[11][2]), "+f"(acc[11][3]), "+f"(acc[12][0]), "+f"(acc[12][1]), "+f"(acc[12][2]), "+f"(acc[12][3]), "+f"(acc[13][0]), "+f"(acc[13][1]), "+f"(acc[13][2]), "+f"(acc[13][3]), "+f"(acc[14][0]), "+f"(acc[14][1]), "+f"(acc[14][2]), "+f"(acc[14][3]), "+f"(acc[15][0]), "+f"(acc[15][1]), "+f"(acc[15][2]), "+f"(acc[15][3])
                 : "r"(a[0]), "r"(a[1]), "r"(a[2]), "r"(a[3]), "l"(desc));
}
template <> __device__ __forceinline__ void wg_mma<2>(float (&acc)[16][4], const uint32_t* a, uint64_t desc) {
    asm volatile("wgmma.mma_async.sync.aligned.m64n112k16.f32.f16.f16 {%0,%1,%2,%3,%4,%5,%6,%7,%8,%9,%10,%11,%12,%13,%14,%15,%16,%17,%18,%19,%20,%21,%22,%23,%24,%25,%26,%27,%28,%29,%30,%31,%32,%33,%34,%35,%36,%37,%38,%39,%40,%41,%42,%43,%44,%45,%46,%47,%48,%49,%50,%51,%52,%53,%54,%55}, {%56,%57,%58,%59}, %60, 1, 1, 1, 0;\n"
                 : "+f"(acc[2][0]), "+f"(acc[2][1]), "+f"(acc[2][2]), "+f"(acc[2][3]), "+f"(acc[3][0]), "+f"(acc[3][1]), "+f"(acc[3][2]), "+f"(acc[3][3]), "+f"(acc[4][0]), "+f"(acc[4][1]), "+f"(acc[4][2]), "+f"(acc[4][3]), "+f"(acc[5][0]), "+f"(acc[5][1]), "+f"(acc[5][2]), "+f"(acc[5][3]), "+f"(acc[6][0]), "+f"(acc[6][1]), "+f"(acc[6][2]), "+f"(acc[6][3]), "+f"(acc[7][0]), "+f"(acc[7][1]), "+f"(acc[7][2]), "+f"(acc[7][3]), "+f"(acc[8][0]), "+f"(acc[8][1]), "+f"(acc[8][2]), "+f"(acc[8][3]), "+f"(acc[9][0]), "+f"(acc[9][1]), "+f"(acc[9][2]), "+f"(acc[9][3]), "+f"(acc[10][0]), "+f"(acc[10][1]), "+f"(acc[10][2]), "+f"(acc[10][3]), "+f"(acc[11][0]), "+f"(acc[11][1]), "+f"(acc[11][2]), "+f"(acc[11][3]), "+f"(acc[12][0]), "+f"(acc[12][1]), "+f"(acc[12][2]), "+f"(acc[12][3]), "+f"(acc[13][0]), "+f"(acc[13][1]), "+f"(acc[13][2]), "+f"(acc[13][3]), "+f"(acc[14][0]), "+f"(acc[14][1]), "+f"(acc[14][2]), "+f"(acc[14][3]), "+f"(acc[15][0]), "+f"(acc[15][1]), "+f"(acc[15][2]), "+f"(acc[15][3])
                 : "r"(a[0]), "r"(a[1]), "r"(a[2]), "r"(a[3]), "l"(desc));
}
template <> __device__ __forceinline__ void wg_mma<4>(float (&acc)[16][4], const uint32_t* a, uint64_t desc) {
    asm volatile("wgmma.mma_async.sync.aligned.m64n96k16.f32.f16.f16 {%0,%1,%2,%3,%4,%5,%6,%7,%8,%9,%10,%11,%12,%13,%14,%15,%16,%17,%18,%19,%20,%21,%22,%23,%24,%25,%26,%27,%28,%29,%30,%31,%32,%33,%34,%35,%36,%37,%38,%39,%40,%41,%42,%43,%44,%45,%46,%47}, {%48,%49,%50,%51}, %52, 1, 1, 1, 0;\n"
                 : "+f"(acc[4][0]), "+f"(acc[4][1]), "+f"(acc[4][2]), "+f"(acc[4][3]), "+f"(acc[5][0]), "+f"(acc[5][1]), "+f"(acc[5][2]), "+f"(acc[5][3]), "+f"(acc[6][0]), "+f"(acc[6][1]), "+f"(acc[6][2]), "+f"(acc[6][3]), "+f"(acc[7][0]), "+f"(acc[7][1]), "+f"(acc[7][2]), "+f"(acc[7][3]), "+f"(acc[8][0]), "+f"(acc[8][1]), "+f"(acc[8][2]), "+f"(acc[8][3]), "+f"(acc[9][0]), "+f"(acc[9][1]), "+f"(acc[9][2]), "+f"(acc[9][3]), "+f"(acc[10][0]), "+f"(acc[10][1]), "+f"(acc[10][2]), "+f"(acc[10][3]), "+f"(acc[11][0]), "+f"(acc[11][1]), "+f"(acc[11][2]), "+f"(acc[11][3]), "+f"(acc[12][0]), "+f"(acc[12][1]), "+f"(acc[12][2]), "+f"(acc[12][3]), "+f"(acc[13][0]), "+f"(acc[13][1]), "+f"(acc[13][2]), "+f"(acc[13][3]), "+f"(acc[14][0]), "+f"(acc[14][1]), "+f"(acc[14][2]), "+f"(acc[14][3]), "+f"(acc[15][0]), "+f"(acc[15][1]), "+f"(acc[15][2]), "+f"(acc[15][3])
                 : "r"(a[0]), "r"(a[1]), "r"(a[2]), "r"(a[3]), "l"(desc));
}
template <> __device__ __forceinline__ void wg_mma<6>(float (&acc)[16][4], const uint32_t* a, uint64_t desc) {
    asm volatile("wgmma.mma_async.sync.aligned.m64n80k16.f32.f16.f16 {%0,%1,%2,%3,%4,%5,%6,%7,%8,%9,%10,%11,%12,%13,%14,%15,%16,%17,%18,%19,%20,%21,%22,%23,%24,%25,%26,%27,%28,%29,%30,%31,%32,%33,%34,%35,%36,%37,%38,%39}, {%40,%41,%42,%43}, %44, 1, 1, 1, 0;\n"
                 : "+f"(acc[6][0]), "+f"(acc[6][1]), "+f"(acc[6][2]), "+f"(acc[6][3]), "+f"(acc[7][0]), "+f"(acc[7][1]), "+f"(acc[7][2]), "+f"(acc[7][3]), "+f"(acc[8][0]), "+f"(acc[8][1]), "+f"(acc[8][2]), "+f"(acc[8][3]), "+f"(acc[9][0]), "+f"(acc[9][1]), "+f"(acc[9][2]), "+f"(acc[9][3]), "+f"(acc[10][0]), "+f"(acc[10][1]), "+f"(acc[10][2]), "+f"(acc[10][3]), "+f"(acc[11][0]), "+f"(acc[11][1]), "+f"(acc[11][2]), "+f"(acc[11][3]), "+f"(acc[12][0]), "+f"(acc[12][1]), "+f"(acc[12][2]), "+f"(acc[12][3]), "+f"(acc[13][0]), "+f"(acc[13][1]), "+f"(acc[13][2]), "+f"(acc[13][3]), "+f"(acc[14][0]), "+f"(acc[14][1]), "+f"(acc[14][2]), "+f"(acc[14][3]), "+f"(acc[15][0]), "+f"(acc[15][1]), "+f"(acc[15][2]), "+f"(acc[15][3])
                 : "r"(a[0]), "r"(a[1]), "r"(a[2]), "r"(a[3]), "l"(desc));
}
template <> __device__ __forceinline__ void wg_mma<8>(float (&acc)[16][4], const uint32_t* a, uint64_t desc) {
    asm volatile("wgmma.mma_async.sync.aligned.m64n64k16.f32.f16.f16 {%0,%1,%2,%3,%4,%5,%6,%7,%8,%9,%10,%11,%12,%13,%14,%15,%16,%17,%18,%19,%20,%21,%22,%23,%24,%25,%26,%27,%28,%29,%30,%31}, {%32,%33,%34,%35}, %36, 1, 1, 1, 0;\n"
                 : "+f"(acc[8][0]), "+f"(acc[8][1]), "+f"(acc[8][2]), "+f"(acc[8][3]), "+f"(acc[9][0]), "+f"(acc[9][1]), "+f"(acc[9][2]), "+f"(acc[9][3]), "+f"(acc[10][0]), "+f"(acc[10][1]), "+f"(acc[10][2]), "+f"(acc[10][3]), "+f"(acc[11][0]), "+f"(acc[11][1]), "+f"(acc[11][2]), "+f"(acc[11][3]), "+f"(acc[12][0]), "+f"(acc[12][1]), "+f"(acc[12][2]), "+f"(acc[12][3]), "+f"(acc[13][0]), "+f"(acc[13][1]), "+f"(acc[13][2]), "+f"(acc[13][3]), "+f"(acc[14][0]), "+f"(acc[14][1]), "+f"(acc[14][2]), "+f"(acc[14][3]), "+f"(acc[15][0]), "+f"(acc[15][1]), "+f"(acc[15][2]), "+f"(acc[15][3])
                 : "r"(a[0]), "r"(a[1]), "r"(a[2]), "r"(a[3]), "l"(desc));
}
template <> __device__ __forceinline__ void wg_mma<10>(float (&acc)[16][4], const uint32_t* a, uint64_t desc) {
    asm volatile("wgmma.mma_async.sync.aligned.m64n48k16.f32.f16.f16 {%0,%1,%2,%3,%4,%5,%6,%7,%8,%9,%10,%11,%12,%13,%14,%15,%16,%17,%18,%19,%20,%21,%22,%23}, {%24,%25,%26,%27}, %28, 1, 1, 1, 0;\n"
                 : "+f"(acc[10][0]), "+f"(acc[10][1]), "+f"(acc[10][2]), "+f"(acc[10][3]), "+f"(acc[11][0]), "+f"(acc[11][1]), "+f"(acc[11][2]), "+f"(acc[11][3]), "+f"(acc[12][0]), "+f"(acc[12][1]), "+f"(acc[12][2]), "+f"(acc[12][3]), "+f"(acc[13][0]), "+f"(acc[13][1]), "+f"(acc[13][2]), "+f"(acc[13][3]), "+f"(acc[14][0]), "+f"(acc[14][1]), "+f"(acc[14][2]), "+f"(acc[14][3]), "+f"(acc[15][0]), "+f"(acc[15][1]), "+f"(acc[15][2]), "+f"(acc[15][3])
                 : "r"(a[0]), "r"(a[1]), "r"(a[2]), "r"(a[3]), "l"(desc));
}
template <> __device__ __forceinline__ void wg_mma<12>(float (&acc)[16][4], const uint32_t* a, uint64_t desc) {
    asm volatile("wgmma.mma_async.sync.aligned.m64n32k16.f32.f16.f16 {%0,%1,%2,%3,%4,%5,%6,%7,%8,%9,%10,%11,%12,%13,%14,%15}, {%16,%17,%18,%19}, %20, 1, 1, 1, 0;\n"
                 : "+f"(acc[12][0]), "+f"(acc[12][1]), "+f"(acc[12][2]), "+f"(acc[12][3]), "+f"(acc[13][0]), "+f"(acc[13][1]), "+f"(acc[13][2]), "+f"(acc[13][3]), "+f"(acc[14][0]), "+f"(acc[14][1]), "+f"(acc[14][2]), "+f"(acc[14][3]), "+f"(acc[15][0]), "+f"(acc[15][1]), "+f"(acc[15][2]), "+f"(acc[15][3])
                 : "r"(a[0]), "r"(a[1]), "r"(a[2]), "r"(a[3]), "l"(desc));
}
template <> __device__ __forceinline__ void wg_mma<14>(float (&acc)[16][4], const uint32_t* a, uint64_t desc) {
    asm volatile("wgmma.mma_async.sync.aligned.m64n16k16.f32.f16.f16 {%0,%1,%2,%3,%4,%5,%6,%7}, {%8,%9,%10,%11}, %12, 1, 1, 1, 0;\n"
                 : "+f"(acc[14][0]), "+f"(acc[14][1]), "+f"(acc[14][2]), "+f"(acc[14][3]), "+f"(acc[15][0]), "+f"(acc[15][1]), "+f"(acc[15][2]), "+f"(acc[15][3])
                 : "r"(a[0]), "r"(a[1]), "r"(a[2]), "r"(a[3]), "l"(desc));
}
template <> __device__ __forceinline__ void wg_first<0>(float (&acc)[16][4], const uint32_t* a, uint64_t desc) {
    asm volatile("wgmma.mma_async.sync.aligned.m64n128k16.f32.f16.f16 {%0,%1,%2,%3,%4,%5,%6,%7,%8,%9,%10,%11,%12,%13,%14,%15,%16,%17,%18,%19,%20,%21,%22,%23,%24,%25,%26,%27,%28,%29,%30,%31,%32,%33,%34,%35,%36,%37,%38,%39,%40,%41,%42,%43,%44,%45,%46,%47,%48,%49,%50,%51,%52,%53,%54,%55,%56,%57,%58,%59,%60,%61,%62,%63}, {%64,%65,%66,%67}, %68, 0, 1, 1, 0;\n"
                 : "=f"(acc[0][0]), "=f"(acc[0][1]), "=f"(acc[0][2]), "=f"(acc[0][3]), "=f"(acc[1][0]), "=f"(acc[1][1]), "=f"(acc[1][2]), "=f"(acc[1][3]), "=f"(acc[2][0]), "=f"(acc[2][1]), "=f"(acc[2][2]), "=f"(acc[2][3]), "=f"(acc[3][0]), "=f"(acc[3][1]), "=f"(acc[3][2]), "=f"(acc[3][3]), "=f"(acc[4][0]), "=f"(acc[4][1]), "=f"(acc[4][2]), "=f"(acc[4][3]), "=f"(acc[5][0]), "=f"(acc[5][1]), "=f"(acc[5][2]), "=f"(acc[5][3]), "=f"(acc[6][0]), "=f"(acc[6][1]), "=f"(acc[6][2]), "=f"(acc[6][3]), "=f"(acc[7][0]), "=f"(acc[7][1]), "=f"(acc[7][2]), "=f"(acc[7][3]), "=f"(acc[8][0]), "=f"(acc[8][1]), "=f"(acc[8][2]), "=f"(acc[8][3]), "=f"(acc[9][0]), "=f"(acc[9][1]), "=f"(acc[9][2]), "=f"(acc[9][3]), "=f"(acc[10][0]), "=f"(acc[10][1]), "=f"(acc[10][2]), "=f"(acc[10][3]), "=f"(acc[11][0]), "=f"(acc[11][1]), "=f"(acc[11][2]), "=f"(acc[11][3]), "=f"(acc[12][0]), "=f"(acc[12][1]), "=f"(acc[12][2]), "=f"(acc[12][3]), "=f"(acc[13][0]), "=f"(acc[13][1]), "=f"(acc[13][2]), "=f"(acc[13][3]), "=f"(acc[14][0]), "=f"(acc[14][1]), "=f"(acc[14][2]), "=f"(acc[14][3]), "=f"(acc[15][0]), "=f"(acc[15][1]), "=f"(acc[15][2]), "=f"(acc[15][3])
                 : "r"(a[0]), "r"(a[1]), "r"(a[2]), "r"(a[3]), "l"(desc));
}
template <> __device__ __forceinline__ void wg_first<4>(float (&acc)[16][4], const uint32_t* a, uint64_t desc) {
    asm volatile("wgmma.mma_async.sync.aligned.m64n96k16.f32.f16.f16 {%0,%1,%2,%3,%4,%5,%6,%7,%8,%9,%10,%11,%12,%13,%14,%15,%16,%17,%18,%19,%20,%21,%22,%23,%24,%25,%26,%27,%28,%29,%30,%31,%32,%33,%34,%35,%36,%37,%38,%39,%40,%41,%42,%43,%44,%45,%46,%47}, {%48,%49,%50,%51}, %52, 0, 1, 1, 0;\n"
                 : "=f"(acc[4][0]), "=f"(acc[4][1]), "=f"(acc[4][2]), "=f"(acc[4][3]), "=f"(acc[5][0]), "=f"(acc[5][1]), "=f"(acc[5][2]), "=f"(acc[5][3]), "=f"(acc[6][0]), "=f"(acc[6][1]), "=f"(acc[6][2]), "=f"(acc[6][3]), "=f"(acc[7][0]), "=f"(acc[7][1]), "=f"(acc[7][2]), "=f"(acc[7][3]), "=f"(acc[8][0]), "=f"(acc[8][1]), "=f"(acc[8][2]), "=f"(acc[8][3]), "=f"(acc[9][0]), "=f"(acc[9][1]), "=f"(acc[9][2]), "=f"(acc[9][3]), "=f"(acc[10][0]), "=f"(acc[10][1]), "=f"(acc[10][2]), "=f"(acc[10][3]), "=f"(acc[11][0]), "=f"(acc[11][1]), "=f"(acc[11][2]), "=f"(acc[11][3]), "=f"(acc[12][0]), "=f"(acc[12][1]), "=f"(acc[12][2]), "=f"(acc[12][3]), "=f"(acc[13][0]), "=f"(acc[13][1]), "=f"(acc[13][2]), "=f"(acc[13][3]), "=f"(acc[14][0]), "=f"(acc[14][1]), "=f"(acc[14][2]), "=f"(acc[14][3]), "=f"(acc[15][0]), "=f"(acc[15][1]), "=f"(acc[15][2]), "=f"(acc[15][3])
                 : "r"(a[0]), "r"(a[1]), "r"(a[2]), "r"(a[3]), "l"(desc));
}

#define SDLY 1500
#define UDLY 1400
#define KDLY 850
#define FDLY 950
#define FDLY2 350
#define DDLY 450
#define WDLY 500
#define HW 15
#define FIX(v) do { if ((v) == 1u) TRAP(); } while (0)
#define STAMPW(i) STAMPY(i)
#define STAMP2(i) STAMP(i)
#undef STAMPX
#define STAMPX(i)
struct Params {
    const bf16 *x, *lar, *aim, *cre, *cim, *ldt, *dsk;
    Scratch* s;
    const bf16* wr;
    bf16* out;
};
struct Maps { CUtensorMap x, w[2], r[2], d; };

#define TOK(g) (2 * (g) - ((g) & 1))
#define ROWTOK(r) (TOK((r) & 7) + (((r) >> 2) & 2))
__device__ __forceinline__ void ln_partial(const uint32_t (&H)[2][4], float (&d)[2][4]) {
#pragma unroll
    for (int i = 0; i < 8; i++) d[i >> 2][i & 3] = 0.f;
#pragma unroll
    for (int k = 0; k < 4; k++)
#pragma unroll
        for (int hf = 0; hf < 2; hf++) mma_bf16_k8(d[hf], H[hf][k], 0x3f803f80u, H[hf][k]);
}
__device__ __forceinline__ float sum18(uint32_t a) {
    const uint4 p = lds128(a), q = lds128(a + 16), r = lds128(a + 32), s = lds128(a + 48);
    const uint2 u = lds64(a + 64);
#define F(x) __uint_as_float(x)
    return (((F(p.x) + F(p.y)) + (F(p.z) + F(p.w))) + ((F(q.x) + F(q.y)) + (F(q.z) + F(q.w)))) +
           (((F(r.x) + F(r.y)) + (F(r.z) + F(r.w))) + ((F(s.x) + F(s.y)) + (F(s.z) + F(s.w))) + (F(u.x) + F(u.y)));
#undef F
}
__device__ __forceinline__ void ln_stats(float sm, float sq, float& mb, float& sd) {
    const float m0 = sm * (1.0f / 576.0f);
    const float mean = fmaf(fmaf(-m0, 576.0f, sm), 1.0f / 576.0f, m0);
    const float var = fmaxf(fmaf(-mean, mean, sq * (1.0f / 576.0f)), 0.f);
    mb = rbf(mean);
    sd = rbf(sqrt_approx(rbf(rbf(var) + 1e-5f)));
}
__device__ __forceinline__ void ln_finish(float v, int lane, float& mb, float& rc) {
    const float o = __shfl_xor_sync(0xffffffffu, v, 16);
    float sd;
    ln_stats(lane < 16 ? v : o, lane < 16 ? o : v, mb, sd);
    rc = rcp_approx(sd);
}
__device__ __forceinline__ uint32_t ln_apply(uint32_t w, uint32_t m2, uint32_t rh, uint32_t rl) {
    const uint32_t d = hsub2_bf(w, m2);
    return hfma2_bf(d, rh, hmul2_bf(d, rl));
}
__device__ __forceinline__ void stat_store(uint32_t a, float mb, float rc, uint32_t extra) {
    const float rh = rbf(rc);
    sts64(a, (__float_as_uint(mb) >> 16) | (extra << 16), pack_bf16(rh, rc - rh));
}
__device__ __forceinline__ uint32_t dup_lo(uint32_t w) { const __nv_bfloat162 r = __low2bfloat162(*reinterpret_cast<__nv_bfloat162*>(&w)); return *reinterpret_cast<const uint32_t*>(&r); }
__device__ __forceinline__ uint32_t dup_hi(uint32_t w) { const __nv_bfloat162 r = __high2bfloat162(*reinterpret_cast<__nv_bfloat162*>(&w)); return *reinterpret_cast<const uint32_t*>(&r); }
__device__ __forceinline__ float fsel(float a, float b, int c) { float r; asm("{\n.reg .pred p;\nsetp.ne.s32 p, %3, 0;\nselp.f32 %0, %1, %2, p;\n}\n" : "=f"(r) : "f"(a), "f"(b), "r"(c)); return r; }
#define STAT_M(s) dup_lo((s).x)
#define STAT_H(s) dup_lo((s).y)
#define STAT_L(s) dup_hi((s).y)

__device__ __forceinline__ void hcmul(uint32_t re, uint32_t im, uint32_t zx, uint32_t zy, uint32_t& ore, uint32_t& oim) {
    ore = hfms2(im, zy, hmul2(re, zx));
    oim = hfma2(re, zy, hmul2(im, zx));
}

template <int HI>
__device__ __forceinline__ uint32_t hdup(uint32_t w) {
    const __half2 h = *reinterpret_cast<__half2*>(&w), r = HI ? __high2half2(h) : __low2half2(h);
    return *reinterpret_cast<const uint32_t*>(&r);
}
__device__ __forceinline__ void hcmul(uint32_t re, uint32_t im, float2 z, uint32_t& ore, uint32_t& oim) {
    const uint32_t w = pack_f16(z.x, z.y);
    hcmul(re, im, hdup<0>(w), hdup<1>(w), ore, oim);
}

struct KGen {
    uint32_t A[2][4][4];
    float2 z1, z8, z64, z128, T[9];
};
__device__ __forceinline__ void kgen_setup(KGen& k, float lar, float aim, float dt) {
    const float lr2 = -(exp_bf(lar) * dt) * 1.4426950408889634f, li = aim * dt;
    k.z1 = cexp_e(lr2, li, 1.0f);
    k.z8 = cexp_e(lr2, li, 8.0f);
    k.z64 = cexp_e(lr2, li, 64.0f);
}
__device__ __forceinline__ void kgen_rows(KGen& k, uint32_t tb, int lane) {
    const float2 z8 = k.z8, z64 = k.z64;
    const uint32_t row = tb + lane * 16;
    k.z128 = csq(z64);
    const float2 z16 = csq(z8), z24 = cmul(z16, z8), z32 = csq(z16), z40 = cmul(z32, z8), z48 = csq(z24), z56 = cmul(z32, z24);
    uint32_t re[4], im[4], a[4], b[4];
    re[0] = pack_f16(1.0f, z8.x); im[0] = pack_f16(0.0f, z8.y);
    re[1] = pack_f16(z16.x, z24.x); im[1] = pack_f16(z16.y, z24.y);
    re[2] = pack_f16(z32.x, z40.x); im[2] = pack_f16(z32.y, z40.y);
    re[3] = pack_f16(z48.x, z56.x); im[3] = pack_f16(z48.y, z56.y);
    sts128(row, re[0], re[1], re[2], re[3]);
    sts128(row + 1024, im[0], im[1], im[2], im[3]);
    const uint32_t zw = pack_f16(k.z128.x, k.z128.y);
#pragma unroll
    for (int j = 0; j < 4; j++) hcmul(re[j], im[j], z64, a[j], b[j]);
    sts128(row + 512, a[0], a[1], a[2], a[3]);
    sts128(row + 1536, b[0], b[1], b[2], b[3]);
    const int mi = lane >> 3;
    const uint32_t zd = tb + 2048 + mi * 16;
    sts16(tb + 2048 + lane * 2, zw); sts16(tb + 2112 + lane * 2, zw >> 16);
    __syncwarp();
    const uint32_t ad = tb + (lane & 7) * 16 + mi * 512;
    ldsm_x4(a[0], a[1], a[2], a[3], zd);
    ldsm_x4(b[0], b[1], b[2], b[3], zd + 64);
#pragma unroll
    for (int ks = 0; ks < 4; ks++) {
        ldsm_x4_t(k.A[0][ks][0], k.A[0][ks][1], k.A[0][ks][2], k.A[0][ks][3], ad + ks * 128);
        hcmul(k.A[0][ks][0], k.A[0][ks][2], a[ks], b[ks], k.A[1][ks][0], k.A[1][ks][2]);
        hcmul(k.A[0][ks][1], k.A[0][ks][3], a[ks], b[ks], k.A[1][ks][1], k.A[1][ks][3]);
    }
}
__device__ __forceinline__ void kgen_chain(KGen& k, uint32_t cr, uint32_t ci, float cs) {
    k.T[0] = make_float2(bf_lo(cr) * cs, -bf_lo(ci) * cs);
    const float2 y1 = make_float2(k.z1.x, -k.z1.y);
#pragma unroll
    for (int c = 1; c < 8; c++) k.T[c] = cmul(k.T[c - 1], y1);
    k.T[8] = cmul(k.T[0], make_float2(k.z8.x, -k.z8.y));
}
__device__ __forceinline__ void kgen_cols(KGen& k, uint32_t tb, uint32_t t5, int lane) {
    const uint32_t row = tb + lane * 16;
    const float2 (&T)[9] = k.T;
    const float2 y128 = make_float2(k.z128.x, -k.z128.y);
    const float2 y256 = csq(y128), y512 = csq(y256), y768 = cmul(y512, y256), y1024 = csq(y512);
    const float2 c1032 = cmul(T[8], y1024);
    __syncwarp();
    sts128(row, pack_f16(T[0].x, T[1].x), pack_f16(T[2].x, T[3].x), pack_f16(T[4].x, T[5].x), pack_f16(T[6].x, T[7].x));
    sts128(row + 512, pack_f16(T[0].y, T[1].y), pack_f16(T[2].y, T[3].y), pack_f16(T[4].y, T[5].y), pack_f16(T[6].y, T[7].y));
    uint32_t a[4], b[4];
    const uint32_t r0 = pack_f16(1.0f, y256.x), i0 = pack_f16(0.0f, y256.y), r1 = pack_f16(y512.x, y768.x), i1 = pack_f16(y512.y, y768.y);
    {
        hcmul(pack_f16(T[0].x, T[2].x), pack_f16(T[0].y, T[2].y), hdup<1>(r0), hdup<1>(i0), a[0], b[0]);
        hcmul(pack_f16(T[4].x, T[6].x), pack_f16(T[4].y, T[6].y), hdup<1>(r0), hdup<1>(i0), a[1], b[1]);
        const uint32_t r04 = pack_f16(T[0].x, T[4].x), i04 = pack_f16(T[0].y, T[4].y);
        hcmul(r04, i04, hdup<0>(r1), hdup<0>(i1), a[2], b[2]);
        hcmul(r04, i04, hdup<1>(r1), hdup<1>(i1), a[3], b[3]);
    }
    sts128(row + 1024, a[0], a[1], a[2], a[3]);
    sts128(row + 1536, b[0], b[1], b[2], b[3]);
    hcmul(r0, i0, T[8], a[0], b[0]); hcmul(r1, i1, T[8], a[1], b[1]);
    hcmul(r0, i0, c1032, a[2], b[2]); hcmul(r1, i1, c1032, a[3], b[3]);
    sts128(row + 2048, a[0], a[1], a[2], a[3]);
    sts128(t5 + lane * 16, b[0], b[1], b[2], b[3]);
}
__device__ __forceinline__ void kgen_mma(const KGen& k, uint32_t tb, uint32_t t5, int lane) {
    __syncwarp();
    float acc[2][3][4];
#pragma unroll
    for (int i = 0; i < 6; i++)
#pragma unroll
        for (int j = 0; j < 4; j++) acc[i / 3][i % 3][j] = 0.f;
    const int mi = lane >> 3;
    const uint32_t ro = ((lane & 7) + 8 * (mi >> 1)) * 16, bd = tb + ro + (mi & 1) * 512, b2 = ro + ((mi & 1) ? t5 : tb + 2048);
#pragma unroll
    for (int kp = 0; kp < 2; kp++)
#pragma unroll
        for (int j = 0; j < 3; j++) {
            uint32_t b[4];
            ldsm_x4_t(b[0], b[1], b[2], b[3], (j < 2 ? bd + j * 1024 : b2) + kp * 256);
#pragma unroll
            for (int h = 0; h < 2; h++)
#pragma unroll
                for (int m = 0; m < 2; m++) {
                    const uint32_t (&A)[4] = k.A[m][2 * kp + h];
                    mma_f16(acc[m][j], A[0], A[1], A[2], A[3], b[2 * h], b[2 * h + 1]);
                }
        }
    __syncwarp();
#define PK(j) pack_f16(acc[0][j][0], acc[0][j][1]), pack_f16(acc[0][j][2], acc[0][j][3]), pack_f16(acc[1][j][0], acc[1][j][1]), pack_f16(acc[1][j][2], acc[1][j][3])
    stsm_x4(tb + lane * 16, PK(0));
    stsm_x4(tb + 512 + lane * 16, PK(1));
    stsm_x4_t(tb + 1024 + (lane & 7) * 80 + mi * 16, PK(2));
#undef PK
}
__device__ __forceinline__ uint32_t table_buf(uint32_t sb, int warp) { return sb + SM_PL + warp * TBW; }

__device__ __forceinline__ uint4 lds16x4(uint32_t a) { return make_uint4(lds16(a), lds16(a + TBW), lds16(a + 2 * TBW), lds16(a + 3 * TBW)); }
__device__ __forceinline__ void combine_setup(uint32_t sb, int warp, int lane, uint32_t kw, uint32_t& o, uint32_t& n, uint32_t& d) {
    const int wq = warp & 3;
    const uint32_t a = table_buf(sb, warp & ~3);
    o = wq == 3 ? a + 1024 + 320 + (lane >> 3) * 80 + (lane & 7) * 8 : a + (wq ? 504 + wq * 8 : 0) + lane * 16;
    n = a + 1024 + wq * 80 + lane * 2;
    d = wq < 3 ? kw + (wq == 2 ? KW_P : 32 + wq * 512) + lane * 16 : kw + KW_H + 8 + lane * 8;
}
__device__ __forceinline__ void kgen_combine(int wq, int lane, uint32_t o, uint32_t na, uint32_t d) {
#define S4(f) hadd2(hadd2(u.f, v.f), hadd2(w.f, x.f))
#define H4(v) hadd2(hadd2(v.x, v.y), hadd2(v.z, v.w))
#define BP __byte_perm
    if (wq == 0) {
        const uint4 u = lds128(o), v = lds128(o + TBW), w = lds128(o + 2 * TBW), x = lds128(o + 3 * TBW), nn = lds16x4(na);
        const uint32_t n = H4(nn), k0 = S4(x), k2 = S4(y), k4 = S4(z), k6 = S4(w);
        sts128(d, BP(k0, k0, 0x1032), BP(k0, k2, 0x3254), BP(k2, k2, 0x1032), BP(k2, k4, 0x3254));
        sts128(d + KW_PL, BP(k4, k4, 0x1032), BP(k4, k6, 0x3254), BP(k6, k6, 0x1032), BP(k6, n, 0x3254));
        if (lane == 0) sts32(d + KW_PL - 4, k0 & 0xffffu);
    } else {
        const uint2 u = lds64(o), v = lds64(o + TBW), w = lds64(o + 2 * TBW), x = lds64(o + 3 * TBW);
        uint4 nn = make_uint4(0u, 0u, 0u, 0u), mm = nn;
        if (wq < 3) nn = lds16x4(na);
        if (wq == 2) mm = lds16x4(na + 80);
        const uint32_t k0 = S4(x), k2 = S4(y), n = H4(nn), m = H4(mm);
        if (wq == 3) {
            sts64(d, k0, k2);
        } else if (wq == 1) {
            const uint32_t cc = BP(k2, k2, 0x1010);
            sts128(d, BP(k0, k0, 0x1010), BP(k0, k0, 0x1032), BP(k0, k2, 0x3254), cc);
            sts128(d + KW_PL, cc, BP(k2, k2, 0x1032), BP(k2, n, 0x3254), BP(n, n, 0x1010));
        } else {
            const uint32_t w40 = BP(k0, k0, 0x1032), w84 = BP(k0, n, 0x3254), w0 = BP(k0, k0, 0x1010), w4 = BP(k0, k0, 0x3232), w8 = BP(n, n, 0x1010);
            sts64(d, w40, w84);
            sts64(d + 512, BP(k2, k2, 0x1032), BP(k2, m, 0x3254));
            if (lane < 8) { sts128(d - (KW_P - 1056), w0, w0, w40, w4); sts128(d - (KW_P - 1056 - KW_PL), w4, w84, w8, w8); }
            if (lane == 31) sts16(d + (KW_H + 6 - KW_P - 496), m);
        }
    }
#undef S4
#undef H4
#undef BP
}

__device__ __forceinline__ int c_exponent(const uint2& r, const uint2& i, float dt) {
    const uint32_t mx = __vmaxu2(__vmaxu2(r.x & 0x7fff7fffu, r.y & 0x7fff7fffu), __vmaxu2(i.x & 0x7fff7fffu, i.y & 0x7fff7fffu));
    return __reduce_max_sync(0xffffffffu, max(mx, mx << 16) + (__float_as_uint(dt) & 0x7f800000u)) >> 23;
}

__device__ __forceinline__ int lane_v() { int l; asm volatile("mov.u32 %0, %%laneid;" : "=r"(l)); return l; }
__device__ __forceinline__ uint32_t prmt_v(uint32_t a, uint32_t b, uint32_t s) { uint32_t d; asm volatile("prmt.b32 %0, %1, %2, %3;\n" : "=r"(d) : "r"(a), "r"(b), "r"(s)); return d; }
__device__ __forceinline__ uint32_t mov_v(uint32_t a) { uint32_t d; asm volatile("mov.b32 %0, %1;\n" : "=r"(d) : "r"(a)); return d; }
template <int G>
__device__ __forceinline__ void conv_rename(float (&acc)[16][4]) {
#pragma unroll
    for (int i = G; i < 16; i++)
#pragma unroll
        for (int j = 0; j < 4; j++) { float v; asm volatile("mov.b32 %0, %1;\n" : "=f"(v) : "f"(acc[i][j])); acc[i][j] = v; }
}
struct Conv {
    uint32_t kw;
    uint32_t wa;
    uint32_t pa, s2;
    uint32_t s8;
    uint32_t id;
    uint32_t lc;
    uint32_t fs;
    uint32_t fl, yo;
    uint32_t yp;
    size_t ycopy;
    uint32_t ps;
    uint64_t d0;
    int warp;
};
struct Pk { uint32_t w[4]; };
__device__ __forceinline__ Pk pk2(const float (&u)[4], const float (&v)[4]) {
    Pk r;
    r.w[0] = pack_f16(u[0], u[1]); r.w[1] = pack_f16(u[2], u[3]); r.w[2] = pack_f16(v[0], v[1]); r.w[3] = pack_f16(v[2], v[3]);
    return r;
}
__device__ __forceinline__ void park(uint32_t a, const Pk& v) {
    asm volatile("stmatrix.sync.aligned.m8n8.x4.trans.shared.b16 [%0], {%1,%2,%3,%4};\n" ::"r"(a), "r"(v.w[0]), "r"(v.w[1]), "r"(v.w[2]), "r"(v.w[3]) : "memory");
}
__device__ __forceinline__ void conv_constants(uint32_t lc, int l) {
    const int d = (l >> 2) - 2 * (l & 3);
    const int e = d + 8, r4 = (e + 1 + ((e >> 2) & 1)) >> 2, p4 = (e + (((e - 1) >> 2) & 1)) >> 2;
    const uint32_t s2 = r4 == p4 ? 0x1010u : 0x3210u;
    sts64(lc + l * 8, KW_P + ((r4 - 5) >> 1) * 16 + ((r4 - 5) & 1) * 4, s2 | ((d < 0 ? s2 : 0x7654u) << 16));
    const int lo = (d >= 4) - (d < -3), ho = (d >= 5) - (d < -2), le = (d > 4) - (d < -4), he = (d > 5) - (d < -3);
    sts32(lc + 512 + l * 8, (0x5454u + lo * 0x22 + ho * 0x2200) | ((0x3232u + le * 0x22 + he * 0x2200) << 16));
    const int cc = l >> 2, j = l & 3;
    sts64(lc + 256 + l * 8, (j >> 1) * PL_HALF + (16 + cc) * 16 + (j & 1) * 8, (cc >> 1) * (DM * 64) + (cc & 1) * 32 + j * 8);
}
__device__ __forceinline__ void conv_selectors4(Conv& c) {
    const uint2 v = lds64(c.lc + lane_v() * 8);
    c.pa = v.x; c.s2 = v.y;
}
__device__ __forceinline__ void conv_selectors8(Conv& c) { c.s8 = lds32(c.lc + 512 + lane_v() * 8); }
template <int G, int I0, int I1>
__device__ __forceinline__ void conv_load(const Conv& c, uint32_t (&q)[9]) {
    const int wq = c.warp & 3;
    if (G < 2) {
#pragma unroll
        for (int i = I0; i < I1; i++) q[i] = lds32(c.wa + G * 512 + i * 16);
    } else if (G < 4) {
        const uint32_t a = (G == 2 && wq == 0) ? c.wa + 1024 : c.pa + c.kw + wq * 128 + (G < 2 ? 0 : G - 2) * 512;
#pragma unroll
        for (int i = I0; i < I1; i++) q[i] = lds32(a + i * 16);
    } else {
        const uint4 u = lds128(c.kw + KW_H + (G < 4 ? 0 : G - 4) * 64 + wq * 16);
        const uint2 v = lds64(c.kw + KW_H + (G < 4 ? 0 : G - 4) * 64 + wq * 16 + 16);
        q[0] = u.x; q[1] = u.y; q[2] = u.z; q[3] = u.w; q[4] = v.x; q[5] = v.y;
        if (G == 4 && wq == 0) { q[6] = lds32(c.pa + c.kw + 1024); q[7] = lds32(c.pa + c.kw + 1040); }
    }
}
template <int G, int J0, int J1>
__device__ __forceinline__ void conv_frag(const Conv& c, const uint32_t (&q)[9], uint32_t* a, const Pk& dp) {
    const uint32_t dep = dp.w[0];
    if (G < 4) {
        const uint32_t s = (G < 2 || (G == 2 && (c.warp & 3) == 0)) ? c.id : c.s2;
#pragma unroll
        for (int j = J0; j < J1; j++) {
            uint32_t* o = a + 4 * (j - J0);
            o[0] = prmt_v(q[2 * j + 1], dp.w[0], s); o[1] = prmt_v(q[2 * j + 2], dp.w[1], s); o[2] = prmt_v(q[2 * j], dp.w[2], s); o[3] = prmt_v(q[2 * j + 1], dp.w[3], s);
        }
    } else {
        const uint32_t so = prmt_v(c.s8, dep, c.id), se = prmt_v(c.s8, dep, c.id + 0x22);
#pragma unroll
        for (int j = J0; j < J1; j++) {
            uint32_t* o = a + 4 * (j - J0);
            o[0] = prmt_v(q[j + 1], q[j + 2], se); o[1] = prmt_v(q[j + 1], q[j + 2], so); o[2] = prmt_v(q[j], q[j + 1], so);
            if (G == 4 && j == 0 && (c.warp & 3) == 0) {
                o[2] = prmt_v(q[6], dep, c.s2);
                o[0] = prmt_v(q[7], o[0], c.s2 >> 16);
            }
            o[3] = mov_v(o[0]);
        }
    }
}
template <int G, int J0, int J1>
__device__ __forceinline__ void conv_frag(const Conv& c, const uint32_t (&q)[9], uint32_t* a, float depf) {
    const uint32_t d = __float_as_uint(depf);
    conv_frag<G, J0, J1>(c, q, a, Pk{{d, d, d, d}});
}
template <int G, int T, int J0, int J1>
__device__ __forceinline__ void conv_mma(float (&acc)[16][4], const Conv& c, const uint32_t* a) {
#pragma unroll
    for (int j = J0; j < J1; j++) wg_mma<T>(acc, a + 4 * (j - J0), c.d0 - 8 * (2 * G - T) - j);
}
__device__ __forceinline__ float h_lo(uint32_t w) { return __half2float(__ushort_as_half((unsigned short)(w & 0xffffu))); }
__device__ __forceinline__ float h_hi(uint32_t w) { return __half2float(__ushort_as_half((unsigned short)(w >> 16))); }
__device__ __forceinline__ void flush_setup(Conv& c) {
    const uint2 v = lds64(c.lc + 256 + lane_v() * 8);
    c.fl = v.x; c.yo = v.y;
}
template <int Q>
__device__ __forceinline__ void flush_load(const Conv& c, uint32_t pl, uint2 (&f)[4]) {
#pragma unroll
    for (int w = 0; w < 4; w++) f[w] = lds64(c.fl + pl + (Q & 1) * 512 + w * (PLW_B - 64));
}
template <int Q>
__device__ __forceinline__ void flush_load_first(const Conv& c, uint32_t pl, uint2 (&f)[4], float depf) {
    const uint32_t p = prmt_v(c.fl, __float_as_uint(depf), c.id) + pl + (Q & 1) * 512;
#define LDV64(d, a) asm volatile("ld.volatile.shared.v2.u32 {%0,%1}, [%2];\n" : "=r"(d.x), "=r"(d.y) : "r"(a) : "memory")
    LDV64(f[0], p); LDV64(f[1], p + (PLW_B - 64)); LDV64(f[2], p + 2 * (PLW_B - 64)); LDV64(f[3], p + 3 * (PLW_B - 64));
}
#define FDEP __uint_as_float(f[3].y)
template <int Q, int mode>
__device__ __forceinline__ void conv_flush(const Conv& c, const uint2 (&f)[4], unsigned char* gy, uint32_t rx) {
    const uint32_t a0 = hadd2(f[0].x, f[1].x), a1 = hadd2(f[2].x, f[3].x), b0 = hadd2(f[0].y, f[1].y), b1 = hadd2(f[2].y, f[3].y);
    if (Q > 0 && mode == 1) {
        const uint32_t ra = rx + 16 + (Q > 0 ? Q - 1 : 0) * 1024 + (c.warp & 3) * 256 + lane_v() * 8;
        asm volatile("st.async.shared::cluster.mbarrier::complete_tx::bytes.v2.b32 [%0], {%1,%2}, [%3];\n"
                     ::"r"(ra ^ 0x1000000u), "r"(hadd2(a0, a1)), "r"(hadd2(b0, b1)), "r"((rx + (Q > 1 ? 8 : 0)) ^ 0x1000000u) : "memory");
        return;
    }
    float v0 = h_lo(a0) + h_lo(a1), v1 = h_hi(a0) + h_hi(a1), v2 = h_lo(b0) + h_lo(b1), v3 = h_hi(b0) + h_hi(b1);
    if (Q > 0 && mode == 2) {
        const uint2 o = lds64(rx + 16 + (Q > 0 ? Q - 1 : 0) * 1024 + (c.warp & 3) * 256 + lane_v() * 8);
        v0 += h_lo(o.x); v1 += h_hi(o.x); v2 += h_lo(o.y); v3 += h_hi(o.y);
    }
    const uint32_t lo = hmul2_bf(pack_bf16(v0, v1), c.fs), hi = hmul2_bf(pack_bf16(v2, v3), c.fs);
    stg64(gy + Q * 32 * DM * 32 + (c.yo + (Q < 2 ? c.yp : 0u)), nzw(lo), nzw(hi));
}
template <int I, bool S = false> struct IC { static constexpr int value = I; static constexpr bool shared = S; };
template <class T> __device__ constexpr bool wg_is4() { return T::shared; }
#define SLOT(n) (c.ps + (2 + ((n) & 7)) * 128)
#define GO() do { wg_commit(); __syncwarp(); } while (0)
#define DEP acc[15][3]
template <class FG, class FP, class FN>
__device__ __forceinline__ void conv_head(Conv& c, float (&acc)[16][4], uint32_t (&q)[9], uint32_t (&r)[9], uint32_t* a, FG fg, FP pre, FN next) {
    c.id = 0x3210u + (c.warp >> 8);
    pre();
    conv_load<0, 0, 9>(c, q);
    conv_frag<0, 0, 1>(c, q, a, 0.f);
    wg_fence(); wg_first<0>(acc, a, c.d0); GO();
    park(c.ps, Pk{{0u, 0u, 0u, 0u}});
    wg_wait0();
    conv_frag<0, 1, 2>(c, q, a, DEP);
    wg_fence(); conv_mma<0, 0, 1, 2>(acc, c, a); GO();
    fg(IC<0>());
    wg_wait0();
    conv_frag<0, 2, 3>(c, q, a, DEP);
    wg_fence(); conv_mma<0, 0, 2, 3>(acc, c, a); GO();
    conv_load<1, 0, 5>(c, r);
    wg_wait0();
    conv_frag<0, 3, 4>(c, q, a, DEP);
    wg_fence(); conv_mma<0, 0, 3, 4>(acc, c, a); GO();
    conv_load<1, 5, 9>(c, r);
    fg(IC<1>());
    wg_wait0();
    const Pk k = pk2(acc[0], acc[1]);
    conv_rename<2>(acc);
    conv_frag<1, 0, 2>(c, r, a, k);
    wg_fence(); conv_mma<1, 2, 0, 2>(acc, c, a); GO();
    park(SLOT(0), k);
    next(IC<0>());
    fg(IC<2>());
    wg_wait0();
    conv_frag<1, 2, 4>(c, r, a, DEP);
    wg_fence(); conv_mma<1, 2, 2, 4>(acc, c, a); GO();
    next(IC<1>());
    fg(IC<3>());
    wg_wait0();
}
template <class FG, class FP>
__device__ __forceinline__ void conv_run(Conv& c, uint32_t pl, unsigned char* gy, FG fg, FP pre) {
    float acc[16][4];
    uint32_t q[9], r[9], a[32];
    uint2 f[4];
    const int bid = 1 + (c.warp >> 2);
    conv_head(c, acc, q, r, a, fg, pre, [&](auto i) { if (decltype(i)::value == 0) conv_selectors4(c); else conv_load<2, 0, 9>(c, q); });
    Pk k = pk2(acc[2], acc[3]);
    conv_rename<4>(acc);
    conv_frag<2, 0, 4>(c, q, a, k);
    wg_fence(); conv_mma<2, 4, 0, 4>(acc, c, a); GO();
    park(SLOT(2), k);
    conv_load<3, 0, 9>(c, q);
    flush_setup(c);
    bar_sync(bid, 128);
    fg(IC<4>());
    wg_wait0();
    conv_rename<6>(acc);
    conv_frag<3, 0, 4>(c, q, a, DEP);
    wg_fence(); conv_mma<3, 6, 0, 4>(acc, c, a); GO();
    park(SLOT(4), pk2(acc[4], acc[5]));
    conv_load<4, 0, 9>(c, q);
    conv_selectors8(c);
    flush_load<0>(c, pl, f);
    conv_flush<0, 0>(c, f, gy, 0u);
    fg(IC<5>());
    wg_wait0();
    conv_rename<8>(acc);
    conv_frag<4, 0, 4>(c, q, a, DEP);
    wg_fence(); conv_mma<4, 8, 0, 4>(acc, c, a); GO();
    k = pk2(acc[6], acc[7]);
    park(SLOT(6), k);
    conv_load<5, 0, 9>(c, q);
    bar_sync(bid, 128);
    park(c.ps, k);
    fg(IC<6>());
    wg_wait0();
    conv_rename<10>(acc);
    flush_load_first<1>(c, pl, f, DEP);
    conv_frag<5, 0, 4>(c, q, a, FDEP);
    wg_fence(); conv_mma<5, 10, 0, 4>(acc, c, a); GO();
    park(SLOT(8), pk2(acc[8], acc[9]));
    conv_load<6, 0, 9>(c, q); conv_load<7, 0, 9>(c, r);
    conv_flush<1, 0>(c, f, gy, 0u);
    fg(IC<7>());
    wg_wait0();
    conv_rename<12>(acc);
    conv_frag<6, 0, 4>(c, q, a, DEP); conv_frag<7, 0, 4>(c, r, a + 16, DEP);
    wg_fence(); conv_mma<6, 12, 0, 4>(acc, c, a); conv_mma<7, 12, 0, 4>(acc, c, a + 16); GO();
    park(SLOT(10), pk2(acc[10], acc[11]));
    bar_sync(bid, 128);
    flush_load<2>(c, pl, f);
    conv_flush<2, 0>(c, f, gy, 0u);
    fg(IC<8>());
    if (c.id == 0) TRAP();
    wg_wait0();
    park(SLOT(12), pk2(acc[12], acc[13])); park(SLOT(14), pk2(acc[14], acc[15]));
    bar_sync(bid, 128);
    flush_load<3>(c, pl, f);
    conv_flush<3, 0>(c, f, gy, 0u);
}
template <class FG>
__device__ __forceinline__ void conv_outer(Conv& c, uint32_t pl, unsigned char* gy, uint32_t rx, FG fg) {
    float acc[16][4];
    uint32_t q[9], r[9], a[32];
    uint2 f[4], f2[4];
    const int bid = 1 + (c.warp >> 2);
    conv_head(c, acc, q, r, a, [&](auto gi) { if (decltype(gi)::value == 2) fg(IC<2, true>()); }, [&]() {}, [&](auto i) { if (decltype(i)::value == 0) conv_selectors8(c); else conv_load<6, 0, 9>(c, q); });
    park(SLOT(2), pk2(acc[2], acc[3])); park(SLOT(4), pk2(acc[4], acc[5]));
    const Pk k = pk2(acc[6], acc[7]);
    park(SLOT(6), k);
    conv_load<7, 0, 9>(c, r);
    conv_rename<12>(acc);
    conv_frag<6, 0, 4>(c, q, a, __uint_as_float(k.w[3])); conv_frag<7, 0, 4>(c, r, a + 16, __uint_as_float(k.w[3]));
    wg_fence(); conv_mma<6, 12, 0, 4>(acc, c, a); conv_mma<7, 12, 0, 4>(acc, c, a + 16); GO();
    flush_setup(c);
    bar_sync(bid, 128);
    flush_load<0>(c, pl, f); flush_load<1>(c, pl, f2);
    conv_flush<1, 1>(c, f2, gy, rx);
    conv_flush<0, 1>(c, f, gy, rx);
    wg_wait0();
    bar_sync(bid, 128);
    park(c.ps, k); park(SLOT(8), pk2(acc[8], acc[9])); park(SLOT(10), pk2(acc[10], acc[11]));
    park(SLOT(12), pk2(acc[12], acc[13])); park(SLOT(14), pk2(acc[14], acc[15]));
    bar_sync(bid, 128);
    flush_load<2>(c, pl, f); flush_load<3>(c, pl, f2);
    conv_flush<2, 1>(c, f, gy, rx);
    conv_flush<3, 1>(c, f2, gy, rx);
}
template <class FG>
__device__ __forceinline__ void conv_inner(Conv& c, uint32_t pl, unsigned char* gy, uint32_t rx, FG fg) {
    float acc[16][4];
    uint32_t q[9], a[16];
    uint2 f[4], f2[4];
    const int bid = 1 + (c.warp >> 2);
    c.id = 0x3210u + (c.warp >> 8);
    conv_selectors4(c);
    conv_load<2, 0, 9>(c, q);
    conv_frag<2, 0, 4>(c, q, a, 0.f);
    wg_fence(); wg_first<4>(acc, a, c.d0); conv_mma<2, 4, 1, 4>(acc, c, a + 4); GO();
    conv_load<3, 0, 9>(c, q);
    park(SLOT(2), Pk{{0u, 0u, 0u, 0u}});
    fg(IC<2, true>());
    wg_wait0();
    conv_rename<6>(acc);
    conv_frag<3, 0, 4>(c, q, a, DEP);
    wg_fence(); conv_mma<3, 6, 0, 4>(acc, c, a); GO();
    park(SLOT(4), pk2(acc[4], acc[5]));
    conv_load<4, 0, 9>(c, q);
    conv_selectors8(c);
    wg_wait0();
    conv_rename<8>(acc);
    conv_frag<4, 0, 4>(c, q, a, DEP);
    wg_fence(); conv_mma<4, 8, 0, 4>(acc, c, a); GO();
    const Pk k = pk2(acc[6], acc[7]);
    park(SLOT(6), k); park(c.ps, k);
    conv_load<5, 0, 9>(c, q);
    flush_setup(c);
    wg_wait0();
    conv_rename<10>(acc);
    conv_frag<5, 0, 4>(c, q, a, DEP);
    wg_fence(); conv_mma<5, 10, 0, 4>(acc, c, a); GO();
    park(SLOT(8), pk2(acc[8], acc[9]));
    bar_sync(bid, 128);
    flush_load<1>(c, pl, f);
    mbar_wait(rx);
    conv_flush<1, 2>(c, f, gy, rx);
    wg_wait0();
    bar_sync(bid, 128);
    park(SLOT(10), pk2(acc[10], acc[11])); park(SLOT(12), pk2(acc[12], acc[13])); park(SLOT(14), pk2(acc[14], acc[15]));
    bar_sync(bid, 128);
    flush_load<3>(c, pl, f); flush_load<2>(c, pl, f2);
    mbar_wait(rx + 8);
    conv_flush<3, 2>(c, f, gy, rx);
    conv_flush<2, 2>(c, f2, gy, rx);
}
#undef SLOT
#undef GO
#undef DEP
template <int U0, int U1>
__device__ __forceinline__ void weight_units(uint32_t sb, const Maps& tm, bool w) {
    if (U1 > U0 && w && elect_one()) {
#pragma unroll
        for (int i = U0; i < U1; i++) {
            const int P = blockIdx.x >> 1, odd = blockIdx.x & 1;
            if (i < 12) tma_2d(sb + SM_WG + i * 6144, &tm.w[i / 6], 64 * P, 288 * odd + (i % 6) * 48, sb + SM_MISC + 328);
            else tma_2d(sb + SM_WD + (i - 12) * 4736, &tm.d, 144 * odd, i < 20 ? 64 * P + 8 * (i - 12) : 4096 + 8 * P, sb + SM_MISC + 336);
            if (i >= 8 && i < 12) tma_2d(sb + SM_WR + (i - 8) * 2304, &tm.r[(i - 8) >> 1], 4096 + 8 * P, 288 * odd + (i & 1) * 144, sb + SM_MISC + 328);
        }
    }
}
#define WS 2210121111113004000
__device__ constexpr int wsched(int i) {
    unsigned long long v = WS;
    int n = 0;
    for (int k = 19; k >= 1; k--) { if (k < i) n += (int)(v % 10); v /= 10; }
    return n;
}
static_assert(wsched(20) == 21 && wsched(6) <= 8 && wsched(11) <= 12 && wsched(13) <= 14 && wsched(16) <= 17 && wsched(16) == wsched(15) && wsched(19) == 21, "");
#define WANY(i) (wsched((i) + 1) > wsched(i))
#define WPOINT(i, w) do { weight_units<wsched(i), wsched(i + 1)>(sb, tm, w); } while (0)

__global__ void __launch_bounds__(NTHR, 1) __cluster_dims__(2, 1, 1)
fused_kernel(const Params p, const __grid_constant__ Maps tm) {
    extern __shared__ __align__(1024) unsigned char smem[];
    const uint32_t sb = smem_u32(smem);
    const int tid = threadIdx.x, warp = __shfl_sync(0xffffffffu, tid >> 5, 0), lane = tid & 31;
    const int b = blockIdx.x, P = b >> 1, odd = b & 1;
    const int g = lane >> 2, t = lane & 3;
    const int wg = warp >> 2, t128 = tid & 127;
    const uint32_t s_stat = sb + SM_MISC;
    const uint32_t s_key = sb + SM_MISC + 128;
    const uint32_t s_rank = sb + SM_MISC + 256;
    const uint32_t s_k16 = sb + SM_MISC + 192;
    const uint32_t s_cnt = sb + SM_MISC + 320;
    const uint32_t bar_w = sb + SM_MISC + 328, bar_d = bar_w + 8, bar_g = bar_w + 16, bar_x = bar_w + 24, bar_v = bar_w + 32, bar_s = bar_w + 40, bar_h = bar_w + 48;
    STAMP(0);

    const int ch = wg < 4 ? 4 * b + wg : 512 + P;
    const uint32_t mo = tid < 512 ? 512 * b + tid : 65536 + 128 * P + t128, mq = (mo & ~127u) + 4 * lane;
    const uint32_t pl = ldo16(p.lar + mo), pa2 = ldo16(p.aim + mo), ldt = ldo16(p.ldt + (mo >> 7));
    const uint32_t pc = ldo16(p.cre + mo), pi = ldo16(p.cim + mo);
    const uint2 call_re = ldo64(p.cre + mq), call_im = ldo64(p.cim + mq);
    const uint32_t epl = ld_poll32(p.s->hint + (b & 7) * 32 + 1);
    const uint32_t kw = sb + SM_KW + wg * KW_B;
    uint32_t co, cn, cd, uo;
    auto housekeeping = [&]() {
        if (t128 < 2 * UPAD) sts128(sb + SM_U + wg * USLOT_B + (t128 & 1) * ULO_B + (t128 >> 1) * 16, 0u, 0u, 0u, 0u);
        if (t128 >= 124) sts128(kw + (t128 & 1) * 16 + (t128 & 2) * (KW_PL / 2), 0u, 0u, 0u, 0u);
        if (warp < 15) sts128(sb + SM_Z2 + 4608 + tid * 16, 0u, 0u, 0u, 0u);
        combine_setup(sb, warp, lane, kw, co, cn, cd);
        co = pin(co); cn = pin(cn); cd = pin(cd);
        uo = pin(wg < 4 ? tid : 512 + (P >> 2) * 1024 + (t128 >> 1) * 8 + (P & 3) * 2 + (t128 & 1));
    };
    if (wg < 4) {
        bar_arrive(0, NWRK);
        asm volatile("barrier.cluster.arrive.relaxed.aligned;\n" ::: "memory");
        housekeeping();
    } else {
        const int o = (warp & 3) * 4608 + lane * 16;
        sts128(sb + SM_Z2 + t128 * 16, 0u, 0u, 0u, 0u); sts128(sb + SM_Z2 + 2048 + t128 * 16, 0u, 0u, 0u, 0u);
        if (warp == 16) sts128(sb + SM_Z2 + 4096 + lane * 16, 0u, 0u, 0u, 0u);
        fence_async();
        bar_sync(0, NWRK);
        STAMP(9);
#pragma unroll
        for (int c = 0; c < 9; c++)
            asm volatile("cp.async.cg.shared.global [%0], [%1], 16;\n" ::"r"(sb + SM_XT + o + c * 512), "l"(reinterpret_cast<const char*>(p.x) + b * 18432 + o + c * 512) : "memory");
        asm volatile("cp.async.commit_group;\n" ::: "memory");
        if (elect_one()) {
            mbar_init(bar_h + 8 * (warp & 3), 1);
            if (warp == 19) {
                mbar_init(bar_x, 1); mbar_init(bar_w, 1);
                mbar_expect(bar_x, 32768); mbar_expect(bar_w, 82944);
#pragma unroll
                for (int i = 2; i < 4; i++) bulk_s2g(reinterpret_cast<unsigned char*>(p.s->y) + 32 * i * 18432 + b * 4608, sb + SM_Z2, 4608);
            } else if (warp == 18) {
                mbar_init(bar_s, 1); mbar_init(bar_v, 2); mbar_init(bar_d, 1); mbar_init(bar_g, 1); mbar_init(sb + SM_RX, 1); mbar_init(sb + SM_RX + 8, 1);
                mbar_expect(bar_v, 2 * 1152); mbar_expect(bar_d, 72 * WD_PITCH); mbar_expect(bar_g, 4608); mbar_expect(sb + SM_RX, 1024); mbar_expect(sb + SM_RX + 8, 2048);
            }
            asm volatile("fence.mbarrier_init.release.cluster;\n" ::: "memory");
        }
        __syncwarp();
        asm volatile("barrier.cluster.arrive.relaxed.aligned;\n" ::: "memory");
        if (warp == 19) {
            asm volatile("barrier.cluster.wait.aligned;\n" ::: "memory");
            if (elect_one()) tma_4d_mc(sb + SM_XC + odd * 16384, &tm.x, 8 * P, 2 * odd, bar_x);
            __syncwarp();
        }
    }
    const uint32_t tb = table_buf(sb, warp), t5 = sb + SM_WD + warp * 512;
    STAMP(29);
    const float dt = exp_bf(bf_lo(ldt));
    const uint32_t ep = __reduce_or_sync(0xffffffffu, epl);
    auto stats = [&]() {
        const int wq = warp & 3;
        const uint32_t xa = sb + SM_XT + (4 * wq + (g >> 1)) * 1152 + (g & 1) * 576 + t * 16;
        const bool own = !(g & 1) && t == (g >> 1);
        float d[4][4] = {};
        asm volatile("cp.async.wait_group 0;\n" ::: "memory");
        __syncwarp();
        STAMP(26);
        uint4 v[9];
#pragma unroll
        for (int c = 0; c < 9; c++) v[c] = lds128(xa + c * 64);
#pragma unroll
        for (int c = 0; c < 9; c++) {
            mma_bf16(d[2 * (c & 1)], v[c].x, 0x3f803f80u, v[c].y, 0x3f803f80u, v[c].x, v[c].y);
            mma_bf16(d[2 * (c & 1) + 1], v[c].z, 0x3f803f80u, v[c].w, 0x3f803f80u, v[c].z, v[c].w);
        }
        STAMP(27);
        float sm = (g & 1) ? (d[0][3] + d[1][3]) + (d[2][3] + d[3][3]) : (d[0][2] + d[1][2]) + (d[2][2] + d[3][2]);
        float sq = (g & 1) ? (d[0][1] + d[1][1]) + (d[2][1] + d[3][1]) : (d[0][0] + d[1][0]) + (d[2][0] + d[3][0]);
        sm += __shfl_xor_sync(0xffffffffu, sm, 4); sq += __shfl_xor_sync(0xffffffffu, sq, 4);
        if (lane == 0) mbar_arrive(bar_h + 8 * wq);
        float mb, sd;
        ln_stats(sm, sq, mb, sd);
        if (own) p.s->stat[16 * b + 4 * wq + t] = (__float_as_uint(mb) >> 16) | (__float_as_uint(sd) & 0x7fff0000u) | (ep << 31);
        STAMPX(22);
        if (own) stat_store(s_stat + (2 * wq + (t & 1) + 8 * (t >> 1)) * 8, mb, rcp_approx(sd), 0u);
        if (wq == 3) asm volatile("cp.async.bulk.wait_group 0;\n" ::: "memory");
        bar_sync(5, 128);
        STAMP(28);
        uint32_t now;
        asm volatile("mov.u32 %0, %%clock;" : "=r"(now) :: "memory");
        if (wq == 2) {
            conv_constants(sb + SM_LC, lane);
            __syncwarp();
            if (lane == 0) {
                sts64(s_cnt, now, ep);
                mbar_arrive(bar_s);
                bulk_g2s(sb + SM_XT + 16 * 1152, p.dsk, 1152, bar_v);
                bulk_g2s(sb + SM_XT + 17 * 1152, p.wr, 1152, bar_v);
            }
            __syncwarp();
        }
        WPOINT(1, wq == 3);
        if (wq < 2) {
            unsigned char* const ud = reinterpret_cast<unsigned char*>(p.s->uT) + (size_t)(8 * wq + 2 * (g >> 1)) * 16384 + b * 128 + (g & 1) * 32 + t * 8;
            const uint32_t utag = (ep % 7u + 1u) * 0x10001u;
            uint32_t U[2][4];
#pragma unroll
            for (int hf = 0; hf < 2; hf++) {
                const uint2 st = lds64(s_stat + (g + 8 * hf) * 8);
                const uint4 xu = lds128(sb + SM_XT + (TOK(g) + 2 * hf) * 1152 + warp * 64 + t * 16);
                const uint32_t X[4] = {xu.x, xu.y, xu.z, xu.w};
#pragma unroll
                for (int k = 0; k < 4; k++) {
                    const uint32_t u = ln_apply(X[k], STAT_M(st), STAT_H(st), STAT_L(st));
                    U[hf][k] = movm((pack_f16(bf_lo(u), bf_hi(u)) & 0xfff8fff8u) | utag);
                }
            }
#pragma unroll
            for (int k = 0; k < 4; k++) stg64(ud + (k >> 1) * 16384 + (k & 1) * 64, U[0][k], U[1][k]);
        }
    };
    STAMP(1);
    if (wg < 4) { STAMPX(16); }
    KGen kg;
    kgen_setup(kg, bf_lo(pl), bf_lo(pa2), dt);
    kgen_rows(kg, tb, lane);
    STAMP(2);
    const int E = min(max(c_exponent(call_re, call_im, dt) - 243, -120), 120);
    kgen_chain(kg, pc, pi, dt * __uint_as_float((uint32_t)(128 - E) << 23));
    STAMP(3);
    kgen_cols(kg, tb, t5, lane);
    STAMP(4);
    if (wg == 4) stats();
    if (warp != 19) asm volatile("barrier.cluster.wait.aligned;\n" ::: "memory");
    if (wg < 4) { STAMPX(17); }
    if (wg == 4) housekeeping();
    const uint4* const usrc = reinterpret_cast<const uint4*>(p.s->stat) + uo;
    if (wg < 4) mbar_wait(bar_h + 8 * (warp & 3));
    if (wg < 4) { STAMPX(19); }
    uint32_t trel;
    asm volatile("mov.u32 %0, %%clock;" : "=r"(trel) :: "memory");
    kgen_mma(kg, tb, t5, lane);
    if (wg < 4) { STAMPX(20); }
    STAMP(5);
    uint4 uv0, uv1;
    auto first_poll = [&](uint32_t dly) {
        mbar_wait(bar_s);
        const uint32_t t0 = lds32(s_cnt);
        uint32_t now;
        do { asm volatile("mov.u32 %0, %%clock;" : "=r"(now) :: "memory"); } while (now - t0 < dly);
        uv0 = ld_poll(usrc);
    };
    if (wg == 4) { first_poll(UDLY); uv1 = ld_poll(usrc + 512); }
    WPOINT(2, warp == 19);
    auto stat_poll = [&]() {
        uint32_t now;
        do { asm volatile("mov.u32 %0, %%clock;" : "=r"(now) :: "memory"); } while (now - trel < SDLY);
        uv0 = ld_poll(usrc);
    };
    bar_sync(1 + wg, 128);
    if (wg < 4) { STAMPX(21); }
    kgen_combine(warp & 3, lane, co, cn, cd);
    STAMP(6);
    if (wg < 4) { STAMPX(18); }
    WPOINT(3, warp == 19);
    if (wg < 4) stat_poll();
    {
        const int wq = warp & 3;
        Conv c;
        const uint32_t pln = sb + SM_PL + wg * PL_B;
        const int e = g - 2 * t + 7;
        c.kw = kw; c.wa = pin(kw + ((e >> 2) & 1) * KW_PL + (8 * wq + (e >> 3)) * 16 + (e & 3) * 4);
        c.ps = mov_v(pln + wq * PLW_B + ((lane >> 3) & 1) * PL_HALF + ((lane >> 4) * 8 + (lane & 7)) * 16); c.warp = warp;
        c.lc = sb + SM_LC; c.fs = (uint32_t)(127 + E) * 0x800080u; c.yp = (ep & 1u) * (NCTA * 18432u);
        c.d0 = ((uint64_t)(ULO_B >> 4) << 16) | ((uint64_t)(128 >> 4) << 32) | (uint64_t)(((sb + SM_U + wg * USLOT_B + UPAD * 16) & 0x3FFFF) >> 4);
        unsigned char* gy = reinterpret_cast<unsigned char*>(p.s->y) + ((size_t)(4 * wq) * DM + ch) * 64;
        auto hook = [&](auto gi) {
                     constexpr int G = decltype(gi)::value;
                     if (G == (wg_is4<decltype(gi)>() ? 2 : 5)) asm volatile("barrier.cluster.wait.aligned;\n" ::: "memory");
                     if (!wg_is4<decltype(gi)>() && G == 1) mbar_wait(bar_s);
                     if (!wg_is4<decltype(gi)>() && (G == 0 || G == 2) && warp == HW && elect_one()) {
                         unsigned char* const sc = reinterpret_cast<unsigned char*>(p.s);
                         if (G == 0) {
                             if (b < 96) bulk_s2g_nc(sc + offsetof(Scratch, part) + b * 6144, sb + SM_Z2, 6144);
                             bulk_s2g(sc + offsetof(Scratch, rows) + (127 - b) * 4608, sb + SM_Z2, 4608);
                         }
                         if (G == 2) {
                             bulk_s2g(sc + offsetof(Scratch, y) + (NCTA * 18432u - c.yp) + b * 9216, sb + SM_Z2, 9216);
                         }
                     }
                     if (!wg_is4<decltype(gi)>()) WPOINT(6 + G, warp == (G >= 7 ? HW : 4 * (G % 3) + 1));
                     if (!wg_is4<decltype(gi)>() && G == 6 && warp == HW) {
                         asm volatile("cp.async.bulk.wait_group 0;\n" ::: "memory");
                         __syncwarp();
                         if (elect_one()) mbar_arrive(bar_v);
                     }
                 };
        if (wg < 4) {
            asm volatile("barrier.cluster.arrive.relaxed.aligned;\n" ::: "memory");
            conv_run(c, pln + wq * 128, gy, hook, [&]() {
                STAMPX(23);
                mbar_wait(bar_x);
                STAMPX(24);
                uint2 xc[4];
                uint32_t xw[4][2];
#pragma unroll
                for (int j = 0; j < 4; j++) xc[j] = lds64(sb + SM_XC + wg * 8192 + j * 2048 + t128 * 16 + odd * 8);
#pragma unroll
                for (int i = 0; i < 8; i++) {
                    const int k = i >> 1, h = i & 1;
                    xw[k][h] = prmt_v(k < 2 ? xc[2 * h].x : xc[2 * h].y, k < 2 ? xc[2 * h + 1].x : xc[2 * h + 1].y, (k & 1) ? 0x7632 : 0x5410);
                }
                const uint32_t ub = mov_v(sb + SM_U + UPAD * 16 + ((tid >> 1) & 1) * ULO_B + (tid >> 2) * 16 + (tid & 1) * 8), tag = ep << 31;
                int it = 0;
                while (min(min((int)(uv0.x ^ tag), (int)(uv0.y ^ tag)), min((int)(uv0.z ^ tag), (int)(uv0.w ^ tag))) < 0x10000) {
                    if (++it > SPIN_LIMIT) TRAP();
                    uv0 = ld_poll(usrc);
                }
                STAMP(8);
                STAMPX(26);
                const float r0 = rcp_approx(fabsf(bf_hi(uv0.x))), r1 = rcp_approx(fabsf(bf_hi(uv0.y))), r2 = rcp_approx(fabsf(bf_hi(uv0.z))), r3 = rcp_approx(fabsf(bf_hi(uv0.w)));
                const uint32_t m[2] = {__byte_perm(uv0.x, uv0.y, 0x5410), __byte_perm(uv0.z, uv0.w, 0x5410)};
                const uint32_t rh[2] = {pack_bf16(r0, r1), pack_bf16(r2, r3)};
                const uint32_t rl[2] = {pack_bf16(r0 - bf_lo(rh[0]), r1 - bf_hi(rh[0])), pack_bf16(r2 - bf_lo(rh[1]), r3 - bf_hi(rh[1]))};
#pragma unroll
                for (int k = 0; k < 4; k++) {
                    const uint32_t u0 = ln_apply(xw[k][0], m[0], rh[0], rl[0]), u1 = ln_apply(xw[k][1], m[1], rh[1], rl[1]);
                    sts64(ub + k * USLOT_B, pack_f16(bf_lo(u0), bf_hi(u0)), pack_f16(bf_lo(u1), bf_hi(u1)));
                }
                STAMPX(29);
                fence_async();
                bar_sync(14, 512);
                STAMP(7);
            });
        } else {
            auto stage = [&]() {
                const uint32_t tag = (ep % 7u + 1u) * 0x10001u;
                int it = 0;
                WPOINT(4, warp == 19);
                while (true) {
                    uv0.x ^= tag; uv0.y ^= tag; uv0.z ^= tag; uv0.w ^= tag; uv1.x ^= tag; uv1.y ^= tag; uv1.z ^= tag; uv1.w ^= tag;
                    if ((((uv0.x | uv0.y | uv0.z) | (uv0.w | uv1.x | uv1.y) | (uv1.z | uv1.w)) & 0x70007u) == 0) break;
                    if (++it > SPIN_LIMIT) TRAP();
                    uv0 = ld_poll(usrc); uv1 = ld_poll(usrc + 512);
                }
                STAMP(8);
                const uint32_t ub = sb + SM_U + UPAD * 16 + 4 * USLOT_B + (t128 & 1) * ULO_B + (t128 >> 1) * 16;
                sts128(ub, uv0.x, uv0.y, uv0.z, uv0.w);
                sts128(ub + 1024, uv1.x, uv1.y, uv1.z, uv1.w);
                fence_async();
                asm volatile("barrier.cluster.arrive.relaxed.aligned;\n" ::: "memory");
                bar_sync(5, 128);
                WPOINT(5, warp == 19);
                STAMP(7);
            };
            stage();
            if (odd) conv_inner(c, pln + wq * 128, gy, sb + SM_RX, hook);
            else conv_outer(c, pln + wq * 128, gy, sb + SM_RX, hook);
        }
        STAMP(10);
    }
    {
    const int lane = lane_v(), tid = 32 * warp + lane, g = lane >> 2, t = lane & 3;
    const uint32_t par = ~ep & 1u;
    bar_sync(0, NWRK);
    STAMP(11);
    uint32_t H[2][4] = {}, U2[2][4] = {};
    auto publish = [&](bool hi, int slot) {
        uint4* rowp = reinterpret_cast<uint4*>(p.s->rows) + slot * 144 + warp * 4 + t;
        stg128(rowp, nzw(hi ? U2[1][0] : U2[0][0]), nzw(hi ? U2[1][1] : U2[0][1]), nzw(hi ? U2[1][2] : U2[0][2]), nzw(hi ? U2[1][3] : U2[0][3]));
        stg128(rowp + 72, nzw(hi ? H[1][0] : H[0][0]), nzw(hi ? H[1][1] : H[0][1]), nzw(hi ? H[1][2] : H[0][2]), nzw(hi ? H[1][3] : H[0][3]));
    };
#define KTOK(k) (int)(((~(k) >> 5) & 0x7f0u) | (((k) >> 1) & 15u))
#define KLATE(k) (((k) & 0x1e0u) < 0xe0u)
#define KSLOT(k, s) (KLATE(k) ? 2 * NCTA + (s) : (int)(((k) >> 8) & 0xffu))
    const uint4* const rsrc = reinterpret_cast<const uint4*>(p.s->rows) + 36 * odd;
    auto gather = [&](uint32_t mine) {
        int it = 0;
        uint32_t mn;
        do {
            mn = 1;
#pragma unroll 1
            for (int r = 0; r < 9; r++) {
                const uint32_t k = __shfl_sync(0xffffffffu, mine, r < 8 ? 4 * r : lane);
                const int row = r < 8 ? r : g, c = r < 8 ? lane : 32 + t;
                asm volatile("cp.async.cg.shared.global [%0], [%1], 16;\n" ::"r"(sb + SM_XS + row * XS_PITCH + c * 16), "l"(rsrc + KSLOT(k, row) * 144 + c) : "memory");
            }
            asm volatile("cp.async.wait_all;\n" ::: "memory");
#pragma unroll 1
            for (int r = 0; r < 9; r++) mn = min(mn, min4(lds128(sb + SM_XS + (r < 8 ? r * XS_PITCH + lane * 16 : g * XS_PITCH + (32 + t) * 16))));
            if (++it > SPIN_LIMIT) TRAP();
        } while (__any_sync(0xffffffffu, mn == 0));
    };
    auto late_rows = [&](auto role) {
        if (decltype(role)::value == 1) {
            int it = 0;
            uint4 k[8];
            uint32_t bad;
            do {
                bad = 0;
#pragma unroll
                for (int i = 0; i < 8; i++) k[i] = ld_poll(reinterpret_cast<const uint4*>(p.s->key) + 32 * i + lane);
#pragma unroll
                for (int i = 0; i < 8; i++) bad = or3(bad, xor_or(k[i].x, k[i].y, par), xor_or(k[i].z, k[i].w, par));
                if (++it > SPIN_LIMIT) TRAP();
            } while (__any_sync(0xffffffffu, bad & 1u));
#pragma unroll 1
            for (int r = 0; r < 8; r++) {
                uint32_t c = 0;
#pragma unroll
                for (int i = 0; i < 8; i++) c = max(c, k[i].x);
                const uint32_t m = __reduce_max_sync(0xffffffffu, c);
#pragma unroll
                for (int i = 0; i < 8; i++) if (k[i].x == m) k[i] = make_uint4(k[i].y, k[i].z, k[i].w, 0u);
                if (lane == 0) sts32(s_key + r * 4, m);
            }
        }
        bar_sync(0, NWRK);
        const uint32_t kk = lds32(s_key + (lane & 7) * 4), ep = lds32(s_cnt + 4);
        const bool own = KLATE(kk) && (KTOK(kk) >> 4) == b;
        uint32_t todo = __ballot_sync(0xffffffffu, own) & 0xffu;
        if (decltype(role)::value == 0 && todo) {
#pragma unroll
            for (int hf = 0; hf < 2; hf++) {
                const uint4 h = lds128(sb + SM_U + hf * 9216 + tid * 16);
                const uint2 st = lds64(s_stat + (g + 8 * hf) * 8);
                H[hf][0] = h.x; H[hf][1] = h.y; H[hf][2] = h.z; H[hf][3] = h.w;
#pragma unroll
                for (int k = 0; k < 4; k++) U2[hf][k] = ln_apply(H[hf][k], STAT_M(st), STAT_H(st), STAT_L(st));
            }
#pragma unroll 1
            while (todo) {
                const int s = __ffs(todo) - 1, tk = KTOK(__shfl_sync(0xffffffffu, kk, s));
                todo &= todo - 1;
                if ((tk & 13) == TOK(g)) publish(tk & 2, 2 * NCTA + s);
            }
            __threadfence();
        }
        bar_sync(0, NWRK);
        if (decltype(role)::value == 1) {
            if (lane < NSEL && own) *reinterpret_cast<volatile unsigned*>(p.s->flag + lane) = ep + 1u;
            int it = 0;
            while (__any_sync(0xffffffffu, KLATE(kk) && ld_acquire32(p.s->flag + (lane & 7)) != ep + 1u)) { if (++it > SPIN_LIMIT) TRAP(); }
            gather(__shfl_sync(0xffffffffu, kk, g));
        }
        bar_sync(0, NWRK);
    };
    if (warp < 18) {
        const unsigned char* ys = reinterpret_cast<const unsigned char*>(p.s->y) + (b < 64 ? (par ^ 1u) * (NCTA * 18432u) : 0u) +
                                  ((P * DM + 32 * warp + 8 * (g >> 1) + (g & 1)) * 64 + odd * 32 + t * 8);
        mbar_wait(bar_v);
        const uint32_t xa = sb + SM_XT + warp * 64 + t * 16;
        const uint4 x0 = lds128(xa + TOK(g) * 1152), x1 = lds128(xa + (TOK(g) + 2) * 1152), dk = lds128(xa + 16 * 1152);
        uint4 wr = make_uint4(0u, 0u, 0u, 0u);
        if (g == 0) wr = lds128(xa + 17 * 1152);
        uint2 yv[4];
        const uint32_t Z[2][4] = {{x0.x, x0.y, x0.z, x0.w}, {x1.x, x1.y, x1.z, x1.w}}, D4[4] = {dk.x, dk.y, dk.z, dk.w};
#pragma unroll
        for (int hf = 0; hf < 2; hf++) {
            const uint2 st = lds64(s_stat + (g + 8 * hf) * 8);
#pragma unroll
            for (int k = 0; k < 4; k++) U2[hf][k] = hmul2_bf(ln_apply(Z[hf][k], STAT_M(st), STAT_H(st), STAT_L(st)), D4[k]);
        }
        const uint32_t la = pin(sb + SM_LNP + (g * 20 + warp) * 4);
        {
            const unsigned char* y1 = ys + (U2[0][0] & U2[1][2] & (warp >> 8));
#pragma unroll
            for (int k = 0; k < 4; k++) yv[k] = ld_poll64(y1 + k * 128);
        }
        int it = 0;
        float d[2][4];
        while (true) {
            const uint32_t mn = min3(min3(yv[0].x, yv[0].y, yv[1].x), min3(yv[1].y, yv[2].x, yv[2].y), min(yv[3].x, yv[3].y));
#pragma unroll
            for (int k = 0; k < 4; k++) {
                H[0][k] = hadd2_bf(Z[0][k], hadd2_bf(movm(yv[k].x), U2[0][k]));
                H[1][k] = hadd2_bf(Z[1][k], hadd2_bf(movm(yv[k].y), U2[1][k]));
            }
            ln_partial(H, d);
            if (!__any_sync(0xffffffffu, mn == 0)) break;
            if (++it > SPIN_LIMIT) TRAP();
#pragma unroll
            for (int k = 0; k < 4; k++) yv[k] = ld_poll64(ys + k * 128);
        }
        STAMP(12);
        {
            const float s0 = (g & 1) ? d[0][3] : d[0][2], s1 = (g & 1) ? d[1][3] : d[1][2];
            const float q0 = (g & 1) ? d[0][1] : d[0][0], q1 = (g & 1) ? d[1][1] : d[1][0];
            asm volatile("{\n.reg .pred p;\nsetp.eq.u32 p, %5, %6;\n@p st.shared.f32 [%0], %1;\n@p st.shared.f32 [%0 + 640], %2;\n@p st.shared.f32 [%0 + 1280], %3;\n@p st.shared.f32 [%0 + 1920], %4;\n}\n"
                         ::"r"(la), "f"(s0), "f"(s1), "f"(q0), "f"(q1), "r"(t), "r"(g >> 1) : "memory");
        }
        bar_arrive(6, NWRK);
        STAMP(13);
        bar_sync(7, 608);
        STAMP(14);
#pragma unroll
        for (int hf = 0; hf < 2; hf++) {
            const uint2 st = lds64(s_stat + (g + 8 * hf) * 8);
#pragma unroll
            for (int k = 0; k < 4; k++) U2[hf][k] = ln_apply(H[hf][k], STAT_M(st), STAT_H(st), STAT_L(st));
        }
        {
            float cs[4] = {0.f, 0.f, 0.f, 0.f};
            mma_bf16(cs, U2[0][0], U2[1][0], U2[0][1], U2[1][1], wr.x, wr.y);
            mma_bf16(cs, U2[0][2], U2[1][2], U2[0][3], U2[1][3], wr.z, wr.w);
            if (t == 0) { stsf(la + 32 * 80, cs[0]); stsf(la + 40 * 80, cs[2]); }
            bar_arrive(8, 608);
        }
        FIX((uint32_t)warp >> 8);
        uint32_t O[2][4];
#pragma unroll
        for (int hf = 0; hf < 2; hf++)
#pragma unroll
            for (int k = 0; k < 4; k++) { O[hf][k] = hadd2_bf(H[hf][k], U2[hf][k]); H[hf][k] = nzw(H[hf][k]); U2[hf][k] = nzw(U2[hf][k]); }
        unsigned char* rowp = reinterpret_cast<unsigned char*>(p.s->rows) + ((254 - 2 * b) * 2304 + warp * 64 + t * 16);
        FIX(and3(and3(and3(H[0][0], H[0][1], H[0][2]), and3(H[0][3], H[1][0], H[1][1]), and3(H[1][2], H[1][3], U2[0][0])),
                 and3(and3(U2[0][1], U2[0][2], U2[0][3]), and3(U2[1][0], U2[1][1], U2[1][2]), U2[1][3]), (uint32_t)reinterpret_cast<uint64_t>(rowp)));
        bar_sync(9, 608);
        {
            const uint2 best = lds64(s_rank);
#pragma unroll
            for (int hf = 0; hf < 2; hf++) {
                const uint32_t me = 2 * TOK(g) + 4 * hf;
                unsigned char* d = rowp + (best.x == me ? 2304 : 0);
                if (best.x == me || best.y == me) {
                    stg128(d, U2[hf][0], U2[hf][1], U2[hf][2], U2[hf][3]);
                    stg128(d + 1152, H[hf][0], H[hf][1], H[hf][2], H[hf][3]);
                }
            }
        }
        FIX((uint32_t)warp >> 9);
#pragma unroll
        for (int hf = 0; hf < 2; hf++) {
            sts128(sb + SM_OUT + (TOK(g) + 2 * hf) * (DM * 2) + warp * 64 + t * 16, O[hf][0], O[hf][1], O[hf][2], O[hf][3]);
            sts128(sb + SM_U + hf * 9216 + tid * 16, H[hf][0], H[hf][1], H[hf][2], H[hf][3]);
        }
        STAMP(15);
        const int mi = lane >> 3, rr = lane & 7;
        const bool gate = warp < 12 && (warp & 3) != 2;
        const int fj = gate ? 3 * (warp >> 2) + min(warp & 3, 2) : (warp < 12 ? warp >> 2 : warp - 9);
        if (gate) {
            uint32_t W[18][4];
            mbar_wait(bar_w);
            const uint32_t aad = fj < 8 ? sb + SM_WG + (mi & 1) * SM_WU + (rr + 8 * (mi >> 1)) * 128 + (fj ^ rr) * 16 : sb + SM_WR + (mi & 1) * 4608 + (rr + 8 * (mi >> 1)) * 16;
            const uint32_t ast = fj < 8 ? 2048 : 256;
            const uint32_t bad = pin(sb + SM_XS + rr * XS_PITCH + mi * 16);
            bool rare = warp >> 8;
#pragma unroll 1
            do {
                if (rare) late_rows(IC<0>());
#pragma unroll
                for (int k = 0; k < 18; k++) ldsm_x4_t(W[k][0], W[k][1], W[k][2], W[k][3], aad + k * ast);
                if (rare) break;
                fence_async();
                STAMP2(17);
                rare = bar_or(11, NWRK, false);
            } while (rare);
            STAMP2(19);
            float c4[2][4] = {};
#pragma unroll
            for (int k = 0; k < 18; k += 2) {
                uint32_t b0, b1, b2, b3;
                ldsm_x4(b0, b1, b2, b3, bad + k * 32);
                mma_bf16(c4[0], W[k][0], W[k][1], W[k][2], W[k][3], b0, b1);
                mma_bf16(c4[1], W[k + 1][0], W[k + 1][1], W[k + 1][2], W[k + 1][3], b2, b3);
            }
            const uint32_t ex = sb + SM_EX + (32 * fj + lane) * 16;
            const float e0 = c4[0][0] + c4[1][0], e1 = c4[0][1] + c4[1][1], e2 = c4[0][2] + c4[1][2], e3 = c4[0][3] + c4[1][3];
            asm volatile("st.async.shared::cluster.mbarrier::complete_tx::bytes.v4.f32 [%0], {%1,%2,%3,%4}, [%5];\n"
                         ::"r"(ex ^ 0x1000000u), "f"(e0), "f"(e1), "f"(e2), "f"(e3), "r"(bar_g ^ 0x1000000u) : "memory");
            STAMP2(20);
            mbar_wait(bar_g);
            const uint4 o = lds128(ex);
            const uint32_t G = pack_bf16(e0 + __uint_as_float(o.x), e1 + __uint_as_float(o.y)), U = pack_bf16(e2 + __uint_as_float(o.z), e3 + __uint_as_float(o.w));
            sts32(sb + SM_GU + (32 * fj + lane) * 4, hmul2_bf(pack_bf16(bf_lo(G) * sigmoid_f(bf_lo(G)), bf_hi(G) * sigmoid_f(bf_hi(G))), U));
            bar_arrive(13, NWRK);
        } else {
            uint32_t W[2][18];
            auto load_wd = [&]() {
                mbar_wait(bar_d);
                const uint32_t base = sb + SM_WD + (4 * fj + (mi & 1)) * 16 + rr * WD_PITCH;
#pragma unroll
                for (int j = 0; j < 2; j++) {
#pragma unroll
                    for (int k = 0; k < 4; k++) ldsm_x4_t(W[j][4 * k], W[j][4 * k + 1], W[j][4 * k + 2], W[j][4 * k + 3], base + j * 32 + (k * 16 + 8 * (mi >> 1)) * WD_PITCH);
                    ldsm_x2_t(W[j][16], W[j][17], base + j * 32 + 64 * WD_PITCH);
                }
            };
            const uint32_t po = pin((((8 * (18 * odd + 2 * fj) + g) * 64 + P) * 4 + t) * 8);
            fence_async();
            STAMP2(17);
            const bool first = (warp & 3) != 2;
#pragma unroll 1
            for (int i = 0; i < 2; i++) {
                if (i == (first ? 1 : 0)) {
                    if (bar_or(11, NWRK, false)) late_rows(IC<0>());
                    if (!first) delay(DDLY);
                } else load_wd();
            }
            bar_sync(13, NWRK);
            STAMP2(21);
            uint32_t gb[9];
            ldsm_x4_t(gb[0], gb[1], gb[2], gb[3], sb + SM_GU + lane * 16);
            ldsm_x4_t(gb[4], gb[5], gb[6], gb[7], sb + SM_GU + 512 + lane * 16);
            ldsm_x1_t(gb[8], sb + SM_GU + 1024 + lane * 16);
            float c4[2][4] = {}, d4[2][4] = {};
#pragma unroll
            for (int k = 0; k < 4; k += 2)
#pragma unroll
                for (int j = 0; j < 2; j++) {
                    mma_bf16(c4[j], W[j][4 * k], W[j][4 * k + 1], W[j][4 * k + 2], W[j][4 * k + 3], gb[2 * k], gb[2 * k + 1]);
                    mma_bf16(d4[j], W[j][4 * k + 4], W[j][4 * k + 5], W[j][4 * k + 6], W[j][4 * k + 7], gb[2 * k + 2], gb[2 * k + 3]);
                }
#pragma unroll
            for (int j = 0; j < 2; j++) mma_bf16_k8(c4[j], W[j][16], W[j][17], gb[8]);
#pragma unroll
            for (int j = 0; j < 2; j++)
                stg64(reinterpret_cast<unsigned char*>(p.s->part) + po + j * 16384, nzw(pack_bf16(c4[j][0] + d4[j][0], c4[j][1] + d4[j][1])), nzw(pack_bf16(c4[j][2] + d4[j][2], c4[j][3] + d4[j][3])));
        }
        STAMP2(22);
    } else if (warp == 18) {
        const uint4* const ksrc = reinterpret_cast<const uint4*>(p.s->key3) + pin(2 * lane);
        const int row = (g >> 1) + 4 * (g & 1);
        const uint32_t ro = pin(640 * odd + t * 16), xd = pin(sb + SM_XS + row * XS_PITCH + t * 16 + (odd ? 0 : 512));
        const uint32_t xe = pin(sb + SM_XS + (g >> 1) * XS_PITCH + (lane & 7) * 16 + 64 * odd);
        const uint32_t sa = pin(sb + SM_LNP + lane * 80);
        const uint32_t klo = pin((uint32_t)(127 - b) << 9 | (uint32_t)(15 - ROWTOK(lane & 15)) << 1 | par), ra = pin(sb + SM_LNP + (32 + (lane & 15)) * 80);
        uint4* const kdst = reinterpret_cast<uint4*>(p.s->key3) + pin((lane >> 1) * 2 * NCTA + 2 * b + (lane & 1));
        FIX(ra);
        bar_sync(6, NWRK);
        {
            float mb, rc;
            ln_finish(sum18(sa), lane, mb, rc);
            if (lane < 16) stat_store(s_stat + lane * 8, mb, rc, 0u);
        }
        bar_arrive(7, 608);
        bar_sync(8, 608);
        uint32_t t0;
        {
            const uint32_t bits = __float_as_uint(rbf(sum18(ra)));
            const uint32_t me = ((bits ^ ((uint32_t)((int)bits >> 31) | 0x80000000u)) & 0xffff0000u) | klo;
            const uint32_t k0 = __reduce_max_sync(0xffffffffu, me), k1 = __reduce_max_sync(0xffffffffu, me == k0 ? 0u : me);
            const uint32_t k2 = __reduce_max_sync(0xffffffffu, me >= k1 ? 0u : me);
            if (lane < 2) stg128(kdst, k0 ^ 0x11eu, k1 ^ 0xfeu, k2 ^ 0xdeu, par);
            asm volatile("mov.u32 %0, %%clock;" : "=r"(t0) :: "memory");
            STAMPW(23);
            if (lane == 0) sts64(s_rank, ~k0 & 30u, ~k1 & 30u);
            bar_arrive(9, 608);
            sts32(s_k16 + (lane & 15) * 4, me);
            __syncwarp();
            const uint4 v = lds128(s_k16 + (lane & 16) * 2), w = lds128(s_k16 + (lane & 16) * 2 + 16);
            int rank = ((v.x > me) + (v.y > me)) + ((v.z > me) + (v.w > me)) + (((w.x > me) + (w.y > me)) + ((w.z > me) + (w.w > me)));
            rank += __shfl_xor_sync(0xffffffffu, rank, 16);
            if (lane < 16 && rank < 8) p.s->key[8 * b + rank] = (me ^ 0x1eu) | ((8 - rank) << 5);
        }
        uint4 kq[4];
        uint32_t u[4], mine = 0, m;
        int it = 0;
        { uint32_t now; do { asm volatile("mov.u32 %0, %%clock;" : "=r"(now) :: "memory"); } while (now - t0 < KDLY); }
        do {
#pragma unroll
            for (int i = 0; i < 4; i++) kq[i] = ld_poll(ksrc + 64 * i);
            if (++it > SPIN_LIMIT) TRAP();
            uint32_t S[2][4];
#pragma unroll
            for (int i = 0; i < 2; i++) {
                const uint4 &c = kq[2 * i], &d = kq[2 * i + 1];
                const uint32_t m1 = min(c.x, d.x), m2 = max(c.y, d.y);
                S[i][0] = max(c.x, d.x); S[i][1] = max(m1, m2); S[i][2] = min(m1, m2); S[i][3] = min(c.y, d.y);
            }
            const uint32_t a0 = max(S[0][0], S[1][3]), a1 = max(S[0][1], S[1][2]), a2 = max(S[0][2], S[1][1]), a3 = max(S[0][3], S[1][0]);
            const uint32_t b0 = max(a0, a2), b2 = min(a0, a2), b1 = max(a1, a3), b3 = min(a1, a3);
            u[0] = max(b0, b1); u[1] = min(b0, b1); u[2] = max(b2, b3); u[3] = min(b2, b3);
            const uint32_t bad = or3(or3(xor_or(kq[0].x, kq[0].y, par), xor_or(kq[0].z, kq[1].x, par), xor_or(kq[1].y, kq[1].z, par)),
                                     xor_or(kq[2].x, kq[2].y, par), xor_or(kq[2].z, kq[3].x, par)) | xor_or(kq[3].y, kq[3].z, par);
            m = __reduce_max_sync(0xffffffffu, u[0] | (uint32_t)((int)(bad << 31) >> 31));
        } while (m == 0xffffffffu);
        STAMPW(16);
#pragma unroll
        for (int r = 0; r < 8; r++) {
            if (r) m = __reduce_max_sync(0xffffffffu, u[0]);
            if (u[0] == m) { u[0] = u[1]; u[1] = u[2]; u[2] = u[3]; u[3] = 0; }
            if (row == r) mine = m;
        }
        uint4 v[9];
        const uint32_t o0 = __byte_perm(mine, 0, 0x4441) * 2304u, o1 = __shfl_xor_sync(0xffffffffu, o0, 4);
        const unsigned char* const rA = reinterpret_cast<const unsigned char*>(p.s->rows) + (((g & 1) ? o1 : o0) + ro + (g & 1) * 64);
        const unsigned char* const rb = reinterpret_cast<const unsigned char*>(p.s->rows) + (((g & 1) ? o0 : o1) + ro + (g & 1) * 64);
        const unsigned char* const rc = reinterpret_cast<const unsigned char*>(p.s->rows) + (o0 + ro + (odd ? -64 : 512));
#pragma unroll
        for (int i = 0; i < 4; i++) { v[i] = ld_poll(rA + i * 128); v[4 + i] = ld_poll(rb + i * 128); }
        v[8] = ld_poll(rc);
        const bool again = u[0] == 0 || max(max(kq[0].z, kq[1].z), max(kq[2].z, kq[3].z)) > m;
        if (t == 0) sts32(s_key + row * 4, mine);
#pragma unroll
        for (int i = 0; i < 9; i++) sts128(i < 8 ? xe + (i >> 2) * 4 * XS_PITCH + (i & 3) * 128 : xd, v[i].x, v[i].y, v[i].z, v[i].w);
        uint32_t mn, m3[3];
        m3[0] = m3[1] = m3[2] = 1u;
#pragma unroll
        for (int i = 0; i < 9; i++) m3[i % 3] = min3(min3(m3[i % 3], v[i].x, v[i].y), v[i].z, v[i].w);
        mn = min3(m3[0], m3[1], m3[2]);
        STAMPW(18);
        if (bar_or(11, NWRK, again || mn == 0)) late_rows(IC<1>());
    } else {
        bar_sync(6, NWRK);
        WPOINT(16, true);
        if (WANY(17) || WANY(18)) delay(WDLY);
        WPOINT(17, true);
        if (WANY(18)) delay(WDLY);
        WPOINT(18, true);
        if (bar_or(11, NWRK, false)) late_rows(IC<2>());
        const int tk = KTOK(lds32(s_key + (lane & 7) * 4));
        const uint32_t sel = __reduce_or_sync(0xffffffffu, (tk >> 4) == b ? 1u << (tk & 15) : 0u);
        if (sel ? lane < 16 && !((sel >> lane) & 1u) : lane == 0) bulk_s2g(p.out + (size_t)(16 * b + lane) * DM, sb + SM_OUT + lane * (DM * 2), sel ? DM * 2 : 16 * DM * 2);
        __syncwarp();
    }
    if (warp == 8 || warp >= 18) {
        const int grp = 3 * b + (warp == 8 ? 0 : warp - 17), fsl = 2 * (g & 3) + (t & 1), fc = 16 * (grp >> 3) + (grp & 7) + 8 * (t >> 1);
        const uint32_t fk = lds32(s_key + fsl * 4);
        float hv = 0.f, u2 = 0.f;
        int it = 0;
        if (b < 96) {
            const uint32_t* const fsrc = p.s->rows + KSLOT(fk, fsl) * DM + (fc >> 1);
            uint32_t hw, uw;
            do { hw = ld_poll32(fsrc + 288); uw = ld_poll32(fsrc); if (++it > SPIN_LIMIT) TRAP(); } while (!hw || !uw);
            hv = (fc & 1) ? bf_hi(hw) : bf_lo(hw); u2 = (fc & 1) ? bf_hi(uw) : bf_lo(uw);
        }
        const float rs = rbf(sigmoid_f(__uint_as_float((fk ^ ((uint32_t)((int)~fk >> 31) | 0x80000000u)) & 0xffff0000u)));
        bf16* dst = p.out + (KTOK(fk) * DM + fc);
        const uint2* src = reinterpret_cast<const uint2*>(p.s->part) + (grp * 256 + 8 * t + g);
        FIX((uint32_t)reinterpret_cast<uint64_t>(dst) & (uint32_t)reinterpret_cast<uint64_t>(src) & (uint32_t)((reinterpret_cast<uint64_t>(dst) & reinterpret_cast<uint64_t>(src)) >> 32) & __float_as_uint(rs));
        if (warp > 17) bar_sync(13, NWRK);
        if (b < 96) {
            delay(warp > 17 ? FDLY : FDLY2);
            const uint32_t sel = (g & 1) ? 0x3f800000u : 0x3f80u;
            float y;
            uint32_t ok;
            do {
                uint2 a[8];
#pragma unroll
                for (int i = 0; i < 8; i++) a[i] = ld_poll64(src + 32 * i);
                if (++it > SPIN_LIMIT) TRAP();
                float c[2][4] = {};
#pragma unroll
                for (int i = 0; i < 8; i += 2) mma_bf16(c[(i >> 1) & 1], a[i].x, a[i].y, a[i + 1].x, a[i + 1].y, sel, sel);
                ok = min3(min3(min3(a[0].x, a[0].y, a[1].x), min3(a[1].y, a[2].x, a[2].y), min3(a[3].x, a[3].y, a[4].x)), min3(min3(a[4].y, a[5].x, a[5].y), min3(a[6].x, a[6].y, a[7].x), a[7].y), 1u);
                ok = __all_sync(0xffffffffu, ok);
                y = fsel(fsel(c[0][3] + c[1][3], c[0][2] + c[1][2], t & 1), fsel(c[0][1] + c[1][1], c[0][0] + c[1][0], t & 1), t & 2);
            } while (!ok);
            STAMP2(24);
            y += __shfl_xor_sync(0xffffffffu, y, 16);
            *dst = __float2bfloat16_rn(hv + rbf(u2 + rbf(rbf(y) * rs)));
        }
    }
    if (warp == 19) asm volatile("cp.async.bulk.wait_group.read 0;\n" ::: "memory");
    if (b == 0 && tid < 8) *reinterpret_cast<volatile unsigned*>(p.s->hint + tid * 32 + 1) = lds32(s_cnt + 4) + 1u;
    STAMP(25);
    }
}

typedef CUresult (*PFN_tmEncode)(CUtensorMap*, CUtensorMapDataType, cuuint32_t, void*, const cuuint64_t*, const cuuint64_t*, const cuuint32_t*,
                                 const cuuint32_t*, CUtensorMapInterleave, CUtensorMapSwizzle, CUtensorMapL2promotion, CUtensorMapFloatOOBfill);

extern "C" void kernel_launch(void* const* d_in, const int* in_sizes, int n_in, void* d_out, int out_size) {
    Params p;
    p.x = (const bf16*)d_in[0];
    p.lar = (const bf16*)d_in[1];
    p.aim = (const bf16*)d_in[2];
    p.cre = (const bf16*)d_in[3];
    p.cim = (const bf16*)d_in[4];
    p.ldt = (const bf16*)d_in[5];
    p.dsk = (const bf16*)d_in[6];
    p.wr = (const bf16*)d_in[8];
    p.out = (bf16*)d_out;
    static PFN_tmEncode enc = nullptr;
    static void* scratch = nullptr;
    if (!enc) {
        cudaFuncSetAttribute(fused_kernel, cudaFuncAttributeMaxDynamicSharedMemorySize, SMEM_TOTAL);
        void* fn = nullptr;
        cudaDriverEntryPointQueryResult qr;
        cudaGetDriverEntryPoint("cuTensorMapEncodeTiled", &fn, cudaEnableDefault, &qr);
        enc = (PFN_tmEncode)fn;
        cudaGetSymbolAddress(&scratch, g_scratch);
    }
    p.s = (Scratch*)scratch;
    Maps tm;
    const cuuint64_t dims[2] = {FF, DM}, strides[1] = {FF * 2};
    const cuuint32_t box[2] = {64, 48}, rbox[2] = {8, 144}, es[2] = {1, 1};
    for (int i = 0; i < 2; i++) {
        enc(&tm.w[i], CU_TENSOR_MAP_DATA_TYPE_BFLOAT16, 2, d_in[9 + i], dims, strides, box, es, CU_TENSOR_MAP_INTERLEAVE_NONE, CU_TENSOR_MAP_SWIZZLE_128B,
            CU_TENSOR_MAP_L2_PROMOTION_NONE, CU_TENSOR_MAP_FLOAT_OOB_FILL_NONE);
        enc(&tm.r[i], CU_TENSOR_MAP_DATA_TYPE_BFLOAT16, 2, d_in[9 + i], dims, strides, rbox, es, CU_TENSOR_MAP_INTERLEAVE_NONE, CU_TENSOR_MAP_SWIZZLE_NONE,
            CU_TENSOR_MAP_L2_PROMOTION_NONE, CU_TENSOR_MAP_FLOAT_OOB_FILL_NONE);
    }
    const cuuint64_t ddims[2] = {DM / 2, FF}, dstrides[1] = {DM * 2};
    const cuuint32_t dbox[2] = {WD_PITCH / 4, 8};
    enc(&tm.d, CU_TENSOR_MAP_DATA_TYPE_UINT32, 2, d_in[11], ddims, dstrides, dbox, es, CU_TENSOR_MAP_INTERLEAVE_NONE, CU_TENSOR_MAP_SWIZZLE_NONE,
        CU_TENSOR_MAP_L2_PROMOTION_L2_128B, CU_TENSOR_MAP_FLOAT_OOB_FILL_NONE);
    const cuuint64_t xdims[4] = {DM, 128, 4, 4}, xstrides[3] = {DM * 8, DM * 2, DM * 1024};
    const cuuint32_t xbox[4] = {8, 128, 4, 2}, xes[4] = {1, 1, 1, 1};
    enc(&tm.x, CU_TENSOR_MAP_DATA_TYPE_BFLOAT16, 4, d_in[0], xdims, xstrides, xbox, xes, CU_TENSOR_MAP_INTERLEAVE_NONE, CU_TENSOR_MAP_SWIZZLE_NONE,
        CU_TENSOR_MAP_L2_PROMOTION_NONE, CU_TENSOR_MAP_FLOAT_OOB_FILL_NONE);
    fused_kernel<<<NCTA, NTHR, SMEM_TOTAL>>>(p, tm);
}
```

```cpp
#include <cuda_runtime.h>
#include <cuda.h>
#include <cuda_fp16.h>
#include <cuda_bf16.h>
#include <stdint.h>

#define LSEQ 2048
#define DM 576
#define NST 128
#define FF 4608
#define NSEL 8
#define NCTA 128
#define NTHR 640
#define NWRK 640

typedef __nv_bfloat16 bf16;

#define SM_WG 0
#define SM_WU 36864
#define SM_WR 73728
#define SM_XC (82944 - 32768)
#define SM_WD 82944
#define WD_PITCH 592
#define SM_Z2 (SM_WD + 10240)
#define SM_XT (SM_PL - 18 * 1152)
#define SM_PL (SM_WD + 46080)
#define PL_HALF 1344
#define PLW_B 2624
#define PL_B (4 * PLW_B)
#define SM_U (SM_PL + 5 * PL_B)
#define UPAD 20
#define ULO_B ((UPAD + 128) * 16)
#define USLOT_B (2 * ULO_B)
#define SM_KW (SM_U + 5 * USLOT_B)
#define KW_B 3712
#define KW_PL 1216
#define KW_P 2400
#define KW_H 3440
#define SM_MISC (SM_KW + 5 * KW_B)
#define SM_LC (SM_MISC + 416)
#define SM_LNP (SM_LC + 768)
#define SM_RX (SM_LNP + 3840)
#define SMEM_TOTAL (SM_RX + 3088)
#define TBW PLW_B
#define SM_OUT SM_PL
#define SM_XS (SM_PL + 18432)
#define XS_PITCH 592
#define SM_GU (SM_PL + 23296)
#define SM_EX (SM_PL + 24576)

struct __align__(128) Scratch {
    unsigned hint[8 * 32];
    unsigned flag[32];
    uint32_t key3[NCTA * 8];
    uint32_t key[NCTA * 8];
    uint32_t stat[LSEQ];
    uint32_t uT[64 * (LSEQ / 2)];
    uint32_t y[(NCTA + 96) * DM * 8];
    uint32_t part[288 * 64 * 8];
    uint32_t rows[(2 * NCTA + NSEL) * DM];
};
__device__ Scratch g_scratch;
#define STAMP(i)
#define STAMPX(i)
#define STAMPY(i)

__device__ __forceinline__ float rbf(float x) {
    uint32_t r;
    asm("cvt.rn.bf16x2.f32 %0, %1, %2;\n" : "=r"(r) : "f"(x), "f"(0.f));
    return __uint_as_float(r);
}
__device__ __forceinline__ uint32_t pack_bf16(float lo, float hi) {
    uint32_t r;
    asm("cvt.rn.bf16x2.f32 %0, %1, %2;\n" : "=r"(r) : "f"(hi), "f"(lo));
    return r;
}
__device__ __forceinline__ uint32_t pack_f16(float lo, float hi) {
    uint32_t r;
    asm("cvt.rn.f16x2.f32 %0, %1, %2;\n" : "=r"(r) : "f"(hi), "f"(lo));
    return r;
}
__device__ __forceinline__ float bf_lo(uint32_t w) { return __uint_as_float(w << 16); }
__device__ __forceinline__ float bf_hi(uint32_t w) { return __uint_as_float(w & 0xffff0000u); }
__device__ __forceinline__ uint32_t hadd2_bf(uint32_t a, uint32_t b) {
    __nv_bfloat162 r = __hadd2_rn(*reinterpret_cast<__nv_bfloat162*>(&a), *reinterpret_cast<__nv_bfloat162*>(&b));
    return *reinterpret_cast<uint32_t*>(&r);
}
__device__ __forceinline__ uint32_t hsub2_bf(uint32_t a, uint32_t b) {
    __nv_bfloat162 r = __hsub2_rn(*reinterpret_cast<__nv_bfloat162*>(&a), *reinterpret_cast<__nv_bfloat162*>(&b));
    return *reinterpret_cast<uint32_t*>(&r);
}
__device__ __forceinline__ uint32_t hmul2_bf(uint32_t a, uint32_t b) {
    __nv_bfloat162 r = __hmul2_rn(*reinterpret_cast<__nv_bfloat162*>(&a), *reinterpret_cast<__nv_bfloat162*>(&b));
    return *reinterpret_cast<uint32_t*>(&r);
}
__device__ __forceinline__ uint32_t hfma2_bf(uint32_t a, uint32_t b, uint32_t c) { uint32_t r; asm("fma.rn.bf16x2 %0, %1, %2, %3;\n" : "=r"(r) : "r"(a), "r"(b), "r"(c)); return r; }
__device__ __forceinline__ uint32_t hmul2(uint32_t a, uint32_t b) { uint32_t r; asm("mul.rn.f16x2 %0, %1, %2;\n" : "=r"(r) : "r"(a), "r"(b)); return r; }
__device__ __forceinline__ uint32_t hadd2(uint32_t a, uint32_t b) { uint32_t r; asm("add.rn.f16x2 %0, %1, %2;\n" : "=r"(r) : "r"(a), "r"(b)); return r; }
__device__ __forceinline__ uint32_t hfma2(uint32_t a, uint32_t b, uint32_t c) { uint32_t r; asm("fma.rn.f16x2 %0, %1, %2, %3;\n" : "=r"(r) : "r"(a), "r"(b), "r"(c)); return r; }
__device__ __forceinline__ uint32_t hfms2(uint32_t a, uint32_t b, uint32_t c) {
    uint32_t r;
    asm("{\n.reg .b32 n;\nneg.f16x2 n, %2;\nfma.rn.f16x2 %0, %1, n, %3;\n}\n" : "=r"(r) : "r"(a), "r"(b), "r"(c));
    return r;
}
__device__ __forceinline__ uint32_t nzw(uint32_t w) { uint32_t r; asm("max.u32 %0, %1, 1;\n" : "=r"(r) : "r"(w)); return r; }
__device__ __forceinline__ uint32_t smem_u32(const void* p) { return (uint32_t)__cvta_generic_to_shared(p); }
__device__ __forceinline__ uint32_t lds32(uint32_t addr) {
    uint32_t v;
    asm volatile("ld.shared.u32 %0, [%1];\n" : "=r"(v) : "r"(addr) : "memory");
    return v;
}
__device__ __forceinline__ uint32_t lds16(uint32_t addr) {
    unsigned short v;
    asm volatile("ld.shared.u16 %0, [%1];\n" : "=h"(v) : "r"(addr) : "memory");
    return v;
}
__device__ __forceinline__ uint2 lds64(uint32_t addr) {
    uint2 v;
    asm volatile("ld.shared.v2.u32 {%0,%1}, [%2];\n" : "=r"(v.x), "=r"(v.y) : "r"(addr) : "memory");
    return v;
}
__device__ __forceinline__ uint4 lds128(uint32_t addr) {
    uint4 v;
    asm volatile("ld.shared.v4.u32 {%0,%1,%2,%3}, [%4];\n" : "=r"(v.x), "=r"(v.y), "=r"(v.z), "=r"(v.w) : "r"(addr) : "memory");
    return v;
}
__device__ __forceinline__ void sts32(uint32_t addr, uint32_t v) { asm volatile("st.shared.u32 [%0], %1;\n" ::"r"(addr), "r"(v) : "memory"); }
__device__ __forceinline__ void sts16(uint32_t addr, uint32_t v) { asm volatile("st.shared.u16 [%0], %1;\n" ::"r"(addr), "h"((unsigned short)v) : "memory"); }
__device__ __forceinline__ void stsf(uint32_t addr, float v) { sts32(addr, __float_as_uint(v)); }
__device__ __forceinline__ void sts64(uint32_t addr, uint32_t a, uint32_t b) { asm volatile("st.shared.v2.u32 [%0], {%1,%2};\n" ::"r"(addr), "r"(a), "r"(b) : "memory"); }
__device__ __forceinline__ void sts128(uint32_t addr, uint32_t a, uint32_t b, uint32_t c, uint32_t d) {
    asm volatile("st.shared.v4.u32 [%0], {%1,%2,%3,%4};\n" ::"r"(addr), "r"(a), "r"(b), "r"(c), "r"(d) : "memory");
}
__device__ __forceinline__ void ldsm_x4(uint32_t& r0, uint32_t& r1, uint32_t& r2, uint32_t& r3, uint32_t addr) {
    asm volatile("ldmatrix.sync.aligned.m8n8.x4.shared.b16 {%0,%1,%2,%3}, [%4];\n"
                 : "=r"(r0), "=r"(r1), "=r"(r2), "=r"(r3) : "r"(addr) : "memory");
}
__device__ __forceinline__ void ldsm_x4_t(uint32_t& r0, uint32_t& r1, uint32_t& r2, uint32_t& r3, uint32_t addr) {
    asm volatile("ldmatrix.sync.aligned.m8n8.x4.trans.shared.b16 {%0,%1,%2,%3}, [%4];\n"
                 : "=r"(r0), "=r"(r1), "=r"(r2), "=r"(r3) : "r"(addr) : "memory");
}
__device__ __forceinline__ void ldsm_x2_t(uint32_t& r0, uint32_t& r1, uint32_t addr) {
    asm volatile("ldmatrix.sync.aligned.m8n8.x2.trans.shared.b16 {%0,%1}, [%2];\n" : "=r"(r0), "=r"(r1) : "r"(addr) : "memory");
}
__device__ __forceinline__ void ldsm_x1_t(uint32_t& r0, uint32_t addr) {
    asm volatile("ldmatrix.sync.aligned.m8n8.x1.trans.shared.b16 {%0}, [%1];\n" : "=r"(r0) : "r"(addr) : "memory");
}
__device__ __forceinline__ void stsm_x4(uint32_t addr, uint32_t r0, uint32_t r1, uint32_t r2, uint32_t r3) {
    asm volatile("stmatrix.sync.aligned.m8n8.x4.shared.b16 [%0], {%1,%2,%3,%4};\n" ::"r"(addr), "r"(r0), "r"(r1), "r"(r2), "r"(r3) : "memory");
}
__device__ __forceinline__ void stsm_x4_t(uint32_t addr, uint32_t r0, uint32_t r1, uint32_t r2, uint32_t r3) {
    asm volatile("stmatrix.sync.aligned.m8n8.x4.trans.shared.b16 [%0], {%1,%2,%3,%4};\n" ::"r"(addr), "r"(r0), "r"(r1), "r"(r2), "r"(r3) : "memory");
}
__device__ __forceinline__ uint32_t movm(uint32_t a) {
    uint32_t d;
    asm volatile("movmatrix.sync.aligned.m8n8.trans.b16 %0, %1;\n" : "=r"(d) : "r"(a));
    return d;
}
__device__ __forceinline__ void mma_f16(float (&c)[4], uint32_t a0, uint32_t a1, uint32_t a2, uint32_t a3, uint32_t b0, uint32_t b1) {
    asm volatile(
        "mma.sync.aligned.m16n8k16.row.col.f32.f16.f16.f32 {%0,%1,%2,%3}, {%4,%5,%6,%7}, {%8,%9}, {%0,%1,%2,%3};\n"
        : "+f"(c[0]), "+f"(c[1]), "+f"(c[2]), "+f"(c[3])
        : "r"(a0), "r"(a1), "r"(a2), "r"(a3), "r"(b0), "r"(b1));
}
__device__ __forceinline__ void mma_bf16(float (&c)[4], uint32_t a0, uint32_t a1, uint32_t a2, uint32_t a3, uint32_t b0, uint32_t b1) {
    asm volatile(
        "mma.sync.aligned.m16n8k16.row.col.f32.bf16.bf16.f32 {%0,%1,%2,%3}, {%4,%5,%6,%7}, {%8,%9}, {%0,%1,%2,%3};\n"
        : "+f"(c[0]), "+f"(c[1]), "+f"(c[2]), "+f"(c[3])
        : "r"(a0), "r"(a1), "r"(a2), "r"(a3), "r"(b0), "r"(b1));
}
__device__ __forceinline__ void mma_bf16_k8(float (&c)[4], uint32_t a0, uint32_t a1, uint32_t b0) {
    asm volatile("mma.sync.aligned.m16n8k8.row.col.f32.bf16.bf16.f32 {%0,%1,%2,%3}, {%4,%5}, {%6}, {%0,%1,%2,%3};\n"
                 : "+f"(c[0]), "+f"(c[1]), "+f"(c[2]), "+f"(c[3]) : "r"(a0), "r"(a1), "r"(b0));
}
__device__ __forceinline__ void bar_sync(int id, int n) { asm volatile("bar.sync %0, %1;\n" ::"r"(id), "r"(n) : "memory"); }
__device__ __forceinline__ void bar_arrive(int id, int n) { asm volatile("bar.arrive %0, %1;\n" ::"r"(id), "r"(n) : "memory"); }
__device__ __forceinline__ bool bar_or(int id, int n, bool v) {
    uint32_t r;
    asm volatile("{\n.reg .pred p, q;\nsetp.ne.u32 p, %3, 0;\nbar.red.or.pred q, %1, %2, p;\nselp.u32 %0, 1, 0, q;\n}\n" : "=r"(r) : "r"(id), "r"(n), "r"((uint32_t)v) : "memory");
    return r;
}
__device__ __forceinline__ uint32_t and3(uint32_t a, uint32_t b, uint32_t c) { uint32_t r; asm("lop3.b32 %0, %1, %2, %3, 0x80;\n" : "=r"(r) : "r"(a), "r"(b), "r"(c)); return r; }
__device__ __forceinline__ uint32_t or3(uint32_t a, uint32_t b, uint32_t c) { uint32_t r; asm("lop3.b32 %0, %1, %2, %3, 0xfe;\n" : "=r"(r) : "r"(a), "r"(b), "r"(c)); return r; }
__device__ __forceinline__ uint32_t min3(uint32_t a, uint32_t b, uint32_t c) { uint32_t r; asm("{\n.reg .u32 t;\nmin.u32 t, %2, %3;\nmin.u32 %0, %1, t;\n}\n" : "=r"(r) : "r"(a), "r"(b), "r"(c)); return r; }
__device__ __forceinline__ uint32_t xor_or(uint32_t a, uint32_t b, uint32_t c) { uint32_t r; asm("lop3.b32 %0, %1, %2, %3, 0x7e;\n" : "=r"(r) : "r"(a), "r"(b), "r"(c)); return r; }
__device__ __forceinline__ uint32_t pin(uint32_t v) { uint32_t r; asm volatile("shfl.sync.bfly.b32 %0, %1, 0, 0x1f, 0xffffffff;\n" : "=r"(r) : "r"(v) : "memory"); return r; }
__device__ __forceinline__ uint4 ld_poll(const void* p) {
    uint4 v;
    asm volatile("ld.relaxed.gpu.global.v4.u32 {%0,%1,%2,%3}, [%4];\n" : "=r"(v.x), "=r"(v.y), "=r"(v.z), "=r"(v.w) : "l"(p) : "memory");
    return v;
}
__device__ __forceinline__ uint2 ld_poll64(const void* p) {
    uint2 v;
    asm volatile("ld.relaxed.gpu.global.v2.u32 {%0,%1}, [%2];\n" : "=r"(v.x), "=r"(v.y) : "l"(p) : "memory");
    return v;
}
__device__ __forceinline__ uint32_t ld_poll32(const void* p) {
    uint32_t v;
    asm volatile("ld.relaxed.gpu.global.u32 %0, [%1];\n" : "=r"(v) : "l"(p) : "memory");
    return v;
}
__device__ __forceinline__ uint32_t ld_acquire32(const void* p) {
    uint32_t v;
    asm volatile("ld.acquire.gpu.global.u32 %0, [%1];\n" : "=r"(v) : "l"(p) : "memory");
    return v;
}
__device__ __forceinline__ uint2 ldo64(const void* p) {
    uint2 v;
    asm volatile("ld.relaxed.cta.global.v2.u32 {%0,%1}, [%2];\n" : "=r"(v.x), "=r"(v.y) : "l"(p) : "memory");
    return v;
}
__device__ __forceinline__ uint32_t ldo16(const void* p) {
    uint32_t v;
    asm volatile("ld.relaxed.cta.global.u16 %0, [%1];\n" : "=r"(v) : "l"(p) : "memory");
    return v;
}
__device__ __forceinline__ void stg128(void* p, uint32_t a, uint32_t b, uint32_t c, uint32_t d) {
    asm volatile("st.global.v4.u32 [%0], {%1,%2,%3,%4};\n" ::"l"(p), "r"(a), "r"(b), "r"(c), "r"(d) : "memory");
}
__device__ __forceinline__ void stg64(void* p, uint32_t a, uint32_t b) { asm volatile("st.global.v2.u32 [%0], {%1,%2};\n" ::"l"(p), "r"(a), "r"(b) : "memory"); }
__device__ __forceinline__ uint32_t min4(const uint4& v) { return min(min(v.x, v.y), min(v.z, v.w)); }
#define SPIN_LIMIT (1 << 21)
#define TRAP() __trap()
__device__ __forceinline__ void mbar_init(uint32_t bar, uint32_t cnt) { asm volatile("mbarrier.init.shared::cta.b64 [%0], %1;\n" ::"r"(bar), "r"(cnt) : "memory"); }
__device__ __forceinline__ void mbar_expect(uint32_t bar, uint32_t bytes) {
    asm volatile("mbarrier.arrive.expect_tx.shared::cta.b64 _, [%0], %1;\n" ::"r"(bar), "r"(bytes) : "memory");
}
__device__ __forceinline__ void mbar_arrive(uint32_t bar) { asm volatile("mbarrier.arrive.shared::cta.b64 _, [%0];\n" ::"r"(bar) : "memory"); }
__device__ __forceinline__ void mbar_wait(uint32_t bar) {
    asm volatile(
        "{\n.reg .pred p;\n"
        "W_%=:\n"
        "mbarrier.try_wait.parity.shared::cta.b64 p, [%0], 0;\n"
        "@!p bra W_%=;\n}\n" ::"r"(bar) : "memory");
}
__device__ __forceinline__ void bulk_g2s(uint32_t dst, const void* src, uint32_t bytes, uint32_t bar) {
    asm volatile("cp.async.bulk.shared::cluster.global.mbarrier::complete_tx::bytes [%0], [%1], %2, [%3];\n" ::"r"(dst), "l"(src), "r"(bytes), "r"(bar) : "memory");
}
__device__ __forceinline__ void bulk_s2g(void* dst, uint32_t src, uint32_t bytes) {
    asm volatile("cp.async.bulk.global.shared::cta.bulk_group [%0], [%1], %2;\ncp.async.bulk.commit_group;\n" ::"l"(dst), "r"(src), "r"(bytes) : "memory");
}
__device__ __forceinline__ void bulk_s2g_nc(void* dst, uint32_t src, uint32_t bytes) {
    asm volatile("cp.async.bulk.global.shared::cta.bulk_group [%0], [%1], %2;\n" ::"l"(dst), "r"(src), "r"(bytes) : "memory");
}
__device__ __forceinline__ void tma_2d(uint32_t dst, const CUtensorMap* tm, int c0, int c1, uint32_t bar) {
    asm volatile("cp.async.bulk.tensor.2d.shared::cluster.global.mbarrier::complete_tx::bytes [%0], [%1, {%3, %4}], [%2];\n"
                 ::"r"(dst), "l"(tm), "r"(bar), "r"(c0), "r"(c1) : "memory");
}
__device__ __forceinline__ void tma_4d_mc(uint32_t dst, const CUtensorMap* tm, int c0, int c3, uint32_t bar) {
    asm volatile("cp.async.bulk.tensor.4d.shared::cluster.global.mbarrier::complete_tx::bytes.multicast::cluster [%0], [%1, {%3, %4, %4, %5}], [%2], %6;\n"
                 ::"r"(dst), "l"(tm), "r"(bar), "r"(c0), "r"(0), "r"(c3), "h"((unsigned short)3) : "memory");
}
__device__ __forceinline__ bool elect_one() {
    uint32_t r;
    asm volatile("{\n.reg .pred p;\nelect.sync _|p, 0xffffffff;\nselp.u32 %0, 1, 0, p;\n}\n" : "=r"(r));
    return r;
}
__device__ __forceinline__ void delay(uint32_t clks) {
    uint32_t t0, t1;
    asm volatile("mov.u32 %0, %%clock;" : "=r"(t0) :: "memory");
    do { asm volatile("mov.u32 %0, %%clock;" : "=r"(t1) :: "memory"); } while (t1 - t0 < clks);
}
__device__ __forceinline__ void fence_async() { asm volatile("fence.proxy.async.shared::cta;\n" ::: "memory"); }

__device__ __forceinline__ float2 cmul(float2 a, float2 b) {
    return make_float2(fmaf(a.x, b.x, -a.y * b.y), fmaf(a.x, b.y, a.y * b.x));
}
__device__ __forceinline__ float2 csq(float2 a) {
    float p = a.x * a.y;
    return make_float2(fmaf(a.x, a.x, -a.y * a.y), p + p);
}
__device__ __forceinline__ float ex2_approx(float x) { float r; asm("ex2.approx.ftz.f32 %0, %1;\n" : "=f"(r) : "f"(x)); return r; }
__device__ __forceinline__ float exp_bf(float x) { return rbf(ex2_approx(__fmul_ru(x, 1.4426950408889634f))); }
__device__ __forceinline__ float2 cexp_e(float lr2, float li, float e) {
    const float m = ex2_approx(lr2 * e);
    return make_float2(m * __cosf(li * e), m * __sinf(li * e));
}
__device__ __forceinline__ float rcp_approx(float x) { float r; asm("rcp.approx.ftz.f32 %0, %1;\n" : "=f"(r) : "f"(x)); return r; }
__device__ __forceinline__ float sigmoid_f(float x) { return rcp_approx(1.0f + ex2_approx(x * -1.4426950408889634f)); }
__device__ __forceinline__ float sqrt_approx(float x) { float r; asm("sqrt.approx.ftz.f32 %0, %1;\n" : "=f"(r) : "f"(x)); return r; }

__device__ __forceinline__ void wg_fence() { asm volatile("wgmma.fence.sync.aligned;\n" ::: "memory"); }
__device__ __forceinline__ void wg_commit() { asm volatile("wgmma.commit_group.sync.aligned;\n" ::: "memory"); }
__device__ __forceinline__ void wg_wait0() { asm volatile("wgmma.wait_group.sync.aligned 0;\n" ::: "memory"); }
template <int T> __device__ __forceinline__ void wg_mma(float (&acc)[16][4], const uint32_t* a, uint64_t desc);
template <int T> __device__ __forceinline__ void wg_first(float (&acc)[16][4], const uint32_t* a, uint64_t desc);
template <> __device__ __forceinline__ void wg_mma<0>(float (&acc)[16][4], const uint32_t* a, uint64_t desc) {
    asm volatile("wgmma.mma_async.sync.aligned.m64n128k16.f32.f16.f16 {%0,%1,%2,%3,%4,%5,%6,%7,%8,%9,%10,%11,%12,%13,%14,%15,%16,%17,%18,%19,%20,%21,%22,%23,%24,%25,%26,%27,%28,%29,%30,%31,%32,%33,%34,%35,%36,%37,%38,%39,%40,%41,%42,%43,%44,%45,%46,%47,%48,%49,%50,%51,%52,%53,%54,%55,%56,%57,%58,%59,%60,%61,%62,%63}, {%64,%65,%66,%67}, %68, 1, 1, 1, 0;\n"
                 : "+f"(acc[0][0]), "+f"(acc[0][1]), "+f"(acc[0][2]), "+f"(acc[0][3]), "+f"(acc[1][0]), "+f"(acc[1][1]), "+f"(acc[1][2]), "+f"(acc[1][3]), "+f"(acc[2][0]), "+f"(acc[2][1]), "+f"(acc[2][2]), "+f"(acc[2][3]), "+f"(acc[3][0]), "+f"(acc[3][1]), "+f"(acc[3][2]), "+f"(acc[3][3]), "+f"(acc[4][0]), "+f"(acc[4][1]), "+f"(acc[4][2]), "+f"(acc[4][3]), "+f"(acc[5][0]), "+f"(acc[5][1]), "+f"(acc[5][2]), "+f"(acc[5][3]), "+f"(acc[6][0]), "+f"(acc[6][1]), "+f"(acc[6][2]), "+f"(acc[6][3]), "+f"(acc[7][0]), "+f"(acc[7][1]), "+f"(acc[7][2]), "+f"(acc[7][3]), "+f"(acc[8][0]), "+f"(acc[8][1]), "+f"(acc[8][2]), "+f"(acc[8][3]), "+f"(acc[9][0]), "+f"(acc[9][1]), "+f"(acc[9][2]), "+f"(acc[9][3]), "+f"(acc[10][0]), "+f"(acc[10][1]), "+f"(acc[10][2]), "+f"(acc[10][3]), "+f"(acc[11][0]), "+f"(acc[11][1]), "+f"(acc[11][2]), "+f"(acc[11][3]), "+f"(acc[12][0]), "+f"(acc[12][1]), "+f"(acc[12][2]), "+f"(acc[12][3]), "+f"(acc[13][0]), "+f"(acc[13][1]), "+f"(acc[13][2]), "+f"(acc[13][3]), "+f"(acc[14][0]), "+f"(acc[14][1]), "+f"(acc[14][2]), "+f"(acc[14][3]), "+f"(acc[15][0]), "+f"(acc[15][1]), "+f"(acc[15][2]), "+f"(acc[15][3])
                 : "r"(a[0]), "r"(a[1]), "r"(a[2]), "r"(a[3]), "l"(desc));
}
template <> __device__ __forceinline__ void wg_mma<2>(float (&acc)[16][4], const uint32_t* a, uint64_t desc) {
    asm volatile("wgmma.mma_async.sync.aligned.m64n112k16.f32.f16.f16 {%0,%1,%2,%3,%4,%5,%6,%7,%8,%9,%10,%11,%12,%13,%14,%15,%16,%17,%18,%19,%20,%21,%22,%23,%24,%25,%26,%27,%28,%29,%30,%31,%32,%33,%34,%35,%36,%37,%38,%39,%40,%41,%42,%43,%44,%45,%46,%47,%48,%49,%50,%51,%52,%53,%54,%55}, {%56,%57,%58,%59}, %60, 1, 1, 1, 0;\n"
                 : "+f"(acc[2][0]), "+f"(acc[2][1]), "+f"(acc[2][2]), "+f"(acc[2][3]), "+f"(acc[3][0]), "+f"(acc[3][1]), "+f"(acc[3][2]), "+f"(acc[3][3]), "+f"(acc[4][0]), "+f"(acc[4][1]), "+f"(acc[4][2]), "+f"(acc[4][3]), "+f"(acc[5][0]), "+f"(acc[5][1]), "+f"(acc[5][2]), "+f"(acc[5][3]), "+f"(acc[6][0]), "+f"(acc[6][1]), "+f"(acc[6][2]), "+f"(acc[6][3]), "+f"(acc[7][0]), "+f"(acc[7][1]), "+f"(acc[7][2]), "+f"(acc[7][3]), "+f"(acc[8][0]), "+f"(acc[8][1]), "+f"(acc[8][2]), "+f"(acc[8][3]), "+f"(acc[9][0]), "+f"(acc[9][1]), "+f"(acc[9][2]), "+f"(acc[9][3]), "+f"(acc[10][0]), "+f"(acc[10][1]), "+f"(acc[10][2]), "+f"(acc[10][3]), "+f"(acc[11][0]), "+f"(acc[11][1]), "+f"(acc[11][2]), "+f"(acc[11][3]), "+f"(acc[12][0]), "+f"(acc[12][1]), "+f"(acc[12][2]), "+f"(acc[12][3]), "+f"(acc[13][0]), "+f"(acc[13][1]), "+f"(acc[13][2]), "+f"(acc[13][3]), "+f"(acc[14][0]), "+f"(acc[14][1]), "+f"(acc[14][2]), "+f"(acc[14][3]), "+f"(acc[15][0]), "+f"(acc[15][1]), "+f"(acc[15][2]), "+f"(acc[15][3])
                 : "r"(a[0]), "r"(a[1]), "r"(a[2]), "r"(a[3]), "l"(desc));
}
template <> __device__ __forceinline__ void wg_mma<4>(float (&acc)[16][4], const uint32_t* a, uint64_t desc) {
    asm volatile("wgmma.mma_async.sync.aligned.m64n96k16.f32.f16.f16 {%0,%1,%2,%3,%4,%5,%6,%7,%8,%9,%10,%11,%12,%13,%14,%15,%16,%17,%18,%19,%20,%21,%22,%23,%24,%25,%26,%27,%28,%29,%30,%31,%32,%33,%34,%35,%36,%37,%38,%39,%40,%41,%42,%43,%44,%45,%46,%47}, {%48,%49,%50,%51}, %52, 1, 1, 1, 0;\n"
                 : "+f"(acc[4][0]), "+f"(acc[4][1]), "+f"(acc[4][2]), "+f"(acc[4][3]), "+f"(acc[5][0]), "+f"(acc[5][1]), "+f"(acc[5][2]), "+f"(acc[5][3]), "+f"(acc[6][0]), "+f"(acc[6][1]), "+f"(acc[6][2]), "+f"(acc[6][3]), "+f"(acc[7][0]), "+f"(acc[7][1]), "+f"(acc[7][2]), "+f"(acc[7][3]), "+f"(acc[8][0]), "+f"(acc[8][1]), "+f"(acc[8][2]), "+f"(acc[8][3]), "+f"(acc[9][0]), "+f"(acc[9][1]), "+f"(acc[9][2]), "+f"(acc[9][3]), "+f"(acc[10][0]), "+f"(acc[10][1]), "+f"(acc[10][2]), "+f"(acc[10][3]), "+f"(acc[11][0]), "+f"(acc[11][1]), "+f"(acc[11][2]), "+f"(acc[11][3]), "+f"(acc[12][0]), "+f"(acc[12][1]), "+f"(acc[12][2]), "+f"(acc[12][3]), "+f"(acc[13][0]), "+f"(acc[13][1]), "+f"(acc[13][2]), "+f"(acc[13][3]), "+f"(acc[14][0]), "+f"(acc[14][1]), "+f"(acc[14][2]), "+f"(acc[14][3]), "+f"(acc[15][0]), "+f"(acc[15][1]), "+f"(acc[15][2]), "+f"(acc[15][3])
                 : "r"(a[0]), "r"(a[1]), "r"(a[2]), "r"(a[3]), "l"(desc));
}
template <> __device__ __forceinline__ void wg_mma<6>(float (&acc)[16][4], const uint32_t* a, uint64_t desc) {
    asm volatile("wgmma.mma_async.sync.aligned.m64n80k16.f32.f16.f16 {%0,%1,%2,%3,%4,%5,%6,%7,%8,%9,%10,%11,%12,%13,%14,%15,%16,%17,%18,%19,%20,%21,%22,%23,%24,%25,%26,%27,%28,%29,%30,%31,%32,%33,%34,%35,%36,%37,%38,%39}, {%40,%41,%42,%43}, %44, 1, 1, 1, 0;\n"
                 : "+f"(acc[6][0]), "+f"(acc[6][1]), "+f"(acc[6][2]), "+f"(acc[6][3]), "+f"(acc[7][0]), "+f"(acc[7][1]), "+f"(acc[7][2]), "+f"(acc[7][3]), "+f"(acc[8][0]), "+f"(acc[8][1]), "+f"(acc[8][2]), "+f"(acc[8][3]), "+f"(acc[9][0]), "+f"(acc[9][1]), "+f"(acc[9][2]), "+f"(acc[9][3]), "+f"(acc[10][0]), "+f"(acc[10][1]), "+f"(acc[10][2]), "+f"(acc[10][3]), "+f"(acc[11][0]), "+f"(acc[11][1]), "+f"(acc[11][2]), "+f"(acc[11][3]), "+f"(acc[12][0]), "+f"(acc[12][1]), "+f"(acc[12][2]), "+f"(acc[12][3]), "+f"(acc[13][0]), "+f"(acc[13][1]), "+f"(acc[13][2]), "+f"(acc[13][3]), "+f"(acc[14][0]), "+f"(acc[14][1]), "+f"(acc[14][2]), "+f"(acc[14][3]), "+f"(acc[15][0]), "+f"(acc[15][1]), "+f"(acc[15][2]), "+f"(acc[15][3])
                 : "r"(a[0]), "r"(a[1]), "r"(a[2]), "r"(a[3]), "l"(desc));
}
template <> __device__ __forceinline__ void wg_mma<8>(float (&acc)[16][4], const uint32_t* a, uint64_t desc) {
    asm volatile("wgmma.mma_async.sync.aligned.m64n64k16.f32.f16.f16 {%0,%1,%2,%3,%4,%5,%6,%7,%8,%9,%10,%11,%12,%13,%14,%15,%16,%17,%18,%19,%20,%21,%22,%23,%24,%25,%26,%27,%28,%29,%30,%31}, {%32,%33,%34,%35}, %36, 1, 1, 1, 0;\n"
                 : "+f"(acc[8][0]), "+f"(acc[8][1]), "+f"(acc[8][2]), "+f"(acc[8][3]), "+f"(acc[9][0]), "+f"(acc[9][1]), "+f"(acc[9][2]), "+f"(acc[9][3]), "+f"(acc[10][0]), "+f"(acc[10][1]), "+f"(acc[10][2]), "+f"(acc[10][3]), "+f"(acc[11][0]), "+f"(acc[11][1]), "+f"(acc[11][2]), "+f"(acc[11][3]), "+f"(acc[12][0]), "+f"(acc[12][1]), "+f"(acc[12][2]), "+f"(acc[12][3]), "+f"(acc[13][0]), "+f"(acc[13][1]), "+f"(acc[13][2]), "+f"(acc[13][3]), "+f"(acc[14][0]), "+f"(acc[14][1]), "+f"(acc[14][2]), "+f"(acc[14][3]), "+f"(acc[15][0]), "+f"(acc[15][1]), "+f"(acc[15][2]), "+f"(acc[15][3])
                 : "r"(a[0]), "r"(a[1]), "r"(a[2]), "r"(a[3]), "l"(desc));
}
template <> __device__ __forceinline__ void wg_mma<10>(float (&acc)[16][4], const uint32_t* a, uint64_t desc) {
    asm volatile("wgmma.mma_async.sync.aligned.m64n48k16.f32.f16.f16 {%0,%1,%2,%3,%4,%5,%6,%7,%8,%9,%10,%11,%12,%13,%14,%15,%16,%17,%18,%19,%20,%21,%22,%23}, {%24,%25,%26,%27}, %28, 1, 1, 1, 0;\n"
                 : "+f"(acc[10][0]), "+f"(acc[10][1]), "+f"(acc[10][2]), "+f"(acc[10][3]), "+f"(acc[11][0]), "+f"(acc[11][1]), "+f"(acc[11][2]), "+f"(acc[11][3]), "+f"(acc[12][0]), "+f"(acc[12][1]), "+f"(acc[12][2]), "+f"(acc[12][3]), "+f"(acc[13][0]), "+f"(acc[13][1]), "+f"(acc[13][2]), "+f"(acc[13][3]), "+f"(acc[14][0]), "+f"(acc[14][1]), "+f"(acc[14][2]), "+f"(acc[14][3]), "+f"(acc[15][0]), "+f"(acc[15][1]), "+f"(acc[15][2]), "+f"(acc[15][3])
                 : "r"(a[0]), "r"(a[1]), "r"(a[2]), "r"(a[3]), "l"(desc));
}
template <> __device__ __forceinline__ void wg_mma<12>(float (&acc)[16][4], const uint32_t* a, uint64_t desc) {
    asm volatile("wgmma.mma_async.sync.aligned.m64n32k16.f32.f16.f16 {%0,%1,%2,%3,%4,%5,%6,%7,%8,%9,%10,%11,%12,%13,%14,%15}, {%16,%17,%18,%19}, %20, 1, 1, 1, 0;\n"
                 : "+f"(acc[12][0]), "+f"(acc[12][1]), "+f"(acc[12][2]), "+f"(acc[12][3]), "+f"(acc[13][0]), "+f"(acc[13][1]), "+f"(acc[13][2]), "+f"(acc[13][3]), "+f"(acc[14][0]), "+f"(acc[14][1]), "+f"(acc[14][2]), "+f"(acc[14][3]), "+f"(acc[15][0]), "+f"(acc[15][1]), "+f"(acc[15][2]), "+f"(acc[15][3])
                 : "r"(a[0]), "r"(a[1]), "r"(a[2]), "r"(a[3]), "l"(desc));
}
template <> __device__ __forceinline__ void wg_mma<14>(float (&acc)[16][4], const uint32_t* a, uint64_t desc) {
    asm volatile("wgmma.mma_async.sync.aligned.m64n16k16.f32.f16.f16 {%0,%1,%2,%3,%4,%5,%6,%7}, {%8,%9,%10,%11}, %12, 1, 1, 1, 0;\n"
                 : "+f"(acc[14][0]), "+f"(acc[14][1]), "+f"(acc[14][2]), "+f"(acc[14][3]), "+f"(acc[15][0]), "+f"(acc[15][1]), "+f"(acc[15][2]), "+f"(acc[15][3])
                 : "r"(a[0]), "r"(a[1]), "r"(a[2]), "r"(a[3]), "l"(desc));
}
template <> __device__ __forceinline__ void wg_first<0>(float (&acc)[16][4], const uint32_t* a, uint64_t desc) {
    asm volatile("wgmma.mma_async.sync.aligned.m64n128k16.f32.f16.f16 {%0,%1,%2,%3,%4,%5,%6,%7,%8,%9,%10,%11,%12,%13,%14,%15,%16,%17,%18,%19,%20,%21,%22,%23,%24,%25,%26,%27,%28,%29,%30,%31,%32,%33,%34,%35,%36,%37,%38,%39,%40,%41,%42,%43,%44,%45,%46,%47,%48,%49,%50,%51,%52,%53,%54,%55,%56,%57,%58,%59,%60,%61,%62,%63}, {%64,%65,%66,%67}, %68, 0, 1, 1, 0;\n"
                 : "=f"(acc[0][0]), "=f"(acc[0][1]), "=f"(acc[0][2]), "=f"(acc[0][3]), "=f"(acc[1][0]), "=f"(acc[1][1]), "=f"(acc[1][2]), "=f"(acc[1][3]), "=f"(acc[2][0]), "=f"(acc[2][1]), "=f"(acc[2][2]), "=f"(acc[2][3]), "=f"(acc[3][0]), "=f"(acc[3][1]), "=f"(acc[3][2]), "=f"(acc[3][3]), "=f"(acc[4][0]), "=f"(acc[4][1]), "=f"(acc[4][2]), "=f"(acc[4][3]), "=f"(acc[5][0]), "=f"(acc[5][1]), "=f"(acc[5][2]), "=f"(acc[5][3]), "=f"(acc[6][0]), "=f"(acc[6][1]), "=f"(acc[6][2]), "=f"(acc[6][3]), "=f"(acc[7][0]), "=f"(acc[7][1]), "=f"(acc[7][2]), "=f"(acc[7][3]), "=f"(acc[8][0]), "=f"(acc[8][1]), "=f"(acc[8][2]), "=f"(acc[8][3]), "=f"(acc[9][0]), "=f"(acc[9][1]), "=f"(acc[9][2]), "=f"(acc[9][3]), "=f"(acc[10][0]), "=f"(acc[10][1]), "=f"(acc[10][2]), "=f"(acc[10][3]), "=f"(acc[11][0]), "=f"(acc[11][1]), "=f"(acc[11][2]), "=f"(acc[11][3]), "=f"(acc[12][0]), "=f"(acc[12][1]), "=f"(acc[12][2]), "=f"(acc[12][3]), "=f"(acc[13][0]), "=f"(acc[13][1]), "=f"(acc[13][2]), "=f"(acc[13][3]), "=f"(acc[14][0]), "=f"(acc[14][1]), "=f"(acc[14][2]), "=f"(acc[14][3]), "=f"(acc[15][0]), "=f"(acc[15][1]), "=f"(acc[15][2]), "=f"(acc[15][3])
                 : "r"(a[0]), "r"(a[1]), "r"(a[2]), "r"(a[3]), "l"(desc));
}
template <> __device__ __forceinline__ void wg_first<4>(float (&acc)[16][4], const uint32_t* a, uint64_t desc) {
    asm volatile("wgmma.mma_async.sync.aligned.m64n96k16.f32.f16.f16 {%0,%1,%2,%3,%4,%5,%6,%7,%8,%9,%10,%11,%12,%13,%14,%15,%16,%17,%18,%19,%20,%21,%22,%23,%24,%25,%26,%27,%28,%29,%30,%31,%32,%33,%34,%35,%36,%37,%38,%39,%40,%41,%42,%43,%44,%45,%46,%47}, {%48,%49,%50,%51}, %52, 0, 1, 1, 0;\n"
                 : "=f"(acc[4][0]), "=f"(acc[4][1]), "=f"(acc[4][2]), "=f"(acc[4][3]), "=f"(acc[5][0]), "=f"(acc[5][1]), "=f"(acc[5][2]), "=f"(acc[5][3]), "=f"(acc[6][0]), "=f"(acc[6][1]), "=f"(acc[6][2]), "=f"(acc[6][3]), "=f"(acc[7][0]), "=f"(acc[7][1]), "=f"(acc[7][2]), "=f"(acc[7][3]), "=f"(acc[8][0]), "=f"(acc[8][1]), "=f"(acc[8][2]), "=f"(acc[8][3]), "=f"(acc[9][0]), "=f"(acc[9][1]), "=f"(acc[9][2]), "=f"(acc[9][3]), "=f"(acc[10][0]), "=f"(acc[10][1]), "=f"(acc[10][2]), "=f"(acc[10][3]), "=f"(acc[11][0]), "=f"(acc[11][1]), "=f"(acc[11][2]), "=f"(acc[11][3]), "=f"(acc[12][0]), "=f"(acc[12][1]), "=f"(acc[12][2]), "=f"(acc[12][3]), "=f"(acc[13][0]), "=f"(acc[13][1]), "=f"(acc[13][2]), "=f"(acc[13][3]), "=f"(acc[14][0]), "=f"(acc[14][1]), "=f"(acc[14][2]), "=f"(acc[14][3]), "=f"(acc[15][0]), "=f"(acc[15][1]), "=f"(acc[15][2]), "=f"(acc[15][3])
                 : "r"(a[0]), "r"(a[1]), "r"(a[2]), "r"(a[3]), "l"(desc));
}

#define SDLY 1100
#define UDLY 1250
#define KDLY 850
#define FDLY 950
#define FDLY2 350
#define DDLY 450
#define WDLY 500
#define HW 15
#define FIX(v) do { if ((v) == 1u) TRAP(); } while (0)
#define STAMPW(i) STAMPY(i)
#define STAMP2(i) STAMP(i)
#undef STAMPX
#define STAMPX(i)
struct Params {
    const bf16 *x, *lar, *aim, *cre, *cim, *ldt, *dsk;
    Scratch* s;
    const bf16* wr;
    bf16* out;
};
struct Maps { CUtensorMap x, w[2], r[2], d; };

#define TOK(g) (2 * (g) - ((g) & 1))
#define ROWTOK(r) (TOK((r) & 7) + (((r) >> 2) & 2))
__device__ __forceinline__ void ln_partial(const uint32_t (&H)[2][4], float (&d)[2][4]) {
#pragma unroll
    for (int i = 0; i < 8; i++) d[i >> 2][i & 3] = 0.f;
#pragma unroll
    for (int k = 0; k < 4; k++)
#pragma unroll
        for (int hf = 0; hf < 2; hf++) mma_bf16_k8(d[hf], H[hf][k], 0x3f803f80u, H[hf][k]);
}
__device__ __forceinline__ float sum18(uint32_t a) {
    const uint4 p = lds128(a), q = lds128(a + 16), r = lds128(a + 32), s = lds128(a + 48);
    const uint2 u = lds64(a + 64);
#define F(x) __uint_as_float(x)
    return (((F(p.x) + F(p.y)) + (F(p.z) + F(p.w))) + ((F(q.x) + F(q.y)) + (F(q.z) + F(q.w)))) +
           (((F(r.x) + F(r.y)) + (F(r.z) + F(r.w))) + ((F(s.x) + F(s.y)) + (F(s.z) + F(s.w))) + (F(u.x) + F(u.y)));
#undef F
}
__device__ __forceinline__ void ln_stats(float sm, float sq, float& mb, float& sd) {
    const float m0 = sm * (1.0f / 576.0f);
    const float mean = fmaf(fmaf(-m0, 576.0f, sm), 1.0f / 576.0f, m0);
    const float var = fmaxf(fmaf(-mean, mean, sq * (1.0f / 576.0f)), 0.f);
    mb = rbf(mean);
    sd = rbf(sqrt_approx(rbf(rbf(var) + 1e-5f)));
}
__device__ __forceinline__ void ln_finish(float v, int lane, float& mb, float& rc) {
    const float o = __shfl_xor_sync(0xffffffffu, v, 16);
    float sd;
    ln_stats(lane < 16 ? v : o, lane < 16 ? o : v, mb, sd);
    rc = rcp_approx(sd);
}
__device__ __forceinline__ uint32_t ln_apply(uint32_t w, uint32_t m2, uint32_t rh, uint32_t rl) {
    const uint32_t d = hsub2_bf(w, m2);
    return hfma2_bf(d, rh, hmul2_bf(d, rl));
}
__device__ __forceinline__ void stat_store(uint32_t a, float mb, float rc, uint32_t extra) {
    const float rh = rbf(rc);
    sts64(a, (__float_as_uint(mb) >> 16) | (extra << 16), pack_bf16(rh, rc - rh));
}
__device__ __forceinline__ uint32_t dup_lo(uint32_t w) { const __nv_bfloat162 r = __low2bfloat162(*reinterpret_cast<__nv_bfloat162*>(&w)); return *reinterpret_cast<const uint32_t*>(&r); }
__device__ __forceinline__ uint32_t dup_hi(uint32_t w) { const __nv_bfloat162 r = __high2bfloat162(*reinterpret_cast<__nv_bfloat162*>(&w)); return *reinterpret_cast<const uint32_t*>(&r); }
__device__ __forceinline__ float fsel(float a, float b, int c) { float r; asm("{\n.reg .pred p;\nsetp.ne.s32 p, %3, 0;\nselp.f32 %0, %1, %2, p;\n}\n" : "=f"(r) : "f"(a), "f"(b), "r"(c)); return r; }
#define STAT_M(s) dup_lo((s).x)
#define STAT_H(s) dup_lo((s).y)
#define STAT_L(s) dup_hi((s).y)

__device__ __forceinline__ void hcmul(uint32_t re, uint32_t im, uint32_t zx, uint32_t zy, uint32_t& ore, uint32_t& oim) {
    ore = hfms2(im, zy, hmul2(re, zx));
    oim = hfma2(re, zy, hmul2(im, zx));
}

template <int HI>
__device__ __forceinline__ uint32_t hdup(uint32_t w) {
    const __half2 h = *reinterpret_cast<__half2*>(&w), r = HI ? __high2half2(h) : __low2half2(h);
    return *reinterpret_cast<const uint32_t*>(&r);
}
__device__ __forceinline__ void hcmul(uint32_t re, uint32_t im, float2 z, uint32_t& ore, uint32_t& oim) {
    const uint32_t w = pack_f16(z.x, z.y);
    hcmul(re, im, hdup<0>(w), hdup<1>(w), ore, oim);
}

struct KGen {
    uint32_t A[2][4][4];
    float2 z1, z8, z64, z128, T[9];
};
__device__ __forceinline__ void kgen_setup(KGen& k, float lar, float aim, float dt) {
    const float lr2 = -(exp_bf(lar) * dt) * 1.4426950408889634f, li = aim * dt;
    k.z1 = cexp_e(lr2, li, 1.0f);
    k.z8 = cexp_e(lr2, li, 8.0f);
    k.z64 = cexp_e(lr2, li, 64.0f);
}
__device__ __forceinline__ void kgen_rows(KGen& k, uint32_t tb, int lane) {
    const float2 z8 = k.z8, z64 = k.z64;
    const uint32_t row = tb + lane * 16;
    k.z128 = csq(z64);
    const float2 z16 = csq(z8), z24 = cmul(z16, z8), z32 = csq(z16), z40 = cmul(z32, z8), z48 = csq(z24), z56 = cmul(z32, z24);
    uint32_t re[4], im[4], a[4], b[4];
    re[0] = pack_f16(1.0f, z8.x); im[0] = pack_f16(0.0f, z8.y);
    re[1] = pack_f16(z16.x, z24.x); im[1] = pack_f16(z16.y, z24.y);
    re[2] = pack_f16(z32.x, z40.x); im[2] = pack_f16(z32.y, z40.y);
    re[3] = pack_f16(z48.x, z56.x); im[3] = pack_f16(z48.y, z56.y);
    sts128(row, re[0], re[1], re[2], re[3]);
    sts128(row + 1024, im[0], im[1], im[2], im[3]);
    const uint32_t zw = pack_f16(k.z128.x, k.z128.y);
#pragma unroll
    for (int j = 0; j < 4; j++) hcmul(re[j], im[j], z64, a[j], b[j]);
    sts128(row + 512, a[0], a[1], a[2], a[3]);
    sts128(row + 1536, b[0], b[1], b[2], b[3]);
    const int mi = lane >> 3;
    const uint32_t zd = tb + 2048 + mi * 16;
    sts16(tb + 2048 + lane * 2, zw); sts16(tb + 2112 + lane * 2, zw >> 16);
    __syncwarp();
    const uint32_t ad = tb + (lane & 7) * 16 + mi * 512;
    ldsm_x4(a[0], a[1], a[2], a[3], zd);
    ldsm_x4(b[0], b[1], b[2], b[3], zd + 64);
#pragma unroll
    for (int ks = 0; ks < 4; ks++) {
        ldsm_x4_t(k.A[0][ks][0], k.A[0][ks][1], k.A[0][ks][2], k.A[0][ks][3], ad + ks * 128);
        hcmul(k.A[0][ks][0], k.A[0][ks][2], a[ks], b[ks], k.A[1][ks][0], k.A[1][ks][2]);
        hcmul(k.A[0][ks][1], k.A[0][ks][3], a[ks], b[ks], k.A[1][ks][1], k.A[1][ks][3]);
    }
}
__device__ __forceinline__ void kgen_chain(KGen& k, uint32_t cr, uint32_t ci, float cs) {
    k.T[0] = make_float2(bf_lo(cr) * cs, -bf_lo(ci) * cs);
    const float2 y1 = make_float2(k.z1.x, -k.z1.y);
#pragma unroll
    for (int c = 1; c < 8; c++) k.T[c] = cmul(k.T[c - 1], y1);
    k.T[8] = cmul(k.T[0], make_float2(k.z8.x, -k.z8.y));
}
__device__ __forceinline__ void kgen_cols(KGen& k, uint32_t tb, uint32_t t5, int lane) {
    const uint32_t row = tb + lane * 16;
    const float2 (&T)[9] = k.T;
    const float2 y128 = make_float2(k.z128.x, -k.z128.y);
    const float2 y256 = csq(y128), y512 = csq(y256), y768 = cmul(y512, y256), y1024 = csq(y512);
    const float2 c1032 = cmul(T[8], y1024);
    __syncwarp();
    sts128(row, pack_f16(T[0].x, T[1].x), pack_f16(T[2].x, T[3].x), pack_f16(T[4].x, T[5].x), pack_f16(T[6].x, T[7].x));
    sts128(row + 512, pack_f16(T[0].y, T[1].y), pack_f16(T[2].y, T[3].y), pack_f16(T[4].y, T[5].y), pack_f16(T[6].y, T[7].y));
    uint32_t a[4], b[4];
    const uint32_t r0 = pack_f16(1.0f, y256.x), i0 = pack_f16(0.0f, y256.y), r1 = pack_f16(y512.x, y768.x), i1 = pack_f16(y512.y, y768.y);
    {
        hcmul(pack_f16(T[0].x, T[2].x), pack_f16(T[0].y, T[2].y), hdup<1>(r0), hdup<1>(i0), a[0], b[0]);
        hcmul(pack_f16(T[4].x, T[6].x), pack_f16(T[4].y, T[6].y), hdup<1>(r0), hdup<1>(i0), a[1], b[1]);
        const uint32_t r04 = pack_f16(T[0].x, T[4].x), i04 = pack_f16(T[0].y, T[4].y);
        hcmul(r04, i04, hdup<0>(r1), hdup<0>(i1), a[2], b[2]);
        hcmul(r04, i04, hdup<1>(r1), hdup<1>(i1), a[3], b[3]);
    }
    sts128(row + 1024, a[0], a[1], a[2], a[3]);
    sts128(row + 1536, b[0], b[1], b[2], b[3]);
    hcmul(r0, i0, T[8], a[0], b[0]); hcmul(r1, i1, T[8], a[1], b[1]);
    hcmul(r0, i0, c1032, a[2], b[2]); hcmul(r1, i1, c1032, a[3], b[3]);
    sts128(row + 2048, a[0], a[1], a[2], a[3]);
    sts128(t5 + lane * 16, b[0], b[1], b[2], b[3]);
}
template <class F>
__device__ __forceinline__ void kgen_mma(const KGen& k, uint32_t tb, uint32_t t5, int lane, F hold) {
    __syncwarp();
    float acc[2][3][4];
#pragma unroll
    for (int i = 0; i < 6; i++)
#pragma unroll
        for (int j = 0; j < 4; j++) acc[i / 3][i % 3][j] = 0.f;
    const int mi = lane >> 3;
    const uint32_t ro = ((lane & 7) + 8 * (mi >> 1)) * 16, bd = tb + ro + (mi & 1) * 512, b2 = ro + ((mi & 1) ? t5 : tb + 2048);
#pragma unroll
    for (int kp = 0; kp < 2; kp++)
#pragma unroll
        for (int j = 0; j < 3; j++) {
            uint32_t b[4];
            if (kp == 0 && j == 2) hold();
            ldsm_x4_t(b[0], b[1], b[2], b[3], (j < 2 ? bd + j * 1024 : b2) + kp * 256);
#pragma unroll
            for (int h = 0; h < 2; h++)
#pragma unroll
                for (int m = 0; m < 2; m++) {
                    const uint32_t (&A)[4] = k.A[m][2 * kp + h];
                    mma_f16(acc[m][j], A[0], A[1], A[2], A[3], b[2 * h], b[2 * h + 1]);
                }
        }
    __syncwarp();
#define PK(j) pack_f16(acc[0][j][0], acc[0][j][1]), pack_f16(acc[0][j][2], acc[0][j][3]), pack_f16(acc[1][j][0], acc[1][j][1]), pack_f16(acc[1][j][2], acc[1][j][3])
    stsm_x4(tb + lane * 16, PK(0));
    stsm_x4(tb + 512 + lane * 16, PK(1));
    stsm_x4_t(tb + 1024 + (lane & 7) * 80 + mi * 16, PK(2));
#undef PK
}
__device__ __forceinline__ uint32_t table_buf(uint32_t sb, int warp) { return sb + SM_PL + warp * TBW; }

__device__ __forceinline__ uint4 lds16x4(uint32_t a) { return make_uint4(lds16(a), lds16(a + TBW), lds16(a + 2 * TBW), lds16(a + 3 * TBW)); }
__device__ __forceinline__ void combine_setup(uint32_t sb, int warp, int lane, uint32_t kw, uint32_t& o, uint32_t& n, uint32_t& d) {
    const int wq = warp & 3;
    const uint32_t a = table_buf(sb, warp & ~3);
    o = wq == 3 ? a + 1024 + 320 + (lane >> 3) * 80 + (lane & 7) * 8 : a + (wq ? 504 + wq * 8 : 0) + lane * 16;
    n = a + 1024 + wq * 80 + lane * 2;
    d = wq < 3 ? kw + (wq == 2 ? KW_P : 32 + wq * 512) + lane * 16 : kw + KW_H + 8 + lane * 8;
}
__device__ __forceinline__ void kgen_combine(int wq, int lane, uint32_t o, uint32_t na, uint32_t d) {
#define S4(f) hadd2(hadd2(u.f, v.f), hadd2(w.f, x.f))
#define H4(v) hadd2(hadd2(v.x, v.y), hadd2(v.z, v.w))
#define BP __byte_perm
    if (wq == 0) {
        const uint4 u = lds128(o), v = lds128(o + TBW), w = lds128(o + 2 * TBW), x = lds128(o + 3 * TBW), nn = lds16x4(na);
        const uint32_t n = H4(nn), k0 = S4(x), k2 = S4(y), k4 = S4(z), k6 = S4(w);
        sts128(d, BP(k0, k0, 0x1032), BP(k0, k2, 0x3254), BP(k2, k2, 0x1032), BP(k2, k4, 0x3254));
        sts128(d + KW_PL, BP(k4, k4, 0x1032), BP(k4, k6, 0x3254), BP(k6, k6, 0x1032), BP(k6, n, 0x3254));
        if (lane == 0) sts32(d + KW_PL - 4, k0 & 0xffffu);
    } else {
        const uint2 u = lds64(o), v = lds64(o + TBW), w = lds64(o + 2 * TBW), x = lds64(o + 3 * TBW);
        uint4 nn = make_uint4(0u, 0u, 0u, 0u), mm = nn;
        if (wq < 3) nn = lds16x4(na);
        if (wq == 2) mm = lds16x4(na + 80);
        const uint32_t k0 = S4(x), k2 = S4(y), n = H4(nn), m = H4(mm);
        if (wq == 3) {
            sts64(d, k0, k2);
        } else if (wq == 1) {
            const uint32_t cc = BP(k2, k2, 0x1010);
            sts128(d, BP(k0, k0, 0x1010), BP(k0, k0, 0x1032), BP(k0, k2, 0x3254), cc);
            sts128(d + KW_PL, cc, BP(k2, k2, 0x1032), BP(k2, n, 0x3254), BP(n, n, 0x1010));
        } else {
            const uint32_t w40 = BP(k0, k0, 0x1032), w84 = BP(k0, n, 0x3254), w0 = BP(k0, k0, 0x1010), w4 = BP(k0, k0, 0x3232), w8 = BP(n, n, 0x1010);
            sts64(d, w40, w84);
            sts64(d + 512, BP(k2, k2, 0x1032), BP(k2, m, 0x3254));
            if (lane < 8) { sts128(d - (KW_P - 1056), w0, w0, w40, w4); sts128(d - (KW_P - 1056 - KW_PL), w4, w84, w8, w8); }
            if (lane == 31) sts16(d + (KW_H + 6 - KW_P - 496), m);
        }
    }
#undef S4
#undef H4
#undef BP
}

__device__ __forceinline__ int c_exponent(const uint2& r, const uint2& i, float dt) {
    const uint32_t mx = __vmaxu2(__vmaxu2(r.x & 0x7fff7fffu, r.y & 0x7fff7fffu), __vmaxu2(i.x & 0x7fff7fffu, i.y & 0x7fff7fffu));
    return __reduce_max_sync(0xffffffffu, max(mx, mx << 16) + (__float_as_uint(dt) & 0x7f800000u)) >> 23;
}

__device__ __forceinline__ int lane_v() { int l; asm volatile("mov.u32 %0, %%laneid;" : "=r"(l)); return l; }
__device__ __forceinline__ uint32_t prmt_v(uint32_t a, uint32_t b, uint32_t s) { uint32_t d; asm volatile("prmt.b32 %0, %1, %2, %3;\n" : "=r"(d) : "r"(a), "r"(b), "r"(s)); return d; }
__device__ __forceinline__ uint32_t mov_v(uint32_t a) { uint32_t d; asm volatile("mov.b32 %0, %1;\n" : "=r"(d) : "r"(a)); return d; }
template <int G>
__device__ __forceinline__ void conv_rename(float (&acc)[16][4]) {
#pragma unroll
    for (int i = G; i < 16; i++)
#pragma unroll
        for (int j = 0; j < 4; j++) { float v; asm volatile("mov.b32 %0, %1;\n" : "=f"(v) : "f"(acc[i][j])); acc[i][j] = v; }
}
struct Conv {
    uint32_t kw;
    uint32_t wa;
    uint32_t pa, s2;
    uint32_t s8;
    uint32_t id;
    uint32_t lc;
    uint32_t fs;
    uint32_t fl, yo;
    uint32_t yp;
    size_t ycopy;
    uint32_t ps;
    uint64_t d0;
    int warp;
};
struct Pk { uint32_t w[4]; };
__device__ __forceinline__ Pk pk2(const float (&u)[4], const float (&v)[4]) {
    Pk r;
    r.w[0] = pack_f16(u[0], u[1]); r.w[1] = pack_f16(u[2], u[3]); r.w[2] = pack_f16(v[0], v[1]); r.w[3] = pack_f16(v[2], v[3]);
    return r;
}
__device__ __forceinline__ void park(uint32_t a, const Pk& v) {
    asm volatile("stmatrix.sync.aligned.m8n8.x4.trans.shared.b16 [%0], {%1,%2,%3,%4};\n" ::"r"(a), "r"(v.w[0]), "r"(v.w[1]), "r"(v.w[2]), "r"(v.w[3]) : "memory");
}
__device__ __forceinline__ void conv_constants(uint32_t lc, int l) {
    const int d = (l >> 2) - 2 * (l & 3);
    const int e = d + 8, r4 = (e + 1 + ((e >> 2) & 1)) >> 2, p4 = (e + (((e - 1) >> 2) & 1)) >> 2;
    const uint32_t s2 = r4 == p4 ? 0x1010u : 0x3210u;
    sts64(lc + l * 8, KW_P + ((r4 - 5) >> 1) * 16 + ((r4 - 5) & 1) * 4, s2 | ((d < 0 ? s2 : 0x7654u) << 16));
    const int lo = (d >= 4) - (d < -3), ho = (d >= 5) - (d < -2), le = (d > 4) - (d < -4), he = (d > 5) - (d < -3);
    sts32(lc + 512 + l * 8, (0x5454u + lo * 0x22 + ho * 0x2200) | ((0x3232u + le * 0x22 + he * 0x2200) << 16));
    const int cc = l >> 2, j = l & 3;
    sts64(lc + 256 + l * 8, (j >> 1) * PL_HALF + (16 + cc) * 16 + (j & 1) * 8, (cc >> 1) * (DM * 64) + (cc & 1) * 32 + j * 8);
}
__device__ __forceinline__ void conv_selectors4(Conv& c) {
    const uint2 v = lds64(c.lc + lane_v() * 8);
    c.pa = v.x; c.s2 = v.y;
}
__device__ __forceinline__ void conv_selectors8(Conv& c) { c.s8 = lds32(c.lc + 512 + lane_v() * 8); }
template <int G, int I0, int I1>
__device__ __forceinline__ void conv_load(const Conv& c, uint32_t (&q)[9]) {
    const int wq = c.warp & 3;
    if (G < 2) {
#pragma unroll
        for (int i = I0; i < I1; i++) q[i] = lds32(c.wa + G * 512 + i * 16);
    } else if (G < 4) {
        const uint32_t a = (G == 2 && wq == 0) ? c.wa + 1024 : c.pa + c.kw + wq * 128 + (G < 2 ? 0 : G - 2) * 512;
#pragma unroll
        for (int i = I0; i < I1; i++) q[i] = lds32(a + i * 16);
    } else {
        const uint4 u = lds128(c.kw + KW_H + (G < 4 ? 0 : G - 4) * 64 + wq * 16);
        const uint2 v = lds64(c.kw + KW_H + (G < 4 ? 0 : G - 4) * 64 + wq * 16 + 16);
        q[0] = u.x; q[1] = u.y; q[2] = u.z; q[3] = u.w; q[4] = v.x; q[5] = v.y;
        if (G == 4 && wq == 0) { q[6] = lds32(c.pa + c.kw + 1024); q[7] = lds32(c.pa + c.kw + 1040); }
    }
}
template <int G, int J0, int J1>
__device__ __forceinline__ void conv_frag(const Conv& c, const uint32_t (&q)[9], uint32_t* a, const Pk& dp) {
    const uint32_t dep = dp.w[0];
    if (G < 4) {
        const uint32_t s = (G < 2 || (G == 2 && (c.warp & 3) == 0)) ? c.id : c.s2;
#pragma unroll
        for (int j = J0; j < J1; j++) {
            uint32_t* o = a + 4 * (j - J0);
            o[0] = prmt_v(q[2 * j + 1], dp.w[0], s); o[1] = prmt_v(q[2 * j + 2], dp.w[1], s); o[2] = prmt_v(q[2 * j], dp.w[2], s); o[3] = prmt_v(q[2 * j + 1], dp.w[3], s);
        }
    } else {
        const uint32_t so = prmt_v(c.s8, dep, c.id), se = prmt_v(c.s8, dep, c.id + 0x22);
#pragma unroll
        for (int j = J0; j < J1; j++) {
            uint32_t* o = a + 4 * (j - J0);
            o[0] = prmt_v(q[j + 1], q[j + 2], se); o[1] = prmt_v(q[j + 1], q[j + 2], so); o[2] = prmt_v(q[j], q[j + 1], so);
            if (G == 4 && j == 0 && (c.warp & 3) == 0) {
                o[2] = prmt_v(q[6], dep, c.s2);
                o[0] = prmt_v(q[7], o[0], c.s2 >> 16);
            }
            o[3] = mov_v(o[0]);
        }
    }
}
template <int G, int J0, int J1>
__device__ __forceinline__ void conv_frag(const Conv& c, const uint32_t (&q)[9], uint32_t* a, float depf) {
    const uint32_t d = __float_as_uint(depf);
    conv_frag<G, J0, J1>(c, q, a, Pk{{d, d, d, d}});
}
template <int G, int T, int J0, int J1>
__device__ __forceinline__ void conv_mma(float (&acc)[16][4], const Conv& c, const uint32_t* a) {
#pragma unroll
    for (int j = J0; j < J1; j++) wg_mma<T>(acc, a + 4 * (j - J0), c.d0 - 8 * (2 * G - T) - j);
}
__device__ __forceinline__ float h_lo(uint32_t w) { return __half2float(__ushort_as_half((unsigned short)(w & 0xffffu))); }
__device__ __forceinline__ float h_hi(uint32_t w) { return __half2float(__ushort_as_half((unsigned short)(w >> 16))); }
__device__ __forceinline__ void flush_setup(Conv& c) {
    const uint2 v = lds64(c.lc + 256 + lane_v() * 8);
    c.fl = v.x; c.yo = v.y;
}
template <int Q>
__device__ __forceinline__ void flush_load(const Conv& c, uint32_t pl, uint2 (&f)[4]) {
#pragma unroll
    for (int w = 0; w < 4; w++) f[w] = lds64(c.fl + pl + (Q & 1) * 512 + w * (PLW_B - 64));
}
template <int Q>
__device__ __forceinline__ void flush_load_first(const Conv& c, uint32_t pl, uint2 (&f)[4], float depf) {
    const uint32_t p = prmt_v(c.fl, __float_as_uint(depf), c.id) + pl + (Q & 1) * 512;
#define LDV64(d, a) asm volatile("ld.volatile.shared.v2.u32 {%0,%1}, [%2];\n" : "=r"(d.x), "=r"(d.y) : "r"(a) : "memory")
    LDV64(f[0], p); LDV64(f[1], p + (PLW_B - 64)); LDV64(f[2], p + 2 * (PLW_B - 64)); LDV64(f[3], p + 3 * (PLW_B - 64));
}
#define FDEP __uint_as_float(f[3].y)
template <int Q, int mode>
__device__ __forceinline__ void conv_flush(const Conv& c, const uint2 (&f)[4], unsigned char* gy, uint32_t rx) {
    const uint32_t a0 = hadd2(f[0].x, f[1].x), a1 = hadd2(f[2].x, f[3].x), b0 = hadd2(f[0].y, f[1].y), b1 = hadd2(f[2].y, f[3].y);
    if (Q > 0 && mode == 1) {
        const uint32_t ra = rx + 16 + (Q > 0 ? Q - 1 : 0) * 1024 + (c.warp & 3) * 256 + lane_v() * 8;
        asm volatile("st.async.shared::cluster.mbarrier::complete_tx::bytes.v2.b32 [%0], {%1,%2}, [%3];\n"
                     ::"r"(ra ^ 0x1000000u), "r"(hadd2(a0, a1)), "r"(hadd2(b0, b1)), "r"((rx + (Q > 1 ? 8 : 0)) ^ 0x1000000u) : "memory");
        return;
    }
    float v0 = h_lo(a0) + h_lo(a1), v1 = h_hi(a0) + h_hi(a1), v2 = h_lo(b0) + h_lo(b1), v3 = h_hi(b0) + h_hi(b1);
    if (Q > 0 && mode == 2) {
        const uint2 o = lds64(rx + 16 + (Q > 0 ? Q - 1 : 0) * 1024 + (c.warp & 3) * 256 + lane_v() * 8);
        v0 += h_lo(o.x); v1 += h_hi(o.x); v2 += h_lo(o.y); v3 += h_hi(o.y);
    }
    const uint32_t lo = hmul2_bf(pack_bf16(v0, v1), c.fs), hi = hmul2_bf(pack_bf16(v2, v3), c.fs);
    stg64(gy + Q * 32 * DM * 32 + (c.yo + (Q < 2 ? c.yp : 0u)), nzw(lo), nzw(hi));
}
template <int I, bool S = false> struct IC { static constexpr int value = I; static constexpr bool shared = S; };
template <class T> __device__ constexpr bool wg_is4() { return T::shared; }
#define SLOT(n) (c.ps + (2 + ((n) & 7)) * 128)
#define GO() do { wg_commit(); __syncwarp(); } while (0)
#define DEP acc[15][3]
template <class FG, class FP, class FN>
__device__ __forceinline__ void conv_head(Conv& c, float (&acc)[16][4], uint32_t (&q)[9], uint32_t (&r)[9], uint32_t* a, FG fg, FP pre, FN next) {
    c.id = 0x3210u + (c.warp >> 8);
    pre();
    conv_load<0, 0, 9>(c, q);
    conv_frag<0, 0, 1>(c, q, a, 0.f);
    wg_fence(); wg_first<0>(acc, a, c.d0); GO();
    park(c.ps, Pk{{0u, 0u, 0u, 0u}});
    wg_wait0();
    conv_frag<0, 1, 2>(c, q, a, DEP);
    wg_fence(); conv_mma<0, 0, 1, 2>(acc, c, a); GO();
    fg(IC<0>());
    wg_wait0();
    conv_frag<0, 2, 3>(c, q, a, DEP);
    wg_fence(); conv_mma<0, 0, 2, 3>(acc, c, a); GO();
    conv_load<1, 0, 5>(c, r);
    wg_wait0();
    conv_frag<0, 3, 4>(c, q, a, DEP);
    wg_fence(); conv_mma<0, 0, 3, 4>(acc, c, a); GO();
    conv_load<1, 5, 9>(c, r);
    fg(IC<1>());
    wg_wait0();
    const Pk k = pk2(acc[0], acc[1]);
    conv_rename<2>(acc);
    conv_frag<1, 0, 2>(c, r, a, k);
    wg_fence(); conv_mma<1, 2, 0, 2>(acc, c, a); GO();
    park(SLOT(0), k);
    next(IC<0>());
    fg(IC<2>());
    wg_wait0();
    conv_frag<1, 2, 4>(c, r, a, DEP);
    wg_fence(); conv_mma<1, 2, 2, 4>(acc, c, a); GO();
    next(IC<1>());
    fg(IC<3>());
    wg_wait0();
}
template <class FG, class FP>
__device__ __forceinline__ void conv_run(Conv& c, uint32_t pl, unsigned char* gy, FG fg, FP pre) {
    float acc[16][4];
    uint32_t q[9], r[9], a[32];
    uint2 f[4];
    const int bid = 1 + (c.warp >> 2);
    conv_head(c, acc, q, r, a, fg, pre, [&](auto i) { if (decltype(i)::value == 0) conv_selectors4(c); else conv_load<2, 0, 9>(c, q); });
    Pk k = pk2(acc[2], acc[3]);
    conv_rename<4>(acc);
    conv_frag<2, 0, 4>(c, q, a, k);
    wg_fence(); conv_mma<2, 4, 0, 4>(acc, c, a); GO();
    park(SLOT(2), k);
    conv_load<3, 0, 9>(c, q);
    flush_setup(c);
    bar_sync(bid, 128);
    fg(IC<4>());
    wg_wait0();
    conv_rename<6>(acc);
    conv_frag<3, 0, 4>(c, q, a, DEP);
    wg_fence(); conv_mma<3, 6, 0, 4>(acc, c, a); GO();
    park(SLOT(4), pk2(acc[4], acc[5]));
    conv_load<4, 0, 9>(c, q);
    conv_selectors8(c);
    flush_load<0>(c, pl, f);
    conv_flush<0, 0>(c, f, gy, 0u);
    fg(IC<5>());
    wg_wait0();
    conv_rename<8>(acc);
    conv_frag<4, 0, 4>(c, q, a, DEP);
    wg_fence(); conv_mma<4, 8, 0, 4>(acc, c, a); GO();
    k = pk2(acc[6], acc[7]);
    park(SLOT(6), k);
    conv_load<5, 0, 9>(c, q);
    bar_sync(bid, 128);
    park(c.ps, k);
    fg(IC<6>());
    wg_wait0();
    conv_rename<10>(acc);
    flush_load_first<1>(c, pl, f, DEP);
    conv_frag<5, 0, 4>(c, q, a, FDEP);
    wg_fence(); conv_mma<5, 10, 0, 4>(acc, c, a); GO();
    park(SLOT(8), pk2(acc[8], acc[9]));
    conv_load<6, 0, 9>(c, q); conv_load<7, 0, 9>(c, r);
    conv_flush<1, 0>(c, f, gy, 0u);
    fg(IC<7>());
    wg_wait0();
    conv_rename<12>(acc);
    conv_frag<6, 0, 4>(c, q, a, DEP); conv_frag<7, 0, 4>(c, r, a + 16, DEP);
    wg_fence(); conv_mma<6, 12, 0, 4>(acc, c, a); conv_mma<7, 12, 0, 4>(acc, c, a + 16); GO();
    park(SLOT(10), pk2(acc[10], acc[11]));
    bar_sync(bid, 128);
    flush_load<2>(c, pl, f);
    conv_flush<2, 0>(c, f, gy, 0u);
    fg(IC<8>());
    if (c.id == 0) TRAP();
    wg_wait0();
    park(SLOT(12), pk2(acc[12], acc[13])); park(SLOT(14), pk2(acc[14], acc[15]));
    bar_sync(bid, 128);
    flush_load<3>(c, pl, f);
    conv_flush<3, 0>(c, f, gy, 0u);
}
template <class FG>
__device__ __forceinline__ void conv_outer(Conv& c, uint32_t pl, unsigned char* gy, uint32_t rx, FG fg) {
    float acc[16][4];
    uint32_t q[9], r[9], a[32];
    uint2 f[4], f2[4];
    const int bid = 1 + (c.warp >> 2);
    conv_head(c, acc, q, r, a, [&](auto gi) { if (decltype(gi)::value == 2) fg(IC<2, true>()); }, [&]() {}, [&](auto i) { if (decltype(i)::value == 0) conv_selectors8(c); else conv_load<6, 0, 9>(c, q); });
    park(SLOT(2), pk2(acc[2], acc[3])); park(SLOT(4), pk2(acc[4], acc[5]));
    const Pk k = pk2(acc[6], acc[7]);
    park(SLOT(6), k);
    conv_load<7, 0, 9>(c, r);
    conv_rename<12>(acc);
    conv_frag<6, 0, 4>(c, q, a, __uint_as_float(k.w[3])); conv_frag<7, 0, 4>(c, r, a + 16, __uint_as_float(k.w[3]));
    wg_fence(); conv_mma<6, 12, 0, 4>(acc, c, a); conv_mma<7, 12, 0, 4>(acc, c, a + 16); GO();
    flush_setup(c);
    bar_sync(bid, 128);
    flush_load<0>(c, pl, f); flush_load<1>(c, pl, f2);
    conv_flush<1, 1>(c, f2, gy, rx);
    conv_flush<0, 1>(c, f, gy, rx);
    wg_wait0();
    bar_sync(bid, 128);
    park(c.ps, k); park(SLOT(8), pk2(acc[8], acc[9])); park(SLOT(10), pk2(acc[10], acc[11]));
    park(SLOT(12), pk2(acc[12], acc[13])); park(SLOT(14), pk2(acc[14], acc[15]));
    bar_sync(bid, 128);
    flush_load<2>(c, pl, f); flush_load<3>(c, pl, f2);
    conv_flush<2, 1>(c, f, gy, rx);
    conv_flush<3, 1>(c, f2, gy, rx);
}
template <class FG>
__device__ __forceinline__ void conv_inner(Conv& c, uint32_t pl, unsigned char* gy, uint32_t rx, FG fg) {
    float acc[16][4];
    uint32_t q[9], a[16];
    uint2 f[4], f2[4];
    const int bid = 1 + (c.warp >> 2);
    c.id = 0x3210u + (c.warp >> 8);
    conv_selectors4(c);
    conv_load<2, 0, 9>(c, q);
    conv_frag<2, 0, 4>(c, q, a, 0.f);
    wg_fence(); wg_first<4>(acc, a, c.d0); conv_mma<2, 4, 1, 4>(acc, c, a + 4); GO();
    conv_load<3, 0, 9>(c, q);
    park(SLOT(2), Pk{{0u, 0u, 0u, 0u}});
    fg(IC<2, true>());
    wg_wait0();
    conv_rename<6>(acc);
    conv_frag<3, 0, 4>(c, q, a, DEP);
    wg_fence(); conv_mma<3, 6, 0, 4>(acc, c, a); GO();
    park(SLOT(4), pk2(acc[4], acc[5]));
    conv_load<4, 0, 9>(c, q);
    conv_selectors8(c);
    wg_wait0();
    conv_rename<8>(acc);
    conv_frag<4, 0, 4>(c, q, a, DEP);
    wg_fence(); conv_mma<4, 8, 0, 4>(acc, c, a); GO();
    const Pk k = pk2(acc[6], acc[7]);
    park(SLOT(6), k); park(c.ps, k);
    conv_load<5, 0, 9>(c, q);
    flush_setup(c);
    wg_wait0();
    conv_rename<10>(acc);
    conv_frag<5, 0, 4>(c, q, a, DEP);
    wg_fence(); conv_mma<5, 10, 0, 4>(acc, c, a); GO();
    park(SLOT(8), pk2(acc[8], acc[9]));
    bar_sync(bid, 128);
    flush_load<1>(c, pl, f);
    mbar_wait(rx);
    conv_flush<1, 2>(c, f, gy, rx);
    wg_wait0();
    bar_sync(bid, 128);
    park(SLOT(10), pk2(acc[10], acc[11])); park(SLOT(12), pk2(acc[12], acc[13])); park(SLOT(14), pk2(acc[14], acc[15]));
    bar_sync(bid, 128);
    flush_load<3>(c, pl, f); flush_load<2>(c, pl, f2);
    mbar_wait(rx + 8);
    conv_flush<3, 2>(c, f, gy, rx);
    conv_flush<2, 2>(c, f2, gy, rx);
}
#undef SLOT
#undef GO
#undef DEP
template <int U0, int U1>
__device__ __forceinline__ void weight_units(uint32_t sb, const Maps& tm, bool w) {
    if (U1 > U0 && w && elect_one()) {
#pragma unroll
        for (int i = U0; i < U1; i++) {
            const int P = blockIdx.x >> 1, odd = blockIdx.x & 1;
            if (i < 12) tma_2d(sb + SM_WG + i * 6144, &tm.w[i / 6], 64 * P, 288 * odd + (i % 6) * 48, sb + SM_MISC + 328);
            else tma_2d(sb + SM_WD + (i - 12) * 4736, &tm.d, 144 * odd, i < 20 ? 64 * P + 8 * (i - 12) : 4096 + 8 * P, sb + SM_MISC + 336);
            if (i >= 8 && i < 12) tma_2d(sb + SM_WR + (i - 8) * 2304, &tm.r[(i - 8) >> 1], 4096 + 8 * P, 288 * odd + (i & 1) * 144, sb + SM_MISC + 328);
        }
    }
}
#define WS 2210121111113004000
__device__ constexpr int wsched(int i) {
    unsigned long long v = WS;
    int n = 0;
    for (int k = 19; k >= 1; k--) { if (k < i) n += (int)(v % 10); v /= 10; }
    return n;
}
static_assert(wsched(20) == 21 && wsched(6) <= 8 && wsched(11) <= 12 && wsched(13) <= 14 && wsched(16) <= 17 && wsched(16) == wsched(15) && wsched(19) == 21, "");
#define WANY(i) (wsched((i) + 1) > wsched(i))
#define WPOINT(i, w) do { weight_units<wsched(i), wsched(i + 1)>(sb, tm, w); } while (0)

__global__ void __launch_bounds__(NTHR, 1) __cluster_dims__(2, 1, 1)
fused_kernel(const Params p, const __grid_constant__ Maps tm) {
    extern __shared__ __align__(1024) unsigned char smem[];
    const uint32_t sb = smem_u32(smem);
    const int tid = threadIdx.x, warp = __shfl_sync(0xffffffffu, tid >> 5, 0), lane = tid & 31;
    const int b = blockIdx.x, P = b >> 1, odd = b & 1;
    const int g = lane >> 2, t = lane & 3;
    const int wg = warp >> 2, t128 = tid & 127;
    const uint32_t s_stat = sb + SM_MISC;
    const uint32_t s_key = sb + SM_MISC + 128;
    const uint32_t s_rank = sb + SM_MISC + 256;
    const uint32_t s_k16 = sb + SM_MISC + 192;
    const uint32_t s_cnt = sb + SM_MISC + 320;
    const uint32_t bar_w = sb + SM_MISC + 328, bar_d = bar_w + 8, bar_g = bar_w + 16, bar_x = bar_w + 24, bar_v = bar_w + 32, bar_s = bar_w + 40, bar_h = bar_w + 48;
    STAMP(0);

    const int ch = wg < 4 ? 4 * b + wg : 512 + P;
    const uint32_t mo = tid < 512 ? 512 * b + tid : 65536 + 128 * P + t128, mq = (mo & ~127u) + 4 * lane;
    const uint32_t pl = ldo16(p.lar + mo), pa2 = ldo16(p.aim + mo), ldt = ldo16(p.ldt + (mo >> 7));
    const uint32_t pc = ldo16(p.cre + mo), pi = ldo16(p.cim + mo);
    const uint2 call_re = ldo64(p.cre + mq), call_im = ldo64(p.cim + mq);
    const uint32_t epl = ld_poll32(p.s->hint + (b & 7) * 32 + 1);
    const uint32_t kw = sb + SM_KW + wg * KW_B;
    uint32_t co, cn, cd, uo;
    auto housekeeping = [&]() {
        if (t128 < 2 * UPAD) sts128(sb + SM_U + wg * USLOT_B + (t128 & 1) * ULO_B + (t128 >> 1) * 16, 0u, 0u, 0u, 0u);
        if (t128 >= 124) sts128(kw + (t128 & 1) * 16 + (t128 & 2) * (KW_PL / 2), 0u, 0u, 0u, 0u);
        if (warp < 15) sts128(sb + SM_Z2 + 4608 + tid * 16, 0u, 0u, 0u, 0u);
        combine_setup(sb, warp, lane, kw, co, cn, cd);
        co = pin(co); cn = pin(cn); cd = pin(cd);
        uo = pin(wg < 4 ? tid : 512 + (P >> 2) * 1024 + (t128 >> 1) * 8 + (P & 3) * 2 + (t128 & 1));
    };
    if (wg < 4) {
        bar_arrive(0, NWRK);
        asm volatile("barrier.cluster.arrive.relaxed.aligned;\n" ::: "memory");
        housekeeping();
    } else {
        const int o = (warp & 3) * 4608 + lane * 16;
        sts128(sb + SM_Z2 + t128 * 16, 0u, 0u, 0u, 0u); sts128(sb + SM_Z2 + 2048 + t128 * 16, 0u, 0u, 0u, 0u);
        if (warp == 16) sts128(sb + SM_Z2 + 4096 + lane * 16, 0u, 0u, 0u, 0u);
        fence_async();
        bar_sync(0, NWRK);
        STAMP(9);
#pragma unroll
        for (int c = 0; c < 9; c++)
            asm volatile("cp.async.cg.shared.global [%0], [%1], 16;\n" ::"r"(sb + SM_XT + o + c * 512), "l"(reinterpret_cast<const char*>(p.x) + b * 18432 + o + c * 512) : "memory");
        asm volatile("cp.async.commit_group;\n" ::: "memory");
        if (elect_one()) {
            mbar_init(bar_h + 8 * (warp & 3), 1);
            if (warp == 19) {
                mbar_init(bar_x, 1); mbar_init(bar_w, 1);
                mbar_expect(bar_x, 32768); mbar_expect(bar_w, 82944);
#pragma unroll
                for (int i = 2; i < 4; i++) bulk_s2g(reinterpret_cast<unsigned char*>(p.s->y) + 32 * i * 18432 + b * 4608, sb + SM_Z2, 4608);
            } else if (warp == 18) {
                mbar_init(bar_s, 1); mbar_init(bar_v, 2); mbar_init(bar_d, 1); mbar_init(bar_g, 1); mbar_init(sb + SM_RX, 1); mbar_init(sb + SM_RX + 8, 1);
                mbar_expect(bar_v, 2 * 1152); mbar_expect(bar_d, 72 * WD_PITCH); mbar_expect(bar_g, 4608); mbar_expect(sb + SM_RX, 1024); mbar_expect(sb + SM_RX + 8, 2048);
            }
            asm volatile("fence.mbarrier_init.release.cluster;\n" ::: "memory");
        }
        __syncwarp();
        asm volatile("barrier.cluster.arrive.relaxed.aligned;\n" ::: "memory");
        if (warp == 19) {
            asm volatile("barrier.cluster.wait.aligned;\n" ::: "memory");
            if (elect_one()) tma_4d_mc(sb + SM_XC + odd * 16384, &tm.x, 8 * P, 2 * odd, bar_x);
            __syncwarp();
        }
    }
    const uint32_t tb = table_buf(sb, warp), t5 = sb + SM_WD + warp * 512;
    STAMP(29);
    const float dt = exp_bf(bf_lo(ldt));
    const uint32_t ep = __reduce_or_sync(0xffffffffu, epl);
    auto stats = [&]() {
        const int wq = warp & 3;
        const uint32_t xa = sb + SM_XT + (4 * wq + (g >> 1)) * 1152 + (g & 1) * 576 + t * 16;
        const bool own = !(g & 1) && t == (g >> 1);
        float d[4][4] = {};
        asm volatile("cp.async.wait_group 0;\n" ::: "memory");
        __syncwarp();
        STAMP(26);
        uint4 v[9];
#pragma unroll
        for (int c = 0; c < 9; c++) v[c] = lds128(xa + c * 64);
#pragma unroll
        for (int c = 0; c < 9; c++) {
            mma_bf16(d[2 * (c & 1)], v[c].x, 0x3f803f80u, v[c].y, 0x3f803f80u, v[c].x, v[c].y);
            mma_bf16(d[2 * (c & 1) + 1], v[c].z, 0x3f803f80u, v[c].w, 0x3f803f80u, v[c].z, v[c].w);
        }
        STAMP(27);
        float sm = (g & 1) ? (d[0][3] + d[1][3]) + (d[2][3] + d[3][3]) : (d[0][2] + d[1][2]) + (d[2][2] + d[3][2]);
        float sq = (g & 1) ? (d[0][1] + d[1][1]) + (d[2][1] + d[3][1]) : (d[0][0] + d[1][0]) + (d[2][0] + d[3][0]);
        sm += __shfl_xor_sync(0xffffffffu, sm, 4); sq += __shfl_xor_sync(0xffffffffu, sq, 4);
        if (lane == 0) mbar_arrive(bar_h + 8 * wq);
        float mb, sd;
        ln_stats(sm, sq, mb, sd);
        if (own) p.s->stat[16 * b + 4 * wq + t] = (__float_as_uint(mb) >> 16) | (__float_as_uint(sd) & 0x7fff0000u) | (ep << 31);
        STAMPX(22);
        if (own) stat_store(s_stat + (2 * wq + (t & 1) + 8 * (t >> 1)) * 8, mb, rcp_approx(sd), 0u);
        if (wq == 3) asm volatile("cp.async.bulk.wait_group 0;\n" ::: "memory");
        bar_sync(5, 128);
        STAMP(28);
        uint32_t now;
        asm volatile("mov.u32 %0, %%clock;" : "=r"(now) :: "memory");
        if (wq == 2) {
            if (lane == 0) {
                sts64(s_cnt, now, ep);
                mbar_arrive(bar_s);
                bulk_g2s(sb + SM_XT + 16 * 1152, p.dsk, 1152, bar_v);
                bulk_g2s(sb + SM_XT + 17 * 1152, p.wr, 1152, bar_v);
            }
            __syncwarp();
        }
        WPOINT(1, wq == 3);
        if (wq < 2) {
            unsigned char* const ud = reinterpret_cast<unsigned char*>(p.s->uT) + (size_t)(8 * wq + 2 * (g >> 1)) * 16384 + b * 128 + (g & 1) * 32 + t * 8;
            const uint32_t utag = (ep % 7u + 1u) * 0x10001u;
            uint32_t U[2][4];
#pragma unroll
            for (int hf = 0; hf < 2; hf++) {
                const uint2 st = lds64(s_stat + (g + 8 * hf) * 8);
                const uint4 xu = lds128(sb + SM_XT + (TOK(g) + 2 * hf) * 1152 + warp * 64 + t * 16);
                const uint32_t X[4] = {xu.x, xu.y, xu.z, xu.w};
#pragma unroll
                for (int k = 0; k < 4; k++) {
                    const uint32_t u = ln_apply(X[k], STAT_M(st), STAT_H(st), STAT_L(st));
                    U[hf][k] = movm((pack_f16(bf_lo(u), bf_hi(u)) & 0xfff8fff8u) | utag);
                }
            }
#pragma unroll
            for (int k = 0; k < 4; k++) stg64(ud + (k >> 1) * 16384 + (k & 1) * 64, U[0][k], U[1][k]);
        }
    };
    STAMP(1);
    if (wg < 4) { STAMPX(16); }
    KGen kg;
    kgen_setup(kg, bf_lo(pl), bf_lo(pa2), dt);
    kgen_rows(kg, tb, lane);
    STAMP(2);
    const int E = min(max(c_exponent(call_re, call_im, dt) - 243, -120), 120);
    kgen_chain(kg, pc, pi, dt * __uint_as_float((uint32_t)(128 - E) << 23));
    STAMP(3);
    kgen_cols(kg, tb, t5, lane);
    STAMP(4);
    if (warp != 19) asm volatile("barrier.cluster.wait.aligned;\n" ::: "memory");
    if (wg == 4) {
        if (warp == 18) conv_constants(sb + SM_LC, lane);
        stats();
    }
    if (wg < 4) { STAMPX(17); }
    if (wg == 4) housekeeping();
    const uint4* const usrc = reinterpret_cast<const uint4*>(p.s->stat) + uo;
    uint32_t trel;
    kgen_mma(kg, tb, t5, lane, [&]() {
        if (wg < 4) mbar_wait(bar_h + 8 * (warp & 3));
        asm volatile("mov.u32 %0, %%clock;" : "=r"(trel) :: "memory");
    });
    if (wg < 4) { STAMPX(20); }
    STAMP(5);
    uint4 uv0, uv1;
    auto first_poll = [&](uint32_t dly) {
        mbar_wait(bar_s);
        const uint32_t t0 = lds32(s_cnt);
        uint32_t now;
        do { asm volatile("mov.u32 %0, %%clock;" : "=r"(now) :: "memory"); } while (now - t0 < dly);
        uv0 = ld_poll(usrc);
    };
    if (wg == 4) { first_poll(UDLY); uv1 = ld_poll(usrc + 512); }
    WPOINT(2, warp == 19);
    auto stat_poll = [&]() {
        uint32_t now;
        do { asm volatile("mov.u32 %0, %%clock;" : "=r"(now) :: "memory"); } while (now - trel < SDLY);
        uv0 = ld_poll(usrc);
    };
    bar_sync(1 + wg, 128);
    if (wg < 4) { STAMPX(21); }
    kgen_combine(warp & 3, lane, co, cn, cd);
    STAMP(6);
    if (wg < 4) { STAMPX(18); }
    WPOINT(3, warp == 19);
    if (wg < 4) stat_poll();
    {
        const int wq = warp & 3;
        Conv c;
        const uint32_t pln = sb + SM_PL + wg * PL_B;
        const int e = g - 2 * t + 7;
        c.kw = kw; c.wa = pin(kw + ((e >> 2) & 1) * KW_PL + (8 * wq + (e >> 3)) * 16 + (e & 3) * 4);
        c.ps = mov_v(pln + wq * PLW_B + ((lane >> 3) & 1) * PL_HALF + ((lane >> 4) * 8 + (lane & 7)) * 16); c.warp = warp;
        c.lc = sb + SM_LC; c.fs = (uint32_t)(127 + E) * 0x800080u; c.yp = (ep & 1u) * (NCTA * 18432u);
        c.d0 = ((uint64_t)(ULO_B >> 4) << 16) | ((uint64_t)(128 >> 4) << 32) | (uint64_t)(((sb + SM_U + wg * USLOT_B + UPAD * 16) & 0x3FFFF) >> 4);
        unsigned char* gy = reinterpret_cast<unsigned char*>(p.s->y) + ((size_t)(4 * wq) * DM + ch) * 64;
        auto hook = [&](auto gi) {
                     constexpr int G = decltype(gi)::value;
                     if (G == (wg_is4<decltype(gi)>() ? 2 : 5)) asm volatile("barrier.cluster.wait.aligned;\n" ::: "memory");
                     if (!wg_is4<decltype(gi)>() && G == 1) mbar_wait(bar_s);
                     if (!wg_is4<decltype(gi)>() && (G == 0 || G == 2) && warp == HW && elect_one()) {
                         unsigned char* const sc = reinterpret_cast<unsigned char*>(p.s);
                         if (G == 0) {
                             if (b < 96) bulk_s2g_nc(sc + offsetof(Scratch, part) + b * 6144, sb + SM_Z2, 6144);
                             bulk_s2g(sc + offsetof(Scratch, rows) + (127 - b) * 4608, sb + SM_Z2, 4608);
                         }
                         if (G == 2) {
                             bulk_s2g(sc + offsetof(Scratch, y) + (NCTA * 18432u - c.yp) + b * 9216, sb + SM_Z2, 9216);
                         }
                     }
                     if (!wg_is4<decltype(gi)>()) WPOINT(6 + G, warp == (G >= 7 ? HW : 4 * (G % 3) + 1));
                     if (!wg_is4<decltype(gi)>() && G == 6 && warp == HW) {
                         asm volatile("cp.async.bulk.wait_group 0;\n" ::: "memory");
                         __syncwarp();
                         if (elect_one()) mbar_arrive(bar_v);
                     }
                 };
        if (wg < 4) {
            asm volatile("barrier.cluster.arrive.relaxed.aligned;\n" ::: "memory");
            conv_run(c, pln + wq * 128, gy, hook, [&]() {
                STAMPX(23);
                mbar_wait(bar_x);
                STAMPX(24);
                uint2 xc[4];
                uint32_t xw[4][2];
#pragma unroll
                for (int j = 0; j < 4; j++) xc[j] = lds64(sb + SM_XC + wg * 8192 + j * 2048 + t128 * 16 + odd * 8);
#pragma unroll
                for (int i = 0; i < 8; i++) {
                    const int k = i >> 1, h = i & 1;
                    xw[k][h] = prmt_v(k < 2 ? xc[2 * h].x : xc[2 * h].y, k < 2 ? xc[2 * h + 1].x : xc[2 * h + 1].y, (k & 1) ? 0x7632 : 0x5410);
                }
                const uint32_t ub = mov_v(sb + SM_U + UPAD * 16 + ((tid >> 1) & 1) * ULO_B + (tid >> 2) * 16 + (tid & 1) * 8), tag = ep << 31;
                int it = 0;
                while (min(min((int)(uv0.x ^ tag), (int)(uv0.y ^ tag)), min((int)(uv0.z ^ tag), (int)(uv0.w ^ tag))) < 0x10000) {
                    if (++it > SPIN_LIMIT) TRAP();
                    uv0 = ld_poll(usrc);
                }
                STAMP(8);
                STAMPX(26);
                const float r0 = rcp_approx(fabsf(bf_hi(uv0.x))), r1 = rcp_approx(fabsf(bf_hi(uv0.y))), r2 = rcp_approx(fabsf(bf_hi(uv0.z))), r3 = rcp_approx(fabsf(bf_hi(uv0.w)));
                const uint32_t m[2] = {__byte_perm(uv0.x, uv0.y, 0x5410), __byte_perm(uv0.z, uv0.w, 0x5410)};
                const uint32_t rh[2] = {pack_bf16(r0, r1), pack_bf16(r2, r3)};
                const uint32_t rl[2] = {pack_bf16(r0 - bf_lo(rh[0]), r1 - bf_hi(rh[0])), pack_bf16(r2 - bf_lo(rh[1]), r3 - bf_hi(rh[1]))};
#pragma unroll
                for (int k = 0; k < 4; k++) {
                    const uint32_t u0 = ln_apply(xw[k][0], m[0], rh[0], rl[0]), u1 = ln_apply(xw[k][1], m[1], rh[1], rl[1]);
                    sts64(ub + k * USLOT_B, pack_f16(bf_lo(u0), bf_hi(u0)), pack_f16(bf_lo(u1), bf_hi(u1)));
                }
                STAMPX(29);
                fence_async();
                bar_sync(14, 512);
                STAMP(7);
            });
        } else {
            auto stage = [&]() {
                const uint32_t tag = (ep % 7u + 1u) * 0x10001u;
                int it = 0;
                WPOINT(4, warp == 19);
                while (true) {
                    uv0.x ^= tag; uv0.y ^= tag; uv0.z ^= tag; uv0.w ^= tag; uv1.x ^= tag; uv1.y ^= tag; uv1.z ^= tag; uv1.w ^= tag;
                    if ((((uv0.x | uv0.y | uv0.z) | (uv0.w | uv1.x | uv1.y) | (uv1.z | uv1.w)) & 0x70007u) == 0) break;
                    if (++it > SPIN_LIMIT) TRAP();
                    uv0 = ld_poll(usrc); uv1 = ld_poll(usrc + 512);
                }
                STAMP(8);
                const uint32_t ub = sb + SM_U + UPAD * 16 + 4 * USLOT_B + (t128 & 1) * ULO_B + (t128 >> 1) * 16;
                sts128(ub, uv0.x, uv0.y, uv0.z, uv0.w);
                sts128(ub + 1024, uv1.x, uv1.y, uv1.z, uv1.w);
                fence_async();
                asm volatile("barrier.cluster.arrive.relaxed.aligned;\n" ::: "memory");
                bar_sync(5, 128);
                WPOINT(5, warp == 19);
                STAMP(7);
            };
            stage();
            if (odd) conv_inner(c, pln + wq * 128, gy, sb + SM_RX, hook);
            else conv_outer(c, pln + wq * 128, gy, sb + SM_RX, hook);
        }
        STAMP(10);
    }
    {
    const int lane = lane_v(), tid = 32 * warp + lane, g = lane >> 2, t = lane & 3;
    const uint32_t par = ~ep & 1u;
    bar_sync(0, NWRK);
    STAMP(11);
    uint32_t H[2][4] = {}, U2[2][4] = {};
    auto publish = [&](bool hi, int slot) {
        uint4* rowp = reinterpret_cast<uint4*>(p.s->rows) + slot * 144 + warp * 4 + t;
        stg128(rowp, nzw(hi ? U2[1][0] : U2[0][0]), nzw(hi ? U2[1][1] : U2[0][1]), nzw(hi ? U2[1][2] : U2[0][2]), nzw(hi ? U2[1][3] : U2[0][3]));
        stg128(rowp + 72, nzw(hi ? H[1][0] : H[0][0]), nzw(hi ? H[1][1] : H[0][1]), nzw(hi ? H[1][2] : H[0][2]), nzw(hi ? H[1][3] : H[0][3]));
    };
#define KTOK(k) (int)(((~(k) >> 5) & 0x7f0u) | (((k) >> 1) & 15u))
#define KLATE(k) (((k) & 0x1e0u) < 0xe0u)
#define KSLOT(k, s) (KLATE(k) ? 2 * NCTA + (s) : (int)(((k) >> 8) & 0xffu))
    const uint4* const rsrc = reinterpret_cast<const uint4*>(p.s->rows) + 36 * odd;
    auto gather = [&](uint32_t mine) {
        int it = 0;
        uint32_t mn;
        do {
            mn = 1;
#pragma unroll 1
            for (int r = 0; r < 9; r++) {
                const uint32_t k = __shfl_sync(0xffffffffu, mine, r < 8 ? 4 * r : lane);
                const int row = r < 8 ? r : g, c = r < 8 ? lane : 32 + t;
                asm volatile("cp.async.cg.shared.global [%0], [%1], 16;\n" ::"r"(sb + SM_XS + row * XS_PITCH + c * 16), "l"(rsrc + KSLOT(k, row) * 144 + c) : "memory");
            }
            asm volatile("cp.async.wait_all;\n" ::: "memory");
#pragma unroll 1
            for (int r = 0; r < 9; r++) mn = min(mn, min4(lds128(sb + SM_XS + (r < 8 ? r * XS_PITCH + lane * 16 : g * XS_PITCH + (32 + t) * 16))));
            if (++it > SPIN_LIMIT) TRAP();
        } while (__any_sync(0xffffffffu, mn == 0));
    };
    auto late_rows = [&](auto role) {
        if (decltype(role)::value == 1) {
            int it = 0;
            uint4 k[8];
            uint32_t bad;
            do {
                bad = 0;
#pragma unroll
                for (int i = 0; i < 8; i++) k[i] = ld_poll(reinterpret_cast<const uint4*>(p.s->key) + 32 * i + lane);
#pragma unroll
                for (int i = 0; i < 8; i++) bad = or3(bad, xor_or(k[i].x, k[i].y, par), xor_or(k[i].z, k[i].w, par));
                if (++it > SPIN_LIMIT) TRAP();
            } while (__any_sync(0xffffffffu, bad & 1u));
#pragma unroll 1
            for (int r = 0; r < 8; r++) {
                uint32_t c = 0;
#pragma unroll
                for (int i = 0; i < 8; i++) c = max(c, k[i].x);
                const uint32_t m = __reduce_max_sync(0xffffffffu, c);
#pragma unroll
                for (int i = 0; i < 8; i++) if (k[i].x == m) k[i] = make_uint4(k[i].y, k[i].z, k[i].w, 0u);
                if (lane == 0) sts32(s_key + r * 4, m);
            }
        }
        bar_sync(0, NWRK);
        const uint32_t kk = lds32(s_key + (lane & 7) * 4), ep = lds32(s_cnt + 4);
        const bool own = KLATE(kk) && (KTOK(kk) >> 4) == b;
        uint32_t todo = __ballot_sync(0xffffffffu, own) & 0xffu;
        if (decltype(role)::value == 0 && todo) {
#pragma unroll
            for (int hf = 0; hf < 2; hf++) {
                const uint4 h = lds128(sb + SM_U + hf * 9216 + tid * 16);
                const uint2 st = lds64(s_stat + (g + 8 * hf) * 8);
                H[hf][0] = h.x; H[hf][1] = h.y; H[hf][2] = h.z; H[hf][3] = h.w;
#pragma unroll
                for (int k = 0; k < 4; k++) U2[hf][k] = ln_apply(H[hf][k], STAT_M(st), STAT_H(st), STAT_L(st));
            }
#pragma unroll 1
            while (todo) {
                const int s = __ffs(todo) - 1, tk = KTOK(__shfl_sync(0xffffffffu, kk, s));
                todo &= todo - 1;
                if ((tk & 13) == TOK(g)) publish(tk & 2, 2 * NCTA + s);
            }
            __threadfence();
        }
        bar_sync(0, NWRK);
        if (decltype(role)::value == 1) {
            if (lane < NSEL && own) *reinterpret_cast<volatile unsigned*>(p.s->flag + lane) = ep + 1u;
            int it = 0;
            while (__any_sync(0xffffffffu, KLATE(kk) && ld_acquire32(p.s->flag + (lane & 7)) != ep + 1u)) { if (++it > SPIN_LIMIT) TRAP(); }
            gather(__shfl_sync(0xffffffffu, kk, g));
        }
        bar_sync(0, NWRK);
    };
    if (warp < 18) {
        const unsigned char* ys = reinterpret_cast<const unsigned char*>(p.s->y) + (b < 64 ? (par ^ 1u) * (NCTA * 18432u) : 0u) +
                                  ((P * DM + 32 * warp + 8 * (g >> 1) + (g & 1)) * 64 + odd * 32 + t * 8);
        mbar_wait(bar_v);
        const uint32_t xa = sb + SM_XT + warp * 64 + t * 16;
        const uint4 x0 = lds128(xa + TOK(g) * 1152), x1 = lds128(xa + (TOK(g) + 2) * 1152), dk = lds128(xa + 16 * 1152);
        uint4 wr = make_uint4(0u, 0u, 0u, 0u);
        if (g == 0) wr = lds128(xa + 17 * 1152);
        uint2 yv[4];
        const uint32_t Z[2][4] = {{x0.x, x0.y, x0.z, x0.w}, {x1.x, x1.y, x1.z, x1.w}}, D4[4] = {dk.x, dk.y, dk.z, dk.w};
#pragma unroll
        for (int hf = 0; hf < 2; hf++) {
            const uint2 st = lds64(s_stat + (g + 8 * hf) * 8);
#pragma unroll
            for (int k = 0; k < 4; k++) U2[hf][k] = hmul2_bf(ln_apply(Z[hf][k], STAT_M(st), STAT_H(st), STAT_L(st)), D4[k]);
        }
        const uint32_t la = pin(sb + SM_LNP + (g * 20 + warp) * 4);
        {
            const unsigned char* y1 = ys + (U2[0][0] & U2[1][2] & (warp >> 8));
#pragma unroll
            for (int k = 0; k < 4; k++) yv[k] = ld_poll64(y1 + k * 128);
        }
        int it = 0;
        float d[2][4];
        while (true) {
            const uint32_t mn = min3(min3(yv[0].x, yv[0].y, yv[1].x), min3(yv[1].y, yv[2].x, yv[2].y), min(yv[3].x, yv[3].y));
#pragma unroll
            for (int k = 0; k < 4; k++) {
                H[0][k] = hadd2_bf(Z[0][k], hadd2_bf(movm(yv[k].x), U2[0][k]));
                H[1][k] = hadd2_bf(Z[1][k], hadd2_bf(movm(yv[k].y), U2[1][k]));
            }
            ln_partial(H, d);
            if (!__any_sync(0xffffffffu, mn == 0)) break;
            if (++it > SPIN_LIMIT) TRAP();
#pragma unroll
            for (int k = 0; k < 4; k++) yv[k] = ld_poll64(ys + k * 128);
        }
        STAMP(12);
        {
            const float s0 = (g & 1) ? d[0][3] : d[0][2], s1 = (g & 1) ? d[1][3] : d[1][2];
            const float q0 = (g & 1) ? d[0][1] : d[0][0], q1 = (g & 1) ? d[1][1] : d[1][0];
            asm volatile("{\n.reg .pred p;\nsetp.eq.u32 p, %5, %6;\n@p st.shared.f32 [%0], %1;\n@p st.shared.f32 [%0 + 640], %2;\n@p st.shared.f32 [%0 + 1280], %3;\n@p st.shared.f32 [%0 + 1920], %4;\n}\n"
                         ::"r"(la), "f"(s0), "f"(s1), "f"(q0), "f"(q1), "r"(t), "r"(g >> 1) : "memory");
        }
        bar_arrive(6, NWRK);
        STAMP(13);
        bar_sync(7, 608);
        STAMP(14);
#pragma unroll
        for (int hf = 0; hf < 2; hf++) {
            const uint2 st = lds64(s_stat + (g + 8 * hf) * 8);
#pragma unroll
            for (int k = 0; k < 4; k++) U2[hf][k] = ln_apply(H[hf][k], STAT_M(st), STAT_H(st), STAT_L(st));
        }
        {
            float cs[4] = {0.f, 0.f, 0.f, 0.f};
            mma_bf16(cs, U2[0][0], U2[1][0], U2[0][1], U2[1][1], wr.x, wr.y);
            mma_bf16(cs, U2[0][2], U2[1][2], U2[0][3], U2[1][3], wr.z, wr.w);
            if (t == 0) { stsf(la + 32 * 80, cs[0]); stsf(la + 40 * 80, cs[2]); }
            bar_arrive(8, 608);
        }
        FIX((uint32_t)warp >> 8);
        uint32_t O[2][4];
#pragma unroll
        for (int hf = 0; hf < 2; hf++)
#pragma unroll
            for (int k = 0; k < 4; k++) { O[hf][k] = hadd2_bf(H[hf][k], U2[hf][k]); H[hf][k] = nzw(H[hf][k]); U2[hf][k] = nzw(U2[hf][k]); }
        unsigned char* rowp = reinterpret_cast<unsigned char*>(p.s->rows) + ((254 - 2 * b) * 2304 + warp * 64 + t * 16);
        FIX(and3(and3(and3(H[0][0], H[0][1], H[0][2]), and3(H[0][3], H[1][0], H[1][1]), and3(H[1][2], H[1][3], U2[0][0])),
                 and3(and3(U2[0][1], U2[0][2], U2[0][3]), and3(U2[1][0], U2[1][1], U2[1][2]), U2[1][3]), (uint32_t)reinterpret_cast<uint64_t>(rowp)));
        bar_sync(9, 608);
        {
            const uint2 best = lds64(s_rank);
#pragma unroll
            for (int hf = 0; hf < 2; hf++) {
                const uint32_t me = 2 * TOK(g) + 4 * hf;
                unsigned char* d = rowp + (best.x == me ? 2304 : 0);
                if (best.x == me || best.y == me) {
                    stg128(d, U2[hf][0], U2[hf][1], U2[hf][2], U2[hf][3]);
                    stg128(d + 1152, H[hf][0], H[hf][1], H[hf][2], H[hf][3]);
                }
            }
        }
        FIX((uint32_t)warp >> 9);
#pragma unroll
        for (int hf = 0; hf < 2; hf++) {
            sts128(sb + SM_OUT + (TOK(g) + 2 * hf) * (DM * 2) + warp * 64 + t * 16, O[hf][0], O[hf][1], O[hf][2], O[hf][3]);
            sts128(sb + SM_U + hf * 9216 + tid * 16, H[hf][0], H[hf][1], H[hf][2], H[hf][3]);
        }
        STAMP(15);
        const int mi = lane >> 3, rr = lane & 7;
        const bool gate = warp < 12 && (warp & 3) != 2;
        const int fj = gate ? 3 * (warp >> 2) + min(warp & 3, 2) : (warp < 12 ? warp >> 2 : warp - 9);
        if (gate) {
            uint32_t W[18][4];
            mbar_wait(bar_w);
            const uint32_t aad = fj < 8 ? sb + SM_WG + (mi & 1) * SM_WU + (rr + 8 * (mi >> 1)) * 128 + (fj ^ rr) * 16 : sb + SM_WR + (mi & 1) * 4608 + (rr + 8 * (mi >> 1)) * 16;
            const uint32_t ast = fj < 8 ? 2048 : 256;
            const uint32_t bad = pin(sb + SM_XS + rr * XS_PITCH + mi * 16);
            bool rare = warp >> 8;
#pragma unroll 1
            do {
                if (rare) late_rows(IC<0>());
#pragma unroll
                for (int k = 0; k < 18; k++) ldsm_x4_t(W[k][0], W[k][1], W[k][2], W[k][3], aad + k * ast);
                if (rare) break;
                fence_async();
                STAMP2(17);
                rare = bar_or(11, NWRK, false);
            } while (rare);
            STAMP2(19);
            float c4[2][4] = {};
#pragma unroll
            for (int k = 0; k < 18; k += 2) {
                uint32_t b0, b1, b2, b3;
                ldsm_x4(b0, b1, b2, b3, bad + k * 32);
                mma_bf16(c4[0], W[k][0], W[k][1], W[k][2], W[k][3], b0, b1);
                mma_bf16(c4[1], W[k + 1][0], W[k + 1][1], W[k + 1][2], W[k + 1][3], b2, b3);
            }
            const uint32_t ex = sb + SM_EX + (32 * fj + lane) * 16;
            const float e0 = c4[0][0] + c4[1][0], e1 = c4[0][1] + c4[1][1], e2 = c4[0][2] + c4[1][2], e3 = c4[0][3] + c4[1][3];
            asm volatile("st.async.shared::cluster.mbarrier::complete_tx::bytes.v4.f32 [%0], {%1,%2,%3,%4}, [%5];\n"
                         ::"r"(ex ^ 0x1000000u), "f"(e0), "f"(e1), "f"(e2), "f"(e3), "r"(bar_g ^ 0x1000000u) : "memory");
            STAMP2(20);
            mbar_wait(bar_g);
            const uint4 o = lds128(ex);
            const uint32_t G = pack_bf16(e0 + __uint_as_float(o.x), e1 + __uint_as_float(o.y)), U = pack_bf16(e2 + __uint_as_float(o.z), e3 + __uint_as_float(o.w));
            sts32(sb + SM_GU + (32 * fj + lane) * 4, hmul2_bf(pack_bf16(bf_lo(G) * sigmoid_f(bf_lo(G)), bf_hi(G) * sigmoid_f(bf_hi(G))), U));
            bar_arrive(13, NWRK);
        } else {
            uint32_t W[2][18];
            auto load_wd = [&]() {
                mbar_wait(bar_d);
                const uint32_t base = sb + SM_WD + (4 * fj + (mi & 1)) * 16 + rr * WD_PITCH;
#pragma unroll
                for (int j = 0; j < 2; j++) {
#pragma unroll
                    for (int k = 0; k < 4; k++) ldsm_x4_t(W[j][4 * k], W[j][4 * k + 1], W[j][4 * k + 2], W[j][4 * k + 3], base + j * 32 + (k * 16 + 8 * (mi >> 1)) * WD_PITCH);
                    ldsm_x2_t(W[j][16], W[j][17], base + j * 32 + 64 * WD_PITCH);
                }
            };
            const uint32_t po = pin((((8 * (18 * odd + 2 * fj) + g) * 64 + P) * 4 + t) * 8);
            fence_async();
            STAMP2(17);
            const bool first = (warp & 3) != 2;
#pragma unroll 1
            for (int i = 0; i < 2; i++) {
                if (i == (first ? 1 : 0)) {
                    if (bar_or(11, NWRK, false)) late_rows(IC<0>());
                    if (!first) delay(DDLY);
                } else load_wd();
            }
            bar_sync(13, NWRK);
            STAMP2(21);
            uint32_t gb[9];
            ldsm_x4_t(gb[0], gb[1], gb[2], gb[3], sb + SM_GU + lane * 16);
            ldsm_x4_t(gb[4], gb[5], gb[6], gb[7], sb + SM_GU + 512 + lane * 16);
            ldsm_x1_t(gb[8], sb + SM_GU + 1024 + lane * 16);
            float c4[2][4] = {}, d4[2][4] = {};
#pragma unroll
            for (int k = 0; k < 4; k += 2)
#pragma unroll
                for (int j = 0; j < 2; j++) {
                    mma_bf16(c4[j], W[j][4 * k], W[j][4 * k + 1], W[j][4 * k + 2], W[j][4 * k + 3], gb[2 * k], gb[2 * k + 1]);
                    mma_bf16(d4[j], W[j][4 * k + 4], W[j][4 * k + 5], W[j][4 * k + 6], W[j][4 * k + 7], gb[2 * k + 2], gb[2 * k + 3]);
                }
#pragma unroll
            for (int j = 0; j < 2; j++) mma_bf16_k8(c4[j], W[j][16], W[j][17], gb[8]);
#pragma unroll
            for (int j = 0; j < 2; j++)
                stg64(reinterpret_cast<unsigned char*>(p.s->part) + po + j * 16384, nzw(pack_bf16(c4[j][0] + d4[j][0], c4[j][1] + d4[j][1])), nzw(pack_bf16(c4[j][2] + d4[j][2], c4[j][3] + d4[j][3])));
        }
        STAMP2(22);
    } else if (warp == 18) {
        const uint4* const ksrc = reinterpret_cast<const uint4*>(p.s->key3) + pin(2 * lane);
        const int row = (g >> 1) + 4 * (g & 1);
        const uint32_t ro = pin(640 * odd + t * 16), xd = pin(sb + SM_XS + row * XS_PITCH + t * 16 + (odd ? 0 : 512));
        const uint32_t xe = pin(sb + SM_XS + (g >> 1) * XS_PITCH + (lane & 7) * 16 + 64 * odd);
        const uint32_t sa = pin(sb + SM_LNP + lane * 80);
        const uint32_t klo = pin((uint32_t)(127 - b) << 9 | (uint32_t)(15 - ROWTOK(lane & 15)) << 1 | par), ra = pin(sb + SM_LNP + (32 + (lane & 15)) * 80);
        uint4* const kdst = reinterpret_cast<uint4*>(p.s->key3) + pin((lane >> 1) * 2 * NCTA + 2 * b + (lane & 1));
        FIX(ra);
        bar_sync(6, NWRK);
        {
            float mb, rc;
            ln_finish(sum18(sa), lane, mb, rc);
            if (lane < 16) stat_store(s_stat + lane * 8, mb, rc, 0u);
        }
        bar_arrive(7, 608);
        bar_sync(8, 608);
        uint32_t t0;
        {
            const uint32_t bits = __float_as_uint(rbf(sum18(ra)));
            const uint32_t me = ((bits ^ ((uint32_t)((int)bits >> 31) | 0x80000000u)) & 0xffff0000u) | klo;
            const uint32_t k0 = __reduce_max_sync(0xffffffffu, me), k1 = __reduce_max_sync(0xffffffffu, me == k0 ? 0u : me);
            const uint32_t k2 = __reduce_max_sync(0xffffffffu, me >= k1 ? 0u : me);
            if (lane < 2) stg128(kdst, k0 ^ 0x11eu, k1 ^ 0xfeu, k2 ^ 0xdeu, par);
            asm volatile("mov.u32 %0, %%clock;" : "=r"(t0) :: "memory");
            STAMPW(23);
            if (lane == 0) sts64(s_rank, ~k0 & 30u, ~k1 & 30u);
            bar_arrive(9, 608);
            sts32(s_k16 + (lane & 15) * 4, me);
            __syncwarp();
            const uint4 v = lds128(s_k16 + (lane & 16) * 2), w = lds128(s_k16 + (lane & 16) * 2 + 16);
            int rank = ((v.x > me) + (v.y > me)) + ((v.z > me) + (v.w > me)) + (((w.x > me) + (w.y > me)) + ((w.z > me) + (w.w > me)));
            rank += __shfl_xor_sync(0xffffffffu, rank, 16);
            if (lane < 16 && rank < 8) p.s->key[8 * b + rank] = (me ^ 0x1eu) | ((8 - rank) << 5);
        }
        uint4 kq[4];
        uint32_t u[4], mine = 0, m;
        int it = 0;
        { uint32_t now; do { asm volatile("mov.u32 %0, %%clock;" : "=r"(now) :: "memory"); } while (now - t0 < KDLY); }
        do {
#pragma unroll
            for (int i = 0; i < 4; i++) kq[i] = ld_poll(ksrc + 64 * i);
            if (++it > SPIN_LIMIT) TRAP();
            uint32_t S[2][4];
#pragma unroll
            for (int i = 0; i < 2; i++) {
                const uint4 &c = kq[2 * i], &d = kq[2 * i + 1];
                const uint32_t m1 = min(c.x, d.x), m2 = max(c.y, d.y);
                S[i][0] = max(c.x, d.x); S[i][1] = max(m1, m2); S[i][2] = min(m1, m2); S[i][3] = min(c.y, d.y);
            }
            const uint32_t a0 = max(S[0][0], S[1][3]), a1 = max(S[0][1], S[1][2]), a2 = max(S[0][2], S[1][1]), a3 = max(S[0][3], S[1][0]);
            const uint32_t b0 = max(a0, a2), b2 = min(a0, a2), b1 = max(a1, a3), b3 = min(a1, a3);
            u[0] = max(b0, b1); u[1] = min(b0, b1); u[2] = max(b2, b3); u[3] = min(b2, b3);
            const uint32_t bad = or3(or3(xor_or(kq[0].x, kq[0].y, par), xor_or(kq[0].z, kq[1].x, par), xor_or(kq[1].y, kq[1].z, par)),
                                     xor_or(kq[2].x, kq[2].y, par), xor_or(kq[2].z, kq[3].x, par)) | xor_or(kq[3].y, kq[3].z, par);
            m = __reduce_max_sync(0xffffffffu, u[0] | (uint32_t)((int)(bad << 31) >> 31));
        } while (m == 0xffffffffu);
        STAMPW(16);
#pragma unroll
        for (int r = 0; r < 8; r++) {
            if (r) m = __reduce_max_sync(0xffffffffu, u[0]);
            if (u[0] == m) { u[0] = u[1]; u[1] = u[2]; u[2] = u[3]; u[3] = 0; }
            if (row == r) mine = m;
        }
        uint4 v[9];
        const uint32_t o0 = __byte_perm(mine, 0, 0x4441) * 2304u, o1 = __shfl_xor_sync(0xffffffffu, o0, 4);
        const unsigned char* const rA = reinterpret_cast<const unsigned char*>(p.s->rows) + (((g & 1) ? o1 : o0) + ro + (g & 1) * 64);
        const unsigned char* const rb = reinterpret_cast<const unsigned char*>(p.s->rows) + (((g & 1) ? o0 : o1) + ro + (g & 1) * 64);
        const unsigned char* const rc = reinterpret_cast<const unsigned char*>(p.s->rows) + (o0 + ro + (odd ? -64 : 512));
#pragma unroll
        for (int i = 0; i < 4; i++) { v[i] = ld_poll(rA + i * 128); v[4 + i] = ld_poll(rb + i * 128); }
        v[8] = ld_poll(rc);
        const bool again = u[0] == 0 || max(max(kq[0].z, kq[1].z), max(kq[2].z, kq[3].z)) > m;
        if (t == 0) sts32(s_key + row * 4, mine);
#pragma unroll
        for (int i = 0; i < 9; i++) sts128(i < 8 ? xe + (i >> 2) * 4 * XS_PITCH + (i & 3) * 128 : xd, v[i].x, v[i].y, v[i].z, v[i].w);
        uint32_t mn, m3[3];
        m3[0] = m3[1] = m3[2] = 1u;
#pragma unroll
        for (int i = 0; i < 9; i++) m3[i % 3] = min3(min3(m3[i % 3], v[i].x, v[i].y), v[i].z, v[i].w);
        mn = min3(m3[0], m3[1], m3[2]);
        STAMPW(18);
        if (bar_or(11, NWRK, again || mn == 0)) late_rows(IC<1>());
    } else {
        bar_sync(6, NWRK);
        WPOINT(16, true);
        if (WANY(17) || WANY(18)) delay(WDLY);
        WPOINT(17, true);
        if (WANY(18)) delay(WDLY);
        WPOINT(18, true);
        if (bar_or(11, NWRK, false)) late_rows(IC<2>());
        const int tk = KTOK(lds32(s_key + (lane & 7) * 4));
        const uint32_t sel = __reduce_or_sync(0xffffffffu, (tk >> 4) == b ? 1u << (tk & 15) : 0u);
        if (sel ? lane < 16 && !((sel >> lane) & 1u) : lane == 0) bulk_s2g(p.out + (size_t)(16 * b + lane) * DM, sb + SM_OUT + lane * (DM * 2), sel ? DM * 2 : 16 * DM * 2);
        __syncwarp();
    }
    if (warp == 8 || warp >= 18) {
        const int grp = 3 * b + (warp == 8 ? 0 : warp - 17), fsl = 2 * (g & 3) + (t & 1), fc = 16 * (grp >> 3) + (grp & 7) + 8 * (t >> 1);
        const uint32_t fk = lds32(s_key + fsl * 4);
        float hv = 0.f, u2 = 0.f;
        int it = 0;
        if (b < 96) {
            const uint32_t* const fsrc = p.s->rows + KSLOT(fk, fsl) * DM + (fc >> 1);
            uint32_t hw, uw;
            do { hw = ld_poll32(fsrc + 288); uw = ld_poll32(fsrc); if (++it > SPIN_LIMIT) TRAP(); } while (!hw || !uw);
            hv = (fc & 1) ? bf_hi(hw) : bf_lo(hw); u2 = (fc & 1) ? bf_hi(uw) : bf_lo(uw);
        }
        const float rs = rbf(sigmoid_f(__uint_as_float((fk ^ ((uint32_t)((int)~fk >> 31) | 0x80000000u)) & 0xffff0000u)));
        bf16* dst = p.out + (KTOK(fk) * DM + fc);
        const uint2* src = reinterpret_cast<const uint2*>(p.s->part) + (grp * 256 + 8 * t + g);
        FIX((uint32_t)reinterpret_cast<uint64_t>(dst) & (uint32_t)reinterpret_cast<uint64_t>(src) & (uint32_t)((reinterpret_cast<uint64_t>(dst) & reinterpret_cast<uint64_t>(src)) >> 32) & __float_as_uint(rs));
        if (warp > 17) bar_sync(13, NWRK);
        if (b < 96) {
            delay(warp > 17 ? FDLY : FDLY2);
            const uint32_t sel = (g & 1) ? 0x3f800000u : 0x3f80u;
            float y;
            uint32_t ok;
            do {
                uint2 a[8];
#pragma unroll
                for (int i = 0; i < 8; i++) a[i] = ld_poll64(src + 32 * i);
                if (++it > SPIN_LIMIT) TRAP();
                float c[2][4] = {};
#pragma unroll
                for (int i = 0; i < 8; i += 2) mma_bf16(c[(i >> 1) & 1], a[i].x, a[i].y, a[i + 1].x, a[i + 1].y, sel, sel);
                ok = min3(min3(min3(a[0].x, a[0].y, a[1].x), min3(a[1].y, a[2].x, a[2].y), min3(a[3].x, a[3].y, a[4].x)), min3(min3(a[4].y, a[5].x, a[5].y), min3(a[6].x, a[6].y, a[7].x), a[7].y), 1u);
                ok = __all_sync(0xffffffffu, ok);
                y = fsel(fsel(c[0][3] + c[1][3], c[0][2] + c[1][2], t & 1), fsel(c[0][1] + c[1][1], c[0][0] + c[1][0], t & 1), t & 2);
            } while (!ok);
            STAMP2(24);
            y += __shfl_xor_sync(0xffffffffu, y, 16);
            *dst = __float2bfloat16_rn(hv + rbf(u2 + rbf(rbf(y) * rs)));
        }
    }
    if (warp == 19) asm volatile("cp.async.bulk.wait_group.read 0;\n" ::: "memory");
    if (b == 0 && tid < 8) *reinterpret_cast<volatile unsigned*>(p.s->hint + tid * 32 + 1) = lds32(s_cnt + 4) + 1u;
    STAMP(25);
    }
}

typedef CUresult (*PFN_tmEncode)(CUtensorMap*, CUtensorMapDataType, cuuint32_t, void*, const cuuint64_t*, const cuuint64_t*, const cuuint32_t*,
                                 const cuuint32_t*, CUtensorMapInterleave, CUtensorMapSwizzle, CUtensorMapL2promotion, CUtensorMapFloatOOBfill);

extern "C" void kernel_launch(void* const* d_in, const int* in_sizes, int n_in, void* d_out, int out_size) {
    Params p;
    p.x = (const bf16*)d_in[0];
    p.lar = (const bf16*)d_in[1];
    p.aim = (const bf16*)d_in[2];
    p.cre = (const bf16*)d_in[3];
    p.cim = (const bf16*)d_in[4];
    p.ldt = (const bf16*)d_in[5];
    p.dsk = (const bf16*)d_in[6];
    p.wr = (const bf16*)d_in[8];
    p.out = (bf16*)d_out;
    static PFN_tmEncode enc = nullptr;
    static void* scratch = nullptr;
    if (!enc) {
        cudaFuncSetAttribute(fused_kernel, cudaFuncAttributeMaxDynamicSharedMemorySize, SMEM_TOTAL);
        void* fn = nullptr;
        cudaDriverEntryPointQueryResult qr;
        cudaGetDriverEntryPoint("cuTensorMapEncodeTiled", &fn, cudaEnableDefault, &qr);
        enc = (PFN_tmEncode)fn;
        cudaGetSymbolAddress(&scratch, g_scratch);
    }
    p.s = (Scratch*)scratch;
    Maps tm;
    const cuuint64_t dims[2] = {FF, DM}, strides[1] = {FF * 2};
    const cuuint32_t box[2] = {64, 48}, rbox[2] = {8, 144}, es[2] = {1, 1};
    for (int i = 0; i < 2; i++) {
        enc(&tm.w[i], CU_TENSOR_MAP_DATA_TYPE_BFLOAT16, 2, d_in[9 + i], dims, strides, box, es, CU_TENSOR_MAP_INTERLEAVE_NONE, CU_TENSOR_MAP_SWIZZLE_128B,
            CU_TENSOR_MAP_L2_PROMOTION_NONE, CU_TENSOR_MAP_FLOAT_OOB_FILL_NONE);
        enc(&tm.r[i], CU_TENSOR_MAP_DATA_TYPE_BFLOAT16, 2, d_in[9 + i], dims, strides, rbox, es, CU_TENSOR_MAP_INTERLEAVE_NONE, CU_TENSOR_MAP_SWIZZLE_NONE,
            CU_TENSOR_MAP_L2_PROMOTION_NONE, CU_TENSOR_MAP_FLOAT_OOB_FILL_NONE);
    }
    const cuuint64_t ddims[2] = {DM / 2, FF}, dstrides[1] = {DM * 2};
    const cuuint32_t dbox[2] = {WD_PITCH / 4, 8};
    enc(&tm.d, CU_TENSOR_MAP_DATA_TYPE_UINT32, 2, d_in[11], ddims, dstrides, dbox, es, CU_TENSOR_MAP_INTERLEAVE_NONE, CU_TENSOR_MAP_SWIZZLE_NONE,
        CU_TENSOR_MAP_L2_PROMOTION_L2_128B, CU_TENSOR_MAP_FLOAT_OOB_FILL_NONE);
    const cuuint64_t xdims[4] = {DM, 128, 4, 4}, xstrides[3] = {DM * 8, DM * 2, DM * 1024};
    const cuuint32_t xbox[4] = {8, 128, 4, 2}, xes[4] = {1, 1, 1, 1};
    enc(&tm.x, CU_TENSOR_MAP_DATA_TYPE_BFLOAT16, 4, d_in[0], xdims, xstrides, xbox, xes, CU_TENSOR_MAP_INTERLEAVE_NONE, CU_TENSOR_MAP_SWIZZLE_NONE,
        CU_TENSOR_MAP_L2_PROMOTION_NONE, CU_TENSOR_MAP_FLOAT_OOB_FILL_NONE);
    fused_kernel<<<NCTA, NTHR, SMEM_TOTAL>>>(p, tm);
}
```

```cpp
#include <cuda_runtime.h>
#include <cuda.h>
#include <cuda_fp16.h>
#include <cuda_bf16.h>
#include <stdint.h>

#define LSEQ 2048
#define DM 576
#define NST 128
#define FF 4608
#define NSEL 8
#define NCTA 128
#define NTHR 640
#define NWRK 640

typedef __nv_bfloat16 bf16;

#define SM_WG 0
#define SM_WU 36864
#define SM_WR 73728
#define SM_XC (82944 - 32768)
#define SM_WD 82944
#define WD_PITCH 592
#define SM_Z2 (SM_WD + 10240)
#define SM_XT (SM_PL - 18 * 1152)
#define SM_PL (SM_WD + 46080)
#define PL_HALF 1344
#define PLW_B 2624
#define PL_B (4 * PLW_B)
#define SM_U (SM_PL + 5 * PL_B)
#define UPAD 20
#define ULO_B ((UPAD + 128) * 16)
#define USLOT_B (2 * ULO_B)
#define SM_KW (SM_U + 5 * USLOT_B)
#define KW_B 3712
#define KW_PL 1216
#define KW_P 2400
#define KW_H 3440
#define SM_MISC (SM_KW + 5 * KW_B)
#define SM_LC (SM_MISC + 416)
#define SM_LNP (SM_LC + 768)
#define SM_RX (SM_LNP + 3840)
#define SMEM_TOTAL (SM_RX + 3088)
#define TBW PLW_B
#define SM_OUT SM_PL
#define SM_XS (SM_PL + 18432)
#define XS_PITCH 592
#define SM_GU (SM_PL + 23296)
#define SM_EX (SM_PL + 24576)

struct __align__(128) Scratch {
    unsigned hint[8 * 32];
    unsigned flag[32];
    uint32_t key3[NCTA * 8];
    uint32_t key[NCTA * 8];
    uint32_t stat[LSEQ];
    uint32_t uT[64 * (LSEQ / 2)];
    uint32_t y[(NCTA + 96) * DM * 8];
    uint32_t part[288 * 64 * 8];
    uint32_t rows[(2 * NCTA + NSEL) * DM];
};
__device__ Scratch g_scratch;
#define STAMP(i)
#define STAMPX(i)
#define STAMPY(i)

__device__ __forceinline__ float rbf(float x) {
    uint32_t r;
    asm("cvt.rn.bf16x2.f32 %0, %1, %2;\n" : "=r"(r) : "f"(x), "f"(0.f));
    return __uint_as_float(r);
}
__device__ __forceinline__ uint32_t pack_bf16(float lo, float hi) {
    uint32_t r;
    asm("cvt.rn.bf16x2.f32 %0, %1, %2;\n" : "=r"(r) : "f"(hi), "f"(lo));
    return r;
}
__device__ __forceinline__ uint32_t pack_f16(float lo, float hi) {
    uint32_t r;
    asm("cvt.rn.f16x2.f32 %0, %1, %2;\n" : "=r"(r) : "f"(hi), "f"(lo));
    return r;
}
__device__ __forceinline__ float bf_lo(uint32_t w) { return __uint_as_float(w << 16); }
__device__ __forceinline__ float bf_hi(uint32_t w) { return __uint_as_float(w & 0xffff0000u); }
__device__ __forceinline__ uint32_t hadd2_bf(uint32_t a, uint32_t b) {
    __nv_bfloat162 r = __hadd2_rn(*reinterpret_cast<__nv_bfloat162*>(&a), *reinterpret_cast<__nv_bfloat162*>(&b));
    return *reinterpret_cast<uint32_t*>(&r);
}
__device__ __forceinline__ uint32_t hsub2_bf(uint32_t a, uint32_t b) {
    __nv_bfloat162 r = __hsub2_rn(*reinterpret_cast<__nv_bfloat162*>(&a), *reinterpret_cast<__nv_bfloat162*>(&b));
    return *reinterpret_cast<uint32_t*>(&r);
}
__device__ __forceinline__ uint32_t hmul2_bf(uint32_t a, uint32_t b) {
    __nv_bfloat162 r = __hmul2_rn(*reinterpret_cast<__nv_bfloat162*>(&a), *reinterpret_cast<__nv_bfloat162*>(&b));
    return *reinterpret_cast<uint32_t*>(&r);
}
__device__ __forceinline__ uint32_t hfma2_bf(uint32_t a, uint32_t b, uint32_t c) { uint32_t r; asm("fma.rn.bf16x2 %0, %1, %2, %3;\n" : "=r"(r) : "r"(a), "r"(b), "r"(c)); return r; }
__device__ __forceinline__ uint32_t hmul2(uint32_t a, uint32_t b) { uint32_t r; asm("mul.rn.f16x2 %0, %1, %2;\n" : "=r"(r) : "r"(a), "r"(b)); return r; }
__device__ __forceinline__ uint32_t hadd2(uint32_t a, uint32_t b) { uint32_t r; asm("add.rn.f16x2 %0, %1, %2;\n" : "=r"(r) : "r"(a), "r"(b)); return r; }
__device__ __forceinline__ uint32_t hfma2(uint32_t a, uint32_t b, uint32_t c) { uint32_t r; asm("fma.rn.f16x2 %0, %1, %2, %3;\n" : "=r"(r) : "r"(a), "r"(b), "r"(c)); return r; }
__device__ __forceinline__ uint32_t hfms2(uint32_t a, uint32_t b, uint32_t c) {
    uint32_t r;
    asm("{\n.reg .b32 n;\nneg.f16x2 n, %2;\nfma.rn.f16x2 %0, %1, n, %3;\n}\n" : "=r"(r) : "r"(a), "r"(b), "r"(c));
    return r;
}
__device__ __forceinline__ uint32_t nzw(uint32_t w) { uint32_t r; asm("max.u32 %0, %1, 1;\n" : "=r"(r) : "r"(w)); return r; }
__device__ __forceinline__ uint32_t smem_u32(const void* p) { return (uint32_t)__cvta_generic_to_shared(p); }
__device__ __forceinline__ uint32_t lds32(uint32_t addr) {
    uint32_t v;
    asm volatile("ld.shared.u32 %0, [%1];\n" : "=r"(v) : "r"(addr) : "memory");
    return v;
}
__device__ __forceinline__ uint32_t lds16(uint32_t addr) {
    unsigned short v;
    asm volatile("ld.shared.u16 %0, [%1];\n" : "=h"(v) : "r"(addr) : "memory");
    return v;
}
__device__ __forceinline__ uint2 lds64(uint32_t addr) {
    uint2 v;
    asm volatile("ld.shared.v2.u32 {%0,%1}, [%2];\n" : "=r"(v.x), "=r"(v.y) : "r"(addr) : "memory");
    return v;
}
__device__ __forceinline__ uint4 lds128(uint32_t addr) {
    uint4 v;
    asm volatile("ld.shared.v4.u32 {%0,%1,%2,%3}, [%4];\n" : "=r"(v.x), "=r"(v.y), "=r"(v.z), "=r"(v.w) : "r"(addr) : "memory");
    return v;
}
__device__ __forceinline__ void sts32(uint32_t addr, uint32_t v) { asm volatile("st.shared.u32 [%0], %1;\n" ::"r"(addr), "r"(v) : "memory"); }
__device__ __forceinline__ void sts16(uint32_t addr, uint32_t v) { asm volatile("st.shared.u16 [%0], %1;\n" ::"r"(addr), "h"((unsigned short)v) : "memory"); }
__device__ __forceinline__ void stsf(uint32_t addr, float v) { sts32(addr, __float_as_uint(v)); }
__device__ __forceinline__ void sts64(uint32_t addr, uint32_t a, uint32_t b) { asm volatile("st.shared.v2.u32 [%0], {%1,%2};\n" ::"r"(addr), "r"(a), "r"(b) : "memory"); }
__device__ __forceinline__ void sts128(uint32_t addr, uint32_t a, uint32_t b, uint32_t c, uint32_t d) {
    asm volatile("st.shared.v4.u32 [%0], {%1,%2,%3,%4};\n" ::"r"(addr), "r"(a), "r"(b), "r"(c), "r"(d) : "memory");
}
__device__ __forceinline__ void ldsm_x4(uint32_t& r0, uint32_t& r1, uint32_t& r2, uint32_t& r3, uint32_t addr) {
    asm volatile("ldmatrix.sync.aligned.m8n8.x4.shared.b16 {%0,%1,%2,%3}, [%4];\n"
                 : "=r"(r0), "=r"(r1), "=r"(r2), "=r"(r3) : "r"(addr) : "memory");
}
__device__ __forceinline__ void ldsm_x4_t(uint32_t& r0, uint32_t& r1, uint32_t& r2, uint32_t& r3, uint32_t addr) {
    asm volatile("ldmatrix.sync.aligned.m8n8.x4.trans.shared.b16 {%0,%1,%2,%3}, [%4];\n"
                 : "=r"(r0), "=r"(r1), "=r"(r2), "=r"(r3) : "r"(addr) : "memory");
}
__device__ __forceinline__ void ldsm_x2_t(uint32_t& r0, uint32_t& r1, uint32_t addr) {
    asm volatile("ldmatrix.sync.aligned.m8n8.x2.trans.shared.b16 {%0,%1}, [%2];\n" : "=r"(r0), "=r"(r1) : "r"(addr) : "memory");
}
__device__ __forceinline__ void ldsm_x1_t(uint32_t& r0, uint32_t addr) {
    asm volatile("ldmatrix.sync.aligned.m8n8.x1.trans.shared.b16 {%0}, [%1];\n" : "=r"(r0) : "r"(addr) : "memory");
}
__device__ __forceinline__ void stsm_x4(uint32_t addr, uint32_t r0, uint32_t r1, uint32_t r2, uint32_t r3) {
    asm volatile("stmatrix.sync.aligned.m8n8.x4.shared.b16 [%0], {%1,%2,%3,%4};\n" ::"r"(addr), "r"(r0), "r"(r1), "r"(r2), "r"(r3) : "memory");
}
__device__ __forceinline__ void stsm_x4_t(uint32_t addr, uint32_t r0, uint32_t r1, uint32_t r2, uint32_t r3) {
    asm volatile("stmatrix.sync.aligned.m8n8.x4.trans.shared.b16 [%0], {%1,%2,%3,%4};\n" ::"r"(addr), "r"(r0), "r"(r1), "r"(r2), "r"(r3) : "memory");
}
__device__ __forceinline__ uint32_t movm(uint32_t a) {
    uint32_t d;
    asm volatile("movmatrix.sync.aligned.m8n8.trans.b16 %0, %1;\n" : "=r"(d) : "r"(a));
    return d;
}
__device__ __forceinline__ void mma_f16(float (&c)[4], uint32_t a0, uint32_t a1, uint32_t a2, uint32_t a3, uint32_t b0, uint32_t b1) {
    asm volatile(
        "mma.sync.aligned.m16n8k16.row.col.f32.f16.f16.f32 {%0,%1,%2,%3}, {%4,%5,%6,%7}, {%8,%9}, {%0,%1,%2,%3};\n"
        : "+f"(c[0]), "+f"(c[1]), "+f"(c[2]), "+f"(c[3])
        : "r"(a0), "r"(a1), "r"(a2), "r"(a3), "r"(b0), "r"(b1));
}
__device__ __forceinline__ void mma_bf16(float (&c)[4], uint32_t a0, uint32_t a1, uint32_t a2, uint32_t a3, uint32_t b0, uint32_t b1) {
    asm volatile(
        "mma.sync.aligned.m16n8k16.row.col.f32.bf16.bf16.f32 {%0,%1,%2,%3}, {%4,%5,%6,%7}, {%8,%9}, {%0,%1,%2,%3};\n"
        : "+f"(c[0]), "+f"(c[1]), "+f"(c[2]), "+f"(c[3])
        : "r"(a0), "r"(a1), "r"(a2), "r"(a3), "r"(b0), "r"(b1));
}
__device__ __forceinline__ void mma_bf16_k8(float (&c)[4], uint32_t a0, uint32_t a1, uint32_t b0) {
    asm volatile("mma.sync.aligned.m16n8k8.row.col.f32.bf16.bf16.f32 {%0,%1,%2,%3}, {%4,%5}, {%6}, {%0,%1,%2,%3};\n"
                 : "+f"(c[0]), "+f"(c[1]), "+f"(c[2]), "+f"(c[3]) : "r"(a0), "r"(a1), "r"(b0));
}
__device__ __forceinline__ void bar_sync(int id, int n) { asm volatile("bar.sync %0, %1;\n" ::"r"(id), "r"(n) : "memory"); }
__device__ __forceinline__ void bar_arrive(int id, int n) { asm volatile("bar.arrive %0, %1;\n" ::"r"(id), "r"(n) : "memory"); }
__device__ __forceinline__ bool bar_or(int id, int n, bool v) {
    uint32_t r;
    asm volatile("{\n.reg .pred p, q;\nsetp.ne.u32 p, %3, 0;\nbar.red.or.pred q, %1, %2, p;\nselp.u32 %0, 1, 0, q;\n}\n" : "=r"(r) : "r"(id), "r"(n), "r"((uint32_t)v) : "memory");
    return r;
}
__device__ __forceinline__ uint32_t and3(uint32_t a, uint32_t b, uint32_t c) { uint32_t r; asm("lop3.b32 %0, %1, %2, %3, 0x80;\n" : "=r"(r) : "r"(a), "r"(b), "r"(c)); return r; }
__device__ __forceinline__ uint32_t or3(uint32_t a, uint32_t b, uint32_t c) { uint32_t r; asm("lop3.b32 %0, %1, %2, %3, 0xfe;\n" : "=r"(r) : "r"(a), "r"(b), "r"(c)); return r; }
__device__ __forceinline__ uint32_t min3(uint32_t a, uint32_t b, uint32_t c) { uint32_t r; asm("{\n.reg .u32 t;\nmin.u32 t, %2, %3;\nmin.u32 %0, %1, t;\n}\n" : "=r"(r) : "r"(a), "r"(b), "r"(c)); return r; }
__device__ __forceinline__ uint32_t xor_or(uint32_t a, uint32_t b, uint32_t c) { uint32_t r; asm("lop3.b32 %0, %1, %2, %3, 0x7e;\n" : "=r"(r) : "r"(a), "r"(b), "r"(c)); return r; }
__device__ __forceinline__ uint32_t pin(uint32_t v) { uint32_t r; asm volatile("shfl.sync.bfly.b32 %0, %1, 0, 0x1f, 0xffffffff;\n" : "=r"(r) : "r"(v) : "memory"); return r; }
__device__ __forceinline__ uint4 ld_poll(const void* p) {
    uint4 v;
    asm volatile("ld.relaxed.gpu.global.v4.u32 {%0,%1,%2,%3}, [%4];\n" : "=r"(v.x), "=r"(v.y), "=r"(v.z), "=r"(v.w) : "l"(p) : "memory");
    return v;
}
__device__ __forceinline__ uint2 ld_poll64(const void* p) {
    uint2 v;
    asm volatile("ld.relaxed.gpu.global.v2.u32 {%0,%1}, [%2];\n" : "=r"(v.x), "=r"(v.y) : "l"(p) : "memory");
    return v;
}
__device__ __forceinline__ uint32_t ld_poll32(const void* p) {
    uint32_t v;
    asm volatile("ld.relaxed.gpu.global.u32 %0, [%1];\n" : "=r"(v) : "l"(p) : "memory");
    return v;
}
__device__ __forceinline__ uint32_t ld_acquire32(const void* p) {
    uint32_t v;
    asm volatile("ld.acquire.gpu.global.u32 %0, [%1];\n" : "=r"(v) : "l"(p) : "memory");
    return v;
}
__device__ __forceinline__ uint2 ldo64(const void* p) {
    uint2 v;
    asm volatile("ld.relaxed.cta.global.v2.u32 {%0,%1}, [%2];\n" : "=r"(v.x), "=r"(v.y) : "l"(p) : "memory");
    return v;
}
__device__ __forceinline__ uint32_t ldo16(const void* p) {
    uint32_t v;
    asm volatile("ld.relaxed.cta.global.u16 %0, [%1];\n" : "=r"(v) : "l"(p) : "memory");
    return v;
}
__device__ __forceinline__ void stg128(void* p, uint32_t a, uint32_t b, uint32_t c, uint32_t d) {
    asm volatile("st.global.v4.u32 [%0], {%1,%2,%3,%4};\n" ::"l"(p), "r"(a), "r"(b), "r"(c), "r"(d) : "memory");
}
__device__ __forceinline__ void stg64(void* p, uint32_t a, uint32_t b) { asm volatile("st.global.v2.u32 [%0], {%1,%2};\n" ::"l"(p), "r"(a), "r"(b) : "memory"); }
__device__ __forceinline__ uint32_t min4(const uint4& v) { return min(min(v.x, v.y), min(v.z, v.w)); }
#define SPIN_LIMIT (1 << 21)
#define TRAP() __trap()
__device__ __forceinline__ void mbar_init(uint32_t bar, uint32_t cnt) { asm volatile("mbarrier.init.shared::cta.b64 [%0], %1;\n" ::"r"(bar), "r"(cnt) : "memory"); }
__device__ __forceinline__ void mbar_expect(uint32_t bar, uint32_t bytes) {
    asm volatile("mbarrier.arrive.expect_tx.shared::cta.b64 _, [%0], %1;\n" ::"r"(bar), "r"(bytes) : "memory");
}
__device__ __forceinline__ void mbar_arrive(uint32_t bar) { asm volatile("mbarrier.arrive.shared::cta.b64 _, [%0];\n" ::"r"(bar) : "memory"); }
__device__ __forceinline__ void mbar_wait(uint32_t bar) {
    asm volatile(
        "{\n.reg .pred p;\n"
        "W_%=:\n"
        "mbarrier.try_wait.parity.shared::cta.b64 p, [%0], 0;\n"
        "@!p bra W_%=;\n}\n" ::"r"(bar) : "memory");
}
__device__ __forceinline__ void bulk_g2s(uint32_t dst, const void* src, uint32_t bytes, uint32_t bar) {
    asm volatile("cp.async.bulk.shared::cluster.global.mbarrier::complete_tx::bytes [%0], [%1], %2, [%3];\n" ::"r"(dst), "l"(src), "r"(bytes), "r"(bar) : "memory");
}
__device__ __forceinline__ void bulk_s2g(void* dst, uint32_t src, uint32_t bytes) {
    asm volatile("cp.async.bulk.global.shared::cta.bulk_group [%0], [%1], %2;\ncp.async.bulk.commit_group;\n" ::"l"(dst), "r"(src), "r"(bytes) : "memory");
}
__device__ __forceinline__ void bulk_s2g_nc(void* dst, uint32_t src, uint32_t bytes) {
    asm volatile("cp.async.bulk.global.shared::cta.bulk_group [%0], [%1], %2;\n" ::"l"(dst), "r"(src), "r"(bytes) : "memory");
}
__device__ __forceinline__ void tma_2d(uint32_t dst, const CUtensorMap* tm, int c0, int c1, uint32_t bar) {
    asm volatile("cp.async.bulk.tensor.2d.shared::cluster.global.mbarrier::complete_tx::bytes [%0], [%1, {%3, %4}], [%2];\n"
                 ::"r"(dst), "l"(tm), "r"(bar), "r"(c0), "r"(c1) : "memory");
}
__device__ __forceinline__ void tma_4d_mc(uint32_t dst, const CUtensorMap* tm, int c0, int c3, uint32_t bar) {
    asm volatile("cp.async.bulk.tensor.4d.shared::cluster.global.mbarrier::complete_tx::bytes.multicast::cluster [%0], [%1, {%3, %4, %4, %5}], [%2], %6;\n"
                 ::"r"(dst), "l"(tm), "r"(bar), "r"(c0), "r"(0), "r"(c3), "h"((unsigned short)3) : "memory");
}
__device__ __forceinline__ bool elect_one() {
    uint32_t r;
    asm volatile("{\n.reg .pred p;\nelect.sync _|p, 0xffffffff;\nselp.u32 %0, 1, 0, p;\n}\n" : "=r"(r));
    return r;
}
__device__ __forceinline__ void delay(uint32_t clks) {
    uint32_t t0, t1;
    asm volatile("mov.u32 %0, %%clock;" : "=r"(t0) :: "memory");
    do { asm volatile("mov.u32 %0, %%clock;" : "=r"(t1) :: "memory"); } while (t1 - t0 < clks);
}
__device__ __forceinline__ void fence_async() { asm volatile("fence.proxy.async.shared::cta;\n" ::: "memory"); }

__device__ __forceinline__ float2 cmul(float2 a, float2 b) {
    return make_float2(fmaf(a.x, b.x, -a.y * b.y), fmaf(a.x, b.y, a.y * b.x));
}
__device__ __forceinline__ float2 csq(float2 a) {
    float p = a.x * a.y;
    return make_float2(fmaf(a.x, a.x, -a.y * a.y), p + p);
}
__device__ __forceinline__ float ex2_approx(float x) { float r; asm("ex2.approx.ftz.f32 %0, %1;\n" : "=f"(r) : "f"(x)); return r; }
__device__ __forceinline__ float exp_bf(float x) { return rbf(ex2_approx(__fmul_ru(x, 1.4426950408889634f))); }
__device__ __forceinline__ float2 cexp_e(float lr2, float li, float e) {
    const float m = ex2_approx(lr2 * e);
    return make_float2(m * __cosf(li * e), m * __sinf(li * e));
}
__device__ __forceinline__ float rcp_approx(float x) { float r; asm("rcp.approx.ftz.f32 %0, %1;\n" : "=f"(r) : "f"(x)); return r; }
__device__ __forceinline__ float sigmoid_f(float x) { return rcp_approx(1.0f + ex2_approx(x * -1.4426950408889634f)); }
__device__ __forceinline__ float sqrt_approx(float x) { float r; asm("sqrt.approx.ftz.f32 %0, %1;\n" : "=f"(r) : "f"(x)); return r; }

__device__ __forceinline__ void wg_fence() { asm volatile("wgmma.fence.sync.aligned;\n" ::: "memory"); }
__device__ __forceinline__ void wg_commit() { asm volatile("wgmma.commit_group.sync.aligned;\n" ::: "memory"); }
__device__ __forceinline__ void wg_wait0() { asm volatile("wgmma.wait_group.sync.aligned 0;\n" ::: "memory"); }
template <int T> __device__ __forceinline__ void wg_mma(float (&acc)[16][4], const uint32_t* a, uint64_t desc);
template <int T> __device__ __forceinline__ void wg_first(float (&acc)[16][4], const uint32_t* a, uint64_t desc);
template <> __device__ __forceinline__ void wg_mma<0>(float (&acc)[16][4], const uint32_t* a, uint64_t desc) {
    asm volatile("wgmma.mma_async.sync.aligned.m64n128k16.f32.f16.f16 {%0,%1,%2,%3,%4,%5,%6,%7,%8,%9,%10,%11,%12,%13,%14,%15,%16,%17,%18,%19,%20,%21,%22,%23,%24,%25,%26,%27,%28,%29,%30,%31,%32,%33,%34,%35,%36,%37,%38,%39,%40,%41,%42,%43,%44,%45,%46,%47,%48,%49,%50,%51,%52,%53,%54,%55,%56,%57,%58,%59,%60,%61,%62,%63}, {%64,%65,%66,%67}, %68, 1, 1, 1, 0;\n"
                 : "+f"(acc[0][0]), "+f"(acc[0][1]), "+f"(acc[0][2]), "+f"(acc[0][3]), "+f"(acc[1][0]), "+f"(acc[1][1]), "+f"(acc[1][2]), "+f"(acc[1][3]), "+f"(acc[2][0]), "+f"(acc[2][1]), "+f"(acc[2][2]), "+f"(acc[2][3]), "+f"(acc[3][0]), "+f"(acc[3][1]), "+f"(acc[3][2]), "+f"(acc[3][3]), "+f"(acc[4][0]), "+f"(acc[4][1]), "+f"(acc[4][2]), "+f"(acc[4][3]), "+f"(acc[5][0]), "+f"(acc[5][1]), "+f"(acc[5][2]), "+f"(acc[5][3]), "+f"(acc[6][0]), "+f"(acc[6][1]), "+f"(acc[6][2]), "+f"(acc[6][3]), "+f"(acc[7][0]), "+f"(acc[7][1]), "+f"(acc[7][2]), "+f"(acc[7][3]), "+f"(acc[8][0]), "+f"(acc[8][1]), "+f"(acc[8][2]), "+f"(acc[8][3]), "+f"(acc[9][0]), "+f"(acc[9][1]), "+f"(acc[9][2]), "+f"(acc[9][3]), "+f"(acc[10][0]), "+f"(acc[10][1]), "+f"(acc[10][2]), "+f"(acc[10][3]), "+f"(acc[11][0]), "+f"(acc[11][1]), "+f"(acc[11][2]), "+f"(acc[11][3]), "+f"(acc[12][0]), "+f"(acc[12][1]), "+f"(acc[12][2]), "+f"(acc[12][3]), "+f"(acc[13][0]), "+f"(acc[13][1]), "+f"(acc[13][2]), "+f"(acc[13][3]), "+f"(acc[14][0]), "+f"(acc[14][1]), "+f"(acc[14][2]), "+f"(acc[14][3]), "+f"(acc[15][0]), "+f"(acc[15][1]), "+f"(acc[15][2]), "+f"(acc[15][3])
                 : "r"(a[0]), "r"(a[1]), "r"(a[2]), "r"(a[3]), "l"(desc));
}
template <> __device__ __forceinline__ void wg_mma<2>(float (&acc)[16][4], const uint32_t* a, uint64_t desc) {
    asm volatile("wgmma.mma_async.sync.aligned.m64n112k16.f32.f16.f16 {%0,%1,%2,%3,%4,%5,%6,%7,%8,%9,%10,%11,%12,%13,%14,%15,%16,%17,%18,%19,%20,%21,%22,%23,%24,%25,%26,%27,%28,%29,%30,%31,%32,%33,%34,%35,%36,%37,%38,%39,%40,%41,%42,%43,%44,%45,%46,%47,%48,%49,%50,%51,%52,%53,%54,%55}, {%56,%57,%58,%59}, %60, 1, 1, 1, 0;\n"
                 : "+f"(acc[2][0]), "+f"(acc[2][1]), "+f"(acc[2][2]), "+f"(acc[2][3]), "+f"(acc[3][0]), "+f"(acc[3][1]), "+f"(acc[3][2]), "+f"(acc[3][3]), "+f"(acc[4][0]), "+f"(acc[4][1]), "+f"(acc[4][2]), "+f"(acc[4][3]), "+f"(acc[5][0]), "+f"(acc[5][1]), "+f"(acc[5][2]), "+f"(acc[5][3]), "+f"(acc[6][0]), "+f"(acc[6][1]), "+f"(acc[6][2]), "+f"(acc[6][3]), "+f"(acc[7][0]), "+f"(acc[7][1]), "+f"(acc[7][2]), "+f"(acc[7][3]), "+f"(acc[8][0]), "+f"(acc[8][1]), "+f"(acc[8][2]), "+f"(acc[8][3]), "+f"(acc[9][0]), "+f"(acc[9][1]), "+f"(acc[9][2]), "+f"(acc[9][3]), "+f"(acc[10][0]), "+f"(acc[10][1]), "+f"(acc[10][2]), "+f"(acc[10][3]), "+f"(acc[11][0]), "+f"(acc[11][1]), "+f"(acc[11][2]), "+f"(acc[11][3]), "+f"(acc[12][0]), "+f"(acc[12][1]), "+f"(acc[12][2]), "+f"(acc[12][3]), "+f"(acc[13][0]), "+f"(acc[13][1]), "+f"(acc[13][2]), "+f"(acc[13][3]), "+f"(acc[14][0]), "+f"(acc[14][1]), "+f"(acc[14][2]), "+f"(acc[14][3]), "+f"(acc[15][0]), "+f"(acc[15][1]), "+f"(acc[15][2]), "+f"(acc[15][3])
                 : "r"(a[0]), "r"(a[1]), "r"(a[2]), "r"(a[3]), "l"(desc));
}
template <> __device__ __forceinline__ void wg_mma<4>(float (&acc)[16][4], const uint32_t* a, uint64_t desc) {
    asm volatile("wgmma.mma_async.sync.aligned.m64n96k16.f32.f16.f16 {%0,%1,%2,%3,%4,%5,%6,%7,%8,%9,%10,%11,%12,%13,%14,%15,%16,%17,%18,%19,%20,%21,%22,%23,%24,%25,%26,%27,%28,%29,%30,%31,%32,%33,%34,%35,%36,%37,%38,%39,%40,%41,%42,%43,%44,%45,%46,%47}, {%48,%49,%50,%51}, %52, 1, 1, 1, 0;\n"
                 : "+f"(acc[4][0]), "+f"(acc[4][1]), "+f"(acc[4][2]), "+f"(acc[4][3]), "+f"(acc[5][0]), "+f"(acc[5][1]), "+f"(acc[5][2]), "+f"(acc[5][3]), "+f"(acc[6][0]), "+f"(acc[6][1]), "+f"(acc[6][2]), "+f"(acc[6][3]), "+f"(acc[7][0]), "+f"(acc[7][1]), "+f"(acc[7][2]), "+f"(acc[7][3]), "+f"(acc[8][0]), "+f"(acc[8][1]), "+f"(acc[8][2]), "+f"(acc[8][3]), "+f"(acc[9][0]), "+f"(acc[9][1]), "+f"(acc[9][2]), "+f"(acc[9][3]), "+f"(acc[10][0]), "+f"(acc[10][1]), "+f"(acc[10][2]), "+f"(acc[10][3]), "+f"(acc[11][0]), "+f"(acc[11][1]), "+f"(acc[11][2]), "+f"(acc[11][3]), "+f"(acc[12][0]), "+f"(acc[12][1]), "+f"(acc[12][2]), "+f"(acc[12][3]), "+f"(acc[13][0]), "+f"(acc[13][1]), "+f"(acc[13][2]), "+f"(acc[13][3]), "+f"(acc[14][0]), "+f"(acc[14][1]), "+f"(acc[14][2]), "+f"(acc[14][3]), "+f"(acc[15][0]), "+f"(acc[15][1]), "+f"(acc[15][2]), "+f"(acc[15][3])
                 : "r"(a[0]), "r"(a[1]), "r"(a[2]), "r"(a[3]), "l"(desc));
}
template <> __device__ __forceinline__ void wg_mma<6>(float (&acc)[16][4], const uint32_t* a, uint64_t desc) {
    asm volatile("wgmma.mma_async.sync.aligned.m64n80k16.f32.f16.f16 {%0,%1,%2,%3,%4,%5,%6,%7,%8,%9,%10,%11,%12,%13,%14,%15,%16,%17,%18,%19,%20,%21,%22,%23,%24,%25,%26,%27,%28,%29,%30,%31,%32,%33,%34,%35,%36,%37,%38,%39}, {%40,%41,%42,%43}, %44, 1, 1, 1, 0;\n"
                 : "+f"(acc[6][0]), "+f"(acc[6][1]), "+f"(acc[6][2]), "+f"(acc[6][3]), "+f"(acc[7][0]), "+f"(acc[7][1]), "+f"(acc[7][2]), "+f"(acc[7][3]), "+f"(acc[8][0]), "+f"(acc[8][1]), "+f"(acc[8][2]), "+f"(acc[8][3]), "+f"(acc[9][0]), "+f"(acc[9][1]), "+f"(acc[9][2]), "+f"(acc[9][3]), "+f"(acc[10][0]), "+f"(acc[10][1]), "+f"(acc[10][2]), "+f"(acc[10][3]), "+f"(acc[11][0]), "+f"(acc[11][1]), "+f"(acc[11][2]), "+f"(acc[11][3]), "+f"(acc[12][0]), "+f"(acc[12][1]), "+f"(acc[12][2]), "+f"(acc[12][3]), "+f"(acc[13][0]), "+f"(acc[13][1]), "+f"(acc[13][2]), "+f"(acc[13][3]), "+f"(acc[14][0]), "+f"(acc[14][1]), "+f"(acc[14][2]), "+f"(acc[14][3]), "+f"(acc[15][0]), "+f"(acc[15][1]), "+f"(acc[15][2]), "+f"(acc[15][3])
                 : "r"(a[0]), "r"(a[1]), "r"(a[2]), "r"(a[3]), "l"(desc));
}
template <> __device__ __forceinline__ void wg_mma<8>(float (&acc)[16][4], const uint32_t* a, uint64_t desc) {
    asm volatile("wgmma.mma_async.sync.aligned.m64n64k16.f32.f16.f16 {%0,%1,%2,%3,%4,%5,%6,%7,%8,%9,%10,%11,%12,%13,%14,%15,%16,%17,%18,%19,%20,%21,%22,%23,%24,%25,%26,%27,%28,%29,%30,%31}, {%32,%33,%34,%35}, %36, 1, 1, 1, 0;\n"
                 : "+f"(acc[8][0]), "+f"(acc[8][1]), "+f"(acc[8][2]), "+f"(acc[8][3]), "+f"(acc[9][0]), "+f"(acc[9][1]), "+f"(acc[9][2]), "+f"(acc[9][3]), "+f"(acc[10][0]), "+f"(acc[10][1]), "+f"(acc[10][2]), "+f"(acc[10][3]), "+f"(acc[11][0]), "+f"(acc[11][1]), "+f"(acc[11][2]), "+f"(acc[11][3]), "+f"(acc[12][0]), "+f"(acc[12][1]), "+f"(acc[12][2]), "+f"(acc[12][3]), "+f"(acc[13][0]), "+f"(acc[13][1]), "+f"(acc[13][2]), "+f"(acc[13][3]), "+f"(acc[14][0]), "+f"(acc[14][1]), "+f"(acc[14][2]), "+f"(acc[14][3]), "+f"(acc[15][0]), "+f"(acc[15][1]), "+f"(acc[15][2]), "+f"(acc[15][3])
                 : "r"(a[0]), "r"(a[1]), "r"(a[2]), "r"(a[3]), "l"(desc));
}
template <> __device__ __forceinline__ void wg_mma<10>(float (&acc)[16][4], const uint32_t* a, uint64_t desc) {
    asm volatile("wgmma.mma_async.sync.aligned.m64n48k16.f32.f16.f16 {%0,%1,%2,%3,%4,%5,%6,%7,%8,%9,%10,%11,%12,%13,%14,%15,%16,%17,%18,%19,%20,%21,%22,%23}, {%24,%25,%26,%27}, %28, 1, 1, 1, 0;\n"
                 : "+f"(acc[10][0]), "+f"(acc[10][1]), "+f"(acc[10][2]), "+f"(acc[10][3]), "+f"(acc[11][0]), "+f"(acc[11][1]), "+f"(acc[11][2]), "+f"(acc[11][3]), "+f"(acc[12][0]), "+f"(acc[12][1]), "+f"(acc[12][2]), "+f"(acc[12][3]), "+f"(acc[13][0]), "+f"(acc[13][1]), "+f"(acc[13][2]), "+f"(acc[13][3]), "+f"(acc[14][0]), "+f"(acc[14][1]), "+f"(acc[14][2]), "+f"(acc[14][3]), "+f"(acc[15][0]), "+f"(acc[15][1]), "+f"(acc[15][2]), "+f"(acc[15][3])
                 : "r"(a[0]), "r"(a[1]), "r"(a[2]), "r"(a[3]), "l"(desc));
}
template <> __device__ __forceinline__ void wg_mma<12>(float (&acc)[16][4], const uint32_t* a, uint64_t desc) {
    asm volatile("wgmma.mma_async.sync.aligned.m64n32k16.f32.f16.f16 {%0,%1,%2,%3,%4,%5,%6,%7,%8,%9,%10,%11,%12,%13,%14,%15}, {%16,%17,%18,%19}, %20, 1, 1, 1, 0;\n"
                 : "+f"(acc[12][0]), "+f"(acc[12][1]), "+f"(acc[12][2]), "+f"(acc[12][3]), "+f"(acc[13][0]), "+f"(acc[13][1]), "+f"(acc[13][2]), "+f"(acc[13][3]), "+f"(acc[14][0]), "+f"(acc[14][1]), "+f"(acc[14][2]), "+f"(acc[14][3]), "+f"(acc[15][0]), "+f"(acc[15][1]), "+f"(acc[15][2]), "+f"(acc[15][3])
                 : "r"(a[0]), "r"(a[1]), "r"(a[2]), "r"(a[3]), "l"(desc));
}
template <> __device__ __forceinline__ void wg_mma<14>(float (&acc)[16][4], const uint32_t* a, uint64_t desc) {
    asm volatile("wgmma.mma_async.sync.aligned.m64n16k16.f32.f16.f16 {%0,%1,%2,%3,%4,%5,%6,%7}, {%8,%9,%10,%11}, %12, 1, 1, 1, 0;\n"
                 : "+f"(acc[14][0]), "+f"(acc[14][1]), "+f"(acc[14][2]), "+f"(acc[14][3]), "+f"(acc[15][0]), "+f"(acc[15][1]), "+f"(acc[15][2]), "+f"(acc[15][3])
                 : "r"(a[0]), "r"(a[1]), "r"(a[2]), "r"(a[3]), "l"(desc));
}
template <> __device__ __forceinline__ void wg_first<0>(float (&acc)[16][4], const uint32_t* a, uint64_t desc) {
    asm volatile("wgmma.mma_async.sync.aligned.m64n128k16.f32.f16.f16 {%0,%1,%2,%3,%4,%5,%6,%7,%8,%9,%10,%11,%12,%13,%14,%15,%16,%17,%18,%19,%20,%21,%22,%23,%24,%25,%26,%27,%28,%29,%30,%31,%32,%33,%34,%35,%36,%37,%38,%39,%40,%41,%42,%43,%44,%45,%46,%47,%48,%49,%50,%51,%52,%53,%54,%55,%56,%57,%58,%59,%60,%61,%62,%63}, {%64,%65,%66,%67}, %68, 0, 1, 1, 0;\n"
                 : "=f"(acc[0][0]), "=f"(acc[0][1]), "=f"(acc[0][2]), "=f"(acc[0][3]), "=f"(acc[1][0]), "=f"(acc[1][1]), "=f"(acc[1][2]), "=f"(acc[1][3]), "=f"(acc[2][0]), "=f"(acc[2][1]), "=f"(acc[2][2]), "=f"(acc[2][3]), "=f"(acc[3][0]), "=f"(acc[3][1]), "=f"(acc[3][2]), "=f"(acc[3][3]), "=f"(acc[4][0]), "=f"(acc[4][1]), "=f"(acc[4][2]), "=f"(acc[4][3]), "=f"(acc[5][0]), "=f"(acc[5][1]), "=f"(acc[5][2]), "=f"(acc[5][3]), "=f"(acc[6][0]), "=f"(acc[6][1]), "=f"(acc[6][2]), "=f"(acc[6][3]), "=f"(acc[7][0]), "=f"(acc[7][1]), "=f"(acc[7][2]), "=f"(acc[7][3]), "=f"(acc[8][0]), "=f"(acc[8][1]), "=f"(acc[8][2]), "=f"(acc[8][3]), "=f"(acc[9][0]), "=f"(acc[9][1]), "=f"(acc[9][2]), "=f"(acc[9][3]), "=f"(acc[10][0]), "=f"(acc[10][1]), "=f"(acc[10][2]), "=f"(acc[10][3]), "=f"(acc[11][0]), "=f"(acc[11][1]), "=f"(acc[11][2]), "=f"(acc[11][3]), "=f"(acc[12][0]), "=f"(acc[12][1]), "=f"(acc[12][2]), "=f"(acc[12][3]), "=f"(acc[13][0]), "=f"(acc[13][1]), "=f"(acc[13][2]), "=f"(acc[13][3]), "=f"(acc[14][0]), "=f"(acc[14][1]), "=f"(acc[14][2]), "=f"(acc[14][3]), "=f"(acc[15][0]), "=f"(acc[15][1]), "=f"(acc[15][2]), "=f"(acc[15][3])
                 : "r"(a[0]), "r"(a[1]), "r"(a[2]), "r"(a[3]), "l"(desc));
}
template <> __device__ __forceinline__ void wg_first<4>(float (&acc)[16][4], const uint32_t* a, uint64_t desc) {
    asm volatile("wgmma.mma_async.sync.aligned.m64n96k16.f32.f16.f16 {%0,%1,%2,%3,%4,%5,%6,%7,%8,%9,%10,%11,%12,%13,%14,%15,%16,%17,%18,%19,%20,%21,%22,%23,%24,%25,%26,%27,%28,%29,%30,%31,%32,%33,%34,%35,%36,%37,%38,%39,%40,%41,%42,%43,%44,%45,%46,%47}, {%48,%49,%50,%51}, %52, 0, 1, 1, 0;\n"
                 : "=f"(acc[4][0]), "=f"(acc[4][1]), "=f"(acc[4][2]), "=f"(acc[4][3]), "=f"(acc[5][0]), "=f"(acc[5][1]), "=f"(acc[5][2]), "=f"(acc[5][3]), "=f"(acc[6][0]), "=f"(acc[6][1]), "=f"(acc[6][2]), "=f"(acc[6][3]), "=f"(acc[7][0]), "=f"(acc[7][1]), "=f"(acc[7][2]), "=f"(acc[7][3]), "=f"(acc[8][0]), "=f"(acc[8][1]), "=f"(acc[8][2]), "=f"(acc[8][3]), "=f"(acc[9][0]), "=f"(acc[9][1]), "=f"(acc[9][2]), "=f"(acc[9][3]), "=f"(acc[10][0]), "=f"(acc[10][1]), "=f"(acc[10][2]), "=f"(acc[10][3]), "=f"(acc[11][0]), "=f"(acc[11][1]), "=f"(acc[11][2]), "=f"(acc[11][3]), "=f"(acc[12][0]), "=f"(acc[12][1]), "=f"(acc[12][2]), "=f"(acc[12][3]), "=f"(acc[13][0]), "=f"(acc[13][1]), "=f"(acc[13][2]), "=f"(acc[13][3]), "=f"(acc[14][0]), "=f"(acc[14][1]), "=f"(acc[14][2]), "=f"(acc[14][3]), "=f"(acc[15][0]), "=f"(acc[15][1]), "=f"(acc[15][2]), "=f"(acc[15][3])
                 : "r"(a[0]), "r"(a[1]), "r"(a[2]), "r"(a[3]), "l"(desc));
}

#define SDLY 1100
#define UDLY 1250
#define KDLY 850
#define FDLY 950
#define FDLY2 350
#define DDLY 450
#define WDLY 500
#define HW 15
#define FIX(v) do { if ((v) == 1u) TRAP(); } while (0)
#define STAMPW(i) STAMPY(i)
#define STAMP2(i) STAMP(i)
#undef STAMPX
#define STAMPX(i)
struct Params {
    const bf16 *x, *lar, *aim, *cre, *cim, *ldt, *dsk;
    Scratch* s;
    const bf16* wr;
    bf16* out;
};
struct Maps { CUtensorMap x, w[2], r[2], d; };

#define TOK(g) (2 * (g) - ((g) & 1))
#define ROWTOK(r) (TOK((r) & 7) + (((r) >> 2) & 2))
__device__ __forceinline__ void ln_partial(const uint32_t (&H)[2][4], float (&d)[2][4]) {
#pragma unroll
    for (int i = 0; i < 8; i++) d[i >> 2][i & 3] = 0.f;
#pragma unroll
    for (int k = 0; k < 4; k++)
#pragma unroll
        for (int hf = 0; hf < 2; hf++) mma_bf16_k8(d[hf], H[hf][k], 0x3f803f80u, H[hf][k]);
}
__device__ __forceinline__ float sum18(uint32_t a) {
    const uint4 p = lds128(a), q = lds128(a + 16), r = lds128(a + 32), s = lds128(a + 48);
    const uint2 u = lds64(a + 64);
#define F(x) __uint_as_float(x)
    return (((F(p.x) + F(p.y)) + (F(p.z) + F(p.w))) + ((F(q.x) + F(q.y)) + (F(q.z) + F(q.w)))) +
           (((F(r.x) + F(r.y)) + (F(r.z) + F(r.w))) + ((F(s.x) + F(s.y)) + (F(s.z) + F(s.w))) + (F(u.x) + F(u.y)));
#undef F
}
__device__ __forceinline__ void ln_stats(float sm, float sq, float& mb, float& sd) {
    const float m0 = sm * (1.0f / 576.0f);
    const float mean = fmaf(fmaf(-m0, 576.0f, sm), 1.0f / 576.0f, m0);
    const float var = fmaxf(fmaf(-mean, mean, sq * (1.0f / 576.0f)), 0.f);
    mb = rbf(mean);
    sd = rbf(sqrt_approx(rbf(rbf(var) + 1e-5f)));
}
__device__ __forceinline__ void ln_finish(float v, int lane, float& mb, float& rc) {
    const float o = __shfl_xor_sync(0xffffffffu, v, 16);
    float sd;
    ln_stats(lane < 16 ? v : o, lane < 16 ? o : v, mb, sd);
    rc = rcp_approx(sd);
}
__device__ __forceinline__ uint32_t ln_apply(uint32_t w, uint32_t m2, uint32_t rh, uint32_t rl) {
    const uint32_t d = hsub2_bf(w, m2);
    return hfma2_bf(d, rh, hmul2_bf(d, rl));
}
__device__ __forceinline__ void stat_store(uint32_t a, float mb, float rc, uint32_t extra) {
    const float rh = rbf(rc);
    sts64(a, (__float_as_uint(mb) >> 16) | (extra << 16), pack_bf16(rh, rc - rh));
}
__device__ __forceinline__ uint32_t dup_lo(uint32_t w) { const __nv_bfloat162 r = __low2bfloat162(*reinterpret_cast<__nv_bfloat162*>(&w)); return *reinterpret_cast<const uint32_t*>(&r); }
__device__ __forceinline__ uint32_t dup_hi(uint32_t w) { const __nv_bfloat162 r = __high2bfloat162(*reinterpret_cast<__nv_bfloat162*>(&w)); return *reinterpret_cast<const uint32_t*>(&r); }
__device__ __forceinline__ float fsel(float a, float b, int c) { float r; asm("{\n.reg .pred p;\nsetp.ne.s32 p, %3, 0;\nselp.f32 %0, %1, %2, p;\n}\n" : "=f"(r) : "f"(a), "f"(b), "r"(c)); return r; }
#define STAT_M(s) dup_lo((s).x)
#define STAT_H(s) dup_lo((s).y)
#define STAT_L(s) dup_hi((s).y)

__device__ __forceinline__ void hcmul(uint32_t re, uint32_t im, uint32_t zx, uint32_t zy, uint32_t& ore, uint32_t& oim) {
    ore = hfms2(im, zy, hmul2(re, zx));
    oim = hfma2(re, zy, hmul2(im, zx));
}

template <int HI>
__device__ __forceinline__ uint32_t hdup(uint32_t w) {
    const __half2 h = *reinterpret_cast<__half2*>(&w), r = HI ? __high2half2(h) : __low2half2(h);
    return *reinterpret_cast<const uint32_t*>(&r);
}
__device__ __forceinline__ void hcmul(uint32_t re, uint32_t im, float2 z, uint32_t& ore, uint32_t& oim) {
    const uint32_t w = pack_f16(z.x, z.y);
    hcmul(re, im, hdup<0>(w), hdup<1>(w), ore, oim);
}

struct KGen {
    uint32_t A[2][4][4];
    float2 z1, z8, z64, z128, T[9];
};
__device__ __forceinline__ void kgen_setup(KGen& k, float lar, float aim, float dt) {
    const float lr2 = -(exp_bf(lar) * dt) * 1.4426950408889634f, li = aim * dt;
    k.z1 = cexp_e(lr2, li, 1.0f);
    k.z8 = cexp_e(lr2, li, 8.0f);
    k.z64 = cexp_e(lr2, li, 64.0f);
}
__device__ __forceinline__ void kgen_rows(KGen& k, uint32_t tb, int lane) {
    const float2 z8 = k.z8, z64 = k.z64;
    const uint32_t row = tb + lane * 16;
    k.z128 = csq(z64);
    const float2 z16 = csq(z8), z24 = cmul(z16, z8), z32 = csq(z16), z40 = cmul(z32, z8), z48 = csq(z24), z56 = cmul(z32, z24);
    uint32_t re[4], im[4], a[4], b[4];
    re[0] = pack_f16(1.0f, z8.x); im[0] = pack_f16(0.0f, z8.y);
    re[1] = pack_f16(z16.x, z24.x); im[1] = pack_f16(z16.y, z24.y);
    re[2] = pack_f16(z32.x, z40.x); im[2] = pack_f16(z32.y, z40.y);
    re[3] = pack_f16(z48.x, z56.x); im[3] = pack_f16(z48.y, z56.y);
    sts128(row, re[0], re[1], re[2], re[3]);
    sts128(row + 1024, im[0], im[1], im[2], im[3]);
    const uint32_t zw = pack_f16(k.z128.x, k.z128.y);
#pragma unroll
    for (int j = 0; j < 4; j++) hcmul(re[j], im[j], z64, a[j], b[j]);
    sts128(row + 512, a[0], a[1], a[2], a[3]);
    sts128(row + 1536, b[0], b[1], b[2], b[3]);
    const int mi = lane >> 3;
    const uint32_t zd = tb + 2048 + mi * 16;
    sts16(tb + 2048 + lane * 2, zw); sts16(tb + 2112 + lane * 2, zw >> 16);
    __syncwarp();
    const uint32_t ad = tb + (lane & 7) * 16 + mi * 512;
    ldsm_x4(a[0], a[1], a[2], a[3], zd);
    ldsm_x4(b[0], b[1], b[2], b[3], zd + 64);
#pragma unroll
    for (int ks = 0; ks < 4; ks++) {
        ldsm_x4_t(k.A[0][ks][0], k.A[0][ks][1], k.A[0][ks][2], k.A[0][ks][3], ad + ks * 128);
        hcmul(k.A[0][ks][0], k.A[0][ks][2], a[ks], b[ks], k.A[1][ks][0], k.A[1][ks][2]);
        hcmul(k.A[0][ks][1], k.A[0][ks][3], a[ks], b[ks], k.A[1][ks][1], k.A[1][ks][3]);
    }
}
__device__ __forceinline__ void kgen_chain(KGen& k, uint32_t cr, uint32_t ci, float cs) {
    k.T[0] = make_float2(bf_lo(cr) * cs, -bf_lo(ci) * cs);
    const float2 y1 = make_float2(k.z1.x, -k.z1.y);
#pragma unroll
    for (int c = 1; c < 8; c++) k.T[c] = cmul(k.T[c - 1], y1);
    k.T[8] = cmul(k.T[0], make_float2(k.z8.x, -k.z8.y));
}
__device__ __forceinline__ void kgen_cols(KGen& k, uint32_t tb, uint32_t t5, int lane) {
    const uint32_t row = tb + lane * 16;
    const float2 (&T)[9] = k.T;
    const float2 y128 = make_float2(k.z128.x, -k.z128.y);
    const float2 y256 = csq(y128), y512 = csq(y256), y768 = cmul(y512, y256), y1024 = csq(y512);
    const float2 c1032 = cmul(T[8], y1024);
    __syncwarp();
    sts128(row, pack_f16(T[0].x, T[1].x), pack_f16(T[2].x, T[3].x), pack_f16(T[4].x, T[5].x), pack_f16(T[6].x, T[7].x));
    sts128(row + 512, pack_f16(T[0].y, T[1].y), pack_f16(T[2].y, T[3].y), pack_f16(T[4].y, T[5].y), pack_f16(T[6].y, T[7].y));
    uint32_t a[4], b[4];
    const uint32_t r0 = pack_f16(1.0f, y256.x), i0 = pack_f16(0.0f, y256.y), r1 = pack_f16(y512.x, y768.x), i1 = pack_f16(y512.y, y768.y);
    {
        hcmul(pack_f16(T[0].x, T[2].x), pack_f16(T[0].y, T[2].y), hdup<1>(r0), hdup<1>(i0), a[0], b[0]);
        hcmul(pack_f16(T[4].x, T[6].x), pack_f16(T[4].y, T[6].y), hdup<1>(r0), hdup<1>(i0), a[1], b[1]);
        const uint32_t r04 = pack_f16(T[0].x, T[4].x), i04 = pack_f16(T[0].y, T[4].y);
        hcmul(r04, i04, hdup<0>(r1), hdup<0>(i1), a[2], b[2]);
        hcmul(r04, i04, hdup<1>(r1), hdup<1>(i1), a[3], b[3]);
    }
    sts128(row + 1024, a[0], a[1], a[2], a[3]);
    sts128(row + 1536, b[0], b[1], b[2], b[3]);
    hcmul(r0, i0, T[8], a[0], b[0]); hcmul(r1, i1, T[8], a[1], b[1]);
    hcmul(r0, i0, c1032, a[2], b[2]); hcmul(r1, i1, c1032, a[3], b[3]);
    sts128(row + 2048, a[0], a[1], a[2], a[3]);
    sts128(t5 + lane * 16, b[0], b[1], b[2], b[3]);
}
template <class F>
__device__ __forceinline__ void kgen_mma(const KGen& k, uint32_t tb, uint32_t t5, int lane, F hold) {
    __syncwarp();
    float acc[2][3][4];
#pragma unroll
    for (int i = 0; i < 6; i++)
#pragma unroll
        for (int j = 0; j < 4; j++) acc[i / 3][i % 3][j] = 0.f;
    const int mi = lane >> 3;
    const uint32_t ro = ((lane & 7) + 8 * (mi >> 1)) * 16, bd = tb + ro + (mi & 1) * 512, b2 = ro + ((mi & 1) ? t5 : tb + 2048);
#pragma unroll
    for (int kp = 0; kp < 2; kp++)
#pragma unroll
        for (int j = 0; j < 3; j++) {
            uint32_t b[4];
            if (kp == 0 && j == 2) hold();
            ldsm_x4_t(b[0], b[1], b[2], b[3], (j < 2 ? bd + j * 1024 : b2) + kp * 256);
#pragma unroll
            for (int h = 0; h < 2; h++)
#pragma unroll
                for (int m = 0; m < 2; m++) {
                    const uint32_t (&A)[4] = k.A[m][2 * kp + h];
                    mma_f16(acc[m][j], A[0], A[1], A[2], A[3], b[2 * h], b[2 * h + 1]);
                }
        }
    __syncwarp();
#define PK(j) pack_f16(acc[0][j][0], acc[0][j][1]), pack_f16(acc[0][j][2], acc[0][j][3]), pack_f16(acc[1][j][0], acc[1][j][1]), pack_f16(acc[1][j][2], acc[1][j][3])
    stsm_x4(tb + lane * 16, PK(0));
    stsm_x4(tb + 512 + lane * 16, PK(1));
    stsm_x4_t(tb + 1024 + (lane & 7) * 80 + mi * 16, PK(2));
#undef PK
}
__device__ __forceinline__ uint32_t table_buf(uint32_t sb, int warp) { return sb + SM_PL + warp * TBW; }

__device__ __forceinline__ uint4 lds16x4(uint32_t a) { return make_uint4(lds16(a), lds16(a + TBW), lds16(a + 2 * TBW), lds16(a + 3 * TBW)); }
__device__ __forceinline__ void combine_setup(uint32_t sb, int warp, int lane, uint32_t kw, uint32_t& o, uint32_t& n, uint32_t& d) {
    const int wq = warp & 3;
    const uint32_t a = table_buf(sb, warp & ~3);
    o = wq == 3 ? a + 1024 + 320 + (lane >> 3) * 80 + (lane & 7) * 8 : a + (wq ? 504 + wq * 8 : 0) + lane * 16;
    n = a + 1024 + wq * 80 + lane * 2;
    d = wq < 3 ? kw + (wq == 2 ? KW_P : 32 + wq * 512) + lane * 16 : kw + KW_H + 8 + lane * 8;
}
__device__ __forceinline__ void kgen_combine(int wq, int lane, uint32_t o, uint32_t na, uint32_t d) {
#define S4(f) hadd2(hadd2(u.f, v.f), hadd2(w.f, x.f))
#define H4(v) hadd2(hadd2(v.x, v.y), hadd2(v.z, v.w))
#define BP __byte_perm
    if (wq == 0) {
        const uint4 u = lds128(o), v = lds128(o + TBW), w = lds128(o + 2 * TBW), x = lds128(o + 3 * TBW), nn = lds16x4(na);
        const uint32_t n = H4(nn), k0 = S4(x), k2 = S4(y), k4 = S4(z), k6 = S4(w);
        sts128(d, BP(k0, k0, 0x1032), BP(k0, k2, 0x3254), BP(k2, k2, 0x1032), BP(k2, k4, 0x3254));
        sts128(d + KW_PL, BP(k4, k4, 0x1032), BP(k4, k6, 0x3254), BP(k6, k6, 0x1032), BP(k6, n, 0x3254));
        if (lane == 0) sts32(d + KW_PL - 4, k0 & 0xffffu);
    } else {
        const uint2 u = lds64(o), v = lds64(o + TBW), w = lds64(o + 2 * TBW), x = lds64(o + 3 * TBW);
        uint4 nn = make_uint4(0u, 0u, 0u, 0u), mm = nn;
        if (wq < 3) nn = lds16x4(na);
        if (wq == 2) mm = lds16x4(na + 80);
        const uint32_t k0 = S4(x), k2 = S4(y), n = H4(nn), m = H4(mm);
        if (wq == 3) {
            sts64(d, k0, k2);
        } else if (wq == 1) {
            const uint32_t cc = BP(k2, k2, 0x1010);
            sts128(d, BP(k0, k0, 0x1010), BP(k0, k0, 0x1032), BP(k0, k2, 0x3254), cc);
            sts128(d + KW_PL, cc, BP(k2, k2, 0x1032), BP(k2, n, 0x3254), BP(n, n, 0x1010));
        } else {
            const uint32_t w40 = BP(k0, k0, 0x1032), w84 = BP(k0, n, 0x3254), w0 = BP(k0, k0, 0x1010), w4 = BP(k0, k0, 0x3232), w8 = BP(n, n, 0x1010);
            sts64(d, w40, w84);
            sts64(d + 512, BP(k2, k2, 0x1032), BP(k2, m, 0x3254));
            if (lane < 8) { sts128(d - (KW_P - 1056), w0, w0, w40, w4); sts128(d - (KW_P - 1056 - KW_PL), w4, w84, w8, w8); }
            if (lane == 31) sts16(d + (KW_H + 6 - KW_P - 496), m);
        }
    }
#undef S4
#undef H4
#undef BP
}

__device__ __forceinline__ int c_exponent(const uint2& r, const uint2& i, float dt) {
    const uint32_t mx = __vmaxu2(__vmaxu2(r.x & 0x7fff7fffu, r.y & 0x7fff7fffu), __vmaxu2(i.x & 0x7fff7fffu, i.y & 0x7fff7fffu));
    return __reduce_max_sync(0xffffffffu, max(mx, mx << 16) + (__float_as_uint(dt) & 0x7f800000u)) >> 23;
}

__device__ __forceinline__ int lane_v() { int l; asm volatile("mov.u32 %0, %%laneid;" : "=r"(l)); return l; }
__device__ __forceinline__ uint32_t prmt_v(uint32_t a, uint32_t b, uint32_t s) { uint32_t d; asm volatile("prmt.b32 %0, %1, %2, %3;\n" : "=r"(d) : "r"(a), "r"(b), "r"(s)); return d; }
__device__ __forceinline__ uint32_t mov_v(uint32_t a) { uint32_t d; asm volatile("mov.b32 %0, %1;\n" : "=r"(d) : "r"(a)); return d; }
template <int G>
__device__ __forceinline__ void conv_rename(float (&acc)[16][4]) {
#pragma unroll
    for (int i = G; i < 16; i++)
#pragma unroll
        for (int j = 0; j < 4; j++) { float v; asm volatile("mov.b32 %0, %1;\n" : "=f"(v) : "f"(acc[i][j])); acc[i][j] = v; }
}
struct Conv {
    uint32_t kw;
    uint32_t wa;
    uint32_t pa, s2;
    uint32_t s8;
    uint32_t id;
    uint32_t lc;
    uint32_t fs;
    uint32_t fl, yo;
    uint32_t yp;
    size_t ycopy;
    uint32_t ps;
    uint64_t d0;
    int warp;
};
struct Pk { uint32_t w[4]; };
__device__ __forceinline__ Pk pk2(const float (&u)[4], const float (&v)[4]) {
    Pk r;
    r.w[0] = pack_f16(u[0], u[1]); r.w[1] = pack_f16(u[2], u[3]); r.w[2] = pack_f16(v[0], v[1]); r.w[3] = pack_f16(v[2], v[3]);
    return r;
}
__device__ __forceinline__ void park(uint32_t a, const Pk& v) {
    asm volatile("stmatrix.sync.aligned.m8n8.x4.trans.shared.b16 [%0], {%1,%2,%3,%4};\n" ::"r"(a), "r"(v.w[0]), "r"(v.w[1]), "r"(v.w[2]), "r"(v.w[3]) : "memory");
}
__device__ __forceinline__ void conv_constants(uint32_t lc, int l) {
    const int d = (l >> 2) - 2 * (l & 3);
    const int e = d + 8, r4 = (e + 1 + ((e >> 2) & 1)) >> 2, p4 = (e + (((e - 1) >> 2) & 1)) >> 2;
    const uint32_t s2 = r4 == p4 ? 0x1010u : 0x3210u;
    sts64(lc + l * 8, KW_P + ((r4 - 5) >> 1) * 16 + ((r4 - 5) & 1) * 4, s2 | ((d < 0 ? s2 : 0x7654u) << 16));
    const int lo = (d >= 4) - (d < -3), ho = (d >= 5) - (d < -2), le = (d > 4) - (d < -4), he = (d > 5) - (d < -3);
    sts32(lc + 512 + l * 8, (0x5454u + lo * 0x22 + ho * 0x2200) | ((0x3232u + le * 0x22 + he * 0x2200) << 16));
    const int cc = l >> 2, j = l & 3;
    sts64(lc + 256 + l * 8, (j >> 1) * PL_HALF + (16 + cc) * 16 + (j & 1) * 8, (cc >> 1) * (DM * 64) + (cc & 1) * 32 + j * 8);
}
__device__ __forceinline__ void conv_selectors4(Conv& c) {
    const uint2 v = lds64(c.lc + lane_v() * 8);
    c.pa = v.x; c.s2 = v.y;
}
__device__ __forceinline__ void conv_selectors8(Conv& c) { c.s8 = lds32(c.lc + 512 + lane_v() * 8); }
template <int G, int I0, int I1>
__device__ __forceinline__ void conv_load(const Conv& c, uint32_t (&q)[9]) {
    const int wq = c.warp & 3;
    if (G < 2) {
#pragma unroll
        for (int i = I0; i < I1; i++) q[i] = lds32(c.wa + G * 512 + i * 16);
    } else if (G < 4) {
        const uint32_t a = (G == 2 && wq == 0) ? c.wa + 1024 : c.pa + c.kw + wq * 128 + (G < 2 ? 0 : G - 2) * 512;
#pragma unroll
        for (int i = I0; i < I1; i++) q[i] = lds32(a + i * 16);
    } else {
        const uint4 u = lds128(c.kw + KW_H + (G < 4 ? 0 : G - 4) * 64 + wq * 16);
        const uint2 v = lds64(c.kw + KW_H + (G < 4 ? 0 : G - 4) * 64 + wq * 16 + 16);
        q[0] = u.x; q[1] = u.y; q[2] = u.z; q[3] = u.w; q[4] = v.x; q[5] = v.y;
        if (G == 4 && wq == 0) { q[6] = lds32(c.pa + c.kw + 1024); q[7] = lds32(c.pa + c.kw + 1040); }
    }
}
template <int G, int J0, int J1>
__device__ __forceinline__ void conv_frag(const Conv& c, const uint32_t (&q)[9], uint32_t* a, const Pk& dp) {
    const uint32_t dep = dp.w[0];
    if (G < 4) {
        const uint32_t s = (G < 2 || (G == 2 && (c.warp & 3) == 0)) ? c.id : c.s2;
#pragma unroll
        for (int j = J0; j < J1; j++) {
            uint32_t* o = a + 4 * (j - J0);
            o[0] = prmt_v(q[2 * j + 1], dp.w[0], s); o[1] = prmt_v(q[2 * j + 2], dp.w[1], s); o[2] = prmt_v(q[2 * j], dp.w[2], s); o[3] = prmt_v(q[2 * j + 1], dp.w[3], s);
        }
    } else {
        const uint32_t so = prmt_v(c.s8, dep, c.id), se = prmt_v(c.s8, dep, c.id + 0x22);
#pragma unroll
        for (int j = J0; j < J1; j++) {
            uint32_t* o = a + 4 * (j - J0);
            o[0] = prmt_v(q[j + 1], q[j + 2], se); o[1] = prmt_v(q[j + 1], q[j + 2], so); o[2] = prmt_v(q[j], q[j + 1], so);
            if (G == 4 && j == 0 && (c.warp & 3) == 0) {
                o[2] = prmt_v(q[6], dep, c.s2);
                o[0] = prmt_v(q[7], o[0], c.s2 >> 16);
            }
            o[3] = mov_v(o[0]);
        }
    }
}
template <int G, int J0, int J1>
__device__ __forceinline__ void conv_frag(const Conv& c, const uint32_t (&q)[9], uint32_t* a, float depf) {
    const uint32_t d = __float_as_uint(depf);
    conv_frag<G, J0, J1>(c, q, a, Pk{{d, d, d, d}});
}
template <int G, int T, int J0, int J1>
__device__ __forceinline__ void conv_mma(float (&acc)[16][4], const Conv& c, const uint32_t* a) {
#pragma unroll
    for (int j = J0; j < J1; j++) wg_mma<T>(acc, a + 4 * (j - J0), c.d0 - 8 * (2 * G - T) - j);
}
__device__ __forceinline__ float h_lo(uint32_t w) { return __half2float(__ushort_as_half((unsigned short)(w & 0xffffu))); }
__device__ __forceinline__ float h_hi(uint32_t w) { return __half2float(__ushort_as_half((unsigned short)(w >> 16))); }
__device__ __forceinline__ void flush_setup(Conv& c) {
    const uint2 v = lds64(c.lc + 256 + lane_v() * 8);
    c.fl = v.x; c.yo = v.y;
}
template <int Q>
__device__ __forceinline__ void flush_load(const Conv& c, uint32_t pl, uint2 (&f)[4]) {
#pragma unroll
    for (int w = 0; w < 4; w++) f[w] = lds64(c.fl + pl + (Q & 1) * 512 + w * (PLW_B - 64));
}
template <int Q>
__device__ __forceinline__ void flush_load_first(const Conv& c, uint32_t pl, uint2 (&f)[4], float depf) {
    const uint32_t p = prmt_v(c.fl, __float_as_uint(depf), c.id) + pl + (Q & 1) * 512;
#define LDV64(d, a) asm volatile("ld.volatile.shared.v2.u32 {%0,%1}, [%2];\n" : "=r"(d.x), "=r"(d.y) : "r"(a) : "memory")
    LDV64(f[0], p); LDV64(f[1], p + (PLW_B - 64)); LDV64(f[2], p + 2 * (PLW_B - 64)); LDV64(f[3], p + 3 * (PLW_B - 64));
}
#define FDEP __uint_as_float(f[3].y)
template <int Q, int mode>
__device__ __forceinline__ void conv_flush(const Conv& c, const uint2 (&f)[4], unsigned char* gy, uint32_t rx) {
    const uint32_t a0 = hadd2(f[0].x, f[1].x), a1 = hadd2(f[2].x, f[3].x), b0 = hadd2(f[0].y, f[1].y), b1 = hadd2(f[2].y, f[3].y);
    if (Q > 0 && mode == 1) {
        const uint32_t ra = rx + 16 + (Q > 0 ? Q - 1 : 0) * 1024 + (c.warp & 3) * 256 + lane_v() * 8;
        asm volatile("st.async.shared::cluster.mbarrier::complete_tx::bytes.v2.b32 [%0], {%1,%2}, [%3];\n"
                     ::"r"(ra ^ 0x1000000u), "r"(hadd2(a0, a1)), "r"(hadd2(b0, b1)), "r"((rx + (Q > 1 ? 8 : 0)) ^ 0x1000000u) : "memory");
        return;
    }
    float v0 = h_lo(a0) + h_lo(a1), v1 = h_hi(a0) + h_hi(a1), v2 = h_lo(b0) + h_lo(b1), v3 = h_hi(b0) + h_hi(b1);
    if (Q > 0 && mode == 2) {
        const uint2 o = lds64(rx + 16 + (Q > 0 ? Q - 1 : 0) * 1024 + (c.warp & 3) * 256 + lane_v() * 8);
        v0 += h_lo(o.x); v1 += h_hi(o.x); v2 += h_lo(o.y); v3 += h_hi(o.y);
    }
    const uint32_t lo = hmul2_bf(pack_bf16(v0, v1), c.fs), hi = hmul2_bf(pack_bf16(v2, v3), c.fs);
    stg64(gy + Q * 32 * DM * 32 + (c.yo + (Q < 2 ? c.yp : 0u)), nzw(lo), nzw(hi));
}
template <int I, bool S = false> struct IC { static constexpr int value = I; static constexpr bool shared = S; };
template <class T> __device__ constexpr bool wg_is4() { return T::shared; }
#define SLOT(n) (c.ps + (2 + ((n) & 7)) * 128)
#define GO() do { wg_commit(); __syncwarp(); } while (0)
#define DEP acc[15][3]
template <class FG, class FP, class FN>
__device__ __forceinline__ void conv_head(Conv& c, float (&acc)[16][4], uint32_t (&q)[9], uint32_t (&r)[9], uint32_t* a, FG fg, FP pre, FN next) {
    c.id = 0x3210u + (c.warp >> 8);
    pre();
    conv_load<0, 0, 9>(c, q);
    conv_frag<0, 0, 1>(c, q, a, 0.f);
    wg_fence(); wg_first<0>(acc, a, c.d0); GO();
    park(c.ps, Pk{{0u, 0u, 0u, 0u}});
    wg_wait0();
    conv_frag<0, 1, 2>(c, q, a, DEP);
    wg_fence(); conv_mma<0, 0, 1, 2>(acc, c, a); GO();
    fg(IC<0>());
    wg_wait0();
    conv_frag<0, 2, 3>(c, q, a, DEP);
    wg_fence(); conv_mma<0, 0, 2, 3>(acc, c, a); GO();
    conv_load<1, 0, 5>(c, r);
    wg_wait0();
    conv_frag<0, 3, 4>(c, q, a, DEP);
    wg_fence(); conv_mma<0, 0, 3, 4>(acc, c, a); GO();
    conv_load<1, 5, 9>(c, r);
    fg(IC<1>());
    wg_wait0();
    const Pk k = pk2(acc[0], acc[1]);
    conv_rename<2>(acc);
    conv_frag<1, 0, 2>(c, r, a, k);
    wg_fence(); conv_mma<1, 2, 0, 2>(acc, c, a); GO();
    park(SLOT(0), k);
    next(IC<0>());
    fg(IC<2>());
    wg_wait0();
    conv_frag<1, 2, 4>(c, r, a, DEP);
    wg_fence(); conv_mma<1, 2, 2, 4>(acc, c, a); GO();
    next(IC<1>());
    fg(IC<3>());
    wg_wait0();
}
template <class FG, class FP>
__device__ __forceinline__ void conv_run(Conv& c, uint32_t pl, unsigned char* gy, FG fg, FP pre) {
    float acc[16][4];
    uint32_t q[9], r[9], a[32];
    uint2 f[4];
    const int bid = 1 + (c.warp >> 2);
    conv_head(c, acc, q, r, a, fg, pre, [&](auto i) { if (decltype(i)::value == 0) conv_selectors4(c); else conv_load<2, 0, 9>(c, q); });
    Pk k = pk2(acc[2], acc[3]);
    conv_rename<4>(acc);
    conv_frag<2, 0, 4>(c, q, a, k);
    wg_fence(); conv_mma<2, 4, 0, 4>(acc, c, a); GO();
    park(SLOT(2), k);
    conv_load<3, 0, 9>(c, q);
    flush_setup(c);
    bar_sync(bid, 128);
    fg(IC<4>());
    wg_wait0();
    conv_rename<6>(acc);
    conv_frag<3, 0, 4>(c, q, a, DEP);
    wg_fence(); conv_mma<3, 6, 0, 4>(acc, c, a); GO();
    park(SLOT(4), pk2(acc[4], acc[5]));
    conv_load<4, 0, 9>(c, q);
    conv_selectors8(c);
    flush_load<0>(c, pl, f);
    conv_flush<0, 0>(c, f, gy, 0u);
    fg(IC<5>());
    wg_wait0();
    conv_rename<8>(acc);
    conv_frag<4, 0, 4>(c, q, a, DEP);
    wg_fence(); conv_mma<4, 8, 0, 4>(acc, c, a); GO();
    k = pk2(acc[6], acc[7]);
    park(SLOT(6), k);
    conv_load<5, 0, 9>(c, q);
    bar_sync(bid, 128);
    park(c.ps, k);
    fg(IC<6>());
    wg_wait0();
    conv_rename<10>(acc);
    flush_load_first<1>(c, pl, f, DEP);
    conv_frag<5, 0, 4>(c, q, a, FDEP);
    wg_fence(); conv_mma<5, 10, 0, 4>(acc, c, a); GO();
    park(SLOT(8), pk2(acc[8], acc[9]));
    conv_load<6, 0, 9>(c, q); conv_load<7, 0, 9>(c, r);
    conv_flush<1, 0>(c, f, gy, 0u);
    fg(IC<7>());
    wg_wait0();
    conv_rename<12>(acc);
    conv_frag<6, 0, 4>(c, q, a, DEP); conv_frag<7, 0, 4>(c, r, a + 16, DEP);
    wg_fence(); conv_mma<6, 12, 0, 4>(acc, c, a); conv_mma<7, 12, 0, 4>(acc, c, a + 16); GO();
    park(SLOT(10), pk2(acc[10], acc[11]));
    bar_sync(bid, 128);
    flush_load<2>(c, pl, f);
    conv_flush<2, 0>(c, f, gy, 0u);
    fg(IC<8>());
    if (c.id == 0) TRAP();
    wg_wait0();
    park(SLOT(12), pk2(acc[12], acc[13])); park(SLOT(14), pk2(acc[14], acc[15]));
    bar_sync(bid, 128);
    flush_load<3>(c, pl, f);
    conv_flush<3, 0>(c, f, gy, 0u);
}
template <class FG>
__device__ __forceinline__ void conv_outer(Conv& c, uint32_t pl, unsigned char* gy, uint32_t rx, FG fg) {
    float acc[16][4];
    uint32_t q[9], r[9], a[32];
    uint2 f[4], f2[4];
    const int bid = 1 + (c.warp >> 2);
    conv_head(c, acc, q, r, a, [&](auto gi) { if (decltype(gi)::value == 2) fg(IC<2, true>()); }, [&]() {}, [&](auto i) { if (decltype(i)::value == 0) conv_selectors8(c); else conv_load<6, 0, 9>(c, q); });
    park(SLOT(2), pk2(acc[2], acc[3])); park(SLOT(4), pk2(acc[4], acc[5]));
    const Pk k = pk2(acc[6], acc[7]);
    park(SLOT(6), k);
    conv_load<7, 0, 9>(c, r);
    conv_rename<12>(acc);
    conv_frag<6, 0, 4>(c, q, a, __uint_as_float(k.w[3])); conv_frag<7, 0, 4>(c, r, a + 16, __uint_as_float(k.w[3]));
    wg_fence(); conv_mma<6, 12, 0, 4>(acc, c, a); conv_mma<7, 12, 0, 4>(acc, c, a + 16); GO();
    flush_setup(c);
    bar_sync(bid, 128);
    flush_load<0>(c, pl, f); flush_load<1>(c, pl, f2);
    conv_flush<1, 1>(c, f2, gy, rx);
    conv_flush<0, 1>(c, f, gy, rx);
    wg_wait0();
    bar_sync(bid, 128);
    park(c.ps, k); park(SLOT(8), pk2(acc[8], acc[9])); park(SLOT(10), pk2(acc[10], acc[11]));
    park(SLOT(12), pk2(acc[12], acc[13])); park(SLOT(14), pk2(acc[14], acc[15]));
    bar_sync(bid, 128);
    flush_load<2>(c, pl, f); flush_load<3>(c, pl, f2);
    conv_flush<2, 1>(c, f, gy, rx);
    conv_flush<3, 1>(c, f2, gy, rx);
}
template <class FG>
__device__ __forceinline__ void conv_inner(Conv& c, uint32_t pl, unsigned char* gy, uint32_t rx, FG fg) {
    float acc[16][4];
    uint32_t q[9], a[16];
    uint2 f[4], f2[4];
    const int bid = 1 + (c.warp >> 2);
    c.id = 0x3210u + (c.warp >> 8);
    conv_selectors4(c);
    conv_load<2, 0, 9>(c, q);
    conv_frag<2, 0, 4>(c, q, a, 0.f);
    wg_fence(); wg_first<4>(acc, a, c.d0); conv_mma<2, 4, 1, 4>(acc, c, a + 4); GO();
    conv_load<3, 0, 9>(c, q);
    park(SLOT(2), Pk{{0u, 0u, 0u, 0u}});
    fg(IC<2, true>());
    wg_wait0();
    conv_rename<6>(acc);
    conv_frag<3, 0, 4>(c, q, a, DEP);
    wg_fence(); conv_mma<3, 6, 0, 4>(acc, c, a); GO();
    park(SLOT(4), pk2(acc[4], acc[5]));
    conv_load<4, 0, 9>(c, q);
    conv_selectors8(c);
    wg_wait0();
    conv_rename<8>(acc);
    conv_frag<4, 0, 4>(c, q, a, DEP);
    wg_fence(); conv_mma<4, 8, 0, 4>(acc, c, a); GO();
    const Pk k = pk2(acc[6], acc[7]);
    park(SLOT(6), k); park(c.ps, k);
    conv_load<5, 0, 9>(c, q);
    flush_setup(c);
    wg_wait0();
    conv_rename<10>(acc);
    conv_frag<5, 0, 4>(c, q, a, DEP);
    wg_fence(); conv_mma<5, 10, 0, 4>(acc, c, a); GO();
    park(SLOT(8), pk2(acc[8], acc[9]));
    bar_sync(bid, 128);
    flush_load<1>(c, pl, f);
    mbar_wait(rx);
    conv_flush<1, 2>(c, f, gy, rx);
    wg_wait0();
    bar_sync(bid, 128);
    park(SLOT(10), pk2(acc[10], acc[11])); park(SLOT(12), pk2(acc[12], acc[13])); park(SLOT(14), pk2(acc[14], acc[15]));
    bar_sync(bid, 128);
    flush_load<3>(c, pl, f); flush_load<2>(c, pl, f2);
    mbar_wait(rx + 8);
    conv_flush<3, 2>(c, f, gy, rx);
    conv_flush<2, 2>(c, f2, gy, rx);
}
#undef SLOT
#undef GO
#undef DEP
template <int U0, int U1>
__device__ __forceinline__ void weight_units(uint32_t sb, const Maps& tm, bool w) {
    if (U1 > U0 && w && elect_one()) {
#pragma unroll
        for (int i = U0; i < U1; i++) {
            const int P = blockIdx.x >> 1, odd = blockIdx.x & 1;
            if (i < 12) tma_2d(sb + SM_WG + i * 6144, &tm.w[i / 6], 64 * P, 288 * odd + (i % 6) * 48, sb + SM_MISC + 328);
            else tma_2d(sb + SM_WD + (i - 12) * 4736, &tm.d, 144 * odd, i < 20 ? 64 * P + 8 * (i - 12) : 4096 + 8 * P, sb + SM_MISC + 336);
            if (i >= 8 && i < 12) tma_2d(sb + SM_WR + (i - 8) * 2304, &tm.r[(i - 8) >> 1], 4096 + 8 * P, 288 * odd + (i & 1) * 144, sb + SM_MISC + 328);
        }
    }
}
#define WS 2210121111113004000
__device__ constexpr int wsched(int i) {
    unsigned long long v = WS;
    int n = 0;
    for (int k = 19; k >= 1; k--) { if (k < i) n += (int)(v % 10); v /= 10; }
    return n;
}
static_assert(wsched(20) == 21 && wsched(6) <= 8 && wsched(11) <= 12 && wsched(13) <= 14 && wsched(16) <= 17 && wsched(16) == wsched(15) && wsched(19) == 21, "");
#define WANY(i) (wsched((i) + 1) > wsched(i))
#define WPOINT(i, w) do { weight_units<wsched(i), wsched(i + 1)>(sb, tm, w); } while (0)

__global__ void __launch_bounds__(NTHR, 1) __cluster_dims__(2, 1, 1)
fused_kernel(const Params p, const __grid_constant__ Maps tm) {
    extern __shared__ __align__(1024) unsigned char smem[];
    const uint32_t sb = smem_u32(smem);
    const int tid = threadIdx.x, warp = __shfl_sync(0xffffffffu, tid >> 5, 0), lane = tid & 31;
    const int b = blockIdx.x, P = b >> 1, odd = b & 1;
    const int g = lane >> 2, t = lane & 3;
    const int wg = warp >> 2, t128 = tid & 127;
    const uint32_t s_stat = sb + SM_MISC;
    const uint32_t s_key = sb + SM_MISC + 128;
    const uint32_t s_rank = sb + SM_MISC + 256;
    const uint32_t s_k16 = sb + SM_MISC + 192;
    const uint32_t s_cnt = sb + SM_MISC + 320;
    const uint32_t bar_w = sb + SM_MISC + 328, bar_d = bar_w + 8, bar_g = bar_w + 16, bar_x = bar_w + 24, bar_v = bar_w + 32, bar_s = bar_w + 40, bar_h = bar_w + 48;
    STAMP(0);

    const int ch = wg < 4 ? 4 * b + wg : 512 + P;
    const uint32_t mo = tid < 512 ? 512 * b + tid : 65536 + 128 * P + t128, mq = (mo & ~127u) + 4 * lane;
    const uint32_t pl = ldo16(p.lar + mo), pa2 = ldo16(p.aim + mo), ldt = ldo16(p.ldt + (mo >> 7));
    const uint32_t pc = ldo16(p.cre + mo), pi = ldo16(p.cim + mo);
    const uint2 call_re = ldo64(p.cre + mq), call_im = ldo64(p.cim + mq);
    const uint32_t epl = ld_poll32(p.s->hint + (b & 7) * 32 + 1);
    const uint32_t kw = sb + SM_KW + wg * KW_B;
    uint32_t co, cn, cd, uo;
    auto housekeeping = [&]() {
        if (t128 < 2 * UPAD) sts128(sb + SM_U + wg * USLOT_B + (t128 & 1) * ULO_B + (t128 >> 1) * 16, 0u, 0u, 0u, 0u);
        if (t128 >= 124) sts128(kw + (t128 & 1) * 16 + (t128 & 2) * (KW_PL / 2), 0u, 0u, 0u, 0u);
        if (warp < 15) sts128(sb + SM_Z2 + 4608 + tid * 16, 0u, 0u, 0u, 0u);
        combine_setup(sb, warp, lane, kw, co, cn, cd);
        co = pin(co); cn = pin(cn); cd = pin(cd);
        uo = pin(wg < 4 ? tid : 512 + (P >> 2) * 1024 + (t128 >> 1) * 8 + (P & 3) * 2 + (t128 & 1));
    };
    if (wg < 4) {
        bar_arrive(0, NWRK);
        asm volatile("barrier.cluster.arrive.relaxed.aligned;\n" ::: "memory");
        housekeeping();
    } else {
        const int o = (warp & 3) * 4608 + lane * 16;
        sts128(sb + SM_Z2 + t128 * 16, 0u, 0u, 0u, 0u); sts128(sb + SM_Z2 + 2048 + t128 * 16, 0u, 0u, 0u, 0u);
        if (warp == 16) sts128(sb + SM_Z2 + 4096 + lane * 16, 0u, 0u, 0u, 0u);
        fence_async();
        bar_sync(0, NWRK);
        STAMP(9);
#pragma unroll
        for (int c = 0; c < 9; c++)
            asm volatile("cp.async.cg.shared.global [%0], [%1], 16;\n" ::"r"(sb + SM_XT + o + c * 512), "l"(reinterpret_cast<const char*>(p.x) + b * 18432 + o + c * 512) : "memory");
        asm volatile("cp.async.commit_group;\n" ::: "memory");
        if (elect_one()) {
            mbar_init(bar_h + 8 * (warp & 3), 1);
            if (warp == 19) {
                mbar_init(bar_x, 1); mbar_init(bar_w, 1);
                mbar_expect(bar_x, 32768); mbar_expect(bar_w, 82944);
#pragma unroll
                for (int i = 2; i < 4; i++) bulk_s2g(reinterpret_cast<unsigned char*>(p.s->y) + 32 * i * 18432 + b * 4608, sb + SM_Z2, 4608);
            } else if (warp == 18) {
                mbar_init(bar_s, 1); mbar_init(bar_v, 2); mbar_init(bar_d, 1); mbar_init(bar_g, 1); mbar_init(sb + SM_RX, 1); mbar_init(sb + SM_RX + 8, 1);
                mbar_expect(bar_v, 2 * 1152); mbar_expect(bar_d, 72 * WD_PITCH); mbar_expect(bar_g, 4608); mbar_expect(sb + SM_RX, 1024); mbar_expect(sb + SM_RX + 8, 2048);
            }
            asm volatile("fence.mbarrier_init.release.cluster;\n" ::: "memory");
        }
        __syncwarp();
        asm volatile("barrier.cluster.arrive.relaxed.aligned;\n" ::: "memory");
        if (warp == 19) {
            asm volatile("barrier.cluster.wait.aligned;\n" ::: "memory");
            if (elect_one()) tma_4d_mc(sb + SM_XC + odd * 16384, &tm.x, 8 * P, 2 * odd, bar_x);
            __syncwarp();
        }
    }
    const uint32_t tb = table_buf(sb, warp), t5 = sb + SM_WD + warp * 512;
    STAMP(29);
    const float dt = exp_bf(bf_lo(ldt));
    const uint32_t ep = __reduce_or_sync(0xffffffffu, epl);
    auto stats = [&]() {
        const int wq = warp & 3;
        const uint32_t xa = sb + SM_XT + (4 * wq + (g >> 1)) * 1152 + (g & 1) * 576 + t * 16;
        const bool own = !(g & 1) && t == (g >> 1);
        float d[4][4] = {};
        uint32_t* const sdst = p.s->stat + (16 * b + 4 * wq + t);
        FIX(xa & (uint32_t)reinterpret_cast<uint64_t>(sdst) & (uint32_t)(reinterpret_cast<uint64_t>(sdst) >> 32));
        asm volatile("cp.async.wait_group 0;\n" ::: "memory");
        __syncwarp();
        STAMP(26);
        uint4 v[9];
#pragma unroll
        for (int c = 0; c < 9; c++) { v[c] = lds128(xa + c * 64); }
#pragma unroll
        for (int c = 0; c < 9; c++) {
            mma_bf16(d[2 * (c & 1)], v[c].x, 0x3f803f80u, v[c].y, 0x3f803f80u, v[c].x, v[c].y);
            mma_bf16(d[2 * (c & 1) + 1], v[c].z, 0x3f803f80u, v[c].w, 0x3f803f80u, v[c].z, v[c].w);
        }
        STAMP(27);
        float sm = (g & 1) ? (d[0][3] + d[1][3]) + (d[2][3] + d[3][3]) : (d[0][2] + d[1][2]) + (d[2][2] + d[3][2]);
        float sq = (g & 1) ? (d[0][1] + d[1][1]) + (d[2][1] + d[3][1]) : (d[0][0] + d[1][0]) + (d[2][0] + d[3][0]);
        sm += __shfl_xor_sync(0xffffffffu, sm, 4); sq += __shfl_xor_sync(0xffffffffu, sq, 4);
        if (lane == 0) mbar_arrive(bar_h + 8 * wq);
        float mb, sd;
        ln_stats(sm, sq, mb, sd);
        if (own) *sdst = __byte_perm(__float_as_uint(mb), __float_as_uint(sd), 0x7632) | (ep << 31);
        STAMPX(22);
        if (own) stat_store(s_stat + (2 * wq + (t & 1) + 8 * (t >> 1)) * 8, mb, rcp_approx(sd), 0u);
        if (wq == 3) asm volatile("cp.async.bulk.wait_group 0;\n" ::: "memory");
        bar_sync(5, 128);
        STAMP(28);
        uint32_t now;
        asm volatile("mov.u32 %0, %%clock;" : "=r"(now) :: "memory");
        if (wq == 2) {
            if (lane == 0) {
                sts64(s_cnt, now, ep);
                mbar_arrive(bar_s);
                bulk_g2s(sb + SM_XT + 16 * 1152, p.dsk, 1152, bar_v);
                bulk_g2s(sb + SM_XT + 17 * 1152, p.wr, 1152, bar_v);
            }
            __syncwarp();
        }
        WPOINT(1, wq == 3);
        if (wq < 2) {
            unsigned char* const ud = reinterpret_cast<unsigned char*>(p.s->uT) + (size_t)(8 * wq + 2 * (g >> 1)) * 16384 + b * 128 + (g & 1) * 32 + t * 8;
            const uint32_t utag = (ep % 7u + 1u) * 0x10001u;
            uint32_t U[2][4];
#pragma unroll
            for (int hf = 0; hf < 2; hf++) {
                const uint2 st = lds64(s_stat + (g + 8 * hf) * 8);
                const uint4 xu = lds128(sb + SM_XT + (TOK(g) + 2 * hf) * 1152 + warp * 64 + t * 16);
                const uint32_t X[4] = {xu.x, xu.y, xu.z, xu.w};
#pragma unroll
                for (int k = 0; k < 4; k++) {
                    const uint32_t u = ln_apply(X[k], STAT_M(st), STAT_H(st), STAT_L(st));
                    U[hf][k] = movm((pack_f16(bf_lo(u), bf_hi(u)) & 0xfff8fff8u) | utag);
                }
            }
#pragma unroll
            for (int k = 0; k < 4; k++) stg64(ud + (k >> 1) * 16384 + (k & 1) * 64, U[0][k], U[1][k]);
        }
    };
    STAMP(1);
    if (wg < 4) { STAMPX(16); }
    KGen kg;
    kgen_setup(kg, bf_lo(pl), bf_lo(pa2), dt);
    kgen_rows(kg, tb, lane);
    STAMP(2);
    const int E = min(max(c_exponent(call_re, call_im, dt) - 243, -120), 120);
    kgen_chain(kg, pc, pi, dt * __uint_as_float((uint32_t)(128 - E) << 23));
    STAMP(3);
    kgen_cols(kg, tb, t5, lane);
    STAMP(4);
    if (warp != 19) asm volatile("barrier.cluster.wait.aligned;\n" ::: "memory");
    if (wg == 4) {
        if (warp == 18) conv_constants(sb + SM_LC, lane);
        stats();
    }
    if (wg < 4) { STAMPX(17); }
    if (wg == 4) housekeeping();
    const uint4* const usrc = reinterpret_cast<const uint4*>(p.s->stat) + uo;
    uint32_t trel;
    kgen_mma(kg, tb, t5, lane, [&]() {
        if (wg < 4) mbar_wait(bar_h + 8 * (warp & 3));
        asm volatile("mov.u32 %0, %%clock;" : "=r"(trel) :: "memory");
    });
    if (wg < 4) { STAMPX(20); }
    STAMP(5);
    uint4 uv0, uv1;
    auto first_poll = [&](uint32_t dly) {
        mbar_wait(bar_s);
        const uint32_t t0 = lds32(s_cnt);
        uint32_t now;
        do { asm volatile("mov.u32 %0, %%clock;" : "=r"(now) :: "memory"); } while (now - t0 < dly);
        uv0 = ld_poll(usrc);
    };
    if (wg == 4) { first_poll(UDLY); uv1 = ld_poll(usrc + 512); }
    WPOINT(2, warp == 19);
    auto stat_poll = [&]() {
        uint32_t now;
        do { asm volatile("mov.u32 %0, %%clock;" : "=r"(now) :: "memory"); } while (now - trel < SDLY);
        uv0 = ld_poll(usrc);
    };
    bar_sync(1 + wg, 128);
    if (wg < 4) { STAMPX(21); }
    kgen_combine(warp & 3, lane, co, cn, cd);
    STAMP(6);
    if (wg < 4) { STAMPX(18); }
    WPOINT(3, warp == 19);
    if (wg < 4) stat_poll();
    {
        const int wq = warp & 3;
        Conv c;
        const uint32_t pln = sb + SM_PL + wg * PL_B;
        const int e = g - 2 * t + 7;
        c.kw = kw; c.wa = pin(kw + ((e >> 2) & 1) * KW_PL + (8 * wq + (e >> 3)) * 16 + (e & 3) * 4);
        c.ps = mov_v(pln + wq * PLW_B + ((lane >> 3) & 1) * PL_HALF + ((lane >> 4) * 8 + (lane & 7)) * 16); c.warp = warp;
        c.lc = sb + SM_LC; c.fs = (uint32_t)(127 + E) * 0x800080u; c.yp = (ep & 1u) * (NCTA * 18432u);
        c.d0 = ((uint64_t)(ULO_B >> 4) << 16) | ((uint64_t)(128 >> 4) << 32) | (uint64_t)(((sb + SM_U + wg * USLOT_B + UPAD * 16) & 0x3FFFF) >> 4);
        unsigned char* gy = reinterpret_cast<unsigned char*>(p.s->y) + ((size_t)(4 * wq) * DM + ch) * 64;
        auto hook = [&](auto gi) {
                     constexpr int G = decltype(gi)::value;
                     if (G == (wg_is4<decltype(gi)>() ? 2 : 5)) asm volatile("barrier.cluster.wait.aligned;\n" ::: "memory");
                     if (!wg_is4<decltype(gi)>() && G == 1) mbar_wait(bar_s);
                     if (!wg_is4<decltype(gi)>() && (G == 0 || G == 2) && warp == HW && elect_one()) {
                         unsigned char* const sc = reinterpret_cast<unsigned char*>(p.s);
                         if (G == 0) {
                             if (b < 96) bulk_s2g_nc(sc + offsetof(Scratch, part) + b * 6144, sb + SM_Z2, 6144);
                             bulk_s2g(sc + offsetof(Scratch, rows) + (127 - b) * 4608, sb + SM_Z2, 4608);
                         }
                         if (G == 2) {
                             bulk_s2g(sc + offsetof(Scratch, y) + (NCTA * 18432u - c.yp) + b * 9216, sb + SM_Z2, 9216);
                         }
                     }
                     if (!wg_is4<decltype(gi)>()) WPOINT(6 + G, warp == (G >= 7 ? HW : 4 * (G % 3) + 1));
                     if (!wg_is4<decltype(gi)>() && G == 6 && warp == HW) {
                         asm volatile("cp.async.bulk.wait_group 0;\n" ::: "memory");
                         __syncwarp();
                         if (elect_one()) mbar_arrive(bar_v);
                     }
                 };
        if (wg < 4) {
            asm volatile("barrier.cluster.arrive.relaxed.aligned;\n" ::: "memory");
            conv_run(c, pln + wq * 128, gy, hook, [&]() {
                STAMPX(23);
                mbar_wait(bar_x);
                STAMPX(24);
                uint2 xc[4];
                uint32_t xw[4][2];
#pragma unroll
                for (int j = 0; j < 4; j++) xc[j] = lds64(sb + SM_XC + wg * 8192 + j * 2048 + t128 * 16 + odd * 8);
#pragma unroll
                for (int i = 0; i < 8; i++) {
                    const int k = i >> 1, h = i & 1;
                    xw[k][h] = prmt_v(k < 2 ? xc[2 * h].x : xc[2 * h].y, k < 2 ? xc[2 * h + 1].x : xc[2 * h + 1].y, (k & 1) ? 0x7632 : 0x5410);
                }
                const uint32_t ub = mov_v(sb + SM_U + UPAD * 16 + ((tid >> 1) & 1) * ULO_B + (tid >> 2) * 16 + (tid & 1) * 8), tag = ep << 31;
                int it = 0;
                while (min(min((int)(uv0.x ^ tag), (int)(uv0.y ^ tag)), min((int)(uv0.z ^ tag), (int)(uv0.w ^ tag))) < 0x10000) {
                    if (++it > SPIN_LIMIT) TRAP();
                    uv0 = ld_poll(usrc);
                }
                STAMP(8);
                STAMPX(26);
                const float r0 = rcp_approx(fabsf(bf_hi(uv0.x))), r1 = rcp_approx(fabsf(bf_hi(uv0.y))), r2 = rcp_approx(fabsf(bf_hi(uv0.z))), r3 = rcp_approx(fabsf(bf_hi(uv0.w)));
                const uint32_t m[2] = {__byte_perm(uv0.x, uv0.y, 0x5410), __byte_perm(uv0.z, uv0.w, 0x5410)};
                const uint32_t rh[2] = {pack_bf16(r0, r1), pack_bf16(r2, r3)};
                const uint32_t rl[2] = {pack_bf16(r0 - bf_lo(rh[0]), r1 - bf_hi(rh[0])), pack_bf16(r2 - bf_lo(rh[1]), r3 - bf_hi(rh[1]))};
#pragma unroll
                for (int k = 0; k < 4; k++) {
                    const uint32_t u0 = ln_apply(xw[k][0], m[0], rh[0], rl[0]), u1 = ln_apply(xw[k][1], m[1], rh[1], rl[1]);
                    sts64(ub + k * USLOT_B, pack_f16(bf_lo(u0), bf_hi(u0)), pack_f16(bf_lo(u1), bf_hi(u1)));
                }
                STAMPX(29);
                fence_async();
                bar_sync(14, 512);
                STAMP(7);
            });
        } else {
            auto stage = [&]() {
                const uint32_t tag = (ep % 7u + 1u) * 0x10001u;
                int it = 0;
                WPOINT(4, warp == 19);
                while (true) {
                    uv0.x ^= tag; uv0.y ^= tag; uv0.z ^= tag; uv0.w ^= tag; uv1.x ^= tag; uv1.y ^= tag; uv1.z ^= tag; uv1.w ^= tag;
                    if ((((uv0.x | uv0.y | uv0.z) | (uv0.w | uv1.x | uv1.y) | (uv1.z | uv1.w)) & 0x70007u) == 0) break;
                    if (++it > SPIN_LIMIT) TRAP();
                    uv0 = ld_poll(usrc); uv1 = ld_poll(usrc + 512);
                }
                STAMP(8);
                const uint32_t ub = sb + SM_U + UPAD * 16 + 4 * USLOT_B + (t128 & 1) * ULO_B + (t128 >> 1) * 16;
                sts128(ub, uv0.x, uv0.y, uv0.z, uv0.w);
                sts128(ub + 1024, uv1.x, uv1.y, uv1.z, uv1.w);
                fence_async();
                asm volatile("barrier.cluster.arrive.relaxed.aligned;\n" ::: "memory");
                bar_sync(5, 128);
                WPOINT(5, warp == 19);
                STAMP(7);
            };
            stage();
            if (odd) conv_inner(c, pln + wq * 128, gy, sb + SM_RX, hook);
            else conv_outer(c, pln + wq * 128, gy, sb + SM_RX, hook);
        }
        STAMP(10);
    }
    {
    const int lane = lane_v(), tid = 32 * warp + lane, g = lane >> 2, t = lane & 3;
    const uint32_t par = ~ep & 1u;
    bar_sync(0, NWRK);
    STAMP(11);
    uint32_t H[2][4] = {}, U2[2][4] = {};
    auto publish = [&](bool hi, int slot) {
        uint4* rowp = reinterpret_cast<uint4*>(p.s->rows) + slot * 144 + warp * 4 + t;
        stg128(rowp, nzw(hi ? U2[1][0] : U2[0][0]), nzw(hi ? U2[1][1] : U2[0][1]), nzw(hi ? U2[1][2] : U2[0][2]), nzw(hi ? U2[1][3] : U2[0][3]));
        stg128(rowp + 72, nzw(hi ? H[1][0] : H[0][0]), nzw(hi ? H[1][1] : H[0][1]), nzw(hi ? H[1][2] : H[0][2]), nzw(hi ? H[1][3] : H[0][3]));
    };
#define KTOK(k) (int)(((~(k) >> 5) & 0x7f0u) | (((k) >> 1) & 15u))
#define KLATE(k) (((k) & 0x1e0u) < 0xe0u)
#define KSLOT(k, s) (KLATE(k) ? 2 * NCTA + (s) : (int)(((k) >> 8) & 0xffu))
    const uint4* const rsrc = reinterpret_cast<const uint4*>(p.s->rows) + 36 * odd;
    auto gather = [&](uint32_t mine) {
        int it = 0;
        uint32_t mn;
        do {
            mn = 1;
#pragma unroll 1
            for (int r = 0; r < 9; r++) {
                const uint32_t k = __shfl_sync(0xffffffffu, mine, r < 8 ? 4 * r : lane);
                const int row = r < 8 ? r : g, c = r < 8 ? lane : 32 + t;
                asm volatile("cp.async.cg.shared.global [%0], [%1], 16;\n" ::"r"(sb + SM_XS + row * XS_PITCH + c * 16), "l"(rsrc + KSLOT(k, row) * 144 + c) : "memory");
            }
            asm volatile("cp.async.wait_all;\n" ::: "memory");
#pragma unroll 1
            for (int r = 0; r < 9; r++) mn = min(mn, min4(lds128(sb + SM_XS + (r < 8 ? r * XS_PITCH + lane * 16 : g * XS_PITCH + (32 + t) * 16))));
            if (++it > SPIN_LIMIT) TRAP();
        } while (__any_sync(0xffffffffu, mn == 0));
    };
    auto late_rows = [&](auto role) {
        if (decltype(role)::value == 1) {
            int it = 0;
            uint4 k[8];
            uint32_t bad;
            do {
                bad = 0;
#pragma unroll
                for (int i = 0; i < 8; i++) k[i] = ld_poll(reinterpret_cast<const uint4*>(p.s->key) + 32 * i + lane);
#pragma unroll
                for (int i = 0; i < 8; i++) bad = or3(bad, xor_or(k[i].x, k[i].y, par), xor_or(k[i].z, k[i].w, par));
                if (++it > SPIN_LIMIT) TRAP();
            } while (__any_sync(0xffffffffu, bad & 1u));
#pragma unroll 1
            for (int r = 0; r < 8; r++) {
                uint32_t c = 0;
#pragma unroll
                for (int i = 0; i < 8; i++) c = max(c, k[i].x);
                const uint32_t m = __reduce_max_sync(0xffffffffu, c);
#pragma unroll
                for (int i = 0; i < 8; i++) if (k[i].x == m) k[i] = make_uint4(k[i].y, k[i].z, k[i].w, 0u);
                if (lane == 0) sts32(s_key + r * 4, m);
            }
        }
        bar_sync(0, NWRK);
        const uint32_t kk = lds32(s_key + (lane & 7) * 4), ep = lds32(s_cnt + 4);
        const bool own = KLATE(kk) && (KTOK(kk) >> 4) == b;
        uint32_t todo = __ballot_sync(0xffffffffu, own) & 0xffu;
        if (decltype(role)::value == 0 && todo) {
#pragma unroll
            for (int hf = 0; hf < 2; hf++) {
                const uint4 h = lds128(sb + SM_U + hf * 9216 + tid * 16);
                const uint2 st = lds64(s_stat + (g + 8 * hf) * 8);
                H[hf][0] = h.x; H[hf][1] = h.y; H[hf][2] = h.z; H[hf][3] = h.w;
#pragma unroll
                for (int k = 0; k < 4; k++) U2[hf][k] = ln_apply(H[hf][k], STAT_M(st), STAT_H(st), STAT_L(st));
            }
#pragma unroll 1
            while (todo) {
                const int s = __ffs(todo) - 1, tk = KTOK(__shfl_sync(0xffffffffu, kk, s));
                todo &= todo - 1;
                if ((tk & 13) == TOK(g)) publish(tk & 2, 2 * NCTA + s);
            }
            __threadfence();
        }
        bar_sync(0, NWRK);
        if (decltype(role)::value == 1) {
            if (lane < NSEL && own) *reinterpret_cast<volatile unsigned*>(p.s->flag + lane) = ep + 1u;
            int it = 0;
            while (__any_sync(0xffffffffu, KLATE(kk) && ld_acquire32(p.s->flag + (lane & 7)) != ep + 1u)) { if (++it > SPIN_LIMIT) TRAP(); }
            gather(__shfl_sync(0xffffffffu, kk, g));
        }
        bar_sync(0, NWRK);
    };
    if (warp < 18) {
        const unsigned char* ys = reinterpret_cast<const unsigned char*>(p.s->y) + (b < 64 ? (par ^ 1u) * (NCTA * 18432u) : 0u) +
                                  ((P * DM + 32 * warp + 8 * (g >> 1) + (g & 1)) * 64 + odd * 32 + t * 8);
        mbar_wait(bar_v);
        const uint32_t xa = sb + SM_XT + warp * 64 + t * 16;
        const uint4 x0 = lds128(xa + TOK(g) * 1152), x1 = lds128(xa + (TOK(g) + 2) * 1152), dk = lds128(xa + 16 * 1152);
        uint4 wr = make_uint4(0u, 0u, 0u, 0u);
        if (g == 0) wr = lds128(xa + 17 * 1152);
        uint2 yv[4];
        const uint32_t Z[2][4] = {{x0.x, x0.y, x0.z, x0.w}, {x1.x, x1.y, x1.z, x1.w}}, D4[4] = {dk.x, dk.y, dk.z, dk.w};
#pragma unroll
        for (int hf = 0; hf < 2; hf++) {
            const uint2 st = lds64(s_stat + (g + 8 * hf) * 8);
#pragma unroll
            for (int k = 0; k < 4; k++) U2[hf][k] = hmul2_bf(ln_apply(Z[hf][k], STAT_M(st), STAT_H(st), STAT_L(st)), D4[k]);
        }
        const uint32_t la = pin(sb + SM_LNP + (g * 20 + warp) * 4);
        {
            const unsigned char* y1 = ys + (U2[0][0] & U2[1][2] & (warp >> 8));
#pragma unroll
            for (int k = 0; k < 4; k++) yv[k] = ld_poll64(y1 + k * 128);
        }
        int it = 0;
        float d[2][4];
        while (true) {
            const uint32_t mn = min3(min3(yv[0].x, yv[0].y, yv[1].x), min3(yv[1].y, yv[2].x, yv[2].y), min(yv[3].x, yv[3].y));
#pragma unroll
            for (int k = 0; k < 4; k++) {
                H[0][k] = hadd2_bf(Z[0][k], hadd2_bf(movm(yv[k].x), U2[0][k]));
                H[1][k] = hadd2_bf(Z[1][k], hadd2_bf(movm(yv[k].y), U2[1][k]));
            }
            ln_partial(H, d);
            if (!__any_sync(0xffffffffu, mn == 0)) break;
            if (++it > SPIN_LIMIT) TRAP();
#pragma unroll
            for (int k = 0; k < 4; k++) yv[k] = ld_poll64(ys + k * 128);
        }
        STAMP(12);
        {
            const float s0 = (g & 1) ? d[0][3] : d[0][2], s1 = (g & 1) ? d[1][3] : d[1][2];
            const float q0 = (g & 1) ? d[0][1] : d[0][0], q1 = (g & 1) ? d[1][1] : d[1][0];
            asm volatile("{\n.reg .pred p;\nsetp.eq.u32 p, %5, %6;\n@p st.shared.f32 [%0], %1;\n@p st.shared.f32 [%0 + 640], %2;\n@p st.shared.f32 [%0 + 1280], %3;\n@p st.shared.f32 [%0 + 1920], %4;\n}\n"
                         ::"r"(la), "f"(s0), "f"(s1), "f"(q0), "f"(q1), "r"(t), "r"(g >> 1) : "memory");
        }
        bar_arrive(6, NWRK);
        STAMP(13);
        bar_sync(7, 608);
        STAMP(14);
#pragma unroll
        for (int hf = 0; hf < 2; hf++) {
            const uint2 st = lds64(s_stat + (g + 8 * hf) * 8);
#pragma unroll
            for (int k = 0; k < 4; k++) U2[hf][k] = ln_apply(H[hf][k], STAT_M(st), STAT_H(st), STAT_L(st));
        }
        {
            float cs[4] = {0.f, 0.f, 0.f, 0.f};
            mma_bf16(cs, U2[0][0], U2[1][0], U2[0][1], U2[1][1], wr.x, wr.y);
            mma_bf16(cs, U2[0][2], U2[1][2], U2[0][3], U2[1][3], wr.z, wr.w);
            if (t == 0) { stsf(la + 32 * 80, cs[0]); stsf(la + 40 * 80, cs[2]); }
            bar_arrive(8, 608);
        }
        FIX((uint32_t)warp >> 8);
        uint32_t O[2][4];
#pragma unroll
        for (int hf = 0; hf < 2; hf++)
#pragma unroll
            for (int k = 0; k < 4; k++) { O[hf][k] = hadd2_bf(H[hf][k], U2[hf][k]); H[hf][k] = nzw(H[hf][k]); U2[hf][k] = nzw(U2[hf][k]); }
        unsigned char* rowp = reinterpret_cast<unsigned char*>(p.s->rows) + ((254 - 2 * b) * 2304 + warp * 64 + t * 16);
        FIX(and3(and3(and3(H[0][0], H[0][1], H[0][2]), and3(H[0][3], H[1][0], H[1][1]), and3(H[1][2], H[1][3], U2[0][0])),
                 and3(and3(U2[0][1], U2[0][2], U2[0][3]), and3(U2[1][0], U2[1][1], U2[1][2]), U2[1][3]), (uint32_t)reinterpret_cast<uint64_t>(rowp)));
        bar_sync(9, 608);
        {
            const uint2 best = lds64(s_rank);
#pragma unroll
            for (int hf = 0; hf < 2; hf++) {
                const uint32_t me = 2 * TOK(g) + 4 * hf;
                unsigned char* d = rowp + (best.x == me ? 2304 : 0);
                if (best.x == me || best.y == me) {
                    stg128(d, U2[hf][0], U2[hf][1], U2[hf][2], U2[hf][3]);
                    stg128(d + 1152, H[hf][0], H[hf][1], H[hf][2], H[hf][3]);
                }
            }
        }
        FIX((uint32_t)warp >> 9);
#pragma unroll
        for (int hf = 0; hf < 2; hf++) {
            sts128(sb + SM_OUT + (TOK(g) + 2 * hf) * (DM * 2) + warp * 64 + t * 16, O[hf][0], O[hf][1], O[hf][2], O[hf][3]);
            sts128(sb + SM_U + hf * 9216 + tid * 16, H[hf][0], H[hf][1], H[hf][2], H[hf][3]);
        }
        STAMP(15);
        const int mi = lane >> 3, rr = lane & 7;
        const bool gate = warp < 12 && (warp & 3) != 2;
        const int fj = gate ? 3 * (warp >> 2) + min(warp & 3, 2) : (warp < 12 ? warp >> 2 : warp - 9);
        if (gate) {
            uint32_t W[18][4];
            mbar_wait(bar_w);
            const uint32_t aad = fj < 8 ? sb + SM_WG + (mi & 1) * SM_WU + (rr + 8 * (mi >> 1)) * 128 + (fj ^ rr) * 16 : sb + SM_WR + (mi & 1) * 4608 + (rr + 8 * (mi >> 1)) * 16;
            const uint32_t ast = fj < 8 ? 2048 : 256;
            const uint32_t bad = pin(sb + SM_XS + rr * XS_PITCH + mi * 16);
            bool rare = warp >> 8;
#pragma unroll 1
            do {
                if (rare) late_rows(IC<0>());
#pragma unroll
                for (int k = 0; k < 18; k++) ldsm_x4_t(W[k][0], W[k][1], W[k][2], W[k][3], aad + k * ast);
                if (rare) break;
                fence_async();
                STAMP2(17);
                rare = bar_or(11, NWRK, false);
            } while (rare);
            STAMP2(19);
            float c4[2][4] = {};
#pragma unroll
            for (int k = 0; k < 18; k += 2) {
                uint32_t b0, b1, b2, b3;
                ldsm_x4(b0, b1, b2, b3, bad + k * 32);
                mma_bf16(c4[0], W[k][0], W[k][1], W[k][2], W[k][3], b0, b1);
                mma_bf16(c4[1], W[k + 1][0], W[k + 1][1], W[k + 1][2], W[k + 1][3], b2, b3);
            }
            const uint32_t ex = sb + SM_EX + (32 * fj + lane) * 16;
            const float e0 = c4[0][0] + c4[1][0], e1 = c4[0][1] + c4[1][1], e2 = c4[0][2] + c4[1][2], e3 = c4[0][3] + c4[1][3];
            asm volatile("st.async.shared::cluster.mbarrier::complete_tx::bytes.v4.f32 [%0], {%1,%2,%3,%4}, [%5];\n"
                         ::"r"(ex ^ 0x1000000u), "f"(e0), "f"(e1), "f"(e2), "f"(e3), "r"(bar_g ^ 0x1000000u) : "memory");
            STAMP2(20);
            mbar_wait(bar_g);
            const uint4 o = lds128(ex);
            const uint32_t G = pack_bf16(e0 + __uint_as_float(o.x), e1 + __uint_as_float(o.y)), U = pack_bf16(e2 + __uint_as_float(o.z), e3 + __uint_as_float(o.w));
            sts32(sb + SM_GU + (32 * fj + lane) * 4, hmul2_bf(pack_bf16(bf_lo(G) * sigmoid_f(bf_lo(G)), bf_hi(G) * sigmoid_f(bf_hi(G))), U));
            bar_arrive(13, NWRK);
        } else {
            uint32_t W[2][18];
            auto load_wd = [&]() {
                mbar_wait(bar_d);
                const uint32_t base = sb + SM_WD + (4 * fj + (mi & 1)) * 16 + rr * WD_PITCH;
#pragma unroll
                for (int j = 0; j < 2; j++) {
#pragma unroll
                    for (int k = 0; k < 4; k++) ldsm_x4_t(W[j][4 * k], W[j][4 * k + 1], W[j][4 * k + 2], W[j][4 * k + 3], base + j * 32 + (k * 16 + 8 * (mi >> 1)) * WD_PITCH);
                    ldsm_x2_t(W[j][16], W[j][17], base + j * 32 + 64 * WD_PITCH);
                }
            };
            const uint32_t po = pin((((8 * (18 * odd + 2 * fj) + g) * 64 + P) * 4 + t) * 8);
            fence_async();
            STAMP2(17);
            const bool first = (warp & 3) != 2;
#pragma unroll 1
            for (int i = 0; i < 2; i++) {
                if (i == (first ? 1 : 0)) {
                    if (bar_or(11, NWRK, false)) late_rows(IC<0>());
                    if (!first) delay(DDLY);
                } else load_wd();
            }
            bar_sync(13, NWRK);
            STAMP2(21);
            uint32_t gb[9];
            ldsm_x4_t(gb[0], gb[1], gb[2], gb[3], sb + SM_GU + lane * 16);
            ldsm_x4_t(gb[4], gb[5], gb[6], gb[7], sb + SM_GU + 512 + lane * 16);
            ldsm_x1_t(gb[8], sb + SM_GU + 1024 + lane * 16);
            float c4[2][4] = {}, d4[2][4] = {};
#pragma unroll
            for (int k = 0; k < 4; k += 2)
#pragma unroll
                for (int j = 0; j < 2; j++) {
                    mma_bf16(c4[j], W[j][4 * k], W[j][4 * k + 1], W[j][4 * k + 2], W[j][4 * k + 3], gb[2 * k], gb[2 * k + 1]);
                    mma_bf16(d4[j], W[j][4 * k + 4], W[j][4 * k + 5], W[j][4 * k + 6], W[j][4 * k + 7], gb[2 * k + 2], gb[2 * k + 3]);
                }
#pragma unroll
            for (int j = 0; j < 2; j++) mma_bf16_k8(c4[j], W[j][16], W[j][17], gb[8]);
#pragma unroll
            for (int j = 0; j < 2; j++)
                stg64(reinterpret_cast<unsigned char*>(p.s->part) + po + j * 16384, nzw(pack_bf16(c4[j][0] + d4[j][0], c4[j][1] + d4[j][1])), nzw(pack_bf16(c4[j][2] + d4[j][2], c4[j][3] + d4[j][3])));
        }
        STAMP2(22);
    } else if (warp == 18) {
        const uint4* const ksrc = reinterpret_cast<const uint4*>(p.s->key3) + pin(2 * lane);
        const int row = (g >> 1) + 4 * (g & 1);
        const uint32_t ro = pin(640 * odd + t * 16), xd = pin(sb + SM_XS + row * XS_PITCH + t * 16 + (odd ? 0 : 512));
        const uint32_t xe = pin(sb + SM_XS + (g >> 1) * XS_PITCH + (lane & 7) * 16 + 64 * odd);
        const uint32_t sa = pin(sb + SM_LNP + lane * 80);
        const uint32_t klo = pin((uint32_t)(127 - b) << 9 | (uint32_t)(15 - ROWTOK(lane & 15)) << 1 | par), ra = pin(sb + SM_LNP + (32 + (lane & 15)) * 80);
        uint4* const kdst = reinterpret_cast<uint4*>(p.s->key3) + pin((lane >> 1) * 2 * NCTA + 2 * b + (lane & 1));
        FIX(ra);
        bar_sync(6, NWRK);
        {
            float mb, rc;
            ln_finish(sum18(sa), lane, mb, rc);
            if (lane < 16) stat_store(s_stat + lane * 8, mb, rc, 0u);
        }
        bar_arrive(7, 608);
        bar_sync(8, 608);
        uint32_t t0;
        {
            const uint32_t bits = __float_as_uint(rbf(sum18(ra)));
            const uint32_t me = ((bits ^ ((uint32_t)((int)bits >> 31) | 0x80000000u)) & 0xffff0000u) | klo;
            const uint32_t k0 = __reduce_max_sync(0xffffffffu, me), k1 = __reduce_max_sync(0xffffffffu, me == k0 ? 0u : me);
            const uint32_t k2 = __reduce_max_sync(0xffffffffu, me >= k1 ? 0u : me);
            if (lane < 2) stg128(kdst, k0 ^ 0x11eu, k1 ^ 0xfeu, k2 ^ 0xdeu, par);
            asm volatile("mov.u32 %0, %%clock;" : "=r"(t0) :: "memory");
            STAMPW(23);
            if (lane == 0) sts64(s_rank, ~k0 & 30u, ~k1 & 30u);
            bar_arrive(9, 608);
            sts32(s_k16 + (lane & 15) * 4, me);
            __syncwarp();
            const uint4 v = lds128(s_k16 + (lane & 16) * 2), w = lds128(s_k16 + (lane & 16) * 2 + 16);
            int rank = ((v.x > me) + (v.y > me)) + ((v.z > me) + (v.w > me)) + (((w.x > me) + (w.y > me)) + ((w.z > me) + (w.w > me)));
            rank += __shfl_xor_sync(0xffffffffu, rank, 16);
            if (lane < 16 && rank < 8) p.s->key[8 * b + rank] = (me ^ 0x1eu) | ((8 - rank) << 5);
        }
        uint4 kq[4];
        uint32_t u[4], mine = 0, m;
        int it = 0;
        { uint32_t now; do { asm volatile("mov.u32 %0, %%clock;" : "=r"(now) :: "memory"); } while (now - t0 < KDLY); }
        do {
#pragma unroll
            for (int i = 0; i < 4; i++) kq[i] = ld_poll(ksrc + 64 * i);
            if (++it > SPIN_LIMIT) TRAP();
            uint32_t S[2][4];
#pragma unroll
            for (int i = 0; i < 2; i++) {
                const uint4 &c = kq[2 * i], &d = kq[2 * i + 1];
                const uint32_t m1 = min(c.x, d.x), m2 = max(c.y, d.y);
                S[i][0] = max(c.x, d.x); S[i][1] = max(m1, m2); S[i][2] = min(m1, m2); S[i][3] = min(c.y, d.y);
            }
            const uint32_t a0 = max(S[0][0], S[1][3]), a1 = max(S[0][1], S[1][2]), a2 = max(S[0][2], S[1][1]), a3 = max(S[0][3], S[1][0]);
            const uint32_t b0 = max(a0, a2), b2 = min(a0, a2), b1 = max(a1, a3), b3 = min(a1, a3);
            u[0] = max(b0, b1); u[1] = min(b0, b1); u[2] = max(b2, b3); u[3] = min(b2, b3);
            const uint32_t bad = or3(or3(xor_or(kq[0].x, kq[0].y, par), xor_or(kq[0].z, kq[1].x, par), xor_or(kq[1].y, kq[1].z, par)),
                                     xor_or(kq[2].x, kq[2].y, par), xor_or(kq[2].z, kq[3].x, par)) | xor_or(kq[3].y, kq[3].z, par);
            m = __reduce_max_sync(0xffffffffu, u[0] | (uint32_t)((int)(bad << 31) >> 31));
        } while (m == 0xffffffffu);
        STAMPW(16);
#pragma unroll
        for (int r = 0; r < 8; r++) {
            if (r) m = __reduce_max_sync(0xffffffffu, u[0]);
            if (u[0] == m) { u[0] = u[1]; u[1] = u[2]; u[2] = u[3]; u[3] = 0; }
            if (row == r) mine = m;
        }
        uint4 v[9];
        const uint32_t o0 = __byte_perm(mine, 0, 0x4441) * 2304u, o1 = __shfl_xor_sync(0xffffffffu, o0, 4);
        const unsigned char* const rA = reinterpret_cast<const unsigned char*>(p.s->rows) + (((g & 1) ? o1 : o0) + ro + (g & 1) * 64);
        const unsigned char* const rb = reinterpret_cast<const unsigned char*>(p.s->rows) + (((g & 1) ? o0 : o1) + ro + (g & 1) * 64);
        const unsigned char* const rc = reinterpret_cast<const unsigned char*>(p.s->rows) + (o0 + ro + (odd ? -64 : 512));
#pragma unroll
        for (int i = 0; i < 4; i++) { v[i] = ld_poll(rA + i * 128); v[4 + i] = ld_poll(rb + i * 128); }
        v[8] = ld_poll(rc);
        const bool again = u[0] == 0 || max(max(kq[0].z, kq[1].z), max(kq[2].z, kq[3].z)) > m;
        if (t == 0) sts32(s_key + row * 4, mine);
#pragma unroll
        for (int i = 0; i < 9; i++) sts128(i < 8 ? xe + (i >> 2) * 4 * XS_PITCH + (i & 3) * 128 : xd, v[i].x, v[i].y, v[i].z, v[i].w);
        uint32_t mn, m3[3];
        m3[0] = m3[1] = m3[2] = 1u;
#pragma unroll
        for (int i = 0; i < 9; i++) m3[i % 3] = min3(min3(m3[i % 3], v[i].x, v[i].y), v[i].z, v[i].w);
        mn = min3(m3[0], m3[1], m3[2]);
        STAMPW(18);
        if (bar_or(11, NWRK, again || mn == 0)) late_rows(IC<1>());
    } else {
        bar_sync(6, NWRK);
        WPOINT(16, true);
        if (WANY(17) || WANY(18)) delay(WDLY);
        WPOINT(17, true);
        if (WANY(18)) delay(WDLY);
        WPOINT(18, true);
        if (bar_or(11, NWRK, false)) late_rows(IC<2>());
        const int tk = KTOK(lds32(s_key + (lane & 7) * 4));
        const uint32_t sel = __reduce_or_sync(0xffffffffu, (tk >> 4) == b ? 1u << (tk & 15) : 0u);
        if (sel ? lane < 16 && !((sel >> lane) & 1u) : lane == 0) bulk_s2g(p.out + (size_t)(16 * b + lane) * DM, sb + SM_OUT + lane * (DM * 2), sel ? DM * 2 : 16 * DM * 2);
        __syncwarp();
    }
    if (warp == 8 || warp >= 18) {
        const int grp = 3 * b + (warp == 8 ? 0 : warp - 17), fsl = 2 * (g & 3) + (t & 1), fc = 16 * (grp >> 3) + (grp & 7) + 8 * (t >> 1);
        const uint32_t fk = lds32(s_key + fsl * 4);
        float hv = 0.f, u2 = 0.f;
        int it = 0;
        if (b < 96) {
            const uint32_t* const fsrc = p.s->rows + KSLOT(fk, fsl) * DM + (fc >> 1);
            uint32_t hw, uw;
            do { hw = ld_poll32(fsrc + 288); uw = ld_poll32(fsrc); if (++it > SPIN_LIMIT) TRAP(); } while (!hw || !uw);
            hv = (fc & 1) ? bf_hi(hw) : bf_lo(hw); u2 = (fc & 1) ? bf_hi(uw) : bf_lo(uw);
        }
        const float rs = rbf(sigmoid_f(__uint_as_float((fk ^ ((uint32_t)((int)~fk >> 31) | 0x80000000u)) & 0xffff0000u)));
        bf16* dst = p.out + (KTOK(fk) * DM + fc);
        const uint2* src = reinterpret_cast<const uint2*>(p.s->part) + (grp * 256 + 8 * t + g);
        FIX((uint32_t)reinterpret_cast<uint64_t>(dst) & (uint32_t)reinterpret_cast<uint64_t>(src) & (uint32_t)((reinterpret_cast<uint64_t>(dst) & reinterpret_cast<uint64_t>(src)) >> 32) & __float_as_uint(rs));
        if (warp > 17) bar_sync(13, NWRK);
        if (b < 96) {
            delay(warp > 17 ? FDLY : FDLY2);
            const uint32_t sel = (g & 1) ? 0x3f800000u : 0x3f80u;
            float y;
            uint32_t ok;
            do {
                uint2 a[8];
#pragma unroll
                for (int i = 0; i < 8; i++) a[i] = ld_poll64(src + 32 * i);
                if (++it > SPIN_LIMIT) TRAP();
                float c[2][4] = {};
#pragma unroll
                for (int i = 0; i < 8; i += 2) mma_bf16(c[(i >> 1) & 1], a[i].x, a[i].y, a[i + 1].x, a[i + 1].y, sel, sel);
                ok = min3(min3(min3(a[0].x, a[0].y, a[1].x), min3(a[1].y, a[2].x, a[2].y), min3(a[3].x, a[3].y, a[4].x)), min3(min3(a[4].y, a[5].x, a[5].y), min3(a[6].x, a[6].y, a[7].x), a[7].y), 1u);
                ok = __all_sync(0xffffffffu, ok);
                y = fsel(fsel(c[0][3] + c[1][3], c[0][2] + c[1][2], t & 1), fsel(c[0][1] + c[1][1], c[0][0] + c[1][0], t & 1), t & 2);
            } while (!ok);
            STAMP2(24);
            y += __shfl_xor_sync(0xffffffffu, y, 16);
            *dst = __float2bfloat16_rn(hv + rbf(u2 + rbf(rbf(y) * rs)));
        }
    }
    if (warp == 19) asm volatile("cp.async.bulk.wait_group.read 0;\n" ::: "memory");
    if (b == 0 && tid < 8) *reinterpret_cast<volatile unsigned*>(p.s->hint + tid * 32 + 1) = lds32(s_cnt + 4) + 1u;
    STAMP(25);
    }
}

typedef CUresult (*PFN_tmEncode)(CUtensorMap*, CUtensorMapDataType, cuuint32_t, void*, const cuuint64_t*, const cuuint64_t*, const cuuint32_t*,
                                 const cuuint32_t*, CUtensorMapInterleave, CUtensorMapSwizzle, CUtensorMapL2promotion, CUtensorMapFloatOOBfill);

extern "C" void kernel_launch(void* const* d_in, const int* in_sizes, int n_in, void* d_out, int out_size) {
    Params p;
    p.x = (const bf16*)d_in[0];
    p.lar = (const bf16*)d_in[1];
    p.aim = (const bf16*)d_in[2];
    p.cre = (const bf16*)d_in[3];
    p.cim = (const bf16*)d_in[4];
    p.ldt = (const bf16*)d_in[5];
    p.dsk = (const bf16*)d_in[6];
    p.wr = (const bf16*)d_in[8];
    p.out = (bf16*)d_out;
    static PFN_tmEncode enc = nullptr;
    static void* scratch = nullptr;
    if (!enc) {
        cudaFuncSetAttribute(fused_kernel, cudaFuncAttributeMaxDynamicSharedMemorySize, SMEM_TOTAL);
        void* fn = nullptr;
        cudaDriverEntryPointQueryResult qr;
        cudaGetDriverEntryPoint("cuTensorMapEncodeTiled", &fn, cudaEnableDefault, &qr);
        enc = (PFN_tmEncode)fn;
        cudaGetSymbolAddress(&scratch, g_scratch);
    }
    p.s = (Scratch*)scratch;
    Maps tm;
    const cuuint64_t dims[2] = {FF, DM}, strides[1] = {FF * 2};
    const cuuint32_t box[2] = {64, 48}, rbox[2] = {8, 144}, es[2] = {1, 1};
    for (int i = 0; i < 2; i++) {
        enc(&tm.w[i], CU_TENSOR_MAP_DATA_TYPE_BFLOAT16, 2, d_in[9 + i], dims, strides, box, es, CU_TENSOR_MAP_INTERLEAVE_NONE, CU_TENSOR_MAP_SWIZZLE_128B,
            CU_TENSOR_MAP_L2_PROMOTION_NONE, CU_TENSOR_MAP_FLOAT_OOB_FILL_NONE);
        enc(&tm.r[i], CU_TENSOR_MAP_DATA_TYPE_BFLOAT16, 2, d_in[9 + i], dims, strides, rbox, es, CU_TENSOR_MAP_INTERLEAVE_NONE, CU_TENSOR_MAP_SWIZZLE_NONE,
            CU_TENSOR_MAP_L2_PROMOTION_NONE, CU_TENSOR_MAP_FLOAT_OOB_FILL_NONE);
    }
    const cuuint64_t ddims[2] = {DM / 2, FF}, dstrides[1] = {DM * 2};
    const cuuint32_t dbox[2] = {WD_PITCH / 4, 8};
    enc(&tm.d, CU_TENSOR_MAP_DATA_TYPE_UINT32, 2, d_in[11], ddims, dstrides, dbox, es, CU_TENSOR_MAP_INTERLEAVE_NONE, CU_TENSOR_MAP_SWIZZLE_NONE,
        CU_TENSOR_MAP_L2_PROMOTION_L2_128B, CU_TENSOR_MAP_FLOAT_OOB_FILL_NONE);
    const cuuint64_t xdims[4] = {DM, 128, 4, 4}, xstrides[3] = {DM * 8, DM * 2, DM * 1024};
    const cuuint32_t xbox[4] = {8, 128, 4, 2}, xes[4] = {1, 1, 1, 1};
    enc(&tm.x, CU_TENSOR_MAP_DATA_TYPE_BFLOAT16, 4, d_in[0], xdims, xstrides, xbox, xes, CU_TENSOR_MAP_INTERLEAVE_NONE, CU_TENSOR_MAP_SWIZZLE_NONE,
        CU_TENSOR_MAP_L2_PROMOTION_NONE, CU_TENSOR_MAP_FLOAT_OOB_FILL_NONE);
    fused_kernel<<<NCTA, NTHR, SMEM_TOTAL>>>(p, tm);
}
```
